```python
import torch

def _softmax(x, axis=-1):
    return torch.softmax(x, dim=axis)

def _gelu(x):
    return torch.nn.functional.gelu(x, approximate='tanh')

def _silu(x):
    return torch.nn.functional.silu(x)

def _sigmoid(x):
    return torch.sigmoid(x)

def _layernorm(x, axis=-1, eps=1e-05):
    m = x.mean(dim=axis, keepdim=True)
    v = x.var(dim=axis, keepdim=True, unbiased=False)
    return (x - m) / torch.sqrt(v + eps)

def _scatter_add(tgt, idx, src, axis=0):
    return tgt.clone().index_add_(axis, idx, src)

def _segment_sum(src, seg, n):
    out = torch.zeros((n,) + src.shape[1:], dtype=src.dtype)
    return out.index_add_(0, seg, src)

def _pad(x, pw):
    flat = tuple((v for pair in reversed(pw) for v in pair))
    return torch.nn.functional.pad(x, flat)
kernel_name = 'adaLN_cond__gqa_block_cached__moe_arch_mod__prompt'

def setup_inputs():

    _w = lambda a: (lambda t: t.to(torch.bfloat16) if t.is_floating_point() else t)(torch.as_tensor(a))

    def _A_setup():
        B, Sq, D = (1, 2048, 576)
        Hq, Hkv, Sk, Dh = (32, 16, 2048, 128)
        assert Hq % Hkv == 0, (Hq, Hkv)
        return {'x': _w((lambda *s: torch.randn(*s, dtype=torch.bfloat16) * 0.1)(B, Sq, D)), 'k_cache': _w((lambda *s: torch.randn(*s, dtype=torch.bfloat16) * 0.8)(B, Hkv, Sk, Dh)), 'v_cache': _w((lambda *s: torch.randn(*s, dtype=torch.bfloat16) * 0.8)(B, Hkv, Sk, Dh)), 'wq': _w((lambda *s: torch.randn(*s, dtype=torch.bfloat16) * 0.8)(D, Hq * Dh) * D ** (-0.5)), 'wo': _w((lambda *s: torch.randn(*s, dtype=torch.bfloat16) * 0.8)(Hq * Dh, D) * (Hq * Dh) ** (-0.5))}
    _A_in = _A_setup()

    def _B_setup():
        B, S, D, F, C = (1, 2048, 576, 4608, 2)
        return {'x': _w((lambda *s: torch.randn(*s, dtype=torch.bfloat16) * 0.1)(B, S, D)), 'w_r': _w((lambda *s: torch.randn(*s, dtype=torch.bfloat16) * 3.2)(D)), 'w_gate': _w((lambda *s: torch.randn(*s, dtype=torch.bfloat16) * 0.2)(D, F)), 'w_up': _w((lambda *s: torch.randn(*s, dtype=torch.bfloat16) * 0.2)(D, F)), 'w_down': _w((lambda *s: torch.randn(*s, dtype=torch.bfloat16) * 0.2)(F, D))}
    _B_in = _B_setup()
    return {'A_x': _A_in['x'], 'A_k_cache': _A_in['k_cache'], 'A_v_cache': _A_in['v_cache'], 'A_wq': _A_in['wq'], 'A_wo': _A_in['wo'], 'B_x': _B_in['x'], 'B_w_r': _B_in['w_r'], 'B_w_gate': _B_in['w_gate'], 'B_w_up': _B_in['w_up'], 'B_w_down': _B_in['w_down'], 'c': _w((lambda *s: torch.randn(*s, dtype=torch.bfloat16) * 0.4)(1, 576) * 8.0), 'w_mod': _w((lambda *s: torch.randn(*s, dtype=torch.bfloat16) * 0.4)(576, 6 * 576) * 576 ** (-0.5) * 8.0)}

def reference(A_x, A_k_cache, A_v_cache, A_wq, A_wo, B_x, B_w_r, B_w_gate, B_w_up, B_w_down, c, w_mod):

    def _A_ref(x, k_cache, v_cache, wq, wo):
        B, Sq, D = x.shape
        Hq, Dh = (32, 128)
        Hkv = k_cache.shape[1]
        rep = Hq // Hkv
        q = (lambda x, *d: x.permute(*d))((x @ wq).reshape(B, Sq, Hq, Dh), 0, 2, 1, 3)
        k = (lambda x, n, axis: torch.repeat_interleave(x, n, dim=axis))(k_cache, rep, axis=1)
        v = (lambda x, n, axis: torch.repeat_interleave(x, n, dim=axis))(v_cache, rep, axis=1)
        scores = torch.einsum('bhqd,bhkd->bhqk', q, k) * Dh ** (-0.5)
        p = _softmax(scores, axis=-1)
        o = torch.einsum('bhqk,bhkd->bhqd', p, v)
        return (lambda x, *d: x.permute(*d))(o, 0, 2, 1, 3).reshape(B, Sq, Hq * Dh) @ wo

    def _B_ref(x, w_r, w_gate, w_up, w_down):
        B, S, D = x.shape
        C = 2
        r = x @ w_r
        idx = torch.argsort(-r, axis=-1)[:, :C]
        idx_e = (lambda x, n, axis: torch.repeat_interleave(x, n, dim=axis))(idx.reshape(B, C, 1), D, axis=2)
        x_sel = (lambda x, i, axis: torch.take_along_dim(x, i, dim=axis))(x, idx_e, axis=1)
        g = _silu(x_sel @ w_gate)
        u = x_sel @ w_up
        y = g * u @ w_down
        r_sel = _sigmoid((lambda x, i, axis: torch.take_along_dim(x, i, dim=axis))(r, idx, axis=1))
        y = y * r_sel.reshape(B, C, 1)
        b_off = (torch.arange(B) * S).reshape(B, 1)
        flat_idx = (idx + b_off).reshape(B * C)
        zero = (x * 0.0).reshape(B * S, D)
        upd = _scatter_add(zero, flat_idx, y.reshape(B * C, D), axis=0)
        return x + upd.reshape(B, S, D)
    x = A_x
    mod = (_silu(c) @ w_mod).reshape(c.shape[0], 6, 1, -1)
    sa, ca, ga, sb, cb, gb = (mod[:, 0].clone(), mod[:, 1].clone(), mod[:, 2].clone(), mod[:, 3].clone(), mod[:, 4].clone(), mod[:, 5].clone())
    h = _layernorm(x, axis=-1) * (1 + ca) + sa
    x = x + ga * _A_ref(h, A_k_cache, A_v_cache, A_wq, A_wo)
    h = _layernorm(x, axis=-1) * (1 + cb) + sb
    x = x + gb * _B_ref(h, B_w_r, B_w_gate, B_w_up, B_w_down)
    return x
```

```cpp
#include <cuda_runtime.h>
#include <cuda_bf16.h>
#include <cuda.h>
#include <stdint.h>
#include <math.h>

typedef __nv_bfloat16 bf16;

constexpr int S_ = 2048;
constexpr int D_ = 576;
constexpr int HQ = 32, HKV = 16, DH = 128;
constexpr int F_ = 4608;
constexpr int QD = HQ * DH;

constexpr int NCTA = 128;
constexpr int WREG = 5 * 4096;
__device__ __align__(1024) uint4 g_h[NCTA * 36 * 32];
__device__ __align__(1024) uint4 g_q3[NCTA * 8 * 128];
__device__ __align__(1024) uint8_t g_keep[NCTA * 8 * 4096];
__device__ unsigned int g_epoch = 1;
__device__ __align__(16) uint2 g_mod[3 * D_];
__device__ __align__(128) unsigned int g_flag_h[NCTA * 32];
__device__ __align__(128) unsigned int g_flag_part[16 * 32];
__device__ __align__(128) unsigned int g_flag_mod[NCTA];
__device__ __align__(128) unsigned int g_flag_q3[16 * 32];
constexpr int CREP = 8;
struct Scratch {
    uint8_t frag[NCTA * 8 * WREG];
    uint4 cand[CREP * NCTA * 2];
    uint2 ypart[72 * NCTA * 8];
    uint4 rows[S_ * (D_ / 2)];
};
__device__ __align__(1024) Scratch g_s;
#define g_frag g_s.frag
#define g_cand g_s.cand
#define g_ypart g_s.ypart
#define g_rows g_s.rows

#define DBG_INIT()
#define DBG_P(i)
#define DBG_PG(i)
#define DBG_T(i)
#define DBG_G(i)

__device__ __forceinline__ uint32_t pack_bf16(float lo, float hi) {
    uint32_t r;
    asm("cvt.rn.bf16x2.f32 %0, %1, %2;" : "=r"(r) : "f"(hi), "f"(lo));
    return r;
}
__device__ __forceinline__ float rbf(float x) { return __uint_as_float(pack_bf16(0.f, x)); }
__device__ __forceinline__ float bf_lo(uint32_t v) { return __uint_as_float(v << 16); }
__device__ __forceinline__ float bf_hi(uint32_t v) { return __uint_as_float(v & 0xffff0000u); }
__device__ __forceinline__ float ex2(float x) {
    float y;
    asm("ex2.approx.ftz.f32 %0, %1;" : "=f"(y) : "f"(x));
    return y;
}
__device__ __forceinline__ uint32_t smem_u32(const void* p) { return (uint32_t)__cvta_generic_to_shared(p); }
__device__ __forceinline__ void mbar_init(uint32_t bar, uint32_t cnt) {
    asm volatile("mbarrier.init.shared::cta.b64 [%0], %1;" ::"r"(bar), "r"(cnt) : "memory");
}
__device__ __forceinline__ void mbar_expect_tx(uint32_t bar, uint32_t bytes) {
    asm volatile("mbarrier.arrive.expect_tx.shared::cta.b64 _, [%0], %1;" ::"r"(bar), "r"(bytes) : "memory");
}
__device__ __forceinline__ void mbar_arrive(uint32_t bar) {
    asm volatile("mbarrier.arrive.shared::cta.b64 _, [%0];" ::"r"(bar) : "memory");
}
__device__ __forceinline__ void mbar_arrive_cluster(uint32_t cluster_addr) {
    asm volatile("mbarrier.arrive.shared::cluster.b64 _, [%0];" ::"r"(cluster_addr) : "memory");
}
constexpr uint32_t SPIN = 1u << 20;
__device__ __forceinline__ void mbar_wait(uint32_t bar, uint32_t parity) {
    asm volatile("{\n.reg .pred p;\n.reg .b32 c;\nmov.b32 c, 0;\n"
                 "W_%=:\nmbarrier.try_wait.parity.shared::cta.b64 p, [%0], %1;\n@p bra D_%=;\n"
                 "add.u32 c, c, 1;\nsetp.lt.u32 p, c, 0x100000;\n@p bra W_%=;\nD_%=:\n}"
                 ::"r"(bar), "r"(parity) : "memory");
}
__device__ __forceinline__ void anchor(uint32_t addr, float v) {
    asm volatile("{\n.reg .pred p;\nsetp.lt.f32 p, %1, 0f00000000;\n@p st.volatile.shared.f32 [%0], %1;\n}" ::"r"(addr), "f"(v) : "memory");
}
__device__ __forceinline__ void mbar_wait_sleep(uint32_t bar, uint32_t parity) {
    asm volatile("{\n.reg .pred p;\n.reg .b32 c;\nmov.b32 c, 0;\n"
                 "W_%=:\nmbarrier.try_wait.parity.shared::cta.b64 p, [%0], %1, 5000;\n@p bra D_%=;\n"
                 "add.u32 c, c, 1;\nsetp.lt.u32 p, c, 0x20000;\n@p bra W_%=;\nD_%=:\n}"
                 ::"r"(bar), "r"(parity) : "memory");
}
__device__ __forceinline__ uint32_t load_tag() {
    uint32_t tag;
    asm volatile("ld.global.ca.u32 %0, [%1];" : "=r"(tag) : "l"(&g_epoch) : "memory");
    return tag;
}
__device__ __forceinline__ uint4 ld_relaxed(const uint4* p) {
    uint4 v;
    asm volatile("ld.relaxed.gpu.global.v4.u32 {%0,%1,%2,%3}, [%4];" : "=r"(v.x), "=r"(v.y), "=r"(v.z), "=r"(v.w) : "l"(p) : "memory");
    return v;
}
__device__ __forceinline__ void st_relaxed(uint4* p, uint32_t a, uint32_t b, uint32_t c, uint32_t d) {
    asm volatile("{\n.reg .b64 u, v;\nmov.b64 u, {%1, %2};\nmov.b64 v, {%3, %4};\nst.relaxed.gpu.global.v2.b64 [%0], {u, v};\n}"
                 ::"l"(p), "r"(a), "r"(b), "r"(c), "r"(d) : "memory");
}
__device__ __forceinline__ void st_relaxed4(void* p, uint32_t a, uint32_t b, uint32_t c, uint32_t d) {
    asm volatile("st.relaxed.gpu.global.v4.u32 [%0], {%1, %2, %3, %4};" ::"l"(p), "r"(a), "r"(b), "r"(c), "r"(d) : "memory");
}
__device__ __forceinline__ uint2 ld_relaxed8(const void* p) {
    uint2 v;
    asm volatile("ld.relaxed.gpu.global.v2.u32 {%0,%1}, [%2];" : "=r"(v.x), "=r"(v.y) : "l"(p) : "memory");
    return v;
}
__device__ __forceinline__ uint2 ld_relaxed64(const uint2* p) {
    uint2 v;
    asm volatile("{\n.reg .b64 u;\nld.relaxed.gpu.global.b64 u, [%2];\nmov.b64 {%0, %1}, u;\n}" : "=r"(v.x), "=r"(v.y) : "l"(p) : "memory");
    return v;
}
__device__ __forceinline__ void st_relaxed64(uint2* p, uint32_t a, uint32_t b) {
    asm volatile("{\n.reg .b64 u;\nmov.b64 u, {%1, %2};\nst.relaxed.gpu.global.b64 [%0], u;\n}" ::"l"(p), "r"(a), "r"(b) : "memory");
}
__device__ __forceinline__ uint4 ld_relaxed2(const uint4* p) {
    uint4 v;
    asm volatile("{\n.reg .b64 u, w;\nld.relaxed.gpu.global.v2.b64 {u, w}, [%4];\nmov.b64 {%0, %1}, u;\nmov.b64 {%2, %3}, w;\n}"
                 : "=r"(v.x), "=r"(v.y), "=r"(v.z), "=r"(v.w) : "l"(p) : "memory");
    return v;
}
__device__ __forceinline__ void poll2x2(const uint4* p0, const uint4* p1, uint32_t tag, uint4& o0, uint4& o1) {
    uint4 v0, v1;
    uint32_t miss, it = 0;
#pragma unroll 1
    do {
        v0 = ld_relaxed2(p0); v1 = ld_relaxed2(p1);
        miss = (v0.y ^ tag) | (v0.w ^ tag) | (v1.y ^ tag) | (v1.w ^ tag);
    } while (miss && ++it < SPIN / 16);
    o0 = v0; o1 = v1;
}
__device__ __forceinline__ void flag_wait(const unsigned int* p, uint32_t tag) {
    uint32_t v, it = 0;
#pragma unroll 1
    do {
        asm volatile("ld.relaxed.gpu.global.u32 %0, [%1];" : "=r"(v) : "l"(p) : "memory");
    } while (__any_sync(0xffffffffu, v != tag) && ++it < SPIN / 16);
    asm volatile("fence.acquire.gpu;" ::: "memory");
    __syncwarp();
}
__device__ __forceinline__ bool elect() {
    uint32_t p;
    asm volatile("{\n.reg .pred p;\nelect.sync _|p, 0xffffffff;\nselp.u32 %0, 1, 0, p;\n}" : "=r"(p));
    return p;
}
__device__ __forceinline__ void flag_release(unsigned int* p, uint32_t tag) {
    asm volatile("st.release.gpu.global.u32 [%0], %1;" ::"l"(p), "r"(tag) : "memory");
}
__device__ __forceinline__ uint32_t touch(const void* p) {
    uint32_t v;
    asm volatile("ld.global.nc.L1::no_allocate.L2::128B.u32 %0, [%1];" : "=r"(v) : "l"(p));
    return v;
}
__device__ __forceinline__ void bar_sync(int id, int n) { asm volatile("bar.sync %0, %1;" ::"r"(id), "r"(n) : "memory"); }
__device__ __forceinline__ void bar_arrive(int id, int n) { asm volatile("bar.arrive %0, %1;" ::"r"(id), "r"(n) : "memory"); }

constexpr uint64_t EVICT_NORMAL = 0x1000000000000000ull, EVICT_FIRST = 0x12F0000000000000ull;
__device__ __forceinline__ void tma2d(uint32_t dst, const CUtensorMap* m, int c0, int c1, uint32_t bar) {
    asm volatile("cp.async.bulk.tensor.2d.shared::cluster.global.mbarrier::complete_tx::bytes.L2::cache_hint [%0], [%1, {%3, %4}], [%2], %5;"
                 ::"r"(dst), "l"(m), "r"(bar), "r"(c0), "r"(c1), "l"(EVICT_FIRST) : "memory");
}
__device__ __forceinline__ void tma2d_mc(uint32_t dst, const CUtensorMap* m, int c0, int c1, uint32_t bar, uint64_t pol) {
    asm volatile("cp.async.bulk.tensor.2d.shared::cluster.global.mbarrier::complete_tx::bytes.multicast::cluster.L2::cache_hint [%0], [%1, {%3, %4}], [%2], %5, %6;"
                 ::"r"(dst), "l"(m), "r"(bar), "r"(c0), "r"(c1), "h"((uint16_t)3), "l"(pol) : "memory");
}
__device__ __forceinline__ void tma3d(uint32_t dst, const CUtensorMap* m, int c0, int c1, int c2, uint32_t bar) {
    asm volatile("cp.async.bulk.tensor.3d.shared::cluster.global.mbarrier::complete_tx::bytes.L2::cache_hint [%0], [%1, {%3, %4, %5}], [%2], %6;"
                 ::"r"(dst), "l"(m), "r"(bar), "r"(c0), "r"(c1), "r"(c2), "l"(EVICT_FIRST) : "memory");
}
__device__ __forceinline__ void bulk_load(uint32_t dst, const void* src, uint32_t bytes, uint32_t bar) {
    asm volatile("cp.async.bulk.shared::cluster.global.mbarrier::complete_tx::bytes [%0], [%1], %2, [%3];"
                 ::"r"(dst), "l"(src), "r"(bytes), "r"(bar) : "memory");
}
__device__ __forceinline__ void l2_prefetch(const void* src, uint32_t bytes) {
    asm volatile("cp.async.bulk.prefetch.L2.global [%0], %1;" ::"l"(src), "r"(bytes) : "memory");
}
__device__ __forceinline__ uint32_t bmul2(uint32_t a, uint32_t b) { uint32_t r; asm("mul.rn.bf16x2 %0, %1, %2;" : "=r"(r) : "r"(a), "r"(b)); return r; }
__device__ __forceinline__ uint32_t badd2(uint32_t a, uint32_t b) { uint32_t r; asm("add.rn.bf16x2 %0, %1, %2;" : "=r"(r) : "r"(a), "r"(b)); return r; }
__device__ __forceinline__ uint32_t bsub2(uint32_t a, uint32_t b) { uint32_t r; asm("sub.rn.bf16x2 %0, %1, %2;" : "=r"(r) : "r"(a), "r"(b)); return r; }
__device__ __forceinline__ uint32_t bmax2(uint32_t a, uint32_t b) { uint32_t r; asm("max.bf16x2 %0, %1, %2;" : "=r"(r) : "r"(a), "r"(b)); return r; }
__device__ __forceinline__ uint32_t bfma2(uint32_t a, uint32_t b, uint32_t c) { uint32_t r; asm("fma.rn.bf16x2 %0, %1, %2, %3;" : "=r"(r) : "r"(a), "r"(b), "r"(c)); return r; }
__device__ __forceinline__ uint4 lds128(uint32_t a) { uint4 v; asm volatile("ld.shared.v4.u32 {%0,%1,%2,%3}, [%4];" : "=r"(v.x), "=r"(v.y), "=r"(v.z), "=r"(v.w) : "r"(a) : "memory"); return v; }
__device__ __forceinline__ uint4 ldsm4(uint32_t a) {
    uint4 v;
    asm volatile("ldmatrix.sync.aligned.m8n8.x4.shared.b16 {%0,%1,%2,%3}, [%4];" : "=r"(v.x), "=r"(v.y), "=r"(v.z), "=r"(v.w) : "r"(a) : "memory");
    return v;
}
__device__ __forceinline__ uint4 ldsm4t(uint32_t a) {
    uint4 v;
    asm volatile("ldmatrix.sync.aligned.m8n8.x4.trans.shared.b16 {%0,%1,%2,%3}, [%4];" : "=r"(v.x), "=r"(v.y), "=r"(v.z), "=r"(v.w) : "r"(a) : "memory");
    return v;
}
__device__ __forceinline__ void mma1688(float* d, uint32_t a0, uint32_t a1, uint32_t b) {
    asm("mma.sync.aligned.m16n8k8.row.col.f32.bf16.bf16.f32 {%0,%1,%2,%3}, {%4,%5}, {%6}, {%0,%1,%2,%3};"
        : "+f"(d[0]), "+f"(d[1]), "+f"(d[2]), "+f"(d[3]) : "r"(a0), "r"(a1), "r"(b));
}
__device__ __forceinline__ void mma16816(float* d, uint32_t a0, uint32_t a1, uint32_t a2, uint32_t a3, uint32_t b0, uint32_t b1) {
    asm("mma.sync.aligned.m16n8k16.row.col.f32.bf16.bf16.f32 {%0,%1,%2,%3}, {%4,%5,%6,%7}, {%8,%9}, {%0,%1,%2,%3};"
                 : "+f"(d[0]), "+f"(d[1]), "+f"(d[2]), "+f"(d[3]) : "r"(a0), "r"(a1), "r"(a2), "r"(a3), "r"(b0), "r"(b1));
}
__device__ __forceinline__ void stsm_x4(uint32_t addr, uint32_t a, uint32_t b, uint32_t c, uint32_t d) {
    asm volatile("stmatrix.sync.aligned.m8n8.x4.shared.b16 [%0], {%1, %2, %3, %4};"
                 ::"r"(addr), "r"(a), "r"(b), "r"(c), "r"(d) : "memory");
}

__device__ __forceinline__ uint64_t mkdesc(uint32_t addr, uint32_t lbo, uint32_t sbo) {
    return (uint64_t)((addr & 0x3FFFF) >> 4) | ((uint64_t)(lbo >> 4) << 16) | ((uint64_t)(sbo >> 4) << 32) | (1ull << 62);
}
constexpr uint32_t SM0 = 1024;
__host__ __device__ constexpr uint32_t desc_lo(uint32_t off, uint32_t lbo) { return ((SM0 + off) >> 4) | ((lbo >> 4) << 16); }
__device__ __forceinline__ uint64_t desc_of(uint32_t lo) { return lo | (0x40000040ull << 32); }
#define WG_FENCE() asm volatile("wgmma.fence.sync.aligned;" ::: "memory")
#define WG_COMMIT() asm volatile("wgmma.commit_group.sync.aligned;" ::: "memory")
#define WG_WAIT(n) asm volatile("wgmma.wait_group.sync.aligned %0;" ::"n"(n) : "memory")

#define F8(a, i) "+f"(a[i]), "+f"(a[i + 1]), "+f"(a[i + 2]), "+f"(a[i + 3]), "+f"(a[i + 4]), "+f"(a[i + 5]), "+f"(a[i + 6]), "+f"(a[i + 7])
#define F16(a, i) F8(a, i), F8(a, i + 8)
#define F64(a) F16(a, 0), F16(a, 16), F16(a, 32), F16(a, 48)
#define F32(a) F16(a, 0), F16(a, 16)
#define L64 "%0,%1,%2,%3,%4,%5,%6,%7,%8,%9,%10,%11,%12,%13,%14,%15,%16,%17,%18,%19,%20,%21,%22,%23,%24,%25,%26,%27,%28,%29,%30,%31,%32,%33,%34,%35,%36,%37,%38,%39,%40,%41,%42,%43,%44,%45,%46,%47,%48,%49,%50,%51,%52,%53,%54,%55,%56,%57,%58,%59,%60,%61,%62,%63"
#define L32 "%0,%1,%2,%3,%4,%5,%6,%7,%8,%9,%10,%11,%12,%13,%14,%15,%16,%17,%18,%19,%20,%21,%22,%23,%24,%25,%26,%27,%28,%29,%30,%31"

template <int TB>
__device__ __forceinline__ void mma_rs128(float (&d)[64], uint32_t a0, uint32_t a1, uint32_t a2, uint32_t a3, uint64_t b, int acc) {
    asm volatile("{\n.reg .pred p;\nsetp.ne.b32 p, %69, 0;\n"
                 "wgmma.mma_async.sync.aligned.m64n128k16.f32.bf16.bf16 {" L64 "}, {%64,%65,%66,%67}, %68, p, 1, 1, %70;\n}"
                 : F64(d) : "r"(a0), "r"(a1), "r"(a2), "r"(a3), "l"(b), "r"(acc), "n"(TB));
}
template <int TB>
__device__ __forceinline__ void mma_rs64(float (&d)[32], uint32_t a0, uint32_t a1, uint32_t a2, uint32_t a3, uint64_t b, int acc) {
    asm volatile("{\n.reg .pred p;\nsetp.ne.b32 p, %37, 0;\n"
                 "wgmma.mma_async.sync.aligned.m64n64k16.f32.bf16.bf16 {" L32 "}, {%32,%33,%34,%35}, %36, p, 1, 1, %38;\n}"
                 : F32(d) : "r"(a0), "r"(a1), "r"(a2), "r"(a3), "l"(b), "r"(acc), "n"(TB));
}
template <int N>
__device__ __forceinline__ void fence_regs(float (&d)[N]) {
#pragma unroll
    for (int i = 0; i < N; i++) asm volatile("" : "+f"(d[i])::"memory");
}
template <int N>
__device__ __forceinline__ void fence_regs(uint32_t (&d)[N]) {
#pragma unroll
    for (int i = 0; i < N; i++) asm volatile("" : "+r"(d[i])::"memory");
}

template <int V> struct IC { static constexpr int value = V; };

constexpr int SLOT = 32768, UNIT = 16384;
constexpr int SM_Q = 4 * SLOT;
constexpr int SM_BAR = 7 * SLOT;
constexpr int SM_RED = SM_BAR + 512;
constexpr int SM_TOTAL = SM_BAR + 3072;
constexpr int XP = D_ * 2 + 16;
constexpr int M_MOD = 16 * XP, M_WR = M_MOD + 4 * D_ * 4;
constexpr float CS = 0.08838834764831845f * 1.4426950408889634f;
#define LMAX 0.5f
#define LMIN 0x1p-104f
#define USE_SPARE 1
#define MAXG 2
#define SPLIT 10
#define ESPLIT 2
#define PV1 8
#define RW 2
#define HW 2
#define HW2 1
#define VGATE 1
#define STAGE 11
#define POFF 102.f
constexpr int WF0 = 24;
constexpr int PF_KV = 8, PF_WO = 120;

struct Args {
    const bf16 *x, *kc, *vc, *wq, *wo, *w_r, *w_gate, *w_up, *w_down, *cvec, *w_mod;
    bf16* out;
};

__device__ __forceinline__ void frag_store(uint8_t* p, const uint32_t (&a)[32]) {
#pragma unroll
    for (int i = 0; i < 8; i++)
        __stcg(reinterpret_cast<uint4*>(p + i * 512), make_uint4(a[4 * i], a[4 * i + 1], a[4 * i + 2], a[4 * i + 3]));
}
__device__ __forceinline__ void frag_load(uint32_t (&a)[32], const uint8_t* p) {
#pragma unroll
    for (int i = 0; i < 8; i++) {
        const uint4 v = __ldcg(reinterpret_cast<const uint4*>(p + i * 512));
        a[4 * i] = v.x; a[4 * i + 1] = v.y; a[4 * i + 2] = v.z; a[4 * i + 3] = v.w;
    }
}
__device__ __forceinline__ float quad_sum(float v) {
    v += __shfl_xor_sync(0xffffffffu, v, 1);
    return v + __shfl_xor_sync(0xffffffffu, v, 2);
}
__device__ __forceinline__ float quad_max(float v) {
    v = fmaxf(v, __shfl_xor_sync(0xffffffffu, v, 1));
    return fmaxf(v, __shfl_xor_sync(0xffffffffu, v, 2));
}
__device__ __forceinline__ float rcp_fast(float x) { float y; asm("rcp.approx.ftz.f32 %0, %1;" : "=f"(y) : "f"(x)); return y; }
__device__ __forceinline__ float sigmoidf_(float x) { return rcp_fast(1.f + ex2(-1.4426950408889634f * x)); }
__device__ __forceinline__ void top2(uint32_t k, uint32_t& k1, uint32_t& k2) {
    k1 = __reduce_max_sync(0xffffffffu, k);
    k2 = __reduce_max_sync(0xffffffffu, k == k1 ? 0 : k);
}

__device__ __forceinline__ void mod_fma(float (&a)[8], const uint4 w, float sc) {
    a[0] += sc * bf_lo(w.x); a[1] += sc * bf_hi(w.x); a[2] += sc * bf_lo(w.y); a[3] += sc * bf_hi(w.y);
    a[4] += sc * bf_lo(w.z); a[5] += sc * bf_hi(w.z); a[6] += sc * bf_lo(w.w); a[7] += sc * bf_hi(w.w);
}
__device__ __forceinline__ float mod_reduce(float (&a)[8], int lane) {
#pragma unroll
    for (int h = 4; h > 0; h >>= 1) {
        const bool up = lane & (8 / h);
#pragma unroll
        for (int i = 0; i < h; i++)
            a[i] = (up ? a[i + h] : a[i]) + __shfl_xor_sync(0xffffffffu, up ? a[i] : a[i + h], 8 / h);
    }
    return a[0] + __shfl_xor_sync(0xffffffffu, a[0], 16);
}

__device__ __forceinline__ float ln_stats(float sum, float sq, uint32_t& mean2) {
    const float mean = sum * (1.f / D_);
    const float var = fmaxf(fmaf(-mean, mean, sq * (1.f / D_)), 0.f);
    float sd;
    asm("sqrt.approx.ftz.f32 %0, %1;" : "=f"(sd) : "f"(rbf(rbf(var) + 1e-5f)));
    mean2 = pack_bf16(mean, mean);
    return rcp_fast(rbf(sd));
}
__device__ __forceinline__ uint32_t ln_pair(uint32_t x, uint32_t mean2, float rsd) {
    const uint32_t d = bsub2(x, mean2);
    return pack_bf16(bf_lo(d) * rsd, bf_hi(d) * rsd);
}
__device__ __forceinline__ void rows_load(uint32_t (&x)[20], uint32_t xs, int cw) {
#pragma unroll
    for (int ch = 0; ch < 5; ch++) {
        const uint4 v = ldsm4(ch < 4 ? xs + ch * 256 : xs + 1024 - cw * 16);
        x[4 * ch] = v.x; x[4 * ch + 1] = v.y; x[4 * ch + 2] = v.z; x[4 * ch + 3] = v.w;
    }
}
__device__ __forceinline__ void stats_add(float (&st)[12], uint32_t a, uint32_t b) {
    mma1688(st, a, b, 0x3f803f80u);
    mma1688(st + 4, a, b, a);
    mma1688(st + 8, a, b, b);
}
__device__ __forceinline__ void rows_normalise(uint32_t* y, const uint32_t* x, const float (&st)[12], float4* st4, int cw, int lane) {
    const int g8 = lane >> 2, qd = lane & 3;
    if ((g8 >> 1) == qd) st4[g8 * 8 + cw] = make_float4(st[0], (g8 & 1) ? st[5] : st[4], st[2], (g8 & 1) ? st[11] : st[10]);
    bar_sync(3, 256);
    const float4 s0 = st4[g8 * 8 + qd], s1 = st4[g8 * 8 + 4 + qd];
    uint32_t ma2, mb2;
    const float ra = ln_stats(quad_sum(s0.x + s1.x), quad_sum(s0.y + s1.y), ma2);
    const float rb = ln_stats(quad_sum(s0.z + s1.z), quad_sum(s0.w + s1.w), mb2);
#pragma unroll
    for (int k = 0; k < 9; k++) { y[2 * k] = ln_pair(x[2 * k], ma2, ra); y[2 * k + 1] = ln_pair(x[2 * k + 1], mb2, rb); }
}
__device__ __forceinline__ uint32_t pair_of(const uint2* mp, int k, int cw) {
    return (k < 8 ? mp[(k >> 1) * 64 + (k & 1) * 4] : (mp - cw * 4)[256]).x;
}

__device__ __noinline__ void attn_fallback(uint32_t bad, uint8_t* frag, uint8_t* keep, const bf16* wq, const bf16* kc, const bf16* vc) {
  const int lane = threadIdx.x & 31, g8 = lane >> 2, qd = lane & 3;
  const int j = (blockIdx.x >> 1) & 7, qb = (blockIdx.x >> 4) * 2 + (blockIdx.x & 1);
  const uint4* hf = g_h + (size_t)(qb * 8 + (threadIdx.x >> 5) - 4) * (36 * 32) + lane;
#pragma unroll 1
  for (int t = 0; t < 4; t++) {
    if (!((bad >> t) & 1)) continue;
    const bf16 *wqp = wq + (4 * j + t) * DH, *kp = kc + (size_t)(2 * j + (t >> 1)) * S_ * DH, *vp = vc + (size_t)(2 * j + (t >> 1)) * S_ * DH;
    uint32_t q[32];
    float o[64];
#pragma unroll
    for (int i = 0; i < 64; i++) o[i] = 0.f;
#pragma unroll 1
    for (int ks = 0; ks < 36; ks++) {
        const uint4 a = __ldcg(hf + ks * 32);
        const unsigned short* wr = reinterpret_cast<const unsigned short*>(wqp + (size_t)(ks * 16 + 2 * qd) * QD + g8);
#pragma unroll
        for (int dt = 0; dt < 16; dt++) {
            const uint32_t b0 = __ldg(wr + dt * 8) | ((uint32_t)__ldg(wr + dt * 8 + QD) << 16);
            const uint32_t b1 = __ldg(wr + dt * 8 + 8 * QD) | ((uint32_t)__ldg(wr + dt * 8 + 9 * QD) << 16);
            mma16816(o + 4 * dt, a.x, a.y, a.z, a.w, b0, b1);
        }
    }
#pragma unroll
    for (int i = 0; i < 32; i++) q[i] = pack_bf16(o[2 * i], o[2 * i + 1]);
#pragma unroll
    for (int i = 0; i < 64; i++) o[i] = 0.f;
    float m0 = -INFINITY, m1 = -INFINITY, l0 = 0.f, l1 = 0.f;
#pragma unroll 1
    for (int key = 0; key < S_; key += 16) {
        float sc[8];
#pragma unroll
        for (int i = 0; i < 8; i++) sc[i] = 0.f;
#pragma unroll
        for (int nt = 0; nt < 2; nt++) {
            const uint32_t* kr = reinterpret_cast<const uint32_t*>(kp + (size_t)(key + nt * 8 + g8) * DH) + qd;
#pragma unroll
            for (int ks = 0; ks < 8; ks++)
                mma16816(sc + 4 * nt, q[4 * ks], q[4 * ks + 1], q[4 * ks + 2], q[4 * ks + 3], __ldg(kr + ks * 8), __ldg(kr + ks * 8 + 4));
        }
        const float n0 = quad_max(fmaxf(fmaxf(m0, fmaxf(sc[0], sc[1])), fmaxf(sc[4], sc[5])));
        const float n1 = quad_max(fmaxf(fmaxf(m1, fmaxf(sc[2], sc[3])), fmaxf(sc[6], sc[7])));
        const float f0 = ex2((m0 - n0) * CS), f1 = ex2((m1 - n1) * CS);
        m0 = n0; m1 = n1;
#pragma unroll
        for (int i = 0; i < 8; i++) sc[i] = ex2((sc[i] - ((i & 2) ? n1 : n0)) * CS);
        l0 = l0 * f0 + (sc[0] + sc[1]) + (sc[4] + sc[5]);
        l1 = l1 * f1 + (sc[2] + sc[3]) + (sc[6] + sc[7]);
        const uint32_t e0 = pack_bf16(sc[0], sc[1]), e1 = pack_bf16(sc[2], sc[3]), e2 = pack_bf16(sc[4], sc[5]), e3 = pack_bf16(sc[6], sc[7]);
        const unsigned short* vr = reinterpret_cast<const unsigned short*>(vp + (size_t)(key + 2 * qd) * DH + g8);
#pragma unroll
        for (int dt = 0; dt < 16; dt++) {
            o[4 * dt] *= f0; o[4 * dt + 1] *= f0; o[4 * dt + 2] *= f1; o[4 * dt + 3] *= f1;
            const uint32_t b0 = __ldg(vr + dt * 8) | ((uint32_t)__ldg(vr + dt * 8 + DH) << 16);
            const uint32_t b1 = __ldg(vr + dt * 8 + 8 * DH) | ((uint32_t)__ldg(vr + dt * 8 + 9 * DH) << 16);
            mma16816(o + 4 * dt, e0, e1, e2, e3, b0, b1);
        }
    }
    const float i0 = 1.f / quad_sum(l0), i1 = 1.f / quad_sum(l1);
#pragma unroll
    for (int i = 0; i < 16; i++) {
        q[2 * i] = pack_bf16(o[4 * i] * i0, o[4 * i + 1] * i0);
        q[2 * i + 1] = pack_bf16(o[4 * i + 2] * i1, o[4 * i + 3] * i1);
    }
    frag_store(t < 3 ? frag + t * 4096 : keep, q);
  }
}

__device__ __forceinline__ void spare_q3(uint32_t sb, uint32_t bar_full, uint32_t bar_empty, int lane, int cw) {
    const uint32_t tag = load_tag();
    uint32_t rel_base, e = 2;
    asm("mapa.shared::cluster.u32 %0, %1, %2;" : "=r"(rel_base) : "r"(bar_empty), "r"(lane & 1));
#pragma unroll 1
    for (int qb = blockIdx.x - NCTA; qb < 16; qb += 4) {
        uint32_t h[144];
        float o[64];
        flag_wait(&g_flag_h[(qb * 8 + cw) * 32], tag);
        const uint4* hf = g_h + (size_t)(qb * 8 + cw) * (36 * 32) + lane;
#pragma unroll
        for (int ks = 0; ks < 36; ks++) {
            const uint4 v = __ldcg(hf + ks * 32);
            h[4 * ks] = v.x; h[4 * ks + 1] = v.y; h[4 * ks + 2] = v.z; h[4 * ks + 3] = v.w;
        }
#pragma unroll
        for (int i = 0; i < 64; i++) o[i] = 0.f;
#pragma unroll 1
        for (int v = 0; v < 4; v++) {
            fence_regs(o);
#pragma unroll
            for (int t = 0; t < 5; t++) {
                mbar_wait(bar_full + 8 * (e & 3), (e >> 2) & 1);
                const uint64_t dv = mkdesc(sb + (e & 3) * SLOT, UNIT, 1024);
                WG_FENCE();
#pragma unroll
                for (int ks = 0; ks < (t < 4 ? 8 : 4); ks++)
                    mma_rs128<1>(o, h[32 * t + 4 * ks], h[32 * t + 4 * ks + 1], h[32 * t + 4 * ks + 2], h[32 * t + 4 * ks + 3], dv + ks * 128, ks | t);
                WG_COMMIT();
                if (t > 0) { WG_WAIT(1); if (lane < 2) mbar_arrive_cluster(rel_base + 8 * ((e - 1) & 3)); }
                e++;
            }
            WG_WAIT(0);
            fence_regs(o);
            if (lane < 2) mbar_arrive_cluster(rel_base + 8 * ((e - 1) & 3));
            uint4* dst = &g_q3[((qb * 8 + 2 * v) * 8 + cw) * 128 + lane];
#pragma unroll
            for (int i = 0; i < 8; i++)
                __stcg(dst + (i >> 2) * 1024 + (i & 3) * 32, make_uint4(pack_bf16(o[8 * i], o[8 * i + 1]), pack_bf16(o[8 * i + 2], o[8 * i + 3]),
                                                                        pack_bf16(o[8 * i + 4], o[8 * i + 5]), pack_bf16(o[8 * i + 6], o[8 * i + 7])));
        }
        bar_sync(3, 256);
        if (cw == 0 && lane == 0) flag_release(&g_flag_q3[qb * 32], tag);
        __syncwarp();
    }
}

template <bool SPARE>
__global__ void __cluster_dims__(2, 1, 1) __launch_bounds__(384, 1)
fused_kernel(const __grid_constant__ CUtensorMap tm_wq,
             const __grid_constant__ CUtensorMap tm_k, const __grid_constant__ CUtensorMap tm_v,
             const __grid_constant__ CUtensorMap tm_wo, const __grid_constant__ CUtensorMap tm_p,
             const __grid_constant__ CUtensorMap tm_x, const __grid_constant__ CUtensorMap tm_d,
             const __grid_constant__ CUtensorMap tm_g, const __grid_constant__ CUtensorMap tm_u, const Args args) {
    extern __shared__ __align__(1024) uint8_t smem_raw[];
    const uint32_t sb = smem_u32(smem_raw);
    const uint32_t bar_full = sb + SM_BAR;
    const uint32_t bar_g = bar_full + 8 * 4;
    const uint32_t bar_mod = bar_g + 8;
    const uint32_t bar_go = bar_mod + 8;
    const uint32_t bar_x = bar_go + 40;
    const uint32_t bar_empty = bar_x + 8;
    const uint32_t bar_pub = bar_empty + 8 * 4;
    const uint32_t bar_qfree = bar_pub + 32;
    const uint32_t bar_out = bar_qfree + 24;
    const uint32_t bar_q3 = bar_out + 8;

    const int c = blockIdx.x & 1;
    const int j = (blockIdx.x >> 1) & 7;
    const int qb = (blockIdx.x >> 4) * 2 + c;
    const int rg = qb * 8 + j;
    const int warp = __shfl_sync(0xffffffffu, threadIdx.x >> 5, 0);

    if (SPARE && blockIdx.x >= NCTA && warp >= 4) {
        asm volatile("barrier.cluster.arrive.relaxed.aligned;" ::: "memory");
        asm volatile("setmaxnreg.inc.sync.aligned.u32 240;");
        asm volatile("barrier.cluster.wait.aligned;" ::: "memory");
        spare_q3(sb, bar_full, bar_empty, threadIdx.x & 31, warp - 4);
        asm volatile("barrier.cluster.arrive.relaxed.aligned;\nbarrier.cluster.wait.aligned;" ::: "memory");
    } else if (warp < 4) {
        asm volatile("setmaxnreg.dec.sync.aligned.u32 24;");
        int lane;
        asm volatile("mov.u32 %0, %%laneid;" : "=r"(lane));
        const uint32_t tag = load_tag();
        if (elect()) {
#pragma unroll 1
            for (int i = warp; i < 25; i += 4) mbar_init(bar_full + 8 * i, i < 12 || i >= 23 ? 1 : i < 16 ? 16 : 8);
            if (SPARE && warp < 2) {
                mbar_arrive(bar_full + 8 * warp);
                asm volatile("mbarrier.arrive.shared::cta.b64 _, [%0], 16;" ::"r"(bar_empty + 8 * warp) : "memory");
            }
            asm volatile("fence.mbarrier_init.release.cluster;" ::: "memory");
        }
        __syncwarp();
        asm volatile("barrier.cluster.arrive.relaxed.aligned;\nbarrier.cluster.wait.aligned;" ::: "memory");
        if (SPARE && blockIdx.x >= NCTA) {
            if (warp == 1) {
#pragma unroll 1
                for (int e = 2; e < 82; e++) {
                    const int v = (e - 2) / 5;
                    mbar_wait_sleep(bar_empty + 8 * (e & 3), ~(e >> 2) & 1);
                    if (elect()) {
                        mbar_expect_tx(bar_full + 8 * (e & 3), SLOT);
                        tma2d_mc(sb + (e & 3) * SLOT + c * UNIT, &tm_wq, (8 * (v & 3) + 4 * c + 3) * DH + 64, (e - 2 - v * 5) * 128,
                                 bar_full + 8 * (e & 3), EVICT_NORMAL);
                    }
                }
            }
            __syncwarp();
            asm volatile("barrier.cluster.arrive.relaxed.aligned;\nbarrier.cluster.wait.aligned;" ::: "memory");
            return;
        }
        if (warp == 3) {
#pragma unroll 1
            for (int e = 4; e < 20; e++) {
                __nanosleep(e == 4 ? 3000 : 400);
                const int hd = (e * 52) >> 8, row = (e - hd * 5) * 128 + qb * 8 + (lane >> 1);
                if (lane < 16 && row < D_)
                    asm volatile("prefetch.global.L2 [%0];" ::"l"(args.wq + (size_t)row * QD + (4 * j + ((0x1320 >> (4 * hd)) & 3)) * DH + (lane & 1) * 64) : "memory");
            }
            __syncwarp();
            mbar_wait_sleep(bar_go, 0);
#pragma unroll 1
            for (int unit = 72 + blockIdx.x; unit < 216; unit += NCTA) {
                float a[8];
#pragma unroll
                for (int i = 0; i < 8; i++) a[i] = 0.f;
#pragma unroll 1
                for (int k = lane >> 1; k < D_; k += 16) {
                    const float cv = __bfloat162float(args.cvec[k]);
                    mod_fma(a, __ldg(reinterpret_cast<const uint4*>(args.w_mod + (size_t)k * (6 * D_) + unit * 16 + (lane & 1) * 8)), rbf(cv * sigmoidf_(cv)));
                }
                const float v = mod_reduce(a, lane), v1 = __shfl_down_sync(0xffffffffu, v, 8);
                if (lane < 8) st_relaxed64(&g_mod[unit * 8 + (lane & 1) * 4 + (lane & 2) + (lane >> 2)], pack_bf16(v, v1), tag);
            }
            __syncwarp();
            if (lane == 0) flag_release(&g_flag_mod[blockIdx.x], tag);
            __syncwarp();
            mbar_wait_sleep(bar_qfree + 16, 0);
            __nanosleep(2000);
            {
                uint4 v;
                uint32_t it = 0;
#pragma unroll 1
                do {
                    v = ld_relaxed(reinterpret_cast<const uint4*>(g_flag_mod) + lane);
                } while (((v.x ^ tag) | (v.y ^ tag) | (v.z ^ tag) | (v.w ^ tag)) && ++it < SPIN / 16);
                asm volatile("fence.acquire.gpu;" ::: "memory");
            }
#pragma unroll
            for (int i = 0; i < 4; i++) reinterpret_cast<uint4*>(smem_raw + SM_RED)[lane + 32 * i] = make_uint4(~0u, ~0u, ~0u, ~0u);
            asm volatile("fence.proxy.async.shared::cta;" ::: "memory");
            __syncwarp();
            if (elect()) {
                uint8_t* mb = g_frag + (size_t)rg * 8 * WREG + 3 * 4096;
#pragma unroll 1
                for (int k = 0; k < 8; k++, mb += WREG) {
#pragma unroll
                    for (int i = 0; i < 3; i++)
                        asm volatile("cp.async.bulk.global.shared::cta.bulk_group [%0], [%1], 2048;" ::"l"(mb + i * 2048), "r"(sb + SM_RED) : "memory");
                    __nanosleep(500);
                }
                asm volatile("cp.async.bulk.commit_group;\ncp.async.bulk.wait_group 0;\nfence.proxy.async.global;" ::: "memory");
            }
            __syncwarp();
            if (lane == 0) mbar_arrive(bar_mod);
            __syncwarp();
            mbar_wait_sleep(bar_go + 8, 0);
            if (lane < 3) asm volatile("prefetch.tensormap [%0];" ::"l"(lane == 0 ? &tm_x : lane == 1 ? &tm_p : &tm_d) : "memory");
            __syncwarp();
            mbar_wait_sleep(bar_go + 8 * 2, 0);
            uint32_t acc = 0;
#pragma unroll 1
            for (int k = lane; k < 16 * 9; k += 32) acc |= touch(args.x + (size_t)rg * 16 * D_ + k * 64);
            if (acc == 0) reinterpret_cast<volatile uint32_t*>(smem_raw + SM_BAR)[127] = acc;
        } else if (warp == 0) {
#pragma unroll 1
            for (int i = 0; i < 48; i++) {
                if (i == 0 || i == 17 || i == 34) mbar_wait_sleep(bar_qfree + (i >> 4) * 8, 0);
                if (SPARE && i == 17) {
                    flag_wait(&g_flag_q3[qb * 32], tag);
                    if (elect()) {
                        asm volatile("fence.proxy.async.global;" ::: "memory");
                        mbar_expect_tx(bar_q3, UNIT);
#pragma unroll 1
                        for (int k = 0; k < 8; k++) bulk_load(sb + SM_Q + 2 * SLOT + k * 4096 + 2048, &g_q3[(rg * 8 + k) * 128], 2048, bar_q3);
                    }
                }
                __nanosleep(700);
                if (elect()) {
                    asm volatile("mbarrier.expect_tx.shared::cta.b64 [%0], %1;" ::"r"(bar_g), "n"(1920) : "memory");
                    tma2d(sb + SM_Q + i * 1920, i < 24 ? &tm_g : &tm_u, (blockIdx.x * 36) & ~7, (i < 24 ? i : i - 24) * 24, bar_g);
                }
            }
#pragma unroll 1
            for (int i = 0; i < 18; i++) {
                __nanosleep(400);
                if (elect()) l2_prefetch(args.w_down + (size_t)(blockIdx.x * 36 + i * 2) * D_, 4 * D_);
            }
            __syncwarp();
            mbar_wait_sleep(bar_go + 8 * 4, 0);
            if (blockIdx.x < 72) {
                uint4* yp = reinterpret_cast<uint4*>(&g_ypart[blockIdx.x * NCTA * 8]) + lane;
#pragma unroll
                for (int k = 0; k < 16; k++) yp[k * 32] = make_uint4(~0u, ~0u, ~0u, ~0u);
                asm volatile("fence.acq_rel.gpu;" ::: "memory");
            }
            __syncwarp();
            if (lane == 0) mbar_arrive(bar_g);
        } else if (warp == 1) {
            __nanosleep(600);
            uint32_t go = bar_go;
            uint64_t marks = 24 | 151 << 8 | 154 << 16 | 159ull << 24 | 165ull << 32;
#pragma unroll 1
            for (int e = SPARE ? 2 : 0; e < 172; e++) {
                const CUtensorMap* tm;
                int c0, c1;
                uint64_t pol = EVICT_FIRST;
                if (e == 158 || e == 163 || e == 169) continue;
                if (e < 21 && e != 19) {
                    const int i = SPARE && e < 12 ? e - 2 : e - (e == 20), hd = (i * 52) >> 8;
                    tm = &tm_wq; c0 = (4 * j + ((0x1320 >> (4 * hd)) & 3)) * DH + c * 64; c1 = (i - hd * 5) * 128 - 64;
                    if (SPARE && e >= 12 && e < 15) { c0 = (4 * j + 3) * DH; c1 = (2 * (e - 12) + c) * 128; }
                } else if (e < 148) {
                    const int i = max(e - 20, 0);
                    const bool isk = i == 0 || ((i & 1) && i < 127);
                    const int n = isk ? (i + 1) >> 1 : (i - 1) >> 1;
                    tm = isk ? &tm_k : &tm_v; c0 = c * 64; c1 = (2 * j + (n >> 5)) * S_ + (n & 15) * 128;
                    if (!(i & 32)) pol = EVICT_NORMAL;
                } else {
                    int i = e - 148 - (e > 158) - (e > 163);
                    if (i == 1 || i == 2) i ^= 3;
                    tm = &tm_wo; c0 = (i >> 1) * 64; c1 = (4 * j + ((i & 1) ? 1 + c : 3 * c)) * DH;
                }
                if (e == 168) {
                    mbar_wait(bar_mod, 0);
                    asm volatile("fence.proxy.async.global;" ::: "memory");
                }
                const uint32_t fb = bar_full + 8 * (e & 3), d = sb + (e & 3) * SLOT;
                if (e >= 24 && e < 152) mbar_wait_sleep(bar_empty + 8 * (e & 3), ~(e >> 2) & 1);
                else mbar_wait(bar_empty + 8 * (e & 3), ~(e >> 2) & 1);
                if (elect()) {
                    mbar_expect_tx(fb, e == 168 ? 16 * XP + 4 * D_ * 4 + D_ * 2 : e >= 170 ? 18 * XP : SLOT);
                    if (e < 168) {
                        tma2d_mc(d + c * UNIT, tm, c0, c1, fb, pol);
                        const int i = e - PF_KV;
                        if (i >= 0 && i < 128 && !(i & 32))
                            l2_prefetch(((i & 1) ? args.vc : args.kc) + (size_t)((2 * j + (i >> 6)) * S_ + (i & 30) * 64) * DH + qb * 1024, 2048);
                        if (e >= PF_WO && e < PF_WO + 18) l2_prefetch(args.wo + (size_t)blockIdx.x * (QD * D_ / NCTA) + (e - PF_WO) * 1024, 2048);
                        if (e == (marks & 255)) mbar_arrive(go);
                    } else {
                        tma2d(d, e == 168 ? &tm_x : &tm_d, 0, e == 168 ? rg * 16 : blockIdx.x * 36 + (e - 170) * 18, fb);
                        if (e == 168) {
                            bulk_load(d + M_MOD, g_mod + D_, 4 * D_ * 4, fb);
                            bulk_load(d + M_WR, args.w_r, D_ * 2, fb);
                        }
                    }
                }
                if (e == (marks & 255)) { go += 8; marks >>= 8; }
            }
        } else {
            if (elect()) {
                mbar_expect_tx(bar_x, 16 * XP);
                tma2d(sb + SM_Q, &tm_x, 0, rg * 16, bar_x);
            }
            if (lane < 3) asm volatile("prefetch.tensormap [%0];" ::"l"(lane == 0 ? &tm_k : lane == 1 ? &tm_v : &tm_wo) : "memory");
#pragma unroll 1
            for (int i = 0; i < 4; i++) {
                if (i == 1) {
#pragma unroll 1
                    for (uint32_t e = 19; e < 148; e++) {
                        mbar_wait_sleep(bar_full + 8 * (e & 3), (e >> 2) & 1);
                        if (VGATE) {
                            if (e & 1) bar_sync(1, 192);
                            if (!(e & 1) || e == 147) bar_sync(4, 160);
                        } else if (!(e & 1) || e == 147) bar_sync(1, 192);
                    }
                    mbar_wait_sleep(bar_go + 8, 0); mbar_wait(bar_mod, 0);
                }
                mbar_wait(bar_pub + 8 * i, 0);
                unsigned int* flags = i ? &g_flag_part[qb * 32 + i * 8 - 8] : &g_flag_h[rg * 32 - j];
                if (elect()) { flag_release(flags + j, tag); DBG_PG(i ? 93 : 90); }
                __syncwarp();
                if (i > 0) {
                    const uint32_t slot = i < 3 ? i + 1 : 1;
                    flag_wait(flags + (lane & 7), tag);
                    asm volatile("fence.proxy.async.global;" ::: "memory");
                    if (lane == 0 && i == 3) DBG_PG(101);
                    mbar_wait(bar_go + 8 + 8 * i, 0);
                    mbar_wait(bar_empty + 8 * slot, i != 1);
                    if (elect()) {
                        mbar_expect_tx(bar_full + 8 * slot, SLOT);
                        tma3d(sb + slot * SLOT, &tm_p, 0, j * 20 + (i - 1) * 4, qb * 8, bar_full + 8 * slot);
                    }
                }
            }
        }
        __syncwarp();
        mbar_wait_sleep(bar_out, 0);
        if (elect()) {
            const int2 sel = reinterpret_cast<const int2*>(smem_raw + SM_RED)[208];
#pragma unroll 1
            for (int i = warp; i < 16; i += 4) {
                const int row = rg * 16 + i;
                if (row != sel.x && row != sel.y)
                    asm volatile("cp.async.bulk.global.shared::cta.bulk_group [%0], [%1], %2;"
                                 ::"l"(args.out + (size_t)row * D_), "r"(sb + i * XP), "n"(D_ * 2) : "memory");
            }
            asm volatile("cp.async.bulk.commit_group;\ncp.async.bulk.wait_group 0;" ::: "memory");
        }
    } else {
        asm volatile("barrier.cluster.arrive.relaxed.aligned;" ::: "memory");
        asm volatile("setmaxnreg.inc.sync.aligned.u32 240;");
        const int lane = threadIdx.x & 31;
        const int cw = warp - 4;
        const int w = cw >> 2;
        const int tid = threadIdx.x - 128;
        float* red = reinterpret_cast<float*>(smem_raw + SM_RED);
        DBG_INIT();
        DBG_G(120);
        DBG_T(100);

        uint32_t tag;
        {
            if (blockIdx.x < 72) {
                const bf16* wrow = args.w_mod + (size_t)(tid >> 1) * (6 * D_) + (tid & 1) * 8 + blockIdx.x * 16;
                uint4 wm[5];
                float sc[5], a[8];
                const uint32_t tag0 = load_tag();
                wm[4] = make_uint4(0, 0, 0, 0);
                sc[4] = 0.f;
#pragma unroll
                for (int i = 0; i < 5; i++)
                    if (i < 4 || tid < 128) {
                        wm[i] = __ldg(reinterpret_cast<const uint4*>(wrow + (size_t)i * 128 * (6 * D_)));
                        sc[i] = __bfloat162float(args.cvec[(tid >> 1) + i * 128]);
                    }
#pragma unroll
                for (int i = 0; i < 8; i++) a[i] = 0.f;
#pragma unroll
                for (int i = 0; i < 5; i++) mod_fma(a, wm[i], rbf(sc[i] * sigmoidf_(sc[i])));
                const float v = mod_reduce(a, lane);
                if (lane < 16) red[cw * 16 + lane] = v;
                bar_sync(3, 256);
                if (tid < 8) {
                    float v0 = 0.f, v1 = 0.f;
#pragma unroll
                    for (int i = 0; i < 8; i++) { v0 += red[i * 16 + tid]; v1 += red[i * 16 + 8 + tid]; }
                    st_relaxed64(&g_mod[blockIdx.x * 8 + (tid & 1) * 4 + (tid & 2) + (tid >> 2)], pack_bf16(v0, v1), tag0);
                }
            }
            DBG_G(106);
            asm volatile("barrier.cluster.wait.aligned;" ::: "memory");
            mbar_wait(bar_x, 0);
            tag = load_tag();
            uint32_t x[20];
            float st[12];
            rows_load(x, sb + SM_Q + (lane & 15) * XP + (lane >> 4) * 16 + cw * 32, cw);
#pragma unroll
            for (int i = 0; i < 12; i++) st[i] = 0.f;
#pragma unroll
            for (int k = 0; k < 9; k++) stats_add(st, x[2 * k], x[2 * k + 1]);
            rows_normalise(x, x, st, reinterpret_cast<float4*>(red + 128), cw, lane);
            fence_regs(x);
            uint4* smod = reinterpret_cast<uint4*>(smem_raw + SM_Q + M_MOD);
            if (tid < D_ / 4) {
                const uint4* mp = reinterpret_cast<const uint4*>(g_mod) + tid;
                poll2x2(mp, mp + D_ / 4, tag, smod[tid], smod[D_ / 4 + tid]);
            }
            bar_sync(3, 256);
            DBG_G(107);
            const uint2* mp = reinterpret_cast<const uint2*>(smod) + cw * 8 + (lane & 3);
#pragma unroll
            for (int k = 0; k < 9; k++) {
                const uint32_t c1 = badd2(pair_of(mp + D_ / 2, k, cw), 0x3f803f80u), sa = pair_of(mp, k, cw);
                x[2 * k] = badd2(bmul2(x[2 * k], c1), sa);
                x[2 * k + 1] = badd2(bmul2(x[2 * k + 1], c1), sa);
            }
            uint4* hdst = g_h + (size_t)(rg * 36 + cw) * 32 + lane;
#pragma unroll
            for (int ch = 0; ch < 4; ch++) __stcg(hdst + ch * 256, make_uint4(x[4 * ch], x[4 * ch + 1], x[4 * ch + 2], x[4 * ch + 3]));
            __stcg(reinterpret_cast<uint2*>(hdst + (32 - cw + (cw >> 1)) * 32) + (cw & 1), make_uint2(x[16], x[17]));
            __syncwarp();
            if (lane == 0) mbar_arrive(bar_pub);
            DBG_G(108);
        }

        uint32_t rel_base;
        asm("mapa.shared::cluster.u32 %0, %1, %2;" : "=r"(rel_base) : "r"(bar_empty), "r"(lane & 1));
        auto release = [&](uint32_t slot) { if (lane < 2) mbar_arrive_cluster(rel_base + 8 * slot); };
        uint32_t q[32], p[32];
        float s[64], o[64];

        uint4* qpark = reinterpret_cast<uint4*>(smem_raw + SM_Q - SLOT) + cw * 256 + lane;
        {
            uint32_t h[144];
            const uint4* hf = g_h + (size_t)(qb * 8 + cw) * (36 * 32) + lane;
            auto load_h = [&](auto lo, auto hi) {
#pragma unroll
                for (int ks = lo.value; ks < hi.value; ks++) {
                    const uint4 v = __ldcg(hf + ks * 32);
                    h[4 * ks] = v.x; h[4 * ks + 1] = v.y; h[4 * ks + 2] = v.z; h[4 * ks + 3] = v.w;
                }
            };
            flag_wait(&g_flag_h[(qb * 8 + cw) * 32], tag);
            load_h(IC<0>{}, IC<4>{});
            DBG_T(104); DBG_G(109);
#pragma unroll
            for (int i = 0; i < 64; i++) o[i] = 0.f;
            uint32_t e = SPARE ? 2 : 0;
#pragma unroll 1
            for (int hd = 1;; hd++) {
                fence_regs(o);
                auto group = [&](auto tc) {
                    constexpr int t = tc.value, k0 = t ? 8 * t - 4 : 0;
                    mbar_wait(bar_full + 8 * (e & 3), (e >> 2) & 1);
                    const uint32_t dv = desc_lo(t ? 0 : 8192, UNIT) + (e & 3) * (SLOT / 16);
                    WG_FENCE();
#pragma unroll
                    for (int ks = k0; ks < 8 * t + 4; ks++)
                        mma_rs128<1>(o, h[4 * ks], h[4 * ks + 1], h[4 * ks + 2], h[4 * ks + 3], desc_of(dv + (ks - k0) * 128), ks);
                    WG_COMMIT();
                    if (t < 4 && hd == 1) load_h(IC<8 * t + 4>{}, IC<t < 4 ? 8 * t + 12 : 0>{});
                    if (t > 0) { WG_WAIT(1); release((e - 1) & 3); }
                    e++;
                };
                group(IC<0>{}); group(IC<1>{}); group(IC<2>{}); group(IC<3>{});
                if (e == 19) break;
                group(IC<4>{});
                WG_WAIT(0);
                fence_regs(o);
                release((e - 1) & 3);
#pragma unroll
                for (int i = 0; i < 8; i++)
                    qpark[hd * 2048 + i * 32] = make_uint4(pack_bf16(o[8 * i], o[8 * i + 1]), pack_bf16(o[8 * i + 2], o[8 * i + 3]),
                                                           pack_bf16(o[8 * i + 4], o[8 * i + 5]), pack_bf16(o[8 * i + 6], o[8 * i + 7]));
                if (SPARE && hd == 2) {
                    float (&u)[32] = reinterpret_cast<float (&)[32]>(o);
                    fence_regs(u);
#pragma unroll
                    for (int t = 0; t < 3; t++) {
                        mbar_wait(bar_full + 8 * t, 1);
                        WG_FENCE();
#pragma unroll
                        for (int ks = 0; ks < (t < 2 ? 16 : 4); ks++)
                            mma_rs64<1>(u, h[64 * t + 4 * ks], h[64 * t + 4 * ks + 1], h[64 * t + 4 * ks + 2], h[64 * t + 4 * ks + 3],
                                        desc_of(desc_lo(t * SLOT, UNIT) + ks * 128), ks | t);
                        WG_COMMIT();
                        if (t > 0) { WG_WAIT(1); release(t - 1); }
                    }
                    WG_WAIT(0);
                    fence_regs(u);
                    release(2);
                    e = 15;
#pragma unroll
                    for (int i = 0; i < 4; i++)
                        qpark[3 * 2048 + i * 32] = make_uint4(pack_bf16(u[8 * i], u[8 * i + 1]), pack_bf16(u[8 * i + 2], u[8 * i + 3]),
                                                              pack_bf16(u[8 * i + 4], u[8 * i + 5]), pack_bf16(u[8 * i + 6], u[8 * i + 7]));
                }
            }
#pragma unroll
            for (int i = 0; i < 8; i++) {
                const uint4 v = qpark[2048 + i * 32];
                q[4 * i] = v.x; q[4 * i + 1] = v.y; q[4 * i + 2] = v.z; q[4 * i + 3] = v.w;
            }
#pragma unroll
            for (int i = 0; i < 32; i++) p[i] = h[112 + i];
            WG_WAIT(0);
            fence_regs(o);
            release(2);
        }
        DBG_T(105);
        DBG_G(125);

        uint8_t* frag = reinterpret_cast<uint8_t*>(__shfl_sync(0xffffffffu, reinterpret_cast<unsigned long long>(g_frag + (size_t)(rg * 8 + cw) * WREG + lane * 16), lane));
        const uint4* qnext = reinterpret_cast<const uint4*>(__shfl_sync(0xffffffffu, reinterpret_cast<unsigned long long>(qpark + 2048), lane));
        uint8_t* odst = reinterpret_cast<uint8_t*>(const_cast<uint4*>(qnext));
        float m0 = 0.f, m1 = 0.f, l0 = 0.f, l1 = 0.f, t0 = 1.f, t1 = 1.f;
        uint32_t bad = 0;
        const int lw = cw & 3;
        const uint32_t relw = lw == RW && lane < 8, handw = lw == HW || cw == HW2;
        auto release4 = [&](uint32_t off) {
            asm volatile("{\n.reg .pred p;\nsetp.ne.b32 p, %1, 0;\n@p mbarrier.arrive.shared::cluster.b64 _, [%0];\n}" ::"r"(rel_base + off), "r"(relw) : "memory"); };
        auto handoff = [&]() {
            asm volatile("{\n.reg .pred p;\nsetp.ne.b32 p, %1, 0;\n@p bar.arrive %0, 192;\n}" ::"r"(2 - w), "r"(handw) : "memory"); };
        if (cw == 4 + HW) bar_arrive(1, 192);
        auto finish = [&](auto lo, auto hi, uint32_t bit, auto sink) {
#pragma unroll
            for (int i = lo.value; i < hi.value; i++) {
                const uint32_t v0 = pack_bf16(o[8 * i] * t0, o[8 * i + 1] * t0), v1 = pack_bf16(o[8 * i + 2] * t1, o[8 * i + 3] * t1);
                const uint32_t v2 = pack_bf16(o[8 * i + 4] * t0, o[8 * i + 5] * t0), v3 = pack_bf16(o[8 * i + 6] * t1, o[8 * i + 7] * t1);
                if (i == 0 && fabsf(o[0] * t0) >= 0x1p-31f) bad |= bit << 8;
                sink(i, v0, v1, v2, v3);
            }
        };
        auto row_sums = [&](uint32_t bit) {
            t0 = quad_sum(l0); t1 = quad_sum(l1);
            if (!(t0 >= LMIN && t0 < LMAX && t1 >= LMIN && t1 < LMAX)) bad |= bit;
            t0 = rcp_fast(t0); t1 = rcp_fast(t1);
            l0 = 0.f; l1 = 0.f;
        };
        auto issue_pv = [&](uint32_t dlo, int acc, auto lo, auto hi) {
            if (VGATE && lo.value == 0) asm volatile("{\n.reg .pred p;\nsetp.eq.b32 p, %0, 0;\n@p bar.sync 4, 160;\n}" ::"r"(w) : "memory");
#pragma unroll
            for (int ks = lo.value; ks < hi.value; ks++)
                mma_rs128<1>(o, p[4 * ks], p[4 * ks + 1], p[4 * ks + 2], p[4 * ks + 3], desc_of(dlo + ks * 128), ks ? 1 : acc);
            WG_COMMIT();
        };
#pragma unroll
        for (int i = 0; i < 64; i++) s[i] = 0.f;
        uint32_t dv_lo = desc_lo(0, UNIT), voff = 0;
        auto issue_qk = [&]() {
            const uint32_t dk = dv_lo ^ (desc_lo(0, UNIT) ^ desc_lo(3 * SLOT, 16));
            bar_sync(1 + w, 192);
            fence_regs(s); fence_regs(q); fence_regs(o); fence_regs(p);
            WG_FENCE();
#pragma unroll
            for (int ks = 0; ks < 8; ks++)
                mma_rs128<0>(s, q[4 * ks], q[4 * ks + 1], q[4 * ks + 2], q[4 * ks + 3], desc_of(dk + (ks >> 2) * 1024 + (ks & 3) * 2), ks != 0);
            WG_COMMIT();
        };
        auto to_frag = [&](int i, uint32_t v0, uint32_t v1, uint32_t v2, uint32_t v3) {
            *reinterpret_cast<uint4*>(odst + i * 512) = make_uint4(v0, v1, v2, v3); };
        int n = 0;
#pragma unroll 1
        for (;;) {
            issue_qk();
            const int jn = n & 15;
            if (jn == 1) {
                finish(IC<ESPLIT>{}, IC<8>{}, 1u << (n >> 4), to_frag);
                WG_FENCE();
                issue_pv(dv_lo, 0, IC<0>{}, IC<PV1>{});
            } else {
                if (jn == 0 && n > 0) {
                    row_sums(1u << (n >> 4));
                    qnext = n == 48 ? reinterpret_cast<const uint4*>(frag) : qnext + 2048;
                    odst = frag + ((n >> 4) - 1) * 4096;
                    if (elect()) mbar_arrive(bar_qfree + (n >> 1) - 8);
                }
                issue_pv(dv_lo, 1, IC<0>{}, IC<PV1>{});
            }
            if (SPARE && n == 47) mbar_wait(bar_q3, 0);
            WG_WAIT(1);
            fence_regs(s); fence_regs(q);
            if (jn == 15) {
#pragma unroll
                for (int i = 0; i < 8; i++) {
                    const uint4 v = qnext[i * 32];
                    q[4 * i] = v.x; q[4 * i + 1] = v.y; q[4 * i + 2] = v.z; q[4 * i + 3] = v.w;
                }
            }
            if (jn == 0) {
                float a0 = fmaxf(s[0], s[1]), a1 = fmaxf(s[2], s[3]), a2 = fmaxf(s[4], s[5]), a3 = fmaxf(s[6], s[7]);
#pragma unroll
                for (int i = 1; i < MAXG; i++) {
                    a0 = fmaxf(a0, fmaxf(s[8 * i], s[8 * i + 1])); a1 = fmaxf(a1, fmaxf(s[8 * i + 2], s[8 * i + 3]));
                    a2 = fmaxf(a2, fmaxf(s[8 * i + 4], s[8 * i + 5])); a3 = fmaxf(a3, fmaxf(s[8 * i + 6], s[8 * i + 7]));
                }
                const uint32_t a = pack_bf16(fmaxf(a0, a2), fmaxf(a1, a3));
                const uint32_t b = bmax2(bmax2(a, __shfl_xor_sync(0xffffffffu, a, 1)), bmax2(__shfl_xor_sync(0xffffffffu, a, 2), __shfl_xor_sync(0xffffffffu, a, 3)));
                m0 = fmaf(-CS, bf_lo(b), -POFF); m1 = fmaf(-CS, bf_hi(b), -POFF);
            }
            if (PV1 < 8) issue_pv(dv_lo, 1, IC<PV1>{}, IC<8>{});
            release4(voff ^ 24);
            handoff();
#pragma unroll 1
            do {
                DBG_T(n);
#pragma unroll
                for (int i = 0; i < 4 * STAGE; i++) s[i] = fmaf(s[i], CS, (i & 2) ? m1 : m0);
#pragma unroll
                for (int i = 0; i < 4 * SPLIT; i++) s[i] = ex2(s[i]);
#pragma unroll
                for (int i = 0; i < SPLIT; i++) { l0 += s[4 * i] + s[4 * i + 1]; l1 += s[4 * i + 2] + s[4 * i + 3]; }
                if (STAGE < 16) {
                    m0 = fmaf(l0, 0.f, m0); m1 = fmaf(l1, 0.f, m1);
                }
                anchor(bar_full + 504, l0 + l1);
                WG_WAIT(0);
                fence_regs(o); fence_regs(p);
                release4(voff);
                dv_lo ^= 2 * SLOT / 16;
                voff ^= 16;
                n++;
#pragma unroll
                for (int i = 4 * STAGE; i < 64; i++) s[i] = fmaf(s[i], CS, (i & 2) ? m1 : m0);
#pragma unroll
                for (int i = 4 * SPLIT; i < 64; i++) s[i] = ex2(s[i]);
#pragma unroll
                for (int i = SPLIT; i < 16; i++) { l0 += s[4 * i] + s[4 * i + 1]; l1 += s[4 * i + 2] + s[4 * i + 3]; }
#pragma unroll
                for (int i = 0; i < 32; i++) p[i] = pack_bf16(s[2 * i], s[2 * i + 1]);
                if (((n + 1) & 15) < 3) break;
                issue_qk();
                issue_pv(dv_lo, 1, IC<0>{}, IC<8>{});
                WG_WAIT(1);
                fence_regs(s); fence_regs(q);
                release4(voff ^ 24);
                handoff();
            } while (n != 99);
            WG_WAIT(0);
            fence_regs(o); fence_regs(p);
            if ((n & 15) == 1) finish(IC<0>{}, IC<ESPLIT>{}, 1u << (n >> 4), to_frag);
            if (n == 64) break;
        }
        DBG_T(64);
        uint32_t a1[32], a2[32];
        bar_sync(1 + w, 192);
        fence_regs(o); fence_regs(p);
        WG_FENCE();
        issue_pv(desc_lo(3 * SLOT, UNIT), 1, IC<0>{}, IC<8>{});
        if (w == 0) handoff();
        row_sums(16);
        mbar_wait(bar_mod, 0);
        WG_WAIT(0);
        fence_regs(o); fence_regs(p);
        release(3);
        finish(IC<0>{}, IC<8>{}, 16, [&](int i, uint32_t v0, uint32_t v1, uint32_t v2, uint32_t v3) {
            p[4 * i] = v0; p[4 * i + 1] = v1; p[4 * i + 2] = v2; p[4 * i + 3] = v3; });
        bad = __reduce_or_sync(0xffffffffu, bad);
        bad = ((bad | ~(bad >> 8)) >> 1) & 15;
        if (__builtin_expect(bad != 0, 0)) {
            uint8_t* keep = g_keep + (size_t)(rg * 8 + cw) * 4096 + lane * 16;
            frag_store(keep, p);
            attn_fallback(bad, frag, keep, args.wq, args.kc, args.vc);
            frag_load(q, frag); frag_load(p, keep);
        }
        DBG_T(80);
        DBG_G(124);

        const uint32_t eye = (lane >> 3) == (lane & 3) ? 0x3f80u << ((lane & 4) * 4) : 0;
        auto sum8 = [&](uint32_t* r, const uint4 (&v)[8]) {
            float d[16];
#pragma unroll
            for (int i = 0; i < 16; i++) d[i] = 0.f;
#pragma unroll
            for (int src = 0; src < 8; src++) {
                mma1688(d + 8 * (src & 1), v[src].x, v[src].y, eye);
                mma1688(d + 8 * (src & 1) + 4, v[src].z, v[src].w, eye);
            }
#pragma unroll
            for (int i = 0; i < 4; i++) r[i] = pack_bf16(d[2 * i] + d[8 + 2 * i], d[2 * i + 1] + d[9 + 2 * i]);
        };
        auto sum8_slot = [&](uint32_t* r, uint32_t e) {
            mbar_wait(bar_full + 8 * (e & 3), (e >> 2) & 1);
            uint4 v[8];
#pragma unroll
            for (int src = 0; src < 8; src++) v[src] = lds128(sb + (e & 3) * SLOT + src * 4096 + tid * 16);
            sum8(r, v);
        };
        uint4 v3[8];
        const uint8_t* mb;
        auto load3 = [&]() {
#pragma unroll
            for (int src = 0; src < 8; src++) v3[src] = ld_relaxed(reinterpret_cast<const uint4*>(mb + (size_t)src * 8 * WREG));
        };
        uint32_t at[18];
        {
            float ua[32], ub[32];
            uint32_t e = 148, prev = 4;
            auto step = [&](float (&u)[32], const uint32_t (&a)[32], const uint32_t (&b)[32], int acc) {
                mbar_wait(bar_full + 8 * (e & 3), (e >> 2) & 1);
                const uint64_t dv = mkdesc(sb + (e & 3) * SLOT, UNIT, 1024);
                if (!acc) fence_regs(u);
                WG_FENCE();
#pragma unroll
                for (int ks = 0; ks < 8; ks++) mma_rs64<1>(u, a[4 * ks], a[4 * ks + 1], a[4 * ks + 2], a[4 * ks + 3], dv + ks * 128, ks | acc);
#pragma unroll
                for (int ks = 0; ks < 8; ks++) mma_rs64<1>(u, b[4 * ks], b[4 * ks + 1], b[4 * ks + 2], b[4 * ks + 3], dv + 1024 + ks * 128, 1);
                WG_COMMIT();
                WG_WAIT(1);
                if (prev < 4 && e < 167) release(prev);
                prev = e & 3;
                e++;
            };
            auto store = [&](float (&u)[32], uint8_t* dst) {
                fence_regs(u);
#pragma unroll
                for (int i = 0; i < 4; i++)
                    st_relaxed4(dst + i * 512, pack_bf16(u[8 * i], u[8 * i + 1]), pack_bf16(u[8 * i + 2], u[8 * i + 3]),
                                pack_bf16(u[8 * i + 4], u[8 * i + 5]), pack_bf16(u[8 * i + 6], u[8 * i + 7]));
            };
#pragma unroll
            for (int i = 0; i < 8; i++) at[i] = 0;
#pragma unroll
            for (int i = 0; i < 32; i++) { ua[i] = 0.f; ub[i] = 0.f; }
            fence_regs(q); fence_regs(p);
            step(ua, q, p, 0);
            frag_load(a1, frag + 4096);
            mbar_wait(bar_full + 8, 1);
            frag_load(a2, frag + 8192);
            step(ub, q, p, 0);
            WG_WAIT(0);
            release(1);
            prev = 4;
            fence_regs(a1); fence_regs(a2); fence_regs(ua); fence_regs(ub);
#pragma unroll 1
            for (int ch = 0; ch < 4; ch++) {
                step(ua, a1, a2, 1);
                if (ch > 0) {
                    if (ch >= 2) {
#pragma unroll
                        for (int i = 0; i < 4; i++) at[i] = at[4 + i];
                        sum8_slot(at + 4, e);
                        __syncwarp();
                        release(e & 3);
                        e++;
                        WG_WAIT(0);
                        release(prev);
                        prev = 4;
                    }
                    step(ub, q, p, 0);
                } else {
                    WG_WAIT(0);
                }
                store(ua, frag + ch * 4096);
                step(ub, a1, a2, 1);
                step(ua, q, p, 0);
                store(ub, frag + ch * 4096 + 2048);
                __syncwarp();
                if (lane == 0 && ch < 3) mbar_arrive(bar_pub + 8 + 8 * ch);
            }
            mb = g_frag + (size_t)(qb * 64 + j) * WREG + 3 * 4096 + tid * 16;
            step(ua, a1, a2, 1);
            mbar_wait(bar_full, 0);
            mbar_wait(bar_g, 0);
            WG_WAIT(0);
            store(ua, frag + 4 * 4096);
        }
        DBG_T(81);
        DBG_G(122);

        const int tid_ = __shfl_sync(0xffffffffu, tid, lane);
        {
        const int tid = tid_, lane = tid & 31;
        const int g8 = lane >> 2, qd = lane & 3, l16 = lane & 15;
        const uint8_t* mbase = smem_raw;
        const uint2* mp = reinterpret_cast<const uint2*>(mbase + M_MOD) + cw * 8 + qd;
        auto modp = [&](int which, int k) { return pair_of(mp + which * (D_ / 2), k, cw); };
        uint32_t x1[20], h2[18], c1[9], sv[9], wr[9];
        uint4 wf[27];
        uint32_t k1, k2;
        const uint32_t xs = sb + l16 * XP + (lane >> 4) * 16 + cw * 32;
        auto load_wf = [&](auto lo, auto hi) {
            const uint32_t wa = sb + SM_Q + ((cw & 1) * D_ + (cw >> 1) * 144 + (lane & 7) + (lane >> 4) * 8) * 80 + (lane & 8) * 2;
#pragma unroll
            for (int i = lo.value; i < hi.value; i++) wf[i] = ldsm4t(wa + (i / 3) * 1280 + (i % 3) * 32);
        };
        auto stage_out = [&]() {
#pragma unroll
            for (int k = 0; k < 18; k++) x1[k] = badd2(x1[k], bmul2(modp(3, k >> 1), h2[k]));
#pragma unroll
            for (int ch = 0; ch < 4; ch++) stsm_x4(xs + ch * 256, x1[4 * ch], x1[4 * ch + 1], x1[4 * ch + 2], x1[4 * ch + 3]);
            asm volatile("stmatrix.sync.aligned.m8n8.x2.shared.b16 [%0], {%1, %2};\nfence.proxy.async.shared::cta;"
                         ::"r"(xs + 1024 - cw * 16), "r"(x1[16]), "r"(x1[17]) : "memory");
        };
        const uint2* candp = reinterpret_cast<const uint2*>(&g_cand[((blockIdx.x & (CREP - 1)) * NCTA + (tid >> 1)) * 2]) + (tid & 1);
        uint2 cv;
        {
            const uint8_t* mb4 = mb + 4096 + ((cw >> 1) - cw) * 512 + (cw & 1) * 8;
            uint32_t ga[9], it = 0;
            load3();
            mbar_wait(bar_full + 8, 0);
            uint2 u[8];
            auto load4 = [&]() {
#pragma unroll
                for (int src = 0; src < 8; src++) u[src] = ld_relaxed8(mb4 + (size_t)src * 8 * WREG);
            };
            {
                uint4 v[8];
#pragma unroll
                for (int src = 0; src < 8; src++) v[src] = lds128(sb + SLOT + src * 4096 + tid * 16);
                sum8(at + 8, v);
            }
            const uint32_t* wp = reinterpret_cast<const uint32_t*>(mbase + M_WR) + cw * 8 + qd;
            rows_load(x1, xs, cw);
#pragma unroll
            for (int k = 0; k < 9; k++) {
                ga[k] = modp(0, k); sv[k] = modp(1, k); c1[k] = badd2(modp(2, k), 0x3f803f80u);
                wr[k] = k < 8 ? wp[(k >> 1) * 64 + (k & 1) * 4] : (wp - cw * 4)[256];
            }
            float st[12];
#pragma unroll
            for (int i = 0; i < 12; i++) st[i] = 0.f;
            auto add_pair = [&](int k) {
                x1[2 * k] = badd2(x1[2 * k], bmul2(ga[k], at[2 * k]));
                x1[2 * k + 1] = badd2(x1[2 * k + 1], bmul2(ga[k], at[2 * k + 1]));
                stats_add(st, x1[2 * k], x1[2 * k + 1]);
            };
#pragma unroll
            for (int k = 0; k < 6; k++) add_pair(k);
            fence_regs(ga); fence_regs(sv); fence_regs(c1); fence_regs(wr); fence_regs(x1); fence_regs(st);
#pragma unroll 1
            while (true) {
                uint32_t mx = 0;
#pragma unroll
                for (int src = 0; src < 8; src++) mx = __vimax3_u32(__vimax3_u32(mx, v3[src].x, v3[src].y), v3[src].z, v3[src].w);
                if (!__any_sync(0xffffffffu, mx == ~0u) || it >= SPIN / 16) break;
#pragma unroll 1
                while (__any_sync(0xffffffffu, ld_relaxed8(mb - lane * 16 + (size_t)(lane & 7) * 8 * WREG).x == ~0u) && ++it < SPIN / 16) {}
                it++;
                load3();
            }
            load4();
            sum8(at + 12, v3);
            add_pair(6); add_pair(7);
            load_wf(IC<0>{}, IC<WF0>{});
            fence_regs(st);
#pragma unroll 1
            while (true) {
                uint32_t mx = 0;
#pragma unroll
                for (int src = 0; src < 8; src++) mx = __vimax3_u32(mx, u[src].x, u[src].y);
                if (!__any_sync(0xffffffffu, mx == ~0u) || ++it >= SPIN / 16) break;
                load4();
            }
            if (lane < 4) mbar_arrive_cluster(rel_base + 8 * (2 + (lane >> 1)));
            float d[8] = {0.f, 0.f, 0.f, 0.f, 0.f, 0.f, 0.f, 0.f};
#pragma unroll
            for (int src = 0; src < 8; src++) mma1688(d + 4 * (src & 1), u[src].x, u[src].y, eye);
            at[16] = pack_bf16(d[0] + d[4], d[1] + d[5]); at[17] = pack_bf16(d[2] + d[6], d[3] + d[7]);
            add_pair(8);
            DBG_G(123);
            float4* st4 = reinterpret_cast<float4*>(red);
            rows_normalise(h2, x1, st, st4, cw, lane);
#pragma unroll
            for (int k = 0; k < 18; k++) h2[k] = badd2(bmul2(h2[k], c1[k >> 1]), sv[k >> 1]);
            float rs[8] = {0.f, 0.f, 0.f, 0.f, 0.f, 0.f, 0.f, 0.f};
#pragma unroll
            for (int k = 0; k < 9; k++)
                mma1688(rs + 4 * (k & 1), h2[2 * k], h2[2 * k + 1], wr[k]);
            if (qd < 2) red[256 + (qd * 8 + g8) * 8 + cw] = qd ? rs[2] + rs[6] : rs[0] + rs[4];
            bar_sync(3, 256);
            const float4 r0 = st4[64 + l16 * 2], r1 = st4[65 + l16 * 2];
            const uint32_t b = __float_as_uint(((r0.x + r0.y) + (r0.z + r0.w)) + ((r1.x + r1.y) + (r1.z + r1.w)));
            const uint32_t key = (((b & 0x80000000u) ? ~b : (b | 0x80000000u)) | 2047u) - (rg * 16 + l16);
            top2(key, k1, k2);
            if (tid < CREP) st_relaxed(&g_cand[(tid * NCTA + rg) * 2], k1, tag, k2, tag);
            cv = make_uint2((tid & 1) ? k2 : k1, tag);
            if ((tid >> 1) != rg) cv = ld_relaxed64(candp);
            uint32_t todo = (((1u << (~k1 & 15)) | (1u << (~k2 & 15))) >> g8) & 0x101;
#pragma unroll 1
            while (todo) {
                const bool hi = !(todo & 1);
                uint4* dst = &g_rows[(rg * 16 + g8 + hi * 8) * (D_ / 2) + cw * 4 + qd];
                uint2* dst4 = reinterpret_cast<uint2*>(dst + 128 - cw * 4 + (cw >> 1) * 4) + (cw & 1);
#pragma unroll
                for (int ch = 0; ch < 4; ch++) st_relaxed(dst + ch * 32, hi ? h2[4 * ch + 1] : h2[4 * ch], tag, hi ? h2[4 * ch + 3] : h2[4 * ch + 2], tag);
                st_relaxed64(dst4, hi ? h2[17] : h2[16], tag);
#pragma unroll
                for (int ch = 0; ch < 4; ch++) st_relaxed(dst + D_ / 4 + ch * 32, hi ? x1[4 * ch + 1] : x1[4 * ch], tag, hi ? x1[4 * ch + 3] : x1[4 * ch + 2], tag);
                st_relaxed64(dst4 + D_ / 2, hi ? x1[17] : x1[16], tag);
                todo &= todo - 1;
            }
            __syncwarp();
            stage_out();
        }
        DBG_G(110);
        float2* part = reinterpret_cast<float2*>(smem_raw + SLOT);
        bf16* act = reinterpret_cast<bf16*>(smem_raw + SLOT + 4096);
        {
            uint32_t it = 0;
#pragma unroll 1
            while (cv.y != tag && ++it < SPIN / 16) cv = ld_relaxed64(candp);
            __syncwarp();
            top2(cv.x, k1, k2);
            if (lane == 0) reinterpret_cast<uint2*>(red + 384)[cw] = make_uint2(k1, k2);
            bar_sync(3, 256);
            DBG_G(111);
            top2(reinterpret_cast<const uint32_t*>(red + 384)[l16], k1, k2);
        }
        const int sel0 = ~k1 & 2047, sel1 = ~k2 & 2047;
        uint4 b[9], b2[3];
        {
            uint2* hs = reinterpret_cast<uint2*>(smem_raw + SLOT + 8192);
            const uint4 *p0 = &g_rows[sel0 * (D_ / 2) + tid], *p1 = &g_rows[sel1 * (D_ / 2) + tid];
            uint4 v0 = make_uint4(0, tag, 0, tag), v1 = v0;
            if (tid < D_ / 4) { v0 = ld_relaxed2(p0); v1 = ld_relaxed2(p1); }
            load_wf(IC<WF0>{}, IC<27>{});
            mbar_wait(bar_full + 8 * 2, 0);
            mbar_wait(bar_full + 8 * 3, 0);
            {
                const uint32_t da = sb + (lane < 18 ? 2 * SLOT + lane * XP : 3 * SLOT + (lane - 18) * XP) + cw * 144;
                const uint32_t db = sb + 3 * SLOT + (14 + (lane & 3)) * XP + cw * 144 + (lane >> 3) * 16;
#pragma unroll
                for (int i = 0; i < 9; i++) b[i] = ldsm4t(da + i * 16);
#pragma unroll
                for (int i = 0; i < 3; i++) b2[i] = ldsm4t(db + i * 48);
            }
            uint32_t it = 0;
#pragma unroll 1
            while (((v0.y ^ tag) | (v0.w ^ tag) | (v1.y ^ tag) | (v1.w ^ tag)) && ++it < SPIN / 16) { v0 = ld_relaxed2(p0); v1 = ld_relaxed2(p1); }
            if (tid < D_ / 4) {
                hs[tid] = make_uint2(v0.x, v0.z);
                hs[148 + tid] = make_uint2(v1.x, v1.z);
            }
            bar_sync(3, 256);
            DBG_G(112);
            if (tid == 255) {
                reinterpret_cast<int2*>(red + 416)[0] = make_int2(sel0, sel1);
                mbar_arrive(bar_out);
            }
            uint2 bv[9];
#pragma unroll
            for (int i = 0; i < 9; i++) bv[i] = hs[(g8 & 1) * 148 + (cw >> 1) * 36 + i * 4 + qd];
            float acc[24];
#pragma unroll
            for (int i = 0; i < 24; i++) acc[i] = 0.f;
#pragma unroll
            for (int i = 0; i < 27; i++) mma16816(acc + 4 * (i % 6), wf[i].x, wf[i].y, wf[i].z, wf[i].w, bv[i / 3].x, bv[i / 3].y);
            if (qd == 0) {
#pragma unroll
                for (int i = 0; i < 5; i++) part[cw * 48 + i * 8 + g8] = make_float2(acc[2 * i] + acc[12 + 2 * i], acc[2 * i + 1] + acc[13 + 2 * i]);
            }
        }
        {
            uint2* dst = &g_ypart[(((g8 & 1) * 36 + ((cw * 9) >> 1)) * NCTA + blockIdx.x) * 8 + (cw & 1) * 4 + qd];
            uint2* dst1 = dst + ((cw & 1) ? NCTA * 8 - 4 : 4);
            bar_sync(3, 256);
            {
                const float* pp = reinterpret_cast<const float*>(part) + ((blockIdx.x & 1) << 3) + (tid & 127);
                const float gs = rbf((pp[0] + pp[192]) + (pp[384] + pp[576])), us = rbf((pp[96] + pp[288]) + (pp[480] + pp[672]));
                const float v = rbf(gs * sigmoidf_(gs)) * us;
                if (tid < 80) act[(tid & 1) * 56 + (tid >> 1)] = __float2bfloat16_rn(tid < 72 ? v : 0.f);
            }
            bar_sync(3, 256);
            DBG_G(113);
            const uint32_t ap = sb + SLOT + 4096 + (lane & 1) * 112 + (lane >> 4) * 16;
            const uint4 a0 = ldsm4(ap), a1 = ldsm4(ap + 32), a2 = ldsm4(ap + 64);
            float y[36];
#pragma unroll
            for (int i = 0; i < 36; i++) y[i] = 0.f;
#pragma unroll
            for (int i = 0; i < 9; i++) {
                const uint32_t bl = i % 3 == 0 ? b2[i / 3].x : i % 3 == 1 ? b2[i / 3].y : b2[i / 3].z;
                mma16816(y + 4 * i, a0.x, a0.y, a0.z, a0.w, b[i].x, b[i].y);
                mma16816(y + 4 * i, a1.x, a1.y, a1.z, a1.w, b[i].z, b[i].w);
                mma1688(y + 4 * i, a2.x, a2.y, bl);
            }
#pragma unroll
            for (int i = 0; i < 9; i++)
                if (lane < 8) st_relaxed64(((i & 1) ? dst1 : dst) + (i >> 1) * (NCTA * 8), __float_as_uint(y[4 * i]), __float_as_uint(y[4 * i + 1]));
        }
        DBG_G(114);
        if (blockIdx.x == 127 && tid == 0) g_epoch = tag + 1;
        if (blockIdx.x < 72) {
            const int tok = blockIdx.x >= 36, grp = blockIdx.x - tok * 36;
            const uint2* src = &g_ypart[blockIdx.x * NCTA * 8 + tid];
            const uint4* hsrc = &g_rows[(tok ? sel1 : sel0) * (D_ / 2) + grp * 4 + qd];
            uint2 v[4];
            uint4 hv, xv;
            uint32_t it = 0;
            bool miss;
#pragma unroll 1
            do {
#pragma unroll
                for (int i = 0; i < 4; i++) v[i] = ld_relaxed64(src + i * 256);
                hv = ld_relaxed2(hsrc);
                xv = ld_relaxed2(hsrc + D_ / 4);
                miss = max(__vimax3_u32(v[0].x, v[1].x, v[2].x), v[3].x) == ~0u || ((hv.y ^ tag) | (hv.w ^ tag) | (xv.y ^ tag) | (xv.w ^ tag));
            } while (__any_sync(0xffffffffu, miss) && ++it < SPIN / 16);
            const uint32_t ksel = ((tok ? k2 : k1) & ~2047u) | 1024u;
            const float sg = sigmoidf_(rbf(__uint_as_float((ksel & 0x80000000u) ? (ksel & 0x7fffffffu) : ~ksel)));
            float y0 = (__uint_as_float(v[0].x) + __uint_as_float(v[1].x)) + (__uint_as_float(v[2].x) + __uint_as_float(v[3].x));
            float y1 = (__uint_as_float(v[0].y) + __uint_as_float(v[1].y)) + (__uint_as_float(v[2].y) + __uint_as_float(v[3].y));
            y0 += __shfl_xor_sync(0xffffffffu, y0, 8); y1 += __shfl_xor_sync(0xffffffffu, y1, 8);
            y0 += __shfl_xor_sync(0xffffffffu, y0, 16); y1 += __shfl_xor_sync(0xffffffffu, y1, 16);
            if (lane < 8) reinterpret_cast<float2*>(red)[cw * 8 + lane] = make_float2(y0, y1);
            bar_sync(3, 256);
            if (cw == 0) {
                const float2 t0_ = reinterpret_cast<const float2*>(red)[lane], t1_ = reinterpret_cast<const float2*>(red)[32 + lane];
                y0 = t0_.x + t1_.x; y1 = t0_.y + t1_.y;
                y0 += __shfl_xor_sync(0xffffffffu, y0, 8); y1 += __shfl_xor_sync(0xffffffffu, y1, 8);
                y0 += __shfl_xor_sync(0xffffffffu, y0, 16); y1 += __shfl_xor_sync(0xffffffffu, y1, 16);
                const uint32_t y2 = bmul2(pack_bf16(y0, y1), pack_bf16(sg, sg));
                const int cp = grp * 8 + (lane & 7);
                const uint32_t gb = reinterpret_cast<const uint2*>(mbase + M_MOD)[3 * (D_ / 2) + cp].x;
                if (lane < 8)
                    reinterpret_cast<uint32_t*>(args.out + (size_t)(tok ? sel1 : sel0) * D_)[cp] =
                        badd2((lane & 4) ? xv.z : xv.x, bmul2(gb, badd2((lane & 4) ? hv.z : hv.x, y2)));
            }
        }
        }
        DBG_T(88);
        DBG_G(121);
    }
}

typedef CUresult (*EncodeFn)(CUtensorMap*, CUtensorMapDataType, cuuint32_t, void*, const cuuint64_t*, const cuuint64_t*,
                             const cuuint32_t*, const cuuint32_t*, CUtensorMapInterleave, CUtensorMapSwizzle,
                             CUtensorMapL2promotion, CUtensorMapFloatOOBfill);

static void make_map(EncodeFn enc, CUtensorMap* m, const void* ptr, int rank, const cuuint64_t* dims,
                     const cuuint64_t* strides, const cuuint32_t* box, CUtensorMapSwizzle sw = CU_TENSOR_MAP_SWIZZLE_128B,
                     CUtensorMapDataType dt = CU_TENSOR_MAP_DATA_TYPE_BFLOAT16) {
    const cuuint32_t es[3] = {1, 1, 1};
    enc(m, dt, rank, const_cast<void*>(ptr), dims, strides, box, es,
        CU_TENSOR_MAP_INTERLEAVE_NONE, sw, CU_TENSOR_MAP_L2_PROMOTION_L2_128B,
        CU_TENSOR_MAP_FLOAT_OOB_FILL_NONE);
}

extern "C" void kernel_launch(void* const* d_in, const int* in_sizes, int n_in, void* d_out, int out_size) {
    const bf16* x = (const bf16*)d_in[0];
    const bf16* kc = (const bf16*)d_in[1];
    const bf16* vc = (const bf16*)d_in[2];
    const bf16* wq = (const bf16*)d_in[3];
    const bf16* wo = (const bf16*)d_in[4];
    const bf16* w_r = (const bf16*)d_in[6];
    const bf16* w_gate = (const bf16*)d_in[7];
    const bf16* w_up = (const bf16*)d_in[8];
    const bf16* w_down = (const bf16*)d_in[9];
    const bf16* cvec = (const bf16*)d_in[10];
    const bf16* w_mod = (const bf16*)d_in[11];
    bf16* out = (bf16*)d_out;

    void* fn = nullptr;
    cudaDriverEntryPointQueryResult qr;
    cudaGetDriverEntryPoint("cuTensorMapEncodeTiled", &fn, cudaEnableDefault, &qr);
    EncodeFn enc = (EncodeFn)fn;
    void* p_frag;
    cudaGetSymbolAddress(&p_frag, g_s);

    CUtensorMap tm_wq, tm_k, tm_v, tm_wo, tm_p, tm_x, tm_d, tm_g, tm_u;
    { cuuint64_t d[2] = {QD, D_}, s[1] = {QD * 2}; cuuint32_t b[2] = {64, 128}; make_map(enc, &tm_wq, wq, 2, d, s, b); }
    { cuuint64_t d[2] = {DH, HKV * S_}, s[1] = {DH * 2}; cuuint32_t b[2] = {64, 128};
      make_map(enc, &tm_k, kc, 2, d, s, b); make_map(enc, &tm_v, vc, 2, d, s, b); }
    { cuuint64_t d[2] = {D_, QD}, s[1] = {D_ * 2}; cuuint32_t b[2] = {64, 128}; make_map(enc, &tm_wo, wo, 2, d, s, b); }
    { cuuint64_t d[3] = {256, 160, NCTA}, s[2] = {1024, 8 * WREG}; cuuint32_t b[3] = {256, 4, 8};
      make_map(enc, &tm_p, p_frag, 3, d, s, b, CU_TENSOR_MAP_SWIZZLE_NONE, CU_TENSOR_MAP_DATA_TYPE_UINT32); }
    { cuuint64_t d[2] = {D_ / 4, S_}, s[1] = {D_ * 2}; cuuint32_t b[2] = {XP / 8, 16};
      make_map(enc, &tm_x, x, 2, d, s, b, CU_TENSOR_MAP_SWIZZLE_NONE, CU_TENSOR_MAP_DATA_TYPE_UINT64); }
    { cuuint64_t d[2] = {D_ / 4, F_}, s[1] = {D_ * 2}; cuuint32_t b[2] = {XP / 8, 18};
      make_map(enc, &tm_d, w_down, 2, d, s, b, CU_TENSOR_MAP_SWIZZLE_NONE, CU_TENSOR_MAP_DATA_TYPE_UINT64); }
    { cuuint64_t d[2] = {F_, D_}, s[1] = {F_ * 2}; cuuint32_t b[2] = {40, 24};
      make_map(enc, &tm_g, w_gate, 2, d, s, b, CU_TENSOR_MAP_SWIZZLE_NONE); make_map(enc, &tm_u, w_up, 2, d, s, b, CU_TENSOR_MAP_SWIZZLE_NONE); }

    cudaFuncSetAttribute(fused_kernel<true>, cudaFuncAttributeMaxDynamicSharedMemorySize, SM_TOTAL);
    cudaFuncSetAttribute(fused_kernel<false>, cudaFuncAttributeMaxDynamicSharedMemorySize, SM_TOTAL);
    cudaLaunchConfig_t cfg = {};
    cfg.gridDim = NCTA + 4; cfg.blockDim = 384; cfg.dynamicSmemBytes = SM_TOTAL;
    cudaLaunchAttribute at;
    at.id = cudaLaunchAttributeClusterDimension; at.val.clusterDim.x = 2; at.val.clusterDim.y = 1; at.val.clusterDim.z = 1;
    cfg.attrs = &at; cfg.numAttrs = 1;
    int ncl = 0;
    if (cudaOccupancyMaxActiveClusters(&ncl, fused_kernel<true>, &cfg) != cudaSuccess) { ncl = 0; cudaGetLastError(); }
    Args args{x, kc, vc, wq, wo, w_r, w_gate, w_up, w_down, cvec, w_mod, out};
    if (USE_SPARE && ncl >= NCTA / 2 + 2)
        fused_kernel<true><<<NCTA + 4, 384, SM_TOTAL>>>(tm_wq, tm_k, tm_v, tm_wo, tm_p, tm_x, tm_d, tm_g, tm_u, args);
    else
        fused_kernel<false><<<NCTA, 384, SM_TOTAL>>>(tm_wq, tm_k, tm_v, tm_wo, tm_p, tm_x, tm_d, tm_g, tm_u, args);
}
```

```cpp
#include <cuda_runtime.h>
#include <cuda_bf16.h>
#include <cuda.h>
#include <stdint.h>
#include <math.h>

typedef __nv_bfloat16 bf16;

constexpr int S_ = 2048;
constexpr int D_ = 576;
constexpr int HQ = 32, HKV = 16, DH = 128;
constexpr int F_ = 4608;
constexpr int QD = HQ * DH;

constexpr int NCTA = 128;
constexpr int WREG = 5 * 4096;
constexpr int CREP = 8;
constexpr int MREP = 4;
struct Scratch {
    unsigned int epoch[128];
    unsigned int flag_mod[NCTA];
    unsigned int flag_part[16 * 32];
    unsigned int flag_q3[16 * 32];
    unsigned int flag_h[NCTA * 32];
    uint2 mod1[MREP * D_];
    uint2 mod2[2 * D_];
    uint4 cand[CREP * NCTA * 2];
    uint2 ypart[72 * NCTA * 8];
    uint4 h[NCTA * 36 * 32];
    uint4 q3[NCTA * 8 * 128];
    uint4 rows[S_ * (D_ / 2)];
    uint8_t frag[NCTA * 8 * WREG];
    uint8_t keep[NCTA * 8 * 4096];
};
__device__ __align__(1024) Scratch g_s;
#define g_h gs->h
#define g_q3 gs->q3
#define g_keep gs->keep
#define g_flag_h gs->flag_h
#define g_flag_part gs->flag_part
#define g_flag_mod gs->flag_mod
#define g_flag_q3 gs->flag_q3
#define g_frag gs->frag
#define g_cand gs->cand
#define g_ypart gs->ypart
#define g_rows gs->rows

#define DBG_INIT()
#define DBG_P(i)
#define DBG_PG(i)
#define DBG_T(i)
#define DBG_G(i)

__device__ __forceinline__ uint32_t pack_bf16(float lo, float hi) {
    uint32_t r;
    asm("cvt.rn.bf16x2.f32 %0, %1, %2;" : "=r"(r) : "f"(hi), "f"(lo));
    return r;
}
__device__ __forceinline__ float rbf(float x) { return __uint_as_float(pack_bf16(0.f, x)); }
__device__ __forceinline__ float bf_lo(uint32_t v) { return __uint_as_float(v << 16); }
__device__ __forceinline__ float bf_hi(uint32_t v) { return __uint_as_float(v & 0xffff0000u); }
__device__ __forceinline__ float ex2(float x) {
    float y;
    asm("ex2.approx.ftz.f32 %0, %1;" : "=f"(y) : "f"(x));
    return y;
}
__device__ __forceinline__ uint32_t smem_u32(const void* p) { return (uint32_t)__cvta_generic_to_shared(p); }
__device__ __forceinline__ void mbar_init(uint32_t bar, uint32_t cnt) {
    asm volatile("mbarrier.init.shared::cta.b64 [%0], %1;" ::"r"(bar), "r"(cnt) : "memory");
}
__device__ __forceinline__ void mbar_expect_tx(uint32_t bar, uint32_t bytes) {
    asm volatile("mbarrier.arrive.expect_tx.shared::cta.b64 _, [%0], %1;" ::"r"(bar), "r"(bytes) : "memory");
}
__device__ __forceinline__ void mbar_arrive(uint32_t bar) {
    asm volatile("mbarrier.arrive.shared::cta.b64 _, [%0];" ::"r"(bar) : "memory");
}
__device__ __forceinline__ void mbar_arrive_cluster(uint32_t cluster_addr) {
    asm volatile("mbarrier.arrive.shared::cluster.b64 _, [%0];" ::"r"(cluster_addr) : "memory");
}
constexpr uint32_t SPIN = 1u << 20;
__device__ __forceinline__ void mbar_wait(uint32_t bar, uint32_t parity) {
    asm volatile("{\n.reg .pred p;\n.reg .b32 c;\nmov.b32 c, 0;\n"
                 "W_%=:\nmbarrier.try_wait.parity.shared::cta.b64 p, [%0], %1;\n@p bra D_%=;\n"
                 "add.u32 c, c, 1;\nsetp.lt.u32 p, c, 0x100000;\n@p bra W_%=;\nD_%=:\n}"
                 ::"r"(bar), "r"(parity) : "memory");
}
__device__ __forceinline__ void anchor(uint32_t addr, float v) {
    asm volatile("{\n.reg .pred p;\nsetp.lt.f32 p, %1, 0f00000000;\n@p st.volatile.shared.f32 [%0], %1;\n}" ::"r"(addr), "f"(v) : "memory");
}
__device__ __forceinline__ void mbar_wait_sleep(uint32_t bar, uint32_t parity) {
    asm volatile("{\n.reg .pred p;\n.reg .b32 c;\nmov.b32 c, 0;\n"
                 "W_%=:\nmbarrier.try_wait.parity.shared::cta.b64 p, [%0], %1, 5000;\n@p bra D_%=;\n"
                 "add.u32 c, c, 1;\nsetp.lt.u32 p, c, 0x20000;\n@p bra W_%=;\nD_%=:\n}"
                 ::"r"(bar), "r"(parity) : "memory");
}
__device__ __forceinline__ uint32_t load_tag(const Scratch* gs) {
    uint32_t tag;
    asm volatile("ld.global.ca.u32 %0, [%1];" : "=r"(tag) : "l"(gs->epoch) : "memory");
    return tag + 1;
}
__device__ __forceinline__ uint4 ld_relaxed(const uint4* p) {
    uint4 v;
    asm volatile("ld.relaxed.gpu.global.v4.u32 {%0,%1,%2,%3}, [%4];" : "=r"(v.x), "=r"(v.y), "=r"(v.z), "=r"(v.w) : "l"(p) : "memory");
    return v;
}
__device__ __forceinline__ void st_relaxed(uint4* p, uint32_t a, uint32_t b, uint32_t c, uint32_t d) {
    asm volatile("{\n.reg .b64 u, v;\nmov.b64 u, {%1, %2};\nmov.b64 v, {%3, %4};\nst.relaxed.gpu.global.v2.b64 [%0], {u, v};\n}"
                 ::"l"(p), "r"(a), "r"(b), "r"(c), "r"(d) : "memory");
}
__device__ __forceinline__ void st_relaxed4(void* p, uint32_t a, uint32_t b, uint32_t c, uint32_t d) {
    asm volatile("st.relaxed.gpu.global.v4.u32 [%0], {%1, %2, %3, %4};" ::"l"(p), "r"(a), "r"(b), "r"(c), "r"(d) : "memory");
}
__device__ __forceinline__ uint2 ld_relaxed8(const void* p) {
    uint2 v;
    asm volatile("ld.relaxed.gpu.global.v2.u32 {%0,%1}, [%2];" : "=r"(v.x), "=r"(v.y) : "l"(p) : "memory");
    return v;
}
__device__ __forceinline__ uint2 ld_relaxed64(const uint2* p) {
    uint2 v;
    asm volatile("{\n.reg .b64 u;\nld.relaxed.gpu.global.b64 u, [%2];\nmov.b64 {%0, %1}, u;\n}" : "=r"(v.x), "=r"(v.y) : "l"(p) : "memory");
    return v;
}
__device__ __forceinline__ void st_relaxed64(uint2* p, uint32_t a, uint32_t b) {
    asm volatile("{\n.reg .b64 u;\nmov.b64 u, {%1, %2};\nst.relaxed.gpu.global.b64 [%0], u;\n}" ::"l"(p), "r"(a), "r"(b) : "memory");
}
__device__ __forceinline__ uint4 ld_relaxed2(const uint4* p) {
    uint4 v;
    asm volatile("{\n.reg .b64 u, w;\nld.relaxed.gpu.global.v2.b64 {u, w}, [%4];\nmov.b64 {%0, %1}, u;\nmov.b64 {%2, %3}, w;\n}"
                 : "=r"(v.x), "=r"(v.y), "=r"(v.z), "=r"(v.w) : "l"(p) : "memory");
    return v;
}
__device__ __forceinline__ void poll2x2(const uint4* p0, const uint4* p1, uint32_t tag, uint4& o0, uint4& o1) {
    uint4 v0, v1;
    uint32_t miss, it = 0;
#pragma unroll 1
    do {
        v0 = ld_relaxed2(p0); v1 = ld_relaxed2(p1);
        miss = (v0.y ^ tag) | (v0.w ^ tag) | (v1.y ^ tag) | (v1.w ^ tag);
    } while (miss && ++it < SPIN / 16);
    o0 = v0; o1 = v1;
}
__device__ __forceinline__ void flag_wait(const unsigned int* p, uint32_t tag) {
    uint32_t v, it = 0;
#pragma unroll 1
    do {
        asm volatile("ld.relaxed.gpu.global.u32 %0, [%1];" : "=r"(v) : "l"(p) : "memory");
    } while (__any_sync(0xffffffffu, v != tag) && ++it < SPIN / 16);
    asm volatile("fence.acquire.gpu;" ::: "memory");
    __syncwarp();
}
__device__ __forceinline__ bool elect() {
    uint32_t p;
    asm volatile("{\n.reg .pred p;\nelect.sync _|p, 0xffffffff;\nselp.u32 %0, 1, 0, p;\n}" : "=r"(p));
    return p;
}
__device__ __forceinline__ void flag_release(unsigned int* p, uint32_t tag) {
    asm volatile("st.release.gpu.global.u32 [%0], %1;" ::"l"(p), "r"(tag) : "memory");
}
__device__ __forceinline__ uint32_t touch(const void* p) {
    uint32_t v;
    asm volatile("ld.global.nc.L1::no_allocate.L2::128B.u32 %0, [%1];" : "=r"(v) : "l"(p));
    return v;
}
__device__ __forceinline__ void bar_sync(int id, int n) { asm volatile("bar.sync %0, %1;" ::"r"(id), "r"(n) : "memory"); }
__device__ __forceinline__ void bar_arrive(int id, int n) { asm volatile("bar.arrive %0, %1;" ::"r"(id), "r"(n) : "memory"); }

constexpr uint64_t EVICT_NORMAL = 0x1000000000000000ull, EVICT_FIRST = 0x12F0000000000000ull;
__device__ __forceinline__ void tma2d(uint32_t dst, const CUtensorMap* m, int c0, int c1, uint32_t bar) {
    asm volatile("cp.async.bulk.tensor.2d.shared::cluster.global.mbarrier::complete_tx::bytes.L2::cache_hint [%0], [%1, {%3, %4}], [%2], %5;"
                 ::"r"(dst), "l"(m), "r"(bar), "r"(c0), "r"(c1), "l"(EVICT_FIRST) : "memory");
}
__device__ __forceinline__ void tma2d_mc(uint32_t dst, const CUtensorMap* m, int c0, int c1, uint32_t bar, uint64_t pol) {
    asm volatile("cp.async.bulk.tensor.2d.shared::cluster.global.mbarrier::complete_tx::bytes.multicast::cluster.L2::cache_hint [%0], [%1, {%3, %4}], [%2], %5, %6;"
                 ::"r"(dst), "l"(m), "r"(bar), "r"(c0), "r"(c1), "h"((uint16_t)3), "l"(pol) : "memory");
}
__device__ __forceinline__ void tma3d(uint32_t dst, const CUtensorMap* m, int c0, int c1, int c2, uint32_t bar) {
    asm volatile("cp.async.bulk.tensor.3d.shared::cluster.global.mbarrier::complete_tx::bytes.L2::cache_hint [%0], [%1, {%3, %4, %5}], [%2], %6;"
                 ::"r"(dst), "l"(m), "r"(bar), "r"(c0), "r"(c1), "r"(c2), "l"(EVICT_FIRST) : "memory");
}
__device__ __forceinline__ void bulk_load(uint32_t dst, const void* src, uint32_t bytes, uint32_t bar) {
    asm volatile("cp.async.bulk.shared::cluster.global.mbarrier::complete_tx::bytes [%0], [%1], %2, [%3];"
                 ::"r"(dst), "l"(src), "r"(bytes), "r"(bar) : "memory");
}
__device__ __forceinline__ void l2_prefetch(const void* src, uint32_t bytes) {
    asm volatile("cp.async.bulk.prefetch.L2.global [%0], %1;" ::"l"(src), "r"(bytes) : "memory");
}
__device__ __forceinline__ uint32_t bmul2(uint32_t a, uint32_t b) { uint32_t r; asm("mul.rn.bf16x2 %0, %1, %2;" : "=r"(r) : "r"(a), "r"(b)); return r; }
__device__ __forceinline__ uint32_t badd2(uint32_t a, uint32_t b) { uint32_t r; asm("add.rn.bf16x2 %0, %1, %2;" : "=r"(r) : "r"(a), "r"(b)); return r; }
__device__ __forceinline__ uint32_t bsub2(uint32_t a, uint32_t b) { uint32_t r; asm("sub.rn.bf16x2 %0, %1, %2;" : "=r"(r) : "r"(a), "r"(b)); return r; }
__device__ __forceinline__ uint32_t bmax2(uint32_t a, uint32_t b) { uint32_t r; asm("max.bf16x2 %0, %1, %2;" : "=r"(r) : "r"(a), "r"(b)); return r; }
__device__ __forceinline__ uint32_t bfma2(uint32_t a, uint32_t b, uint32_t c) { uint32_t r; asm("fma.rn.bf16x2 %0, %1, %2, %3;" : "=r"(r) : "r"(a), "r"(b), "r"(c)); return r; }
__device__ __forceinline__ uint4 lds128(uint32_t a) { uint4 v; asm volatile("ld.shared.v4.u32 {%0,%1,%2,%3}, [%4];" : "=r"(v.x), "=r"(v.y), "=r"(v.z), "=r"(v.w) : "r"(a) : "memory"); return v; }
__device__ __forceinline__ uint4 ldsm4(uint32_t a) {
    uint4 v;
    asm volatile("ldmatrix.sync.aligned.m8n8.x4.shared.b16 {%0,%1,%2,%3}, [%4];" : "=r"(v.x), "=r"(v.y), "=r"(v.z), "=r"(v.w) : "r"(a) : "memory");
    return v;
}
__device__ __forceinline__ uint4 ldsm4t(uint32_t a) {
    uint4 v;
    asm volatile("ldmatrix.sync.aligned.m8n8.x4.trans.shared.b16 {%0,%1,%2,%3}, [%4];" : "=r"(v.x), "=r"(v.y), "=r"(v.z), "=r"(v.w) : "r"(a) : "memory");
    return v;
}
__device__ __forceinline__ void mma1688(float* d, uint32_t a0, uint32_t a1, uint32_t b) {
    asm("mma.sync.aligned.m16n8k8.row.col.f32.bf16.bf16.f32 {%0,%1,%2,%3}, {%4,%5}, {%6}, {%0,%1,%2,%3};"
        : "+f"(d[0]), "+f"(d[1]), "+f"(d[2]), "+f"(d[3]) : "r"(a0), "r"(a1), "r"(b));
}
__device__ __forceinline__ void mma16816(float* d, uint32_t a0, uint32_t a1, uint32_t a2, uint32_t a3, uint32_t b0, uint32_t b1) {
    asm("mma.sync.aligned.m16n8k16.row.col.f32.bf16.bf16.f32 {%0,%1,%2,%3}, {%4,%5,%6,%7}, {%8,%9}, {%0,%1,%2,%3};"
                 : "+f"(d[0]), "+f"(d[1]), "+f"(d[2]), "+f"(d[3]) : "r"(a0), "r"(a1), "r"(a2), "r"(a3), "r"(b0), "r"(b1));
}
__device__ __forceinline__ void stsm_x4(uint32_t addr, uint32_t a, uint32_t b, uint32_t c, uint32_t d) {
    asm volatile("stmatrix.sync.aligned.m8n8.x4.shared.b16 [%0], {%1, %2, %3, %4};"
                 ::"r"(addr), "r"(a), "r"(b), "r"(c), "r"(d) : "memory");
}

__device__ __forceinline__ uint64_t mkdesc(uint32_t addr, uint32_t lbo, uint32_t sbo) {
    return (uint64_t)((addr & 0x3FFFF) >> 4) | ((uint64_t)(lbo >> 4) << 16) | ((uint64_t)(sbo >> 4) << 32) | (1ull << 62);
}
constexpr uint32_t SM0 = 1024;
__host__ __device__ constexpr uint32_t desc_lo(uint32_t off, uint32_t lbo) { return ((SM0 + off) >> 4) | ((lbo >> 4) << 16); }
__device__ __forceinline__ uint64_t desc_of(uint32_t lo) { return lo | (0x40000040ull << 32); }
#define WG_FENCE() asm volatile("wgmma.fence.sync.aligned;" ::: "memory")
#define WG_COMMIT() asm volatile("wgmma.commit_group.sync.aligned;" ::: "memory")
#define WG_WAIT(n) asm volatile("wgmma.wait_group.sync.aligned %0;" ::"n"(n) : "memory")

#define F8(a, i) "+f"(a[i]), "+f"(a[i + 1]), "+f"(a[i + 2]), "+f"(a[i + 3]), "+f"(a[i + 4]), "+f"(a[i + 5]), "+f"(a[i + 6]), "+f"(a[i + 7])
#define F16(a, i) F8(a, i), F8(a, i + 8)
#define F64(a) F16(a, 0), F16(a, 16), F16(a, 32), F16(a, 48)
#define F32(a) F16(a, 0), F16(a, 16)
#define L64 "%0,%1,%2,%3,%4,%5,%6,%7,%8,%9,%10,%11,%12,%13,%14,%15,%16,%17,%18,%19,%20,%21,%22,%23,%24,%25,%26,%27,%28,%29,%30,%31,%32,%33,%34,%35,%36,%37,%38,%39,%40,%41,%42,%43,%44,%45,%46,%47,%48,%49,%50,%51,%52,%53,%54,%55,%56,%57,%58,%59,%60,%61,%62,%63"
#define L32 "%0,%1,%2,%3,%4,%5,%6,%7,%8,%9,%10,%11,%12,%13,%14,%15,%16,%17,%18,%19,%20,%21,%22,%23,%24,%25,%26,%27,%28,%29,%30,%31"

template <int TB>
__device__ __forceinline__ void mma_rs128(float (&d)[64], uint32_t a0, uint32_t a1, uint32_t a2, uint32_t a3, uint64_t b, int acc) {
    asm volatile("{\n.reg .pred p;\nsetp.ne.b32 p, %69, 0;\n"
                 "wgmma.mma_async.sync.aligned.m64n128k16.f32.bf16.bf16 {" L64 "}, {%64,%65,%66,%67}, %68, p, 1, 1, %70;\n}"
                 : F64(d) : "r"(a0), "r"(a1), "r"(a2), "r"(a3), "l"(b), "r"(acc), "n"(TB));
}
template <int TB>
__device__ __forceinline__ void mma_rs64(float (&d)[32], uint32_t a0, uint32_t a1, uint32_t a2, uint32_t a3, uint64_t b, int acc) {
    asm volatile("{\n.reg .pred p;\nsetp.ne.b32 p, %37, 0;\n"
                 "wgmma.mma_async.sync.aligned.m64n64k16.f32.bf16.bf16 {" L32 "}, {%32,%33,%34,%35}, %36, p, 1, 1, %38;\n}"
                 : F32(d) : "r"(a0), "r"(a1), "r"(a2), "r"(a3), "l"(b), "r"(acc), "n"(TB));
}
template <int N>
__device__ __forceinline__ void fence_regs(float (&d)[N]) {
#pragma unroll
    for (int i = 0; i < N; i++) asm volatile("" : "+f"(d[i])::"memory");
}
template <int N>
__device__ __forceinline__ void fence_regs(uint32_t (&d)[N]) {
#pragma unroll
    for (int i = 0; i < N; i++) asm volatile("" : "+r"(d[i])::"memory");
}

template <int V> struct IC { static constexpr int value = V; };

constexpr int SLOT = 32768, UNIT = 16384;
constexpr int SM_Q = 4 * SLOT;
constexpr int SM_BAR = 7 * SLOT;
constexpr int SM_RED = SM_BAR + 512;
constexpr int SM_TOTAL = SM_BAR + 3072;
constexpr int XP = D_ * 2 + 16;
constexpr int M_MOD = 16 * XP, M_WR = M_MOD + 4 * D_ * 4;
constexpr float CS = 0.08838834764831845f * 1.4426950408889634f;
#define LMAX 0.5f
#define LMIN 0x1p-104f
#define USE_SPARE 1
#define MAXG 2
#define SPLIT 10
#define ESPLIT 2
#define PV1 8
#define RW 2
#define HW 2
#define HW2 1
#define XDELAY 200
#define QDELAY 300
#define TMPF 1
#define HPUB 1
#define NOPART 0
#define STAGE 11
#define POFF 102.f
constexpr int WF0 = 24;
constexpr int PF_KV = 8, PF_WO = 120;

struct Args {
    const bf16 *w_mod, *cvec;
    Scratch* gs;
    bf16* out;
    const bf16 *x, *kc, *vc, *wq, *wo, *w_r, *w_down;
};

__device__ __forceinline__ void frag_store(uint8_t* p, const uint32_t (&a)[32]) {
#pragma unroll
    for (int i = 0; i < 8; i++)
        __stcg(reinterpret_cast<uint4*>(p + i * 512), make_uint4(a[4 * i], a[4 * i + 1], a[4 * i + 2], a[4 * i + 3]));
}
__device__ __forceinline__ void frag_load(uint32_t (&a)[32], const uint8_t* p) {
#pragma unroll
    for (int i = 0; i < 8; i++) {
        const uint4 v = __ldcg(reinterpret_cast<const uint4*>(p + i * 512));
        a[4 * i] = v.x; a[4 * i + 1] = v.y; a[4 * i + 2] = v.z; a[4 * i + 3] = v.w;
    }
}
__device__ __forceinline__ float quad_sum(float v) {
    v += __shfl_xor_sync(0xffffffffu, v, 1);
    return v + __shfl_xor_sync(0xffffffffu, v, 2);
}
__device__ __forceinline__ float quad_max(float v) {
    v = fmaxf(v, __shfl_xor_sync(0xffffffffu, v, 1));
    return fmaxf(v, __shfl_xor_sync(0xffffffffu, v, 2));
}
__device__ __forceinline__ float rcp_fast(float x) { float y; asm("rcp.approx.ftz.f32 %0, %1;" : "=f"(y) : "f"(x)); return y; }
__device__ __forceinline__ float sigmoidf_(float x) { return rcp_fast(1.f + ex2(-1.4426950408889634f * x)); }
__device__ __forceinline__ void top2(uint32_t k, uint32_t& k1, uint32_t& k2) {
    k1 = __reduce_max_sync(0xffffffffu, k);
    k2 = __reduce_max_sync(0xffffffffu, k == k1 ? 0 : k);
}

__device__ __forceinline__ void mod_fma(float (&a)[8], const uint4 w, float sc) {
    a[0] += sc * bf_lo(w.x); a[1] += sc * bf_hi(w.x); a[2] += sc * bf_lo(w.y); a[3] += sc * bf_hi(w.y);
    a[4] += sc * bf_lo(w.z); a[5] += sc * bf_hi(w.z); a[6] += sc * bf_lo(w.w); a[7] += sc * bf_hi(w.w);
}
__device__ __forceinline__ float mod_reduce(float (&a)[8], int lane) {
#pragma unroll
    for (int h = 4; h > 0; h >>= 1) {
        const bool up = lane & (8 / h);
#pragma unroll
        for (int i = 0; i < h; i++)
            a[i] = (up ? a[i + h] : a[i]) + __shfl_xor_sync(0xffffffffu, up ? a[i] : a[i + h], 8 / h);
    }
    return a[0] + __shfl_xor_sync(0xffffffffu, a[0], 16);
}

__device__ __forceinline__ float ln_stats(float sum, float sq, uint32_t& mean2) {
    const float mean = sum * (1.f / D_);
    const float var = fmaxf(fmaf(-mean, mean, sq * (1.f / D_)), 0.f);
    float sd;
    asm("sqrt.approx.ftz.f32 %0, %1;" : "=f"(sd) : "f"(rbf(rbf(var) + 1e-5f)));
    mean2 = pack_bf16(mean, mean);
    return rcp_fast(rbf(sd));
}
__device__ __forceinline__ uint32_t ln_pair(uint32_t x, uint32_t mean2, float rsd) {
    const uint32_t d = bsub2(x, mean2);
    return pack_bf16(bf_lo(d) * rsd, bf_hi(d) * rsd);
}
__device__ __forceinline__ void rows_load(uint32_t (&x)[20], uint32_t xs, int cw) {
#pragma unroll
    for (int ch = 0; ch < 5; ch++) {
        const uint4 v = ldsm4(ch < 4 ? xs + ch * 256 : xs + 1024 - cw * 16);
        x[4 * ch] = v.x; x[4 * ch + 1] = v.y; x[4 * ch + 2] = v.z; x[4 * ch + 3] = v.w;
    }
}
__device__ __forceinline__ void stats_add(float (&st)[12], uint32_t a, uint32_t b) {
    mma1688(st, a, b, 0x3f803f80u);
    mma1688(st + 4, a, b, a);
    mma1688(st + 8, a, b, b);
}
__device__ __forceinline__ void rows_normalise(uint32_t* y, const uint32_t* x, const float (&st)[12], float4* st4, int cw, int lane) {
    const int g8 = lane >> 2, qd = lane & 3;
    if ((g8 >> 1) == qd) st4[g8 * 8 + cw] = make_float4(st[0], (g8 & 1) ? st[5] : st[4], st[2], (g8 & 1) ? st[11] : st[10]);
    bar_sync(3, 256);
    const float4 s0 = st4[g8 * 8 + qd], s1 = st4[g8 * 8 + 4 + qd];
    uint32_t ma2, mb2;
    const float ra = ln_stats(quad_sum(s0.x + s1.x), quad_sum(s0.y + s1.y), ma2);
    const float rb = ln_stats(quad_sum(s0.z + s1.z), quad_sum(s0.w + s1.w), mb2);
#pragma unroll
    for (int k = 0; k < 9; k++) { y[2 * k] = ln_pair(x[2 * k], ma2, ra); y[2 * k + 1] = ln_pair(x[2 * k + 1], mb2, rb); }
}
__device__ __forceinline__ uint32_t pair_of(const uint2* mp, int k, int cw) {
    return (k < 8 ? mp[(k >> 1) * 64 + (k & 1) * 4] : (mp - cw * 4)[256]).x;
}

__device__ __noinline__ void attn_fallback(uint32_t bad, uint8_t* frag, uint8_t* keep, const bf16* wq, const bf16* kc, const bf16* vc) {
  const Scratch* gs = &g_s;
  const int lane = threadIdx.x & 31, g8 = lane >> 2, qd = lane & 3;
  const int j = (blockIdx.x >> 1) & 7, qb = (blockIdx.x >> 4) * 2 + (blockIdx.x & 1);
  const uint4* hf = g_h + (size_t)(qb * 8 + (threadIdx.x >> 5) - 4) * (36 * 32) + lane;
#pragma unroll 1
  for (int t = 0; t < 4; t++) {
    if (!((bad >> t) & 1)) continue;
    const bf16 *wqp = wq + (4 * j + t) * DH, *kp = kc + (size_t)(2 * j + (t >> 1)) * S_ * DH, *vp = vc + (size_t)(2 * j + (t >> 1)) * S_ * DH;
    uint32_t q[32];
    float o[64];
#pragma unroll
    for (int i = 0; i < 64; i++) o[i] = 0.f;
#pragma unroll 1
    for (int ks = 0; ks < 36; ks++) {
        const uint4 a = __ldcg(hf + ks * 32);
        const unsigned short* wr = reinterpret_cast<const unsigned short*>(wqp + (size_t)(ks * 16 + 2 * qd) * QD + g8);
#pragma unroll
        for (int dt = 0; dt < 16; dt++) {
            const uint32_t b0 = __ldg(wr + dt * 8) | ((uint32_t)__ldg(wr + dt * 8 + QD) << 16);
            const uint32_t b1 = __ldg(wr + dt * 8 + 8 * QD) | ((uint32_t)__ldg(wr + dt * 8 + 9 * QD) << 16);
            mma16816(o + 4 * dt, a.x, a.y, a.z, a.w, b0, b1);
        }
    }
#pragma unroll
    for (int i = 0; i < 32; i++) q[i] = pack_bf16(o[2 * i], o[2 * i + 1]);
#pragma unroll
    for (int i = 0; i < 64; i++) o[i] = 0.f;
    float m0 = -INFINITY, m1 = -INFINITY, l0 = 0.f, l1 = 0.f;
#pragma unroll 1
    for (int key = 0; key < S_; key += 16) {
        float sc[8];
#pragma unroll
        for (int i = 0; i < 8; i++) sc[i] = 0.f;
#pragma unroll
        for (int nt = 0; nt < 2; nt++) {
            const uint32_t* kr = reinterpret_cast<const uint32_t*>(kp + (size_t)(key + nt * 8 + g8) * DH) + qd;
#pragma unroll
            for (int ks = 0; ks < 8; ks++)
                mma16816(sc + 4 * nt, q[4 * ks], q[4 * ks + 1], q[4 * ks + 2], q[4 * ks + 3], __ldg(kr + ks * 8), __ldg(kr + ks * 8 + 4));
        }
        const float n0 = quad_max(fmaxf(fmaxf(m0, fmaxf(sc[0], sc[1])), fmaxf(sc[4], sc[5])));
        const float n1 = quad_max(fmaxf(fmaxf(m1, fmaxf(sc[2], sc[3])), fmaxf(sc[6], sc[7])));
        const float f0 = ex2((m0 - n0) * CS), f1 = ex2((m1 - n1) * CS);
        m0 = n0; m1 = n1;
#pragma unroll
        for (int i = 0; i < 8; i++) sc[i] = ex2((sc[i] - ((i & 2) ? n1 : n0)) * CS);
        l0 = l0 * f0 + (sc[0] + sc[1]) + (sc[4] + sc[5]);
        l1 = l1 * f1 + (sc[2] + sc[3]) + (sc[6] + sc[7]);
        const uint32_t e0 = pack_bf16(sc[0], sc[1]), e1 = pack_bf16(sc[2], sc[3]), e2 = pack_bf16(sc[4], sc[5]), e3 = pack_bf16(sc[6], sc[7]);
        const unsigned short* vr = reinterpret_cast<const unsigned short*>(vp + (size_t)(key + 2 * qd) * DH + g8);
#pragma unroll
        for (int dt = 0; dt < 16; dt++) {
            o[4 * dt] *= f0; o[4 * dt + 1] *= f0; o[4 * dt + 2] *= f1; o[4 * dt + 3] *= f1;
            const uint32_t b0 = __ldg(vr + dt * 8) | ((uint32_t)__ldg(vr + dt * 8 + DH) << 16);
            const uint32_t b1 = __ldg(vr + dt * 8 + 8 * DH) | ((uint32_t)__ldg(vr + dt * 8 + 9 * DH) << 16);
            mma16816(o + 4 * dt, e0, e1, e2, e3, b0, b1);
        }
    }
    const float i0 = 1.f / quad_sum(l0), i1 = 1.f / quad_sum(l1);
#pragma unroll
    for (int i = 0; i < 16; i++) {
        q[2 * i] = pack_bf16(o[4 * i] * i0, o[4 * i + 1] * i0);
        q[2 * i + 1] = pack_bf16(o[4 * i + 2] * i1, o[4 * i + 3] * i1);
    }
    frag_store(t < 3 ? frag + t * 4096 : keep, q);
  }
}

__device__ __forceinline__ void spare_q3(Scratch* gs, uint32_t sb, uint32_t bar_full, uint32_t bar_empty, int lane, int cw) {
    const uint32_t tag = load_tag(gs);
    uint32_t rel_base, e = 2;
    asm("mapa.shared::cluster.u32 %0, %1, %2;" : "=r"(rel_base) : "r"(bar_empty), "r"(lane & 1));
#pragma unroll 1
    for (int qb = blockIdx.x - NCTA; qb < 16; qb += 4) {
        uint32_t h[144];
        float o[64];
        flag_wait(&g_flag_h[(qb * 8 + cw) * 32 + (lane & 7)], tag);
        const uint4* hf = g_h + (size_t)(qb * 8 + cw) * (36 * 32) + lane;
#pragma unroll
        for (int ks = 0; ks < 36; ks++) {
            const uint4 v = __ldcg(hf + ks * 32);
            h[4 * ks] = v.x; h[4 * ks + 1] = v.y; h[4 * ks + 2] = v.z; h[4 * ks + 3] = v.w;
        }
#pragma unroll
        for (int i = 0; i < 64; i++) o[i] = 0.f;
#pragma unroll 1
        for (int v = 0; v < 4; v++) {
            fence_regs(o);
#pragma unroll
            for (int t = 0; t < 5; t++) {
                mbar_wait(bar_full + 8 * (e & 3), (e >> 2) & 1);
                const uint64_t dv = mkdesc(sb + (e & 3) * SLOT, UNIT, 1024);
                WG_FENCE();
#pragma unroll
                for (int ks = 0; ks < (t < 4 ? 8 : 4); ks++)
                    mma_rs128<1>(o, h[32 * t + 4 * ks], h[32 * t + 4 * ks + 1], h[32 * t + 4 * ks + 2], h[32 * t + 4 * ks + 3], dv + ks * 128, ks | t);
                WG_COMMIT();
                if (t > 0) { WG_WAIT(1); if (lane < 2) mbar_arrive_cluster(rel_base + 8 * ((e - 1) & 3)); }
                e++;
            }
            WG_WAIT(0);
            fence_regs(o);
            if (lane < 2) mbar_arrive_cluster(rel_base + 8 * ((e - 1) & 3));
            uint4* dst = &g_q3[((qb * 8 + 2 * v) * 8 + cw) * 128 + lane];
#pragma unroll
            for (int i = 0; i < 8; i++)
                __stcg(dst + (i >> 2) * 1024 + (i & 3) * 32, make_uint4(pack_bf16(o[8 * i], o[8 * i + 1]), pack_bf16(o[8 * i + 2], o[8 * i + 3]),
                                                                        pack_bf16(o[8 * i + 4], o[8 * i + 5]), pack_bf16(o[8 * i + 6], o[8 * i + 7])));
        }
        bar_sync(3, 256);
        if (cw == 0 && lane == 0) flag_release(&g_flag_q3[qb * 32], tag);
        __syncwarp();
    }
}

template <bool SPARE>
__global__ void __cluster_dims__(2, 1, 1) __launch_bounds__(384, 1)
fused_kernel(const Args args, const __grid_constant__ CUtensorMap tm_wq,
             const __grid_constant__ CUtensorMap tm_k, const __grid_constant__ CUtensorMap tm_v,
             const __grid_constant__ CUtensorMap tm_wo, const __grid_constant__ CUtensorMap tm_p,
             const __grid_constant__ CUtensorMap tm_x, const __grid_constant__ CUtensorMap tm_d,
             const __grid_constant__ CUtensorMap tm_g, const __grid_constant__ CUtensorMap tm_u) {
    extern __shared__ __align__(1024) uint8_t smem_raw[];
    const uint32_t sb = smem_u32(smem_raw);
    Scratch* const gs = args.gs;
    const uint32_t bar_full = sb + SM_BAR;
    const uint32_t bar_g = bar_full + 8 * 4;
    const uint32_t bar_mod = bar_g + 8;
    const uint32_t bar_go = bar_mod + 8;
    const uint32_t bar_x = bar_go + 40;
    const uint32_t bar_empty = bar_x + 8;
    const uint32_t bar_pub = bar_empty + 8 * 4;
    const uint32_t bar_qfree = bar_pub + 32;
    const uint32_t bar_out = bar_qfree + 24;
    const uint32_t bar_q3 = bar_out + 8;

    const int c = blockIdx.x & 1;
    const int j = (blockIdx.x >> 1) & 7;
    const int qb = (blockIdx.x >> 4) * 2 + c;
    const int rg = qb * 8 + j;
    const int warp = __shfl_sync(0xffffffffu, threadIdx.x >> 5, 0);

    if (SPARE && blockIdx.x >= NCTA && warp >= 4) {
        asm volatile("barrier.cluster.arrive.relaxed.aligned;" ::: "memory");
        asm volatile("setmaxnreg.inc.sync.aligned.u32 240;");
        asm volatile("barrier.cluster.wait.aligned;" ::: "memory");
        spare_q3(gs, sb, bar_full, bar_empty, threadIdx.x & 31, warp - 4);
        asm volatile("barrier.cluster.arrive.relaxed.aligned;\nbarrier.cluster.wait.aligned;" ::: "memory");
    } else if (warp < 4) {
        asm volatile("setmaxnreg.dec.sync.aligned.u32 24;");
        int lane;
        asm volatile("mov.u32 %0, %%laneid;" : "=r"(lane));
        if (warp == 2 && elect()) {
            if (TMPF) asm volatile("prefetch.tensormap [%0];" ::"l"(&tm_x) : "memory");
#pragma unroll
            for (int i = 0; i < 25; i++) mbar_init(bar_full + 8 * i, i < 12 || i >= 23 ? 1 : i < 16 ? 16 : 8);
            if (SPARE) {
#pragma unroll
                for (int i = 0; i < 2; i++) {
                    mbar_arrive(bar_full + 8 * i);
                    asm volatile("mbarrier.arrive.shared::cta.b64 _, [%0], 16;" ::"r"(bar_empty + 8 * i) : "memory");
                }
            }
            asm volatile("fence.mbarrier_init.release.cluster;" ::: "memory");
        }
        __syncwarp();
        asm volatile("barrier.cluster.arrive.relaxed.aligned;" ::: "memory");
        if (warp == 2 && !(SPARE && blockIdx.x >= NCTA)) {
            if (XDELAY) __nanosleep(XDELAY);
            if (elect()) {
                mbar_expect_tx(bar_x, 16 * XP);
                tma2d(sb + SM_Q, &tm_x, 0, rg * 16, bar_x);
            }
            __syncwarp();
        }
        asm volatile("barrier.cluster.wait.aligned;" ::: "memory");
        const uint32_t tag = load_tag(gs);
        if (SPARE && blockIdx.x >= NCTA) {
            if (warp == 1) {
#pragma unroll 1
                for (int e = 2; e < 82; e++) {
                    const int v = (e - 2) / 5;
                    mbar_wait_sleep(bar_empty + 8 * (e & 3), ~(e >> 2) & 1);
                    if (elect()) {
                        mbar_expect_tx(bar_full + 8 * (e & 3), SLOT);
                        tma2d_mc(sb + (e & 3) * SLOT + c * UNIT, &tm_wq, (8 * (v & 3) + 4 * c + 3) * DH + 64, (e - 2 - v * 5) * 128,
                                 bar_full + 8 * (e & 3), EVICT_NORMAL);
                    }
                }
            }
            __syncwarp();
            asm volatile("barrier.cluster.arrive.relaxed.aligned;\nbarrier.cluster.wait.aligned;" ::: "memory");
            return;
        }
        if (warp == 3) {
#pragma unroll 1
            for (int e = 4; e < 20; e++) {
                __nanosleep(e == 4 ? 3000 : 400);
                const int hd = (e * 52) >> 8, row = (e - hd * 5) * 128 + qb * 8 + (lane >> 1);
                if (lane < 16 && row < D_)
                    asm volatile("prefetch.global.L2 [%0];" ::"l"(args.wq + (size_t)row * QD + (4 * j + ((0x1320 >> (4 * hd)) & 3)) * DH + (lane & 1) * 64) : "memory");
            }
            __syncwarp();
            mbar_wait_sleep(bar_go, 0);
#pragma unroll 1
            for (int unit = 72 + blockIdx.x; unit < 216; unit += NCTA) {
                float a[8];
#pragma unroll
                for (int i = 0; i < 8; i++) a[i] = 0.f;
#pragma unroll 1
                for (int k = lane >> 1; k < D_; k += 16) {
                    const float cv = __bfloat162float(args.cvec[k]);
                    mod_fma(a, __ldg(reinterpret_cast<const uint4*>(args.w_mod + (size_t)k * (6 * D_) + unit * 16 + (lane & 1) * 8)), rbf(cv * sigmoidf_(cv)));
                }
                const float v = mod_reduce(a, lane), v1 = __shfl_down_sync(0xffffffffu, v, 8);
                if (lane < 8) st_relaxed64(&gs->mod2[(unit - 72) * 8 + (lane & 1) * 4 + (lane & 2) + (lane >> 2)], pack_bf16(v, v1), tag);
            }
            __syncwarp();
            if (lane == 0) flag_release(&g_flag_mod[blockIdx.x], tag);
            __syncwarp();
            mbar_wait_sleep(bar_qfree + 16, 0);
            __nanosleep(2000);
            {
                uint4 v;
                uint32_t it = 0;
#pragma unroll 1
                do {
                    v = ld_relaxed(reinterpret_cast<const uint4*>(g_flag_mod) + lane);
                } while (((v.x ^ tag) | (v.y ^ tag) | (v.z ^ tag) | (v.w ^ tag)) && ++it < SPIN / 16);
                asm volatile("fence.acquire.gpu;" ::: "memory");
            }
#pragma unroll
            for (int i = 0; i < 4; i++) reinterpret_cast<uint4*>(smem_raw + SM_RED)[lane + 32 * i] = make_uint4(~0u, ~0u, ~0u, ~0u);
            asm volatile("fence.proxy.async.shared::cta;" ::: "memory");
            __syncwarp();
            if (elect()) {
                uint8_t* mb = g_frag + (size_t)rg * 8 * WREG + 3 * 4096;
#pragma unroll 1
                for (int k = 0; k < 8; k++, mb += WREG) {
#pragma unroll
                    for (int i = 0; i < 3; i++)
                        asm volatile("cp.async.bulk.global.shared::cta.bulk_group [%0], [%1], 2048;" ::"l"(mb + i * 2048), "r"(sb + SM_RED) : "memory");
                    __nanosleep(500);
                }
                asm volatile("cp.async.bulk.commit_group;\ncp.async.bulk.wait_group 0;\nfence.proxy.async.global;" ::: "memory");
            }
            __syncwarp();
            if (lane == 0) mbar_arrive(bar_mod);
            __syncwarp();
            mbar_wait_sleep(bar_go + 8, 0);
            if (lane < 3) asm volatile("prefetch.tensormap [%0];" ::"l"(lane == 0 ? &tm_x : lane == 1 ? &tm_p : &tm_d) : "memory");
            __syncwarp();
            mbar_wait_sleep(bar_go + 8 * 2, 0);
            uint32_t acc = 0;
#pragma unroll 1
            for (int k = lane; k < 16 * 9; k += 32) acc |= touch(args.x + (size_t)rg * 16 * D_ + k * 64);
            if (acc == 0) reinterpret_cast<volatile uint32_t*>(smem_raw + SM_BAR)[127] = acc;
        } else if (warp == 0) {
#pragma unroll 1
            for (int i = 0; i < 48; i++) {
                if (i == 0 || i == 17 || i == 34) mbar_wait_sleep(bar_qfree + (i >> 4) * 8, 0);
                if (SPARE && i == 17) {
                    flag_wait(&g_flag_q3[qb * 32], tag);
                    if (elect()) {
                        asm volatile("fence.proxy.async.global;" ::: "memory");
                        mbar_expect_tx(bar_q3, UNIT);
#pragma unroll 1
                        for (int k = 0; k < 8; k++) bulk_load(sb + SM_Q + 2 * SLOT + k * 4096 + 2048, &g_q3[(rg * 8 + k) * 128], 2048, bar_q3);
                    }
                }
                __nanosleep(700);
                if (elect()) {
                    asm volatile("mbarrier.expect_tx.shared::cta.b64 [%0], %1;" ::"r"(bar_g), "n"(1920) : "memory");
                    tma2d(sb + SM_Q + i * 1920, i < 24 ? &tm_g : &tm_u, (blockIdx.x * 36) & ~7, (i < 24 ? i : i - 24) * 24, bar_g);
                }
            }
#pragma unroll 1
            for (int i = 0; i < 18; i++) {
                __nanosleep(400);
                if (elect()) l2_prefetch(args.w_down + (size_t)(blockIdx.x * 36 + i * 2) * D_, 4 * D_);
            }
            __syncwarp();
            mbar_wait_sleep(bar_go + 8 * 4, 0);
            if (blockIdx.x < 72) {
                uint4* yp = reinterpret_cast<uint4*>(&g_ypart[blockIdx.x * NCTA * 8]) + lane;
#pragma unroll
                for (int k = 0; k < 16; k++) yp[k * 32] = make_uint4(~0u, ~0u, ~0u, ~0u);
                asm volatile("fence.acq_rel.gpu;" ::: "memory");
            }
            __syncwarp();
            if (lane == 0) mbar_arrive(bar_g);
        } else if (warp == 1) {
            __nanosleep(QDELAY);
            uint32_t go = bar_go;
            uint64_t marks = 24 | 151 << 8 | 154 << 16 | 159ull << 24 | 165ull << 32;
#pragma unroll 1
            for (int e = SPARE ? 2 : 0; e < 172; e++) {
                const CUtensorMap* tm;
                int c0, c1;
                uint64_t pol = EVICT_FIRST;
                if (e == 158 || e == 163 || e == 169) continue;
                if (e < 21 && e != 19) {
                    const int i = SPARE && e < 12 ? e - 2 : e - (e == 20), hd = (i * 52) >> 8;
                    tm = &tm_wq; c0 = (4 * j + ((0x1320 >> (4 * hd)) & 3)) * DH + c * 64; c1 = (i - hd * 5) * 128 - 64;
                    if (SPARE && e >= 12 && e < 15) { c0 = (4 * j + 3) * DH; c1 = (2 * (e - 12) + c) * 128; }
                } else if (e < 148) {
                    const int i = max(e - 20, 0);
                    const bool isk = i == 0 || ((i & 1) && i < 127);
                    const int n = isk ? (i + 1) >> 1 : (i - 1) >> 1;
                    tm = isk ? &tm_k : &tm_v; c0 = c * 64; c1 = (2 * j + (n >> 5)) * S_ + (n & 15) * 128;
                    if (!(i & 32)) pol = EVICT_NORMAL;
                } else {
                    int i = e - 148 - (e > 158) - (e > 163);
                    if (i == 1 || i == 2) i ^= 3;
                    tm = &tm_wo; c0 = (i >> 1) * 64; c1 = (4 * j + ((i & 1) ? 1 + c : 3 * c)) * DH;
                }
                if (e == 168) {
                    mbar_wait(bar_mod, 0);
                    asm volatile("fence.proxy.async.global;" ::: "memory");
                }
                const uint32_t fb = bar_full + 8 * (e & 3), d = sb + (e & 3) * SLOT;
                if (e >= 24 && e < 152) mbar_wait_sleep(bar_empty + 8 * (e & 3), ~(e >> 2) & 1);
                else mbar_wait(bar_empty + 8 * (e & 3), ~(e >> 2) & 1);
                if (elect()) {
                    mbar_expect_tx(fb, e == 168 ? 16 * XP + 4 * D_ * 4 + D_ * 2 : e >= 170 ? 18 * XP : SLOT);
                    if (e < 168) {
                        tma2d_mc(d + c * UNIT, tm, c0, c1, fb, pol);
                        const int i = e - PF_KV;
                        if (i >= 0 && i < 128 && !(i & 32))
                            l2_prefetch(((i & 1) ? args.vc : args.kc) + (size_t)((2 * j + (i >> 6)) * S_ + (i & 30) * 64) * DH + qb * 1024, 2048);
                        if (e >= PF_WO && e < PF_WO + 18) l2_prefetch(args.wo + (size_t)blockIdx.x * (QD * D_ / NCTA) + (e - PF_WO) * 1024, 2048);
                        if (e == (marks & 255)) mbar_arrive(go);
                    } else {
                        tma2d(d, e == 168 ? &tm_x : &tm_d, 0, e == 168 ? rg * 16 : blockIdx.x * 36 + (e - 170) * 18, fb);
                        if (e == 168) {
                            bulk_load(d + M_MOD, gs->mod2, 4 * D_ * 4, fb);
                            bulk_load(d + M_WR, args.w_r, D_ * 2, fb);
                        }
                    }
                }
                if (e == (marks & 255)) { go += 8; marks >>= 8; }
            }
        } else {
            if (lane < 3) asm volatile("prefetch.tensormap [%0];" ::"l"(lane == 0 ? &tm_k : lane == 1 ? &tm_v : &tm_wo) : "memory");
            bar_sync(1, 192);
#pragma unroll 1
            for (uint32_t e = 20; e < 148; e++) {
                mbar_wait_sleep(bar_full + 8 * (e & 3), (e >> 2) & 1);
                if (e & 1) bar_sync(1, 192);
                if (!(e & 1) || e == 147) bar_sync(4, 160);
            }
            mbar_wait_sleep(bar_go + 8, 0);
            mbar_wait(bar_mod, 0);
#pragma unroll 1
            for (int i = 1; i < 4; i++) {
                mbar_wait(bar_pub + 8 * i, 0);
                unsigned int* flags = &g_flag_part[qb * 32 + i * 8 - 8];
                if (elect()) { flag_release(flags + j, tag); DBG_PG(93); }
                __syncwarp();
                const uint32_t slot = i < 3 ? i + 1 : 1;
                flag_wait(flags + (lane & 7), tag);
                asm volatile("fence.proxy.async.global;" ::: "memory");
                if (lane == 0 && i == 3) DBG_PG(101);
                mbar_wait(bar_go + 8 + 8 * i, 0);
                mbar_wait(bar_empty + 8 * slot, i != 1);
                if (elect()) {
                    mbar_expect_tx(bar_full + 8 * slot, SLOT);
                    tma3d(sb + slot * SLOT, &tm_p, 0, j * 20 + (i - 1) * 4, qb * 8, bar_full + 8 * slot);
                }
            }
        }
        __syncwarp();
        mbar_wait_sleep(bar_out, 0);
        if (elect()) {
            const int2 sel = reinterpret_cast<const int2*>(smem_raw + SM_RED)[208];
#pragma unroll 1
            for (int i = warp; i < 16; i += 4) {
                const int row = rg * 16 + i;
                if (row != sel.x && row != sel.y)
                    asm volatile("cp.async.bulk.global.shared::cta.bulk_group [%0], [%1], %2;"
                                 ::"l"(args.out + (size_t)row * D_), "r"(sb + i * XP), "n"(D_ * 2) : "memory");
            }
            asm volatile("cp.async.bulk.commit_group;\ncp.async.bulk.wait_group 0;" ::: "memory");
        }
    } else {
        uint32_t cv[5] = {0, 0, 0, 0, 0}, tag0 = 0;
        if (blockIdx.x < 72) {
            uint32_t ws;
            int tid;
            asm volatile("mov.u32 %0, smem_raw;\nmov.u32 %1, %%tid.x;" : "=r"(ws), "=r"(tid));
            tid -= 128;
            ws += SM_Q + SLOT + tid * 16;
            const bf16* wrow = args.w_mod + (size_t)(tid >> 1) * (6 * D_) + (tid & 1) * 8 + blockIdx.x * 16;
#pragma unroll
            for (int i = 0; i < 5; i++)
                if (i < 4 || tid < 128) {
                    asm volatile("cp.async.cg.shared.global [%0], [%1], 16;" ::"r"(ws + i * 4096), "l"(wrow + (size_t)i * 128 * (6 * D_)) : "memory");
                    cv[i] = reinterpret_cast<const unsigned short*>(args.cvec)[(tid >> 1) + i * 128];
                }
            tag0 = load_tag(gs) - 1;
        }
        asm volatile("barrier.cluster.arrive.relaxed.aligned;" ::: "memory");
        asm volatile("setmaxnreg.inc.sync.aligned.u32 240;");
        const int lane = threadIdx.x & 31;
        const int cw = warp - 4;
        const int w = cw >> 2;
        const int tid = threadIdx.x - 128;
        float* red = reinterpret_cast<float*>(smem_raw + SM_RED);
        DBG_INIT();
        DBG_G(120);
        DBG_T(100);

        uint32_t tag;
        {
            if (blockIdx.x < 72) {
                const uint32_t ws = sb + SM_Q + SLOT + tid * 16;
                float sc[5], a[8];
#pragma unroll
                for (int i = 0; i < 5; i++) sc[i] = __uint_as_float(cv[i] << 16);
#pragma unroll
                for (int i = 0; i < 5; i++) sc[i] = rbf(sc[i] * sigmoidf_(sc[i]));
#pragma unroll
                for (int i = 0; i < 8; i++) a[i] = 0.f;
                anchor(bar_full + 504, sc[0] + sc[1] + sc[2] + sc[3] + sc[4] + 2.f);
                asm volatile("cp.async.wait_all;" ::: "memory");
#pragma unroll
                for (int i = 0; i < 5; i++) mod_fma(a, lds128(ws + (i < 4 || tid < 128 ? i * 4096 : 0)), sc[i]);
                const float v = mod_reduce(a, lane);
                if (lane < 16) red[cw * 16 + lane] = v;
                bar_sync(3, 256);
                if (tid < 8 * MREP) {
                    float v0 = 0.f, v1 = 0.f;
#pragma unroll
                    for (int i = 0; i < 8; i++) { v0 += red[i * 16 + (tid & 7)]; v1 += red[i * 16 + 8 + (tid & 7)]; }
                    st_relaxed64(&gs->mod1[(tid >> 3) * D_ + blockIdx.x * 8 + (tid & 1) * 4 + (tid & 2) + ((tid >> 2) & 1)], pack_bf16(v0, v1), tag0 + 1);
                }
            }
            DBG_G(106);
            asm volatile("barrier.cluster.wait.aligned;" ::: "memory");
            mbar_wait(bar_x, 0);
            tag = load_tag(gs);
            uint32_t x[20];
            float st[12];
            rows_load(x, sb + SM_Q + (lane & 15) * XP + (lane >> 4) * 16 + cw * 32, cw);
#pragma unroll
            for (int i = 0; i < 12; i++) st[i] = 0.f;
#pragma unroll
            for (int k = 0; k < 9; k++) stats_add(st, x[2 * k], x[2 * k + 1]);
            rows_normalise(x, x, st, reinterpret_cast<float4*>(red + 128), cw, lane);
            fence_regs(x);
            uint4* smod = reinterpret_cast<uint4*>(smem_raw + SM_Q + M_MOD);
            if (tid < D_ / 4) {
                const uint4* mp = reinterpret_cast<const uint4*>(gs->mod1 + ((blockIdx.x >> 1) & (MREP - 1)) * D_) + tid;
                poll2x2(mp, mp + D_ / 4, tag, smod[tid], smod[D_ / 4 + tid]);
            }
            bar_sync(3, 256);
            DBG_G(107);
            const uint2* mp = reinterpret_cast<const uint2*>(smod) + cw * 8 + (lane & 3);
#pragma unroll
            for (int k = 0; k < 9; k++) {
                const uint32_t c1 = badd2(pair_of(mp + D_ / 2, k, cw), 0x3f803f80u), sa = pair_of(mp, k, cw);
                x[2 * k] = badd2(bmul2(x[2 * k], c1), sa);
                x[2 * k + 1] = badd2(bmul2(x[2 * k + 1], c1), sa);
            }
            uint4* hdst = g_h + (size_t)(rg * 36 + cw) * 32 + lane;
#pragma unroll
            for (int ch = 0; ch < 4; ch++) __stcg(hdst + ch * 256, make_uint4(x[4 * ch], x[4 * ch + 1], x[4 * ch + 2], x[4 * ch + 3]));
            if (!NOPART) __stcg(reinterpret_cast<uint2*>(hdst + (32 - cw + (cw >> 1)) * 32) + (cw & 1), make_uint2(x[16], x[17]));
            if (cw == 7) {
                bar_sync(3, 256);
                if (lane < 8) flag_release(&g_flag_h[rg * 32 + lane], tag);
            } else bar_arrive(3, 256);
            DBG_G(108);
        }

        uint32_t rel_base;
        asm("mapa.shared::cluster.u32 %0, %1, %2;" : "=r"(rel_base) : "r"(bar_empty), "r"(lane & 1));
        auto release = [&](uint32_t slot) { if (lane < 2) mbar_arrive_cluster(rel_base + 8 * slot); };
        uint32_t q[32], p[32];
        float s[64], o[64];

        uint4* qpark = reinterpret_cast<uint4*>(smem_raw + SM_Q - SLOT) + cw * 256 + lane;
        {
            uint32_t h[144];
            const uint4* hf = g_h + (size_t)(qb * 8 + cw) * (36 * 32) + lane;
            auto load_h = [&](auto lo, auto hi) {
#pragma unroll
                for (int ks = lo.value; ks < hi.value; ks++) {
                    const uint4 v = __ldcg(hf + ks * 32);
                    h[4 * ks] = v.x; h[4 * ks + 1] = v.y; h[4 * ks + 2] = v.z; h[4 * ks + 3] = v.w;
                }
            };
            flag_wait(&g_flag_h[(qb * 8 + cw) * 32 + (lane & 7)], tag);
            load_h(IC<0>{}, IC<4>{});
            DBG_T(104); DBG_G(109);
#pragma unroll
            for (int i = 0; i < 64; i++) o[i] = 0.f;
            uint32_t e = SPARE ? 2 : 0;
#pragma unroll 1
            for (int hd = 1;; hd++) {
                fence_regs(o);
                auto group = [&](auto tc) {
                    constexpr int t = tc.value, k0 = t ? 8 * t - 4 : 0;
                    mbar_wait(bar_full + 8 * (e & 3), (e >> 2) & 1);
                    const uint32_t dv = desc_lo(t ? 0 : 8192, UNIT) + (e & 3) * (SLOT / 16);
                    WG_FENCE();
#pragma unroll
                    for (int ks = k0; ks < 8 * t + 4; ks++)
                        mma_rs128<1>(o, h[4 * ks], h[4 * ks + 1], h[4 * ks + 2], h[4 * ks + 3], desc_of(dv + (ks - k0) * 128), ks);
                    WG_COMMIT();
                    if (t < 4 && hd == 1) load_h(IC<8 * t + 4>{}, IC<t < 4 ? 8 * t + 12 : 0>{});
                    if (t > 0) { WG_WAIT(1); release((e - 1) & 3); }
                    e++;
                };
                group(IC<0>{}); group(IC<1>{}); group(IC<2>{}); group(IC<3>{});
                if (e == 19) break;
                group(IC<4>{});
                WG_WAIT(0);
                fence_regs(o);
                release((e - 1) & 3);
#pragma unroll
                for (int i = 0; i < 8; i++)
                    qpark[hd * 2048 + i * 32] = make_uint4(pack_bf16(o[8 * i], o[8 * i + 1]), pack_bf16(o[8 * i + 2], o[8 * i + 3]),
                                                           pack_bf16(o[8 * i + 4], o[8 * i + 5]), pack_bf16(o[8 * i + 6], o[8 * i + 7]));
                if (SPARE && hd == 2) {
                    float (&u)[32] = reinterpret_cast<float (&)[32]>(o);
                    fence_regs(u);
#pragma unroll
                    for (int t = 0; t < 3; t++) {
                        mbar_wait(bar_full + 8 * t, 1);
                        WG_FENCE();
#pragma unroll
                        for (int ks = 0; ks < (t < 2 ? 16 : 4); ks++)
                            mma_rs64<1>(u, h[64 * t + 4 * ks], h[64 * t + 4 * ks + 1], h[64 * t + 4 * ks + 2], h[64 * t + 4 * ks + 3],
                                        desc_of(desc_lo(t * SLOT, UNIT) + ks * 128), ks | t);
                        WG_COMMIT();
                        if (t > 0) { WG_WAIT(1); release(t - 1); }
                    }
                    WG_WAIT(0);
                    fence_regs(u);
                    release(2);
                    e = 15;
#pragma unroll
                    for (int i = 0; i < 4; i++)
                        qpark[3 * 2048 + i * 32] = make_uint4(pack_bf16(u[8 * i], u[8 * i + 1]), pack_bf16(u[8 * i + 2], u[8 * i + 3]),
                                                              pack_bf16(u[8 * i + 4], u[8 * i + 5]), pack_bf16(u[8 * i + 6], u[8 * i + 7]));
                }
            }
#pragma unroll
            for (int i = 0; i < 8; i++) {
                const uint4 v = qpark[2048 + i * 32];
                q[4 * i] = v.x; q[4 * i + 1] = v.y; q[4 * i + 2] = v.z; q[4 * i + 3] = v.w;
            }
#pragma unroll
            for (int i = 0; i < 32; i++) p[i] = h[112 + i];
            mbar_wait(bar_full + 24, 0);
            WG_WAIT(0);
            fence_regs(o);
            release(2);
        }
        DBG_T(105);
        DBG_G(125);

        uint8_t* frag = reinterpret_cast<uint8_t*>(__shfl_sync(0xffffffffu, reinterpret_cast<unsigned long long>(g_frag + (size_t)(rg * 8 + cw) * WREG + lane * 16), lane));
        const uint4* qnext = reinterpret_cast<const uint4*>(__shfl_sync(0xffffffffu, reinterpret_cast<unsigned long long>(qpark + 2048), lane));
        uint8_t* odst = reinterpret_cast<uint8_t*>(const_cast<uint4*>(qnext));
        float m0 = 0.f, m1 = 0.f, l0 = 0.f, l1 = 0.f, t0 = 1.f, t1 = 1.f;
        uint32_t bad = 0;
        const int lw = cw & 3;
        const uint32_t relw = lw == RW && lane < 8, handw = lw == HW || cw == HW2;
        auto release4 = [&](uint32_t off) {
            asm volatile("{\n.reg .pred p;\nsetp.ne.b32 p, %1, 0;\n@p mbarrier.arrive.shared::cluster.b64 _, [%0];\n}" ::"r"(rel_base + off), "r"(relw) : "memory"); };
        auto handoff = [&]() {
            asm volatile("{\n.reg .pred p;\nsetp.ne.b32 p, %1, 0;\n@p bar.arrive %0, 192;\n}" ::"r"(2 - w), "r"(handw) : "memory"); };
        if (cw == 4 + HW) bar_arrive(1, 192);
        auto finish = [&](auto lo, auto hi, uint32_t bit, auto sink) {
#pragma unroll
            for (int i = lo.value; i < hi.value; i++) {
                const uint32_t v0 = pack_bf16(o[8 * i] * t0, o[8 * i + 1] * t0), v1 = pack_bf16(o[8 * i + 2] * t1, o[8 * i + 3] * t1);
                const uint32_t v2 = pack_bf16(o[8 * i + 4] * t0, o[8 * i + 5] * t0), v3 = pack_bf16(o[8 * i + 6] * t1, o[8 * i + 7] * t1);
                if (i == 0 && fabsf(o[0] * t0) >= 0x1p-31f) bad |= bit << 8;
                sink(i, v0, v1, v2, v3);
            }
        };
        auto row_sums = [&](uint32_t bit) {
            t0 = quad_sum(l0); t1 = quad_sum(l1);
            if (!(t0 >= LMIN && t0 < LMAX && t1 >= LMIN && t1 < LMAX)) bad |= bit;
            t0 = rcp_fast(t0); t1 = rcp_fast(t1);
            l0 = 0.f; l1 = 0.f;
        };
        auto issue_pv = [&](uint32_t dlo, int acc, auto lo, auto hi) {
            if (lo.value == 0) asm volatile("{\n.reg .pred p;\nsetp.eq.b32 p, %0, 0;\n@p bar.sync 4, 160;\n}" ::"r"(w) : "memory");
#pragma unroll
            for (int ks = lo.value; ks < hi.value; ks++)
                mma_rs128<1>(o, p[4 * ks], p[4 * ks + 1], p[4 * ks + 2], p[4 * ks + 3], desc_of(dlo + ks * 128), ks ? 1 : acc);
            WG_COMMIT();
        };
#pragma unroll
        for (int i = 0; i < 64; i++) s[i] = 0.f;
        uint32_t dv_lo = desc_lo(0, UNIT), voff = 0;
        auto issue_qk = [&]() {
            const uint32_t dk = dv_lo ^ (desc_lo(0, UNIT) ^ desc_lo(3 * SLOT, 16));
            bar_sync(1 + w, 192);
            fence_regs(s); fence_regs(q); fence_regs(o); fence_regs(p);
            WG_FENCE();
#pragma unroll
            for (int ks = 0; ks < 8; ks++)
                mma_rs128<0>(s, q[4 * ks], q[4 * ks + 1], q[4 * ks + 2], q[4 * ks + 3], desc_of(dk + (ks >> 2) * 1024 + (ks & 3) * 2), ks != 0);
            WG_COMMIT();
        };
        auto to_frag = [&](int i, uint32_t v0, uint32_t v1, uint32_t v2, uint32_t v3) {
            *reinterpret_cast<uint4*>(odst + i * 512) = make_uint4(v0, v1, v2, v3); };
        int n = 0;
#pragma unroll 1
        for (;;) {
            issue_qk();
            const int jn = n & 15;
            if (jn == 1) {
                finish(IC<ESPLIT>{}, IC<8>{}, 1u << (n >> 4), to_frag);
                WG_FENCE();
                issue_pv(dv_lo, 0, IC<0>{}, IC<PV1>{});
            } else {
                if (jn == 0 && n > 0) {
                    row_sums(1u << (n >> 4));
                    qnext = n == 48 ? reinterpret_cast<const uint4*>(frag) : qnext + 2048;
                    odst = frag + ((n >> 4) - 1) * 4096;
                    if (elect()) mbar_arrive(bar_qfree + (n >> 1) - 8);
                }
                issue_pv(dv_lo, 1, IC<0>{}, IC<PV1>{});
            }
            if (SPARE && n == 47) mbar_wait(bar_q3, 0);
            WG_WAIT(1);
            fence_regs(s); fence_regs(q);
            if (jn == 15) {
#pragma unroll
                for (int i = 0; i < 8; i++) {
                    const uint4 v = qnext[i * 32];
                    q[4 * i] = v.x; q[4 * i + 1] = v.y; q[4 * i + 2] = v.z; q[4 * i + 3] = v.w;
                }
            }
            if (jn == 0) {
                float a0 = fmaxf(s[0], s[1]), a1 = fmaxf(s[2], s[3]), a2 = fmaxf(s[4], s[5]), a3 = fmaxf(s[6], s[7]);
#pragma unroll
                for (int i = 1; i < MAXG; i++) {
                    a0 = fmaxf(a0, fmaxf(s[8 * i], s[8 * i + 1])); a1 = fmaxf(a1, fmaxf(s[8 * i + 2], s[8 * i + 3]));
                    a2 = fmaxf(a2, fmaxf(s[8 * i + 4], s[8 * i + 5])); a3 = fmaxf(a3, fmaxf(s[8 * i + 6], s[8 * i + 7]));
                }
                const uint32_t a = pack_bf16(fmaxf(a0, a2), fmaxf(a1, a3));
                const uint32_t b = bmax2(bmax2(a, __shfl_xor_sync(0xffffffffu, a, 1)), bmax2(__shfl_xor_sync(0xffffffffu, a, 2), __shfl_xor_sync(0xffffffffu, a, 3)));
                m0 = fmaf(-CS, bf_lo(b), -POFF); m1 = fmaf(-CS, bf_hi(b), -POFF);
            }
            if (PV1 < 8) issue_pv(dv_lo, 1, IC<PV1>{}, IC<8>{});
            release4(voff ^ 24);
            handoff();
#pragma unroll 1
            do {
                DBG_T(n);
#pragma unroll
                for (int i = 0; i < 4 * STAGE; i++) s[i] = fmaf(s[i], CS, (i & 2) ? m1 : m0);
#pragma unroll
                for (int i = 0; i < 4 * SPLIT; i++) s[i] = ex2(s[i]);
#pragma unroll
                for (int i = 0; i < SPLIT; i++) { l0 += s[4 * i] + s[4 * i + 1]; l1 += s[4 * i + 2] + s[4 * i + 3]; }
                if (STAGE < 16) {
                    m0 = fmaf(l0, 0.f, m0); m1 = fmaf(l1, 0.f, m1);
                }
                anchor(bar_full + 504, l0 + l1);
                WG_WAIT(0);
                fence_regs(o); fence_regs(p);
                release4(voff);
                dv_lo ^= 2 * SLOT / 16;
                voff ^= 16;
                n++;
#pragma unroll
                for (int i = 4 * STAGE; i < 64; i++) s[i] = fmaf(s[i], CS, (i & 2) ? m1 : m0);
#pragma unroll
                for (int i = 4 * SPLIT; i < 64; i++) s[i] = ex2(s[i]);
#pragma unroll
                for (int i = SPLIT; i < 16; i++) { l0 += s[4 * i] + s[4 * i + 1]; l1 += s[4 * i + 2] + s[4 * i + 3]; }
#pragma unroll
                for (int i = 0; i < 32; i++) p[i] = pack_bf16(s[2 * i], s[2 * i + 1]);
                if (((n + 1) & 15) < 3) break;
                issue_qk();
                issue_pv(dv_lo, 1, IC<0>{}, IC<8>{});
                WG_WAIT(1);
                fence_regs(s); fence_regs(q);
                release4(voff ^ 24);
                handoff();
            } while (n != 99);
            WG_WAIT(0);
            fence_regs(o); fence_regs(p);
            if ((n & 15) == 1) finish(IC<0>{}, IC<ESPLIT>{}, 1u << (n >> 4), to_frag);
            if (n == 64) break;
        }
        DBG_T(64);
        uint32_t a1[32], a2[32];
        bar_sync(1 + w, 192);
        fence_regs(o); fence_regs(p);
        WG_FENCE();
        issue_pv(desc_lo(3 * SLOT, UNIT), 1, IC<0>{}, IC<8>{});
        if (w == 0) handoff();
        row_sums(16);
        mbar_wait(bar_mod, 0);
        WG_WAIT(0);
        fence_regs(o); fence_regs(p);
        release(3);
        finish(IC<0>{}, IC<8>{}, 16, [&](int i, uint32_t v0, uint32_t v1, uint32_t v2, uint32_t v3) {
            p[4 * i] = v0; p[4 * i + 1] = v1; p[4 * i + 2] = v2; p[4 * i + 3] = v3; });
        bad = __reduce_or_sync(0xffffffffu, bad);
        bad = ((bad | ~(bad >> 8)) >> 1) & 15;
        if (__builtin_expect(bad != 0, 0)) {
            uint8_t* keep = g_keep + (size_t)(rg * 8 + cw) * 4096 + lane * 16;
            frag_store(keep, p);
            attn_fallback(bad, frag, keep, args.wq, args.kc, args.vc);
            frag_load(q, frag); frag_load(p, keep);
        }
        DBG_T(80);
        DBG_G(124);

        const uint32_t eye = (lane >> 3) == (lane & 3) ? 0x3f80u << ((lane & 4) * 4) : 0;
        auto sum8 = [&](uint32_t* r, const uint4 (&v)[8]) {
            float d[16];
#pragma unroll
            for (int i = 0; i < 16; i++) d[i] = 0.f;
#pragma unroll
            for (int src = 0; src < 8; src++) {
                mma1688(d + 8 * (src & 1), v[src].x, v[src].y, eye);
                mma1688(d + 8 * (src & 1) + 4, v[src].z, v[src].w, eye);
            }
#pragma unroll
            for (int i = 0; i < 4; i++) r[i] = pack_bf16(d[2 * i] + d[8 + 2 * i], d[2 * i + 1] + d[9 + 2 * i]);
        };
        auto sum8_slot = [&](uint32_t* r, uint32_t e) {
            mbar_wait(bar_full + 8 * (e & 3), (e >> 2) & 1);
            uint4 v[8];
#pragma unroll
            for (int src = 0; src < 8; src++) v[src] = lds128(sb + (e & 3) * SLOT + src * 4096 + tid * 16);
            sum8(r, v);
        };
        uint4 v3[8];
        const uint8_t* mb;
        auto load3 = [&]() {
#pragma unroll
            for (int src = 0; src < 8; src++) v3[src] = ld_relaxed(reinterpret_cast<const uint4*>(mb + (size_t)src * 8 * WREG));
        };
        uint32_t at[18];
        {
            float ua[32], ub[32];
            uint32_t e = 148, prev = 4;
            auto step = [&](float (&u)[32], const uint32_t (&a)[32], const uint32_t (&b)[32], int acc) {
                mbar_wait(bar_full + 8 * (e & 3), (e >> 2) & 1);
                const uint64_t dv = mkdesc(sb + (e & 3) * SLOT, UNIT, 1024);
                if (!acc) fence_regs(u);
                WG_FENCE();
#pragma unroll
                for (int ks = 0; ks < 8; ks++) mma_rs64<1>(u, a[4 * ks], a[4 * ks + 1], a[4 * ks + 2], a[4 * ks + 3], dv + ks * 128, ks | acc);
#pragma unroll
                for (int ks = 0; ks < 8; ks++) mma_rs64<1>(u, b[4 * ks], b[4 * ks + 1], b[4 * ks + 2], b[4 * ks + 3], dv + 1024 + ks * 128, 1);
                WG_COMMIT();
                WG_WAIT(1);
                if (prev < 4 && e < 167) release(prev);
                prev = e & 3;
                e++;
            };
            auto store = [&](float (&u)[32], uint8_t* dst) {
                fence_regs(u);
#pragma unroll
                for (int i = 0; i < 4; i++)
                    st_relaxed4(dst + i * 512, pack_bf16(u[8 * i], u[8 * i + 1]), pack_bf16(u[8 * i + 2], u[8 * i + 3]),
                                pack_bf16(u[8 * i + 4], u[8 * i + 5]), pack_bf16(u[8 * i + 6], u[8 * i + 7]));
            };
#pragma unroll
            for (int i = 0; i < 8; i++) at[i] = 0;
#pragma unroll
            for (int i = 0; i < 32; i++) { ua[i] = 0.f; ub[i] = 0.f; }
            fence_regs(q); fence_regs(p);
            step(ua, q, p, 0);
            frag_load(a1, frag + 4096);
            mbar_wait(bar_full + 8, 1);
            frag_load(a2, frag + 8192);
            step(ub, q, p, 0);
            WG_WAIT(0);
            release(1);
            prev = 4;
            fence_regs(a1); fence_regs(a2); fence_regs(ua); fence_regs(ub);
#pragma unroll 1
            for (int ch = 0; ch < 4; ch++) {
                step(ua, a1, a2, 1);
                if (ch > 0) {
                    if (ch >= 2) {
#pragma unroll
                        for (int i = 0; i < 4; i++) at[i] = at[4 + i];
                        sum8_slot(at + 4, e);
                        __syncwarp();
                        release(e & 3);
                        e++;
                        WG_WAIT(0);
                        release(prev);
                        prev = 4;
                    }
                    step(ub, q, p, 0);
                } else {
                    WG_WAIT(0);
                }
                store(ua, frag + ch * 4096);
                step(ub, a1, a2, 1);
                step(ua, q, p, 0);
                store(ub, frag + ch * 4096 + 2048);
                __syncwarp();
                if (lane == 0 && ch < 3) mbar_arrive(bar_pub + 8 + 8 * ch);
            }
            mb = g_frag + (size_t)(qb * 64 + j) * WREG + 3 * 4096 + tid * 16;
            step(ua, a1, a2, 1);
            mbar_wait(bar_full, 0);
            mbar_wait(bar_g, 0);
            WG_WAIT(0);
            store(ua, frag + 4 * 4096);
        }
        DBG_T(81);
        DBG_G(122);

        const int tid_ = __shfl_sync(0xffffffffu, tid, lane);
        {
        const int tid = tid_, lane = tid & 31;
        const int g8 = lane >> 2, qd = lane & 3, l16 = lane & 15;
        const uint8_t* mbase = smem_raw;
        const uint2* mp = reinterpret_cast<const uint2*>(mbase + M_MOD) + cw * 8 + qd;
        auto modp = [&](int which, int k) { return pair_of(mp + which * (D_ / 2), k, cw); };
        uint32_t x1[20], h2[18], c1[9], sv[9], wr[9];
        uint4 wf[27];
        uint32_t k1, k2;
        const uint32_t xs = sb + l16 * XP + (lane >> 4) * 16 + cw * 32;
        auto load_wf = [&](auto lo, auto hi) {
            const uint32_t wa = sb + SM_Q + ((cw & 1) * D_ + (cw >> 1) * 144 + (lane & 7) + (lane >> 4) * 8) * 80 + (lane & 8) * 2;
#pragma unroll
            for (int i = lo.value; i < hi.value; i++) wf[i] = ldsm4t(wa + (i / 3) * 1280 + (i % 3) * 32);
        };
        auto stage_out = [&]() {
#pragma unroll
            for (int k = 0; k < 18; k++) x1[k] = badd2(x1[k], bmul2(modp(3, k >> 1), h2[k]));
#pragma unroll
            for (int ch = 0; ch < 4; ch++) stsm_x4(xs + ch * 256, x1[4 * ch], x1[4 * ch + 1], x1[4 * ch + 2], x1[4 * ch + 3]);
            asm volatile("stmatrix.sync.aligned.m8n8.x2.shared.b16 [%0], {%1, %2};\nfence.proxy.async.shared::cta;"
                         ::"r"(xs + 1024 - cw * 16), "r"(x1[16]), "r"(x1[17]) : "memory");
        };
        const uint2* candp = reinterpret_cast<const uint2*>(&g_cand[((blockIdx.x & (CREP - 1)) * NCTA + (tid >> 1)) * 2]) + (tid & 1);
        uint2 cd;
        {
            const uint8_t* mb4 = mb + 4096 + ((cw >> 1) - cw) * 512 + (cw & 1) * 8;
            uint32_t ga[9], it = 0;
            load3();
            mbar_wait(bar_full + 8, 0);
            uint2 u[8];
            auto load4 = [&]() {
#pragma unroll
                for (int src = 0; src < 8; src++) u[src] = ld_relaxed8(mb4 + (size_t)src * 8 * WREG);
            };
            {
                uint4 v[8];
#pragma unroll
                for (int src = 0; src < 8; src++) v[src] = lds128(sb + SLOT + src * 4096 + tid * 16);
                sum8(at + 8, v);
            }
            const uint32_t* wp = reinterpret_cast<const uint32_t*>(mbase + M_WR) + cw * 8 + qd;
            rows_load(x1, xs, cw);
#pragma unroll
            for (int k = 0; k < 9; k++) {
                ga[k] = modp(0, k); sv[k] = modp(1, k); c1[k] = badd2(modp(2, k), 0x3f803f80u);
                wr[k] = k < 8 ? wp[(k >> 1) * 64 + (k & 1) * 4] : (wp - cw * 4)[256];
            }
            float st[12];
#pragma unroll
            for (int i = 0; i < 12; i++) st[i] = 0.f;
            auto add_pair = [&](int k) {
                x1[2 * k] = badd2(x1[2 * k], bmul2(ga[k], at[2 * k]));
                x1[2 * k + 1] = badd2(x1[2 * k + 1], bmul2(ga[k], at[2 * k + 1]));
                stats_add(st, x1[2 * k], x1[2 * k + 1]);
            };
#pragma unroll
            for (int k = 0; k < 6; k++) add_pair(k);
            fence_regs(ga); fence_regs(sv); fence_regs(c1); fence_regs(wr); fence_regs(x1); fence_regs(st);
#pragma unroll 1
            while (true) {
                uint32_t mx = 0;
#pragma unroll
                for (int src = 0; src < 8; src++) mx = __vimax3_u32(__vimax3_u32(mx, v3[src].x, v3[src].y), v3[src].z, v3[src].w);
                if (!__any_sync(0xffffffffu, mx == ~0u) || it >= SPIN / 16) break;
#pragma unroll 1
                while (__any_sync(0xffffffffu, ld_relaxed8(mb - lane * 16 + (size_t)(lane & 7) * 8 * WREG).x == ~0u) && ++it < SPIN / 16) {}
                it++;
                load3();
            }
            load4();
            sum8(at + 12, v3);
            add_pair(6); add_pair(7);
            load_wf(IC<0>{}, IC<WF0>{});
            fence_regs(st);
#pragma unroll 1
            while (true) {
                uint32_t mx = 0;
#pragma unroll
                for (int src = 0; src < 8; src++) mx = __vimax3_u32(mx, u[src].x, u[src].y);
                if (!__any_sync(0xffffffffu, mx == ~0u) || ++it >= SPIN / 16) break;
                load4();
            }
            if (lane < 4) mbar_arrive_cluster(rel_base + 8 * (2 + (lane >> 1)));
            float d[8] = {0.f, 0.f, 0.f, 0.f, 0.f, 0.f, 0.f, 0.f};
#pragma unroll
            for (int src = 0; src < 8; src++) mma1688(d + 4 * (src & 1), u[src].x, u[src].y, eye);
            at[16] = pack_bf16(d[0] + d[4], d[1] + d[5]); at[17] = pack_bf16(d[2] + d[6], d[3] + d[7]);
            add_pair(8);
            DBG_G(123);
            float4* st4 = reinterpret_cast<float4*>(red);
            rows_normalise(h2, x1, st, st4, cw, lane);
#pragma unroll
            for (int k = 0; k < 18; k++) h2[k] = badd2(bmul2(h2[k], c1[k >> 1]), sv[k >> 1]);
            float rs[8] = {0.f, 0.f, 0.f, 0.f, 0.f, 0.f, 0.f, 0.f};
#pragma unroll
            for (int k = 0; k < 9; k++)
                mma1688(rs + 4 * (k & 1), h2[2 * k], h2[2 * k + 1], wr[k]);
            if (qd < 2) red[256 + (qd * 8 + g8) * 8 + cw] = qd ? rs[2] + rs[6] : rs[0] + rs[4];
            bar_sync(3, 256);
            const float4 r0 = st4[64 + l16 * 2], r1 = st4[65 + l16 * 2];
            const uint32_t b = __float_as_uint(((r0.x + r0.y) + (r0.z + r0.w)) + ((r1.x + r1.y) + (r1.z + r1.w)));
            const uint32_t key = (((b & 0x80000000u) ? ~b : (b | 0x80000000u)) | 2047u) - (rg * 16 + l16);
            top2(key, k1, k2);
            if (tid < CREP) st_relaxed(&g_cand[(tid * NCTA + rg) * 2], k1, tag, k2, tag);
            cd = make_uint2((tid & 1) ? k2 : k1, tag);
            if ((tid >> 1) != rg) cd = ld_relaxed64(candp);
            uint32_t todo = (((1u << (~k1 & 15)) | (1u << (~k2 & 15))) >> g8) & 0x101;
#pragma unroll 1
            while (todo) {
                const bool hi = !(todo & 1);
                uint4* dst = &g_rows[(rg * 16 + g8 + hi * 8) * (D_ / 2) + cw * 4 + qd];
                uint2* dst4 = reinterpret_cast<uint2*>(dst + 128 - cw * 4 + (cw >> 1) * 4) + (cw & 1);
#pragma unroll
                for (int ch = 0; ch < 4; ch++) st_relaxed(dst + ch * 32, hi ? h2[4 * ch + 1] : h2[4 * ch], tag, hi ? h2[4 * ch + 3] : h2[4 * ch + 2], tag);
                st_relaxed64(dst4, hi ? h2[17] : h2[16], tag);
#pragma unroll
                for (int ch = 0; ch < 4; ch++) st_relaxed(dst + D_ / 4 + ch * 32, hi ? x1[4 * ch + 1] : x1[4 * ch], tag, hi ? x1[4 * ch + 3] : x1[4 * ch + 2], tag);
                st_relaxed64(dst4 + D_ / 2, hi ? x1[17] : x1[16], tag);
                todo &= todo - 1;
            }
            __syncwarp();
            stage_out();
        }
        DBG_G(110);
        float2* part = reinterpret_cast<float2*>(smem_raw + SLOT);
        bf16* act = reinterpret_cast<bf16*>(smem_raw + SLOT + 4096);
        {
            uint32_t it = 0;
#pragma unroll 1
            while (cd.y != tag && ++it < SPIN / 16) cd = ld_relaxed64(candp);
            __syncwarp();
            top2(cd.x, k1, k2);
            if (lane == 0) reinterpret_cast<uint2*>(red + 384)[cw] = make_uint2(k1, k2);
            bar_sync(3, 256);
            DBG_G(111);
            top2(reinterpret_cast<const uint32_t*>(red + 384)[l16], k1, k2);
        }
        const int sel0 = ~k1 & 2047, sel1 = ~k2 & 2047;
        uint4 b[9], b2[3];
        {
            uint2* hs = reinterpret_cast<uint2*>(smem_raw + SLOT + 8192);
            const uint4 *p0 = &g_rows[sel0 * (D_ / 2) + tid], *p1 = &g_rows[sel1 * (D_ / 2) + tid];
            uint4 v0 = make_uint4(0, tag, 0, tag), v1 = v0;
            if (tid < D_ / 4) { v0 = ld_relaxed2(p0); v1 = ld_relaxed2(p1); }
            load_wf(IC<WF0>{}, IC<27>{});
            mbar_wait(bar_full + 8 * 2, 0);
            mbar_wait(bar_full + 8 * 3, 0);
            {
                const uint32_t da = sb + (lane < 18 ? 2 * SLOT + lane * XP : 3 * SLOT + (lane - 18) * XP) + cw * 144;
                const uint32_t db = sb + 3 * SLOT + (14 + (lane & 3)) * XP + cw * 144 + (lane >> 3) * 16;
#pragma unroll
                for (int i = 0; i < 9; i++) b[i] = ldsm4t(da + i * 16);
#pragma unroll
                for (int i = 0; i < 3; i++) b2[i] = ldsm4t(db + i * 48);
            }
            uint32_t it = 0;
#pragma unroll 1
            while (((v0.y ^ tag) | (v0.w ^ tag) | (v1.y ^ tag) | (v1.w ^ tag)) && ++it < SPIN / 16) { v0 = ld_relaxed2(p0); v1 = ld_relaxed2(p1); }
            if (tid < D_ / 4) {
                hs[tid] = make_uint2(v0.x, v0.z);
                hs[148 + tid] = make_uint2(v1.x, v1.z);
            }
            bar_sync(3, 256);
            DBG_G(112);
            if (tid == 255) {
                reinterpret_cast<int2*>(red + 416)[0] = make_int2(sel0, sel1);
                mbar_arrive(bar_out);
            }
            uint2 bv[9];
#pragma unroll
            for (int i = 0; i < 9; i++) bv[i] = hs[(g8 & 1) * 148 + (cw >> 1) * 36 + i * 4 + qd];
            float acc[24];
#pragma unroll
            for (int i = 0; i < 24; i++) acc[i] = 0.f;
#pragma unroll
            for (int i = 0; i < 27; i++) mma16816(acc + 4 * (i % 6), wf[i].x, wf[i].y, wf[i].z, wf[i].w, bv[i / 3].x, bv[i / 3].y);
            if (qd == 0) {
#pragma unroll
                for (int i = 0; i < 5; i++) part[cw * 48 + i * 8 + g8] = make_float2(acc[2 * i] + acc[12 + 2 * i], acc[2 * i + 1] + acc[13 + 2 * i]);
            }
        }
        {
            uint2* dst = &g_ypart[(((g8 & 1) * 36 + ((cw * 9) >> 1)) * NCTA + blockIdx.x) * 8 + (cw & 1) * 4 + qd];
            uint2* dst1 = dst + ((cw & 1) ? NCTA * 8 - 4 : 4);
            bar_sync(3, 256);
            {
                const float* pp = reinterpret_cast<const float*>(part) + ((blockIdx.x & 1) << 3) + (tid & 127);
                const float gs = rbf((pp[0] + pp[192]) + (pp[384] + pp[576])), us = rbf((pp[96] + pp[288]) + (pp[480] + pp[672]));
                const float v = rbf(gs * sigmoidf_(gs)) * us;
                if (tid < 80) act[(tid & 1) * 56 + (tid >> 1)] = __float2bfloat16_rn(tid < 72 ? v : 0.f);
            }
            bar_sync(3, 256);
            DBG_G(113);
            const uint32_t ap = sb + SLOT + 4096 + (lane & 1) * 112 + (lane >> 4) * 16;
            const uint4 a0 = ldsm4(ap), a1 = ldsm4(ap + 32), a2 = ldsm4(ap + 64);
            float y[36];
#pragma unroll
            for (int i = 0; i < 36; i++) y[i] = 0.f;
#pragma unroll
            for (int i = 0; i < 9; i++) {
                const uint32_t bl = i % 3 == 0 ? b2[i / 3].x : i % 3 == 1 ? b2[i / 3].y : b2[i / 3].z;
                mma16816(y + 4 * i, a0.x, a0.y, a0.z, a0.w, b[i].x, b[i].y);
                mma16816(y + 4 * i, a1.x, a1.y, a1.z, a1.w, b[i].z, b[i].w);
                mma1688(y + 4 * i, a2.x, a2.y, bl);
            }
#pragma unroll
            for (int i = 0; i < 9; i++)
                if (lane < 8) st_relaxed64(((i & 1) ? dst1 : dst) + (i >> 1) * (NCTA * 8), __float_as_uint(y[4 * i]), __float_as_uint(y[4 * i + 1]));
        }
        DBG_G(114);
        if (blockIdx.x == 127 && tid == 0) gs->epoch[0] = tag;
        if (blockIdx.x < 72) {
            const int tok = blockIdx.x >= 36, grp = blockIdx.x - tok * 36;
            const uint2* src = &g_ypart[blockIdx.x * NCTA * 8 + tid];
            const uint4* hsrc = &g_rows[(tok ? sel1 : sel0) * (D_ / 2) + grp * 4 + qd];
            uint2 v[4];
            uint4 hv, xv;
            uint32_t it = 0;
            bool miss;
#pragma unroll 1
            do {
#pragma unroll
                for (int i = 0; i < 4; i++) v[i] = ld_relaxed64(src + i * 256);
                hv = ld_relaxed2(hsrc);
                xv = ld_relaxed2(hsrc + D_ / 4);
                miss = max(__vimax3_u32(v[0].x, v[1].x, v[2].x), v[3].x) == ~0u || ((hv.y ^ tag) | (hv.w ^ tag) | (xv.y ^ tag) | (xv.w ^ tag));
            } while (__any_sync(0xffffffffu, miss) && ++it < SPIN / 16);
            const uint32_t ksel = ((tok ? k2 : k1) & ~2047u) | 1024u;
            const float sg = sigmoidf_(rbf(__uint_as_float((ksel & 0x80000000u) ? (ksel & 0x7fffffffu) : ~ksel)));
            float y0 = (__uint_as_float(v[0].x) + __uint_as_float(v[1].x)) + (__uint_as_float(v[2].x) + __uint_as_float(v[3].x));
            float y1 = (__uint_as_float(v[0].y) + __uint_as_float(v[1].y)) + (__uint_as_float(v[2].y) + __uint_as_float(v[3].y));
            y0 += __shfl_xor_sync(0xffffffffu, y0, 8); y1 += __shfl_xor_sync(0xffffffffu, y1, 8);
            y0 += __shfl_xor_sync(0xffffffffu, y0, 16); y1 += __shfl_xor_sync(0xffffffffu, y1, 16);
            if (lane < 8) reinterpret_cast<float2*>(red)[cw * 8 + lane] = make_float2(y0, y1);
            bar_sync(3, 256);
            if (cw == 0) {
                const float2 t0_ = reinterpret_cast<const float2*>(red)[lane], t1_ = reinterpret_cast<const float2*>(red)[32 + lane];
                y0 = t0_.x + t1_.x; y1 = t0_.y + t1_.y;
                y0 += __shfl_xor_sync(0xffffffffu, y0, 8); y1 += __shfl_xor_sync(0xffffffffu, y1, 8);
                y0 += __shfl_xor_sync(0xffffffffu, y0, 16); y1 += __shfl_xor_sync(0xffffffffu, y1, 16);
                const uint32_t y2 = bmul2(pack_bf16(y0, y1), pack_bf16(sg, sg));
                const int cp = grp * 8 + (lane & 7);
                const uint32_t gb = reinterpret_cast<const uint2*>(mbase + M_MOD)[3 * (D_ / 2) + cp].x;
                if (lane < 8)
                    reinterpret_cast<uint32_t*>(args.out + (size_t)(tok ? sel1 : sel0) * D_)[cp] =
                        badd2((lane & 4) ? xv.z : xv.x, bmul2(gb, badd2((lane & 4) ? hv.z : hv.x, y2)));
            }
        }
        }
        DBG_T(88);
        DBG_G(121);
    }
}

typedef CUresult (*EncodeFn)(CUtensorMap*, CUtensorMapDataType, cuuint32_t, void*, const cuuint64_t*, const cuuint64_t*,
                             const cuuint32_t*, const cuuint32_t*, CUtensorMapInterleave, CUtensorMapSwizzle,
                             CUtensorMapL2promotion, CUtensorMapFloatOOBfill);

static void make_map(EncodeFn enc, CUtensorMap* m, const void* ptr, int rank, const cuuint64_t* dims,
                     const cuuint64_t* strides, const cuuint32_t* box, CUtensorMapSwizzle sw = CU_TENSOR_MAP_SWIZZLE_128B,
                     CUtensorMapDataType dt = CU_TENSOR_MAP_DATA_TYPE_BFLOAT16) {
    const cuuint32_t es[3] = {1, 1, 1};
    enc(m, dt, rank, const_cast<void*>(ptr), dims, strides, box, es,
        CU_TENSOR_MAP_INTERLEAVE_NONE, sw, CU_TENSOR_MAP_L2_PROMOTION_L2_128B,
        CU_TENSOR_MAP_FLOAT_OOB_FILL_NONE);
}

extern "C" void kernel_launch(void* const* d_in, const int* in_sizes, int n_in, void* d_out, int out_size) {
    const bf16* x = (const bf16*)d_in[0];
    const bf16* kc = (const bf16*)d_in[1];
    const bf16* vc = (const bf16*)d_in[2];
    const bf16* wq = (const bf16*)d_in[3];
    const bf16* wo = (const bf16*)d_in[4];
    const bf16* w_r = (const bf16*)d_in[6];
    const bf16* w_gate = (const bf16*)d_in[7];
    const bf16* w_up = (const bf16*)d_in[8];
    const bf16* w_down = (const bf16*)d_in[9];
    const bf16* cvec = (const bf16*)d_in[10];
    const bf16* w_mod = (const bf16*)d_in[11];
    bf16* out = (bf16*)d_out;

    void* fn = nullptr;
    cudaDriverEntryPointQueryResult qr;
    cudaGetDriverEntryPoint("cuTensorMapEncodeTiled", &fn, cudaEnableDefault, &qr);
    EncodeFn enc = (EncodeFn)fn;
    void* p_s;
    cudaGetSymbolAddress(&p_s, g_s);

    CUtensorMap tm_wq, tm_k, tm_v, tm_wo, tm_p, tm_x, tm_d, tm_g, tm_u;
    { cuuint64_t d[2] = {QD, D_}, s[1] = {QD * 2}; cuuint32_t b[2] = {64, 128}; make_map(enc, &tm_wq, wq, 2, d, s, b); }
    { cuuint64_t d[2] = {DH, HKV * S_}, s[1] = {DH * 2}; cuuint32_t b[2] = {64, 128};
      make_map(enc, &tm_k, kc, 2, d, s, b); make_map(enc, &tm_v, vc, 2, d, s, b); }
    { cuuint64_t d[2] = {D_, QD}, s[1] = {D_ * 2}; cuuint32_t b[2] = {64, 128}; make_map(enc, &tm_wo, wo, 2, d, s, b); }
    { cuuint64_t d[3] = {256, 160, NCTA}, s[2] = {1024, 8 * WREG}; cuuint32_t b[3] = {256, 4, 8};
      make_map(enc, &tm_p, ((Scratch*)p_s)->frag, 3, d, s, b, CU_TENSOR_MAP_SWIZZLE_NONE, CU_TENSOR_MAP_DATA_TYPE_UINT32); }
    { cuuint64_t d[2] = {D_ / 4, S_}, s[1] = {D_ * 2}; cuuint32_t b[2] = {XP / 8, 16};
      make_map(enc, &tm_x, x, 2, d, s, b, CU_TENSOR_MAP_SWIZZLE_NONE, CU_TENSOR_MAP_DATA_TYPE_UINT64); }
    { cuuint64_t d[2] = {D_ / 4, F_}, s[1] = {D_ * 2}; cuuint32_t b[2] = {XP / 8, 18};
      make_map(enc, &tm_d, w_down, 2, d, s, b, CU_TENSOR_MAP_SWIZZLE_NONE, CU_TENSOR_MAP_DATA_TYPE_UINT64); }
    { cuuint64_t d[2] = {F_, D_}, s[1] = {F_ * 2}; cuuint32_t b[2] = {40, 24};
      make_map(enc, &tm_g, w_gate, 2, d, s, b, CU_TENSOR_MAP_SWIZZLE_NONE); make_map(enc, &tm_u, w_up, 2, d, s, b, CU_TENSOR_MAP_SWIZZLE_NONE); }

    cudaFuncSetAttribute(fused_kernel<true>, cudaFuncAttributeMaxDynamicSharedMemorySize, SM_TOTAL);
    cudaFuncSetAttribute(fused_kernel<false>, cudaFuncAttributeMaxDynamicSharedMemorySize, SM_TOTAL);
    cudaLaunchConfig_t cfg = {};
    cfg.gridDim = NCTA + 4; cfg.blockDim = 384; cfg.dynamicSmemBytes = SM_TOTAL;
    cudaLaunchAttribute at;
    at.id = cudaLaunchAttributeClusterDimension; at.val.clusterDim.x = 2; at.val.clusterDim.y = 1; at.val.clusterDim.z = 1;
    cfg.attrs = &at; cfg.numAttrs = 1;
    int ncl = 0;
    if (cudaOccupancyMaxActiveClusters(&ncl, fused_kernel<true>, &cfg) != cudaSuccess) { ncl = 0; cudaGetLastError(); }
    Args args{w_mod, cvec, (Scratch*)p_s, out, x, kc, vc, wq, wo, w_r, w_down};
    if (USE_SPARE && ncl >= NCTA / 2 + 2)
        fused_kernel<true><<<NCTA + 4, 384, SM_TOTAL>>>(args, tm_wq, tm_k, tm_v, tm_wo, tm_p, tm_x, tm_d, tm_g, tm_u);
    else
        fused_kernel<false><<<NCTA, 384, SM_TOTAL>>>(args, tm_wq, tm_k, tm_v, tm_wo, tm_p, tm_x, tm_d, tm_g, tm_u);
}
```

```cpp
#include <cuda_runtime.h>
#include <cuda_bf16.h>
#include <cuda.h>
#include <stdint.h>
#include <math.h>

typedef __nv_bfloat16 bf16;

constexpr int S_ = 2048;
constexpr int D_ = 576;
constexpr int HQ = 32, HKV = 16, DH = 128;
constexpr int F_ = 4608;
constexpr int QD = HQ * DH;

constexpr int NCTA = 128;
constexpr int WREG = 5 * 4096;
constexpr int CREP = 8;
constexpr int RSLOT = 144;
constexpr int MREP = 4;
struct Scratch {
    unsigned int epoch[128];
    unsigned int flag_mod[NCTA];
    unsigned int flag_part[16 * 32];
    unsigned int flag_q3[16 * 32];
    unsigned int flag_h[NCTA * 32];
    uint2 mod1[MREP * D_];
    uint32_t mod2[4 * D_];
    uint4 cand[CREP * NCTA * 2];
    uint2 ypart[72 * NCTA * 8];
    uint4 h[2][NCTA * 36 * 32];
    uint4 q3[NCTA * 8 * 128];
    uint4 rows[NCTA * 2 * RSLOT];
    uint8_t frag[NCTA * 8 * WREG];
    uint8_t keep[NCTA * 8 * 4096];
};
__device__ __align__(1024) Scratch g_s;
#define g_h gs->h[tag & 1]
#define g_q3 gs->q3
#define g_keep gs->keep
#define g_flag_h gs->flag_h
#define g_flag_part gs->flag_part
#define g_flag_mod gs->flag_mod
#define g_flag_q3 gs->flag_q3
#define g_frag gs->frag
#define g_cand gs->cand
#define g_ypart gs->ypart
#define g_rows gs->rows

#define DBG_INIT()
#define DBG_P(i)
#define DBG_PG(i)
#define DBG_T(i)
#define DBG_G(i)

__device__ __forceinline__ uint32_t pack_bf16(float lo, float hi) {
    uint32_t r;
    asm("cvt.rn.bf16x2.f32 %0, %1, %2;" : "=r"(r) : "f"(hi), "f"(lo));
    return r;
}
__device__ __forceinline__ float rbf(float x) { return __uint_as_float(pack_bf16(0.f, x)); }
__device__ __forceinline__ float bf_lo(uint32_t v) { return __uint_as_float(v << 16); }
__device__ __forceinline__ float bf_hi(uint32_t v) { return __uint_as_float(v & 0xffff0000u); }
__device__ __forceinline__ float ex2(float x) {
    float y;
    asm("ex2.approx.ftz.f32 %0, %1;" : "=f"(y) : "f"(x));
    return y;
}
template <class T>
__device__ __forceinline__ T* padd(T* p, uint32_t off) {
    unsigned long long r;
    asm("{\n.reg .b32 l, h;\nmov.b64 {l, h}, %1;\nadd.cc.u32 l, l, %2;\naddc.u32 h, h, 0;\nmov.b64 %0, {l, h};\n}" : "=l"(r) : "l"(p), "r"(off));
    return reinterpret_cast<T*>(r);
}
__device__ __forceinline__ uint32_t smem_u32(const void* p) { return (uint32_t)__cvta_generic_to_shared(p); }
__device__ __forceinline__ void mbar_init(uint32_t bar, uint32_t cnt) {
    asm volatile("mbarrier.init.shared::cta.b64 [%0], %1;" ::"r"(bar), "r"(cnt) : "memory");
}
__device__ __forceinline__ void mbar_expect_tx(uint32_t bar, uint32_t bytes) {
    asm volatile("mbarrier.arrive.expect_tx.shared::cta.b64 _, [%0], %1;" ::"r"(bar), "r"(bytes) : "memory");
}
__device__ __forceinline__ void mbar_arrive(uint32_t bar) {
    asm volatile("mbarrier.arrive.shared::cta.b64 _, [%0];" ::"r"(bar) : "memory");
}
__device__ __forceinline__ void mbar_arrive_cluster(uint32_t cluster_addr) {
    asm volatile("mbarrier.arrive.shared::cluster.b64 _, [%0];" ::"r"(cluster_addr) : "memory");
}
constexpr uint32_t SPIN = 1u << 20;
__device__ __forceinline__ void mbar_wait(uint32_t bar, uint32_t parity) {
    asm volatile("{\n.reg .pred p;\n.reg .b32 c;\nmov.b32 c, 0;\n"
                 "W_%=:\nmbarrier.try_wait.parity.shared::cta.b64 p, [%0], %1;\n@p bra D_%=;\n"
                 "add.u32 c, c, 1;\nsetp.lt.u32 p, c, 0x100000;\n@p bra W_%=;\nD_%=:\n}"
                 ::"r"(bar), "r"(parity) : "memory");
}
__device__ __forceinline__ void anchor(uint32_t addr, float v) {
    asm volatile("{\n.reg .pred p;\nsetp.lt.f32 p, %1, 0f00000000;\n@p st.volatile.shared.f32 [%0], %1;\n}" ::"r"(addr), "f"(v) : "memory");
}
__device__ __forceinline__ void mbar_wait_sleep(uint32_t bar, uint32_t parity) {
    asm volatile("{\n.reg .pred p;\n.reg .b32 c;\nmov.b32 c, 0;\n"
                 "W_%=:\nmbarrier.try_wait.parity.shared::cta.b64 p, [%0], %1, 5000;\n@p bra D_%=;\n"
                 "add.u32 c, c, 1;\nsetp.lt.u32 p, c, 0x20000;\n@p bra W_%=;\nD_%=:\n}"
                 ::"r"(bar), "r"(parity) : "memory");
}
__device__ __forceinline__ uint32_t load_tag(const Scratch* gs) {
    uint32_t tag;
    asm volatile("ld.global.ca.u32 %0, [%1];" : "=r"(tag) : "l"(gs->epoch) : "memory");
    return tag + 1;
}
__device__ __forceinline__ uint4 ld_relaxed(const uint4* p) {
    uint4 v;
    asm volatile("ld.relaxed.gpu.global.v4.u32 {%0,%1,%2,%3}, [%4];" : "=r"(v.x), "=r"(v.y), "=r"(v.z), "=r"(v.w) : "l"(p) : "memory");
    return v;
}
__device__ __forceinline__ void st_relaxed(uint4* p, uint32_t a, uint32_t b, uint32_t c, uint32_t d) {
    asm volatile("{\n.reg .b64 u, v;\nmov.b64 u, {%1, %2};\nmov.b64 v, {%3, %4};\nst.relaxed.gpu.global.v2.b64 [%0], {u, v};\n}"
                 ::"l"(p), "r"(a), "r"(b), "r"(c), "r"(d) : "memory");
}
__device__ __forceinline__ void st_relaxed4(void* p, uint32_t a, uint32_t b, uint32_t c, uint32_t d) {
    asm volatile("st.relaxed.gpu.global.v4.u32 [%0], {%1, %2, %3, %4};" ::"l"(p), "r"(a), "r"(b), "r"(c), "r"(d) : "memory");
}
__device__ __forceinline__ uint2 ld_relaxed8(const void* p) {
    uint2 v;
    asm volatile("ld.relaxed.gpu.global.v2.u32 {%0,%1}, [%2];" : "=r"(v.x), "=r"(v.y) : "l"(p) : "memory");
    return v;
}
__device__ __forceinline__ uint2 ld_relaxed64(const uint2* p) {
    uint2 v;
    asm volatile("{\n.reg .b64 u;\nld.relaxed.gpu.global.b64 u, [%2];\nmov.b64 {%0, %1}, u;\n}" : "=r"(v.x), "=r"(v.y) : "l"(p) : "memory");
    return v;
}
__device__ __forceinline__ void st_relaxed64(uint2* p, uint32_t a, uint32_t b) {
    asm volatile("{\n.reg .b64 u;\nmov.b64 u, {%1, %2};\nst.relaxed.gpu.global.b64 [%0], u;\n}" ::"l"(p), "r"(a), "r"(b) : "memory");
}
__device__ __forceinline__ uint4 ld_relaxed2(const uint4* p) {
    uint4 v;
    asm volatile("{\n.reg .b64 u, w;\nld.relaxed.gpu.global.v2.b64 {u, w}, [%4];\nmov.b64 {%0, %1}, u;\nmov.b64 {%2, %3}, w;\n}"
                 : "=r"(v.x), "=r"(v.y), "=r"(v.z), "=r"(v.w) : "l"(p) : "memory");
    return v;
}
__device__ __forceinline__ void reload16(uint4& v, const void* p, uint32_t& miss) {
    asm volatile("{\n.reg .pred p;\n.reg .b32 m;\n.reg .b64 u, w;\nmax.u32 m, %0, %2;\nsetp.eq.u32 p, m, 0xffffffff;\n"
                 "mov.b64 u, {%0, %1};\nmov.b64 w, {%2, %3};\n@p ld.relaxed.gpu.global.v2.b64 {u, w}, [%5];\n"
                 "mov.b64 {%0, %1}, u;\nmov.b64 {%2, %3}, w;\n@p mov.u32 %4, 1;\n}"
                 : "+r"(v.x), "+r"(v.y), "+r"(v.z), "+r"(v.w), "+r"(miss) : "l"(p) : "memory");
}
__device__ __forceinline__ void reload8(uint2& v, const void* p, uint32_t& miss) {
    asm volatile("{\n.reg .pred p;\n.reg .b64 u;\nsetp.eq.u32 p, %0, 0xffffffff;\nmov.b64 u, {%0, %1};\n"
                 "@p ld.relaxed.gpu.global.b64 u, [%3];\nmov.b64 {%0, %1}, u;\n@p mov.u32 %2, 1;\n}"
                 : "+r"(v.x), "+r"(v.y), "+r"(miss) : "l"(p) : "memory");
}
__device__ __forceinline__ uint32_t ld_relaxed32(const void* p) {
    uint32_t v;
    asm volatile("ld.relaxed.gpu.global.u32 %0, [%1];" : "=r"(v) : "l"(p) : "memory");
    return v;
}
__device__ __forceinline__ void poll2x2(const uint4* p0, const uint4* p1, uint32_t tag, uint4& o0, uint4& o1) {
    uint4 v0, v1;
    uint32_t miss, it = 0;
#pragma unroll 1
    do {
        v0 = ld_relaxed2(p0); v1 = ld_relaxed2(p1);
        miss = (v0.y ^ tag) | (v0.w ^ tag) | (v1.y ^ tag) | (v1.w ^ tag);
    } while (miss && ++it < SPIN / 16);
    o0 = v0; o1 = v1;
}
__device__ __forceinline__ void flag_wait(const unsigned int* p, uint32_t tag) {
    uint32_t v, it = 0;
#pragma unroll 1
    do {
        asm volatile("ld.relaxed.gpu.global.u32 %0, [%1];" : "=r"(v) : "l"(p) : "memory");
    } while (__any_sync(0xffffffffu, v != tag) && ++it < SPIN / 16);
    asm volatile("fence.acquire.gpu;" ::: "memory");
    __syncwarp();
}
__device__ __forceinline__ bool elect() {
    uint32_t p;
    asm volatile("{\n.reg .pred p;\nelect.sync _|p, 0xffffffff;\nselp.u32 %0, 1, 0, p;\n}" : "=r"(p));
    return p;
}
__device__ __forceinline__ void flag_release(unsigned int* p, uint32_t tag) {
    asm volatile("st.release.gpu.global.u32 [%0], %1;" ::"l"(p), "r"(tag) : "memory");
}
__device__ __forceinline__ uint32_t touch(const void* p) {
    uint32_t v;
    asm volatile("ld.global.nc.L1::no_allocate.L2::128B.u32 %0, [%1];" : "=r"(v) : "l"(p));
    return v;
}
__device__ __forceinline__ void bar_sync(int id, int n) { asm volatile("bar.sync %0, %1;" ::"r"(id), "r"(n) : "memory"); }
__device__ __forceinline__ void bar_arrive(int id, int n) { asm volatile("bar.arrive %0, %1;" ::"r"(id), "r"(n) : "memory"); }

constexpr uint64_t EVICT_NORMAL = 0x1000000000000000ull, EVICT_FIRST = 0x12F0000000000000ull;
__device__ __forceinline__ void tma2d(uint32_t dst, const CUtensorMap* m, int c0, int c1, uint32_t bar) {
    asm volatile("cp.async.bulk.tensor.2d.shared::cluster.global.mbarrier::complete_tx::bytes.L2::cache_hint [%0], [%1, {%3, %4}], [%2], %5;"
                 ::"r"(dst), "l"(m), "r"(bar), "r"(c0), "r"(c1), "l"(EVICT_FIRST) : "memory");
}
__device__ __forceinline__ void tma2d_mc(uint32_t dst, const CUtensorMap* m, int c0, int c1, uint32_t bar, uint64_t pol) {
    asm volatile("cp.async.bulk.tensor.2d.shared::cluster.global.mbarrier::complete_tx::bytes.multicast::cluster.L2::cache_hint [%0], [%1, {%3, %4}], [%2], %5, %6;"
                 ::"r"(dst), "l"(m), "r"(bar), "r"(c0), "r"(c1), "h"((uint16_t)3), "l"(pol) : "memory");
}
__device__ __forceinline__ void tma3d(uint32_t dst, const CUtensorMap* m, int c0, int c1, int c2, uint32_t bar) {
    asm volatile("cp.async.bulk.tensor.3d.shared::cluster.global.mbarrier::complete_tx::bytes.L2::cache_hint [%0], [%1, {%3, %4, %5}], [%2], %6;"
                 ::"r"(dst), "l"(m), "r"(bar), "r"(c0), "r"(c1), "r"(c2), "l"(EVICT_FIRST) : "memory");
}
__device__ __forceinline__ void bulk_load(uint32_t dst, const void* src, uint32_t bytes, uint32_t bar) {
    asm volatile("cp.async.bulk.shared::cluster.global.mbarrier::complete_tx::bytes [%0], [%1], %2, [%3];"
                 ::"r"(dst), "l"(src), "r"(bytes), "r"(bar) : "memory");
}
__device__ __forceinline__ void l2_prefetch(const void* src, uint32_t bytes) {
    asm volatile("cp.async.bulk.prefetch.L2.global [%0], %1;" ::"l"(src), "r"(bytes) : "memory");
}
__device__ __forceinline__ uint32_t bmul2(uint32_t a, uint32_t b) { uint32_t r; asm("mul.rn.bf16x2 %0, %1, %2;" : "=r"(r) : "r"(a), "r"(b)); return r; }
__device__ __forceinline__ uint32_t badd2(uint32_t a, uint32_t b) { uint32_t r; asm("add.rn.bf16x2 %0, %1, %2;" : "=r"(r) : "r"(a), "r"(b)); return r; }
__device__ __forceinline__ uint32_t bsub2(uint32_t a, uint32_t b) { uint32_t r; asm("sub.rn.bf16x2 %0, %1, %2;" : "=r"(r) : "r"(a), "r"(b)); return r; }
__device__ __forceinline__ uint32_t bmax2(uint32_t a, uint32_t b) { uint32_t r; asm("max.bf16x2 %0, %1, %2;" : "=r"(r) : "r"(a), "r"(b)); return r; }
__device__ __forceinline__ uint32_t bfma2(uint32_t a, uint32_t b, uint32_t c) { uint32_t r; asm("fma.rn.bf16x2 %0, %1, %2, %3;" : "=r"(r) : "r"(a), "r"(b), "r"(c)); return r; }
__device__ __forceinline__ uint4 lds128(uint32_t a) { uint4 v; asm volatile("ld.shared.v4.u32 {%0,%1,%2,%3}, [%4];" : "=r"(v.x), "=r"(v.y), "=r"(v.z), "=r"(v.w) : "r"(a) : "memory"); return v; }
__device__ __forceinline__ uint4 ldsm4(uint32_t a) {
    uint4 v;
    asm volatile("ldmatrix.sync.aligned.m8n8.x4.shared.b16 {%0,%1,%2,%3}, [%4];" : "=r"(v.x), "=r"(v.y), "=r"(v.z), "=r"(v.w) : "r"(a) : "memory");
    return v;
}
__device__ __forceinline__ uint4 ldsm4t(uint32_t a) {
    uint4 v;
    asm volatile("ldmatrix.sync.aligned.m8n8.x4.trans.shared.b16 {%0,%1,%2,%3}, [%4];" : "=r"(v.x), "=r"(v.y), "=r"(v.z), "=r"(v.w) : "r"(a) : "memory");
    return v;
}
__device__ __forceinline__ void mma1688(float* d, uint32_t a0, uint32_t a1, uint32_t b) {
    asm("mma.sync.aligned.m16n8k8.row.col.f32.bf16.bf16.f32 {%0,%1,%2,%3}, {%4,%5}, {%6}, {%0,%1,%2,%3};"
        : "+f"(d[0]), "+f"(d[1]), "+f"(d[2]), "+f"(d[3]) : "r"(a0), "r"(a1), "r"(b));
}
__device__ __forceinline__ void mma16816(float* d, uint32_t a0, uint32_t a1, uint32_t a2, uint32_t a3, uint32_t b0, uint32_t b1) {
    asm("mma.sync.aligned.m16n8k16.row.col.f32.bf16.bf16.f32 {%0,%1,%2,%3}, {%4,%5,%6,%7}, {%8,%9}, {%0,%1,%2,%3};"
                 : "+f"(d[0]), "+f"(d[1]), "+f"(d[2]), "+f"(d[3]) : "r"(a0), "r"(a1), "r"(a2), "r"(a3), "r"(b0), "r"(b1));
}
__device__ __forceinline__ void stsm_x4(uint32_t addr, uint32_t a, uint32_t b, uint32_t c, uint32_t d) {
    asm volatile("stmatrix.sync.aligned.m8n8.x4.shared.b16 [%0], {%1, %2, %3, %4};"
                 ::"r"(addr), "r"(a), "r"(b), "r"(c), "r"(d) : "memory");
}

__device__ __forceinline__ uint64_t mkdesc(uint32_t addr, uint32_t lbo, uint32_t sbo) {
    return (uint64_t)((addr & 0x3FFFF) >> 4) | ((uint64_t)(lbo >> 4) << 16) | ((uint64_t)(sbo >> 4) << 32) | (1ull << 62);
}
constexpr uint32_t SM0 = 1024;
__host__ __device__ constexpr uint32_t desc_lo(uint32_t off, uint32_t lbo) { return ((SM0 + off) >> 4) | ((lbo >> 4) << 16); }
__device__ __forceinline__ uint64_t desc_of(uint32_t lo) { return lo | (0x40000040ull << 32); }
#define WG_FENCE() asm volatile("wgmma.fence.sync.aligned;" ::: "memory")
#define WG_COMMIT() asm volatile("wgmma.commit_group.sync.aligned;" ::: "memory")
#define WG_WAIT(n) asm volatile("wgmma.wait_group.sync.aligned %0;" ::"n"(n) : "memory")

#define F8(a, i) "+f"(a[i]), "+f"(a[i + 1]), "+f"(a[i + 2]), "+f"(a[i + 3]), "+f"(a[i + 4]), "+f"(a[i + 5]), "+f"(a[i + 6]), "+f"(a[i + 7])
#define F16(a, i) F8(a, i), F8(a, i + 8)
#define F64(a) F16(a, 0), F16(a, 16), F16(a, 32), F16(a, 48)
#define F32(a) F16(a, 0), F16(a, 16)
#define L64 "%0,%1,%2,%3,%4,%5,%6,%7,%8,%9,%10,%11,%12,%13,%14,%15,%16,%17,%18,%19,%20,%21,%22,%23,%24,%25,%26,%27,%28,%29,%30,%31,%32,%33,%34,%35,%36,%37,%38,%39,%40,%41,%42,%43,%44,%45,%46,%47,%48,%49,%50,%51,%52,%53,%54,%55,%56,%57,%58,%59,%60,%61,%62,%63"
#define L32 "%0,%1,%2,%3,%4,%5,%6,%7,%8,%9,%10,%11,%12,%13,%14,%15,%16,%17,%18,%19,%20,%21,%22,%23,%24,%25,%26,%27,%28,%29,%30,%31"

template <int TB>
__device__ __forceinline__ void mma_rs128(float (&d)[64], uint32_t a0, uint32_t a1, uint32_t a2, uint32_t a3, uint64_t b, int acc) {
    asm volatile("{\n.reg .pred p;\nsetp.ne.b32 p, %69, 0;\n"
                 "wgmma.mma_async.sync.aligned.m64n128k16.f32.bf16.bf16 {" L64 "}, {%64,%65,%66,%67}, %68, p, 1, 1, %70;\n}"
                 : F64(d) : "r"(a0), "r"(a1), "r"(a2), "r"(a3), "l"(b), "r"(acc), "n"(TB));
}
template <int TB>
__device__ __forceinline__ void mma_rs64(float (&d)[32], uint32_t a0, uint32_t a1, uint32_t a2, uint32_t a3, uint64_t b, int acc) {
    asm volatile("{\n.reg .pred p;\nsetp.ne.b32 p, %37, 0;\n"
                 "wgmma.mma_async.sync.aligned.m64n64k16.f32.bf16.bf16 {" L32 "}, {%32,%33,%34,%35}, %36, p, 1, 1, %38;\n}"
                 : F32(d) : "r"(a0), "r"(a1), "r"(a2), "r"(a3), "l"(b), "r"(acc), "n"(TB));
}
template <int N>
__device__ __forceinline__ void fence_regs(float (&d)[N]) {
#pragma unroll
    for (int i = 0; i < N; i++) asm volatile("" : "+f"(d[i])::"memory");
}
template <int N>
__device__ __forceinline__ void fence_regs(uint32_t (&d)[N]) {
#pragma unroll
    for (int i = 0; i < N; i++) asm volatile("" : "+r"(d[i])::"memory");
}

template <int V> struct IC { static constexpr int value = V; };

constexpr int SLOT = 32768, UNIT = 16384;
constexpr int SM_Q = 4 * SLOT;
constexpr int SM_BAR = 7 * SLOT;
constexpr int SM_RED = SM_BAR + 512;
constexpr int SM_TOTAL = SM_BAR + 3072;
constexpr int XP = D_ * 2 + 16;
constexpr int M_MOD = 16 * XP;
constexpr int SM_T = SM_Q + 2 * D_ * 80, SM_TW = SM_T + D_ * 8, SM_TS = SM_TW + D_ * 2;
constexpr float CS = 0.08838834764831845f * 1.4426950408889634f;
#define LMAX 0.5f
#define LMIN 0x1p-104f
#define USE_SPARE 1
#define MAXG 2
#define SPLIT 10
#define ESPLIT 2
#define PV1 8
#define RW 2
#define HW 2
#define HW2 1
#define XDELAY 200
#define QDELAY 300
#define TMPF 1
#define PFD0 2000
#define PFD1 400
#define HSENT 1
#define HDELAY 500
#define STAGE 11
#define POFF 102.f
#define WF0 8
#define WF1 16
#define C3D 300
#define C4D 300
#define DD 0
#define OUTP 0
constexpr int PF_KV = 8, PF_WO = 120;

struct Args {
    const bf16 *w_mod, *cvec;
    Scratch* gs;
    bf16* out;
    const bf16 *x, *kc, *vc, *wq, *wo, *w_r, *w_down;
};

__device__ __forceinline__ void frag_store(uint8_t* p, const uint32_t (&a)[32]) {
#pragma unroll
    for (int i = 0; i < 8; i++)
        __stcg(reinterpret_cast<uint4*>(p + i * 512), make_uint4(a[4 * i], a[4 * i + 1], a[4 * i + 2], a[4 * i + 3]));
}
__device__ __forceinline__ void frag_load(uint32_t (&a)[32], const uint8_t* p) {
#pragma unroll
    for (int i = 0; i < 8; i++) {
        const uint4 v = __ldcg(reinterpret_cast<const uint4*>(p + i * 512));
        a[4 * i] = v.x; a[4 * i + 1] = v.y; a[4 * i + 2] = v.z; a[4 * i + 3] = v.w;
    }
}
__device__ __forceinline__ float quad_sum(float v) {
    v += __shfl_xor_sync(0xffffffffu, v, 1);
    return v + __shfl_xor_sync(0xffffffffu, v, 2);
}
__device__ __forceinline__ float quad_max(float v) {
    v = fmaxf(v, __shfl_xor_sync(0xffffffffu, v, 1));
    return fmaxf(v, __shfl_xor_sync(0xffffffffu, v, 2));
}
__device__ __forceinline__ float rcp_fast(float x) { float y; asm("rcp.approx.ftz.f32 %0, %1;" : "=f"(y) : "f"(x)); return y; }
__device__ __forceinline__ float sigmoidf_(float x) { return rcp_fast(1.f + ex2(-1.4426950408889634f * x)); }
__device__ __forceinline__ void top2(uint32_t k, uint32_t& k1, uint32_t& k2) {
    k1 = __reduce_max_sync(0xffffffffu, k);
    k2 = __reduce_max_sync(0xffffffffu, k == k1 ? 0 : k);
}

__device__ __forceinline__ void mod_fma(float (&a)[8], const uint4 w, float sc) {
    a[0] += sc * bf_lo(w.x); a[1] += sc * bf_hi(w.x); a[2] += sc * bf_lo(w.y); a[3] += sc * bf_hi(w.y);
    a[4] += sc * bf_lo(w.z); a[5] += sc * bf_hi(w.z); a[6] += sc * bf_lo(w.w); a[7] += sc * bf_hi(w.w);
}
__device__ __forceinline__ float mod_reduce(float (&a)[8], int lane) {
#pragma unroll
    for (int h = 4; h > 0; h >>= 1) {
        const bool up = lane & (8 / h);
#pragma unroll
        for (int i = 0; i < h; i++)
            a[i] = (up ? a[i + h] : a[i]) + __shfl_xor_sync(0xffffffffu, up ? a[i] : a[i + h], 8 / h);
    }
    return a[0] + __shfl_xor_sync(0xffffffffu, a[0], 16);
}

__device__ __forceinline__ float ln_stats(float sum, float sq, uint32_t& mean2) {
    const float mean = sum * (1.f / D_);
    const float var = fmaxf(fmaf(-mean, mean, sq * (1.f / D_)), 0.f);
    float sd;
    asm("sqrt.approx.ftz.f32 %0, %1;" : "=f"(sd) : "f"(rbf(rbf(var) + 1e-5f)));
    mean2 = pack_bf16(mean, mean);
    return rcp_fast(rbf(sd));
}
__device__ __forceinline__ uint32_t ln_pair(uint32_t x, uint32_t mean2, float rsd) {
    const uint32_t d = bsub2(x, mean2);
    return pack_bf16(bf_lo(d) * rsd, bf_hi(d) * rsd);
}
__device__ __forceinline__ void rows_load(uint32_t (&x)[20], uint32_t xs, int cw) {
#pragma unroll
    for (int ch = 0; ch < 5; ch++) {
        const uint4 v = ldsm4(ch < 4 ? xs + ch * 256 : xs + 1024 - cw * 16);
        x[4 * ch] = v.x; x[4 * ch + 1] = v.y; x[4 * ch + 2] = v.z; x[4 * ch + 3] = v.w;
    }
}
__device__ __forceinline__ void stats_add(float (&st)[12], uint32_t a, uint32_t b, uint32_t w) {
    mma1688(st, a, b, w);
    mma1688(st + 4, a, b, a);
    mma1688(st + 8, a, b, b);
}
__device__ __forceinline__ float rows_stats(const float (&st)[12], float4* rec, int cw, int lane, uint32_t& mean2, float& dot) {
    const int g8 = lane >> 2;
    if ((g8 >> 1) == (lane & 3)) {
        rec[cw * 16 + g8] = make_float4(st[0], (g8 & 1) ? st[5] : st[4], st[1], 0.f);
        rec[cw * 16 + 8 + g8] = make_float4(st[2], (g8 & 1) ? st[11] : st[10], st[3], 0.f);
    }
    bar_sync(3, 256);
    const float4* r = rec + (lane >> 4) * 64 + (lane & 15);
    const float4 s0 = r[0], s1 = r[16], s2 = r[32], s3 = r[48];
    const float sum = (s0.x + s1.x) + (s2.x + s3.x), sq = (s0.y + s1.y) + (s2.y + s3.y);
    dot = (s0.z + s1.z) + (s2.z + s3.z);
    dot += __shfl_xor_sync(0xffffffffu, dot, 16);
    return ln_stats(sum + __shfl_xor_sync(0xffffffffu, sum, 16), sq + __shfl_xor_sync(0xffffffffu, sq, 16), mean2);
}
__device__ __forceinline__ void rows_normalise(uint32_t* y, const uint32_t* x, uint32_t mean2, float rsd, int lane) {
    const int g8 = lane >> 2;
    const uint32_t ma2 = __shfl_sync(0xffffffffu, mean2, g8), mb2 = __shfl_sync(0xffffffffu, mean2, g8 + 8);
    const float ra = __shfl_sync(0xffffffffu, rsd, g8), rb = __shfl_sync(0xffffffffu, rsd, g8 + 8);
#pragma unroll
    for (int k = 0; k < 9; k++) { y[2 * k] = ln_pair(x[2 * k], ma2, ra); y[2 * k + 1] = ln_pair(x[2 * k + 1], mb2, rb); }
}
__device__ __forceinline__ uint32_t pair_of(const uint2* mp, int k, int cw) {
    return (k < 8 ? mp[(k >> 1) * 64 + (k & 1) * 4] : (mp - cw * 4)[256]).x;
}

__device__ __forceinline__ uint4 h_frag(const uint4* hf, int ks, int lane) {
    if (ks < 32) return ld_relaxed2(hf + ks * 32);
    const uint2* p = reinterpret_cast<const uint2*>(padd(hf, 256 - lane * 8) + ks * 32 - 16);
    const uint2 a = ld_relaxed64(p), b = ld_relaxed64(p + 32);
    return make_uint4(a.x, a.y, b.x, b.y);
}

__device__ __noinline__ void attn_fallback(uint32_t bad, uint32_t tag, uint8_t* frag, uint8_t* keep, const bf16* wq, const bf16* kc, const bf16* vc) {
  const Scratch* gs = &g_s;
  const int lane = threadIdx.x & 31, g8 = lane >> 2, qd = lane & 3;
  const int j = (blockIdx.x >> 1) & 7, qb = (blockIdx.x >> 4) * 2 + (blockIdx.x & 1);
  const uint4* hf = g_h + (size_t)(qb * 8 + (threadIdx.x >> 5) - 4) * (36 * 32) + lane;
#pragma unroll 1
  for (int t = 0; t < 4; t++) {
    if (!((bad >> t) & 1)) continue;
    const bf16 *wqp = wq + (4 * j + t) * DH, *kp = kc + (size_t)(2 * j + (t >> 1)) * S_ * DH, *vp = vc + (size_t)(2 * j + (t >> 1)) * S_ * DH;
    uint32_t q[32];
    float o[64];
#pragma unroll
    for (int i = 0; i < 64; i++) o[i] = 0.f;
#pragma unroll 1
    for (int ks = 0; ks < 36; ks++) {
        const uint4 a = h_frag(hf, ks, lane);
        const unsigned short* wr = reinterpret_cast<const unsigned short*>(wqp + (size_t)(ks * 16 + 2 * qd) * QD + g8);
#pragma unroll
        for (int dt = 0; dt < 16; dt++) {
            const uint32_t b0 = __ldg(wr + dt * 8) | ((uint32_t)__ldg(wr + dt * 8 + QD) << 16);
            const uint32_t b1 = __ldg(wr + dt * 8 + 8 * QD) | ((uint32_t)__ldg(wr + dt * 8 + 9 * QD) << 16);
            mma16816(o + 4 * dt, a.x, a.y, a.z, a.w, b0, b1);
        }
    }
#pragma unroll
    for (int i = 0; i < 32; i++) q[i] = pack_bf16(o[2 * i], o[2 * i + 1]);
#pragma unroll
    for (int i = 0; i < 64; i++) o[i] = 0.f;
    float m0 = -INFINITY, m1 = -INFINITY, l0 = 0.f, l1 = 0.f;
#pragma unroll 1
    for (int key = 0; key < S_; key += 16) {
        float sc[8];
#pragma unroll
        for (int i = 0; i < 8; i++) sc[i] = 0.f;
#pragma unroll
        for (int nt = 0; nt < 2; nt++) {
            const uint32_t* kr = reinterpret_cast<const uint32_t*>(kp + (size_t)(key + nt * 8 + g8) * DH) + qd;
#pragma unroll
            for (int ks = 0; ks < 8; ks++)
                mma16816(sc + 4 * nt, q[4 * ks], q[4 * ks + 1], q[4 * ks + 2], q[4 * ks + 3], __ldg(kr + ks * 8), __ldg(kr + ks * 8 + 4));
        }
        const float n0 = quad_max(fmaxf(fmaxf(m0, fmaxf(sc[0], sc[1])), fmaxf(sc[4], sc[5])));
        const float n1 = quad_max(fmaxf(fmaxf(m1, fmaxf(sc[2], sc[3])), fmaxf(sc[6], sc[7])));
        const float f0 = ex2((m0 - n0) * CS), f1 = ex2((m1 - n1) * CS);
        m0 = n0; m1 = n1;
#pragma unroll
        for (int i = 0; i < 8; i++) sc[i] = ex2((sc[i] - ((i & 2) ? n1 : n0)) * CS);
        l0 = l0 * f0 + (sc[0] + sc[1]) + (sc[4] + sc[5]);
        l1 = l1 * f1 + (sc[2] + sc[3]) + (sc[6] + sc[7]);
        const uint32_t e0 = pack_bf16(sc[0], sc[1]), e1 = pack_bf16(sc[2], sc[3]), e2 = pack_bf16(sc[4], sc[5]), e3 = pack_bf16(sc[6], sc[7]);
        const unsigned short* vr = reinterpret_cast<const unsigned short*>(vp + (size_t)(key + 2 * qd) * DH + g8);
#pragma unroll
        for (int dt = 0; dt < 16; dt++) {
            o[4 * dt] *= f0; o[4 * dt + 1] *= f0; o[4 * dt + 2] *= f1; o[4 * dt + 3] *= f1;
            const uint32_t b0 = __ldg(vr + dt * 8) | ((uint32_t)__ldg(vr + dt * 8 + DH) << 16);
            const uint32_t b1 = __ldg(vr + dt * 8 + 8 * DH) | ((uint32_t)__ldg(vr + dt * 8 + 9 * DH) << 16);
            mma16816(o + 4 * dt, e0, e1, e2, e3, b0, b1);
        }
    }
    const float i0 = 1.f / quad_sum(l0), i1 = 1.f / quad_sum(l1);
#pragma unroll
    for (int i = 0; i < 16; i++) {
        q[2 * i] = pack_bf16(o[4 * i] * i0, o[4 * i + 1] * i0);
        q[2 * i + 1] = pack_bf16(o[4 * i + 2] * i1, o[4 * i + 3] * i1);
    }
    frag_store(t < 3 ? frag + t * 4096 : keep, q);
  }
}

__device__ __forceinline__ void spare_q3(Scratch* gs, uint32_t sb, uint32_t bar_full, uint32_t bar_empty, int lane, int cw) {
    const uint32_t tag = load_tag(gs);
    uint32_t rel_base, e = 3;
    asm("mapa.shared::cluster.u32 %0, %1, %2;" : "=r"(rel_base) : "r"(bar_empty), "r"(lane & 1));
#pragma unroll 1
    for (int qb = blockIdx.x - NCTA; qb < 16; qb += 4) {
        uint32_t h[144];
        float o[64];
        flag_wait(&g_flag_h[(qb * 8 + cw) * 32], tag);
        const uint4* hf = g_h + (size_t)(qb * 8 + cw) * (36 * 32) + lane;
#pragma unroll
        for (int ks = 0; ks < 36; ks++) {
            const uint4 v = h_frag(hf, ks, lane);
            h[4 * ks] = v.x; h[4 * ks + 1] = v.y; h[4 * ks + 2] = v.z; h[4 * ks + 3] = v.w;
        }
#pragma unroll
        for (int i = 0; i < 64; i++) o[i] = 0.f;
#pragma unroll 1
        for (int v = 0; v < 4; v++) {
            fence_regs(o);
#pragma unroll
            for (int t = 0; t < 5; t++) {
                mbar_wait(bar_full + 8 * (e & 3), (e >> 2) & 1);
                const uint64_t dv = mkdesc(sb + (e & 3) * SLOT, UNIT, 1024);
                WG_FENCE();
#pragma unroll
                for (int ks = 0; ks < (t < 4 ? 8 : 4); ks++)
                    mma_rs128<1>(o, h[32 * t + 4 * ks], h[32 * t + 4 * ks + 1], h[32 * t + 4 * ks + 2], h[32 * t + 4 * ks + 3], dv + ks * 128, ks | t);
                WG_COMMIT();
                if (t > 0) { WG_WAIT(1); if (lane < 2) mbar_arrive_cluster(rel_base + 8 * ((e - 1) & 3)); }
                e++;
            }
            WG_WAIT(0);
            fence_regs(o);
            if (lane < 2) mbar_arrive_cluster(rel_base + 8 * ((e - 1) & 3));
            uint4* dst = &g_q3[((qb * 8 + 2 * v) * 8 + cw) * 128 + lane];
#pragma unroll
            for (int i = 0; i < 8; i++)
                __stcg(dst + (i >> 2) * 1024 + (i & 3) * 32, make_uint4(pack_bf16(o[8 * i], o[8 * i + 1]), pack_bf16(o[8 * i + 2], o[8 * i + 3]),
                                                                        pack_bf16(o[8 * i + 4], o[8 * i + 5]), pack_bf16(o[8 * i + 6], o[8 * i + 7])));
        }
        bar_sync(3, 256);
        if (cw == 0 && lane == 0) flag_release(&g_flag_q3[qb * 32], tag);
        __syncwarp();
    }
}

template <bool SPARE>
__global__ void __cluster_dims__(2, 1, 1) __launch_bounds__(384, 1)
fused_kernel(const Args args, const __grid_constant__ CUtensorMap tm_wq,
             const __grid_constant__ CUtensorMap tm_k, const __grid_constant__ CUtensorMap tm_v,
             const __grid_constant__ CUtensorMap tm_wo, const __grid_constant__ CUtensorMap tm_p,
             const __grid_constant__ CUtensorMap tm_x, const __grid_constant__ CUtensorMap tm_d,
             const __grid_constant__ CUtensorMap tm_g, const __grid_constant__ CUtensorMap tm_u) {
    extern __shared__ __align__(1024) uint8_t smem_raw[];
    const uint32_t sb = smem_u32(smem_raw);
    Scratch* const gs = args.gs;
    const uint32_t bar_full = sb + SM_BAR;
    const uint32_t bar_g = bar_full + 8 * 4;
    const uint32_t bar_mod = bar_g + 8;
    const uint32_t bar_go = bar_mod + 8;
    const uint32_t bar_x = bar_go + 40;
    const uint32_t bar_empty = bar_x + 8;
    const uint32_t bar_pub = bar_empty + 8 * 4;
    const uint32_t bar_qfree = bar_pub + 32;
    const uint32_t bar_out = bar_qfree + 24;
    const uint32_t bar_q3 = bar_out + 8;
    const uint32_t bar_pre = bar_q3 + 16;
    const uint32_t bar_w0 = bar_q3 + 8;
    constexpr int E0 = SPARE ? 2 : 0;

    const int c = blockIdx.x & 1;
    const int j = (blockIdx.x >> 1) & 7;
    const int qb = (blockIdx.x >> 4) * 2 + c;
    const int rg = qb * 8 + j;
    const int warp = __shfl_sync(0xffffffffu, threadIdx.x >> 5, 0);

    if (SPARE && blockIdx.x >= NCTA && warp >= 4) {
        asm volatile("barrier.cluster.arrive.relaxed.aligned;" ::: "memory");
        asm volatile("setmaxnreg.inc.sync.aligned.u32 240;");
        asm volatile("barrier.cluster.wait.aligned;" ::: "memory");
        spare_q3(gs, sb, bar_full, bar_empty, threadIdx.x & 31, warp - 4);
        asm volatile("barrier.cluster.arrive.relaxed.aligned;\nbarrier.cluster.wait.aligned;" ::: "memory");
    } else if (warp < 4) {
        asm volatile("setmaxnreg.dec.sync.aligned.u32 24;");
        int lane;
        asm volatile("mov.u32 %0, %%laneid;" : "=r"(lane));
        if (warp == 2 && elect()) {
            if (TMPF) asm volatile("prefetch.tensormap [%0];" ::"l"(&tm_x) : "memory");
#pragma unroll
            for (int i = 0; i < 27; i++) mbar_init(bar_full + 8 * i, i < 12 || i >= 23 ? 1 : i < 16 ? 16 : 8);
#pragma unroll
            for (int i = 0; i <= E0; i++) {
                mbar_arrive(bar_full + 8 * i);
                asm volatile("mbarrier.arrive.shared::cta.b64 _, [%0], 16;" ::"r"(bar_empty + 8 * i) : "memory");
            }
            asm volatile("fence.mbarrier_init.release.cluster;" ::: "memory");
        }
        __syncwarp();
        asm volatile("barrier.cluster.arrive.relaxed.aligned;" ::: "memory");
        if (warp == 2 && !(SPARE && blockIdx.x >= NCTA)) {
            if (XDELAY) __nanosleep(XDELAY);
            if (elect()) {
                mbar_expect_tx(bar_x, 16 * XP);
                tma2d(sb + SM_Q, &tm_x, 0, rg * 16, bar_x);
            }
            __syncwarp();
        }
        asm volatile("barrier.cluster.wait.aligned;" ::: "memory");
        const uint32_t tag = load_tag(gs);
        if (SPARE && blockIdx.x >= NCTA) {
            if (warp == 1) {
#pragma unroll 1
                for (int e = 3; e < 83; e++) {
                    const int v = (e - 3) / 5;
                    mbar_wait_sleep(bar_empty + 8 * (e & 3), ~(e >> 2) & 1);
                    if (elect()) {
                        mbar_expect_tx(bar_full + 8 * (e & 3), SLOT);
                        tma2d_mc(sb + (e & 3) * SLOT + c * UNIT, &tm_wq, (8 * (v & 3) + 4 * c + 3) * DH + 64, (e - 3 - v * 5) * 128,
                                 bar_full + 8 * (e & 3), EVICT_NORMAL);
                    }
                }
            }
            __syncwarp();
            asm volatile("barrier.cluster.arrive.relaxed.aligned;\nbarrier.cluster.wait.aligned;" ::: "memory");
            return;
        }
        if (warp == 3) {
#pragma unroll 1
            for (int e = 4; e < 20; e++) {
                __nanosleep(e == 4 ? PFD0 : PFD1);
                const int hd = (e * 52) >> 8, row = (e - hd * 5) * 128 + qb * 8 + (lane >> 1);
                if (lane < 16 && row < D_)
                    asm volatile("prefetch.global.L2 [%0];" ::"l"(padd(args.wq, (row * QD + (4 * j + ((0x1320 >> (4 * hd)) & 3)) * DH + (lane & 1) * 64) * 2)) : "memory");
            }
            __syncwarp();
            mbar_wait_sleep(bar_go, 0);
#pragma unroll 1
            for (int unit = 72 + blockIdx.x; unit < 216; unit += NCTA) {
                float a[8];
#pragma unroll
                for (int i = 0; i < 8; i++) a[i] = 0.f;
#pragma unroll 1
                for (int k = lane >> 1; k < D_; k += 16) {
                    const float cv = __bfloat162float(*padd(args.cvec, k * 2));
                    mod_fma(a, __ldg(reinterpret_cast<const uint4*>(padd(args.w_mod, (k * (6 * D_) + unit * 16 + (lane & 1) * 8) * 2))), rbf(cv * sigmoidf_(cv)));
                }
                const float v = mod_reduce(a, lane), v1 = __shfl_down_sync(0xffffffffu, v, 8);
                if (lane < 8) *padd(gs->mod2, ((unit - 72) * 8 + (lane & 1) * 4 + (lane & 2) + (lane >> 2)) * 4) = pack_bf16(v, v1);
            }
            __syncwarp();
            if (lane == 0) flag_release(padd(g_flag_mod, blockIdx.x * 4), tag);
#pragma unroll 1
            for (int k = 0; k < 36 * HSENT; k++) {
                __nanosleep(200);
                __stcg(padd(gs->h[0], (~tag & 1) * (NCTA * 36 * 512) + ((rg * 36 + k) * 32 + lane) * 16), make_uint4(0, 0, 0, 0));
            }
            __syncwarp();
            mbar_wait_sleep(bar_qfree + 16, 0);
            __nanosleep(2000);
            {
                uint4 v;
                uint32_t it = 0;
#pragma unroll 1
                do {
                    v = ld_relaxed(reinterpret_cast<const uint4*>(padd(g_flag_mod, lane * 16)));
                } while (((v.x ^ tag) | (v.y ^ tag) | (v.z ^ tag) | (v.w ^ tag)) && ++it < SPIN / 16);
                asm volatile("fence.acquire.gpu;" ::: "memory");
            }
            __syncwarp();
            {
                float w1 = 0.f, w2 = 0.f;
#pragma unroll 1
                for (int k = lane; k < D_ / 2; k += 32) {
                    const uint32_t* mp = padd(gs->mod2, k * 4);
                    const uint32_t sv = __ldcg(mp + D_ / 2), c1 = badd2(__ldcg(mp + D_), 0x3f803f80u);
                    const uint32_t wr = *reinterpret_cast<const uint32_t*>(padd(args.w_r, k * 4)), wp = bmul2(c1, wr);
                    reinterpret_cast<uint4*>(smem_raw + SM_T)[k] = make_uint4(__ldcg(mp), c1, sv, __ldcg(mp + 3 * D_ / 2));
                    reinterpret_cast<uint32_t*>(smem_raw + SM_TW)[k] = wp;
                    w1 += bf_lo(wp) + bf_hi(wp);
                    w2 += bf_lo(sv) * bf_lo(wr) + bf_hi(sv) * bf_hi(wr);
                }
#pragma unroll 1
                for (int i = 1; i < 32; i <<= 1) { w1 += __shfl_xor_sync(0xffffffffu, w1, i); w2 += __shfl_xor_sync(0xffffffffu, w2, i); }
                *reinterpret_cast<float2*>(smem_raw + SM_TS) = make_float2(w1, w2);
            }
#pragma unroll
            for (int i = 0; i < 4; i++) reinterpret_cast<uint4*>(smem_raw + SM_RED)[lane + 32 * i] = make_uint4(~0u, ~0u, ~0u, ~0u);
            asm volatile("fence.proxy.async.shared::cta;" ::: "memory");
            __syncwarp();
            if (elect()) {
                uint8_t* mb = g_frag + (size_t)rg * 8 * WREG + 3 * 4096;
#pragma unroll 1
                for (int k = 0; k < 8; k++, mb += WREG) {
#pragma unroll
                    for (int i = 0; i < 3; i++)
                        asm volatile("cp.async.bulk.global.shared::cta.bulk_group [%0], [%1], 2048;" ::"l"(mb + i * 2048), "r"(sb + SM_RED) : "memory");
                    __nanosleep(500);
                }
                asm volatile("cp.async.bulk.commit_group;\ncp.async.bulk.wait_group 0;\nfence.proxy.async.global;" ::: "memory");
            }
            __syncwarp();
            if (lane == 0) mbar_arrive(bar_mod);
            __syncwarp();
            mbar_wait_sleep(bar_go + 8, 0);
            if (lane < 3) asm volatile("prefetch.tensormap [%0];" ::"l"(lane == 0 ? &tm_x : lane == 1 ? &tm_p : &tm_d) : "memory");
            __syncwarp();
            mbar_wait_sleep(bar_go + 8 * 2, 0);
            uint32_t acc = 0;
#pragma unroll 1
            for (int k = lane; k < 16 * 9; k += 32) acc |= touch(padd(args.x, (rg * 16 * D_ + k * 64) * 2));
            if (acc == 0) reinterpret_cast<volatile uint32_t*>(smem_raw + SM_BAR)[127] = acc;
        } else if (warp == 0) {
#pragma unroll 1
            for (int i = 0; i < 48; i++) {
                if (i == 0 || i == 17 || i == 34) mbar_wait_sleep(bar_qfree + (i >> 4) * 8, 0);
                if (SPARE && i == 17) {
                    flag_wait(&g_flag_q3[qb * 32], tag);
                    if (elect()) {
                        asm volatile("fence.proxy.async.global;" ::: "memory");
                        mbar_expect_tx(bar_q3, UNIT);
#pragma unroll 1
                        for (int k = 0; k < 8; k++) bulk_load(sb + SM_Q + 2 * SLOT + k * 4096 + 2048, &g_q3[(rg * 8 + k) * 128], 2048, bar_q3);
                    }
                }
                __nanosleep(700);
                if (elect()) {
                    asm volatile("mbarrier.expect_tx.shared::cta.b64 [%0], %1;" ::"r"(bar_g), "n"(1920) : "memory");
                    tma2d(sb + SM_Q + i * 1920, i < 24 ? &tm_g : &tm_u, (blockIdx.x * 36) & ~7, (i < 24 ? i : i - 24) * 24, bar_g);
                }
            }
            if (elect()) mbar_arrive(bar_g);
#pragma unroll 1
            for (int i = 0; i < 18; i++) {
                __nanosleep(400);
                if (elect()) l2_prefetch(args.w_down + (size_t)(blockIdx.x * 36 + i * 2) * D_, 4 * D_);
            }
            __syncwarp();
            mbar_wait_sleep(bar_go + 8 * 4, 0);
            uint4* rp = padd(g_rows, (rg * 2 * RSLOT + lane) * 16);
#pragma unroll
            for (int k = 0; k < 9; k++) rp[k * 32] = make_uint4(~0u, ~0u, ~0u, ~0u);
            if (blockIdx.x < 72) {
                uint4* yp = reinterpret_cast<uint4*>(padd(g_ypart, blockIdx.x * NCTA * 64 + lane * 16));
#pragma unroll
                for (int k = 0; k < 16; k++) yp[k * 32] = make_uint4(~0u, ~0u, ~0u, ~0u);
            }
            asm volatile("fence.acq_rel.gpu;" ::: "memory");
            __syncwarp();
            if (lane == 0) mbar_arrive(bar_pre);
        } else if (warp == 1) {
            __nanosleep(QDELAY);
            uint32_t go = bar_go;
            uint64_t marks = 24 | 151 << 8 | 154 << 16 | 159ull << 24 | 165ull << 32;
#pragma unroll 1
            for (int e = E0; e < 168; e++) {
                const CUtensorMap* tm;
                int c0, c1;
                uint64_t pol = EVICT_FIRST;
                if (e == 158 || e == 163) continue;
                if (e < 21 && e != 19) {
                    const int i = SPARE && e < 12 ? e - 2 : e - (e == 20), hd = (i * 52) >> 8;
                    tm = &tm_wq; c0 = (4 * j + ((0x1320 >> (4 * hd)) & 3)) * DH + c * 64; c1 = (i - hd * 5) * 128 - 64;
                    if (SPARE && e >= 12 && e < 15) { c0 = (4 * j + 3) * DH; c1 = (2 * (e - 12) + c) * 128; }
                } else if (e < 148) {
                    const int i = max(e - 20, 0);
                    const bool isk = i == 0 || ((i & 1) && i < 127);
                    const int n = isk ? (i + 1) >> 1 : (i - 1) >> 1;
                    tm = isk ? &tm_k : &tm_v; c0 = c * 64; c1 = (2 * j + (n >> 5)) * S_ + (n & 15) * 128;
                    if (!(i & 32)) pol = EVICT_NORMAL;
                } else {
                    int i = e - 148 - (e > 158) - (e > 163);
                    if (i == 1 || i == 2) i ^= 3;
                    tm = &tm_wo; c0 = (i >> 1) * 64; c1 = (4 * j + ((i & 1) ? 1 + c : 3 * c)) * DH;
                }
                const uint32_t fb = e == E0 ? bar_w0 : bar_full + 8 * (e & 3), d = sb + (e == E0 ? 6 : e & 3) * SLOT;
                if (e >= 24 && e < 152) mbar_wait_sleep(bar_empty + 8 * (e & 3), ~(e >> 2) & 1);
                else if (e != E0) mbar_wait(bar_empty + 8 * (e & 3), ~(e >> 2) & 1);
                if (elect()) {
                    mbar_expect_tx(fb, SLOT);
                    tma2d_mc(d + c * UNIT, tm, c0, c1, fb, pol);
                    const int i = e - PF_KV;
                    if (i >= 0 && i < 128 && !(i & 32))
                        l2_prefetch(((i & 1) ? args.vc : args.kc) + (size_t)((2 * j + (i >> 6)) * S_ + (i & 30) * 64) * DH + qb * 1024, 2048);
                    if (e >= PF_WO && e < PF_WO + 18) l2_prefetch(args.wo + (size_t)blockIdx.x * (QD * D_ / NCTA) + (e - PF_WO) * 1024, 2048);
                    if (e == (marks & 255)) mbar_arrive(go);
                }
                if (e == (marks & 255)) { go += 8; marks >>= 8; }
            }
            asm volatile("fence.proxy.async.global;" ::: "memory");
            mbar_wait(bar_empty, 1);
            if (elect()) {
                mbar_expect_tx(bar_full, 16 * XP);
                tma2d(sb, &tm_x, 0, rg * 16, bar_full);
            }
            mbar_wait(bar_empty + 16, 1);
            if (C3D) __nanosleep(C3D);
            if (elect()) {
                mbar_expect_tx(bar_full + 16, SLOT);
                tma3d(sb + 2 * SLOT, &tm_p, 0, j * 20 + 12, qb * 8, bar_full + 16);
                tma3d(sb + 2 * SLOT + UNIT, &tm_p, 0, j * 20 + 14, qb * 8, bar_full + 16);
            }
            mbar_wait(bar_empty + 24, 1);
            if (C4D) __nanosleep(C4D);
            if (elect()) {
                mbar_expect_tx(bar_full + 24, UNIT);
                tma3d(sb + 3 * SLOT, &tm_p, 0, j * 20 + 16, qb * 8, bar_full + 24);
            }
            mbar_wait(bar_empty + 8, 0);
            mbar_wait(bar_empty + 16, 0);
            if (DD) __nanosleep(DD);
            if (elect()) {
#pragma unroll
                for (int i = 1; i < 3; i++) {
                    mbar_expect_tx(bar_full + 8 * i, 18 * XP);
                    tma2d(sb + i * SLOT, &tm_d, 0, blockIdx.x * 36 + (i - 1) * 18, bar_full + 8 * i);
                }
            }
        } else {
            if (lane < 3) asm volatile("prefetch.tensormap [%0];" ::"l"(lane == 0 ? &tm_k : lane == 1 ? &tm_v : &tm_wo) : "memory");
            if (SPARE && HSENT) {
                mbar_wait_sleep(bar_pub, 0);
                if (lane == 0) flag_release(padd(g_flag_h, rg * 128), tag);
                __syncwarp();
            }
            bar_sync(1, 192);
#pragma unroll 1
            for (uint32_t e = 20; e < 148; e++) {
                mbar_wait_sleep(bar_full + 8 * (e & 3), (e >> 2) & 1);
                if (e & 1) bar_sync(1, 192);
                if (!(e & 1) || e == 147) bar_sync(4, 160);
            }
            mbar_wait_sleep(bar_go + 8, 0);
            mbar_wait(bar_mod, 0);
#pragma unroll 1
            for (int i = 1; i < 4; i++) {
                mbar_wait(bar_pub + 8 * i, 0);
                unsigned int* flags = padd(g_flag_part, (qb * 32 + i * 8 - 8) * 4);
                if (elect()) { flag_release(padd(flags, j * 4), tag); DBG_PG(93); }
                __syncwarp();
                const uint32_t slot = i < 3 ? i + 1 : 1;
                flag_wait(padd(flags, (lane & 7) * 4), tag);
                asm volatile("fence.proxy.async.global;" ::: "memory");
                if (lane == 0 && i == 3) DBG_PG(101);
                mbar_wait(bar_go + 8 + 8 * i, 0);
                mbar_wait(bar_empty + 8 * slot, i != 1);
                if (elect()) {
                    mbar_expect_tx(bar_full + 8 * slot, SLOT);
                    tma3d(sb + slot * SLOT, &tm_p, 0, j * 20 + (i - 1) * 4, qb * 8, bar_full + 8 * slot);
                    tma3d(sb + slot * SLOT + UNIT, &tm_p, 0, j * 20 + (i - 1) * 4 + 2, qb * 8, bar_full + 8 * slot);
                }
            }
        }
        __syncwarp();
        mbar_wait_sleep(bar_out, 0);
        if (elect()) {
            asm volatile("fence.proxy.async.shared::cta;" ::: "memory");
            const int2 sel = reinterpret_cast<const int2*>(smem_raw + SM_RED)[8];
#pragma unroll 1
            for (int i = warp; i < 16; i += 4) {
                const int row = rg * 16 + i;
                if (row != sel.x && row != sel.y)
                    asm volatile("cp.async.bulk.global.shared::cta.bulk_group [%0], [%1], %2;"
                                 ::"l"(args.out + (size_t)row * D_), "r"(sb + i * XP), "n"(D_ * 2) : "memory");
            }
            asm volatile("cp.async.bulk.commit_group;\ncp.async.bulk.wait_group 0;" ::: "memory");
        }
    } else {
        uint32_t cv[5] = {0, 0, 0, 0, 0}, tag0 = 0;
        if (blockIdx.x < 72) {
            uint32_t ws;
            int tid;
            asm volatile("mov.u32 %0, smem_raw;\nmov.u32 %1, %%tid.x;" : "=r"(ws), "=r"(tid));
            tid -= 128;
            ws += SM_Q + SLOT + tid * 16;
            const bf16* wrow = args.w_mod + (size_t)(tid >> 1) * (6 * D_) + (tid & 1) * 8 + blockIdx.x * 16;
#pragma unroll
            for (int i = 0; i < 5; i++)
                if (i < 4 || tid < 128) {
                    asm volatile("cp.async.cg.shared.global [%0], [%1], 16;" ::"r"(ws + i * 4096), "l"(wrow + (size_t)i * 128 * (6 * D_)) : "memory");
                    cv[i] = reinterpret_cast<const unsigned short*>(args.cvec)[(tid >> 1) + i * 128];
                }
            tag0 = load_tag(gs) - 1;
        }
        asm volatile("barrier.cluster.arrive.relaxed.aligned;" ::: "memory");
        asm volatile("setmaxnreg.inc.sync.aligned.u32 240;");
        const int lane = threadIdx.x & 31;
        const int cw = warp - 4;
        const int w = cw >> 2;
        const int tid = threadIdx.x - 128;
        float* red = reinterpret_cast<float*>(smem_raw + SM_RED);
        DBG_INIT();
        DBG_G(120);
        DBG_T(100);

        uint32_t tag;
        {

            if (blockIdx.x < 72) {
                const uint32_t ws = sb + SM_Q + SLOT + tid * 16;
                float sc[5], a[8];
#pragma unroll
                for (int i = 0; i < 5; i++) sc[i] = __uint_as_float(cv[i] << 16);
#pragma unroll
                for (int i = 0; i < 5; i++) sc[i] = rbf(sc[i] * sigmoidf_(sc[i]));
#pragma unroll
                for (int i = 0; i < 8; i++) a[i] = 0.f;
                anchor(bar_full + 504, sc[0] + sc[1] + sc[2] + sc[3] + sc[4] + 2.f);
                asm volatile("cp.async.wait_all;" ::: "memory");
#pragma unroll
                for (int i = 0; i < 5; i++) mod_fma(a, lds128(ws + (i < 4 || tid < 128 ? i * 4096 : 0)), sc[i]);
                const float v = mod_reduce(a, lane);
                if (lane < 16) red[cw * 16 + lane] = v;

                bar_sync(3, 256);
                if (tid < 8 * MREP) {
                    float v0 = 0.f, v1 = 0.f;
#pragma unroll
                    for (int i = 0; i < 8; i++) { v0 += red[i * 16 + (tid & 7)]; v1 += red[i * 16 + 8 + (tid & 7)]; }
                    st_relaxed64(&gs->mod1[(tid >> 3) * D_ + blockIdx.x * 8 + (tid & 1) * 4 + (tid & 2) + ((tid >> 2) & 1)], pack_bf16(v0, v1), tag0 + 1);
                }
            }
            DBG_G(106);
            asm volatile("barrier.cluster.wait.aligned;" ::: "memory");
            mbar_wait(bar_x, 0);
            tag = load_tag(gs);
            uint32_t x[20];
            float st[12];
            rows_load(x, sb + SM_Q + (lane & 15) * XP + (lane >> 4) * 16 + cw * 32, cw);
#pragma unroll
            for (int i = 0; i < 12; i++) st[i] = 0.f;
#pragma unroll
            for (int k = 0; k < 9; k++) stats_add(st, x[2 * k], x[2 * k + 1], 0x3f803f80u);
            uint32_t mean2;
            float dot;
            const float rsd = rows_stats(st, reinterpret_cast<float4*>(red + 128), cw, lane, mean2, dot);
            rows_normalise(x, x, mean2, rsd, lane);
            fence_regs(x);
            uint4* smod = reinterpret_cast<uint4*>(smem_raw + SM_Q + M_MOD);
            if (tid < D_ / 4) {
                const uint4* mp = reinterpret_cast<const uint4*>(gs->mod1 + ((blockIdx.x >> 1) & (MREP - 1)) * D_) + tid;
                poll2x2(mp, mp + D_ / 4, tag, smod[tid], smod[D_ / 4 + tid]);
            }
            bar_sync(3, 256);
            DBG_G(107);
            const uint2* mp = reinterpret_cast<const uint2*>(smod) + cw * 8 + (lane & 3);
#pragma unroll
            for (int k = 0; k < 9; k++) {
                const uint32_t c1 = badd2(pair_of(mp + D_ / 2, k, cw), 0x3f803f80u), sa = pair_of(mp, k, cw);
                x[2 * k] = badd2(bmul2(x[2 * k], c1), sa);
                if (x[2 * k] == 0) x[2 * k] = 0x8000u;
                x[2 * k + 1] = badd2(bmul2(x[2 * k + 1], c1), sa);
            }
            uint4* hdst = g_h + (size_t)(rg * 36 + cw) * 32 + lane;
#pragma unroll
            for (int ch = 0; ch < 4; ch++) st_relaxed(hdst + ch * 256, x[4 * ch], x[4 * ch + 1], x[4 * ch + 2], x[4 * ch + 3]);
            st_relaxed64(reinterpret_cast<uint2*>(g_h + (size_t)(rg * 36 + 32) * 32) + tid, x[16], x[17]);
            __syncwarp();
            if (SPARE && lane == 0) mbar_arrive(bar_pub);
            DBG_G(108);
        }

        uint32_t rel_base;
        asm("mapa.shared::cluster.u32 %0, %1, %2;" : "=r"(rel_base) : "r"(bar_empty), "r"(lane & 1));
        auto release = [&](uint32_t slot) { if (lane < 2) mbar_arrive_cluster(rel_base + 8 * slot); };
        uint32_t q[32], p[32];
        float s[64], o[64];

        uint4* qpark = reinterpret_cast<uint4*>(smem_raw + SM_Q - SLOT) + cw * 256 + lane;
        {
            uint32_t h[144];
            const uint4* hf = g_h + (size_t)(qb * 8 + cw) * (36 * 32) + lane;
            auto load_h = [&](auto lo, auto hi) {
#pragma unroll
                for (int ks = lo.value; ks < hi.value; ks++) {
                    const uint4 v = h_frag(hf, ks, lane);
                    h[4 * ks] = v.x; h[4 * ks + 1] = v.y; h[4 * ks + 2] = v.z; h[4 * ks + 3] = v.w;
                }
            };
            auto check_h = [&](auto lo, auto hi) {
                uint32_t it = 0;
#pragma unroll 1
                while (true) {
                    uint32_t mn = ~0u;
#pragma unroll
                    for (int ks = lo.value; ks < hi.value; ks++) mn = __vimin3_u32(mn, h[4 * ks], h[4 * ks + 2]);
                    if (!__any_sync(0xffffffffu, mn == 0) || ++it >= SPIN / 16) break;
                    load_h(lo, hi);
                }
            };
            if (!HSENT) flag_wait(&g_flag_h[(qb * 8 + cw) * 32], tag);
            if (HSENT) __nanosleep(HDELAY);
            load_h(IC<0>{}, IC<4>{});
            DBG_T(104); DBG_G(109);
#pragma unroll
            for (int i = 0; i < 64; i++) o[i] = 0.f;
            uint32_t e = E0;
#pragma unroll 1
            for (int hd = 1;; hd++) {
                fence_regs(o);
                auto group = [&](auto tc) {
                    constexpr int t = tc.value, k0 = t ? 8 * t - 4 : 0;
                    const bool first = t == 0 && hd == 1;
                    mbar_wait(first ? bar_w0 : bar_full + 8 * (e & 3), (e >> 2) & 1);
                    const uint32_t dv = desc_lo(t ? 0 : 8192, UNIT) + (first ? 6 : e & 3) * (SLOT / 16);
                    if (HSENT && hd == 1) check_h(IC<k0>{}, IC<8 * t + 4>{});
                    WG_FENCE();
#pragma unroll
                    for (int ks = k0; ks < 8 * t + 4; ks++)
                        mma_rs128<1>(o, h[4 * ks], h[4 * ks + 1], h[4 * ks + 2], h[4 * ks + 3], desc_of(dv + (ks - k0) * 128), ks);
                    WG_COMMIT();
                    if (hd == 1) { if (t == 0) {   } if (t == 1) {   } if (t == 2) {   } if (t == 3) {   } if (t == 4) {   } }
                    if (t < 4 && hd == 1) load_h(IC<8 * t + 4>{}, IC<t < 4 ? 8 * t + 12 : 0>{});
                    if (t > 0) { WG_WAIT(1); if (t > 1 || hd > 1) release((e - 1) & 3); }
                    e++;
                };
                group(IC<0>{}); group(IC<1>{}); group(IC<2>{}); group(IC<3>{});
                if (e == 19) break;
                group(IC<4>{});
                WG_WAIT(0);
                if (hd == 1) {     }
                fence_regs(o);
                release((e - 1) & 3);
#pragma unroll
                for (int i = 0; i < 8; i++)
                    qpark[hd * 2048 + i * 32] = make_uint4(pack_bf16(o[8 * i], o[8 * i + 1]), pack_bf16(o[8 * i + 2], o[8 * i + 3]),
                                                           pack_bf16(o[8 * i + 4], o[8 * i + 5]), pack_bf16(o[8 * i + 6], o[8 * i + 7]));
                if (SPARE && hd == 2) {
                    float (&u)[32] = reinterpret_cast<float (&)[32]>(o);
                    fence_regs(u);
#pragma unroll
                    for (int t = 0; t < 3; t++) {
                        mbar_wait(bar_full + 8 * t, 1);
                        WG_FENCE();
#pragma unroll
                        for (int ks = 0; ks < (t < 2 ? 16 : 4); ks++)
                            mma_rs64<1>(u, h[64 * t + 4 * ks], h[64 * t + 4 * ks + 1], h[64 * t + 4 * ks + 2], h[64 * t + 4 * ks + 3],
                                        desc_of(desc_lo(t * SLOT, UNIT) + ks * 128), ks | t);
                        WG_COMMIT();
                        if (t > 0) { WG_WAIT(1); release(t - 1); }
                    }
                    WG_WAIT(0);
                    fence_regs(u);
                    release(2);
                    e = 15;
#pragma unroll
                    for (int i = 0; i < 4; i++)
                        qpark[3 * 2048 + i * 32] = make_uint4(pack_bf16(u[8 * i], u[8 * i + 1]), pack_bf16(u[8 * i + 2], u[8 * i + 3]),
                                                              pack_bf16(u[8 * i + 4], u[8 * i + 5]), pack_bf16(u[8 * i + 6], u[8 * i + 7]));
                }
            }
#pragma unroll
            for (int i = 0; i < 8; i++) {
                const uint4 v = qpark[2048 + i * 32];
                q[4 * i] = v.x; q[4 * i + 1] = v.y; q[4 * i + 2] = v.z; q[4 * i + 3] = v.w;
            }
#pragma unroll
            for (int i = 0; i < 32; i++) p[i] = h[112 + i];
            mbar_wait(bar_full + 24, 0);
            WG_WAIT(0);
            fence_regs(o);
            release(2);
        }
        DBG_T(105);
        DBG_G(125);

        uint8_t* frag = reinterpret_cast<uint8_t*>(__shfl_sync(0xffffffffu, reinterpret_cast<unsigned long long>(g_frag + (size_t)(rg * 8 + cw) * WREG + lane * 16), lane));
        const uint4* qnext = reinterpret_cast<const uint4*>(__shfl_sync(0xffffffffu, reinterpret_cast<unsigned long long>(padd(smem_raw, SM_Q + tid * 16 + cw * 3584)), lane));
        uint8_t* odst = reinterpret_cast<uint8_t*>(const_cast<uint4*>(qnext));
        float m0 = 0.f, m1 = 0.f, l0 = 0.f, l1 = 0.f, t0 = 1.f, t1 = 1.f;
        uint32_t bad = 0;
        const int lw = cw & 3;
        const uint32_t relw = lw == RW && lane < 8, handw = lw == HW || cw == HW2;
        auto release4 = [&](uint32_t off) {
            asm volatile("{\n.reg .pred p;\nsetp.ne.b32 p, %1, 0;\n@p mbarrier.arrive.shared::cluster.b64 _, [%0];\n}" ::"r"(rel_base + off), "r"(relw) : "memory"); };
        auto handoff = [&]() {
            asm volatile("{\n.reg .pred p;\nsetp.ne.b32 p, %1, 0;\n@p bar.arrive %0, 192;\n}" ::"r"(2 - w), "r"(handw) : "memory"); };
        if (cw == 4 + HW) bar_arrive(1, 192);
        auto finish = [&](auto lo, auto hi, uint32_t bit, auto sink) {
#pragma unroll
            for (int i = lo.value; i < hi.value; i++) {
                const uint32_t v0 = pack_bf16(o[8 * i] * t0, o[8 * i + 1] * t0), v1 = pack_bf16(o[8 * i + 2] * t1, o[8 * i + 3] * t1);
                const uint32_t v2 = pack_bf16(o[8 * i + 4] * t0, o[8 * i + 5] * t0), v3 = pack_bf16(o[8 * i + 6] * t1, o[8 * i + 7] * t1);
                if (i == 0 && fabsf(o[0] * t0) >= 0x1p-31f) bad |= bit << 8;
                sink(i, v0, v1, v2, v3);
            }
        };
        auto row_sums = [&](uint32_t bit) {
            t0 = quad_sum(l0); t1 = quad_sum(l1);
            if (!(t0 >= LMIN && t0 < LMAX && t1 >= LMIN && t1 < LMAX)) bad |= bit;
            t0 = rcp_fast(t0); t1 = rcp_fast(t1);
            l0 = 0.f; l1 = 0.f;
        };
        auto issue_pv = [&](uint32_t dlo, int acc, auto lo, auto hi) {
            if (lo.value == 0) asm volatile("{\n.reg .pred p;\nsetp.eq.b32 p, %0, 0;\n@p bar.sync 4, 160;\n}" ::"r"(w) : "memory");
#pragma unroll
            for (int ks = lo.value; ks < hi.value; ks++)
                mma_rs128<1>(o, p[4 * ks], p[4 * ks + 1], p[4 * ks + 2], p[4 * ks + 3], desc_of(dlo + ks * 128), ks ? 1 : acc);
            WG_COMMIT();
        };
#pragma unroll
        for (int i = 0; i < 64; i++) s[i] = 0.f;
        uint32_t dv_lo = desc_lo(0, UNIT), voff = 0;
        auto issue_qk = [&]() {
            const uint32_t dk = dv_lo ^ (desc_lo(0, UNIT) ^ desc_lo(3 * SLOT, 16));
            bar_sync(1 + w, 192);
            fence_regs(s); fence_regs(q); fence_regs(o); fence_regs(p);
            WG_FENCE();
#pragma unroll
            for (int ks = 0; ks < 8; ks++)
                mma_rs128<0>(s, q[4 * ks], q[4 * ks + 1], q[4 * ks + 2], q[4 * ks + 3], desc_of(dk + (ks >> 2) * 1024 + (ks & 3) * 2), ks != 0);
            WG_COMMIT();
        };
        auto to_frag = [&](int i, uint32_t v0, uint32_t v1, uint32_t v2, uint32_t v3) {
            *reinterpret_cast<uint4*>(odst + i * 512) = make_uint4(v0, v1, v2, v3); };
        int n = 0;
#pragma unroll 1
        for (;;) {
            issue_qk();
            const int jn = n & 15;
            if (jn == 1) {
                finish(IC<ESPLIT>{}, IC<8>{}, 1u << (n >> 4), to_frag);
                WG_FENCE();
                issue_pv(dv_lo, 0, IC<0>{}, IC<PV1>{});
            } else {
                if (jn == 0 && n > 0) {
                    row_sums(1u << (n >> 4));
                    qnext = n == 48 ? reinterpret_cast<const uint4*>(frag) : qnext + 2048;
                    odst = frag + ((n >> 4) - 1) * 4096;
                    if (elect()) mbar_arrive(bar_qfree + (n >> 1) - 8);
                }
                issue_pv(dv_lo, 1, IC<0>{}, IC<PV1>{});
            }
            if (SPARE && n == 47) mbar_wait(bar_q3, 0);
            WG_WAIT(1);
            fence_regs(s); fence_regs(q);
            if (jn == 15) {
#pragma unroll
                for (int i = 0; i < 8; i++) {
                    const uint4 v = qnext[i * 32];
                    q[4 * i] = v.x; q[4 * i + 1] = v.y; q[4 * i + 2] = v.z; q[4 * i + 3] = v.w;
                }
            }
            if (jn == 0) {
                float a0 = fmaxf(s[0], s[1]), a1 = fmaxf(s[2], s[3]), a2 = fmaxf(s[4], s[5]), a3 = fmaxf(s[6], s[7]);
#pragma unroll
                for (int i = 1; i < MAXG; i++) {
                    a0 = fmaxf(a0, fmaxf(s[8 * i], s[8 * i + 1])); a1 = fmaxf(a1, fmaxf(s[8 * i + 2], s[8 * i + 3]));
                    a2 = fmaxf(a2, fmaxf(s[8 * i + 4], s[8 * i + 5])); a3 = fmaxf(a3, fmaxf(s[8 * i + 6], s[8 * i + 7]));
                }
                const uint32_t a = pack_bf16(fmaxf(a0, a2), fmaxf(a1, a3));
                const uint32_t b = bmax2(bmax2(a, __shfl_xor_sync(0xffffffffu, a, 1)), bmax2(__shfl_xor_sync(0xffffffffu, a, 2), __shfl_xor_sync(0xffffffffu, a, 3)));
                m0 = fmaf(-CS, bf_lo(b), -POFF); m1 = fmaf(-CS, bf_hi(b), -POFF);
            }
            if (PV1 < 8) issue_pv(dv_lo, 1, IC<PV1>{}, IC<8>{});
            release4(voff ^ 24);
            handoff();
#pragma unroll 1
            do {
                DBG_T(n);
#pragma unroll
                for (int i = 0; i < 4 * STAGE; i++) s[i] = fmaf(s[i], CS, (i & 2) ? m1 : m0);
#pragma unroll
                for (int i = 0; i < 4 * SPLIT; i++) s[i] = ex2(s[i]);
#pragma unroll
                for (int i = 0; i < SPLIT; i++) { l0 += s[4 * i] + s[4 * i + 1]; l1 += s[4 * i + 2] + s[4 * i + 3]; }
                if (STAGE < 16) {
                    m0 = fmaf(l0, 0.f, m0); m1 = fmaf(l1, 0.f, m1);
                }
                anchor(bar_full + 504, l0 + l1);
                WG_WAIT(0);
                fence_regs(o); fence_regs(p);
                release4(voff);
                dv_lo ^= 2 * SLOT / 16;
                voff ^= 16;
                n++;
#pragma unroll
                for (int i = 4 * STAGE; i < 64; i++) s[i] = fmaf(s[i], CS, (i & 2) ? m1 : m0);
#pragma unroll
                for (int i = 4 * SPLIT; i < 64; i++) s[i] = ex2(s[i]);
#pragma unroll
                for (int i = SPLIT; i < 16; i++) { l0 += s[4 * i] + s[4 * i + 1]; l1 += s[4 * i + 2] + s[4 * i + 3]; }
#pragma unroll
                for (int i = 0; i < 32; i++) p[i] = pack_bf16(s[2 * i], s[2 * i + 1]);
                if (((n + 1) & 15) < 3) break;
                issue_qk();
                issue_pv(dv_lo, 1, IC<0>{}, IC<8>{});
                WG_WAIT(1);
                fence_regs(s); fence_regs(q);
                release4(voff ^ 24);
                handoff();
            } while (n != 99);
            WG_WAIT(0);
            fence_regs(o); fence_regs(p);
            if ((n & 15) == 1) finish(IC<0>{}, IC<ESPLIT>{}, 1u << (n >> 4), to_frag);
            if (n == 64) break;
        }
        DBG_T(64);
        uint32_t a1[32], a2[32];
        bar_sync(1 + w, 192);
        fence_regs(o); fence_regs(p);
        WG_FENCE();
        issue_pv(desc_lo(3 * SLOT, UNIT), 1, IC<0>{}, IC<8>{});
        if (w == 0) handoff();
        row_sums(16);
        mbar_wait(bar_mod, 0);
        WG_WAIT(0);
        fence_regs(o); fence_regs(p);
        release(3);
        finish(IC<0>{}, IC<8>{}, 16, [&](int i, uint32_t v0, uint32_t v1, uint32_t v2, uint32_t v3) {
            p[4 * i] = v0; p[4 * i + 1] = v1; p[4 * i + 2] = v2; p[4 * i + 3] = v3; });
        bad = __reduce_or_sync(0xffffffffu, bad);
        bad = ((bad | ~(bad >> 8)) >> 1) & 15;
        if (__builtin_expect(bad != 0, 0)) {
            uint8_t* keep = g_keep + (size_t)(rg * 8 + cw) * 4096 + lane * 16;
            frag_store(keep, p);
            attn_fallback(bad, tag, frag, keep, args.wq, args.kc, args.vc);
            frag_load(q, frag); frag_load(p, keep);
        }
        DBG_T(80);
        DBG_G(124);

        const uint32_t eye = (lane >> 3) == (lane & 3) ? 0x3f80u << ((lane & 4) * 4) : 0;
        auto sum8 = [&](uint32_t* r, const uint4 (&v)[8]) {
            float d[16];
#pragma unroll
            for (int i = 0; i < 16; i++) d[i] = 0.f;
#pragma unroll
            for (int src = 0; src < 8; src++) {
                mma1688(d + 8 * (src & 1), v[src].x, v[src].y, eye);
                mma1688(d + 8 * (src & 1) + 4, v[src].z, v[src].w, eye);
            }
#pragma unroll
            for (int i = 0; i < 4; i++) r[i] = pack_bf16(d[2 * i] + d[8 + 2 * i], d[2 * i + 1] + d[9 + 2 * i]);
        };
        auto sum8_slot = [&](uint32_t* r, uint32_t e) {
            mbar_wait(bar_full + 8 * (e & 3), (e >> 2) & 1);
            uint4 v[8];
#pragma unroll
            for (int src = 0; src < 8; src++) v[src] = lds128(sb + (e & 3) * SLOT + w * (UNIT - 2048) + src * 2048 + tid * 16);
            sum8(r, v);
        };
        uint4 v3[8], wf[27];
        uint2 u4[8];
        const uint8_t *mb, *mb4;
        int tid_;
        auto load_wf = [&](auto lo, auto hi) {
            const uint32_t wa = sb + SM_Q + ((cw & 1) * D_ + (cw >> 1) * 32 + (tid_ & 7) + (tid_ & 16) / 2) * 80 + (tid_ & 8) * 2;
#pragma unroll
            for (int i = lo.value; i < hi.value; i++)
                wf[i] = ldsm4t((i < 24 ? wa + ((i / 3 & 3) * 8 + i / 12) * 1280 : wa + (32 - (cw >> 1)) * 1280) + (i % 3) * 32);
        };
        uint32_t at[18];
        {
            float ua[32], ub[32];
            uint32_t e = 148, prev = 4;
            auto step = [&](float (&u)[32], const uint32_t (&a)[32], const uint32_t (&b)[32], int acc) {
                mbar_wait(bar_full + 8 * (e & 3), (e >> 2) & 1);
                const uint64_t dv = mkdesc(sb + (e & 3) * SLOT, UNIT, 1024);
                if (!acc) fence_regs(u);
                WG_FENCE();
#pragma unroll
                for (int ks = 0; ks < 8; ks++) mma_rs64<1>(u, a[4 * ks], a[4 * ks + 1], a[4 * ks + 2], a[4 * ks + 3], dv + ks * 128, ks | acc);
#pragma unroll
                for (int ks = 0; ks < 8; ks++) mma_rs64<1>(u, b[4 * ks], b[4 * ks + 1], b[4 * ks + 2], b[4 * ks + 3], dv + 1024 + ks * 128, 1);
                WG_COMMIT();
                WG_WAIT(1);
                if (prev < 4) release(prev);
                prev = e & 3;
                e++;
            };
            auto store = [&](float (&u)[32], uint8_t* dst) {
                fence_regs(u);
#pragma unroll
                for (int i = 0; i < 4; i++)
                    st_relaxed4(dst + i * 512, pack_bf16(u[8 * i], u[8 * i + 1]), pack_bf16(u[8 * i + 2], u[8 * i + 3]),
                                pack_bf16(u[8 * i + 4], u[8 * i + 5]), pack_bf16(u[8 * i + 6], u[8 * i + 7]));
            };
#pragma unroll
            for (int i = 0; i < 8; i++) at[i] = 0;
#pragma unroll
            for (int i = 0; i < 32; i++) { ua[i] = 0.f; ub[i] = 0.f; }
            fence_regs(q); fence_regs(p);
            step(ua, q, p, 0);
            frag_load(a1, frag + 4096);
            mbar_wait(bar_full + 8, 1);
            frag_load(a2, frag + 8192);
            step(ub, q, p, 0);
            WG_WAIT(0);
            release(1);
            prev = 4;
            fence_regs(a1); fence_regs(a2); fence_regs(ua); fence_regs(ub);
#pragma unroll 1
            for (int ch = 0; ch < 4; ch++) {
                step(ua, a1, a2, 1);
                if (ch > 0) {
                    if (ch >= 2) {
#pragma unroll
                        for (int i = 0; i < 4; i++) at[i] = at[4 + i];
                        sum8_slot(at + 4, e);
                        __syncwarp();
                        release(e & 3);
                        e++;
                        WG_WAIT(0);
                        release(prev);
                        prev = 4;
                    }
                    step(ub, q, p, 0);
                } else {
                    WG_WAIT(0);
                }
                store(ua, frag + ch * 4096);
                step(ub, a1, a2, 1);
                step(ua, q, p, 0);
                store(ub, frag + ch * 4096 + 2048);
                __syncwarp();
                if (lane == 0 && ch < 3) mbar_arrive(bar_pub + 8 + 8 * ch);
            }
            tid_ = __shfl_sync(0xffffffffu, tid, lane);
            mb = padd(g_frag, (qb * 64 + j) * WREG + 3 * 4096 + tid * 16);
            mb4 = padd(mb, 4096 + ((cw >> 1) - cw) * 512 + (cw & 1) * 8);
            step(ua, a1, a2, 1);
            mbar_wait(bar_g, 0);
            load_wf(IC<0>{}, IC<WF0>{});
            WG_WAIT(0);
            release(3);
            store(ua, frag + 4 * 4096);
        }
        DBG_T(81);
        DBG_G(122);

        {
        const int tid = tid_, lane = tid & 31;
        const int g8 = lane >> 2, qd = lane & 3, l16 = lane & 15;
        uint32_t x1[20], h2[18], k1, k2;
        uint4 tp[9];
        const uint32_t xs = sb + l16 * XP + (lane >> 4) * 16 + cw * 32;
        float4* rec = reinterpret_cast<float4*>(red + 128);
        const uint2* candp = reinterpret_cast<const uint2*>(padd(g_cand, ((blockIdx.x & (CREP - 1)) * NCTA + (tid >> 1)) * 32 + (tid & 1) * 8));
        uint2 cd;
        {
            uint32_t wp[9], it = 0, miss;
            const uint32_t pa = sb + w * (UNIT - 2048) + tid * 16;
            const uint32_t ta = sb + SM_T + (cw * 8 + qd) * 16, wa = sb + SM_TW + (cw * 8 + qd) * 4;
#pragma unroll
            for (int k = 0; k < 9; k++) {
                const int pr = (k >> 1) * 64 + (k & 1) * 4;
                tp[k] = lds128(k < 8 ? ta + pr * 16 : ta + (256 - cw * 4) * 16);
                asm volatile("ld.shared.u32 %0, [%1];" : "=r"(wp[k]) : "r"(k < 8 ? wa + pr * 4 : wa + (256 - cw * 4) * 4) : "memory");
                if (!(g8 & 1)) wp[k] = 0x3f803f80u;
            }
            mbar_wait(bar_full, 0);
            rows_load(x1, xs, cw);
            mbar_wait(bar_full + 8, 0);
            {
                uint4 v[8];
#pragma unroll
                for (int src = 0; src < 8; src++) v[src] = lds128(pa + SLOT + src * 2048);
                sum8(at + 8, v);
            }
            float st[12];
#pragma unroll
            for (int i = 0; i < 12; i++) st[i] = 0.f;
            auto add_pair = [&](int k) {
                x1[2 * k] = badd2(x1[2 * k], bmul2(tp[k].x, at[2 * k]));
                x1[2 * k + 1] = badd2(x1[2 * k + 1], bmul2(tp[k].x, at[2 * k + 1]));
                stats_add(st, x1[2 * k], x1[2 * k + 1], wp[k]);
            };
#pragma unroll
            for (int k = 0; k < 6; k++) add_pair(k);
            mbar_wait(bar_full + 16, 0);
#pragma unroll
            for (int src = 0; src < 8; src++) v3[src] = lds128(pa + 2 * SLOT + src * 2048);
#pragma unroll 1
            do {
                miss = 0;
#pragma unroll
                for (int src = 0; src < 8; src++) reload16(v3[src], mb + (size_t)src * 8 * WREG, miss);
            } while (__any_sync(0xffffffffu, miss) && ++it < SPIN / 16);
            if (lane < 4) mbar_arrive_cluster(rel_base + 8 * (1 + (lane >> 1)));
            sum8(at + 12, v3);
            add_pair(6); add_pair(7);
            load_wf(IC<WF0>{}, IC<WF1>{});
            mbar_wait(bar_pre, 0);
            mbar_wait(bar_full + 24, 0);
#pragma unroll
            for (int src = 0; src < 8; src++)
                asm volatile("ld.shared.v2.u32 {%0, %1}, [%2];" : "=r"(u4[src].x), "=r"(u4[src].y)
                             : "r"(sb + 3 * SLOT + src * 2048 + (cw >> 1) * 512 + lane * 16 + (cw & 1) * 8) : "memory");
#pragma unroll 1
            do {
                miss = 0;
#pragma unroll
                for (int src = 0; src < 8; src++) reload8(u4[src], mb4 + (size_t)src * 8 * WREG, miss);
            } while (__any_sync(0xffffffffu, miss) && ++it < SPIN / 16);
            float d[8] = {0.f, 0.f, 0.f, 0.f, 0.f, 0.f, 0.f, 0.f};
#pragma unroll
            for (int i = 0; i < 4; i++) mma16816(d + 4 * (i & 1), u4[2 * i].x, u4[2 * i].y, u4[2 * i + 1].x, u4[2 * i + 1].y, eye, eye);
            at[16] = pack_bf16(d[0] + d[4], d[1] + d[5]); at[17] = pack_bf16(d[2] + d[6], d[3] + d[7]);
            add_pair(8);
            DBG_G(123);
            const float2 ws = *reinterpret_cast<const float2*>(smem_raw + SM_TS);
            uint4* cdst = padd(g_cand, ((tid & (CREP - 1)) * NCTA + rg) * 32);
            uint32_t mean2;
            float dot;
            const float rsd = rows_stats(st, rec, cw, lane, mean2, dot);
            const uint32_t b = __float_as_uint(fmaf(fmaf(-bf_lo(mean2), ws.x, dot), rsd, ws.y));
            const uint32_t key = (((b & 0x80000000u) ? ~b : (b | 0x80000000u)) | 2047u) - (rg * 16 + l16);
            top2(key, k1, k2);
            if (tid < CREP) st_relaxed(cdst, k1, tag, k2, tag);
            rows_normalise(h2, x1, mean2, rsd, lane);
#pragma unroll
            for (int k = 0; k < 18; k++) h2[k] = badd2(bmul2(h2[k], tp[k >> 1].y), tp[k >> 1].z);
            const uint32_t r1 = ~k1 & 15, r2 = ~k2 & 15;
            uint32_t todo = ((r1 & 7) == g8) | ((r2 & 7) == g8) << 1;
#pragma unroll 1
            while (todo) {
                const bool second = !(todo & 1), hi = (second ? r2 : r1) & 8;
                uint4* dst = padd(g_rows, ((rg * 2 + second) * RSLOT + cw * 16 + qd) * 16);
                uint32_t r[18];
#pragma unroll
                for (int k = 0; k < 9; k++) { r[k] = hi ? h2[2 * k + 1] : h2[2 * k]; r[9 + k] = hi ? x1[2 * k + 1] : x1[2 * k]; }
                fence_regs(r);
                st_relaxed(dst, r[0], r[1], r[2], r[3]);
                st_relaxed(dst + 4, r[4], r[5], r[6], r[7]);
                st_relaxed64(reinterpret_cast<uint2*>(padd(dst, 2048 - cw * 224 - qd * 8)), r[8], r[17]);
                st_relaxed(dst + 8, r[9], r[10], r[11], r[12]);
                st_relaxed(dst + 12, r[13], r[14], r[15], r[16]);
                todo &= todo - 1;
            }
            __syncwarp();
            cd = ld_relaxed64(candp);
#pragma unroll
            for (int k = 0; k < 18; k++) x1[k] = badd2(x1[k], bmul2(tp[k >> 1].w, h2[k]));
#pragma unroll
            for (int ch = 0; ch < 4; ch++) stsm_x4(xs + ch * 256, x1[4 * ch], x1[4 * ch + 1], x1[4 * ch + 2], x1[4 * ch + 3]);
            asm volatile("stmatrix.sync.aligned.m8n8.x2.shared.b16 [%0], {%1, %2};" ::"r"(xs + 1024 - cw * 16), "r"(x1[16]), "r"(x1[17]) : "memory");
            load_wf(IC<WF1>{}, IC<27>{});
        }
        DBG_G(110);
        float2* part = reinterpret_cast<float2*>(smem_raw + 3 * SLOT + UNIT);
        bf16* act = reinterpret_cast<bf16*>(smem_raw + 3 * SLOT + UNIT + 4096);
        {
            uint32_t it = 0;
#pragma unroll 1
            while (cd.y != tag && ++it < SPIN / 16) cd = ld_relaxed64(candp);
            __syncwarp();
            top2(cd.x, k1, k2);
            if (lane == 0) reinterpret_cast<uint2*>(red)[cw] = make_uint2(k1, k2);
            bar_sync(3, 256);
            DBG_G(111);
            top2(reinterpret_cast<const uint32_t*>(red)[l16], k1, k2);
        }
        const int sel0 = ~k1 & 2047, sel1 = ~k2 & 2047;
        const uint32_t slot0 = (sel0 >> 4) * 2, slot1 = (sel1 >> 4) * 2 + ((sel0 ^ sel1) < 16);
        uint4 b[9], b2[3];
        {
            const bool tk = cw < 4 ? cw & 2 : lane & 16;
            const int ri = cw < 4 ? tid & 63 : 64 + l16;
            const uint4* hp = padd(g_rows, ((tk ? slot1 : slot0) * RSLOT + (cw < 4 ? ri + (ri & 56) : ri + 64)) * 16);
            const uint32_t hs = sb + 3 * SLOT + UNIT + 8192;
            uint4 hr = make_uint4(cw < 5 ? ~0u : 0, 0, 0, 0);
            uint32_t it = 0, miss;
            reload16(hr, hp, miss);
            if (OUTP == 0 && tid == 255) {
                reinterpret_cast<int2*>(red)[8] = make_int2(sel0, sel1);
                mbar_arrive(bar_out);
            }
            mbar_wait(bar_full + 8, 1);
            mbar_wait(bar_full + 16, 1);
            {
                const uint32_t da = sb + (lane < 18 ? SLOT + lane * XP : 2 * SLOT + (lane - 18) * XP) + cw * 144;
                const uint32_t db = sb + 2 * SLOT + (14 + (lane & 3)) * XP + cw * 144 + (lane >> 3) * 16;
#pragma unroll
                for (int i = 0; i < 9; i++) b[i] = ldsm4t(da + i * 16);
#pragma unroll
                for (int i = 0; i < 3; i++) b2[i] = ldsm4t(db + i * 48);
            }
#pragma unroll 1
            do {
                miss = 0;
                reload16(hr, hp, miss);
            } while (__any_sync(0xffffffffu, miss) && ++it < SPIN / 16);
            if (cw < 5) asm volatile("st.shared.v4.u32 [%0], {%1, %2, %3, %4};" ::"r"(hs + (tk * 84 + ri) * 16), "r"(hr.x), "r"(hr.y), "r"(hr.z), "r"(hr.w) : "memory");
            bar_sync(3, 256);
            uint4 hv[4];
            uint32_t hw[2];
#pragma unroll
            for (int i = 0; i < 4; i++) hv[i] = lds128(hs + ((g8 & 1) * 84 + (cw >> 1) * 16 + qd + i * 4) * 16);
#pragma unroll
            for (int i = 0; i < 2; i++)
                asm volatile("ld.shared.u32 %0, [%1];" : "=r"(hw[i]) : "r"(hs + ((g8 & 1) * 84 + 64) * 16 + (cw >> 1) * 64 + qd * 8 + i * 32) : "memory");
            DBG_G(112);
            float acc[24];
#pragma unroll
            for (int i = 0; i < 24; i++) acc[i] = 0.f;
#pragma unroll
            for (int i = 0; i < 27; i++) {
                const int ks = i / 3;
                mma16816(acc + 4 * (i % 6), wf[i].x, wf[i].y, wf[i].z, wf[i].w, ks == 8 ? hw[0] : (ks & 1) ? hv[ks >> 1 & 3].z : hv[ks >> 1 & 3].x,
                         ks == 8 ? hw[1] : (ks & 1) ? hv[ks >> 1 & 3].w : hv[ks >> 1 & 3].y);
            }
            if (qd == 0) {
#pragma unroll
                for (int i = 0; i < 5; i++) part[cw * 48 + i * 8 + g8] = make_float2(acc[2 * i] + acc[12 + 2 * i], acc[2 * i + 1] + acc[13 + 2 * i]);
            }
        }
        {
            uint2* dst = padd(g_ypart, ((((g8 & 1) * 36 + ((cw * 9) >> 1)) * NCTA + blockIdx.x) * 8 + (cw & 1) * 4 + qd) * 8);
            uint2* dst1 = dst + ((cw & 1) ? NCTA * 8 - 4 : 4);
            bar_sync(3, 256);
            {
                const float* pp = reinterpret_cast<const float*>(part) + ((blockIdx.x & 1) << 3) + (tid & 127);
                const float gs = rbf((pp[0] + pp[192]) + (pp[384] + pp[576])), us = rbf((pp[96] + pp[288]) + (pp[480] + pp[672]));
                const float v = rbf(gs * sigmoidf_(gs)) * us;
                if (tid < 80) act[(tid & 1) * 56 + (tid >> 1)] = __float2bfloat16_rn(tid < 72 ? v : 0.f);
            }
            bar_sync(3, 256);
            DBG_G(113);
            const uint32_t ap = sb + 3 * SLOT + UNIT + 4096 + (lane & 1) * 112 + (lane >> 4) * 16;
            const uint4 a0 = ldsm4(ap), a1 = ldsm4(ap + 32), a2 = ldsm4(ap + 64);
            float y[36];
#pragma unroll
            for (int i = 0; i < 36; i++) y[i] = 0.f;
#pragma unroll
            for (int i = 0; i < 9; i++) {
                const uint32_t bl = i % 3 == 0 ? b2[i / 3].x : i % 3 == 1 ? b2[i / 3].y : b2[i / 3].z;
                mma16816(y + 4 * i, a0.x, a0.y, a0.z, a0.w, b[i].x, b[i].y);
                mma16816(y + 4 * i, a1.x, a1.y, a1.z, a1.w, b[i].z, b[i].w);
                mma1688(y + 4 * i, a2.x, a2.y, bl);
            }
#pragma unroll
            for (int i = 0; i < 9; i++)
                if (lane < 8) st_relaxed64(((i & 1) ? dst1 : dst) + (i >> 1) * (NCTA * 8), __float_as_uint(y[4 * i]), __float_as_uint(y[4 * i + 1]));
        }
        DBG_G(114);
        if (OUTP == 1 && tid == 255) {
            reinterpret_cast<int2*>(red)[8] = make_int2(sel0, sel1);
            mbar_arrive(bar_out);
        }
        if (blockIdx.x == 127 && tid == 0) gs->epoch[0] = tag;
        if (blockIdx.x < 72) {
            const int tok = blockIdx.x >= 36, grp = blockIdx.x - tok * 36, cp = grp * 8 + (lane & 7);
            const uint2* src = padd(g_ypart, (blockIdx.x * NCTA * 8 + tid) * 8);
            const uint8_t* hsrc = reinterpret_cast<const uint8_t*>(padd(g_rows, (tok ? slot1 : slot0) * (RSLOT * 16) +
                (grp < 32 ? (grp & 7) * 256 + (grp >> 4) * 64 + qd * 16 + (grp & 8) + (lane & 4) : 2048 + (cp - 256) * 8)));
            const uint8_t* xsrc = hsrc + (grp < 32 ? 128 : 4);
            uint32_t* dst = padd(reinterpret_cast<uint32_t*>(args.out), (tok ? sel1 : sel0) * (D_ * 2) + cp * 4);
            const uint32_t gb = reinterpret_cast<const uint4*>(smem_raw + SM_T)[cp].w;
            const uint32_t ksel = ((tok ? k2 : k1) & ~2047u) | 1024u;
            const float sg = sigmoidf_(rbf(__uint_as_float((ksel & 0x80000000u) ? (ksel & 0x7fffffffu) : ~ksel)));
            uint2 v[4];
            uint32_t hv, xv, it = 0;
            bool miss;
#pragma unroll 1
            do {
#pragma unroll
                for (int i = 0; i < 4; i++) v[i] = ld_relaxed64(src + i * 256);
                hv = ld_relaxed32(hsrc);
                xv = ld_relaxed32(xsrc);
                miss = max(__vimax3_u32(v[0].x, v[1].x, v[2].x), __vimax3_u32(v[3].x, hv, xv)) == ~0u;
            } while (__any_sync(0xffffffffu, miss) && ++it < SPIN / 16);
            float y0 = (__uint_as_float(v[0].x) + __uint_as_float(v[1].x)) + (__uint_as_float(v[2].x) + __uint_as_float(v[3].x));
            float y1 = (__uint_as_float(v[0].y) + __uint_as_float(v[1].y)) + (__uint_as_float(v[2].y) + __uint_as_float(v[3].y));
            y0 += __shfl_xor_sync(0xffffffffu, y0, 8); y1 += __shfl_xor_sync(0xffffffffu, y1, 8);
            y0 += __shfl_xor_sync(0xffffffffu, y0, 16); y1 += __shfl_xor_sync(0xffffffffu, y1, 16);
            if (lane < 8) reinterpret_cast<float2*>(rec)[cw * 8 + lane] = make_float2(y0, y1);
            bar_sync(3, 256);
            if (cw == 0) {
                const float2 t0_ = reinterpret_cast<const float2*>(rec)[lane], t1_ = reinterpret_cast<const float2*>(rec)[32 + lane];
                y0 = t0_.x + t1_.x; y1 = t0_.y + t1_.y;
                y0 += __shfl_xor_sync(0xffffffffu, y0, 8); y1 += __shfl_xor_sync(0xffffffffu, y1, 8);
                y0 += __shfl_xor_sync(0xffffffffu, y0, 16); y1 += __shfl_xor_sync(0xffffffffu, y1, 16);
                const uint32_t y2 = bmul2(pack_bf16(y0, y1), pack_bf16(sg, sg));
                if (lane < 8) *dst = badd2(xv, bmul2(gb, badd2(hv, y2)));
            }
        }
        }
        DBG_T(88);
        DBG_G(121);
    }
}

typedef CUresult (*EncodeFn)(CUtensorMap*, CUtensorMapDataType, cuuint32_t, void*, const cuuint64_t*, const cuuint64_t*,
                             const cuuint32_t*, const cuuint32_t*, CUtensorMapInterleave, CUtensorMapSwizzle,
                             CUtensorMapL2promotion, CUtensorMapFloatOOBfill);

static void make_map(EncodeFn enc, CUtensorMap* m, const void* ptr, int rank, const cuuint64_t* dims,
                     const cuuint64_t* strides, const cuuint32_t* box, CUtensorMapSwizzle sw = CU_TENSOR_MAP_SWIZZLE_128B,
                     CUtensorMapDataType dt = CU_TENSOR_MAP_DATA_TYPE_BFLOAT16) {
    const cuuint32_t es[3] = {1, 1, 1};
    enc(m, dt, rank, const_cast<void*>(ptr), dims, strides, box, es,
        CU_TENSOR_MAP_INTERLEAVE_NONE, sw, CU_TENSOR_MAP_L2_PROMOTION_L2_128B,
        CU_TENSOR_MAP_FLOAT_OOB_FILL_NONE);
}

extern "C" void kernel_launch(void* const* d_in, const int* in_sizes, int n_in, void* d_out, int out_size) {
    const bf16* x = (const bf16*)d_in[0];
    const bf16* kc = (const bf16*)d_in[1];
    const bf16* vc = (const bf16*)d_in[2];
    const bf16* wq = (const bf16*)d_in[3];
    const bf16* wo = (const bf16*)d_in[4];
    const bf16* w_r = (const bf16*)d_in[6];
    const bf16* w_gate = (const bf16*)d_in[7];
    const bf16* w_up = (const bf16*)d_in[8];
    const bf16* w_down = (const bf16*)d_in[9];
    const bf16* cvec = (const bf16*)d_in[10];
    const bf16* w_mod = (const bf16*)d_in[11];
    bf16* out = (bf16*)d_out;

    void* fn = nullptr;
    cudaDriverEntryPointQueryResult qr;
    cudaGetDriverEntryPoint("cuTensorMapEncodeTiled", &fn, cudaEnableDefault, &qr);
    EncodeFn enc = (EncodeFn)fn;
    void* p_s;
    cudaGetSymbolAddress(&p_s, g_s);

    CUtensorMap tm_wq, tm_k, tm_v, tm_wo, tm_p, tm_x, tm_d, tm_g, tm_u;
    { cuuint64_t d[2] = {QD, D_}, s[1] = {QD * 2}; cuuint32_t b[2] = {64, 128}; make_map(enc, &tm_wq, wq, 2, d, s, b); }
    { cuuint64_t d[2] = {DH, HKV * S_}, s[1] = {DH * 2}; cuuint32_t b[2] = {64, 128};
      make_map(enc, &tm_k, kc, 2, d, s, b); make_map(enc, &tm_v, vc, 2, d, s, b); }
    { cuuint64_t d[2] = {D_, QD}, s[1] = {D_ * 2}; cuuint32_t b[2] = {64, 128}; make_map(enc, &tm_wo, wo, 2, d, s, b); }
    { cuuint64_t d[3] = {256, 160, NCTA}, s[2] = {1024, 8 * WREG}; cuuint32_t b[3] = {256, 2, 8};
      make_map(enc, &tm_p, ((Scratch*)p_s)->frag, 3, d, s, b, CU_TENSOR_MAP_SWIZZLE_NONE, CU_TENSOR_MAP_DATA_TYPE_UINT32); }
    { cuuint64_t d[2] = {D_ / 4, S_}, s[1] = {D_ * 2}; cuuint32_t b[2] = {XP / 8, 16};
      make_map(enc, &tm_x, x, 2, d, s, b, CU_TENSOR_MAP_SWIZZLE_NONE, CU_TENSOR_MAP_DATA_TYPE_UINT64); }
    { cuuint64_t d[2] = {D_ / 4, F_}, s[1] = {D_ * 2}; cuuint32_t b[2] = {XP / 8, 18};
      make_map(enc, &tm_d, w_down, 2, d, s, b, CU_TENSOR_MAP_SWIZZLE_NONE, CU_TENSOR_MAP_DATA_TYPE_UINT64); }
    { cuuint64_t d[2] = {F_, D_}, s[1] = {F_ * 2}; cuuint32_t b[2] = {40, 24};
      make_map(enc, &tm_g, w_gate, 2, d, s, b, CU_TENSOR_MAP_SWIZZLE_NONE); make_map(enc, &tm_u, w_up, 2, d, s, b, CU_TENSOR_MAP_SWIZZLE_NONE); }

    cudaFuncSetAttribute(fused_kernel<true>, cudaFuncAttributeMaxDynamicSharedMemorySize, SM_TOTAL);
    cudaFuncSetAttribute(fused_kernel<false>, cudaFuncAttributeMaxDynamicSharedMemorySize, SM_TOTAL);
    cudaLaunchConfig_t cfg = {};
    cfg.gridDim = NCTA + 4; cfg.blockDim = 384; cfg.dynamicSmemBytes = SM_TOTAL;
    cudaLaunchAttribute at;
    at.id = cudaLaunchAttributeClusterDimension; at.val.clusterDim.x = 2; at.val.clusterDim.y = 1; at.val.clusterDim.z = 1;
    cfg.attrs = &at; cfg.numAttrs = 1;
    int ncl = 0;
    if (cudaOccupancyMaxActiveClusters(&ncl, fused_kernel<true>, &cfg) != cudaSuccess) { ncl = 0; cudaGetLastError(); }
    Args args{w_mod, cvec, (Scratch*)p_s, out, x, kc, vc, wq, wo, w_r, w_down};
    if (USE_SPARE && ncl >= NCTA / 2 + 2)
        fused_kernel<true><<<NCTA + 4, 384, SM_TOTAL>>>(args, tm_wq, tm_k, tm_v, tm_wo, tm_p, tm_x, tm_d, tm_g, tm_u);
    else
        fused_kernel<false><<<NCTA, 384, SM_TOTAL>>>(args, tm_wq, tm_k, tm_v, tm_wo, tm_p, tm_x, tm_d, tm_g, tm_u);
}
```

```cpp
#include <cuda_runtime.h>
#include <cuda_bf16.h>
#include <cuda.h>
#include <stdint.h>
#include <math.h>

typedef __nv_bfloat16 bf16;

constexpr int S_ = 2048;
constexpr int D_ = 576;
constexpr int HQ = 32, HKV = 16, DH = 128;
constexpr int F_ = 4608;
constexpr int QD = HQ * DH;

constexpr int NCTA = 128;
constexpr int WREG = 5 * 4096;
constexpr int CREP = 8;
constexpr int RSLOT = 144;
constexpr int MREP = 4;
struct Scratch {
    unsigned int epoch[128];
    unsigned int flag_mod[NCTA];
    unsigned int flag_part[16 * 32];
    unsigned int flag_q3[16 * 32];
    unsigned int flag_h[NCTA * 32];
    uint2 mod1[MREP * D_];
    uint32_t mod2[4 * D_];
    uint4 cand[CREP * NCTA * 2];
    uint2 ypart[72 * NCTA * 8];
    uint4 h[2][NCTA * 36 * 32];
    uint4 q3[NCTA * 8 * 128];
    uint4 rows[NCTA * 2 * RSLOT];
    uint8_t frag[NCTA * 8 * WREG];
    uint8_t keep[NCTA * 8 * 4096];
};
__device__ __align__(1024) Scratch g_s;
#define g_h gs->h[tag & 1]
#define g_q3 gs->q3
#define g_keep gs->keep
#define g_flag_h gs->flag_h
#define g_flag_part gs->flag_part
#define g_flag_mod gs->flag_mod
#define g_flag_q3 gs->flag_q3
#define g_frag gs->frag
#define g_cand gs->cand
#define g_ypart gs->ypart
#define g_rows gs->rows

#define DBG_INIT()
#define DBG_P(i)
#define DBG_PG(i)
#define DBG_T(i)
#define DBG_G(i)

__device__ __forceinline__ uint32_t pack_bf16(float lo, float hi) {
    uint32_t r;
    asm("cvt.rn.bf16x2.f32 %0, %1, %2;" : "=r"(r) : "f"(hi), "f"(lo));
    return r;
}
__device__ __forceinline__ float rbf(float x) { return __uint_as_float(pack_bf16(0.f, x)); }
__device__ __forceinline__ float bf_lo(uint32_t v) { return __uint_as_float(v << 16); }
__device__ __forceinline__ float bf_hi(uint32_t v) { return __uint_as_float(v & 0xffff0000u); }
__device__ __forceinline__ float ex2(float x) {
    float y;
    asm("ex2.approx.ftz.f32 %0, %1;" : "=f"(y) : "f"(x));
    return y;
}
template <class T>
__device__ __forceinline__ T* padd(T* p, uint32_t off) {
    unsigned long long r;
    asm("{\n.reg .b32 l, h;\nmov.b64 {l, h}, %1;\nadd.cc.u32 l, l, %2;\naddc.u32 h, h, 0;\nmov.b64 %0, {l, h};\n}" : "=l"(r) : "l"(p), "r"(off));
    return reinterpret_cast<T*>(r);
}
__device__ __forceinline__ uint32_t smem_u32(const void* p) { return (uint32_t)__cvta_generic_to_shared(p); }
__device__ __forceinline__ void mbar_init(uint32_t bar, uint32_t cnt) {
    asm volatile("mbarrier.init.shared::cta.b64 [%0], %1;" ::"r"(bar), "r"(cnt) : "memory");
}
__device__ __forceinline__ void mbar_expect_tx(uint32_t bar, uint32_t bytes) {
    asm volatile("mbarrier.arrive.expect_tx.shared::cta.b64 _, [%0], %1;" ::"r"(bar), "r"(bytes) : "memory");
}
__device__ __forceinline__ void mbar_arrive(uint32_t bar) {
    asm volatile("mbarrier.arrive.shared::cta.b64 _, [%0];" ::"r"(bar) : "memory");
}
__device__ __forceinline__ void mbar_arrive_cluster(uint32_t cluster_addr) {
    asm volatile("mbarrier.arrive.shared::cluster.b64 _, [%0];" ::"r"(cluster_addr) : "memory");
}
constexpr uint32_t SPIN = 1u << 20;
__device__ __forceinline__ void mbar_wait(uint32_t bar, uint32_t parity) {
    asm volatile("{\n.reg .pred p;\n.reg .b32 c;\nmov.b32 c, 0;\n"
                 "W_%=:\nmbarrier.try_wait.parity.shared::cta.b64 p, [%0], %1;\n@p bra D_%=;\n"
                 "add.u32 c, c, 1;\nsetp.lt.u32 p, c, 0x100000;\n@p bra W_%=;\nD_%=:\n}"
                 ::"r"(bar), "r"(parity) : "memory");
}
__device__ __forceinline__ void anchor(uint32_t addr, float v) {
    asm volatile("{\n.reg .pred p;\nsetp.lt.f32 p, %1, 0f00000000;\n@p st.volatile.shared.f32 [%0], %1;\n}" ::"r"(addr), "f"(v) : "memory");
}
__device__ __forceinline__ void mbar_wait_sleep(uint32_t bar, uint32_t parity) {
    asm volatile("{\n.reg .pred p;\n.reg .b32 c;\nmov.b32 c, 0;\n"
                 "W_%=:\nmbarrier.try_wait.parity.shared::cta.b64 p, [%0], %1, 5000;\n@p bra D_%=;\n"
                 "add.u32 c, c, 1;\nsetp.lt.u32 p, c, 0x20000;\n@p bra W_%=;\nD_%=:\n}"
                 ::"r"(bar), "r"(parity) : "memory");
}
__device__ __forceinline__ uint32_t load_tag(const Scratch* gs) {
    uint32_t tag;
    asm volatile("ld.global.ca.u32 %0, [%1];" : "=r"(tag) : "l"(gs->epoch) : "memory");
    return tag + 1;
}
__device__ __forceinline__ uint4 ld_relaxed(const uint4* p) {
    uint4 v;
    asm volatile("ld.relaxed.gpu.global.v4.u32 {%0,%1,%2,%3}, [%4];" : "=r"(v.x), "=r"(v.y), "=r"(v.z), "=r"(v.w) : "l"(p) : "memory");
    return v;
}
__device__ __forceinline__ void st_relaxed(uint4* p, uint32_t a, uint32_t b, uint32_t c, uint32_t d) {
    asm volatile("{\n.reg .b64 u, v;\nmov.b64 u, {%1, %2};\nmov.b64 v, {%3, %4};\nst.relaxed.gpu.global.v2.b64 [%0], {u, v};\n}"
                 ::"l"(p), "r"(a), "r"(b), "r"(c), "r"(d) : "memory");
}
__device__ __forceinline__ void st_relaxed4(void* p, uint32_t a, uint32_t b, uint32_t c, uint32_t d) {
    asm volatile("st.relaxed.gpu.global.v4.u32 [%0], {%1, %2, %3, %4};" ::"l"(p), "r"(a), "r"(b), "r"(c), "r"(d) : "memory");
}
__device__ __forceinline__ uint2 ld_relaxed8(const void* p) {
    uint2 v;
    asm volatile("ld.relaxed.gpu.global.v2.u32 {%0,%1}, [%2];" : "=r"(v.x), "=r"(v.y) : "l"(p) : "memory");
    return v;
}
__device__ __forceinline__ uint2 ld_relaxed64(const uint2* p) {
    uint2 v;
    asm volatile("{\n.reg .b64 u;\nld.relaxed.gpu.global.b64 u, [%2];\nmov.b64 {%0, %1}, u;\n}" : "=r"(v.x), "=r"(v.y) : "l"(p) : "memory");
    return v;
}
__device__ __forceinline__ void st_relaxed64(uint2* p, uint32_t a, uint32_t b) {
    asm volatile("{\n.reg .b64 u;\nmov.b64 u, {%1, %2};\nst.relaxed.gpu.global.b64 [%0], u;\n}" ::"l"(p), "r"(a), "r"(b) : "memory");
}
__device__ __forceinline__ uint4 ld_relaxed2(const uint4* p) {
    uint4 v;
    asm volatile("{\n.reg .b64 u, w;\nld.relaxed.gpu.global.v2.b64 {u, w}, [%4];\nmov.b64 {%0, %1}, u;\nmov.b64 {%2, %3}, w;\n}"
                 : "=r"(v.x), "=r"(v.y), "=r"(v.z), "=r"(v.w) : "l"(p) : "memory");
    return v;
}
__device__ __forceinline__ void reload16(uint4& v, const void* p, uint32_t& miss) {
    asm volatile("{\n.reg .pred p;\n.reg .b32 m;\n.reg .b64 u, w;\nmax.u32 m, %0, %2;\nsetp.eq.u32 p, m, 0xffffffff;\n"
                 "mov.b64 u, {%0, %1};\nmov.b64 w, {%2, %3};\n@p ld.relaxed.gpu.global.v2.b64 {u, w}, [%5];\n"
                 "mov.b64 {%0, %1}, u;\nmov.b64 {%2, %3}, w;\n@p mov.u32 %4, 1;\n}"
                 : "+r"(v.x), "+r"(v.y), "+r"(v.z), "+r"(v.w), "+r"(miss) : "l"(p) : "memory");
}
__device__ __forceinline__ void reload8(uint2& v, const void* p, uint32_t& miss) {
    asm volatile("{\n.reg .pred p;\n.reg .b64 u;\nsetp.eq.u32 p, %0, 0xffffffff;\nmov.b64 u, {%0, %1};\n"
                 "@p ld.relaxed.gpu.global.b64 u, [%3];\nmov.b64 {%0, %1}, u;\n@p mov.u32 %2, 1;\n}"
                 : "+r"(v.x), "+r"(v.y), "+r"(miss) : "l"(p) : "memory");
}
__device__ __forceinline__ uint32_t ld_relaxed32(const void* p) {
    uint32_t v;
    asm volatile("ld.relaxed.gpu.global.u32 %0, [%1];" : "=r"(v) : "l"(p) : "memory");
    return v;
}
__device__ __forceinline__ void poll2x2(const uint4* p0, const uint4* p1, uint32_t tag, uint4& o0, uint4& o1) {
    uint4 v0, v1;
    uint32_t miss, it = 0;
#pragma unroll 1
    do {
        v0 = ld_relaxed2(p0); v1 = ld_relaxed2(p1);
        miss = (v0.y ^ tag) | (v0.w ^ tag) | (v1.y ^ tag) | (v1.w ^ tag);
    } while (miss && ++it < SPIN / 16);
    o0 = v0; o1 = v1;
}
__device__ __forceinline__ void flag_wait(const unsigned int* p, uint32_t tag) {
    uint32_t v, it = 0;
#pragma unroll 1
    do {
        asm volatile("ld.relaxed.gpu.global.u32 %0, [%1];" : "=r"(v) : "l"(p) : "memory");
    } while (__any_sync(0xffffffffu, v != tag) && ++it < SPIN / 16);
    asm volatile("fence.acquire.gpu;" ::: "memory");
    __syncwarp();
}
__device__ __forceinline__ bool elect() {
    uint32_t p;
    asm volatile("{\n.reg .pred p;\nelect.sync _|p, 0xffffffff;\nselp.u32 %0, 1, 0, p;\n}" : "=r"(p));
    return p;
}
__device__ __forceinline__ void flag_release(unsigned int* p, uint32_t tag) {
    asm volatile("st.release.gpu.global.u32 [%0], %1;" ::"l"(p), "r"(tag) : "memory");
}
__device__ __forceinline__ uint32_t touch(const void* p) {
    uint32_t v;
    asm volatile("ld.global.nc.L1::no_allocate.L2::128B.u32 %0, [%1];" : "=r"(v) : "l"(p));
    return v;
}
__device__ __forceinline__ void bar_sync(int id, int n) { asm volatile("bar.sync %0, %1;" ::"r"(id), "r"(n) : "memory"); }
__device__ __forceinline__ void bar_arrive(int id, int n) { asm volatile("bar.arrive %0, %1;" ::"r"(id), "r"(n) : "memory"); }

constexpr uint64_t EVICT_NORMAL = 0x1000000000000000ull, EVICT_FIRST = 0x12F0000000000000ull;
__device__ __forceinline__ void tma2d(uint32_t dst, const CUtensorMap* m, int c0, int c1, uint32_t bar) {
    asm volatile("cp.async.bulk.tensor.2d.shared::cluster.global.mbarrier::complete_tx::bytes.L2::cache_hint [%0], [%1, {%3, %4}], [%2], %5;"
                 ::"r"(dst), "l"(m), "r"(bar), "r"(c0), "r"(c1), "l"(EVICT_FIRST) : "memory");
}
__device__ __forceinline__ void tma2d_mc(uint32_t dst, const CUtensorMap* m, int c0, int c1, uint32_t bar, uint64_t pol) {
    asm volatile("cp.async.bulk.tensor.2d.shared::cluster.global.mbarrier::complete_tx::bytes.multicast::cluster.L2::cache_hint [%0], [%1, {%3, %4}], [%2], %5, %6;"
                 ::"r"(dst), "l"(m), "r"(bar), "r"(c0), "r"(c1), "h"((uint16_t)3), "l"(pol) : "memory");
}
__device__ __forceinline__ void tma3d(uint32_t dst, const CUtensorMap* m, int c0, int c1, int c2, uint32_t bar) {
    asm volatile("cp.async.bulk.tensor.3d.shared::cluster.global.mbarrier::complete_tx::bytes.L2::cache_hint [%0], [%1, {%3, %4, %5}], [%2], %6;"
                 ::"r"(dst), "l"(m), "r"(bar), "r"(c0), "r"(c1), "r"(c2), "l"(EVICT_FIRST) : "memory");
}
__device__ __forceinline__ void bulk_load(uint32_t dst, const void* src, uint32_t bytes, uint32_t bar) {
    asm volatile("cp.async.bulk.shared::cluster.global.mbarrier::complete_tx::bytes [%0], [%1], %2, [%3];"
                 ::"r"(dst), "l"(src), "r"(bytes), "r"(bar) : "memory");
}
__device__ __forceinline__ void l2_prefetch(const void* src, uint32_t bytes) {
    asm volatile("cp.async.bulk.prefetch.L2.global [%0], %1;" ::"l"(src), "r"(bytes) : "memory");
}
__device__ __forceinline__ uint32_t bmul2(uint32_t a, uint32_t b) { uint32_t r; asm("mul.rn.bf16x2 %0, %1, %2;" : "=r"(r) : "r"(a), "r"(b)); return r; }
__device__ __forceinline__ uint32_t badd2(uint32_t a, uint32_t b) { uint32_t r; asm("add.rn.bf16x2 %0, %1, %2;" : "=r"(r) : "r"(a), "r"(b)); return r; }
__device__ __forceinline__ uint32_t bsub2(uint32_t a, uint32_t b) { uint32_t r; asm("sub.rn.bf16x2 %0, %1, %2;" : "=r"(r) : "r"(a), "r"(b)); return r; }
__device__ __forceinline__ uint32_t bmax2(uint32_t a, uint32_t b) { uint32_t r; asm("max.bf16x2 %0, %1, %2;" : "=r"(r) : "r"(a), "r"(b)); return r; }
__device__ __forceinline__ uint32_t bfma2(uint32_t a, uint32_t b, uint32_t c) { uint32_t r; asm("fma.rn.bf16x2 %0, %1, %2, %3;" : "=r"(r) : "r"(a), "r"(b), "r"(c)); return r; }
__device__ __forceinline__ uint4 lds128(uint32_t a) { uint4 v; asm volatile("ld.shared.v4.u32 {%0,%1,%2,%3}, [%4];" : "=r"(v.x), "=r"(v.y), "=r"(v.z), "=r"(v.w) : "r"(a) : "memory"); return v; }
__device__ __forceinline__ uint2 lds64(uint32_t a) { uint2 v; asm volatile("ld.shared.v2.u32 {%0,%1}, [%2];" : "=r"(v.x), "=r"(v.y) : "r"(a) : "memory"); return v; }
__device__ __forceinline__ uint32_t lds32(uint32_t a) { uint32_t v; asm volatile("ld.shared.u32 %0, [%1];" : "=r"(v) : "r"(a) : "memory"); return v; }
__device__ __forceinline__ uint4 ldsm4(uint32_t a) {
    uint4 v;
    asm volatile("ldmatrix.sync.aligned.m8n8.x4.shared.b16 {%0,%1,%2,%3}, [%4];" : "=r"(v.x), "=r"(v.y), "=r"(v.z), "=r"(v.w) : "r"(a) : "memory");
    return v;
}
__device__ __forceinline__ uint4 ldsm4t(uint32_t a) {
    uint4 v;
    asm volatile("ldmatrix.sync.aligned.m8n8.x4.trans.shared.b16 {%0,%1,%2,%3}, [%4];" : "=r"(v.x), "=r"(v.y), "=r"(v.z), "=r"(v.w) : "r"(a) : "memory");
    return v;
}
__device__ __forceinline__ void mma1688(float* d, uint32_t a0, uint32_t a1, uint32_t b) {
    asm("mma.sync.aligned.m16n8k8.row.col.f32.bf16.bf16.f32 {%0,%1,%2,%3}, {%4,%5}, {%6}, {%0,%1,%2,%3};"
        : "+f"(d[0]), "+f"(d[1]), "+f"(d[2]), "+f"(d[3]) : "r"(a0), "r"(a1), "r"(b));
}
__device__ __forceinline__ void mma16816(float* d, uint32_t a0, uint32_t a1, uint32_t a2, uint32_t a3, uint32_t b0, uint32_t b1) {
    asm("mma.sync.aligned.m16n8k16.row.col.f32.bf16.bf16.f32 {%0,%1,%2,%3}, {%4,%5,%6,%7}, {%8,%9}, {%0,%1,%2,%3};"
                 : "+f"(d[0]), "+f"(d[1]), "+f"(d[2]), "+f"(d[3]) : "r"(a0), "r"(a1), "r"(a2), "r"(a3), "r"(b0), "r"(b1));
}
__device__ __forceinline__ void stsm_x4(uint32_t addr, uint32_t a, uint32_t b, uint32_t c, uint32_t d) {
    asm volatile("stmatrix.sync.aligned.m8n8.x4.shared.b16 [%0], {%1, %2, %3, %4};"
                 ::"r"(addr), "r"(a), "r"(b), "r"(c), "r"(d) : "memory");
}

__device__ __forceinline__ uint64_t mkdesc(uint32_t addr, uint32_t lbo, uint32_t sbo) {
    return (uint64_t)((addr & 0x3FFFF) >> 4) | ((uint64_t)(lbo >> 4) << 16) | ((uint64_t)(sbo >> 4) << 32) | (1ull << 62);
}
constexpr uint32_t SM0 = 1024;
__host__ __device__ constexpr uint32_t desc_lo(uint32_t off, uint32_t lbo) { return ((SM0 + off) >> 4) | ((lbo >> 4) << 16); }
__device__ __forceinline__ uint64_t desc_of(uint32_t lo) { return lo | (0x40000040ull << 32); }
#define WG_FENCE() asm volatile("wgmma.fence.sync.aligned;" ::: "memory")
#define WG_COMMIT() asm volatile("wgmma.commit_group.sync.aligned;" ::: "memory")
#define WG_WAIT(n) asm volatile("wgmma.wait_group.sync.aligned %0;" ::"n"(n) : "memory")

#define F8(a, i) "+f"(a[i]), "+f"(a[i + 1]), "+f"(a[i + 2]), "+f"(a[i + 3]), "+f"(a[i + 4]), "+f"(a[i + 5]), "+f"(a[i + 6]), "+f"(a[i + 7])
#define F16(a, i) F8(a, i), F8(a, i + 8)
#define F64(a) F16(a, 0), F16(a, 16), F16(a, 32), F16(a, 48)
#define F32(a) F16(a, 0), F16(a, 16)
#define L64 "%0,%1,%2,%3,%4,%5,%6,%7,%8,%9,%10,%11,%12,%13,%14,%15,%16,%17,%18,%19,%20,%21,%22,%23,%24,%25,%26,%27,%28,%29,%30,%31,%32,%33,%34,%35,%36,%37,%38,%39,%40,%41,%42,%43,%44,%45,%46,%47,%48,%49,%50,%51,%52,%53,%54,%55,%56,%57,%58,%59,%60,%61,%62,%63"
#define L32 "%0,%1,%2,%3,%4,%5,%6,%7,%8,%9,%10,%11,%12,%13,%14,%15,%16,%17,%18,%19,%20,%21,%22,%23,%24,%25,%26,%27,%28,%29,%30,%31"

template <int TB>
__device__ __forceinline__ void mma_rs128(float (&d)[64], uint32_t a0, uint32_t a1, uint32_t a2, uint32_t a3, uint64_t b, int acc) {
    asm volatile("{\n.reg .pred p;\nsetp.ne.b32 p, %69, 0;\n"
                 "wgmma.mma_async.sync.aligned.m64n128k16.f32.bf16.bf16 {" L64 "}, {%64,%65,%66,%67}, %68, p, 1, 1, %70;\n}"
                 : F64(d) : "r"(a0), "r"(a1), "r"(a2), "r"(a3), "l"(b), "r"(acc), "n"(TB));
}
template <int TB>
__device__ __forceinline__ void mma_rs64(float (&d)[32], uint32_t a0, uint32_t a1, uint32_t a2, uint32_t a3, uint64_t b, int acc) {
    asm volatile("{\n.reg .pred p;\nsetp.ne.b32 p, %37, 0;\n"
                 "wgmma.mma_async.sync.aligned.m64n64k16.f32.bf16.bf16 {" L32 "}, {%32,%33,%34,%35}, %36, p, 1, 1, %38;\n}"
                 : F32(d) : "r"(a0), "r"(a1), "r"(a2), "r"(a3), "l"(b), "r"(acc), "n"(TB));
}
template <int N>
__device__ __forceinline__ void fence_regs(float (&d)[N]) {
#pragma unroll
    for (int i = 0; i < N; i++) asm volatile("" : "+f"(d[i])::"memory");
}
template <int N>
__device__ __forceinline__ void fence_regs(uint32_t (&d)[N]) {
#pragma unroll
    for (int i = 0; i < N; i++) asm volatile("" : "+r"(d[i])::"memory");
}

template <int V> struct IC { static constexpr int value = V; };

constexpr int SLOT = 32768, UNIT = 16384;
constexpr int SM_Q = 4 * SLOT;
constexpr int SM_BAR = 7 * SLOT;
constexpr int SM_RED = SM_BAR + 512;
constexpr int SM_TOTAL = SM_BAR + 3072;
constexpr int XP = D_ * 2 + 16;
constexpr int M_MOD = 16 * XP;
constexpr int SM_T = SM_Q + 2 * D_ * 80, SM_TC = SM_T + D_ * 4, SM_TG = SM_TC + D_ * 4, SM_TS = SM_TG + D_ * 2;
constexpr float CS = 0.08838834764831845f * 1.4426950408889634f;
#define LMAX 0.5f
#define LMIN 0x1p-104f
#define USE_SPARE 1
#define MAXG 2
#define SPLIT 10
#define ESPLIT 2
#define PV1 8
#define RW 2
#define HW 2
#define HW2 1
#define XDELAY 200
#define QDELAY 300
#define TMPF 1
#define PFD0 2000
#define PFD1 400
#define HSENT 1
#define HDELAY 500
#define STAGE 11
#define POFF 102.f
#define WF0 6
#define WF1 16
#define C3D 0
#define C4D 300
#define DD 300
#define P2E 1
#define BO 0
#define MAP 2
#define SO 0
#define WF2 27
#define OUTP 0
constexpr int PF_KV = 8, PF_WO = 120;

__device__ __forceinline__ int cluster_role() {
    int k = blockIdx.x >> 1;
    if (MAP == 0) return k & 63;
    if (MAP == 1) return (k & 7) * 8 + ((k >> 3) & 7);
    if (MAP == 3) {
        asm("mov.u32 %0, %%smid;" : "=r"(k));
        k >>= 1;
        const int r = ((k - 32) * 37) >> 8;
        return k < 32 ? (k & 7) * 8 + (k >> 3) : k < 60 ? (k - 31 - r * 7) * 8 + 4 + r : (k - 58) & 7;
    }
    const int r = ((k - 36) * 37) >> 8, i = k - 36 - r * 7;
    if (MAP == 4) return k < 4 ? 4 + k : k < 36 ? ((k - 4) & 7) * 8 + ((k - 4) >> 3) : (i + 1) * 8 + ((4 + r) & 7);
    return k < 4 ? 12 + k : k < 36 ? ((k - 4) & 7) * 8 + ((k - 4) >> 3) : (i + (i > 0)) * 8 + ((4 + r) & 7);
}

struct Args {
    const bf16 *w_mod, *cvec;
    Scratch* gs;
    bf16* out;
    const bf16 *x, *kc, *vc, *wq, *wo, *w_r, *w_down;
};

__device__ __forceinline__ void frag_store(uint8_t* p, const uint32_t (&a)[32]) {
#pragma unroll
    for (int i = 0; i < 8; i++)
        __stcg(reinterpret_cast<uint4*>(p + i * 512), make_uint4(a[4 * i], a[4 * i + 1], a[4 * i + 2], a[4 * i + 3]));
}
__device__ __forceinline__ void frag_load(uint32_t (&a)[32], const uint8_t* p) {
#pragma unroll
    for (int i = 0; i < 8; i++) {
        const uint4 v = __ldcg(reinterpret_cast<const uint4*>(p + i * 512));
        a[4 * i] = v.x; a[4 * i + 1] = v.y; a[4 * i + 2] = v.z; a[4 * i + 3] = v.w;
    }
}
__device__ __forceinline__ float quad_sum(float v) {
    v += __shfl_xor_sync(0xffffffffu, v, 1);
    return v + __shfl_xor_sync(0xffffffffu, v, 2);
}
__device__ __forceinline__ float quad_max(float v) {
    v = fmaxf(v, __shfl_xor_sync(0xffffffffu, v, 1));
    return fmaxf(v, __shfl_xor_sync(0xffffffffu, v, 2));
}
__device__ __forceinline__ float rcp_fast(float x) { float y; asm("rcp.approx.ftz.f32 %0, %1;" : "=f"(y) : "f"(x)); return y; }
__device__ __forceinline__ float sigmoidf_(float x) { return rcp_fast(1.f + ex2(-1.4426950408889634f * x)); }
__device__ __forceinline__ void top2(uint32_t k, uint32_t& k1, uint32_t& k2) {
    k1 = __reduce_max_sync(0xffffffffu, k);
    k2 = __reduce_max_sync(0xffffffffu, k == k1 ? 0 : k);
}

__device__ __forceinline__ void mod_fma(float (&a)[8], const uint4 w, float sc) {
    a[0] += sc * bf_lo(w.x); a[1] += sc * bf_hi(w.x); a[2] += sc * bf_lo(w.y); a[3] += sc * bf_hi(w.y);
    a[4] += sc * bf_lo(w.z); a[5] += sc * bf_hi(w.z); a[6] += sc * bf_lo(w.w); a[7] += sc * bf_hi(w.w);
}
__device__ __forceinline__ float mod_reduce(float (&a)[8], int lane) {
#pragma unroll
    for (int h = 4; h > 0; h >>= 1) {
        const bool up = lane & (8 / h);
#pragma unroll
        for (int i = 0; i < h; i++)
            a[i] = (up ? a[i + h] : a[i]) + __shfl_xor_sync(0xffffffffu, up ? a[i] : a[i + h], 8 / h);
    }
    return a[0] + __shfl_xor_sync(0xffffffffu, a[0], 16);
}

__device__ __forceinline__ float ln_stats(float sum, float sq, uint32_t& mean2) {
    const float mean = sum * (1.f / D_);
    const float var = fmaxf(fmaf(-mean, mean, sq * (1.f / D_)), 0.f);
    float sd;
    asm("sqrt.approx.ftz.f32 %0, %1;" : "=f"(sd) : "f"(rbf(rbf(var) + 1e-5f)));
    mean2 = pack_bf16(mean, mean);
    return rcp_fast(rbf(sd));
}
__device__ __forceinline__ uint32_t ln_pair(uint32_t x, uint32_t mean2, float rsd) {
    const uint32_t d = bsub2(x, mean2);
    return pack_bf16(bf_lo(d) * rsd, bf_hi(d) * rsd);
}
__device__ __forceinline__ void rows_load(uint32_t (&x)[20], uint32_t xs, int cw) {
#pragma unroll
    for (int ch = 0; ch < 5; ch++) {
        const uint4 v = ldsm4(ch < 4 ? xs + ch * 256 : xs + 1024 - cw * 16);
        x[4 * ch] = v.x; x[4 * ch + 1] = v.y; x[4 * ch + 2] = v.z; x[4 * ch + 3] = v.w;
    }
}
__device__ __forceinline__ void stats_add(float (&st)[12], uint32_t a, uint32_t b, uint32_t w) {
    mma1688(st, a, b, w);
    mma1688(st + 4, a, b, a);
    mma1688(st + 8, a, b, b);
}
__device__ __forceinline__ float rows_stats(const float (&st)[12], float4* rec, int cw, int lane, uint32_t& mean2, float& dot) {
    const int g8 = lane >> 2;
    if ((g8 >> 1) == (lane & 3)) {
        rec[cw * 16 + g8] = make_float4(st[0], (g8 & 1) ? st[5] : st[4], st[1], 0.f);
        rec[cw * 16 + 8 + g8] = make_float4(st[2], (g8 & 1) ? st[11] : st[10], st[3], 0.f);
    }
    bar_sync(3, 256);
    const float4* r = rec + (lane >> 4) * 64 + (lane & 15);
    const float4 s0 = r[0], s1 = r[16], s2 = r[32], s3 = r[48];
    const float sum = (s0.x + s1.x) + (s2.x + s3.x), sq = (s0.y + s1.y) + (s2.y + s3.y);
    dot = (s0.z + s1.z) + (s2.z + s3.z);
    dot += __shfl_xor_sync(0xffffffffu, dot, 16);
    return ln_stats(sum + __shfl_xor_sync(0xffffffffu, sum, 16), sq + __shfl_xor_sync(0xffffffffu, sq, 16), mean2);
}
__device__ __forceinline__ void rows_normalise(uint32_t* y, const uint32_t* x, uint32_t mean2, float rsd, int lane) {
    const int g8 = lane >> 2;
    const uint32_t ma2 = __shfl_sync(0xffffffffu, mean2, g8), mb2 = __shfl_sync(0xffffffffu, mean2, g8 + 8);
    const float ra = __shfl_sync(0xffffffffu, rsd, g8), rb = __shfl_sync(0xffffffffu, rsd, g8 + 8);
#pragma unroll
    for (int k = 0; k < 9; k++) { y[2 * k] = ln_pair(x[2 * k], ma2, ra); y[2 * k + 1] = ln_pair(x[2 * k + 1], mb2, rb); }
}
__device__ __forceinline__ uint32_t pair_of(const uint2* mp, int k, int cw) {
    return (k < 8 ? mp[(k >> 1) * 64 + (k & 1) * 4] : (mp - cw * 4)[256]).x;
}

__device__ __forceinline__ uint4 h_frag(const uint4* hf, int ks, int lane) {
    if (ks < 32) return ld_relaxed2(hf + ks * 32);
    const uint2* p = reinterpret_cast<const uint2*>(padd(hf, 256 - lane * 8) + ks * 32 - 16);
    const uint2 a = ld_relaxed64(p), b = ld_relaxed64(p + 32);
    return make_uint4(a.x, a.y, b.x, b.y);
}

__device__ __noinline__ void attn_fallback(uint32_t bad, uint32_t tag, uint8_t* frag, uint8_t* keep, const bf16* wq, const bf16* kc, const bf16* vc) {
  const Scratch* gs = &g_s;
  const int lane = threadIdx.x & 31, g8 = lane >> 2, qd = lane & 3;
  const int j = cluster_role() & 7, qb = (cluster_role() >> 3) * 2 + (blockIdx.x & 1);
  const uint4* hf = g_h + (size_t)(qb * 8 + (threadIdx.x >> 5) - 4) * (36 * 32) + lane;
#pragma unroll 1
  for (int t = 0; t < 4; t++) {
    if (!((bad >> t) & 1)) continue;
    const bf16 *wqp = wq + (4 * j + t) * DH, *kp = kc + (size_t)(2 * j + (t >> 1)) * S_ * DH, *vp = vc + (size_t)(2 * j + (t >> 1)) * S_ * DH;
    uint32_t q[32];
    float o[64];
#pragma unroll
    for (int i = 0; i < 64; i++) o[i] = 0.f;
#pragma unroll 1
    for (int ks = 0; ks < 36; ks++) {
        const uint4 a = h_frag(hf, ks, lane);
        const unsigned short* wr = reinterpret_cast<const unsigned short*>(wqp + (size_t)(ks * 16 + 2 * qd) * QD + g8);
#pragma unroll
        for (int dt = 0; dt < 16; dt++) {
            const uint32_t b0 = __ldg(wr + dt * 8) | ((uint32_t)__ldg(wr + dt * 8 + QD) << 16);
            const uint32_t b1 = __ldg(wr + dt * 8 + 8 * QD) | ((uint32_t)__ldg(wr + dt * 8 + 9 * QD) << 16);
            mma16816(o + 4 * dt, a.x, a.y, a.z, a.w, b0, b1);
        }
    }
#pragma unroll
    for (int i = 0; i < 32; i++) q[i] = pack_bf16(o[2 * i], o[2 * i + 1]);
#pragma unroll
    for (int i = 0; i < 64; i++) o[i] = 0.f;
    float m0 = -INFINITY, m1 = -INFINITY, l0 = 0.f, l1 = 0.f;
#pragma unroll 1
    for (int key = 0; key < S_; key += 16) {
        float sc[8];
#pragma unroll
        for (int i = 0; i < 8; i++) sc[i] = 0.f;
#pragma unroll
        for (int nt = 0; nt < 2; nt++) {
            const uint32_t* kr = reinterpret_cast<const uint32_t*>(kp + (size_t)(key + nt * 8 + g8) * DH) + qd;
#pragma unroll
            for (int ks = 0; ks < 8; ks++)
                mma16816(sc + 4 * nt, q[4 * ks], q[4 * ks + 1], q[4 * ks + 2], q[4 * ks + 3], __ldg(kr + ks * 8), __ldg(kr + ks * 8 + 4));
        }
        const float n0 = quad_max(fmaxf(fmaxf(m0, fmaxf(sc[0], sc[1])), fmaxf(sc[4], sc[5])));
        const float n1 = quad_max(fmaxf(fmaxf(m1, fmaxf(sc[2], sc[3])), fmaxf(sc[6], sc[7])));
        const float f0 = ex2((m0 - n0) * CS), f1 = ex2((m1 - n1) * CS);
        m0 = n0; m1 = n1;
#pragma unroll
        for (int i = 0; i < 8; i++) sc[i] = ex2((sc[i] - ((i & 2) ? n1 : n0)) * CS);
        l0 = l0 * f0 + (sc[0] + sc[1]) + (sc[4] + sc[5]);
        l1 = l1 * f1 + (sc[2] + sc[3]) + (sc[6] + sc[7]);
        const uint32_t e0 = pack_bf16(sc[0], sc[1]), e1 = pack_bf16(sc[2], sc[3]), e2 = pack_bf16(sc[4], sc[5]), e3 = pack_bf16(sc[6], sc[7]);
        const unsigned short* vr = reinterpret_cast<const unsigned short*>(vp + (size_t)(key + 2 * qd) * DH + g8);
#pragma unroll
        for (int dt = 0; dt < 16; dt++) {
            o[4 * dt] *= f0; o[4 * dt + 1] *= f0; o[4 * dt + 2] *= f1; o[4 * dt + 3] *= f1;
            const uint32_t b0 = __ldg(vr + dt * 8) | ((uint32_t)__ldg(vr + dt * 8 + DH) << 16);
            const uint32_t b1 = __ldg(vr + dt * 8 + 8 * DH) | ((uint32_t)__ldg(vr + dt * 8 + 9 * DH) << 16);
            mma16816(o + 4 * dt, e0, e1, e2, e3, b0, b1);
        }
    }
    const float i0 = 1.f / quad_sum(l0), i1 = 1.f / quad_sum(l1);
#pragma unroll
    for (int i = 0; i < 16; i++) {
        q[2 * i] = pack_bf16(o[4 * i] * i0, o[4 * i + 1] * i0);
        q[2 * i + 1] = pack_bf16(o[4 * i + 2] * i1, o[4 * i + 3] * i1);
    }
    frag_store(t < 3 ? frag + t * 4096 : keep, q);
  }
}

__device__ __forceinline__ void spare_q3(Scratch* gs, uint32_t sb, uint32_t bar_full, uint32_t bar_empty, int lane, int cw) {
    const uint32_t tag = load_tag(gs);
    uint32_t rel_base, e = 3;
    asm("mapa.shared::cluster.u32 %0, %1, %2;" : "=r"(rel_base) : "r"(bar_empty), "r"(lane & 1));
#pragma unroll 1
    for (int qb = blockIdx.x - NCTA; qb < 16; qb += 4) {
        uint32_t h[144];
        float o[64];
        flag_wait(&g_flag_h[(qb * 8 + cw) * 32], tag);
        const uint4* hf = g_h + (size_t)(qb * 8 + cw) * (36 * 32) + lane;
#pragma unroll
        for (int ks = 0; ks < 36; ks++) {
            const uint4 v = h_frag(hf, ks, lane);
            h[4 * ks] = v.x; h[4 * ks + 1] = v.y; h[4 * ks + 2] = v.z; h[4 * ks + 3] = v.w;
        }
#pragma unroll
        for (int i = 0; i < 64; i++) o[i] = 0.f;
#pragma unroll 1
        for (int v = 0; v < 4; v++) {
            fence_regs(o);
#pragma unroll
            for (int t = 0; t < 5; t++) {
                mbar_wait(bar_full + 8 * (e & 3), (e >> 2) & 1);
                const uint64_t dv = mkdesc(sb + (e & 3) * SLOT, UNIT, 1024);
                WG_FENCE();
#pragma unroll
                for (int ks = 0; ks < (t < 4 ? 8 : 4); ks++)
                    mma_rs128<1>(o, h[32 * t + 4 * ks], h[32 * t + 4 * ks + 1], h[32 * t + 4 * ks + 2], h[32 * t + 4 * ks + 3], dv + ks * 128, ks | t);
                WG_COMMIT();
                if (t > 0) { WG_WAIT(1); if (lane < 2) mbar_arrive_cluster(rel_base + 8 * ((e - 1) & 3)); }
                e++;
            }
            WG_WAIT(0);
            fence_regs(o);
            if (lane < 2) mbar_arrive_cluster(rel_base + 8 * ((e - 1) & 3));
            uint4* dst = &g_q3[((qb * 8 + 2 * v) * 8 + cw) * 128 + lane];
#pragma unroll
            for (int i = 0; i < 8; i++)
                __stcg(dst + (i >> 2) * 1024 + (i & 3) * 32, make_uint4(pack_bf16(o[8 * i], o[8 * i + 1]), pack_bf16(o[8 * i + 2], o[8 * i + 3]),
                                                                        pack_bf16(o[8 * i + 4], o[8 * i + 5]), pack_bf16(o[8 * i + 6], o[8 * i + 7])));
        }
        bar_sync(3, 256);
        if (cw == 0 && lane == 0) flag_release(&g_flag_q3[qb * 32], tag);
        __syncwarp();
    }
}

template <bool SPARE>
__global__ void __cluster_dims__(2, 1, 1) __launch_bounds__(384, 1)
fused_kernel(const Args args, const __grid_constant__ CUtensorMap tm_wq,
             const __grid_constant__ CUtensorMap tm_k, const __grid_constant__ CUtensorMap tm_v,
             const __grid_constant__ CUtensorMap tm_wo, const __grid_constant__ CUtensorMap tm_p,
             const __grid_constant__ CUtensorMap tm_x, const __grid_constant__ CUtensorMap tm_d,
             const __grid_constant__ CUtensorMap tm_g, const __grid_constant__ CUtensorMap tm_u) {
    extern __shared__ __align__(1024) uint8_t smem_raw[];
    const uint32_t sb = smem_u32(smem_raw);
    Scratch* const gs = args.gs;
    const uint32_t bar_full = sb + SM_BAR;
    const uint32_t bar_g = bar_full + 8 * 4;
    const uint32_t bar_mod = bar_g + 8;
    const uint32_t bar_go = bar_mod + 8;
    const uint32_t bar_x = bar_go + 40;
    const uint32_t bar_empty = bar_x + 8;
    const uint32_t bar_pub = bar_empty + 8 * 4;
    const uint32_t bar_qfree = bar_pub + 32;
    const uint32_t bar_out = bar_qfree + 24;
    const uint32_t bar_q3 = bar_out + 8;
    const uint32_t bar_pre = bar_q3 + 16;
    const uint32_t bar_w0 = bar_q3 + 8;
    constexpr int E0 = SPARE ? 2 : 0;

    const int c = blockIdx.x & 1;
    const int role = cluster_role();
    const int j = role & 7;
    const int qb = (role >> 3) * 2 + c;
    const int rg = qb * 8 + j;
    const int warp = __shfl_sync(0xffffffffu, threadIdx.x >> 5, 0);

    if (SPARE && blockIdx.x >= NCTA && warp >= 4) {
        asm volatile("barrier.cluster.arrive.relaxed.aligned;" ::: "memory");
        asm volatile("setmaxnreg.inc.sync.aligned.u32 240;");
        asm volatile("barrier.cluster.wait.aligned;" ::: "memory");
        spare_q3(gs, sb, bar_full, bar_empty, threadIdx.x & 31, warp - 4);
        asm volatile("barrier.cluster.arrive.relaxed.aligned;\nbarrier.cluster.wait.aligned;" ::: "memory");
    } else if (warp < 4) {
        asm volatile("setmaxnreg.dec.sync.aligned.u32 24;");
        int lane;
        asm volatile("mov.u32 %0, %%laneid;" : "=r"(lane));
        if (warp == 2 && elect()) {
            if (TMPF) asm volatile("prefetch.tensormap [%0];" ::"l"(&tm_x) : "memory");
#pragma unroll
            for (int i = 0; i < 27; i++) mbar_init(bar_full + 8 * i, i < 12 || i >= 23 ? 1 : i < 16 ? 16 : 8);
#pragma unroll
            for (int i = 0; i <= E0; i++) {
                mbar_arrive(bar_full + 8 * i);
                asm volatile("mbarrier.arrive.shared::cta.b64 _, [%0], 16;" ::"r"(bar_empty + 8 * i) : "memory");
            }
            asm volatile("fence.mbarrier_init.release.cluster;" ::: "memory");
        }
        __syncwarp();
        asm volatile("barrier.cluster.arrive.relaxed.aligned;" ::: "memory");
        if (warp == 2 && !(SPARE && blockIdx.x >= NCTA)) {
            if (XDELAY) __nanosleep(XDELAY);
            if (elect()) {
                mbar_expect_tx(bar_x, 16 * XP);
                tma2d(sb + SM_Q, &tm_x, 0, rg * 16, bar_x);
            }
            __syncwarp();
        }
        asm volatile("barrier.cluster.wait.aligned;" ::: "memory");
        const uint32_t tag = load_tag(gs);
        if (SPARE && blockIdx.x >= NCTA) {
            if (warp == 1) {
#pragma unroll 1
                for (int e = 3; e < 83; e++) {
                    const int v = (e - 3) / 5;
                    mbar_wait_sleep(bar_empty + 8 * (e & 3), ~(e >> 2) & 1);
                    if (elect()) {
                        mbar_expect_tx(bar_full + 8 * (e & 3), SLOT);
                        tma2d_mc(sb + (e & 3) * SLOT + c * UNIT, &tm_wq, (8 * (v & 3) + 4 * c + 3) * DH + 64, (e - 3 - v * 5) * 128,
                                 bar_full + 8 * (e & 3), EVICT_NORMAL);
                    }
                }
            }
            __syncwarp();
            asm volatile("barrier.cluster.arrive.relaxed.aligned;\nbarrier.cluster.wait.aligned;" ::: "memory");
            return;
        }
        if (warp == 3) {
#pragma unroll 1
            for (int e = 4; e < 20; e++) {
                __nanosleep(e == 4 ? PFD0 : PFD1);
                const int hd = (e * 52) >> 8, row = (e - hd * 5) * 128 + qb * 8 + (lane >> 1);
                if (lane < 16 && row < D_)
                    asm volatile("prefetch.global.L2 [%0];" ::"l"(padd(args.wq, (row * QD + (4 * j + ((0x1320 >> (4 * hd)) & 3)) * DH + (lane & 1) * 64) * 2)) : "memory");
            }
            __syncwarp();
            mbar_wait_sleep(bar_go, 0);
#pragma unroll 1
            for (int unit = 72 + blockIdx.x; unit < 216; unit += NCTA) {
                float a[8];
#pragma unroll
                for (int i = 0; i < 8; i++) a[i] = 0.f;
#pragma unroll 1
                for (int k = lane >> 1; k < D_; k += 16) {
                    const float cv = __bfloat162float(*padd(args.cvec, k * 2));
                    mod_fma(a, __ldg(reinterpret_cast<const uint4*>(padd(args.w_mod, (k * (6 * D_) + unit * 16 + (lane & 1) * 8) * 2))), rbf(cv * sigmoidf_(cv)));
                }
                const float v = mod_reduce(a, lane), v1 = __shfl_down_sync(0xffffffffu, v, 8);
                if (lane < 8) *padd(gs->mod2, ((unit - 72) * 8 + (lane & 1) * 4 + (lane & 2) + (lane >> 2)) * 4) = pack_bf16(v, v1);
            }
            __syncwarp();
            if (lane == 0) flag_release(padd(g_flag_mod, blockIdx.x * 4), tag);
#pragma unroll 1
            for (int k = 0; k < 36 * HSENT; k++) {
                __nanosleep(200);
                __stcg(padd(gs->h[0], (~tag & 1) * (NCTA * 36 * 512) + ((rg * 36 + k) * 32 + lane) * 16), make_uint4(0, 0, 0, 0));
            }
            __syncwarp();
            mbar_wait_sleep(bar_qfree + 16, 0);
            __nanosleep(2000);
            {
                uint4 v;
                uint32_t it = 0;
#pragma unroll 1
                do {
                    v = ld_relaxed(reinterpret_cast<const uint4*>(padd(g_flag_mod, lane * 16)));
                } while (((v.x ^ tag) | (v.y ^ tag) | (v.z ^ tag) | (v.w ^ tag)) && ++it < SPIN / 16);
                asm volatile("fence.acquire.gpu;" ::: "memory");
            }
            __syncwarp();
            {
                float w1 = 0.f, w2 = 0.f;
#pragma unroll 1
                for (int k = lane; k < D_ / 2; k += 32) {
                    const uint32_t* mp = padd(gs->mod2, k * 4);
                    const uint32_t sv = __ldcg(mp + D_ / 2), c1 = badd2(__ldcg(mp + D_), 0x3f803f80u);
                    const uint32_t wr = *reinterpret_cast<const uint32_t*>(padd(args.w_r, k * 4)), wp = bmul2(c1, wr);
                    reinterpret_cast<uint2*>(smem_raw + SM_T)[k] = make_uint2(__ldcg(mp), wp);
                    reinterpret_cast<uint2*>(smem_raw + SM_TC)[k] = make_uint2(c1, sv);
                    reinterpret_cast<uint32_t*>(smem_raw + SM_TG)[k] = __ldcg(mp + 3 * D_ / 2);
                    w1 += bf_lo(wp) + bf_hi(wp);
                    w2 += bf_lo(sv) * bf_lo(wr) + bf_hi(sv) * bf_hi(wr);
                }
#pragma unroll 1
                for (int i = 1; i < 32; i <<= 1) { w1 += __shfl_xor_sync(0xffffffffu, w1, i); w2 += __shfl_xor_sync(0xffffffffu, w2, i); }
                *reinterpret_cast<float2*>(smem_raw + SM_TS) = make_float2(w1, w2);
            }
#pragma unroll
            for (int i = 0; i < 4; i++) reinterpret_cast<uint4*>(smem_raw + SM_RED)[lane + 32 * i] = make_uint4(~0u, ~0u, ~0u, ~0u);
            asm volatile("fence.proxy.async.shared::cta;" ::: "memory");
            __syncwarp();
            if (elect()) {
                uint8_t* mb = g_frag + (size_t)rg * 8 * WREG + 3 * 4096;
#pragma unroll 1
                for (int k = 0; k < 8; k++, mb += WREG) {
#pragma unroll
                    for (int i = 0; i < 3; i++)
                        asm volatile("cp.async.bulk.global.shared::cta.bulk_group [%0], [%1], 2048;" ::"l"(mb + i * 2048), "r"(sb + SM_RED) : "memory");
                    __nanosleep(500);
                }
                asm volatile("cp.async.bulk.commit_group;\ncp.async.bulk.wait_group 0;\nfence.proxy.async.global;" ::: "memory");
            }
            __syncwarp();
            if (lane == 0) mbar_arrive(bar_mod);
            __syncwarp();
            mbar_wait_sleep(bar_go + 8, 0);
            if (lane < 3) asm volatile("prefetch.tensormap [%0];" ::"l"(lane == 0 ? &tm_x : lane == 1 ? &tm_p : &tm_d) : "memory");
            __syncwarp();
            mbar_wait_sleep(bar_go + 8 * 2, 0);
            uint32_t acc = 0;
#pragma unroll 1
            for (int k = lane; k < 16 * 9; k += 32) acc |= touch(padd(args.x, (rg * 16 * D_ + k * 64) * 2));
            if (acc == 0) reinterpret_cast<volatile uint32_t*>(smem_raw + SM_BAR)[127] = acc;
        } else if (warp == 0) {
#pragma unroll 1
            for (int i = 0; i < 48; i++) {
                if (i == 0 || i == 17 || i == 34) mbar_wait_sleep(bar_qfree + (i >> 4) * 8, 0);
                if (SPARE && i == 17) {
                    flag_wait(&g_flag_q3[qb * 32], tag);
                    if (elect()) {
                        asm volatile("fence.proxy.async.global;" ::: "memory");
                        mbar_expect_tx(bar_q3, UNIT);
#pragma unroll 1
                        for (int k = 0; k < 8; k++) bulk_load(sb + SM_Q + 2 * SLOT + k * 4096 + 2048, &g_q3[(rg * 8 + k) * 128], 2048, bar_q3);
                    }
                }
                __nanosleep(700);
                if (elect()) {
                    asm volatile("mbarrier.expect_tx.shared::cta.b64 [%0], %1;" ::"r"(bar_g), "n"(1920) : "memory");
                    tma2d(sb + SM_Q + i * 1920, i < 24 ? &tm_g : &tm_u, (blockIdx.x * 36) & ~7, (i < 24 ? i : i - 24) * 24, bar_g);
                }
            }
            if (elect()) mbar_arrive(bar_g);
#pragma unroll 1
            for (int i = 0; i < 18; i++) {
                __nanosleep(400);
                if (elect()) l2_prefetch(args.w_down + (size_t)(blockIdx.x * 36 + i * 2) * D_, 4 * D_);
            }
            __syncwarp();
            mbar_wait_sleep(bar_go + 8 * 4, 0);
            uint4* rp = padd(g_rows, (rg * 2 * RSLOT + lane) * 16);
#pragma unroll
            for (int k = 0; k < 9; k++) rp[k * 32] = make_uint4(~0u, ~0u, ~0u, ~0u);
            if (blockIdx.x < 72) {
                uint4* yp = reinterpret_cast<uint4*>(padd(g_ypart, blockIdx.x * NCTA * 64 + lane * 16));
#pragma unroll
                for (int k = 0; k < 16; k++) yp[k * 32] = make_uint4(~0u, ~0u, ~0u, ~0u);
            }
            asm volatile("fence.acq_rel.gpu;" ::: "memory");
            __syncwarp();
            if (lane == 0) mbar_arrive(bar_pre);
        } else if (warp == 1) {
            __nanosleep(QDELAY);
            uint32_t go = bar_go;
            uint64_t marks = 24 | 151 << 8 | 154 << 16 | 159ull << 24 | 165ull << 32;
#pragma unroll 1
            for (int e = E0; e < 168; e++) {
                const CUtensorMap* tm;
                int c0, c1;
                uint64_t pol = EVICT_FIRST;
                if (e == 158 || e == 163) continue;
                if (e < 21 && e != 19) {
                    const int i = SPARE && e < 12 ? e - 2 : e - (e == 20), hd = (i * 52) >> 8;
                    tm = &tm_wq; c0 = (4 * j + ((0x1320 >> (4 * hd)) & 3)) * DH + c * 64; c1 = (i - hd * 5) * 128 - 64;
                    if (SPARE && e >= 12 && e < 15) { c0 = (4 * j + 3) * DH; c1 = (2 * (e - 12) + c) * 128; }
                } else if (e < 148) {
                    const int i = max(e - 20, 0);
                    const bool isk = i == 0 || ((i & 1) && i < 127);
                    const int n = isk ? (i + 1) >> 1 : (i - 1) >> 1;
                    tm = isk ? &tm_k : &tm_v; c0 = c * 64; c1 = (2 * j + (n >> 5)) * S_ + (n & 15) * 128;
                    if (!(i & 32)) pol = EVICT_NORMAL;
                } else {
                    int i = e - 148 - (e > 158) - (e > 163);
                    if (i == 1 || i == 2) i ^= 3;
                    tm = &tm_wo; c0 = (i >> 1) * 64; c1 = (4 * j + ((i & 1) ? 1 + c : 3 * c)) * DH;
                }
                const uint32_t fb = e == E0 ? bar_w0 : bar_full + 8 * (e & 3), d = sb + (e == E0 ? 6 : e & 3) * SLOT;
                if (e >= 24 && e < 152) mbar_wait_sleep(bar_empty + 8 * (e & 3), ~(e >> 2) & 1);
                else if (e != E0) mbar_wait(bar_empty + 8 * (e & 3), ~(e >> 2) & 1);
                if (elect()) {
                    mbar_expect_tx(fb, SLOT);
                    tma2d_mc(d + c * UNIT, tm, c0, c1, fb, pol);
                    const int i = e - PF_KV;
                    if (i >= 0 && i < 128 && !(i & 32))
                        l2_prefetch(((i & 1) ? args.vc : args.kc) + (size_t)((2 * j + (i >> 6)) * S_ + (i & 30) * 64) * DH + qb * 1024, 2048);
                    if (e >= PF_WO && e < PF_WO + 18) l2_prefetch(args.wo + (size_t)blockIdx.x * (QD * D_ / NCTA) + (e - PF_WO) * 1024, 2048);
                    if (e == (marks & 255)) mbar_arrive(go);
                }
                if (e == (marks & 255)) { go += 8; marks >>= 8; }
            }
            asm volatile("fence.proxy.async.global;" ::: "memory");
            mbar_wait(bar_empty, 1);
            if (elect()) {
                mbar_expect_tx(bar_full, 16 * XP);
                tma2d(sb, &tm_x, 0, rg * 16, bar_full);
            }
            mbar_wait(bar_empty + 16, 1);
            if (C3D) __nanosleep(C3D);
            if (elect()) {
                mbar_expect_tx(bar_full + 16, SLOT);
                tma3d(sb + 2 * SLOT, &tm_p, 0, j * 20 + 12, qb * 8, bar_full + 16);
                tma3d(sb + 2 * SLOT + UNIT, &tm_p, 0, j * 20 + 14, qb * 8, bar_full + 16);
            }
            mbar_wait(bar_empty + 24, 1);
            if (C4D) __nanosleep(C4D);
            if (elect()) {
                mbar_expect_tx(bar_full + 24, UNIT);
                tma3d(sb + 3 * SLOT, &tm_p, 0, j * 20 + 16, qb * 8, bar_full + 24);
            }
            mbar_wait(bar_empty + 8, 0);
            mbar_wait(bar_empty + 16, 0);
            if (DD) __nanosleep(DD);
            if (elect()) {
#pragma unroll
                for (int i = 1; i < 3; i++) {
                    mbar_expect_tx(bar_full + 8 * i, 18 * XP);
                    tma2d(sb + i * SLOT, &tm_d, 0, blockIdx.x * 36 + (i - 1) * 18, bar_full + 8 * i);
                }
            }
        } else {
            if (lane < 3) asm volatile("prefetch.tensormap [%0];" ::"l"(lane == 0 ? &tm_k : lane == 1 ? &tm_v : &tm_wo) : "memory");
            if (SPARE && HSENT) {
                mbar_wait_sleep(bar_pub, 0);
                if (lane == 0) flag_release(padd(g_flag_h, rg * 128), tag);
                __syncwarp();
            }
            bar_sync(1, 192);
#pragma unroll 1
            for (uint32_t e = 20; e < 148; e++) {
                mbar_wait_sleep(bar_full + 8 * (e & 3), (e >> 2) & 1);
                if (e & 1) bar_sync(1, 192);
                if (!(e & 1) || e == 147) bar_sync(4, 160);
            }
            mbar_wait_sleep(bar_go + 8, 0);
            mbar_wait(bar_mod, 0);
#pragma unroll 1
            for (int i = 1; i < 4; i++) {
                mbar_wait(bar_pub + 8 * i, 0);
                unsigned int* flags = padd(g_flag_part, (qb * 32 + i * 8 - 8) * 4);
                if (elect()) { flag_release(padd(flags, j * 4), tag); DBG_PG(93); }
                __syncwarp();
                const uint32_t slot = i < 3 ? i + 1 : 1;
                flag_wait(padd(flags, (lane & 7) * 4), tag);
                asm volatile("fence.proxy.async.global;" ::: "memory");
                if (lane == 0 && i == 3) DBG_PG(101);
                mbar_wait(bar_go + 8 + 8 * i, 0);
                mbar_wait(bar_empty + 8 * slot, i != 1);
                if (elect()) {
                    mbar_expect_tx(bar_full + 8 * slot, SLOT);
                    tma3d(sb + slot * SLOT, &tm_p, 0, j * 20 + (i - 1) * 4, qb * 8, bar_full + 8 * slot);
                    tma3d(sb + slot * SLOT + UNIT, &tm_p, 0, j * 20 + (i - 1) * 4 + 2, qb * 8, bar_full + 8 * slot);
                }
            }
        }
        __syncwarp();
        mbar_wait_sleep(bar_out, 0);
        if (elect()) {
            asm volatile("fence.proxy.async.shared::cta;" ::: "memory");
            const int2 sel = reinterpret_cast<const int2*>(smem_raw + SM_RED)[8];
#pragma unroll 1
            for (int i = warp; i < 16; i += 4) {
                const int row = rg * 16 + i;
                if (row != sel.x && row != sel.y)
                    asm volatile("cp.async.bulk.global.shared::cta.bulk_group [%0], [%1], %2;"
                                 ::"l"(args.out + (size_t)row * D_), "r"(sb + i * XP), "n"(D_ * 2) : "memory");
            }
            asm volatile("cp.async.bulk.commit_group;\ncp.async.bulk.wait_group 0;" ::: "memory");
        }
    } else {
        uint32_t cv[5] = {0, 0, 0, 0, 0}, tag0 = 0;
        if (blockIdx.x < 72) {
            uint32_t ws;
            int tid;
            asm volatile("mov.u32 %0, smem_raw;\nmov.u32 %1, %%tid.x;" : "=r"(ws), "=r"(tid));
            tid -= 128;
            ws += SM_Q + SLOT + tid * 16;
            const bf16* wrow = args.w_mod + (size_t)(tid >> 1) * (6 * D_) + (tid & 1) * 8 + blockIdx.x * 16;
#pragma unroll
            for (int i = 0; i < 5; i++)
                if (i < 4 || tid < 128) {
                    asm volatile("cp.async.cg.shared.global [%0], [%1], 16;" ::"r"(ws + i * 4096), "l"(wrow + (size_t)i * 128 * (6 * D_)) : "memory");
                    cv[i] = reinterpret_cast<const unsigned short*>(args.cvec)[(tid >> 1) + i * 128];
                }
            tag0 = load_tag(gs) - 1;
        }
        asm volatile("barrier.cluster.arrive.relaxed.aligned;" ::: "memory");
        asm volatile("setmaxnreg.inc.sync.aligned.u32 240;");
        const int lane = threadIdx.x & 31;
        const int cw = warp - 4;
        const int w = cw >> 2;
        const int tid = threadIdx.x - 128;
        float* red = reinterpret_cast<float*>(smem_raw + SM_RED);
        DBG_INIT();
        DBG_G(120);
        DBG_T(100);

        uint32_t tag;
        {

            if (blockIdx.x < 72) {
                const uint32_t ws = sb + SM_Q + SLOT + tid * 16;
                float sc[5], a[8];
#pragma unroll
                for (int i = 0; i < 5; i++) sc[i] = __uint_as_float(cv[i] << 16);
#pragma unroll
                for (int i = 0; i < 5; i++) sc[i] = rbf(sc[i] * sigmoidf_(sc[i]));
#pragma unroll
                for (int i = 0; i < 8; i++) a[i] = 0.f;
                anchor(bar_full + 504, sc[0] + sc[1] + sc[2] + sc[3] + sc[4] + 2.f);
                asm volatile("cp.async.wait_all;" ::: "memory");
#pragma unroll
                for (int i = 0; i < 5; i++) mod_fma(a, lds128(ws + (i < 4 || tid < 128 ? i * 4096 : 0)), sc[i]);
                const float v = mod_reduce(a, lane);
                if (lane < 16) red[cw * 16 + lane] = v;

                bar_sync(3, 256);
                if (tid < 8 * MREP) {
                    float v0 = 0.f, v1 = 0.f;
#pragma unroll
                    for (int i = 0; i < 8; i++) { v0 += red[i * 16 + (tid & 7)]; v1 += red[i * 16 + 8 + (tid & 7)]; }
                    st_relaxed64(&gs->mod1[(tid >> 3) * D_ + blockIdx.x * 8 + (tid & 1) * 4 + (tid & 2) + ((tid >> 2) & 1)], pack_bf16(v0, v1), tag0 + 1);
                }
            }
            DBG_G(106);
            asm volatile("barrier.cluster.wait.aligned;" ::: "memory");
            mbar_wait(bar_x, 0);
            tag = load_tag(gs);
            uint32_t x[20];
            float st[12];
            rows_load(x, sb + SM_Q + (lane & 15) * XP + (lane >> 4) * 16 + cw * 32, cw);
#pragma unroll
            for (int i = 0; i < 12; i++) st[i] = 0.f;
#pragma unroll
            for (int k = 0; k < 9; k++) stats_add(st, x[2 * k], x[2 * k + 1], 0x3f803f80u);
            uint32_t mean2;
            float dot;
            const float rsd = rows_stats(st, reinterpret_cast<float4*>(red + 128), cw, lane, mean2, dot);
            rows_normalise(x, x, mean2, rsd, lane);
            fence_regs(x);
            uint4* smod = reinterpret_cast<uint4*>(smem_raw + SM_Q + M_MOD);
            if (tid < D_ / 4) {
                const uint4* mp = reinterpret_cast<const uint4*>(gs->mod1 + ((blockIdx.x >> 1) & (MREP - 1)) * D_) + tid;
                poll2x2(mp, mp + D_ / 4, tag, smod[tid], smod[D_ / 4 + tid]);
            }
            bar_sync(3, 256);
            DBG_G(107);
            const uint2* mp = reinterpret_cast<const uint2*>(smod) + cw * 8 + (lane & 3);
#pragma unroll
            for (int k = 0; k < 9; k++) {
                const uint32_t c1 = badd2(pair_of(mp + D_ / 2, k, cw), 0x3f803f80u), sa = pair_of(mp, k, cw);
                x[2 * k] = badd2(bmul2(x[2 * k], c1), sa);
                if (x[2 * k] == 0) x[2 * k] = 0x8000u;
                x[2 * k + 1] = badd2(bmul2(x[2 * k + 1], c1), sa);
            }
            uint4* hdst = g_h + (size_t)(rg * 36 + cw) * 32 + lane;
#pragma unroll
            for (int ch = 0; ch < 4; ch++) st_relaxed(hdst + ch * 256, x[4 * ch], x[4 * ch + 1], x[4 * ch + 2], x[4 * ch + 3]);
            st_relaxed64(reinterpret_cast<uint2*>(g_h + (size_t)(rg * 36 + 32) * 32) + tid, x[16], x[17]);
            __syncwarp();
            if (SPARE && lane == 0) mbar_arrive(bar_pub);
            DBG_G(108);
        }

        uint32_t rel_base;
        asm("mapa.shared::cluster.u32 %0, %1, %2;" : "=r"(rel_base) : "r"(bar_empty), "r"(lane & 1));
        auto release = [&](uint32_t slot) { if (lane < 2) mbar_arrive_cluster(rel_base + 8 * slot); };
        uint32_t q[32], p[32];
        float s[64], o[64];

        uint4* qpark = reinterpret_cast<uint4*>(smem_raw + SM_Q - SLOT) + cw * 256 + lane;
        {
            uint32_t h[144];
            const uint4* hf = g_h + (size_t)(qb * 8 + cw) * (36 * 32) + lane;
            auto load_h = [&](auto lo, auto hi) {
#pragma unroll
                for (int ks = lo.value; ks < hi.value; ks++) {
                    const uint4 v = h_frag(hf, ks, lane);
                    h[4 * ks] = v.x; h[4 * ks + 1] = v.y; h[4 * ks + 2] = v.z; h[4 * ks + 3] = v.w;
                }
            };
            auto check_h = [&](auto lo, auto hi) {
                uint32_t it = 0;
#pragma unroll 1
                while (true) {
                    uint32_t mn = ~0u;
#pragma unroll
                    for (int ks = lo.value; ks < hi.value; ks++) mn = __vimin3_u32(mn, h[4 * ks], h[4 * ks + 2]);
                    if (!__any_sync(0xffffffffu, mn == 0) || ++it >= SPIN / 16) break;
                    load_h(lo, hi);
                }
            };
            if (!HSENT) flag_wait(&g_flag_h[(qb * 8 + cw) * 32], tag);
            if (HSENT) __nanosleep(HDELAY);
            load_h(IC<0>{}, IC<4>{});
            DBG_T(104); DBG_G(109);
#pragma unroll
            for (int i = 0; i < 64; i++) o[i] = 0.f;
            uint32_t e = E0;
#pragma unroll 1
            for (int hd = 1;; hd++) {
                fence_regs(o);
                auto group = [&](auto tc) {
                    constexpr int t = tc.value, k0 = t ? 8 * t - 4 : 0;
                    const bool first = t == 0 && hd == 1;
                    mbar_wait(first ? bar_w0 : bar_full + 8 * (e & 3), (e >> 2) & 1);
                    const uint32_t dv = desc_lo(t ? 0 : 8192, UNIT) + (first ? 6 : e & 3) * (SLOT / 16);
                    if (HSENT && hd == 1) check_h(IC<k0>{}, IC<8 * t + 4>{});
                    WG_FENCE();
#pragma unroll
                    for (int ks = k0; ks < 8 * t + 4; ks++)
                        mma_rs128<1>(o, h[4 * ks], h[4 * ks + 1], h[4 * ks + 2], h[4 * ks + 3], desc_of(dv + (ks - k0) * 128), ks);
                    WG_COMMIT();
                    if (hd == 1) { if (t == 0) {   } if (t == 1) {   } if (t == 2) {   } if (t == 3) {   } if (t == 4) {   } }
                    if (t < 4 && hd == 1) load_h(IC<8 * t + 4>{}, IC<t < 4 ? 8 * t + 12 : 0>{});
                    if (t > 0) { WG_WAIT(1); if (t > 1 || hd > 1) release((e - 1) & 3); }
                    e++;
                };
                group(IC<0>{}); group(IC<1>{}); group(IC<2>{}); group(IC<3>{});
                if (e == 19) break;
                group(IC<4>{});
                WG_WAIT(0);
                if (hd == 1) {     }
                fence_regs(o);
                release((e - 1) & 3);
#pragma unroll
                for (int i = 0; i < 8; i++)
                    qpark[hd * 2048 + i * 32] = make_uint4(pack_bf16(o[8 * i], o[8 * i + 1]), pack_bf16(o[8 * i + 2], o[8 * i + 3]),
                                                           pack_bf16(o[8 * i + 4], o[8 * i + 5]), pack_bf16(o[8 * i + 6], o[8 * i + 7]));
                if (SPARE && hd == 2) {
                    float (&u)[32] = reinterpret_cast<float (&)[32]>(o);
                    fence_regs(u);
#pragma unroll
                    for (int t = 0; t < 3; t++) {
                        mbar_wait(bar_full + 8 * t, 1);
                        WG_FENCE();
#pragma unroll
                        for (int ks = 0; ks < (t < 2 ? 16 : 4); ks++)
                            mma_rs64<1>(u, h[64 * t + 4 * ks], h[64 * t + 4 * ks + 1], h[64 * t + 4 * ks + 2], h[64 * t + 4 * ks + 3],
                                        desc_of(desc_lo(t * SLOT, UNIT) + ks * 128), ks | t);
                        WG_COMMIT();
                        if (t > 0) { WG_WAIT(1); release(t - 1); }
                    }
                    WG_WAIT(0);
                    fence_regs(u);
                    release(2);
                    e = 15;
#pragma unroll
                    for (int i = 0; i < 4; i++)
                        qpark[3 * 2048 + i * 32] = make_uint4(pack_bf16(u[8 * i], u[8 * i + 1]), pack_bf16(u[8 * i + 2], u[8 * i + 3]),
                                                              pack_bf16(u[8 * i + 4], u[8 * i + 5]), pack_bf16(u[8 * i + 6], u[8 * i + 7]));
                }
            }
#pragma unroll
            for (int i = 0; i < 8; i++) {
                const uint4 v = qpark[2048 + i * 32];
                q[4 * i] = v.x; q[4 * i + 1] = v.y; q[4 * i + 2] = v.z; q[4 * i + 3] = v.w;
            }
#pragma unroll
            for (int i = 0; i < 32; i++) p[i] = h[112 + i];
            mbar_wait(bar_full + 24, 0);
            WG_WAIT(0);
            fence_regs(o);
            release(2);
        }
        DBG_T(105);
        DBG_G(125);

        uint8_t* frag = reinterpret_cast<uint8_t*>(__shfl_sync(0xffffffffu, reinterpret_cast<unsigned long long>(g_frag + (size_t)(rg * 8 + cw) * WREG + lane * 16), lane));
        const uint4* qnext = reinterpret_cast<const uint4*>(__shfl_sync(0xffffffffu, reinterpret_cast<unsigned long long>(padd(smem_raw, SM_Q + tid * 16 + cw * 3584)), lane));
        uint8_t* odst = reinterpret_cast<uint8_t*>(const_cast<uint4*>(qnext));
        float m0 = 0.f, m1 = 0.f, l0 = 0.f, l1 = 0.f, t0 = 1.f, t1 = 1.f;
        uint32_t bad = 0;
        const int lw = cw & 3;
        const uint32_t relw = lw == RW && lane < 8, handw = lw == HW || cw == HW2;
        auto release4 = [&](uint32_t off) {
            asm volatile("{\n.reg .pred p;\nsetp.ne.b32 p, %1, 0;\n@p mbarrier.arrive.shared::cluster.b64 _, [%0];\n}" ::"r"(rel_base + off), "r"(relw) : "memory"); };
        auto handoff = [&]() {
            asm volatile("{\n.reg .pred p;\nsetp.ne.b32 p, %1, 0;\n@p bar.arrive %0, 192;\n}" ::"r"(2 - w), "r"(handw) : "memory"); };
        if (cw == 4 + HW) bar_arrive(1, 192);
        auto finish = [&](auto lo, auto hi, uint32_t bit, auto sink) {
#pragma unroll
            for (int i = lo.value; i < hi.value; i++) {
                const uint32_t v0 = pack_bf16(o[8 * i] * t0, o[8 * i + 1] * t0), v1 = pack_bf16(o[8 * i + 2] * t1, o[8 * i + 3] * t1);
                const uint32_t v2 = pack_bf16(o[8 * i + 4] * t0, o[8 * i + 5] * t0), v3 = pack_bf16(o[8 * i + 6] * t1, o[8 * i + 7] * t1);
                if (i == 0 && fabsf(o[0] * t0) >= 0x1p-31f) bad |= bit << 8;
                sink(i, v0, v1, v2, v3);
            }
        };
        auto row_sums = [&](uint32_t bit) {
            t0 = quad_sum(l0); t1 = quad_sum(l1);
            if (!(t0 >= LMIN && t0 < LMAX && t1 >= LMIN && t1 < LMAX)) bad |= bit;
            t0 = rcp_fast(t0); t1 = rcp_fast(t1);
            l0 = 0.f; l1 = 0.f;
        };
        auto issue_pv = [&](uint32_t dlo, int acc, auto lo, auto hi) {
            if (lo.value == 0) asm volatile("{\n.reg .pred p;\nsetp.eq.b32 p, %0, 0;\n@p bar.sync 4, 160;\n}" ::"r"(w) : "memory");
#pragma unroll
            for (int ks = lo.value; ks < hi.value; ks++)
                mma_rs128<1>(o, p[4 * ks], p[4 * ks + 1], p[4 * ks + 2], p[4 * ks + 3], desc_of(dlo + ks * 128), ks ? 1 : acc);
            WG_COMMIT();
        };
#pragma unroll
        for (int i = 0; i < 64; i++) s[i] = 0.f;
        uint32_t dv_lo = desc_lo(0, UNIT), voff = 0;
        auto issue_qk = [&]() {
            const uint32_t dk = dv_lo ^ (desc_lo(0, UNIT) ^ desc_lo(3 * SLOT, 16));
            bar_sync(1 + w, 192);
            fence_regs(s); fence_regs(q); fence_regs(o); fence_regs(p);
            WG_FENCE();
#pragma unroll
            for (int ks = 0; ks < 8; ks++)
                mma_rs128<0>(s, q[4 * ks], q[4 * ks + 1], q[4 * ks + 2], q[4 * ks + 3], desc_of(dk + (ks >> 2) * 1024 + (ks & 3) * 2), ks != 0);
            WG_COMMIT();
        };
        auto to_frag = [&](int i, uint32_t v0, uint32_t v1, uint32_t v2, uint32_t v3) {
            *reinterpret_cast<uint4*>(odst + i * 512) = make_uint4(v0, v1, v2, v3); };
        int n = 0;
#pragma unroll 1
        for (;;) {
            issue_qk();
            const int jn = n & 15;
            if (jn == 1) {
                finish(IC<ESPLIT>{}, IC<8>{}, 1u << (n >> 4), to_frag);
                WG_FENCE();
                issue_pv(dv_lo, 0, IC<0>{}, IC<PV1>{});
            } else {
                if (jn == 0 && n > 0) {
                    row_sums(1u << (n >> 4));
                    qnext = n == 48 ? reinterpret_cast<const uint4*>(frag) : qnext + 2048;
                    odst = frag + ((n >> 4) - 1) * 4096;
                    if (elect()) mbar_arrive(bar_qfree + (n >> 1) - 8);
                }
                issue_pv(dv_lo, 1, IC<0>{}, IC<PV1>{});
            }
            if (SPARE && n == 47) mbar_wait(bar_q3, 0);
            WG_WAIT(1);
            fence_regs(s); fence_regs(q);
            if (jn == 15) {
#pragma unroll
                for (int i = 0; i < 8; i++) {
                    const uint4 v = qnext[i * 32];
                    q[4 * i] = v.x; q[4 * i + 1] = v.y; q[4 * i + 2] = v.z; q[4 * i + 3] = v.w;
                }
            }
            if (jn == 0) {
                float a0 = fmaxf(s[0], s[1]), a1 = fmaxf(s[2], s[3]), a2 = fmaxf(s[4], s[5]), a3 = fmaxf(s[6], s[7]);
#pragma unroll
                for (int i = 1; i < MAXG; i++) {
                    a0 = fmaxf(a0, fmaxf(s[8 * i], s[8 * i + 1])); a1 = fmaxf(a1, fmaxf(s[8 * i + 2], s[8 * i + 3]));
                    a2 = fmaxf(a2, fmaxf(s[8 * i + 4], s[8 * i + 5])); a3 = fmaxf(a3, fmaxf(s[8 * i + 6], s[8 * i + 7]));
                }
                const uint32_t a = pack_bf16(fmaxf(a0, a2), fmaxf(a1, a3));
                const uint32_t b = bmax2(bmax2(a, __shfl_xor_sync(0xffffffffu, a, 1)), bmax2(__shfl_xor_sync(0xffffffffu, a, 2), __shfl_xor_sync(0xffffffffu, a, 3)));
                m0 = fmaf(-CS, bf_lo(b), -POFF); m1 = fmaf(-CS, bf_hi(b), -POFF);
            }
            if (PV1 < 8) issue_pv(dv_lo, 1, IC<PV1>{}, IC<8>{});
            release4(voff ^ 24);
            handoff();
#pragma unroll 1
            do {
                DBG_T(n);
#pragma unroll
                for (int i = 0; i < 4 * STAGE; i++) s[i] = fmaf(s[i], CS, (i & 2) ? m1 : m0);
#pragma unroll
                for (int i = 0; i < 4 * SPLIT; i++) s[i] = ex2(s[i]);
#pragma unroll
                for (int i = 0; i < SPLIT; i++) { l0 += s[4 * i] + s[4 * i + 1]; l1 += s[4 * i + 2] + s[4 * i + 3]; }
                if (STAGE < 16) {
                    m0 = fmaf(l0, 0.f, m0); m1 = fmaf(l1, 0.f, m1);
                }
                anchor(bar_full + 504, l0 + l1);
                WG_WAIT(0);
                fence_regs(o); fence_regs(p);
                release4(voff);
                dv_lo ^= 2 * SLOT / 16;
                voff ^= 16;
                n++;
#pragma unroll
                for (int i = 4 * STAGE; i < 64; i++) s[i] = fmaf(s[i], CS, (i & 2) ? m1 : m0);
#pragma unroll
                for (int i = 4 * SPLIT; i < 64; i++) s[i] = ex2(s[i]);
#pragma unroll
                for (int i = SPLIT; i < 16; i++) { l0 += s[4 * i] + s[4 * i + 1]; l1 += s[4 * i + 2] + s[4 * i + 3]; }
#pragma unroll
                for (int i = 0; i < 32; i++) p[i] = pack_bf16(s[2 * i], s[2 * i + 1]);
                if (((n + 1) & 15) < 3) break;
                issue_qk();
                issue_pv(dv_lo, 1, IC<0>{}, IC<8>{});
                WG_WAIT(1);
                fence_regs(s); fence_regs(q);
                release4(voff ^ 24);
                handoff();
            } while (n != 99);
            WG_WAIT(0);
            fence_regs(o); fence_regs(p);
            if ((n & 15) == 1) finish(IC<0>{}, IC<ESPLIT>{}, 1u << (n >> 4), to_frag);
            if (n == 64) break;
        }
        DBG_T(64);
        uint32_t a1[32], a2[32];
        bar_sync(1 + w, 192);
        fence_regs(o); fence_regs(p);
        WG_FENCE();
        issue_pv(desc_lo(3 * SLOT, UNIT), 1, IC<0>{}, IC<8>{});
        if (w == 0) handoff();
        row_sums(16);
        mbar_wait(bar_mod, 0);
        WG_WAIT(0);
        fence_regs(o); fence_regs(p);
        release(3);
        finish(IC<0>{}, IC<8>{}, 16, [&](int i, uint32_t v0, uint32_t v1, uint32_t v2, uint32_t v3) {
            p[4 * i] = v0; p[4 * i + 1] = v1; p[4 * i + 2] = v2; p[4 * i + 3] = v3; });
        bad = __reduce_or_sync(0xffffffffu, bad);
        bad = ((bad | ~(bad >> 8)) >> 1) & 15;
        if (__builtin_expect(bad != 0, 0)) {
            uint8_t* keep = g_keep + (size_t)(rg * 8 + cw) * 4096 + lane * 16;
            frag_store(keep, p);
            attn_fallback(bad, tag, frag, keep, args.wq, args.kc, args.vc);
            frag_load(q, frag); frag_load(p, keep);
        }
        DBG_T(80);
        DBG_G(124);

        const uint32_t eye = (lane >> 3) == (lane & 3) ? 0x3f80u << ((lane & 4) * 4) : 0;
        auto sum8 = [&](uint32_t* r, const uint4 (&v)[8]) {
            float d[16];
#pragma unroll
            for (int i = 0; i < 16; i++) d[i] = 0.f;
#pragma unroll
            for (int src = 0; src < 8; src++) {
                mma1688(d + 8 * (src & 1), v[src].x, v[src].y, eye);
                mma1688(d + 8 * (src & 1) + 4, v[src].z, v[src].w, eye);
            }
#pragma unroll
            for (int i = 0; i < 4; i++) r[i] = pack_bf16(d[2 * i] + d[8 + 2 * i], d[2 * i + 1] + d[9 + 2 * i]);
        };
        auto sum8_slot = [&](uint32_t* r, uint32_t e) {
            mbar_wait(bar_full + 8 * (e & 3), (e >> 2) & 1);
            uint4 v[8];
#pragma unroll
            for (int src = 0; src < 8; src++) v[src] = lds128(sb + (e & 3) * SLOT + w * (UNIT - 2048) + src * 2048 + tid * 16);
            sum8(r, v);
        };
        uint4 v2[8], v3[8], wf[27];
        uint2 u4[8], gw[9];
        uint32_t x1[20], xs, pa, ta;
        const uint8_t *mb, *mb4;
        int tid_;
        auto load_wf = [&](auto lo, auto hi) {
            const uint32_t wa = sb + SM_Q + ((cw & 1) * D_ + (cw >> 1) * 32 + (tid_ & 7) + (tid_ & 16) / 2) * 80 + (tid_ & 8) * 2;
#pragma unroll
            for (int i = lo.value; i < hi.value; i++)
                wf[i] = ldsm4t((i < 24 ? wa + ((i / 3 & 3) * 8 + i / 12) * 1280 : wa + (32 - (cw >> 1)) * 1280) + (i % 3) * 32);
        };
        uint32_t at[18];
        {
            float ua[32], ub[32];
            uint32_t e = 148, prev = 4;
            auto step = [&](float (&u)[32], const uint32_t (&a)[32], const uint32_t (&b)[32], int acc) {
                mbar_wait(bar_full + 8 * (e & 3), (e >> 2) & 1);
                const uint64_t dv = mkdesc(sb + (e & 3) * SLOT, UNIT, 1024);
                if (!acc) fence_regs(u);
                WG_FENCE();
#pragma unroll
                for (int ks = 0; ks < 8; ks++) mma_rs64<1>(u, a[4 * ks], a[4 * ks + 1], a[4 * ks + 2], a[4 * ks + 3], dv + ks * 128, ks | acc);
#pragma unroll
                for (int ks = 0; ks < 8; ks++) mma_rs64<1>(u, b[4 * ks], b[4 * ks + 1], b[4 * ks + 2], b[4 * ks + 3], dv + 1024 + ks * 128, 1);
                WG_COMMIT();
                WG_WAIT(1);
                if (prev < 4) release(prev);
                prev = e & 3;
                e++;
            };
            auto store = [&](float (&u)[32], uint8_t* dst) {
                fence_regs(u);
#pragma unroll
                for (int i = 0; i < 4; i++)
                    st_relaxed4(dst + i * 512, pack_bf16(u[8 * i], u[8 * i + 1]), pack_bf16(u[8 * i + 2], u[8 * i + 3]),
                                pack_bf16(u[8 * i + 4], u[8 * i + 5]), pack_bf16(u[8 * i + 6], u[8 * i + 7]));
            };
#pragma unroll
            for (int i = 0; i < 8; i++) at[i] = 0;
#pragma unroll
            for (int i = 0; i < 32; i++) { ua[i] = 0.f; ub[i] = 0.f; }
            fence_regs(q); fence_regs(p);
            step(ua, q, p, 0);
            frag_load(a1, frag + 4096);
            mbar_wait(bar_full + 8, 1);
            frag_load(a2, frag + 8192);
            step(ub, q, p, 0);
            WG_WAIT(0);
            release(1);
            prev = 4;
            fence_regs(a1); fence_regs(a2); fence_regs(ua); fence_regs(ub);
#pragma unroll 1
            for (int ch = 0; ch < 4; ch++) {
                step(ua, a1, a2, 1);
                if (ch > 0) {
                    if (ch >= 2) {
#pragma unroll
                        for (int i = 0; i < 4; i++) at[i] = at[4 + i];
                        sum8_slot(at + 4, e);
                        __syncwarp();
                        release(e & 3);
                        e++;
                        WG_WAIT(0);
                        release(prev);
                        prev = 4;
                    }
                    step(ub, q, p, 0);
                } else {
                    WG_WAIT(0);
                }
                store(ua, frag + ch * 4096);
                step(ub, a1, a2, 1);
                step(ua, q, p, 0);
                store(ub, frag + ch * 4096 + 2048);
                __syncwarp();
                if (lane == 0 && ch < 3) mbar_arrive(bar_pub + 8 + 8 * ch);
            }
            tid_ = __shfl_sync(0xffffffffu, tid, lane);
            mb = padd(g_frag, (qb * 64 + j) * WREG + 3 * 4096 + tid * 16);
            mb4 = padd(mb, 4096 + ((cw >> 1) - cw) * 512 + (cw & 1) * 8);
            step(ua, a1, a2, 1);
            xs = sb + (tid_ & 15) * XP + (tid_ & 16) + cw * 32;
            pa = sb + w * (UNIT - 2048) + tid_ * 16;
            ta = sb + (cw * 8 + (tid_ & 3)) * 8;
#pragma unroll
            for (int k = 0; k < 9; k++) {
                gw[k] = lds64(ta + SM_T + (k < 8 ? (k >> 1) * 64 + (k & 1) * 4 : 256 - cw * 4) * 8);
                if (!(tid_ & 4)) gw[k].y = 0x3f803f80u;
            }
            mbar_wait(bar_g, 0);
            load_wf(IC<0>{}, IC<WF0>{});
            mbar_wait(bar_full, 0);
            rows_load(x1, xs, cw);
            if (P2E) {
                mbar_wait(bar_full + 8, 0);
#pragma unroll
                for (int src = 0; src < 8; src++) v2[src] = lds128(pa + SLOT + src * 2048);
            }
            WG_WAIT(0);
            release(3);
            store(ua, frag + 4 * 4096);
        }
        DBG_T(81);
        DBG_G(122);

        {
        const int tid = tid_, lane = tid & 31;
        const int g8 = lane >> 2, qd = lane & 3, l16 = lane & 15;
        uint32_t h2[18], k1, k2;
        float4* rec = reinterpret_cast<float4*>(red + 128);
        const uint2* candp = reinterpret_cast<const uint2*>(padd(g_cand, ((blockIdx.x & (CREP - 1)) * NCTA + (tid >> 1)) * 32 + (tid & 1) * 8));
        uint2 cd;
        auto stage_out = [&]() {
#pragma unroll
            for (int k = 0; k < 9; k++) {
                const uint32_t gb = lds32(sb + SM_TG + (cw * 8 + qd + (k < 8 ? (k >> 1) * 64 + (k & 1) * 4 : 256 - cw * 4)) * 4);
                x1[2 * k] = badd2(x1[2 * k], bmul2(gb, h2[2 * k]));
                x1[2 * k + 1] = badd2(x1[2 * k + 1], bmul2(gb, h2[2 * k + 1]));
            }
#pragma unroll
            for (int ch = 0; ch < 4; ch++) stsm_x4(xs + ch * 256, x1[4 * ch], x1[4 * ch + 1], x1[4 * ch + 2], x1[4 * ch + 3]);
            asm volatile("stmatrix.sync.aligned.m8n8.x2.shared.b16 [%0], {%1, %2};" ::"r"(xs + 1024 - cw * 16), "r"(x1[16]), "r"(x1[17]) : "memory");
        };
        {
            uint32_t it = 0, miss;
            if (!P2E) {
                mbar_wait(bar_full + 8, 0);
#pragma unroll
                for (int src = 0; src < 8; src++) v2[src] = lds128(pa + SLOT + src * 2048);
            }
            sum8(at + 8, v2);
            float st[12];
#pragma unroll
            for (int i = 0; i < 12; i++) st[i] = 0.f;
            auto add_pair = [&](int k) {
                x1[2 * k] = badd2(x1[2 * k], bmul2(gw[k].x, at[2 * k]));
                x1[2 * k + 1] = badd2(x1[2 * k + 1], bmul2(gw[k].x, at[2 * k + 1]));
                stats_add(st, x1[2 * k], x1[2 * k + 1], gw[k].y);
            };
#pragma unroll
            for (int k = 0; k < 6; k++) add_pair(k);
            mbar_wait(bar_full + 16, 0);
#pragma unroll
            for (int src = 0; src < 8; src++) v3[src] = lds128(pa + 2 * SLOT + src * 2048);
#pragma unroll 1
            do {
                if (BO && it) __nanosleep(BO);
                miss = 0;
#pragma unroll
                for (int src = 0; src < 8; src++) reload16(v3[src], mb + (size_t)src * 8 * WREG, miss);
            } while (__any_sync(0xffffffffu, miss) && ++it < SPIN / 16);
            if (lane < 4) mbar_arrive_cluster(rel_base + 8 * (1 + (lane >> 1)));
            sum8(at + 12, v3);
            add_pair(6); add_pair(7);
            load_wf(IC<WF0>{}, IC<WF1>{});
            uint2 cs[9];
#pragma unroll
            for (int k = 0; k < 9; k++) cs[k] = lds64(ta + SM_TC + (k < 8 ? (k >> 1) * 64 + (k & 1) * 4 : 256 - cw * 4) * 8);
            mbar_wait(bar_pre, 0);
            mbar_wait(bar_full + 24, 0);
#pragma unroll
            for (int src = 0; src < 8; src++) u4[src] = lds64(sb + 3 * SLOT + src * 2048 + (cw >> 1) * 512 + lane * 16 + (cw & 1) * 8);
#pragma unroll 1
            do {
                if (BO && miss) __nanosleep(BO);
                miss = 0;
#pragma unroll
                for (int src = 0; src < 8; src++) reload8(u4[src], mb4 + (size_t)src * 8 * WREG, miss);
            } while (__any_sync(0xffffffffu, miss) && ++it < SPIN / 16);
            float d[8] = {0.f, 0.f, 0.f, 0.f, 0.f, 0.f, 0.f, 0.f};
#pragma unroll
            for (int i = 0; i < 4; i++) mma16816(d + 4 * (i & 1), u4[2 * i].x, u4[2 * i].y, u4[2 * i + 1].x, u4[2 * i + 1].y, eye, eye);
            at[16] = pack_bf16(d[0] + d[4], d[1] + d[5]); at[17] = pack_bf16(d[2] + d[6], d[3] + d[7]);
            add_pair(8);
            DBG_G(123);
            const float2 ws = *reinterpret_cast<const float2*>(smem_raw + SM_TS);
            uint4* cdst = padd(g_cand, ((tid & (CREP - 1)) * NCTA + rg) * 32);
            uint32_t mean2;
            float dot;
            const float rsd = rows_stats(st, rec, cw, lane, mean2, dot);
            const uint32_t b = __float_as_uint(fmaf(fmaf(-bf_lo(mean2), ws.x, dot), rsd, ws.y));
            const uint32_t key = (((b & 0x80000000u) ? ~b : (b | 0x80000000u)) | 2047u) - (rg * 16 + l16);
            top2(key, k1, k2);
            if (tid < CREP) st_relaxed(cdst, k1, tag, k2, tag);
            cd = ld_relaxed64(candp);
            rows_normalise(h2, x1, mean2, rsd, lane);
#pragma unroll
            for (int k = 0; k < 18; k++) h2[k] = badd2(bmul2(h2[k], cs[k >> 1].x), cs[k >> 1].y);
            const uint32_t r1 = ~k1 & 15, r2 = ~k2 & 15;
            uint32_t todo = ((r1 & 7) == g8) | ((r2 & 7) == g8) << 1;
#pragma unroll 1
            while (todo) {
                const bool second = !(todo & 1), hi = (second ? r2 : r1) & 8;
                uint4* dst = padd(g_rows, ((rg * 2 + second) * RSLOT + cw * 16 + qd) * 16);
                uint32_t r[18];
#pragma unroll
                for (int k = 0; k < 9; k++) { r[k] = hi ? h2[2 * k + 1] : h2[2 * k]; r[9 + k] = hi ? x1[2 * k + 1] : x1[2 * k]; }
                fence_regs(r);
                st_relaxed(dst, r[0], r[1], r[2], r[3]);
                st_relaxed(dst + 4, r[4], r[5], r[6], r[7]);
                st_relaxed64(reinterpret_cast<uint2*>(padd(dst, 2048 - cw * 224 - qd * 8)), r[8], r[17]);
                st_relaxed(dst + 8, r[9], r[10], r[11], r[12]);
                st_relaxed(dst + 12, r[13], r[14], r[15], r[16]);
                todo &= todo - 1;
            }
            __syncwarp();

            if (SO == 0) stage_out();
            load_wf(IC<WF1>{}, IC<WF2>{});
        }
        DBG_G(110);
        float2* part = reinterpret_cast<float2*>(smem_raw + 3 * SLOT + UNIT);
        bf16* act = reinterpret_cast<bf16*>(smem_raw + 3 * SLOT + UNIT + 4096);
        {
            uint32_t it = 0;
            const bool own = (tid >> 1) == rg;
            const uint32_t ks = sb + 3 * SLOT + UNIT + 5120;
#pragma unroll 1
            while (cd.y != tag && !own && ++it < SPIN / 16) cd = ld_relaxed64(candp);
            asm volatile("st.shared.u32 [%0], %1;" ::"r"(ks + tid * 4), "r"(own ? (tid & 1) ? k2 : k1 : cd.x) : "memory");
            bar_sync(3, 256);
            DBG_G(111);
            const uint4 a = lds128(ks + lane * 16), b = lds128(ks + 512 + lane * 16);
            const uint32_t a1 = max(a.x, a.z), a2 = __vimax3_u32(min(a.x, a.z), a.y, a.w);
            const uint32_t b1 = max(b.x, b.z), b2 = __vimax3_u32(min(b.x, b.z), b.y, b.w);
            const uint32_t c1 = max(a1, b1), c2 = __vimax3_u32(min(a1, b1), a2, b2);
            k1 = __reduce_max_sync(0xffffffffu, c1);
            k2 = __reduce_max_sync(0xffffffffu, c1 == k1 ? c2 : c1);
        }
        const int sel0 = ~k1 & 2047, sel1 = ~k2 & 2047;
        const uint32_t slot0 = (sel0 >> 4) * 2, slot1 = (sel1 >> 4) * 2 + ((sel0 ^ sel1) < 16);
        uint4 b[9], b2[3];
        {
            const bool tk = cw < 4 ? cw & 2 : lane & 16;
            const int ri = cw < 4 ? tid & 63 : 64 + l16;
            const uint4* hp = padd(g_rows, ((tk ? slot1 : slot0) * RSLOT + (cw < 4 ? ri + (ri & 56) : ri + 64)) * 16);
            const uint32_t hs = sb + 3 * SLOT + UNIT + 8192;
            uint4 hr = make_uint4(cw < 5 ? ~0u : 0, 0, 0, 0);
            uint32_t it = 0, miss;
            reload16(hr, hp, miss);
            if (OUTP == 0 && SO == 0 && tid == 255) {
                reinterpret_cast<int2*>(red)[8] = make_int2(sel0, sel1);
                mbar_arrive(bar_out);
            }
            if (SO == 1) stage_out();
            load_wf(IC<WF2>{}, IC<27>{});
            mbar_wait(bar_full + 8, 1);
            mbar_wait(bar_full + 16, 1);
            {
                const uint32_t da = sb + (lane < 18 ? SLOT + lane * XP : 2 * SLOT + (lane - 18) * XP) + cw * 144;
                const uint32_t db = sb + 2 * SLOT + (14 + (lane & 3)) * XP + cw * 144 + (lane >> 3) * 16;
#pragma unroll
                for (int i = 0; i < 9; i++) b[i] = ldsm4t(da + i * 16);
#pragma unroll
                for (int i = 0; i < 3; i++) b2[i] = ldsm4t(db + i * 48);
            }
#pragma unroll 1
            do {
                miss = 0;
                reload16(hr, hp, miss);
            } while (__any_sync(0xffffffffu, miss) && ++it < SPIN / 16);
            if (cw < 5) asm volatile("st.shared.v4.u32 [%0], {%1, %2, %3, %4};" ::"r"(hs + (tk * 84 + ri) * 16), "r"(hr.x), "r"(hr.y), "r"(hr.z), "r"(hr.w) : "memory");
            bar_sync(3, 256);
            if (OUTP == 0 && SO == 1 && tid == 255) {
                reinterpret_cast<int2*>(red)[8] = make_int2(sel0, sel1);
                mbar_arrive(bar_out);
            }
            uint4 hv[4];
            uint32_t hw[2];
#pragma unroll
            for (int i = 0; i < 4; i++) hv[i] = lds128(hs + ((g8 & 1) * 84 + (cw >> 1) * 16 + qd + i * 4) * 16);
#pragma unroll
            for (int i = 0; i < 2; i++)
                hw[i] = lds32(hs + ((g8 & 1) * 84 + 64) * 16 + (cw >> 1) * 64 + qd * 8 + i * 32);
            DBG_G(112);
            float acc[24];
#pragma unroll
            for (int i = 0; i < 24; i++) acc[i] = 0.f;
#pragma unroll
            for (int i = 0; i < 27; i++) {
                const int ks = i / 3;
                mma16816(acc + 4 * (i % 6), wf[i].x, wf[i].y, wf[i].z, wf[i].w, ks == 8 ? hw[0] : (ks & 1) ? hv[ks >> 1 & 3].z : hv[ks >> 1 & 3].x,
                         ks == 8 ? hw[1] : (ks & 1) ? hv[ks >> 1 & 3].w : hv[ks >> 1 & 3].y);
            }
            if (qd == 0) {
#pragma unroll
                for (int i = 0; i < 5; i++) part[cw * 48 + i * 8 + g8] = make_float2(acc[2 * i] + acc[12 + 2 * i], acc[2 * i + 1] + acc[13 + 2 * i]);
            }
        }
        {
            uint2* dst = padd(g_ypart, ((((g8 & 1) * 36 + ((cw * 9) >> 1)) * NCTA + blockIdx.x) * 8 + (cw & 1) * 4 + qd) * 8);
            uint2* dst1 = dst + ((cw & 1) ? NCTA * 8 - 4 : 4);
            bar_sync(3, 256);

            {
                const float* pp = reinterpret_cast<const float*>(part) + ((blockIdx.x & 1) << 3) + (tid & 127);
                const float gs = rbf((pp[0] + pp[192]) + (pp[384] + pp[576])), us = rbf((pp[96] + pp[288]) + (pp[480] + pp[672]));
                const float v = rbf(gs * sigmoidf_(gs)) * us;
                if (tid < 80) act[(tid & 1) * 56 + (tid >> 1)] = __float2bfloat16_rn(tid < 72 ? v : 0.f);
            }
            bar_sync(3, 256);
            DBG_G(113);
            const uint32_t ap = sb + 3 * SLOT + UNIT + 4096 + (lane & 1) * 112 + (lane >> 4) * 16;
            const uint4 a0 = ldsm4(ap), a1 = ldsm4(ap + 32), a2 = ldsm4(ap + 64);
            float y[36];
#pragma unroll
            for (int i = 0; i < 36; i++) y[i] = 0.f;
#pragma unroll
            for (int i = 0; i < 9; i++) {
                const uint32_t bl = i % 3 == 0 ? b2[i / 3].x : i % 3 == 1 ? b2[i / 3].y : b2[i / 3].z;
                mma16816(y + 4 * i, a0.x, a0.y, a0.z, a0.w, b[i].x, b[i].y);
                mma16816(y + 4 * i, a1.x, a1.y, a1.z, a1.w, b[i].z, b[i].w);
                mma1688(y + 4 * i, a2.x, a2.y, bl);
            }
#pragma unroll
            for (int i = 0; i < 9; i++)
                if (lane < 8) st_relaxed64(((i & 1) ? dst1 : dst) + (i >> 1) * (NCTA * 8), __float_as_uint(y[4 * i]), __float_as_uint(y[4 * i + 1]));
        }
        DBG_G(114);
        if (OUTP == 1 && tid == 255) {
            reinterpret_cast<int2*>(red)[8] = make_int2(sel0, sel1);
            mbar_arrive(bar_out);
        }
        if (blockIdx.x == 127 && tid == 0) gs->epoch[0] = tag;
        if (blockIdx.x < 72) {
            const int tok = blockIdx.x >= 36, grp = blockIdx.x - tok * 36, cp = grp * 8 + (lane & 7);
            const uint2* src = padd(g_ypart, (blockIdx.x * NCTA * 8 + tid) * 8);
            const uint8_t* hsrc = reinterpret_cast<const uint8_t*>(padd(g_rows, (tok ? slot1 : slot0) * (RSLOT * 16) +
                (grp < 32 ? (grp & 7) * 256 + (grp >> 4) * 64 + qd * 16 + (grp & 8) + (lane & 4) : 2048 + (cp - 256) * 8)));
            const uint8_t* xsrc = hsrc + (grp < 32 ? 128 : 4);
            uint32_t* dst = padd(reinterpret_cast<uint32_t*>(args.out), (tok ? sel1 : sel0) * (D_ * 2) + cp * 4);
            const uint32_t gb = reinterpret_cast<const uint32_t*>(smem_raw + SM_TG)[cp];
            const uint32_t ksel = ((tok ? k2 : k1) & ~2047u) | 1024u;
            const float sg = sigmoidf_(rbf(__uint_as_float((ksel & 0x80000000u) ? (ksel & 0x7fffffffu) : ~ksel)));
            uint2 v[4];
            uint32_t hv, xv, it = 0;
            bool miss;
#pragma unroll 1
            do {
#pragma unroll
                for (int i = 0; i < 4; i++) v[i] = ld_relaxed64(src + i * 256);
                hv = ld_relaxed32(hsrc);
                xv = ld_relaxed32(xsrc);
                miss = max(__vimax3_u32(v[0].x, v[1].x, v[2].x), __vimax3_u32(v[3].x, hv, xv)) == ~0u;
            } while (__any_sync(0xffffffffu, miss) && ++it < SPIN / 16);
            float y0 = (__uint_as_float(v[0].x) + __uint_as_float(v[1].x)) + (__uint_as_float(v[2].x) + __uint_as_float(v[3].x));
            float y1 = (__uint_as_float(v[0].y) + __uint_as_float(v[1].y)) + (__uint_as_float(v[2].y) + __uint_as_float(v[3].y));
            y0 += __shfl_xor_sync(0xffffffffu, y0, 8); y1 += __shfl_xor_sync(0xffffffffu, y1, 8);
            y0 += __shfl_xor_sync(0xffffffffu, y0, 16); y1 += __shfl_xor_sync(0xffffffffu, y1, 16);
            if (lane < 8) reinterpret_cast<float2*>(rec)[cw * 8 + lane] = make_float2(y0, y1);
            bar_sync(3, 256);
            if (cw == 0) {
                const float2 t0_ = reinterpret_cast<const float2*>(rec)[lane], t1_ = reinterpret_cast<const float2*>(rec)[32 + lane];
                y0 = t0_.x + t1_.x; y1 = t0_.y + t1_.y;
                y0 += __shfl_xor_sync(0xffffffffu, y0, 8); y1 += __shfl_xor_sync(0xffffffffu, y1, 8);
                y0 += __shfl_xor_sync(0xffffffffu, y0, 16); y1 += __shfl_xor_sync(0xffffffffu, y1, 16);
                const uint32_t y2 = bmul2(pack_bf16(y0, y1), pack_bf16(sg, sg));
                if (lane < 8) *dst = badd2(xv, bmul2(gb, badd2(hv, y2)));
            }
        }
        }
        DBG_T(88);
        DBG_G(121);
    }
}

typedef CUresult (*EncodeFn)(CUtensorMap*, CUtensorMapDataType, cuuint32_t, void*, const cuuint64_t*, const cuuint64_t*,
                             const cuuint32_t*, const cuuint32_t*, CUtensorMapInterleave, CUtensorMapSwizzle,
                             CUtensorMapL2promotion, CUtensorMapFloatOOBfill);

static void make_map(EncodeFn enc, CUtensorMap* m, const void* ptr, int rank, const cuuint64_t* dims,
                     const cuuint64_t* strides, const cuuint32_t* box, CUtensorMapSwizzle sw = CU_TENSOR_MAP_SWIZZLE_128B,
                     CUtensorMapDataType dt = CU_TENSOR_MAP_DATA_TYPE_BFLOAT16) {
    const cuuint32_t es[3] = {1, 1, 1};
    enc(m, dt, rank, const_cast<void*>(ptr), dims, strides, box, es,
        CU_TENSOR_MAP_INTERLEAVE_NONE, sw, CU_TENSOR_MAP_L2_PROMOTION_L2_128B,
        CU_TENSOR_MAP_FLOAT_OOB_FILL_NONE);
}

extern "C" void kernel_launch(void* const* d_in, const int* in_sizes, int n_in, void* d_out, int out_size) {
    const bf16* x = (const bf16*)d_in[0];
    const bf16* kc = (const bf16*)d_in[1];
    const bf16* vc = (const bf16*)d_in[2];
    const bf16* wq = (const bf16*)d_in[3];
    const bf16* wo = (const bf16*)d_in[4];
    const bf16* w_r = (const bf16*)d_in[6];
    const bf16* w_gate = (const bf16*)d_in[7];
    const bf16* w_up = (const bf16*)d_in[8];
    const bf16* w_down = (const bf16*)d_in[9];
    const bf16* cvec = (const bf16*)d_in[10];
    const bf16* w_mod = (const bf16*)d_in[11];
    bf16* out = (bf16*)d_out;

    void* fn = nullptr;
    cudaDriverEntryPointQueryResult qr;
    cudaGetDriverEntryPoint("cuTensorMapEncodeTiled", &fn, cudaEnableDefault, &qr);
    EncodeFn enc = (EncodeFn)fn;
    void* p_s;
    cudaGetSymbolAddress(&p_s, g_s);

    CUtensorMap tm_wq, tm_k, tm_v, tm_wo, tm_p, tm_x, tm_d, tm_g, tm_u;
    { cuuint64_t d[2] = {QD, D_}, s[1] = {QD * 2}; cuuint32_t b[2] = {64, 128}; make_map(enc, &tm_wq, wq, 2, d, s, b); }
    { cuuint64_t d[2] = {DH, HKV * S_}, s[1] = {DH * 2}; cuuint32_t b[2] = {64, 128};
      make_map(enc, &tm_k, kc, 2, d, s, b); make_map(enc, &tm_v, vc, 2, d, s, b); }
    { cuuint64_t d[2] = {D_, QD}, s[1] = {D_ * 2}; cuuint32_t b[2] = {64, 128}; make_map(enc, &tm_wo, wo, 2, d, s, b); }
    { cuuint64_t d[3] = {256, 160, NCTA}, s[2] = {1024, 8 * WREG}; cuuint32_t b[3] = {256, 2, 8};
      make_map(enc, &tm_p, ((Scratch*)p_s)->frag, 3, d, s, b, CU_TENSOR_MAP_SWIZZLE_NONE, CU_TENSOR_MAP_DATA_TYPE_UINT32); }
    { cuuint64_t d[2] = {D_ / 4, S_}, s[1] = {D_ * 2}; cuuint32_t b[2] = {XP / 8, 16};
      make_map(enc, &tm_x, x, 2, d, s, b, CU_TENSOR_MAP_SWIZZLE_NONE, CU_TENSOR_MAP_DATA_TYPE_UINT64); }
    { cuuint64_t d[2] = {D_ / 4, F_}, s[1] = {D_ * 2}; cuuint32_t b[2] = {XP / 8, 18};
      make_map(enc, &tm_d, w_down, 2, d, s, b, CU_TENSOR_MAP_SWIZZLE_NONE, CU_TENSOR_MAP_DATA_TYPE_UINT64); }
    { cuuint64_t d[2] = {F_, D_}, s[1] = {F_ * 2}; cuuint32_t b[2] = {40, 24};
      make_map(enc, &tm_g, w_gate, 2, d, s, b, CU_TENSOR_MAP_SWIZZLE_NONE); make_map(enc, &tm_u, w_up, 2, d, s, b, CU_TENSOR_MAP_SWIZZLE_NONE); }

    cudaFuncSetAttribute(fused_kernel<true>, cudaFuncAttributeMaxDynamicSharedMemorySize, SM_TOTAL);
    cudaFuncSetAttribute(fused_kernel<false>, cudaFuncAttributeMaxDynamicSharedMemorySize, SM_TOTAL);
    cudaLaunchConfig_t cfg = {};
    cfg.gridDim = NCTA + 4; cfg.blockDim = 384; cfg.dynamicSmemBytes = SM_TOTAL;
    cudaLaunchAttribute at;
    at.id = cudaLaunchAttributeClusterDimension; at.val.clusterDim.x = 2; at.val.clusterDim.y = 1; at.val.clusterDim.z = 1;
    cfg.attrs = &at; cfg.numAttrs = 1;
    int ncl = 0;
    if (cudaOccupancyMaxActiveClusters(&ncl, fused_kernel<true>, &cfg) != cudaSuccess) { ncl = 0; cudaGetLastError(); }
    Args args{w_mod, cvec, (Scratch*)p_s, out, x, kc, vc, wq, wo, w_r, w_down};
    if (USE_SPARE && ncl >= NCTA / 2 + 2)
        fused_kernel<true><<<NCTA + 4, 384, SM_TOTAL>>>(args, tm_wq, tm_k, tm_v, tm_wo, tm_p, tm_x, tm_d, tm_g, tm_u);
    else
        fused_kernel<false><<<NCTA, 384, SM_TOTAL>>>(args, tm_wq, tm_k, tm_v, tm_wo, tm_p, tm_x, tm_d, tm_g, tm_u);
}
```

```cpp
#include <cuda_runtime.h>
#include <cuda_bf16.h>
#include <cuda.h>
#include <stdint.h>
#include <math.h>

typedef __nv_bfloat16 bf16;

constexpr int S_ = 2048;
constexpr int D_ = 576;
constexpr int HQ = 32, HKV = 16, DH = 128;
constexpr int F_ = 4608;
constexpr int QD = HQ * DH;

constexpr int NCTA = 128;
constexpr int WREG = 5 * 4096;
constexpr int CREP = 8;
constexpr int RSLOT = 144;
constexpr int MREP = 4;
struct Scratch {
    unsigned int epoch[128];
    unsigned int flag_mod[NCTA];
    unsigned int flag_part[16 * 32];
    unsigned int flag_q3[16 * 32];
    unsigned int flag_h[NCTA * 32];
    uint2 mod1[MREP * D_];
    uint32_t mod2[4 * D_];
    uint4 cand[CREP * NCTA * 2];
    uint2 ypart[72 * NCTA * 8];
    uint4 h[2][NCTA * 36 * 32];
    uint4 q3[NCTA * 8 * 128];
    uint4 rows[NCTA * 2 * RSLOT];
    uint8_t frag[NCTA * 8 * WREG];
    uint8_t keep[NCTA * 8 * 4096];
};
__device__ __align__(1024) Scratch g_s;
#define g_h gs->h[tag & 1]
#define g_q3 gs->q3
#define g_keep gs->keep
#define g_flag_h gs->flag_h
#define g_flag_part gs->flag_part
#define g_flag_mod gs->flag_mod
#define g_flag_q3 gs->flag_q3
#define g_frag gs->frag
#define g_cand gs->cand
#define g_ypart gs->ypart
#define g_rows gs->rows

#define DBG_INIT()
#define DBG_P(i)
#define DBG_PG(i)
#define DBG_T(i)
#define DBG_G(i)

__device__ __forceinline__ uint32_t pack_bf16(float lo, float hi) {
    uint32_t r;
    asm("cvt.rn.bf16x2.f32 %0, %1, %2;" : "=r"(r) : "f"(hi), "f"(lo));
    return r;
}
__device__ __forceinline__ float rbf(float x) { return __uint_as_float(pack_bf16(0.f, x)); }
__device__ __forceinline__ float bf_lo(uint32_t v) { return __uint_as_float(v << 16); }
__device__ __forceinline__ float bf_hi(uint32_t v) { return __uint_as_float(v & 0xffff0000u); }
__device__ __forceinline__ float ex2(float x) {
    float y;
    asm("ex2.approx.ftz.f32 %0, %1;" : "=f"(y) : "f"(x));
    return y;
}
template <class T>
__device__ __forceinline__ T* padd(T* p, uint32_t off) {
    unsigned long long r;
    asm("{\n.reg .b32 l, h;\nmov.b64 {l, h}, %1;\nadd.cc.u32 l, l, %2;\naddc.u32 h, h, 0;\nmov.b64 %0, {l, h};\n}" : "=l"(r) : "l"(p), "r"(off));
    return reinterpret_cast<T*>(r);
}
__device__ __forceinline__ uint32_t smem_u32(const void* p) { return (uint32_t)__cvta_generic_to_shared(p); }
__device__ __forceinline__ void mbar_init(uint32_t bar, uint32_t cnt) {
    asm volatile("mbarrier.init.shared::cta.b64 [%0], %1;" ::"r"(bar), "r"(cnt) : "memory");
}
__device__ __forceinline__ void mbar_expect_tx(uint32_t bar, uint32_t bytes) {
    asm volatile("mbarrier.arrive.expect_tx.shared::cta.b64 _, [%0], %1;" ::"r"(bar), "r"(bytes) : "memory");
}
__device__ __forceinline__ void mbar_arrive(uint32_t bar) {
    asm volatile("mbarrier.arrive.shared::cta.b64 _, [%0];" ::"r"(bar) : "memory");
}
__device__ __forceinline__ void mbar_arrive_cluster(uint32_t cluster_addr) {
    asm volatile("mbarrier.arrive.shared::cluster.b64 _, [%0];" ::"r"(cluster_addr) : "memory");
}
constexpr uint32_t SPIN = 1u << 20;
__device__ __forceinline__ void mbar_wait(uint32_t bar, uint32_t parity) {
    asm volatile("{\n.reg .pred p;\n.reg .b32 c;\nmov.b32 c, 0;\n"
                 "W_%=:\nmbarrier.try_wait.parity.shared::cta.b64 p, [%0], %1;\n@p bra D_%=;\n"
                 "add.u32 c, c, 1;\nsetp.lt.u32 p, c, 0x100000;\n@p bra W_%=;\nD_%=:\n}"
                 ::"r"(bar), "r"(parity) : "memory");
}
__device__ __forceinline__ void anchor(uint32_t addr, float v) {
    asm volatile("{\n.reg .pred p;\nsetp.lt.f32 p, %1, 0f00000000;\n@p st.volatile.shared.f32 [%0], %1;\n}" ::"r"(addr), "f"(v) : "memory");
}
__device__ __forceinline__ void mbar_wait_sleep(uint32_t bar, uint32_t parity) {
    asm volatile("{\n.reg .pred p;\n.reg .b32 c;\nmov.b32 c, 0;\n"
                 "W_%=:\nmbarrier.try_wait.parity.shared::cta.b64 p, [%0], %1, 5000;\n@p bra D_%=;\n"
                 "add.u32 c, c, 1;\nsetp.lt.u32 p, c, 0x20000;\n@p bra W_%=;\nD_%=:\n}"
                 ::"r"(bar), "r"(parity) : "memory");
}
__device__ __forceinline__ uint32_t load_tag(const Scratch* gs) {
    uint32_t tag;
    asm volatile("ld.global.ca.u32 %0, [%1];" : "=r"(tag) : "l"(gs->epoch) : "memory");
    return tag + 1;
}
__device__ __forceinline__ uint4 ld_relaxed(const uint4* p) {
    uint4 v;
    asm volatile("ld.relaxed.gpu.global.v4.u32 {%0,%1,%2,%3}, [%4];" : "=r"(v.x), "=r"(v.y), "=r"(v.z), "=r"(v.w) : "l"(p) : "memory");
    return v;
}
__device__ __forceinline__ void st_relaxed(uint4* p, uint32_t a, uint32_t b, uint32_t c, uint32_t d) {
    asm volatile("{\n.reg .b64 u, v;\nmov.b64 u, {%1, %2};\nmov.b64 v, {%3, %4};\nst.relaxed.gpu.global.v2.b64 [%0], {u, v};\n}"
                 ::"l"(p), "r"(a), "r"(b), "r"(c), "r"(d) : "memory");
}
__device__ __forceinline__ void st_relaxed4(void* p, uint32_t a, uint32_t b, uint32_t c, uint32_t d) {
    asm volatile("st.relaxed.gpu.global.v4.u32 [%0], {%1, %2, %3, %4};" ::"l"(p), "r"(a), "r"(b), "r"(c), "r"(d) : "memory");
}
__device__ __forceinline__ uint2 ld_relaxed8(const void* p) {
    uint2 v;
    asm volatile("ld.relaxed.gpu.global.v2.u32 {%0,%1}, [%2];" : "=r"(v.x), "=r"(v.y) : "l"(p) : "memory");
    return v;
}
__device__ __forceinline__ uint2 ld_relaxed64(const uint2* p) {
    uint2 v;
    asm volatile("{\n.reg .b64 u;\nld.relaxed.gpu.global.b64 u, [%2];\nmov.b64 {%0, %1}, u;\n}" : "=r"(v.x), "=r"(v.y) : "l"(p) : "memory");
    return v;
}
__device__ __forceinline__ void st_relaxed64(uint2* p, uint32_t a, uint32_t b) {
    asm volatile("{\n.reg .b64 u;\nmov.b64 u, {%1, %2};\nst.relaxed.gpu.global.b64 [%0], u;\n}" ::"l"(p), "r"(a), "r"(b) : "memory");
}
__device__ __forceinline__ uint4 ld_relaxed2(const uint4* p) {
    uint4 v;
    asm volatile("{\n.reg .b64 u, w;\nld.relaxed.gpu.global.v2.b64 {u, w}, [%4];\nmov.b64 {%0, %1}, u;\nmov.b64 {%2, %3}, w;\n}"
                 : "=r"(v.x), "=r"(v.y), "=r"(v.z), "=r"(v.w) : "l"(p) : "memory");
    return v;
}
__device__ __forceinline__ void reload16(uint4& v, const void* p, uint32_t& miss) {
    asm volatile("{\n.reg .pred p;\n.reg .b32 m;\n.reg .b64 u, w;\nmax.u32 m, %0, %2;\nsetp.eq.u32 p, m, 0xffffffff;\n"
                 "mov.b64 u, {%0, %1};\nmov.b64 w, {%2, %3};\n@p ld.relaxed.gpu.global.v2.b64 {u, w}, [%5];\n"
                 "mov.b64 {%0, %1}, u;\nmov.b64 {%2, %3}, w;\n@p mov.u32 %4, 1;\n}"
                 : "+r"(v.x), "+r"(v.y), "+r"(v.z), "+r"(v.w), "+r"(miss) : "l"(p) : "memory");
}
__device__ __forceinline__ void reload8(uint2& v, const void* p, uint32_t& miss) {
    asm volatile("{\n.reg .pred p;\n.reg .b64 u;\nsetp.eq.u32 p, %0, 0xffffffff;\nmov.b64 u, {%0, %1};\n"
                 "@p ld.relaxed.gpu.global.b64 u, [%3];\nmov.b64 {%0, %1}, u;\n@p mov.u32 %2, 1;\n}"
                 : "+r"(v.x), "+r"(v.y), "+r"(miss) : "l"(p) : "memory");
}
__device__ __forceinline__ uint32_t ld_relaxed32(const void* p) {
    uint32_t v;
    asm volatile("ld.relaxed.gpu.global.u32 %0, [%1];" : "=r"(v) : "l"(p) : "memory");
    return v;
}
__device__ __forceinline__ void poll2x2(const uint4* p0, const uint4* p1, uint32_t tag, uint4& o0, uint4& o1) {
    uint4 v0, v1;
    uint32_t miss, it = 0;
#pragma unroll 1
    do {
        v0 = ld_relaxed2(p0); v1 = ld_relaxed2(p1);
        miss = (v0.y ^ tag) | (v0.w ^ tag) | (v1.y ^ tag) | (v1.w ^ tag);
    } while (miss && ++it < SPIN / 16);
    o0 = v0; o1 = v1;
}
__device__ __forceinline__ void flag_wait(const unsigned int* p, uint32_t tag) {
    uint32_t v, it = 0;
#pragma unroll 1
    do {
        asm volatile("ld.relaxed.gpu.global.u32 %0, [%1];" : "=r"(v) : "l"(p) : "memory");
    } while (__any_sync(0xffffffffu, v != tag) && ++it < SPIN / 16);
    asm volatile("fence.acquire.gpu;" ::: "memory");
    __syncwarp();
}
__device__ __forceinline__ bool elect() {
    uint32_t p;
    asm volatile("{\n.reg .pred p;\nelect.sync _|p, 0xffffffff;\nselp.u32 %0, 1, 0, p;\n}" : "=r"(p));
    return p;
}
__device__ __forceinline__ void flag_release(unsigned int* p, uint32_t tag) {
    asm volatile("st.release.gpu.global.u32 [%0], %1;" ::"l"(p), "r"(tag) : "memory");
}
__device__ __forceinline__ uint32_t touch(const void* p) {
    uint32_t v;
    asm volatile("ld.global.nc.L1::no_allocate.L2::128B.u32 %0, [%1];" : "=r"(v) : "l"(p));
    return v;
}
__device__ __forceinline__ void bar_sync(int id, int n) { asm volatile("bar.sync %0, %1;" ::"r"(id), "r"(n) : "memory"); }
__device__ __forceinline__ void bar_arrive(int id, int n) { asm volatile("bar.arrive %0, %1;" ::"r"(id), "r"(n) : "memory"); }

constexpr uint64_t EVICT_NORMAL = 0x1000000000000000ull, EVICT_FIRST = 0x12F0000000000000ull;
__device__ __forceinline__ void tma2d(uint32_t dst, const CUtensorMap* m, int c0, int c1, uint32_t bar) {
    asm volatile("cp.async.bulk.tensor.2d.shared::cluster.global.mbarrier::complete_tx::bytes.L2::cache_hint [%0], [%1, {%3, %4}], [%2], %5;"
                 ::"r"(dst), "l"(m), "r"(bar), "r"(c0), "r"(c1), "l"(EVICT_FIRST) : "memory");
}
__device__ __forceinline__ void tma2d_mc(uint32_t dst, const CUtensorMap* m, int c0, int c1, uint32_t bar, uint64_t pol) {
    asm volatile("cp.async.bulk.tensor.2d.shared::cluster.global.mbarrier::complete_tx::bytes.multicast::cluster.L2::cache_hint [%0], [%1, {%3, %4}], [%2], %5, %6;"
                 ::"r"(dst), "l"(m), "r"(bar), "r"(c0), "r"(c1), "h"((uint16_t)3), "l"(pol) : "memory");
}
__device__ __forceinline__ void tma3d(uint32_t dst, const CUtensorMap* m, int c0, int c1, int c2, uint32_t bar) {
    asm volatile("cp.async.bulk.tensor.3d.shared::cluster.global.mbarrier::complete_tx::bytes.L2::cache_hint [%0], [%1, {%3, %4, %5}], [%2], %6;"
                 ::"r"(dst), "l"(m), "r"(bar), "r"(c0), "r"(c1), "r"(c2), "l"(EVICT_FIRST) : "memory");
}
__device__ __forceinline__ void bulk_load(uint32_t dst, const void* src, uint32_t bytes, uint32_t bar) {
    asm volatile("cp.async.bulk.shared::cluster.global.mbarrier::complete_tx::bytes [%0], [%1], %2, [%3];"
                 ::"r"(dst), "l"(src), "r"(bytes), "r"(bar) : "memory");
}
__device__ __forceinline__ void l2_prefetch(const void* src, uint32_t bytes) {
    asm volatile("cp.async.bulk.prefetch.L2.global [%0], %1;" ::"l"(src), "r"(bytes) : "memory");
}
__device__ __forceinline__ uint32_t bmul2(uint32_t a, uint32_t b) { uint32_t r; asm("mul.rn.bf16x2 %0, %1, %2;" : "=r"(r) : "r"(a), "r"(b)); return r; }
__device__ __forceinline__ uint32_t badd2(uint32_t a, uint32_t b) { uint32_t r; asm("add.rn.bf16x2 %0, %1, %2;" : "=r"(r) : "r"(a), "r"(b)); return r; }
__device__ __forceinline__ uint32_t bsub2(uint32_t a, uint32_t b) { uint32_t r; asm("sub.rn.bf16x2 %0, %1, %2;" : "=r"(r) : "r"(a), "r"(b)); return r; }
__device__ __forceinline__ uint32_t bmax2(uint32_t a, uint32_t b) { uint32_t r; asm("max.bf16x2 %0, %1, %2;" : "=r"(r) : "r"(a), "r"(b)); return r; }
__device__ __forceinline__ uint32_t bfma2(uint32_t a, uint32_t b, uint32_t c) { uint32_t r; asm("fma.rn.bf16x2 %0, %1, %2, %3;" : "=r"(r) : "r"(a), "r"(b), "r"(c)); return r; }
__device__ __forceinline__ uint4 lds128(uint32_t a) { uint4 v; asm volatile("ld.shared.v4.u32 {%0,%1,%2,%3}, [%4];" : "=r"(v.x), "=r"(v.y), "=r"(v.z), "=r"(v.w) : "r"(a) : "memory"); return v; }
__device__ __forceinline__ uint2 lds64(uint32_t a) { uint2 v; asm volatile("ld.shared.v2.u32 {%0,%1}, [%2];" : "=r"(v.x), "=r"(v.y) : "r"(a) : "memory"); return v; }
__device__ __forceinline__ uint32_t lds32(uint32_t a) { uint32_t v; asm volatile("ld.shared.u32 %0, [%1];" : "=r"(v) : "r"(a) : "memory"); return v; }
__device__ __forceinline__ uint4 ldsm4(uint32_t a) {
    uint4 v;
    asm volatile("ldmatrix.sync.aligned.m8n8.x4.shared.b16 {%0,%1,%2,%3}, [%4];" : "=r"(v.x), "=r"(v.y), "=r"(v.z), "=r"(v.w) : "r"(a) : "memory");
    return v;
}
__device__ __forceinline__ uint4 ldsm4t(uint32_t a) {
    uint4 v;
    asm volatile("ldmatrix.sync.aligned.m8n8.x4.trans.shared.b16 {%0,%1,%2,%3}, [%4];" : "=r"(v.x), "=r"(v.y), "=r"(v.z), "=r"(v.w) : "r"(a) : "memory");
    return v;
}
__device__ __forceinline__ void mma1688(float* d, uint32_t a0, uint32_t a1, uint32_t b) {
    asm("mma.sync.aligned.m16n8k8.row.col.f32.bf16.bf16.f32 {%0,%1,%2,%3}, {%4,%5}, {%6}, {%0,%1,%2,%3};"
        : "+f"(d[0]), "+f"(d[1]), "+f"(d[2]), "+f"(d[3]) : "r"(a0), "r"(a1), "r"(b));
}
__device__ __forceinline__ void mma16816(float* d, uint32_t a0, uint32_t a1, uint32_t a2, uint32_t a3, uint32_t b0, uint32_t b1) {
    asm("mma.sync.aligned.m16n8k16.row.col.f32.bf16.bf16.f32 {%0,%1,%2,%3}, {%4,%5,%6,%7}, {%8,%9}, {%0,%1,%2,%3};"
                 : "+f"(d[0]), "+f"(d[1]), "+f"(d[2]), "+f"(d[3]) : "r"(a0), "r"(a1), "r"(a2), "r"(a3), "r"(b0), "r"(b1));
}
__device__ __forceinline__ void stsm_x4(uint32_t addr, uint32_t a, uint32_t b, uint32_t c, uint32_t d) {
    asm volatile("stmatrix.sync.aligned.m8n8.x4.shared.b16 [%0], {%1, %2, %3, %4};"
                 ::"r"(addr), "r"(a), "r"(b), "r"(c), "r"(d) : "memory");
}

__device__ __forceinline__ uint64_t mkdesc(uint32_t addr, uint32_t lbo, uint32_t sbo) {
    return (uint64_t)((addr & 0x3FFFF) >> 4) | ((uint64_t)(lbo >> 4) << 16) | ((uint64_t)(sbo >> 4) << 32) | (1ull << 62);
}
constexpr uint32_t SM0 = 1024;
__host__ __device__ constexpr uint32_t desc_lo(uint32_t off, uint32_t lbo) { return ((SM0 + off) >> 4) | ((lbo >> 4) << 16); }
__device__ __forceinline__ uint64_t desc_of(uint32_t lo) { return lo | (0x40000040ull << 32); }
#define WG_FENCE() asm volatile("wgmma.fence.sync.aligned;" ::: "memory")
#define WG_COMMIT() asm volatile("wgmma.commit_group.sync.aligned;" ::: "memory")
#define WG_WAIT(n) asm volatile("wgmma.wait_group.sync.aligned %0;" ::"n"(n) : "memory")

#define F8(a, i) "+f"(a[i]), "+f"(a[i + 1]), "+f"(a[i + 2]), "+f"(a[i + 3]), "+f"(a[i + 4]), "+f"(a[i + 5]), "+f"(a[i + 6]), "+f"(a[i + 7])
#define F16(a, i) F8(a, i), F8(a, i + 8)
#define F64(a) F16(a, 0), F16(a, 16), F16(a, 32), F16(a, 48)
#define F32(a) F16(a, 0), F16(a, 16)
#define L64 "%0,%1,%2,%3,%4,%5,%6,%7,%8,%9,%10,%11,%12,%13,%14,%15,%16,%17,%18,%19,%20,%21,%22,%23,%24,%25,%26,%27,%28,%29,%30,%31,%32,%33,%34,%35,%36,%37,%38,%39,%40,%41,%42,%43,%44,%45,%46,%47,%48,%49,%50,%51,%52,%53,%54,%55,%56,%57,%58,%59,%60,%61,%62,%63"
#define L32 "%0,%1,%2,%3,%4,%5,%6,%7,%8,%9,%10,%11,%12,%13,%14,%15,%16,%17,%18,%19,%20,%21,%22,%23,%24,%25,%26,%27,%28,%29,%30,%31"

template <int TB>
__device__ __forceinline__ void mma_rs128(float (&d)[64], uint32_t a0, uint32_t a1, uint32_t a2, uint32_t a3, uint64_t b, int acc) {
    asm volatile("{\n.reg .pred p;\nsetp.ne.b32 p, %69, 0;\n"
                 "wgmma.mma_async.sync.aligned.m64n128k16.f32.bf16.bf16 {" L64 "}, {%64,%65,%66,%67}, %68, p, 1, 1, %70;\n}"
                 : F64(d) : "r"(a0), "r"(a1), "r"(a2), "r"(a3), "l"(b), "r"(acc), "n"(TB));
}
template <int TB>
__device__ __forceinline__ void mma_rs64(float (&d)[32], uint32_t a0, uint32_t a1, uint32_t a2, uint32_t a3, uint64_t b, int acc) {
    asm volatile("{\n.reg .pred p;\nsetp.ne.b32 p, %37, 0;\n"
                 "wgmma.mma_async.sync.aligned.m64n64k16.f32.bf16.bf16 {" L32 "}, {%32,%33,%34,%35}, %36, p, 1, 1, %38;\n}"
                 : F32(d) : "r"(a0), "r"(a1), "r"(a2), "r"(a3), "l"(b), "r"(acc), "n"(TB));
}
template <int N>
__device__ __forceinline__ void fence_regs(float (&d)[N]) {
#pragma unroll
    for (int i = 0; i < N; i++) asm volatile("" : "+f"(d[i])::"memory");
}
template <int N>
__device__ __forceinline__ void fence_regs(uint32_t (&d)[N]) {
#pragma unroll
    for (int i = 0; i < N; i++) asm volatile("" : "+r"(d[i])::"memory");
}

template <int V> struct IC { static constexpr int value = V; };

constexpr int SLOT = 32768, UNIT = 16384;
constexpr int SM_Q = 4 * SLOT;
constexpr int SM_BAR = 7 * SLOT;
constexpr int SM_RED = SM_BAR + 512;
constexpr int SM_TOTAL = SM_BAR + 3072;
constexpr int XP = D_ * 2 + 16;
constexpr int M_MOD = 16 * XP;
constexpr int SM_T = SM_Q + 2 * D_ * 80, SM_TC = SM_T + D_ * 4, SM_TG = SM_TC + D_ * 4, SM_TS = SM_TG + D_ * 2;
constexpr float CS = 0.08838834764831845f * 1.4426950408889634f;
#define LMAX 0.5f
#define LMIN 0x1p-104f
#define USE_SPARE 1
#define MAXG 2
#define SPLIT 10
#define ESPLIT 2
#define PV1 8
#define RW 2
#define HW 2
#define HW2 1
#define XDELAY 200
#define QDELAY 300
#define TMPF 1
#define PFD0 2000
#define PFD1 400
#define HSENT 1
#define HDELAY 500
#define STAGE 11
#define POFF 102.f
#define WF0 6
#define WF1 16
#define C3D 0
#define C4D 300
#define DD 300
#define P2E 1
#define BO 0
#define MAP 2
#define CFULL 0
#define WFE 1
#define OUTD 0
#define OUTPOL EVICT_FIRST
#define SO 0
#define WF2 22
#define OUTP 0
constexpr int PF_KV = 8, PF_WO = 120;

__device__ __forceinline__ int cluster_role() {
    int k = blockIdx.x >> 1;
    if (MAP == 0) return k & 63;
    if (MAP == 1) return (k & 7) * 8 + ((k >> 3) & 7);
    if (MAP == 3) {
        asm("mov.u32 %0, %%smid;" : "=r"(k));
        k >>= 1;
        const int r = ((k - 32) * 37) >> 8;
        return k < 32 ? (k & 7) * 8 + (k >> 3) : k < 60 ? (k - 31 - r * 7) * 8 + 4 + r : (k - 58) & 7;
    }
    const int r = ((k - 36) * 37) >> 8, i = k - 36 - r * 7;
    if (MAP == 4) return k < 4 ? 4 + k : k < 36 ? ((k - 4) & 7) * 8 + ((k - 4) >> 3) : (i + 1) * 8 + ((4 + r) & 7);
    return k < 4 ? 12 + k : k < 36 ? ((k - 4) & 7) * 8 + ((k - 4) >> 3) : (i + (i > 0)) * 8 + ((4 + r) & 7);
}

struct Args {
    const bf16 *w_mod, *cvec;
    Scratch* gs;
    bf16* out;
    const bf16 *x, *kc, *vc, *wq, *wo, *w_r, *w_down;
};

__device__ __forceinline__ void frag_store(uint8_t* p, const uint32_t (&a)[32]) {
#pragma unroll
    for (int i = 0; i < 8; i++)
        __stcg(reinterpret_cast<uint4*>(p + i * 512), make_uint4(a[4 * i], a[4 * i + 1], a[4 * i + 2], a[4 * i + 3]));
}
__device__ __forceinline__ void frag_load(uint32_t (&a)[32], const uint8_t* p) {
#pragma unroll
    for (int i = 0; i < 8; i++) {
        const uint4 v = __ldcg(reinterpret_cast<const uint4*>(p + i * 512));
        a[4 * i] = v.x; a[4 * i + 1] = v.y; a[4 * i + 2] = v.z; a[4 * i + 3] = v.w;
    }
}
__device__ __forceinline__ float quad_sum(float v) {
    v += __shfl_xor_sync(0xffffffffu, v, 1);
    return v + __shfl_xor_sync(0xffffffffu, v, 2);
}
__device__ __forceinline__ float quad_max(float v) {
    v = fmaxf(v, __shfl_xor_sync(0xffffffffu, v, 1));
    return fmaxf(v, __shfl_xor_sync(0xffffffffu, v, 2));
}
__device__ __forceinline__ float rcp_fast(float x) { float y; asm("rcp.approx.ftz.f32 %0, %1;" : "=f"(y) : "f"(x)); return y; }
__device__ __forceinline__ float sigmoidf_(float x) { return rcp_fast(1.f + ex2(-1.4426950408889634f * x)); }
__device__ __forceinline__ void top2(uint32_t k, uint32_t& k1, uint32_t& k2) {
    k1 = __reduce_max_sync(0xffffffffu, k);
    k2 = __reduce_max_sync(0xffffffffu, k == k1 ? 0 : k);
}

__device__ __forceinline__ void mod_fma(float (&a)[8], const uint4 w, float sc) {
    a[0] += sc * bf_lo(w.x); a[1] += sc * bf_hi(w.x); a[2] += sc * bf_lo(w.y); a[3] += sc * bf_hi(w.y);
    a[4] += sc * bf_lo(w.z); a[5] += sc * bf_hi(w.z); a[6] += sc * bf_lo(w.w); a[7] += sc * bf_hi(w.w);
}
__device__ __forceinline__ float mod_reduce(float (&a)[8], int lane) {
#pragma unroll
    for (int h = 4; h > 0; h >>= 1) {
        const bool up = lane & (8 / h);
#pragma unroll
        for (int i = 0; i < h; i++)
            a[i] = (up ? a[i + h] : a[i]) + __shfl_xor_sync(0xffffffffu, up ? a[i] : a[i + h], 8 / h);
    }
    return a[0] + __shfl_xor_sync(0xffffffffu, a[0], 16);
}

__device__ __forceinline__ float ln_stats(float sum, float sq, uint32_t& mean2) {
    const float mean = sum * (1.f / D_);
    const float var = fmaxf(fmaf(-mean, mean, sq * (1.f / D_)), 0.f);
    float sd;
    asm("sqrt.approx.ftz.f32 %0, %1;" : "=f"(sd) : "f"(rbf(rbf(var) + 1e-5f)));
    mean2 = pack_bf16(mean, mean);
    return rcp_fast(rbf(sd));
}
__device__ __forceinline__ uint32_t ln_pair(uint32_t x, uint32_t mean2, float rsd) {
    const uint32_t d = bsub2(x, mean2);
    return pack_bf16(bf_lo(d) * rsd, bf_hi(d) * rsd);
}
__device__ __forceinline__ void rows_load(uint32_t (&x)[20], uint32_t xs, int cw) {
#pragma unroll
    for (int ch = 0; ch < 5; ch++) {
        const uint4 v = ldsm4(ch < 4 ? xs + ch * 256 : xs + 1024 - cw * 16);
        x[4 * ch] = v.x; x[4 * ch + 1] = v.y; x[4 * ch + 2] = v.z; x[4 * ch + 3] = v.w;
    }
}
__device__ __forceinline__ void stats_add(float (&st)[12], uint32_t a, uint32_t b, uint32_t w) {
    mma1688(st, a, b, w);
    mma1688(st + 4, a, b, a);
    mma1688(st + 8, a, b, b);
}
__device__ __forceinline__ float rows_stats(const float (&st)[12], float4* rec, int cw, int lane, uint32_t& mean2, float& dot) {
    const int g8 = lane >> 2;
    if ((g8 >> 1) == (lane & 3)) {
        rec[cw * 16 + g8] = make_float4(st[0], (g8 & 1) ? st[5] : st[4], st[1], 0.f);
        rec[cw * 16 + 8 + g8] = make_float4(st[2], (g8 & 1) ? st[11] : st[10], st[3], 0.f);
    }
    bar_sync(3, 256);
    const float4* r = rec + (lane >> 4) * 64 + (lane & 15);
    const float4 s0 = r[0], s1 = r[16], s2 = r[32], s3 = r[48];
    const float sum = (s0.x + s1.x) + (s2.x + s3.x), sq = (s0.y + s1.y) + (s2.y + s3.y);
    dot = (s0.z + s1.z) + (s2.z + s3.z);
    dot += __shfl_xor_sync(0xffffffffu, dot, 16);
    return ln_stats(sum + __shfl_xor_sync(0xffffffffu, sum, 16), sq + __shfl_xor_sync(0xffffffffu, sq, 16), mean2);
}
template <class F>
__device__ __forceinline__ void rows_normalise(uint32_t* y, const uint32_t* x, uint32_t mean2, float rsd, int lane, F loads) {
    const int g8 = lane >> 2;
    const uint32_t ma2 = __shfl_sync(0xffffffffu, mean2, g8), mb2 = __shfl_sync(0xffffffffu, mean2, g8 + 8);
    const float ra = __shfl_sync(0xffffffffu, rsd, g8), rb = __shfl_sync(0xffffffffu, rsd, g8 + 8);
    loads();
#pragma unroll
    for (int k = 0; k < 9; k++) { y[2 * k] = ln_pair(x[2 * k], ma2, ra); y[2 * k + 1] = ln_pair(x[2 * k + 1], mb2, rb); }
}
__device__ __forceinline__ uint32_t pair_of(const uint2* mp, int k, int cw) {
    return (k < 8 ? mp[(k >> 1) * 64 + (k & 1) * 4] : (mp - cw * 4)[256]).x;
}

__device__ __forceinline__ uint4 h_frag(const uint4* hf, int ks, int lane) {
    if (ks < 32) return ld_relaxed2(hf + ks * 32);
    const uint2* p = reinterpret_cast<const uint2*>(padd(hf, 256 - lane * 8) + ks * 32 - 16);
    const uint2 a = ld_relaxed64(p), b = ld_relaxed64(p + 32);
    return make_uint4(a.x, a.y, b.x, b.y);
}

__device__ __noinline__ void attn_fallback(uint32_t bad, uint32_t tag, uint8_t* frag, uint8_t* keep, const bf16* wq, const bf16* kc, const bf16* vc) {
  const Scratch* gs = &g_s;
  const int lane = threadIdx.x & 31, g8 = lane >> 2, qd = lane & 3;
  const int j = cluster_role() & 7, qb = (cluster_role() >> 3) * 2 + (blockIdx.x & 1);
  const uint4* hf = g_h + (size_t)(qb * 8 + (threadIdx.x >> 5) - 4) * (36 * 32) + lane;
#pragma unroll 1
  for (int t = 0; t < 4; t++) {
    if (!((bad >> t) & 1)) continue;
    const bf16 *wqp = wq + (4 * j + t) * DH, *kp = kc + (size_t)(2 * j + (t >> 1)) * S_ * DH, *vp = vc + (size_t)(2 * j + (t >> 1)) * S_ * DH;
    uint32_t q[32];
    float o[64];
#pragma unroll
    for (int i = 0; i < 64; i++) o[i] = 0.f;
#pragma unroll 1
    for (int ks = 0; ks < 36; ks++) {
        const uint4 a = h_frag(hf, ks, lane);
        const unsigned short* wr = reinterpret_cast<const unsigned short*>(wqp + (size_t)(ks * 16 + 2 * qd) * QD + g8);
#pragma unroll
        for (int dt = 0; dt < 16; dt++) {
            const uint32_t b0 = __ldg(wr + dt * 8) | ((uint32_t)__ldg(wr + dt * 8 + QD) << 16);
            const uint32_t b1 = __ldg(wr + dt * 8 + 8 * QD) | ((uint32_t)__ldg(wr + dt * 8 + 9 * QD) << 16);
            mma16816(o + 4 * dt, a.x, a.y, a.z, a.w, b0, b1);
        }
    }
#pragma unroll
    for (int i = 0; i < 32; i++) q[i] = pack_bf16(o[2 * i], o[2 * i + 1]);
#pragma unroll
    for (int i = 0; i < 64; i++) o[i] = 0.f;
    float m0 = -INFINITY, m1 = -INFINITY, l0 = 0.f, l1 = 0.f;
#pragma unroll 1
    for (int key = 0; key < S_; key += 16) {
        float sc[8];
#pragma unroll
        for (int i = 0; i < 8; i++) sc[i] = 0.f;
#pragma unroll
        for (int nt = 0; nt < 2; nt++) {
            const uint32_t* kr = reinterpret_cast<const uint32_t*>(kp + (size_t)(key + nt * 8 + g8) * DH) + qd;
#pragma unroll
            for (int ks = 0; ks < 8; ks++)
                mma16816(sc + 4 * nt, q[4 * ks], q[4 * ks + 1], q[4 * ks + 2], q[4 * ks + 3], __ldg(kr + ks * 8), __ldg(kr + ks * 8 + 4));
        }
        const float n0 = quad_max(fmaxf(fmaxf(m0, fmaxf(sc[0], sc[1])), fmaxf(sc[4], sc[5])));
        const float n1 = quad_max(fmaxf(fmaxf(m1, fmaxf(sc[2], sc[3])), fmaxf(sc[6], sc[7])));
        const float f0 = ex2((m0 - n0) * CS), f1 = ex2((m1 - n1) * CS);
        m0 = n0; m1 = n1;
#pragma unroll
        for (int i = 0; i < 8; i++) sc[i] = ex2((sc[i] - ((i & 2) ? n1 : n0)) * CS);
        l0 = l0 * f0 + (sc[0] + sc[1]) + (sc[4] + sc[5]);
        l1 = l1 * f1 + (sc[2] + sc[3]) + (sc[6] + sc[7]);
        const uint32_t e0 = pack_bf16(sc[0], sc[1]), e1 = pack_bf16(sc[2], sc[3]), e2 = pack_bf16(sc[4], sc[5]), e3 = pack_bf16(sc[6], sc[7]);
        const unsigned short* vr = reinterpret_cast<const unsigned short*>(vp + (size_t)(key + 2 * qd) * DH + g8);
#pragma unroll
        for (int dt = 0; dt < 16; dt++) {
            o[4 * dt] *= f0; o[4 * dt + 1] *= f0; o[4 * dt + 2] *= f1; o[4 * dt + 3] *= f1;
            const uint32_t b0 = __ldg(vr + dt * 8) | ((uint32_t)__ldg(vr + dt * 8 + DH) << 16);
            const uint32_t b1 = __ldg(vr + dt * 8 + 8 * DH) | ((uint32_t)__ldg(vr + dt * 8 + 9 * DH) << 16);
            mma16816(o + 4 * dt, e0, e1, e2, e3, b0, b1);
        }
    }
    const float i0 = 1.f / quad_sum(l0), i1 = 1.f / quad_sum(l1);
#pragma unroll
    for (int i = 0; i < 16; i++) {
        q[2 * i] = pack_bf16(o[4 * i] * i0, o[4 * i + 1] * i0);
        q[2 * i + 1] = pack_bf16(o[4 * i + 2] * i1, o[4 * i + 3] * i1);
    }
    frag_store(t < 3 ? frag + t * 4096 : keep, q);
  }
}

__device__ __forceinline__ void spare_q3(Scratch* gs, uint32_t sb, uint32_t bar_full, uint32_t bar_empty, int lane, int cw) {
    const uint32_t tag = load_tag(gs);
    uint32_t rel_base, e = 3;
    asm("mapa.shared::cluster.u32 %0, %1, %2;" : "=r"(rel_base) : "r"(bar_empty), "r"(lane & 1));
#pragma unroll 1
    for (int qb = blockIdx.x - NCTA; qb < 16; qb += 4) {
        uint32_t h[144];
        float o[64];
        flag_wait(&g_flag_h[(qb * 8 + cw) * 32], tag);
        const uint4* hf = g_h + (size_t)(qb * 8 + cw) * (36 * 32) + lane;
#pragma unroll
        for (int ks = 0; ks < 36; ks++) {
            const uint4 v = h_frag(hf, ks, lane);
            h[4 * ks] = v.x; h[4 * ks + 1] = v.y; h[4 * ks + 2] = v.z; h[4 * ks + 3] = v.w;
        }
#pragma unroll
        for (int i = 0; i < 64; i++) o[i] = 0.f;
#pragma unroll 1
        for (int v = 0; v < 4; v++) {
            fence_regs(o);
#pragma unroll
            for (int t = 0; t < 5; t++) {
                mbar_wait(bar_full + 8 * (e & 3), (e >> 2) & 1);
                const uint64_t dv = mkdesc(sb + (e & 3) * SLOT, UNIT, 1024);
                WG_FENCE();
#pragma unroll
                for (int ks = 0; ks < (t < 4 ? 8 : 4); ks++)
                    mma_rs128<1>(o, h[32 * t + 4 * ks], h[32 * t + 4 * ks + 1], h[32 * t + 4 * ks + 2], h[32 * t + 4 * ks + 3], dv + ks * 128, ks | t);
                WG_COMMIT();
                if (t > 0) { WG_WAIT(1); if (lane < 2) mbar_arrive_cluster(rel_base + 8 * ((e - 1) & 3)); }
                e++;
            }
            WG_WAIT(0);
            fence_regs(o);
            if (lane < 2) mbar_arrive_cluster(rel_base + 8 * ((e - 1) & 3));
            uint4* dst = &g_q3[((qb * 8 + 2 * v) * 8 + cw) * 128 + lane];
#pragma unroll
            for (int i = 0; i < 8; i++)
                __stcg(dst + (i >> 2) * 1024 + (i & 3) * 32, make_uint4(pack_bf16(o[8 * i], o[8 * i + 1]), pack_bf16(o[8 * i + 2], o[8 * i + 3]),
                                                                        pack_bf16(o[8 * i + 4], o[8 * i + 5]), pack_bf16(o[8 * i + 6], o[8 * i + 7])));
        }
        bar_sync(3, 256);
        if (cw == 0 && lane == 0) flag_release(&g_flag_q3[qb * 32], tag);
        __syncwarp();
    }
}

template <bool SPARE>
__global__ void __cluster_dims__(2, 1, 1) __launch_bounds__(384, 1)
fused_kernel(const Args args, const __grid_constant__ CUtensorMap tm_wq,
             const __grid_constant__ CUtensorMap tm_k, const __grid_constant__ CUtensorMap tm_v,
             const __grid_constant__ CUtensorMap tm_wo, const __grid_constant__ CUtensorMap tm_p,
             const __grid_constant__ CUtensorMap tm_x, const __grid_constant__ CUtensorMap tm_d,
             const __grid_constant__ CUtensorMap tm_g, const __grid_constant__ CUtensorMap tm_u) {
    extern __shared__ __align__(1024) uint8_t smem_raw[];
    const uint32_t sb = smem_u32(smem_raw);
    Scratch* const gs = args.gs;
    const uint32_t bar_full = sb + SM_BAR;
    const uint32_t bar_g = bar_full + 8 * 4;
    const uint32_t bar_mod = bar_g + 8;
    const uint32_t bar_go = bar_mod + 8;
    const uint32_t bar_x = bar_go + 40;
    const uint32_t bar_empty = bar_x + 8;
    const uint32_t bar_pub = bar_empty + 8 * 4;
    const uint32_t bar_qfree = bar_pub + 32;
    const uint32_t bar_out = bar_qfree + 24;
    const uint32_t bar_q3 = bar_out + 8;
    const uint32_t bar_pre = bar_q3 + 16;
    const uint32_t bar_w0 = bar_q3 + 8;
    constexpr int E0 = SPARE ? 2 : 0;

    const int c = blockIdx.x & 1;
    const int role = cluster_role();
    const int j = role & 7;
    const int qb = (role >> 3) * 2 + c;
    const int rg = qb * 8 + j;
    const int warp = __shfl_sync(0xffffffffu, threadIdx.x >> 5, 0);

    if (SPARE && blockIdx.x >= NCTA && warp >= 4) {
        asm volatile("barrier.cluster.arrive.relaxed.aligned;" ::: "memory");
        asm volatile("setmaxnreg.inc.sync.aligned.u32 240;");
        asm volatile("barrier.cluster.wait.aligned;" ::: "memory");
        spare_q3(gs, sb, bar_full, bar_empty, threadIdx.x & 31, warp - 4);
        asm volatile("barrier.cluster.arrive.relaxed.aligned;\nbarrier.cluster.wait.aligned;" ::: "memory");
    } else if (warp < 4) {
        asm volatile("setmaxnreg.dec.sync.aligned.u32 24;");
        int lane;
        asm volatile("mov.u32 %0, %%laneid;" : "=r"(lane));
        if (warp == 2 && elect()) {
            if (TMPF) asm volatile("prefetch.tensormap [%0];" ::"l"(&tm_x) : "memory");
#pragma unroll
            for (int i = 0; i < 27; i++) mbar_init(bar_full + 8 * i, i < 12 || i >= 23 ? 1 : i < 16 ? 16 : 8);
#pragma unroll
            for (int i = 0; i <= E0; i++) {
                mbar_arrive(bar_full + 8 * i);
                asm volatile("mbarrier.arrive.shared::cta.b64 _, [%0], 16;" ::"r"(bar_empty + 8 * i) : "memory");
            }
            asm volatile("fence.mbarrier_init.release.cluster;" ::: "memory");
        }
        __syncwarp();
        asm volatile("barrier.cluster.arrive.relaxed.aligned;" ::: "memory");
        if (warp == 2 && !(SPARE && blockIdx.x >= NCTA)) {
            if (XDELAY) __nanosleep(XDELAY);
            if (elect()) {
                mbar_expect_tx(bar_x, 16 * XP);
                tma2d(sb + SM_Q, &tm_x, 0, rg * 16, bar_x);
            }
            __syncwarp();
        }
        asm volatile("barrier.cluster.wait.aligned;" ::: "memory");
        const uint32_t tag = load_tag(gs);
        if (SPARE && blockIdx.x >= NCTA) {
            if (warp == 1) {
#pragma unroll 1
                for (int e = 3; e < 83; e++) {
                    const int v = (e - 3) / 5;
                    mbar_wait_sleep(bar_empty + 8 * (e & 3), ~(e >> 2) & 1);
                    if (elect()) {
                        mbar_expect_tx(bar_full + 8 * (e & 3), SLOT);
                        tma2d_mc(sb + (e & 3) * SLOT + c * UNIT, &tm_wq, (8 * (v & 3) + 4 * c + 3) * DH + 64, (e - 3 - v * 5) * 128,
                                 bar_full + 8 * (e & 3), EVICT_NORMAL);
                    }
                }
            }
            __syncwarp();
            asm volatile("barrier.cluster.arrive.relaxed.aligned;\nbarrier.cluster.wait.aligned;" ::: "memory");
            return;
        }
        if (warp == 3) {
#pragma unroll 1
            for (int e = 4; e < 20; e++) {
                __nanosleep(e == 4 ? PFD0 : PFD1);
                const int hd = (e * 52) >> 8, row = (e - hd * 5) * 128 + qb * 8 + (lane >> 1);
                if (lane < 16 && row < D_)
                    asm volatile("prefetch.global.L2 [%0];" ::"l"(padd(args.wq, (row * QD + (4 * j + ((0x1320 >> (4 * hd)) & 3)) * DH + (lane & 1) * 64) * 2)) : "memory");
            }
            __syncwarp();
            mbar_wait_sleep(bar_go, 0);
#pragma unroll 1
            for (int unit = 72 + blockIdx.x; unit < 216; unit += NCTA) {
                float a[8];
#pragma unroll
                for (int i = 0; i < 8; i++) a[i] = 0.f;
#pragma unroll 1
                for (int k = lane >> 1; k < D_; k += 16) {
                    const float cv = __bfloat162float(*padd(args.cvec, k * 2));
                    mod_fma(a, __ldg(reinterpret_cast<const uint4*>(padd(args.w_mod, (k * (6 * D_) + unit * 16 + (lane & 1) * 8) * 2))), rbf(cv * sigmoidf_(cv)));
                }
                const float v = mod_reduce(a, lane), v1 = __shfl_down_sync(0xffffffffu, v, 8);
                if (lane < 8) *padd(gs->mod2, ((unit - 72) * 8 + (lane & 1) * 4 + (lane & 2) + (lane >> 2)) * 4) = pack_bf16(v, v1);
            }
            __syncwarp();
            if (lane == 0) flag_release(padd(g_flag_mod, blockIdx.x * 4), tag);
#pragma unroll 1
            for (int k = 0; k < 36 * HSENT; k++) {
                __nanosleep(200);
                __stcg(padd(gs->h[0], (~tag & 1) * (NCTA * 36 * 512) + ((rg * 36 + k) * 32 + lane) * 16), make_uint4(0, 0, 0, 0));
            }
            __syncwarp();
            mbar_wait_sleep(bar_qfree + 16, 0);
            __nanosleep(2000);
            {
                uint4 v;
                uint32_t it = 0;
#pragma unroll 1
                do {
                    v = ld_relaxed(reinterpret_cast<const uint4*>(padd(g_flag_mod, lane * 16)));
                } while (((v.x ^ tag) | (v.y ^ tag) | (v.z ^ tag) | (v.w ^ tag)) && ++it < SPIN / 16);
                asm volatile("fence.acquire.gpu;" ::: "memory");
            }
            __syncwarp();
            {
                float w1 = 0.f, w2 = 0.f;
#pragma unroll 1
                for (int k = lane; k < D_ / 2; k += 32) {
                    const uint32_t* mp = padd(gs->mod2, k * 4);
                    const uint32_t sv = __ldcg(mp + D_ / 2), c1 = badd2(__ldcg(mp + D_), 0x3f803f80u);
                    const uint32_t wr = *reinterpret_cast<const uint32_t*>(padd(args.w_r, k * 4)), wp = bmul2(c1, wr);
                    reinterpret_cast<uint2*>(smem_raw + SM_T)[k] = make_uint2(__ldcg(mp), wp);
                    reinterpret_cast<uint2*>(smem_raw + SM_TC)[k] = make_uint2(c1, sv);
                    reinterpret_cast<uint32_t*>(smem_raw + SM_TG)[k] = __ldcg(mp + 3 * D_ / 2);
                    w1 += bf_lo(wp) + bf_hi(wp);
                    w2 += bf_lo(sv) * bf_lo(wr) + bf_hi(sv) * bf_hi(wr);
                }
#pragma unroll 1
                for (int i = 1; i < 32; i <<= 1) { w1 += __shfl_xor_sync(0xffffffffu, w1, i); w2 += __shfl_xor_sync(0xffffffffu, w2, i); }
                *reinterpret_cast<float2*>(smem_raw + SM_TS) = make_float2(w1, w2);
            }
#pragma unroll
            for (int i = 0; i < 4; i++) reinterpret_cast<uint4*>(smem_raw + SM_RED)[lane + 32 * i] = make_uint4(~0u, ~0u, ~0u, ~0u);
            asm volatile("fence.proxy.async.shared::cta;" ::: "memory");
            __syncwarp();
            if (elect()) {
                uint8_t* mb = g_frag + (size_t)rg * 8 * WREG + 3 * 4096;
#pragma unroll 1
                for (int k = 0; k < 8; k++, mb += WREG) {
#pragma unroll
                    for (int i = 0; i < 3; i++)
                        asm volatile("cp.async.bulk.global.shared::cta.bulk_group [%0], [%1], 2048;" ::"l"(mb + i * 2048), "r"(sb + SM_RED) : "memory");
                    __nanosleep(500);
                }
                asm volatile("cp.async.bulk.commit_group;\ncp.async.bulk.wait_group 0;\nfence.proxy.async.global;" ::: "memory");
            }
            __syncwarp();
            if (lane == 0) mbar_arrive(bar_mod);
            __syncwarp();
            mbar_wait_sleep(bar_go + 8, 0);
            if (lane < 3) asm volatile("prefetch.tensormap [%0];" ::"l"(lane == 0 ? &tm_x : lane == 1 ? &tm_p : &tm_d) : "memory");
            __syncwarp();
            mbar_wait_sleep(bar_go + 8 * 2, 0);
            uint32_t acc = 0;
#pragma unroll 1
            for (int k = lane; k < 16 * 9; k += 32) acc |= touch(padd(args.x, (rg * 16 * D_ + k * 64) * 2));
            if (acc == 0) reinterpret_cast<volatile uint32_t*>(smem_raw + SM_BAR)[127] = acc;
        } else if (warp == 0) {
#pragma unroll 1
            for (int i = 0; i < 48; i++) {
                if (i == 0 || i == 17 || i == 34) mbar_wait_sleep(bar_qfree + (i >> 4) * 8, 0);
                if (SPARE && i == 17) {
                    flag_wait(&g_flag_q3[qb * 32], tag);
                    if (elect()) {
                        asm volatile("fence.proxy.async.global;" ::: "memory");
                        mbar_expect_tx(bar_q3, UNIT);
#pragma unroll 1
                        for (int k = 0; k < 8; k++) bulk_load(sb + SM_Q + 2 * SLOT + k * 4096 + 2048, &g_q3[(rg * 8 + k) * 128], 2048, bar_q3);
                    }
                }
                __nanosleep(700);
                if (elect()) {
                    asm volatile("mbarrier.expect_tx.shared::cta.b64 [%0], %1;" ::"r"(bar_g), "n"(1920) : "memory");
                    tma2d(sb + SM_Q + i * 1920, i < 24 ? &tm_g : &tm_u, (blockIdx.x * 36) & ~7, (i < 24 ? i : i - 24) * 24, bar_g);
                }
            }
            if (elect()) mbar_arrive(bar_g);
#pragma unroll 1
            for (int i = 0; i < 18; i++) {
                __nanosleep(400);
                if (elect()) l2_prefetch(args.w_down + (size_t)(blockIdx.x * 36 + i * 2) * D_, 4 * D_);
            }
            __syncwarp();
            mbar_wait_sleep(bar_go + 8 * 4, 0);
            uint4* rp = padd(g_rows, (rg * 2 * RSLOT + lane) * 16);
#pragma unroll
            for (int k = 0; k < 9; k++) rp[k * 32] = make_uint4(~0u, ~0u, ~0u, ~0u);
            if (blockIdx.x < 72) {
                uint4* yp = reinterpret_cast<uint4*>(padd(g_ypart, blockIdx.x * NCTA * 64 + lane * 16));
#pragma unroll
                for (int k = 0; k < 16; k++) yp[k * 32] = make_uint4(~0u, ~0u, ~0u, ~0u);
            }
            asm volatile("fence.acq_rel.gpu;" ::: "memory");
            __syncwarp();
            if (lane == 0) mbar_arrive(bar_pre);
        } else if (warp == 1) {
            __nanosleep(QDELAY);
            uint32_t go = bar_go;
            uint64_t marks = 24 | 151 << 8 | 154 << 16 | 159ull << 24 | 165ull << 32;
#pragma unroll 1
            for (int e = E0; e < 168; e++) {
                const CUtensorMap* tm;
                int c0, c1;
                uint64_t pol = EVICT_FIRST;
                if (e == 158 || e == 163) continue;
                if (e < 21 && e != 19) {
                    const int i = SPARE && e < 12 ? e - 2 : e - (e == 20), hd = (i * 52) >> 8;
                    tm = &tm_wq; c0 = (4 * j + ((0x1320 >> (4 * hd)) & 3)) * DH + c * 64; c1 = (i - hd * 5) * 128 - 64;
                    if (SPARE && e >= 12 && e < 15) { c0 = (4 * j + 3) * DH; c1 = (2 * (e - 12) + c) * 128; }
                } else if (e < 148) {
                    const int i = max(e - 20, 0);
                    const bool isk = i == 0 || ((i & 1) && i < 127);
                    const int n = isk ? (i + 1) >> 1 : (i - 1) >> 1;
                    tm = isk ? &tm_k : &tm_v; c0 = c * 64; c1 = (2 * j + (n >> 5)) * S_ + (n & 15) * 128;
                    if (!(i & 32)) pol = EVICT_NORMAL;
                } else {
                    int i = e - 148 - (e > 158) - (e > 163);
                    if (i == 1 || i == 2) i ^= 3;
                    tm = &tm_wo; c0 = (i >> 1) * 64; c1 = (4 * j + ((i & 1) ? 1 + c : 3 * c)) * DH;
                }
                const uint32_t fb = e == E0 ? bar_w0 : bar_full + 8 * (e & 3), d = sb + (e == E0 ? 6 : e & 3) * SLOT;
                if (e >= 24 && e < 152) mbar_wait_sleep(bar_empty + 8 * (e & 3), ~(e >> 2) & 1);
                else if (e != E0) mbar_wait(bar_empty + 8 * (e & 3), ~(e >> 2) & 1);
                if (elect()) {
                    mbar_expect_tx(fb, SLOT);
                    tma2d_mc(d + c * UNIT, tm, c0, c1, fb, pol);
                    const int i = e - PF_KV;
                    if (i >= 0 && i < 128 && !(i & 32))
                        l2_prefetch(((i & 1) ? args.vc : args.kc) + (size_t)((2 * j + (i >> 6)) * S_ + (i & 30) * 64) * DH + qb * 1024, 2048);
                    if (e >= PF_WO && e < PF_WO + 18) l2_prefetch(args.wo + (size_t)blockIdx.x * (QD * D_ / NCTA) + (e - PF_WO) * 1024, 2048);
                    if (e == (marks & 255)) mbar_arrive(go);
                }
                if (e == (marks & 255)) { go += 8; marks >>= 8; }
            }
            asm volatile("fence.proxy.async.global;" ::: "memory");
            mbar_wait(bar_empty, 1);
            if (elect()) {
                mbar_expect_tx(bar_full, 16 * XP);
                tma2d(sb, &tm_x, 0, rg * 16, bar_full);
            }
            mbar_wait(bar_empty + 16, 1);
            if (C3D) __nanosleep(C3D);
            if (elect()) {
                mbar_expect_tx(bar_full + 16, SLOT);
                tma3d(sb + 2 * SLOT, &tm_p, 0, j * 20 + 12, qb * 8, bar_full + 16);
                tma3d(sb + 2 * SLOT + UNIT, &tm_p, 0, j * 20 + 14, qb * 8, bar_full + 16);
            }
            mbar_wait(bar_empty + 24, 1);
            if (C4D) __nanosleep(C4D);
            if (elect()) {
                mbar_expect_tx(bar_full + 24, UNIT);
                tma3d(sb + 3 * SLOT, &tm_p, 0, j * 20 + 16, qb * 8, bar_full + 24);
            }
            mbar_wait(bar_empty + 8, 0);
            mbar_wait(bar_empty + 16, 0);
            if (DD) __nanosleep(DD);
            if (elect()) {
#pragma unroll
                for (int i = 1; i < 3; i++) {
                    mbar_expect_tx(bar_full + 8 * i, 18 * XP);
                    tma2d(sb + i * SLOT, &tm_d, 0, blockIdx.x * 36 + (i - 1) * 18, bar_full + 8 * i);
                }
            }
        } else {
            if (lane < 3) asm volatile("prefetch.tensormap [%0];" ::"l"(lane == 0 ? &tm_k : lane == 1 ? &tm_v : &tm_wo) : "memory");
            if (SPARE && HSENT) {
                mbar_wait_sleep(bar_pub, 0);
                if (lane == 0) flag_release(padd(g_flag_h, rg * 128), tag);
                __syncwarp();
            }
            bar_sync(1, 192);
#pragma unroll 1
            for (uint32_t e = 20; e < 148; e++) {
                mbar_wait_sleep(bar_full + 8 * (e & 3), (e >> 2) & 1);
                if (e & 1) bar_sync(1, 192);
                if (!(e & 1) || e == 147) bar_sync(4, 160);
            }
            mbar_wait_sleep(bar_go + 8, 0);
            mbar_wait(bar_mod, 0);
#pragma unroll 1
            for (int i = 1; i < 4; i++) {
                mbar_wait(bar_pub + 8 * i, 0);
                unsigned int* flags = padd(g_flag_part, (qb * 32 + i * 8 - 8) * 4);
                if (elect()) { flag_release(padd(flags, j * 4), tag); DBG_PG(93); }
                __syncwarp();
                const uint32_t slot = i < 3 ? i + 1 : 1;
                flag_wait(padd(flags, (lane & 7) * 4), tag);
                asm volatile("fence.proxy.async.global;" ::: "memory");
                if (lane == 0 && i == 3) DBG_PG(101);
                mbar_wait(bar_go + 8 + 8 * i, 0);
                mbar_wait(bar_empty + 8 * slot, i != 1);
                if (elect()) {
                    mbar_expect_tx(bar_full + 8 * slot, SLOT);
                    tma3d(sb + slot * SLOT, &tm_p, 0, j * 20 + (i - 1) * 4, qb * 8, bar_full + 8 * slot);
                    tma3d(sb + slot * SLOT + UNIT, &tm_p, 0, j * 20 + (i - 1) * 4 + 2, qb * 8, bar_full + 8 * slot);
                }
            }
        }
        __syncwarp();
        mbar_wait_sleep(bar_out, 0);
        if (OUTD) __nanosleep(OUTD);
        if (elect()) {
            asm volatile("fence.proxy.async.shared::cta;" ::: "memory");
            const int2 sel = reinterpret_cast<const int2*>(smem_raw + SM_RED)[8];
#pragma unroll 1
            for (int i = warp; i < 16; i += 4) {
                const int row = rg * 16 + i;
                if (row != sel.x && row != sel.y)
                    asm volatile("cp.async.bulk.global.shared::cta.bulk_group.L2::cache_hint [%0], [%1], %2, %3;"
                                 ::"l"(args.out + (size_t)row * D_), "r"(sb + i * XP), "n"(D_ * 2), "l"(OUTPOL) : "memory");
            }
            asm volatile("cp.async.bulk.commit_group;\ncp.async.bulk.wait_group 0;" ::: "memory");
        }
    } else {
        uint32_t cv[5] = {0, 0, 0, 0, 0}, tag0 = 0;
        if (blockIdx.x < 72) {
            uint32_t ws;
            int tid;
            asm volatile("mov.u32 %0, smem_raw;\nmov.u32 %1, %%tid.x;" : "=r"(ws), "=r"(tid));
            tid -= 128;
            ws += SM_Q + SLOT + tid * 16;
            const bf16* wrow = args.w_mod + (size_t)(tid >> 1) * (6 * D_) + (tid & 1) * 8 + blockIdx.x * 16;
#pragma unroll
            for (int i = 0; i < 5; i++)
                if (i < 4 || tid < 128) {
                    asm volatile("cp.async.cg.shared.global [%0], [%1], 16;" ::"r"(ws + i * 4096), "l"(wrow + (size_t)i * 128 * (6 * D_)) : "memory");
                    cv[i] = reinterpret_cast<const unsigned short*>(args.cvec)[(tid >> 1) + i * 128];
                }
            tag0 = load_tag(gs) - 1;
        }
        asm volatile("barrier.cluster.arrive.relaxed.aligned;" ::: "memory");
        asm volatile("setmaxnreg.inc.sync.aligned.u32 240;");
        const int lane = threadIdx.x & 31;
        const int cw = warp - 4;
        const int w = cw >> 2;
        const int tid = threadIdx.x - 128;
        float* red = reinterpret_cast<float*>(smem_raw + SM_RED);
        DBG_INIT();
        DBG_G(120);
        DBG_T(100);

        uint32_t tag;
        {

            if (blockIdx.x < 72) {
                const uint32_t ws = sb + SM_Q + SLOT + tid * 16;
                float sc[5], a[8];
#pragma unroll
                for (int i = 0; i < 5; i++) sc[i] = __uint_as_float(cv[i] << 16);
#pragma unroll
                for (int i = 0; i < 5; i++) sc[i] = rbf(sc[i] * sigmoidf_(sc[i]));
#pragma unroll
                for (int i = 0; i < 8; i++) a[i] = 0.f;
                anchor(bar_full + 504, sc[0] + sc[1] + sc[2] + sc[3] + sc[4] + 2.f);
                asm volatile("cp.async.wait_all;" ::: "memory");
#pragma unroll
                for (int i = 0; i < 5; i++) mod_fma(a, lds128(ws + (i < 4 || tid < 128 ? i * 4096 : 0)), sc[i]);
                const float v = mod_reduce(a, lane);
                if (lane < 16) red[cw * 16 + lane] = v;

                bar_sync(3, 256);
                if (tid < 8 * MREP) {
                    float v0 = 0.f, v1 = 0.f;
#pragma unroll
                    for (int i = 0; i < 8; i++) { v0 += red[i * 16 + (tid & 7)]; v1 += red[i * 16 + 8 + (tid & 7)]; }
                    st_relaxed64(&gs->mod1[(tid >> 3) * D_ + blockIdx.x * 8 + (tid & 1) * 4 + (tid & 2) + ((tid >> 2) & 1)], pack_bf16(v0, v1), tag0 + 1);
                }
            }
            DBG_G(106);
            asm volatile("barrier.cluster.wait.aligned;" ::: "memory");
            mbar_wait(bar_x, 0);
            tag = load_tag(gs);
            uint32_t x[20];
            float st[12];
            rows_load(x, sb + SM_Q + (lane & 15) * XP + (lane >> 4) * 16 + cw * 32, cw);
#pragma unroll
            for (int i = 0; i < 12; i++) st[i] = 0.f;
#pragma unroll
            for (int k = 0; k < 9; k++) stats_add(st, x[2 * k], x[2 * k + 1], 0x3f803f80u);
            uint32_t mean2;
            float dot;
            const float rsd = rows_stats(st, reinterpret_cast<float4*>(red + 128), cw, lane, mean2, dot);
            rows_normalise(x, x, mean2, rsd, lane, []() {});
            fence_regs(x);
            uint4* smod = reinterpret_cast<uint4*>(smem_raw + SM_Q + M_MOD);
            if (tid < D_ / 4) {
                const uint4* mp = reinterpret_cast<const uint4*>(gs->mod1 + ((blockIdx.x >> 1) & (MREP - 1)) * D_) + tid;
                poll2x2(mp, mp + D_ / 4, tag, smod[tid], smod[D_ / 4 + tid]);
            }
            bar_sync(3, 256);
            DBG_G(107);
            const uint2* mp = reinterpret_cast<const uint2*>(smod) + cw * 8 + (lane & 3);
#pragma unroll
            for (int k = 0; k < 9; k++) {
                const uint32_t c1 = badd2(pair_of(mp + D_ / 2, k, cw), 0x3f803f80u), sa = pair_of(mp, k, cw);
                x[2 * k] = badd2(bmul2(x[2 * k], c1), sa);
                if (x[2 * k] == 0) x[2 * k] = 0x8000u;
                x[2 * k + 1] = badd2(bmul2(x[2 * k + 1], c1), sa);
            }
            uint4* hdst = g_h + (size_t)(rg * 36 + cw) * 32 + lane;
#pragma unroll
            for (int ch = 0; ch < 4; ch++) st_relaxed(hdst + ch * 256, x[4 * ch], x[4 * ch + 1], x[4 * ch + 2], x[4 * ch + 3]);
            st_relaxed64(reinterpret_cast<uint2*>(g_h + (size_t)(rg * 36 + 32) * 32) + tid, x[16], x[17]);
            __syncwarp();
            if (SPARE && lane == 0) mbar_arrive(bar_pub);
            DBG_G(108);
        }

        uint32_t rel_base;
        asm("mapa.shared::cluster.u32 %0, %1, %2;" : "=r"(rel_base) : "r"(bar_empty), "r"(lane & 1));
        auto release = [&](uint32_t slot) { if (lane < 2) mbar_arrive_cluster(rel_base + 8 * slot); };
        uint32_t q[32], p[32];
        float s[64], o[64];

        uint4* qpark = reinterpret_cast<uint4*>(smem_raw + SM_Q - SLOT) + cw * 256 + lane;
        {
            uint32_t h[144];
            const uint4* hf = g_h + (size_t)(qb * 8 + cw) * (36 * 32) + lane;
            auto load_h = [&](auto lo, auto hi) {
#pragma unroll
                for (int ks = lo.value; ks < hi.value; ks++) {
                    const uint4 v = h_frag(hf, ks, lane);
                    h[4 * ks] = v.x; h[4 * ks + 1] = v.y; h[4 * ks + 2] = v.z; h[4 * ks + 3] = v.w;
                }
            };
            auto check_h = [&](auto lo, auto hi) {
                uint32_t it = 0;
#pragma unroll 1
                while (true) {
                    uint32_t mn = ~0u;
#pragma unroll
                    for (int ks = lo.value; ks < hi.value; ks++) mn = __vimin3_u32(mn, h[4 * ks], h[4 * ks + 2]);
                    if (!__any_sync(0xffffffffu, mn == 0) || ++it >= SPIN / 16) break;
                    load_h(lo, hi);
                }
            };
            if (!HSENT) flag_wait(&g_flag_h[(qb * 8 + cw) * 32], tag);
            if (HSENT) __nanosleep(HDELAY);
            load_h(IC<0>{}, IC<4>{});
            DBG_T(104); DBG_G(109);
#pragma unroll
            for (int i = 0; i < 64; i++) o[i] = 0.f;
            uint32_t e = E0;
#pragma unroll 1
            for (int hd = 1;; hd++) {
                fence_regs(o);
                auto group = [&](auto tc) {
                    constexpr int t = tc.value, k0 = t ? 8 * t - 4 : 0;
                    const bool first = t == 0 && hd == 1;
                    mbar_wait(first ? bar_w0 : bar_full + 8 * (e & 3), (e >> 2) & 1);
                    const uint32_t dv = desc_lo(t ? 0 : 8192, UNIT) + (first ? 6 : e & 3) * (SLOT / 16);
                    if (HSENT && hd == 1) check_h(IC<k0>{}, IC<8 * t + 4>{});
                    WG_FENCE();
#pragma unroll
                    for (int ks = k0; ks < 8 * t + 4; ks++)
                        mma_rs128<1>(o, h[4 * ks], h[4 * ks + 1], h[4 * ks + 2], h[4 * ks + 3], desc_of(dv + (ks - k0) * 128), ks);
                    WG_COMMIT();
                    if (hd == 1) { if (t == 0) {   } if (t == 1) {   } if (t == 2) {   } if (t == 3) {   } if (t == 4) {   } }
                    if (t < 4 && hd == 1) load_h(IC<8 * t + 4>{}, IC<t < 4 ? 8 * t + 12 : 0>{});
                    if (t > 0) { WG_WAIT(1); if (t > 1 || hd > 1) release((e - 1) & 3); }
                    e++;
                };
                group(IC<0>{}); group(IC<1>{}); group(IC<2>{}); group(IC<3>{});
                if (e == 19) break;
                group(IC<4>{});
                WG_WAIT(0);
                if (hd == 1) {     }
                fence_regs(o);
                release((e - 1) & 3);
#pragma unroll
                for (int i = 0; i < 8; i++)
                    qpark[hd * 2048 + i * 32] = make_uint4(pack_bf16(o[8 * i], o[8 * i + 1]), pack_bf16(o[8 * i + 2], o[8 * i + 3]),
                                                           pack_bf16(o[8 * i + 4], o[8 * i + 5]), pack_bf16(o[8 * i + 6], o[8 * i + 7]));
                if (SPARE && hd == 2) {
                    float (&u)[32] = reinterpret_cast<float (&)[32]>(o);
                    fence_regs(u);
#pragma unroll
                    for (int t = 0; t < 3; t++) {
                        mbar_wait(bar_full + 8 * t, 1);
                        WG_FENCE();
#pragma unroll
                        for (int ks = 0; ks < (t < 2 ? 16 : 4); ks++)
                            mma_rs64<1>(u, h[64 * t + 4 * ks], h[64 * t + 4 * ks + 1], h[64 * t + 4 * ks + 2], h[64 * t + 4 * ks + 3],
                                        desc_of(desc_lo(t * SLOT, UNIT) + ks * 128), ks | t);
                        WG_COMMIT();
                        if (t > 0) { WG_WAIT(1); release(t - 1); }
                    }
                    WG_WAIT(0);
                    fence_regs(u);
                    release(2);
                    e = 15;
#pragma unroll
                    for (int i = 0; i < 4; i++)
                        qpark[3 * 2048 + i * 32] = make_uint4(pack_bf16(u[8 * i], u[8 * i + 1]), pack_bf16(u[8 * i + 2], u[8 * i + 3]),
                                                              pack_bf16(u[8 * i + 4], u[8 * i + 5]), pack_bf16(u[8 * i + 6], u[8 * i + 7]));
                }
            }
#pragma unroll
            for (int i = 0; i < 8; i++) {
                const uint4 v = qpark[2048 + i * 32];
                q[4 * i] = v.x; q[4 * i + 1] = v.y; q[4 * i + 2] = v.z; q[4 * i + 3] = v.w;
            }
#pragma unroll
            for (int i = 0; i < 32; i++) p[i] = h[112 + i];
            mbar_wait(bar_full + 24, 0);
            WG_WAIT(0);
            fence_regs(o);
            release(2);
        }
        DBG_T(105);
        DBG_G(125);

        uint8_t* frag = reinterpret_cast<uint8_t*>(__shfl_sync(0xffffffffu, reinterpret_cast<unsigned long long>(g_frag + (size_t)(rg * 8 + cw) * WREG + lane * 16), lane));
        const uint4* qnext = reinterpret_cast<const uint4*>(__shfl_sync(0xffffffffu, reinterpret_cast<unsigned long long>(padd(smem_raw, SM_Q + tid * 16 + cw * 3584)), lane));
        uint8_t* odst = reinterpret_cast<uint8_t*>(const_cast<uint4*>(qnext));
        float m0 = 0.f, m1 = 0.f, l0 = 0.f, l1 = 0.f, t0 = 1.f, t1 = 1.f;
        uint32_t bad = 0;
        const int lw = cw & 3;
        const uint32_t relw = lw == RW && lane < 8, handw = lw == HW || cw == HW2;
        auto release4 = [&](uint32_t off) {
            asm volatile("{\n.reg .pred p;\nsetp.ne.b32 p, %1, 0;\n@p mbarrier.arrive.shared::cluster.b64 _, [%0];\n}" ::"r"(rel_base + off), "r"(relw) : "memory"); };
        auto handoff = [&]() {
            asm volatile("{\n.reg .pred p;\nsetp.ne.b32 p, %1, 0;\n@p bar.arrive %0, 192;\n}" ::"r"(2 - w), "r"(handw) : "memory"); };
        if (cw == 4 + HW) bar_arrive(1, 192);
        auto finish = [&](auto lo, auto hi, uint32_t bit, auto sink) {
#pragma unroll
            for (int i = lo.value; i < hi.value; i++) {
                const uint32_t v0 = pack_bf16(o[8 * i] * t0, o[8 * i + 1] * t0), v1 = pack_bf16(o[8 * i + 2] * t1, o[8 * i + 3] * t1);
                const uint32_t v2 = pack_bf16(o[8 * i + 4] * t0, o[8 * i + 5] * t0), v3 = pack_bf16(o[8 * i + 6] * t1, o[8 * i + 7] * t1);
                if (i == 0 && fabsf(o[0] * t0) >= 0x1p-31f) bad |= bit << 8;
                sink(i, v0, v1, v2, v3);
            }
        };
        auto row_sums = [&](uint32_t bit) {
            t0 = quad_sum(l0); t1 = quad_sum(l1);
            if (!(t0 >= LMIN && t0 < LMAX && t1 >= LMIN && t1 < LMAX)) bad |= bit;
            t0 = rcp_fast(t0); t1 = rcp_fast(t1);
            l0 = 0.f; l1 = 0.f;
        };
        auto issue_pv = [&](uint32_t dlo, int acc, auto lo, auto hi) {
            if (lo.value == 0) asm volatile("{\n.reg .pred p;\nsetp.eq.b32 p, %0, 0;\n@p bar.sync 4, 160;\n}" ::"r"(w) : "memory");
#pragma unroll
            for (int ks = lo.value; ks < hi.value; ks++)
                mma_rs128<1>(o, p[4 * ks], p[4 * ks + 1], p[4 * ks + 2], p[4 * ks + 3], desc_of(dlo + ks * 128), ks ? 1 : acc);
            WG_COMMIT();
        };
#pragma unroll
        for (int i = 0; i < 64; i++) s[i] = 0.f;
        uint32_t dv_lo = desc_lo(0, UNIT), voff = 0;
        auto issue_qk = [&]() {
            const uint32_t dk = dv_lo ^ (desc_lo(0, UNIT) ^ desc_lo(3 * SLOT, 16));
            bar_sync(1 + w, 192);
            fence_regs(s); fence_regs(q); fence_regs(o); fence_regs(p);
            WG_FENCE();
#pragma unroll
            for (int ks = 0; ks < 8; ks++)
                mma_rs128<0>(s, q[4 * ks], q[4 * ks + 1], q[4 * ks + 2], q[4 * ks + 3], desc_of(dk + (ks >> 2) * 1024 + (ks & 3) * 2), ks != 0);
            WG_COMMIT();
        };
        auto to_frag = [&](int i, uint32_t v0, uint32_t v1, uint32_t v2, uint32_t v3) {
            *reinterpret_cast<uint4*>(odst + i * 512) = make_uint4(v0, v1, v2, v3); };
        int n = 0;
#pragma unroll 1
        for (;;) {
            issue_qk();
            const int jn = n & 15;
            if (jn == 1) {
                finish(IC<ESPLIT>{}, IC<8>{}, 1u << (n >> 4), to_frag);
                WG_FENCE();
                issue_pv(dv_lo, 0, IC<0>{}, IC<PV1>{});
            } else {
                if (jn == 0 && n > 0) {
                    row_sums(1u << (n >> 4));
                    qnext = n == 48 ? reinterpret_cast<const uint4*>(frag) : qnext + 2048;
                    odst = frag + ((n >> 4) - 1) * 4096;
                    if (elect()) mbar_arrive(bar_qfree + (n >> 1) - 8);
                }
                issue_pv(dv_lo, 1, IC<0>{}, IC<PV1>{});
            }
            if (SPARE && n == 47) mbar_wait(bar_q3, 0);
            WG_WAIT(1);
            fence_regs(s); fence_regs(q);
            if (jn == 15) {
#pragma unroll
                for (int i = 0; i < 8; i++) {
                    const uint4 v = qnext[i * 32];
                    q[4 * i] = v.x; q[4 * i + 1] = v.y; q[4 * i + 2] = v.z; q[4 * i + 3] = v.w;
                }
            }
            if (jn == 0) {
                float a0 = fmaxf(s[0], s[1]), a1 = fmaxf(s[2], s[3]), a2 = fmaxf(s[4], s[5]), a3 = fmaxf(s[6], s[7]);
#pragma unroll
                for (int i = 1; i < MAXG; i++) {
                    a0 = fmaxf(a0, fmaxf(s[8 * i], s[8 * i + 1])); a1 = fmaxf(a1, fmaxf(s[8 * i + 2], s[8 * i + 3]));
                    a2 = fmaxf(a2, fmaxf(s[8 * i + 4], s[8 * i + 5])); a3 = fmaxf(a3, fmaxf(s[8 * i + 6], s[8 * i + 7]));
                }
                const uint32_t a = pack_bf16(fmaxf(a0, a2), fmaxf(a1, a3));
                const uint32_t b = bmax2(bmax2(a, __shfl_xor_sync(0xffffffffu, a, 1)), bmax2(__shfl_xor_sync(0xffffffffu, a, 2), __shfl_xor_sync(0xffffffffu, a, 3)));
                m0 = fmaf(-CS, bf_lo(b), -POFF); m1 = fmaf(-CS, bf_hi(b), -POFF);
            }
            if (PV1 < 8) issue_pv(dv_lo, 1, IC<PV1>{}, IC<8>{});
            release4(voff ^ 24);
            handoff();
#pragma unroll 1
            do {
                DBG_T(n);
#pragma unroll
                for (int i = 0; i < 4 * STAGE; i++) s[i] = fmaf(s[i], CS, (i & 2) ? m1 : m0);
#pragma unroll
                for (int i = 0; i < 4 * SPLIT; i++) s[i] = ex2(s[i]);
#pragma unroll
                for (int i = 0; i < SPLIT; i++) { l0 += s[4 * i] + s[4 * i + 1]; l1 += s[4 * i + 2] + s[4 * i + 3]; }
                if (STAGE < 16) {
                    m0 = fmaf(l0, 0.f, m0); m1 = fmaf(l1, 0.f, m1);
                }
                anchor(bar_full + 504, l0 + l1);
                WG_WAIT(0);
                fence_regs(o); fence_regs(p);
                release4(voff);
                dv_lo ^= 2 * SLOT / 16;
                voff ^= 16;
                n++;
#pragma unroll
                for (int i = 4 * STAGE; i < 64; i++) s[i] = fmaf(s[i], CS, (i & 2) ? m1 : m0);
#pragma unroll
                for (int i = 4 * SPLIT; i < 64; i++) s[i] = ex2(s[i]);
#pragma unroll
                for (int i = SPLIT; i < 16; i++) { l0 += s[4 * i] + s[4 * i + 1]; l1 += s[4 * i + 2] + s[4 * i + 3]; }
#pragma unroll
                for (int i = 0; i < 32; i++) p[i] = pack_bf16(s[2 * i], s[2 * i + 1]);
                if (((n + 1) & 15) < 3) break;
                issue_qk();
                issue_pv(dv_lo, 1, IC<0>{}, IC<8>{});
                WG_WAIT(1);
                fence_regs(s); fence_regs(q);
                release4(voff ^ 24);
                handoff();
            } while (n != 99);
            WG_WAIT(0);
            fence_regs(o); fence_regs(p);
            if ((n & 15) == 1) finish(IC<0>{}, IC<ESPLIT>{}, 1u << (n >> 4), to_frag);
            if (n == 64) break;
        }
        DBG_T(64);
        uint32_t a1[32], a2[32];
        bar_sync(1 + w, 192);
        fence_regs(o); fence_regs(p);
        WG_FENCE();
        issue_pv(desc_lo(3 * SLOT, UNIT), 1, IC<0>{}, IC<8>{});
        if (w == 0) handoff();
        row_sums(16);
        mbar_wait(bar_mod, 0);
        WG_WAIT(0);
        fence_regs(o); fence_regs(p);
        release(3);
        finish(IC<0>{}, IC<8>{}, 16, [&](int i, uint32_t v0, uint32_t v1, uint32_t v2, uint32_t v3) {
            p[4 * i] = v0; p[4 * i + 1] = v1; p[4 * i + 2] = v2; p[4 * i + 3] = v3; });
        bad = __reduce_or_sync(0xffffffffu, bad);
        bad = ((bad | ~(bad >> 8)) >> 1) & 15;
        if (__builtin_expect(bad != 0, 0)) {
            uint8_t* keep = g_keep + (size_t)(rg * 8 + cw) * 4096 + lane * 16;
            frag_store(keep, p);
            attn_fallback(bad, tag, frag, keep, args.wq, args.kc, args.vc);
            frag_load(q, frag); frag_load(p, keep);
        }
        DBG_T(80);
        DBG_G(124);

        const uint32_t eye = (lane >> 3) == (lane & 3) ? 0x3f80u << ((lane & 4) * 4) : 0;
        auto sum8 = [&](uint32_t* r, const uint4 (&v)[8]) {
            float d[16];
#pragma unroll
            for (int i = 0; i < 16; i++) d[i] = 0.f;
#pragma unroll
            for (int src = 0; src < 8; src++) {
                mma1688(d + 8 * (src & 1), v[src].x, v[src].y, eye);
                mma1688(d + 8 * (src & 1) + 4, v[src].z, v[src].w, eye);
            }
#pragma unroll
            for (int i = 0; i < 4; i++) r[i] = pack_bf16(d[2 * i] + d[8 + 2 * i], d[2 * i + 1] + d[9 + 2 * i]);
        };
        auto sum8_slot = [&](uint32_t* r, uint32_t e) {
            mbar_wait(bar_full + 8 * (e & 3), (e >> 2) & 1);
            uint4 v[8];
#pragma unroll
            for (int src = 0; src < 8; src++) v[src] = lds128(sb + (e & 3) * SLOT + w * (UNIT - 2048) + src * 2048 + tid * 16);
            sum8(r, v);
        };
        uint4 v2[8], v3[8], wf[27];
        uint2 u4[8], gw[9];
        uint32_t x1[20], xs, pa, ta;
        const uint8_t *mb, *mb4;
        int tid_;
        auto load_wf = [&](auto lo, auto hi) {
            const uint32_t wa = sb + SM_Q + ((cw & 1) * D_ + (cw >> 1) * 32 + (tid_ & 7) + (tid_ & 16) / 2) * 80 + (tid_ & 8) * 2;
#pragma unroll
            for (int i = lo.value; i < hi.value; i++)
                wf[i] = ldsm4t((i < 24 ? wa + ((i / 3 & 3) * 8 + i / 12) * 1280 : wa + (32 - (cw >> 1)) * 1280) + (i % 3) * 32);
        };
        uint32_t at[18];
        {
            float ua[32], ub[32];
            uint32_t e = 148, prev = 4;
            auto step = [&](float (&u)[32], const uint32_t (&a)[32], const uint32_t (&b)[32], int acc) {
                mbar_wait(bar_full + 8 * (e & 3), (e >> 2) & 1);
                const uint64_t dv = mkdesc(sb + (e & 3) * SLOT, UNIT, 1024);
                if (!acc) fence_regs(u);
                WG_FENCE();
#pragma unroll
                for (int ks = 0; ks < 8; ks++) mma_rs64<1>(u, a[4 * ks], a[4 * ks + 1], a[4 * ks + 2], a[4 * ks + 3], dv + ks * 128, ks | acc);
#pragma unroll
                for (int ks = 0; ks < 8; ks++) mma_rs64<1>(u, b[4 * ks], b[4 * ks + 1], b[4 * ks + 2], b[4 * ks + 3], dv + 1024 + ks * 128, 1);
                WG_COMMIT();
                WG_WAIT(1);
                if (prev < 4) release(prev);
                prev = e & 3;
                e++;
            };
            auto store = [&](float (&u)[32], uint8_t* dst) {
                fence_regs(u);
#pragma unroll
                for (int i = 0; i < 4; i++)
                    st_relaxed4(dst + i * 512, pack_bf16(u[8 * i], u[8 * i + 1]), pack_bf16(u[8 * i + 2], u[8 * i + 3]),
                                pack_bf16(u[8 * i + 4], u[8 * i + 5]), pack_bf16(u[8 * i + 6], u[8 * i + 7]));
            };
#pragma unroll
            for (int i = 0; i < 8; i++) at[i] = 0;
#pragma unroll
            for (int i = 0; i < 32; i++) { ua[i] = 0.f; ub[i] = 0.f; }
            fence_regs(q); fence_regs(p);
            step(ua, q, p, 0);
            frag_load(a1, frag + 4096);
            mbar_wait(bar_full + 8, 1);
            frag_load(a2, frag + 8192);
            step(ub, q, p, 0);
            WG_WAIT(0);
            release(1);
            prev = 4;
            fence_regs(a1); fence_regs(a2); fence_regs(ua); fence_regs(ub);
#pragma unroll 1
            for (int ch = 0; ch < 4; ch++) {
                step(ua, a1, a2, 1);
                if (ch > 0) {
                    if (ch >= 2) {
#pragma unroll
                        for (int i = 0; i < 4; i++) at[i] = at[4 + i];
                        sum8_slot(at + 4, e);
                        __syncwarp();
                        release(e & 3);
                        e++;
                        WG_WAIT(0);
                        release(prev);
                        prev = 4;
                    }
                    step(ub, q, p, 0);
                } else {
                    WG_WAIT(0);
                }
                store(ua, frag + ch * 4096);
                step(ub, a1, a2, 1);
                step(ua, q, p, 0);
                store(ub, frag + ch * 4096 + 2048);
                __syncwarp();
                if (lane == 0 && ch < 3) mbar_arrive(bar_pub + 8 + 8 * ch);
            }
            tid_ = __shfl_sync(0xffffffffu, tid, lane);
            mb = padd(g_frag, (qb * 64 + j) * WREG + 3 * 4096 + tid * 16);
            mb4 = padd(mb, 4096 + ((cw >> 1) - cw) * 512 + (cw & 1) * 8);
            step(ua, a1, a2, 1);
            xs = sb + (tid_ & 15) * XP + (tid_ & 16) + cw * 32;
            pa = sb + w * (UNIT - 2048) + tid_ * 16;
            ta = sb + (cw * 8 + (tid_ & 3)) * 8;
#pragma unroll
            for (int k = 0; k < 9; k++) {
                gw[k] = lds64(ta + SM_T + (k < 8 ? (k >> 1) * 64 + (k & 1) * 4 : 256 - cw * 4) * 8);
                if (!(tid_ & 4)) gw[k].y = 0x3f803f80u;
            }
            mbar_wait(bar_g, 0);
            load_wf(IC<0>{}, IC<WF0>{});
            mbar_wait(bar_full, 0);
            rows_load(x1, xs, cw);
            if (P2E) {
                mbar_wait(bar_full + 8, 0);
#pragma unroll
                for (int src = 0; src < 8; src++) v2[src] = lds128(pa + SLOT + src * 2048);
            }
            WG_WAIT(0);
            release(3);
            store(ua, frag + 4 * 4096);
        }
        DBG_T(81);
        DBG_G(122);

        {
        const int tid = tid_, lane = tid & 31;
        const int g8 = lane >> 2, qd = lane & 3, l16 = lane & 15;
        uint32_t h2[18], gb[9], k1, k2;
        float4* rec = reinterpret_cast<float4*>(red + 128);
        const uint2* candp = reinterpret_cast<const uint2*>(padd(g_cand, ((blockIdx.x & (CREP - 1)) * NCTA + (tid >> 1)) * 32 + (tid & 1) * 8));
        uint2 cd;
        auto stage_out = [&]() {
#pragma unroll
            for (int k = 0; k < 9; k++) {
                x1[2 * k] = badd2(x1[2 * k], bmul2(gb[k], h2[2 * k]));
                x1[2 * k + 1] = badd2(x1[2 * k + 1], bmul2(gb[k], h2[2 * k + 1]));
            }
#pragma unroll
            for (int ch = 0; ch < 4; ch++) stsm_x4(xs + ch * 256, x1[4 * ch], x1[4 * ch + 1], x1[4 * ch + 2], x1[4 * ch + 3]);
            asm volatile("stmatrix.sync.aligned.m8n8.x2.shared.b16 [%0], {%1, %2};" ::"r"(xs + 1024 - cw * 16), "r"(x1[16]), "r"(x1[17]) : "memory");
        };
        {
            uint32_t it = 0, miss;
            if (!P2E) {
                mbar_wait(bar_full + 8, 0);
#pragma unroll
                for (int src = 0; src < 8; src++) v2[src] = lds128(pa + SLOT + src * 2048);
            }
            sum8(at + 8, v2);
            float st[12];
#pragma unroll
            for (int i = 0; i < 12; i++) st[i] = 0.f;
            auto add_pair = [&](int k) {
                x1[2 * k] = badd2(x1[2 * k], bmul2(gw[k].x, at[2 * k]));
                x1[2 * k + 1] = badd2(x1[2 * k + 1], bmul2(gw[k].x, at[2 * k + 1]));
                stats_add(st, x1[2 * k], x1[2 * k + 1], gw[k].y);
            };
#pragma unroll
            for (int k = 0; k < 6; k++) add_pair(k);
            mbar_wait(bar_full + 16, 0);
#pragma unroll
            for (int src = 0; src < 8; src++) v3[src] = lds128(pa + 2 * SLOT + src * 2048);
#pragma unroll 1
            do {
                if (BO && it) __nanosleep(BO);
                miss = 0;
#pragma unroll
                for (int src = 0; src < 8; src++) reload16(v3[src], mb + (size_t)src * 8 * WREG, miss);
            } while (__any_sync(0xffffffffu, miss) && ++it < SPIN / 16);
            if (lane < 4) mbar_arrive_cluster(rel_base + 8 * (1 + (lane >> 1)));
            sum8(at + 12, v3);
            add_pair(6); add_pair(7);
            load_wf(IC<WF0>{}, IC<WF1>{});
            uint2 cs[9];
#pragma unroll
            for (int k = 0; k < 9; k++) cs[k] = lds64(ta + SM_TC + (k < 8 ? (k >> 1) * 64 + (k & 1) * 4 : 256 - cw * 4) * 8);
            mbar_wait(bar_pre, 0);
            mbar_wait(bar_full + 24, 0);
#pragma unroll
            for (int src = 0; src < 8; src++) u4[src] = lds64(sb + 3 * SLOT + src * 2048 + (cw >> 1) * 512 + lane * 16 + (cw & 1) * 8);
#pragma unroll 1
            do {
                if (BO && miss) __nanosleep(BO);
                miss = 0;
#pragma unroll
                for (int src = 0; src < 8; src++) reload8(u4[src], mb4 + (size_t)src * 8 * WREG, miss);
            } while (__any_sync(0xffffffffu, miss) && ++it < SPIN / 16);
            float d[8] = {0.f, 0.f, 0.f, 0.f, 0.f, 0.f, 0.f, 0.f};
#pragma unroll
            for (int i = 0; i < 4; i++) mma16816(d + 4 * (i & 1), u4[2 * i].x, u4[2 * i].y, u4[2 * i + 1].x, u4[2 * i + 1].y, eye, eye);
            at[16] = pack_bf16(d[0] + d[4], d[1] + d[5]); at[17] = pack_bf16(d[2] + d[6], d[3] + d[7]);
            add_pair(8);
            DBG_G(123);
            const float2 ws = *reinterpret_cast<const float2*>(smem_raw + SM_TS);
            uint4* cdst = padd(g_cand, CFULL ? ((tid >> 1) * NCTA + rg) * 32 + (tid & 1) * 16 : (tid * NCTA + rg) * 32);
            uint32_t mean2;
            float dot;
            const float rsd = rows_stats(st, rec, cw, lane, mean2, dot);
            const uint32_t b = __float_as_uint(fmaf(fmaf(-bf_lo(mean2), ws.x, dot), rsd, ws.y));
            const uint32_t key = (((b & 0x80000000u) ? ~b : (b | 0x80000000u)) | 2047u) - (rg * 16 + l16);
            top2(key, k1, k2);
            if (tid < (CFULL + 1) * CREP) st_relaxed(cdst, k1, tag, k2, tag);
            cd = ld_relaxed64(candp);
            rows_normalise(h2, x1, mean2, rsd, lane, [&]() {
#pragma unroll
                for (int k = 0; k < 9; k++) gb[k] = lds32(sb + SM_TG + (cw * 8 + qd + (k < 8 ? (k >> 1) * 64 + (k & 1) * 4 : 256 - cw * 4)) * 4);
                if (WFE) load_wf(IC<WF1>{}, IC<WF2>{});
            });
#pragma unroll
            for (int k = 0; k < 18; k++) h2[k] = badd2(bmul2(h2[k], cs[k >> 1].x), cs[k >> 1].y);
            const uint32_t r1 = ~k1 & 15, r2 = ~k2 & 15;
            uint32_t todo = ((r1 & 7) == g8) | ((r2 & 7) == g8) << 1;
#pragma unroll 1
            while (todo) {
                const bool second = !(todo & 1), hi = (second ? r2 : r1) & 8;
                uint4* dst = padd(g_rows, ((rg * 2 + second) * RSLOT + cw * 16 + qd) * 16);
                uint32_t r[18];
#pragma unroll
                for (int k = 0; k < 9; k++) { r[k] = hi ? h2[2 * k + 1] : h2[2 * k]; r[9 + k] = hi ? x1[2 * k + 1] : x1[2 * k]; }
                fence_regs(r);
                st_relaxed(dst, r[0], r[1], r[2], r[3]);
                st_relaxed(dst + 4, r[4], r[5], r[6], r[7]);
                st_relaxed64(reinterpret_cast<uint2*>(padd(dst, 2048 - cw * 224 - qd * 8)), r[8], r[17]);
                st_relaxed(dst + 8, r[9], r[10], r[11], r[12]);
                st_relaxed(dst + 12, r[13], r[14], r[15], r[16]);
                todo &= todo - 1;
            }
            __syncwarp();

            if (SO == 0) stage_out();
            if (!WFE) load_wf(IC<WF1>{}, IC<WF2>{});
        }
        DBG_G(110);
        float2* part = reinterpret_cast<float2*>(smem_raw + 3 * SLOT + UNIT);
        bf16* act = reinterpret_cast<bf16*>(smem_raw + 3 * SLOT + UNIT + 4096);
        {
            uint32_t it = 0;
            const bool own = (tid >> 1) == rg;
            const uint32_t ks = sb + 3 * SLOT + UNIT + 5120;
#pragma unroll 1
            while (cd.y != tag && !own && ++it < SPIN / 16) cd = ld_relaxed64(candp);
            asm volatile("st.shared.u32 [%0], %1;" ::"r"(ks + tid * 4), "r"(own ? (tid & 1) ? k2 : k1 : cd.x) : "memory");
            bar_sync(3, 256);
            DBG_G(111);
            const uint4 a = lds128(ks + lane * 16), b = lds128(ks + 512 + lane * 16);
            const uint32_t a1 = max(a.x, a.z), a2 = __vimax3_u32(min(a.x, a.z), a.y, a.w);
            const uint32_t b1 = max(b.x, b.z), b2 = __vimax3_u32(min(b.x, b.z), b.y, b.w);
            const uint32_t c1 = max(a1, b1), c2 = __vimax3_u32(min(a1, b1), a2, b2);
            k1 = __reduce_max_sync(0xffffffffu, c1);
            k2 = __reduce_max_sync(0xffffffffu, c1 == k1 ? c2 : c1);
        }
        const int sel0 = ~k1 & 2047, sel1 = ~k2 & 2047;
        const uint32_t slot0 = (sel0 >> 4) * 2, slot1 = (sel1 >> 4) * 2 + ((sel0 ^ sel1) < 16);
        uint4 b[9], b2[3];
        {
            const bool tk = cw < 4 ? cw & 2 : lane & 16;
            const int ri = cw < 4 ? tid & 63 : 64 + l16;
            const uint4* hp = padd(g_rows, ((tk ? slot1 : slot0) * RSLOT + (cw < 4 ? ri + (ri & 56) : ri + 64)) * 16);
            const uint32_t hs = sb + 3 * SLOT + UNIT + 8192;
            uint4 hr = make_uint4(cw < 5 ? ~0u : 0, 0, 0, 0);
            uint32_t it = 0, miss;
            reload16(hr, hp, miss);
            if (OUTP == 0 && SO == 0 && tid == 255) {
                reinterpret_cast<int2*>(red)[8] = make_int2(sel0, sel1);
                mbar_arrive(bar_out);
            }
            if (SO == 1) stage_out();
            load_wf(IC<WF2>{}, IC<27>{});
            mbar_wait(bar_full + 8, 1);
            mbar_wait(bar_full + 16, 1);
            {
                const uint32_t da = sb + (lane < 18 ? SLOT + lane * XP : 2 * SLOT + (lane - 18) * XP) + cw * 144;
                const uint32_t db = sb + 2 * SLOT + (14 + (lane & 3)) * XP + cw * 144 + (lane >> 3) * 16;
#pragma unroll
                for (int i = 0; i < 9; i++) b[i] = ldsm4t(da + i * 16);
#pragma unroll
                for (int i = 0; i < 3; i++) b2[i] = ldsm4t(db + i * 48);
            }
#pragma unroll 1
            do {
                miss = 0;
                reload16(hr, hp, miss);
            } while (__any_sync(0xffffffffu, miss) && ++it < SPIN / 16);
            if (cw < 5) asm volatile("st.shared.v4.u32 [%0], {%1, %2, %3, %4};" ::"r"(hs + (tk * 84 + ri) * 16), "r"(hr.x), "r"(hr.y), "r"(hr.z), "r"(hr.w) : "memory");
            bar_sync(3, 256);
            if (OUTP == 0 && SO == 1 && tid == 255) {
                reinterpret_cast<int2*>(red)[8] = make_int2(sel0, sel1);
                mbar_arrive(bar_out);
            }
            uint4 hv[4];
            uint32_t hw[2];
#pragma unroll
            for (int i = 0; i < 4; i++) hv[i] = lds128(hs + ((g8 & 1) * 84 + (cw >> 1) * 16 + qd + i * 4) * 16);
#pragma unroll
            for (int i = 0; i < 2; i++)
                hw[i] = lds32(hs + ((g8 & 1) * 84 + 64) * 16 + (cw >> 1) * 64 + qd * 8 + i * 32);
            DBG_G(112);
            float acc[24];
#pragma unroll
            for (int i = 0; i < 24; i++) acc[i] = 0.f;
#pragma unroll
            for (int i = 0; i < 27; i++) {
                const int ks = i / 3;
                mma16816(acc + 4 * (i % 6), wf[i].x, wf[i].y, wf[i].z, wf[i].w, ks == 8 ? hw[0] : (ks & 1) ? hv[ks >> 1 & 3].z : hv[ks >> 1 & 3].x,
                         ks == 8 ? hw[1] : (ks & 1) ? hv[ks >> 1 & 3].w : hv[ks >> 1 & 3].y);
            }
            if (qd == 0) {
#pragma unroll
                for (int i = 0; i < 5; i++) part[cw * 48 + i * 8 + g8] = make_float2(acc[2 * i] + acc[12 + 2 * i], acc[2 * i + 1] + acc[13 + 2 * i]);
            }
        }
        {
            uint2* dst = padd(g_ypart, ((((g8 & 1) * 36 + ((cw * 9) >> 1)) * NCTA + blockIdx.x) * 8 + (cw & 1) * 4 + qd) * 8);
            uint2* dst1 = dst + ((cw & 1) ? NCTA * 8 - 4 : 4);
            bar_sync(3, 256);

            {
                const float* pp = reinterpret_cast<const float*>(part) + ((blockIdx.x & 1) << 3) + (tid & 127);
                const float gs = rbf((pp[0] + pp[192]) + (pp[384] + pp[576])), us = rbf((pp[96] + pp[288]) + (pp[480] + pp[672]));
                const float v = rbf(gs * sigmoidf_(gs)) * us;
                if (tid < 80) act[(tid & 1) * 56 + (tid >> 1)] = __float2bfloat16_rn(tid < 72 ? v : 0.f);
            }
            bar_sync(3, 256);
            DBG_G(113);
            const uint32_t ap = sb + 3 * SLOT + UNIT + 4096 + (lane & 1) * 112 + (lane >> 4) * 16;
            const uint4 a0 = ldsm4(ap), a1 = ldsm4(ap + 32), a2 = ldsm4(ap + 64);
            float y[36];
#pragma unroll
            for (int i = 0; i < 36; i++) y[i] = 0.f;
#pragma unroll
            for (int i = 0; i < 9; i++) {
                const uint32_t bl = i % 3 == 0 ? b2[i / 3].x : i % 3 == 1 ? b2[i / 3].y : b2[i / 3].z;
                mma16816(y + 4 * i, a0.x, a0.y, a0.z, a0.w, b[i].x, b[i].y);
                mma16816(y + 4 * i, a1.x, a1.y, a1.z, a1.w, b[i].z, b[i].w);
                mma1688(y + 4 * i, a2.x, a2.y, bl);
            }
#pragma unroll
            for (int i = 0; i < 9; i++)
                if (lane < 8) st_relaxed64(((i & 1) ? dst1 : dst) + (i >> 1) * (NCTA * 8), __float_as_uint(y[4 * i]), __float_as_uint(y[4 * i + 1]));
        }
        DBG_G(114);
        if (OUTP == 1 && tid == 255) {
            reinterpret_cast<int2*>(red)[8] = make_int2(sel0, sel1);
            mbar_arrive(bar_out);
        }
        if (blockIdx.x == 127 && tid == 0) gs->epoch[0] = tag;
        if (blockIdx.x < 72) {
            const int tok = blockIdx.x >= 36, grp = blockIdx.x - tok * 36, cp = grp * 8 + (lane & 7);
            const uint2* src = padd(g_ypart, (blockIdx.x * NCTA * 8 + tid) * 8);
            const uint8_t* hsrc = reinterpret_cast<const uint8_t*>(padd(g_rows, (tok ? slot1 : slot0) * (RSLOT * 16) +
                (grp < 32 ? (grp & 7) * 256 + (grp >> 4) * 64 + qd * 16 + (grp & 8) + (lane & 4) : 2048 + (cp - 256) * 8)));
            const uint8_t* xsrc = hsrc + (grp < 32 ? 128 : 4);
            uint32_t* dst = padd(reinterpret_cast<uint32_t*>(args.out), (tok ? sel1 : sel0) * (D_ * 2) + cp * 4);
            const uint32_t gb = reinterpret_cast<const uint32_t*>(smem_raw + SM_TG)[cp];
            const uint32_t ksel = ((tok ? k2 : k1) & ~2047u) | 1024u;
            const float sg = sigmoidf_(rbf(__uint_as_float((ksel & 0x80000000u) ? (ksel & 0x7fffffffu) : ~ksel)));
            uint2 v[4];
            uint32_t hv, xv, it = 0;
            bool miss;
#pragma unroll 1
            do {
#pragma unroll
                for (int i = 0; i < 4; i++) v[i] = ld_relaxed64(src + i * 256);
                hv = ld_relaxed32(hsrc);
                xv = ld_relaxed32(xsrc);
                miss = max(__vimax3_u32(v[0].x, v[1].x, v[2].x), __vimax3_u32(v[3].x, hv, xv)) == ~0u;
            } while (__any_sync(0xffffffffu, miss) && ++it < SPIN / 16);
            float y0 = (__uint_as_float(v[0].x) + __uint_as_float(v[1].x)) + (__uint_as_float(v[2].x) + __uint_as_float(v[3].x));
            float y1 = (__uint_as_float(v[0].y) + __uint_as_float(v[1].y)) + (__uint_as_float(v[2].y) + __uint_as_float(v[3].y));
            y0 += __shfl_xor_sync(0xffffffffu, y0, 8); y1 += __shfl_xor_sync(0xffffffffu, y1, 8);
            y0 += __shfl_xor_sync(0xffffffffu, y0, 16); y1 += __shfl_xor_sync(0xffffffffu, y1, 16);
            if (lane < 8) reinterpret_cast<float2*>(rec)[cw * 8 + lane] = make_float2(y0, y1);
            bar_sync(3, 256);
            if (cw == 0) {
                const float2 t0_ = reinterpret_cast<const float2*>(rec)[lane], t1_ = reinterpret_cast<const float2*>(rec)[32 + lane];
                y0 = t0_.x + t1_.x; y1 = t0_.y + t1_.y;
                y0 += __shfl_xor_sync(0xffffffffu, y0, 8); y1 += __shfl_xor_sync(0xffffffffu, y1, 8);
                y0 += __shfl_xor_sync(0xffffffffu, y0, 16); y1 += __shfl_xor_sync(0xffffffffu, y1, 16);
                const uint32_t y2 = bmul2(pack_bf16(y0, y1), pack_bf16(sg, sg));
                if (lane < 8) *dst = badd2(xv, bmul2(gb, badd2(hv, y2)));
            }
        }
        }
        DBG_T(88);
        DBG_G(121);
    }
}

typedef CUresult (*EncodeFn)(CUtensorMap*, CUtensorMapDataType, cuuint32_t, void*, const cuuint64_t*, const cuuint64_t*,
                             const cuuint32_t*, const cuuint32_t*, CUtensorMapInterleave, CUtensorMapSwizzle,
                             CUtensorMapL2promotion, CUtensorMapFloatOOBfill);

static void make_map(EncodeFn enc, CUtensorMap* m, const void* ptr, int rank, const cuuint64_t* dims,
                     const cuuint64_t* strides, const cuuint32_t* box, CUtensorMapSwizzle sw = CU_TENSOR_MAP_SWIZZLE_128B,
                     CUtensorMapDataType dt = CU_TENSOR_MAP_DATA_TYPE_BFLOAT16) {
    const cuuint32_t es[3] = {1, 1, 1};
    enc(m, dt, rank, const_cast<void*>(ptr), dims, strides, box, es,
        CU_TENSOR_MAP_INTERLEAVE_NONE, sw, CU_TENSOR_MAP_L2_PROMOTION_L2_128B,
        CU_TENSOR_MAP_FLOAT_OOB_FILL_NONE);
}

extern "C" void kernel_launch(void* const* d_in, const int* in_sizes, int n_in, void* d_out, int out_size) {
    const bf16* x = (const bf16*)d_in[0];
    const bf16* kc = (const bf16*)d_in[1];
    const bf16* vc = (const bf16*)d_in[2];
    const bf16* wq = (const bf16*)d_in[3];
    const bf16* wo = (const bf16*)d_in[4];
    const bf16* w_r = (const bf16*)d_in[6];
    const bf16* w_gate = (const bf16*)d_in[7];
    const bf16* w_up = (const bf16*)d_in[8];
    const bf16* w_down = (const bf16*)d_in[9];
    const bf16* cvec = (const bf16*)d_in[10];
    const bf16* w_mod = (const bf16*)d_in[11];
    bf16* out = (bf16*)d_out;

    void* fn = nullptr;
    cudaDriverEntryPointQueryResult qr;
    cudaGetDriverEntryPoint("cuTensorMapEncodeTiled", &fn, cudaEnableDefault, &qr);
    EncodeFn enc = (EncodeFn)fn;
    void* p_s;
    cudaGetSymbolAddress(&p_s, g_s);

    CUtensorMap tm_wq, tm_k, tm_v, tm_wo, tm_p, tm_x, tm_d, tm_g, tm_u;
    { cuuint64_t d[2] = {QD, D_}, s[1] = {QD * 2}; cuuint32_t b[2] = {64, 128}; make_map(enc, &tm_wq, wq, 2, d, s, b); }
    { cuuint64_t d[2] = {DH, HKV * S_}, s[1] = {DH * 2}; cuuint32_t b[2] = {64, 128};
      make_map(enc, &tm_k, kc, 2, d, s, b); make_map(enc, &tm_v, vc, 2, d, s, b); }
    { cuuint64_t d[2] = {D_, QD}, s[1] = {D_ * 2}; cuuint32_t b[2] = {64, 128}; make_map(enc, &tm_wo, wo, 2, d, s, b); }
    { cuuint64_t d[3] = {256, 160, NCTA}, s[2] = {1024, 8 * WREG}; cuuint32_t b[3] = {256, 2, 8};
      make_map(enc, &tm_p, ((Scratch*)p_s)->frag, 3, d, s, b, CU_TENSOR_MAP_SWIZZLE_NONE, CU_TENSOR_MAP_DATA_TYPE_UINT32); }
    { cuuint64_t d[2] = {D_ / 4, S_}, s[1] = {D_ * 2}; cuuint32_t b[2] = {XP / 8, 16};
      make_map(enc, &tm_x, x, 2, d, s, b, CU_TENSOR_MAP_SWIZZLE_NONE, CU_TENSOR_MAP_DATA_TYPE_UINT64); }
    { cuuint64_t d[2] = {D_ / 4, F_}, s[1] = {D_ * 2}; cuuint32_t b[2] = {XP / 8, 18};
      make_map(enc, &tm_d, w_down, 2, d, s, b, CU_TENSOR_MAP_SWIZZLE_NONE, CU_TENSOR_MAP_DATA_TYPE_UINT64); }
    { cuuint64_t d[2] = {F_, D_}, s[1] = {F_ * 2}; cuuint32_t b[2] = {40, 24};
      make_map(enc, &tm_g, w_gate, 2, d, s, b, CU_TENSOR_MAP_SWIZZLE_NONE); make_map(enc, &tm_u, w_up, 2, d, s, b, CU_TENSOR_MAP_SWIZZLE_NONE); }

    cudaFuncSetAttribute(fused_kernel<true>, cudaFuncAttributeMaxDynamicSharedMemorySize, SM_TOTAL);
    cudaFuncSetAttribute(fused_kernel<false>, cudaFuncAttributeMaxDynamicSharedMemorySize, SM_TOTAL);
    cudaLaunchConfig_t cfg = {};
    cfg.gridDim = NCTA + 4; cfg.blockDim = 384; cfg.dynamicSmemBytes = SM_TOTAL;
    cudaLaunchAttribute at;
    at.id = cudaLaunchAttributeClusterDimension; at.val.clusterDim.x = 2; at.val.clusterDim.y = 1; at.val.clusterDim.z = 1;
    cfg.attrs = &at; cfg.numAttrs = 1;
    int ncl = 0;
    if (cudaOccupancyMaxActiveClusters(&ncl, fused_kernel<true>, &cfg) != cudaSuccess) { ncl = 0; cudaGetLastError(); }
    Args args{w_mod, cvec, (Scratch*)p_s, out, x, kc, vc, wq, wo, w_r, w_down};
    if (USE_SPARE && ncl >= NCTA / 2 + 2)
        fused_kernel<true><<<NCTA + 4, 384, SM_TOTAL>>>(args, tm_wq, tm_k, tm_v, tm_wo, tm_p, tm_x, tm_d, tm_g, tm_u);
    else
        fused_kernel<false><<<NCTA, 384, SM_TOTAL>>>(args, tm_wq, tm_k, tm_v, tm_wo, tm_p, tm_x, tm_d, tm_g, tm_u);
}
```

```cpp
#include <cuda_runtime.h>
#include <cuda_bf16.h>
#include <cuda.h>
#include <stdint.h>
#include <math.h>

typedef __nv_bfloat16 bf16;

constexpr int S_ = 2048;
constexpr int D_ = 576;
constexpr int HQ = 32, HKV = 16, DH = 128;
constexpr int F_ = 4608;
constexpr int QD = HQ * DH;

constexpr int NCTA = 128;
constexpr int WREG = 5 * 4096;
constexpr int CREP = 8;
constexpr int RSLOT = 144;
constexpr int MREP = 4;
struct Scratch {
    unsigned int epoch[128];
    unsigned int flag_mod[NCTA];
    unsigned int flag_part[16 * 32];
    unsigned int flag_q3[16 * 32];
    unsigned int flag_h[NCTA * 32];
    uint2 mod1[MREP * D_];
    uint32_t mod2[4 * D_];
    uint4 cand[CREP * NCTA * 2];
    uint2 ypart[72 * NCTA * 8];
    uint4 h[2][NCTA * 36 * 32];
    uint4 q3[NCTA * 8 * 128];
    uint4 rows[NCTA * 2 * RSLOT];
    uint8_t frag[NCTA * 8 * WREG];
    uint8_t keep[NCTA * 8 * 4096];
};
__device__ __align__(1024) Scratch g_s;
#define g_h gs->h[tag & 1]
#define g_q3 gs->q3
#define g_keep gs->keep
#define g_flag_h gs->flag_h
#define g_flag_part gs->flag_part
#define g_flag_mod gs->flag_mod
#define g_flag_q3 gs->flag_q3
#define g_frag gs->frag
#define g_cand gs->cand
#define g_ypart gs->ypart
#define g_rows gs->rows

#define DBG_INIT()
#define DBG_P(i)
#define DBG_PG(i)
#define DBG_T(i)
#define DBG_G(i)

__device__ __forceinline__ uint32_t pack_bf16(float lo, float hi) {
    uint32_t r;
    asm("cvt.rn.bf16x2.f32 %0, %1, %2;" : "=r"(r) : "f"(hi), "f"(lo));
    return r;
}
__device__ __forceinline__ float rbf(float x) { return __uint_as_float(pack_bf16(0.f, x)); }
__device__ __forceinline__ float bf_lo(uint32_t v) { return __uint_as_float(v << 16); }
__device__ __forceinline__ float bf_hi(uint32_t v) { return __uint_as_float(v & 0xffff0000u); }
__device__ __forceinline__ float ex2(float x) {
    float y;
    asm("ex2.approx.ftz.f32 %0, %1;" : "=f"(y) : "f"(x));
    return y;
}
template <class T>
__device__ __forceinline__ T* padd(T* p, uint32_t off) {
    unsigned long long r;
    asm("{\n.reg .b32 l, h;\nmov.b64 {l, h}, %1;\nadd.cc.u32 l, l, %2;\naddc.u32 h, h, 0;\nmov.b64 %0, {l, h};\n}" : "=l"(r) : "l"(p), "r"(off));
    return reinterpret_cast<T*>(r);
}
__device__ __forceinline__ uint32_t smem_u32(const void* p) { return (uint32_t)__cvta_generic_to_shared(p); }
__device__ __forceinline__ void mbar_init(uint32_t bar, uint32_t cnt) {
    asm volatile("mbarrier.init.shared::cta.b64 [%0], %1;" ::"r"(bar), "r"(cnt) : "memory");
}
__device__ __forceinline__ void mbar_expect_tx(uint32_t bar, uint32_t bytes) {
    asm volatile("mbarrier.arrive.expect_tx.shared::cta.b64 _, [%0], %1;" ::"r"(bar), "r"(bytes) : "memory");
}
__device__ __forceinline__ void mbar_arrive(uint32_t bar) {
    asm volatile("mbarrier.arrive.shared::cta.b64 _, [%0];" ::"r"(bar) : "memory");
}
__device__ __forceinline__ void mbar_arrive_cluster(uint32_t cluster_addr) {
    asm volatile("mbarrier.arrive.shared::cluster.b64 _, [%0];" ::"r"(cluster_addr) : "memory");
}
constexpr uint32_t SPIN = 1u << 20;
__device__ __forceinline__ void mbar_wait(uint32_t bar, uint32_t parity) {
    asm volatile("{\n.reg .pred p;\n.reg .b32 c;\nmov.b32 c, 0;\n"
                 "W_%=:\nmbarrier.try_wait.parity.shared::cta.b64 p, [%0], %1;\n@p bra D_%=;\n"
                 "add.u32 c, c, 1;\nsetp.lt.u32 p, c, 0x100000;\n@p bra W_%=;\nD_%=:\n}"
                 ::"r"(bar), "r"(parity) : "memory");
}
__device__ __forceinline__ void anchor(uint32_t addr, float v) {
    asm volatile("{\n.reg .pred p;\nsetp.lt.f32 p, %1, 0f00000000;\n@p st.volatile.shared.f32 [%0], %1;\n}" ::"r"(addr), "f"(v) : "memory");
}
__device__ __forceinline__ void mbar_wait_sleep(uint32_t bar, uint32_t parity) {
    asm volatile("{\n.reg .pred p;\n.reg .b32 c;\nmov.b32 c, 0;\n"
                 "W_%=:\nmbarrier.try_wait.parity.shared::cta.b64 p, [%0], %1, 5000;\n@p bra D_%=;\n"
                 "add.u32 c, c, 1;\nsetp.lt.u32 p, c, 0x20000;\n@p bra W_%=;\nD_%=:\n}"
                 ::"r"(bar), "r"(parity) : "memory");
}
__device__ __forceinline__ uint32_t load_tag(const Scratch* gs) {
    uint32_t tag;
    asm volatile("ld.global.ca.u32 %0, [%1];" : "=r"(tag) : "l"(gs->epoch) : "memory");
    return tag + 1;
}
__device__ __forceinline__ uint4 ld_relaxed(const uint4* p) {
    uint4 v;
    asm volatile("ld.relaxed.gpu.global.v4.u32 {%0,%1,%2,%3}, [%4];" : "=r"(v.x), "=r"(v.y), "=r"(v.z), "=r"(v.w) : "l"(p) : "memory");
    return v;
}
__device__ __forceinline__ void st_relaxed(uint4* p, uint32_t a, uint32_t b, uint32_t c, uint32_t d) {
    asm volatile("{\n.reg .b64 u, v;\nmov.b64 u, {%1, %2};\nmov.b64 v, {%3, %4};\nst.relaxed.gpu.global.v2.b64 [%0], {u, v};\n}"
                 ::"l"(p), "r"(a), "r"(b), "r"(c), "r"(d) : "memory");
}
__device__ __forceinline__ void st_relaxed4(void* p, uint32_t a, uint32_t b, uint32_t c, uint32_t d) {
    asm volatile("st.relaxed.gpu.global.v4.u32 [%0], {%1, %2, %3, %4};" ::"l"(p), "r"(a), "r"(b), "r"(c), "r"(d) : "memory");
}
__device__ __forceinline__ uint2 ld_relaxed8(const void* p) {
    uint2 v;
    asm volatile("ld.relaxed.gpu.global.v2.u32 {%0,%1}, [%2];" : "=r"(v.x), "=r"(v.y) : "l"(p) : "memory");
    return v;
}
__device__ __forceinline__ uint2 ld_relaxed64(const uint2* p) {
    uint2 v;
    asm volatile("{\n.reg .b64 u;\nld.relaxed.gpu.global.b64 u, [%2];\nmov.b64 {%0, %1}, u;\n}" : "=r"(v.x), "=r"(v.y) : "l"(p) : "memory");
    return v;
}
__device__ __forceinline__ void st_relaxed64(uint2* p, uint32_t a, uint32_t b) {
    asm volatile("{\n.reg .b64 u;\nmov.b64 u, {%1, %2};\nst.relaxed.gpu.global.b64 [%0], u;\n}" ::"l"(p), "r"(a), "r"(b) : "memory");
}
__device__ __forceinline__ uint4 ld_relaxed2(const uint4* p) {
    uint4 v;
    asm volatile("{\n.reg .b64 u, w;\nld.relaxed.gpu.global.v2.b64 {u, w}, [%4];\nmov.b64 {%0, %1}, u;\nmov.b64 {%2, %3}, w;\n}"
                 : "=r"(v.x), "=r"(v.y), "=r"(v.z), "=r"(v.w) : "l"(p) : "memory");
    return v;
}
__device__ __forceinline__ void reload16(uint4& v, const void* p, uint32_t& miss) {
    asm volatile("{\n.reg .pred p;\n.reg .b32 m;\n.reg .b64 u, w;\nmax.u32 m, %0, %2;\nsetp.eq.u32 p, m, 0xffffffff;\n"
                 "mov.b64 u, {%0, %1};\nmov.b64 w, {%2, %3};\n@p ld.relaxed.gpu.global.v2.b64 {u, w}, [%5];\n"
                 "mov.b64 {%0, %1}, u;\nmov.b64 {%2, %3}, w;\n@p mov.u32 %4, 1;\n}"
                 : "+r"(v.x), "+r"(v.y), "+r"(v.z), "+r"(v.w), "+r"(miss) : "l"(p) : "memory");
}
__device__ __forceinline__ void reload8(uint2& v, const void* p, uint32_t& miss) {
    asm volatile("{\n.reg .pred p;\n.reg .b64 u;\nsetp.eq.u32 p, %0, 0xffffffff;\nmov.b64 u, {%0, %1};\n"
                 "@p ld.relaxed.gpu.global.b64 u, [%3];\nmov.b64 {%0, %1}, u;\n@p mov.u32 %2, 1;\n}"
                 : "+r"(v.x), "+r"(v.y), "+r"(miss) : "l"(p) : "memory");
}
__device__ __forceinline__ uint32_t ld_relaxed32(const void* p) {
    uint32_t v;
    asm volatile("ld.relaxed.gpu.global.u32 %0, [%1];" : "=r"(v) : "l"(p) : "memory");
    return v;
}
__device__ __forceinline__ void poll2x2(const uint4* p0, const uint4* p1, uint32_t tag, uint4& o0, uint4& o1) {
    uint4 v0, v1;
    uint32_t miss, it = 0;
#pragma unroll 1
    do {
        v0 = ld_relaxed2(p0); v1 = ld_relaxed2(p1);
        miss = (v0.y ^ tag) | (v0.w ^ tag) | (v1.y ^ tag) | (v1.w ^ tag);
    } while (miss && ++it < SPIN / 16);
    o0 = v0; o1 = v1;
}
__device__ __forceinline__ void flag_wait(const unsigned int* p, uint32_t tag) {
    uint32_t v, it = 0;
#pragma unroll 1
    do {
        asm volatile("ld.relaxed.gpu.global.u32 %0, [%1];" : "=r"(v) : "l"(p) : "memory");
    } while (__any_sync(0xffffffffu, v != tag) && ++it < SPIN / 16);
    asm volatile("fence.acquire.gpu;" ::: "memory");
    __syncwarp();
}
__device__ __forceinline__ bool elect() {
    uint32_t p;
    asm volatile("{\n.reg .pred p;\nelect.sync _|p, 0xffffffff;\nselp.u32 %0, 1, 0, p;\n}" : "=r"(p));
    return p;
}
__device__ __forceinline__ void flag_release(unsigned int* p, uint32_t tag) {
    asm volatile("st.release.gpu.global.u32 [%0], %1;" ::"l"(p), "r"(tag) : "memory");
}
__device__ __forceinline__ uint32_t touch(const void* p) {
    uint32_t v;
    asm volatile("ld.global.nc.L1::no_allocate.L2::128B.u32 %0, [%1];" : "=r"(v) : "l"(p));
    return v;
}
__device__ __forceinline__ void bar_sync(int id, int n) { asm volatile("bar.sync %0, %1;" ::"r"(id), "r"(n) : "memory"); }
__device__ __forceinline__ void bar_arrive(int id, int n) { asm volatile("bar.arrive %0, %1;" ::"r"(id), "r"(n) : "memory"); }

constexpr uint64_t EVICT_NORMAL = 0x1000000000000000ull, EVICT_FIRST = 0x12F0000000000000ull;
__device__ __forceinline__ void tma2d(uint32_t dst, const CUtensorMap* m, int c0, int c1, uint32_t bar) {
    asm volatile("cp.async.bulk.tensor.2d.shared::cluster.global.mbarrier::complete_tx::bytes.L2::cache_hint [%0], [%1, {%3, %4}], [%2], %5;"
                 ::"r"(dst), "l"(m), "r"(bar), "r"(c0), "r"(c1), "l"(EVICT_FIRST) : "memory");
}
__device__ __forceinline__ void tma2d_mc(uint32_t dst, const CUtensorMap* m, int c0, int c1, uint32_t bar, uint64_t pol) {
    asm volatile("cp.async.bulk.tensor.2d.shared::cluster.global.mbarrier::complete_tx::bytes.multicast::cluster.L2::cache_hint [%0], [%1, {%3, %4}], [%2], %5, %6;"
                 ::"r"(dst), "l"(m), "r"(bar), "r"(c0), "r"(c1), "h"((uint16_t)3), "l"(pol) : "memory");
}
__device__ __forceinline__ void tma3d(uint32_t dst, const CUtensorMap* m, int c0, int c1, int c2, uint32_t bar) {
    asm volatile("cp.async.bulk.tensor.3d.shared::cluster.global.mbarrier::complete_tx::bytes.L2::cache_hint [%0], [%1, {%3, %4, %5}], [%2], %6;"
                 ::"r"(dst), "l"(m), "r"(bar), "r"(c0), "r"(c1), "r"(c2), "l"(EVICT_FIRST) : "memory");
}
__device__ __forceinline__ void bulk_load(uint32_t dst, const void* src, uint32_t bytes, uint32_t bar) {
    asm volatile("cp.async.bulk.shared::cluster.global.mbarrier::complete_tx::bytes [%0], [%1], %2, [%3];"
                 ::"r"(dst), "l"(src), "r"(bytes), "r"(bar) : "memory");
}
__device__ __forceinline__ void l2_prefetch(const void* src, uint32_t bytes) {
    asm volatile("cp.async.bulk.prefetch.L2.global [%0], %1;" ::"l"(src), "r"(bytes) : "memory");
}
__device__ __forceinline__ uint32_t bmul2(uint32_t a, uint32_t b) { uint32_t r; asm("mul.rn.bf16x2 %0, %1, %2;" : "=r"(r) : "r"(a), "r"(b)); return r; }
__device__ __forceinline__ uint32_t badd2(uint32_t a, uint32_t b) { uint32_t r; asm("add.rn.bf16x2 %0, %1, %2;" : "=r"(r) : "r"(a), "r"(b)); return r; }
__device__ __forceinline__ uint32_t bsub2(uint32_t a, uint32_t b) { uint32_t r; asm("sub.rn.bf16x2 %0, %1, %2;" : "=r"(r) : "r"(a), "r"(b)); return r; }
__device__ __forceinline__ uint32_t bmax2(uint32_t a, uint32_t b) { uint32_t r; asm("max.bf16x2 %0, %1, %2;" : "=r"(r) : "r"(a), "r"(b)); return r; }
__device__ __forceinline__ uint32_t bfma2(uint32_t a, uint32_t b, uint32_t c) { uint32_t r; asm("fma.rn.bf16x2 %0, %1, %2, %3;" : "=r"(r) : "r"(a), "r"(b), "r"(c)); return r; }
__device__ __forceinline__ uint4 lds128(uint32_t a) { uint4 v; asm volatile("ld.shared.v4.u32 {%0,%1,%2,%3}, [%4];" : "=r"(v.x), "=r"(v.y), "=r"(v.z), "=r"(v.w) : "r"(a) : "memory"); return v; }
__device__ __forceinline__ uint2 lds64(uint32_t a) { uint2 v; asm volatile("ld.shared.v2.u32 {%0,%1}, [%2];" : "=r"(v.x), "=r"(v.y) : "r"(a) : "memory"); return v; }
__device__ __forceinline__ uint32_t lds32(uint32_t a) { uint32_t v; asm volatile("ld.shared.u32 %0, [%1];" : "=r"(v) : "r"(a) : "memory"); return v; }
__device__ __forceinline__ uint4 ldsm4(uint32_t a) {
    uint4 v;
    asm volatile("ldmatrix.sync.aligned.m8n8.x4.shared.b16 {%0,%1,%2,%3}, [%4];" : "=r"(v.x), "=r"(v.y), "=r"(v.z), "=r"(v.w) : "r"(a) : "memory");
    return v;
}
__device__ __forceinline__ uint4 ldsm4t(uint32_t a) {
    uint4 v;
    asm volatile("ldmatrix.sync.aligned.m8n8.x4.trans.shared.b16 {%0,%1,%2,%3}, [%4];" : "=r"(v.x), "=r"(v.y), "=r"(v.z), "=r"(v.w) : "r"(a) : "memory");
    return v;
}
__device__ __forceinline__ void mma1688(float* d, uint32_t a0, uint32_t a1, uint32_t b) {
    asm("mma.sync.aligned.m16n8k8.row.col.f32.bf16.bf16.f32 {%0,%1,%2,%3}, {%4,%5}, {%6}, {%0,%1,%2,%3};"
        : "+f"(d[0]), "+f"(d[1]), "+f"(d[2]), "+f"(d[3]) : "r"(a0), "r"(a1), "r"(b));
}
__device__ __forceinline__ void mma16816(float* d, uint32_t a0, uint32_t a1, uint32_t a2, uint32_t a3, uint32_t b0, uint32_t b1) {
    asm("mma.sync.aligned.m16n8k16.row.col.f32.bf16.bf16.f32 {%0,%1,%2,%3}, {%4,%5,%6,%7}, {%8,%9}, {%0,%1,%2,%3};"
                 : "+f"(d[0]), "+f"(d[1]), "+f"(d[2]), "+f"(d[3]) : "r"(a0), "r"(a1), "r"(a2), "r"(a3), "r"(b0), "r"(b1));
}
__device__ __forceinline__ void stsm_x4(uint32_t addr, uint32_t a, uint32_t b, uint32_t c, uint32_t d) {
    asm volatile("stmatrix.sync.aligned.m8n8.x4.shared.b16 [%0], {%1, %2, %3, %4};"
                 ::"r"(addr), "r"(a), "r"(b), "r"(c), "r"(d) : "memory");
}

__device__ __forceinline__ uint64_t mkdesc(uint32_t addr, uint32_t lbo, uint32_t sbo) {
    return (uint64_t)((addr & 0x3FFFF) >> 4) | ((uint64_t)(lbo >> 4) << 16) | ((uint64_t)(sbo >> 4) << 32) | (1ull << 62);
}
constexpr uint32_t SM0 = 1024;
__host__ __device__ constexpr uint32_t desc_lo(uint32_t off, uint32_t lbo) { return ((SM0 + off) >> 4) | ((lbo >> 4) << 16); }
__device__ __forceinline__ uint64_t desc_of(uint32_t lo) { return lo | (0x40000040ull << 32); }
#define WG_FENCE() asm volatile("wgmma.fence.sync.aligned;" ::: "memory")
#define WG_COMMIT() asm volatile("wgmma.commit_group.sync.aligned;" ::: "memory")
#define WG_WAIT(n) asm volatile("wgmma.wait_group.sync.aligned %0;" ::"n"(n) : "memory")

#define F8(a, i) "+f"(a[i]), "+f"(a[i + 1]), "+f"(a[i + 2]), "+f"(a[i + 3]), "+f"(a[i + 4]), "+f"(a[i + 5]), "+f"(a[i + 6]), "+f"(a[i + 7])
#define F16(a, i) F8(a, i), F8(a, i + 8)
#define F64(a) F16(a, 0), F16(a, 16), F16(a, 32), F16(a, 48)
#define F32(a) F16(a, 0), F16(a, 16)
#define L64 "%0,%1,%2,%3,%4,%5,%6,%7,%8,%9,%10,%11,%12,%13,%14,%15,%16,%17,%18,%19,%20,%21,%22,%23,%24,%25,%26,%27,%28,%29,%30,%31,%32,%33,%34,%35,%36,%37,%38,%39,%40,%41,%42,%43,%44,%45,%46,%47,%48,%49,%50,%51,%52,%53,%54,%55,%56,%57,%58,%59,%60,%61,%62,%63"
#define L32 "%0,%1,%2,%3,%4,%5,%6,%7,%8,%9,%10,%11,%12,%13,%14,%15,%16,%17,%18,%19,%20,%21,%22,%23,%24,%25,%26,%27,%28,%29,%30,%31"

template <int TB>
__device__ __forceinline__ void mma_rs128(float (&d)[64], uint32_t a0, uint32_t a1, uint32_t a2, uint32_t a3, uint64_t b, int acc) {
    asm volatile("{\n.reg .pred p;\nsetp.ne.b32 p, %69, 0;\n"
                 "wgmma.mma_async.sync.aligned.m64n128k16.f32.bf16.bf16 {" L64 "}, {%64,%65,%66,%67}, %68, p, 1, 1, %70;\n}"
                 : F64(d) : "r"(a0), "r"(a1), "r"(a2), "r"(a3), "l"(b), "r"(acc), "n"(TB));
}
template <int TB>
__device__ __forceinline__ void mma_rs64(float (&d)[32], uint32_t a0, uint32_t a1, uint32_t a2, uint32_t a3, uint64_t b, int acc) {
    asm volatile("{\n.reg .pred p;\nsetp.ne.b32 p, %37, 0;\n"
                 "wgmma.mma_async.sync.aligned.m64n64k16.f32.bf16.bf16 {" L32 "}, {%32,%33,%34,%35}, %36, p, 1, 1, %38;\n}"
                 : F32(d) : "r"(a0), "r"(a1), "r"(a2), "r"(a3), "l"(b), "r"(acc), "n"(TB));
}
template <int N>
__device__ __forceinline__ void fence_regs(float (&d)[N]) {
#pragma unroll
    for (int i = 0; i < N; i++) asm volatile("" : "+f"(d[i])::"memory");
}
template <int N>
__device__ __forceinline__ void fence_regs(uint32_t (&d)[N]) {
#pragma unroll
    for (int i = 0; i < N; i++) asm volatile("" : "+r"(d[i])::"memory");
}

template <int V> struct IC { static constexpr int value = V; };

constexpr int SLOT = 32768, UNIT = 16384;
constexpr int SM_Q = 4 * SLOT;
constexpr int SM_BAR = 7 * SLOT;
constexpr int SM_RED = SM_BAR + 512;
constexpr int SM_TOTAL = SM_BAR + 3072;
constexpr int XP = D_ * 2 + 16;
constexpr int M_MOD = 16 * XP;
constexpr int SM_T = SM_Q + 2 * D_ * 80, SM_TC = SM_T + D_ * 4, SM_TG = SM_TC + D_ * 4, SM_TS = SM_TG + D_ * 2;
constexpr float CS = 0.08838834764831845f * 1.4426950408889634f;
#define LMAX 0.5f
#define LMIN 0x1p-104f
#define USE_SPARE 1
#define MAXG 2
#define SPLIT 10
#define ESPLIT 2
#define PV1 8
#define RW 2
#define HW 2
#define HW2 1
#define XDELAY 200
#define QDELAY 300
#define TMPF 1
#define PFD0 2000
#define PFD1 400
#define HSENT 1
#define HDELAY 500
#define RCM 8
#define RPE 0
#define STAGE 11
#define POFF 102.f
#define WF0 6
#define WF1 16
#define C3D 0
#define C4D 300
#define DD 300
#define P2E 1
#define BO 0
#define MAP 2
#define CFULL 0
#define WFE 1
#define OUTD 0
#define OUTPOL EVICT_FIRST
#define SO 0
#define WF2 22
#define OUTP 0
constexpr int PF_KV = 8, PF_WO = 120;

__device__ __forceinline__ int cluster_role() {
    int k = blockIdx.x >> 1;
    if (MAP == 0) return k & 63;
    if (MAP == 1) return (k & 7) * 8 + ((k >> 3) & 7);
    if (MAP == 3) {
        asm("mov.u32 %0, %%smid;" : "=r"(k));
        k >>= 1;
        const int r = ((k - 32) * 37) >> 8;
        return k < 32 ? (k & 7) * 8 + (k >> 3) : k < 60 ? (k - 31 - r * 7) * 8 + 4 + r : (k - 58) & 7;
    }
    const int r = ((k - 36) * 37) >> 8, i = k - 36 - r * 7;
    if (MAP == 4) return k < 4 ? 4 + k : k < 36 ? ((k - 4) & 7) * 8 + ((k - 4) >> 3) : (i + 1) * 8 + ((4 + r) & 7);
    return k < 4 ? 12 + k : k < 36 ? ((k - 4) & 7) * 8 + ((k - 4) >> 3) : (i + (i > 0)) * 8 + ((4 + r) & 7);
}

struct Args {
    const bf16 *w_mod, *cvec;
    Scratch* gs;
    bf16* out;
    const bf16 *x, *kc, *vc, *wq, *wo, *w_r, *w_down;
};

__device__ __forceinline__ void frag_store(uint8_t* p, const uint32_t (&a)[32]) {
#pragma unroll
    for (int i = 0; i < 8; i++)
        __stcg(reinterpret_cast<uint4*>(p + i * 512), make_uint4(a[4 * i], a[4 * i + 1], a[4 * i + 2], a[4 * i + 3]));
}
__device__ __forceinline__ void frag_load(uint32_t (&a)[32], const uint8_t* p) {
#pragma unroll
    for (int i = 0; i < 8; i++) {
        const uint4 v = __ldcg(reinterpret_cast<const uint4*>(p + i * 512));
        a[4 * i] = v.x; a[4 * i + 1] = v.y; a[4 * i + 2] = v.z; a[4 * i + 3] = v.w;
    }
}
__device__ __forceinline__ float quad_sum(float v) {
    v += __shfl_xor_sync(0xffffffffu, v, 1);
    return v + __shfl_xor_sync(0xffffffffu, v, 2);
}
__device__ __forceinline__ float quad_max(float v) {
    v = fmaxf(v, __shfl_xor_sync(0xffffffffu, v, 1));
    return fmaxf(v, __shfl_xor_sync(0xffffffffu, v, 2));
}
__device__ __forceinline__ float rcp_fast(float x) { float y; asm("rcp.approx.ftz.f32 %0, %1;" : "=f"(y) : "f"(x)); return y; }
__device__ __forceinline__ float sigmoidf_(float x) { return rcp_fast(1.f + ex2(-1.4426950408889634f * x)); }
__device__ __forceinline__ void top2(uint32_t k, uint32_t& k1, uint32_t& k2) {
    k1 = __reduce_max_sync(0xffffffffu, k);
    k2 = __reduce_max_sync(0xffffffffu, k == k1 ? 0 : k);
}

__device__ __forceinline__ void mod_fma(float (&a)[8], const uint4 w, float sc) {
    a[0] += sc * bf_lo(w.x); a[1] += sc * bf_hi(w.x); a[2] += sc * bf_lo(w.y); a[3] += sc * bf_hi(w.y);
    a[4] += sc * bf_lo(w.z); a[5] += sc * bf_hi(w.z); a[6] += sc * bf_lo(w.w); a[7] += sc * bf_hi(w.w);
}
__device__ __forceinline__ float mod_reduce(float (&a)[8], int lane) {
#pragma unroll
    for (int h = 4; h > 0; h >>= 1) {
        const bool up = lane & (8 / h);
#pragma unroll
        for (int i = 0; i < h; i++)
            a[i] = (up ? a[i + h] : a[i]) + __shfl_xor_sync(0xffffffffu, up ? a[i] : a[i + h], 8 / h);
    }
    return a[0] + __shfl_xor_sync(0xffffffffu, a[0], 16);
}

__device__ __forceinline__ float ln_stats(float sum, float sq, uint32_t& mean2) {
    const float mean = sum * (1.f / D_);
    const float var = fmaxf(fmaf(-mean, mean, sq * (1.f / D_)), 0.f);
    float sd;
    asm("sqrt.approx.ftz.f32 %0, %1;" : "=f"(sd) : "f"(rbf(rbf(var) + 1e-5f)));
    mean2 = pack_bf16(mean, mean);
    return rcp_fast(rbf(sd));
}
__device__ __forceinline__ uint32_t ln_pair(uint32_t x, uint32_t mean2, float rsd) {
    const uint32_t d = bsub2(x, mean2);
    return pack_bf16(bf_lo(d) * rsd, bf_hi(d) * rsd);
}
__device__ __forceinline__ void rows_load(uint32_t (&x)[20], uint32_t xs, int cw) {
#pragma unroll
    for (int ch = 0; ch < 5; ch++) {
        const uint4 v = ldsm4(ch < 4 ? xs + ch * 256 : xs + 1024 - cw * 16);
        x[4 * ch] = v.x; x[4 * ch + 1] = v.y; x[4 * ch + 2] = v.z; x[4 * ch + 3] = v.w;
    }
}
__device__ __forceinline__ void stats_add(float (&st)[12], uint32_t a, uint32_t b, uint32_t w) {
    mma1688(st, a, b, w);
    mma1688(st + 4, a, b, a);
    mma1688(st + 8, a, b, b);
}
__device__ __forceinline__ float rows_stats(const float (&st)[12], float4* rec, int cw, int lane, uint32_t& mean2, float& dot) {
    const int g8 = lane >> 2;
    if ((g8 >> 1) == (lane & 3)) {
        rec[cw * 16 + g8] = make_float4(st[0], (g8 & 1) ? st[5] : st[4], st[1], 0.f);
        rec[cw * 16 + 8 + g8] = make_float4(st[2], (g8 & 1) ? st[11] : st[10], st[3], 0.f);
    }
    bar_sync(3, 256);
    const float4* r = rec + (lane >> 4) * 64 + (lane & 15);
    const float4 s0 = r[0], s1 = r[16], s2 = r[32], s3 = r[48];
    const float sum = (s0.x + s1.x) + (s2.x + s3.x), sq = (s0.y + s1.y) + (s2.y + s3.y);
    dot = (s0.z + s1.z) + (s2.z + s3.z);
    dot += __shfl_xor_sync(0xffffffffu, dot, 16);
    return ln_stats(sum + __shfl_xor_sync(0xffffffffu, sum, 16), sq + __shfl_xor_sync(0xffffffffu, sq, 16), mean2);
}
template <class F>
__device__ __forceinline__ void rows_normalise(uint32_t* y, const uint32_t* x, uint32_t mean2, float rsd, int lane, F loads) {
    const int g8 = lane >> 2;
    const uint32_t ma2 = __shfl_sync(0xffffffffu, mean2, g8), mb2 = __shfl_sync(0xffffffffu, mean2, g8 + 8);
    const float ra = __shfl_sync(0xffffffffu, rsd, g8), rb = __shfl_sync(0xffffffffu, rsd, g8 + 8);
    loads();
#pragma unroll
    for (int k = 0; k < 9; k++) { y[2 * k] = ln_pair(x[2 * k], ma2, ra); y[2 * k + 1] = ln_pair(x[2 * k + 1], mb2, rb); }
}
__device__ __forceinline__ uint32_t pair_of(const uint2* mp, int k, int cw) {
    return (k < 8 ? mp[(k >> 1) * 64 + (k & 1) * 4] : (mp - cw * 4)[256]).x;
}

__device__ __forceinline__ uint4 h_frag(const uint4* hf, int ks, int lane) {
    if (ks < 32) return ld_relaxed2(hf + ks * 32);
    const uint2* p = reinterpret_cast<const uint2*>(padd(hf, 256 - lane * 8) + ks * 32 - 16);
    const uint2 a = ld_relaxed64(p), b = ld_relaxed64(p + 32);
    return make_uint4(a.x, a.y, b.x, b.y);
}

__device__ __noinline__ void attn_fallback(uint32_t bad, uint32_t tag, uint8_t* frag, uint8_t* keep, const bf16* wq, const bf16* kc, const bf16* vc) {
  const Scratch* gs = &g_s;
  const int lane = threadIdx.x & 31, g8 = lane >> 2, qd = lane & 3;
  const int j = cluster_role() & 7, qb = (cluster_role() >> 3) * 2 + (blockIdx.x & 1);
  const uint4* hf = g_h + (size_t)(qb * 8 + (threadIdx.x >> 5) - 4) * (36 * 32) + lane;
#pragma unroll 1
  for (int t = 0; t < 4; t++) {
    if (!((bad >> t) & 1)) continue;
    const bf16 *wqp = wq + (4 * j + t) * DH, *kp = kc + (size_t)(2 * j + (t >> 1)) * S_ * DH, *vp = vc + (size_t)(2 * j + (t >> 1)) * S_ * DH;
    uint32_t q[32];
    float o[64];
#pragma unroll
    for (int i = 0; i < 64; i++) o[i] = 0.f;
#pragma unroll 1
    for (int ks = 0; ks < 36; ks++) {
        const uint4 a = h_frag(hf, ks, lane);
        const unsigned short* wr = reinterpret_cast<const unsigned short*>(wqp + (size_t)(ks * 16 + 2 * qd) * QD + g8);
#pragma unroll
        for (int dt = 0; dt < 16; dt++) {
            const uint32_t b0 = __ldg(wr + dt * 8) | ((uint32_t)__ldg(wr + dt * 8 + QD) << 16);
            const uint32_t b1 = __ldg(wr + dt * 8 + 8 * QD) | ((uint32_t)__ldg(wr + dt * 8 + 9 * QD) << 16);
            mma16816(o + 4 * dt, a.x, a.y, a.z, a.w, b0, b1);
        }
    }
#pragma unroll
    for (int i = 0; i < 32; i++) q[i] = pack_bf16(o[2 * i], o[2 * i + 1]);
#pragma unroll
    for (int i = 0; i < 64; i++) o[i] = 0.f;
    float m0 = -INFINITY, m1 = -INFINITY, l0 = 0.f, l1 = 0.f;
#pragma unroll 1
    for (int key = 0; key < S_; key += 16) {
        float sc[8];
#pragma unroll
        for (int i = 0; i < 8; i++) sc[i] = 0.f;
#pragma unroll
        for (int nt = 0; nt < 2; nt++) {
            const uint32_t* kr = reinterpret_cast<const uint32_t*>(kp + (size_t)(key + nt * 8 + g8) * DH) + qd;
#pragma unroll
            for (int ks = 0; ks < 8; ks++)
                mma16816(sc + 4 * nt, q[4 * ks], q[4 * ks + 1], q[4 * ks + 2], q[4 * ks + 3], __ldg(kr + ks * 8), __ldg(kr + ks * 8 + 4));
        }
        const float n0 = quad_max(fmaxf(fmaxf(m0, fmaxf(sc[0], sc[1])), fmaxf(sc[4], sc[5])));
        const float n1 = quad_max(fmaxf(fmaxf(m1, fmaxf(sc[2], sc[3])), fmaxf(sc[6], sc[7])));
        const float f0 = ex2((m0 - n0) * CS), f1 = ex2((m1 - n1) * CS);
        m0 = n0; m1 = n1;
#pragma unroll
        for (int i = 0; i < 8; i++) sc[i] = ex2((sc[i] - ((i & 2) ? n1 : n0)) * CS);
        l0 = l0 * f0 + (sc[0] + sc[1]) + (sc[4] + sc[5]);
        l1 = l1 * f1 + (sc[2] + sc[3]) + (sc[6] + sc[7]);
        const uint32_t e0 = pack_bf16(sc[0], sc[1]), e1 = pack_bf16(sc[2], sc[3]), e2 = pack_bf16(sc[4], sc[5]), e3 = pack_bf16(sc[6], sc[7]);
        const unsigned short* vr = reinterpret_cast<const unsigned short*>(vp + (size_t)(key + 2 * qd) * DH + g8);
#pragma unroll
        for (int dt = 0; dt < 16; dt++) {
            o[4 * dt] *= f0; o[4 * dt + 1] *= f0; o[4 * dt + 2] *= f1; o[4 * dt + 3] *= f1;
            const uint32_t b0 = __ldg(vr + dt * 8) | ((uint32_t)__ldg(vr + dt * 8 + DH) << 16);
            const uint32_t b1 = __ldg(vr + dt * 8 + 8 * DH) | ((uint32_t)__ldg(vr + dt * 8 + 9 * DH) << 16);
            mma16816(o + 4 * dt, e0, e1, e2, e3, b0, b1);
        }
    }
    const float i0 = 1.f / quad_sum(l0), i1 = 1.f / quad_sum(l1);
#pragma unroll
    for (int i = 0; i < 16; i++) {
        q[2 * i] = pack_bf16(o[4 * i] * i0, o[4 * i + 1] * i0);
        q[2 * i + 1] = pack_bf16(o[4 * i + 2] * i1, o[4 * i + 3] * i1);
    }
    frag_store(t < 3 ? frag + t * 4096 : keep, q);
  }
}

__device__ __forceinline__ void spare_q3(Scratch* gs, uint32_t sb, uint32_t bar_full, uint32_t bar_empty, int lane, int cw) {
    const uint32_t tag = load_tag(gs);
    uint32_t rel_base, e = 3;
    asm("mapa.shared::cluster.u32 %0, %1, %2;" : "=r"(rel_base) : "r"(bar_empty), "r"(lane & 1));
#pragma unroll 1
    for (int qb = blockIdx.x - NCTA; qb < 16; qb += 4) {
        uint32_t h[144];
        float o[64];
        flag_wait(&g_flag_h[(qb * 8 + cw) * 32], tag);
        const uint4* hf = g_h + (size_t)(qb * 8 + cw) * (36 * 32) + lane;
#pragma unroll
        for (int ks = 0; ks < 36; ks++) {
            const uint4 v = h_frag(hf, ks, lane);
            h[4 * ks] = v.x; h[4 * ks + 1] = v.y; h[4 * ks + 2] = v.z; h[4 * ks + 3] = v.w;
        }
#pragma unroll
        for (int i = 0; i < 64; i++) o[i] = 0.f;
#pragma unroll 1
        for (int v = 0; v < 4; v++) {
            fence_regs(o);
#pragma unroll
            for (int t = 0; t < 5; t++) {
                mbar_wait(bar_full + 8 * (e & 3), (e >> 2) & 1);
                const uint64_t dv = mkdesc(sb + (e & 3) * SLOT, UNIT, 1024);
                WG_FENCE();
#pragma unroll
                for (int ks = 0; ks < (t < 4 ? 8 : 4); ks++)
                    mma_rs128<1>(o, h[32 * t + 4 * ks], h[32 * t + 4 * ks + 1], h[32 * t + 4 * ks + 2], h[32 * t + 4 * ks + 3], dv + ks * 128, ks | t);
                WG_COMMIT();
                if (t > 0) { WG_WAIT(1); if (lane < 2) mbar_arrive_cluster(rel_base + 8 * ((e - 1) & 3)); }
                e++;
            }
            WG_WAIT(0);
            fence_regs(o);
            if (lane < 2) mbar_arrive_cluster(rel_base + 8 * ((e - 1) & 3));
            uint4* dst = &g_q3[((qb * 8 + 2 * v) * 8 + cw) * 128 + lane];
#pragma unroll
            for (int i = 0; i < 8; i++)
                __stcg(dst + (i >> 2) * 1024 + (i & 3) * 32, make_uint4(pack_bf16(o[8 * i], o[8 * i + 1]), pack_bf16(o[8 * i + 2], o[8 * i + 3]),
                                                                        pack_bf16(o[8 * i + 4], o[8 * i + 5]), pack_bf16(o[8 * i + 6], o[8 * i + 7])));
        }
        bar_sync(3, 256);
        if (cw == 0 && lane == 0) flag_release(&g_flag_q3[qb * 32], tag);
        __syncwarp();
    }
}

template <bool SPARE>
__global__ void __cluster_dims__(2, 1, 1) __launch_bounds__(384, 1)
fused_kernel(const Args args, const __grid_constant__ CUtensorMap tm_wq,
             const __grid_constant__ CUtensorMap tm_k, const __grid_constant__ CUtensorMap tm_v,
             const __grid_constant__ CUtensorMap tm_wo, const __grid_constant__ CUtensorMap tm_p,
             const __grid_constant__ CUtensorMap tm_x, const __grid_constant__ CUtensorMap tm_d,
             const __grid_constant__ CUtensorMap tm_g, const __grid_constant__ CUtensorMap tm_u) {
    extern __shared__ __align__(1024) uint8_t smem_raw[];
    const uint32_t sb = smem_u32(smem_raw);
    Scratch* const gs = args.gs;
    const uint32_t bar_full = sb + SM_BAR;
    const uint32_t bar_g = bar_full + 8 * 4;
    const uint32_t bar_mod = bar_g + 8;
    const uint32_t bar_go = bar_mod + 8;
    const uint32_t bar_x = bar_go + 40;
    const uint32_t bar_empty = bar_x + 8;
    const uint32_t bar_pub = bar_empty + 8 * 4;
    const uint32_t bar_qfree = bar_pub + 32;
    const uint32_t bar_out = bar_qfree + 24;
    const uint32_t bar_q3 = bar_out + 8;
    const uint32_t bar_pre = bar_q3 + 16;
    const uint32_t bar_w0 = bar_q3 + 8;
    constexpr int E0 = SPARE ? 2 : 0;

    const int c = blockIdx.x & 1;
    const int role = cluster_role();
    const int j = role & 7;
    const int qb = (role >> 3) * 2 + c;
    const int rg = qb * 8 + j;
    const int warp = __shfl_sync(0xffffffffu, threadIdx.x >> 5, 0);

    if (SPARE && blockIdx.x >= NCTA && warp >= 4) {
        asm volatile("barrier.cluster.arrive.relaxed.aligned;" ::: "memory");
        asm volatile("setmaxnreg.inc.sync.aligned.u32 240;");
        asm volatile("barrier.cluster.wait.aligned;" ::: "memory");
        spare_q3(gs, sb, bar_full, bar_empty, threadIdx.x & 31, warp - 4);
        asm volatile("barrier.cluster.arrive.relaxed.aligned;\nbarrier.cluster.wait.aligned;" ::: "memory");
    } else if (warp < 4) {
        asm volatile("setmaxnreg.dec.sync.aligned.u32 24;");
        int lane;
        asm volatile("mov.u32 %0, %%laneid;" : "=r"(lane));
        if (warp == 2 && elect()) {
            if (TMPF) asm volatile("prefetch.tensormap [%0];" ::"l"(&tm_x) : "memory");
#pragma unroll
            for (int i = 0; i < 27; i++) mbar_init(bar_full + 8 * i, i < 12 || i >= 23 ? 1 : i < 16 ? 16 : 8);
#pragma unroll
            for (int i = 0; i <= E0; i++) {
                mbar_arrive(bar_full + 8 * i);
                asm volatile("mbarrier.arrive.shared::cta.b64 _, [%0], 16;" ::"r"(bar_empty + 8 * i) : "memory");
            }
            asm volatile("fence.mbarrier_init.release.cluster;" ::: "memory");
        }
        __syncwarp();
        asm volatile("barrier.cluster.arrive.relaxed.aligned;" ::: "memory");
        if (warp == 2 && !(SPARE && blockIdx.x >= NCTA)) {
            if (XDELAY) __nanosleep(XDELAY);
            if (elect()) {
                mbar_expect_tx(bar_x, 16 * XP);
                tma2d(sb + SM_Q, &tm_x, 0, rg * 16, bar_x);
            }
            __syncwarp();
        }
        asm volatile("barrier.cluster.wait.aligned;" ::: "memory");
        const uint32_t tag = load_tag(gs);
        if (SPARE && blockIdx.x >= NCTA) {
            if (warp == 1) {
#pragma unroll 1
                for (int e = 3; e < 83; e++) {
                    const int v = (e - 3) / 5;
                    mbar_wait_sleep(bar_empty + 8 * (e & 3), ~(e >> 2) & 1);
                    if (elect()) {
                        mbar_expect_tx(bar_full + 8 * (e & 3), SLOT);
                        tma2d_mc(sb + (e & 3) * SLOT + c * UNIT, &tm_wq, (8 * (v & 3) + 4 * c + 3) * DH + 64, (e - 3 - v * 5) * 128,
                                 bar_full + 8 * (e & 3), EVICT_NORMAL);
                    }
                }
            }
            __syncwarp();
            asm volatile("barrier.cluster.arrive.relaxed.aligned;\nbarrier.cluster.wait.aligned;" ::: "memory");
            return;
        }
        if (warp == 3) {
#pragma unroll 1
            for (int e = 4; e < 20; e++) {
                __nanosleep(e == 4 ? PFD0 : PFD1);
                const int hd = (e * 52) >> 8, row = (e - hd * 5) * 128 + qb * 8 + (lane >> 1);
                if (lane < 16 && row < D_)
                    asm volatile("prefetch.global.L2 [%0];" ::"l"(padd(args.wq, (row * QD + (4 * j + ((0x1320 >> (4 * hd)) & 3)) * DH + (lane & 1) * 64) * 2)) : "memory");
            }
            __syncwarp();
            mbar_wait_sleep(bar_go, 0);
#pragma unroll 1
            for (int unit = 72 + blockIdx.x; unit < 216; unit += NCTA) {
                float a[8];
#pragma unroll
                for (int i = 0; i < 8; i++) a[i] = 0.f;
#pragma unroll 1
                for (int k = lane >> 1; k < D_; k += 16) {
                    const float cv = __bfloat162float(*padd(args.cvec, k * 2));
                    mod_fma(a, __ldg(reinterpret_cast<const uint4*>(padd(args.w_mod, (k * (6 * D_) + unit * 16 + (lane & 1) * 8) * 2))), rbf(cv * sigmoidf_(cv)));
                }
                const float v = mod_reduce(a, lane), v1 = __shfl_down_sync(0xffffffffu, v, 8);
                if (lane < 8) *padd(gs->mod2, ((unit - 72) * 8 + (lane & 1) * 4 + (lane & 2) + (lane >> 2)) * 4) = pack_bf16(v, v1);
            }
            __syncwarp();
            if (lane == 0) flag_release(padd(g_flag_mod, blockIdx.x * 4), tag);
#pragma unroll 1
            for (int k = 0; k < 36 * HSENT; k++) {
                __nanosleep(200);
                __stcg(padd(gs->h[0], (~tag & 1) * (NCTA * 36 * 512) + ((rg * 36 + k) * 32 + lane) * 16), make_uint4(0, 0, 0, 0));
            }
            __syncwarp();
            mbar_wait_sleep(bar_qfree + 16, 0);
            __nanosleep(2000);
            {
                uint4 v;
                uint32_t it = 0;
#pragma unroll 1
                do {
                    v = ld_relaxed(reinterpret_cast<const uint4*>(padd(g_flag_mod, lane * 16)));
                } while (((v.x ^ tag) | (v.y ^ tag) | (v.z ^ tag) | (v.w ^ tag)) && ++it < SPIN / 16);
                asm volatile("fence.acquire.gpu;" ::: "memory");
            }
            __syncwarp();
            {
                float w1 = 0.f, w2 = 0.f;
#pragma unroll 1
                for (int k = lane; k < D_ / 2; k += 32) {
                    const uint32_t* mp = padd(gs->mod2, k * 4);
                    const uint32_t sv = __ldcg(mp + D_ / 2), c1 = badd2(__ldcg(mp + D_), 0x3f803f80u);
                    const uint32_t wr = *reinterpret_cast<const uint32_t*>(padd(args.w_r, k * 4)), wp = bmul2(c1, wr);
                    reinterpret_cast<uint2*>(smem_raw + SM_T)[k] = make_uint2(__ldcg(mp), wp);
                    reinterpret_cast<uint2*>(smem_raw + SM_TC)[k] = make_uint2(c1, sv);
                    reinterpret_cast<uint32_t*>(smem_raw + SM_TG)[k] = __ldcg(mp + 3 * D_ / 2);
                    w1 += bf_lo(wp) + bf_hi(wp);
                    w2 += bf_lo(sv) * bf_lo(wr) + bf_hi(sv) * bf_hi(wr);
                }
#pragma unroll 1
                for (int i = 1; i < 32; i <<= 1) { w1 += __shfl_xor_sync(0xffffffffu, w1, i); w2 += __shfl_xor_sync(0xffffffffu, w2, i); }
                *reinterpret_cast<float2*>(smem_raw + SM_TS) = make_float2(w1, w2);
            }
#pragma unroll
            for (int i = 0; i < 4; i++) reinterpret_cast<uint4*>(smem_raw + SM_RED)[lane + 32 * i] = make_uint4(~0u, ~0u, ~0u, ~0u);
            asm volatile("fence.proxy.async.shared::cta;" ::: "memory");
            __syncwarp();
            if (elect()) {
                uint8_t* mb = g_frag + (size_t)rg * 8 * WREG + 3 * 4096;
#pragma unroll 1
                for (int k = 0; k < 8; k++, mb += WREG) {
#pragma unroll
                    for (int i = 0; i < 3; i++)
                        asm volatile("cp.async.bulk.global.shared::cta.bulk_group [%0], [%1], 2048;" ::"l"(mb + i * 2048), "r"(sb + SM_RED) : "memory");
                    __nanosleep(500);
                }
                asm volatile("cp.async.bulk.commit_group;\ncp.async.bulk.wait_group 0;\nfence.proxy.async.global;" ::: "memory");
            }
            __syncwarp();
            if (lane == 0) mbar_arrive(bar_mod);
            __syncwarp();
            mbar_wait_sleep(bar_go + 8, 0);
            if (lane < 3) asm volatile("prefetch.tensormap [%0];" ::"l"(lane == 0 ? &tm_x : lane == 1 ? &tm_p : &tm_d) : "memory");
            __syncwarp();
            mbar_wait_sleep(bar_go + 8 * 2, 0);
            uint32_t acc = 0;
#pragma unroll 1
            for (int k = lane; k < 16 * 9; k += 32) acc |= touch(padd(args.x, (rg * 16 * D_ + k * 64) * 2));
            if (acc == 0) reinterpret_cast<volatile uint32_t*>(smem_raw + SM_BAR)[127] = acc;
        } else if (warp == 0) {
#pragma unroll 1
            for (int i = 0; i < 48; i++) {
                if (i == 0 || i == 17 || i == 34) mbar_wait_sleep(bar_qfree + (i >> 4) * 8, 0);
                if (SPARE && i == 17) {
                    flag_wait(&g_flag_q3[qb * 32], tag);
                    if (elect()) {
                        asm volatile("fence.proxy.async.global;" ::: "memory");
                        mbar_expect_tx(bar_q3, UNIT);
#pragma unroll 1
                        for (int k = 0; k < 8; k++) bulk_load(sb + SM_Q + 2 * SLOT + k * 4096 + 2048, &g_q3[(rg * 8 + k) * 128], 2048, bar_q3);
                    }
                }
                __nanosleep(700);
                if (elect()) {
                    asm volatile("mbarrier.expect_tx.shared::cta.b64 [%0], %1;" ::"r"(bar_g), "n"(1920) : "memory");
                    tma2d(sb + SM_Q + i * 1920, i < 24 ? &tm_g : &tm_u, (blockIdx.x * 36) & ~7, (i < 24 ? i : i - 24) * 24, bar_g);
                }
            }
            if (elect()) mbar_arrive(bar_g);
#pragma unroll 1
            for (int i = 0; i < 18; i++) {
                __nanosleep(400);
                if (elect()) l2_prefetch(args.w_down + (size_t)(blockIdx.x * 36 + i * 2) * D_, 4 * D_);
            }
            __syncwarp();
            mbar_wait_sleep(bar_go + 8 * 4, 0);
            uint4* rp = padd(g_rows, (rg * 2 * RSLOT + lane) * 16);
#pragma unroll
            for (int k = 0; k < 9; k++) rp[k * 32] = make_uint4(~0u, ~0u, ~0u, ~0u);
            if (blockIdx.x < 72) {
                uint4* yp = reinterpret_cast<uint4*>(padd(g_ypart, blockIdx.x * NCTA * 64 + lane * 16));
#pragma unroll
                for (int k = 0; k < 16; k++) yp[k * 32] = make_uint4(~0u, ~0u, ~0u, ~0u);
            }
            asm volatile("fence.acq_rel.gpu;" ::: "memory");
            __syncwarp();
            if (lane == 0) mbar_arrive(bar_pre);
        } else if (warp == 1) {
            __nanosleep(QDELAY);
            uint32_t go = bar_go;
            uint64_t marks = 24 | 151 << 8 | 154 << 16 | 159ull << 24 | 165ull << 32;
#pragma unroll 1
            for (int e = E0; e < 168; e++) {
                const CUtensorMap* tm;
                int c0, c1;
                uint64_t pol = EVICT_FIRST;
                if (e == 158 || e == 163) continue;
                if (e < 21 && e != 19) {
                    const int i = SPARE && e < 12 ? e - 2 : e - (e == 20), hd = (i * 52) >> 8;
                    tm = &tm_wq; c0 = (4 * j + ((0x1320 >> (4 * hd)) & 3)) * DH + c * 64; c1 = (i - hd * 5) * 128 - 64;
                    if (SPARE && e >= 12 && e < 15) { c0 = (4 * j + 3) * DH; c1 = (2 * (e - 12) + c) * 128; }
                } else if (e < 148) {
                    const int i = max(e - 20, 0);
                    const bool isk = i == 0 || ((i & 1) && i < 127);
                    const int n = isk ? (i + 1) >> 1 : (i - 1) >> 1;
                    tm = isk ? &tm_k : &tm_v; c0 = c * 64; c1 = (2 * j + (n >> 5)) * S_ + (n & 15) * 128;
                    if (!(i & 32)) pol = EVICT_NORMAL;
                } else {
                    int i = e - 148 - (e > 158) - (e > 163);
                    if (i == 1 || i == 2) i ^= 3;
                    tm = &tm_wo; c0 = (i >> 1) * 64; c1 = (4 * j + ((i & 1) ? 1 + c : 3 * c)) * DH;
                }
                const uint32_t fb = e == E0 ? bar_w0 : bar_full + 8 * (e & 3), d = sb + (e == E0 ? 6 : e & 3) * SLOT;
                if (e >= 24 && e < 152) mbar_wait_sleep(bar_empty + 8 * (e & 3), ~(e >> 2) & 1);
                else if (e != E0) mbar_wait(bar_empty + 8 * (e & 3), ~(e >> 2) & 1);
                if (elect()) {
                    mbar_expect_tx(fb, SLOT);
                    tma2d_mc(d + c * UNIT, tm, c0, c1, fb, pol);
                    const int i = e - PF_KV;
                    if (i >= 0 && i < 128 && !(i & 32))
                        l2_prefetch(((i & 1) ? args.vc : args.kc) + (size_t)((2 * j + (i >> 6)) * S_ + (i & 30) * 64) * DH + qb * 1024, 2048);
                    if (e >= PF_WO && e < PF_WO + 18) l2_prefetch(args.wo + (size_t)blockIdx.x * (QD * D_ / NCTA) + (e - PF_WO) * 1024, 2048);
                    if (e == (marks & 255)) mbar_arrive(go);
                }
                if (e == (marks & 255)) { go += 8; marks >>= 8; }
            }
            asm volatile("fence.proxy.async.global;" ::: "memory");
            mbar_wait(bar_empty, 1);
            if (elect()) {
                mbar_expect_tx(bar_full, 16 * XP);
                tma2d(sb, &tm_x, 0, rg * 16, bar_full);
            }
            mbar_wait(bar_empty + 16, 1);
            if (C3D) __nanosleep(C3D);
            if (elect()) {
                mbar_expect_tx(bar_full + 16, SLOT);
                tma3d(sb + 2 * SLOT, &tm_p, 0, j * 20 + 12, qb * 8, bar_full + 16);
                tma3d(sb + 2 * SLOT + UNIT, &tm_p, 0, j * 20 + 14, qb * 8, bar_full + 16);
            }
            mbar_wait(bar_empty + 24, 1);
            if (C4D) __nanosleep(C4D);
            if (elect()) {
                mbar_expect_tx(bar_full + 24, UNIT);
                tma3d(sb + 3 * SLOT, &tm_p, 0, j * 20 + 16, qb * 8, bar_full + 24);
            }
            mbar_wait(bar_empty + 8, 0);
            mbar_wait(bar_empty + 16, 0);
            if (DD) __nanosleep(DD);
            if (elect()) {
#pragma unroll
                for (int i = 1; i < 3; i++) {
                    mbar_expect_tx(bar_full + 8 * i, 18 * XP);
                    tma2d(sb + i * SLOT, &tm_d, 0, blockIdx.x * 36 + (i - 1) * 18, bar_full + 8 * i);
                }
            }
        } else {
            if (lane < 3) asm volatile("prefetch.tensormap [%0];" ::"l"(lane == 0 ? &tm_k : lane == 1 ? &tm_v : &tm_wo) : "memory");
            if (SPARE && HSENT) {
                mbar_wait_sleep(bar_pub, 0);
                if (lane == 0) flag_release(padd(g_flag_h, rg * 128), tag);
                __syncwarp();
            }
            bar_sync(1, 192);
#pragma unroll 1
            for (uint32_t e = 20; e < 148; e++) {
                mbar_wait_sleep(bar_full + 8 * (e & 3), (e >> 2) & 1);
                if (e & 1) bar_sync(1, 192);
                if (!(e & 1) || e == 147) bar_sync(4, 160);
            }
            mbar_wait_sleep(bar_go + 8, 0);
            mbar_wait(bar_mod, 0);
#pragma unroll 1
            for (int i = 1; i < 4; i++) {
                mbar_wait(bar_pub + 8 * i, 0);
                unsigned int* flags = padd(g_flag_part, (qb * 32 + i * 8 - 8) * 4);
                if (elect()) { flag_release(padd(flags, j * 4), tag); DBG_PG(93); }
                __syncwarp();
                const uint32_t slot = i < 3 ? i + 1 : 1;
                flag_wait(padd(flags, (lane & 7) * 4), tag);
                asm volatile("fence.proxy.async.global;" ::: "memory");
                if (lane == 0 && i == 3) DBG_PG(101);
                mbar_wait(bar_go + 8 + 8 * i, 0);
                mbar_wait(bar_empty + 8 * slot, i != 1);
                if (elect()) {
                    mbar_expect_tx(bar_full + 8 * slot, SLOT);
                    tma3d(sb + slot * SLOT, &tm_p, 0, j * 20 + (i - 1) * 4, qb * 8, bar_full + 8 * slot);
                    tma3d(sb + slot * SLOT + UNIT, &tm_p, 0, j * 20 + (i - 1) * 4 + 2, qb * 8, bar_full + 8 * slot);
                }
            }
        }
        __syncwarp();
        mbar_wait_sleep(bar_out, 0);
        if (OUTD) __nanosleep(OUTD);
        if (elect()) {
            asm volatile("fence.proxy.async.shared::cta;" ::: "memory");
            const int2 sel = reinterpret_cast<const int2*>(smem_raw + SM_RED)[8];
#pragma unroll 1
            for (int i = warp; i < 16; i += 4) {
                const int row = rg * 16 + i;
                if (row != sel.x && row != sel.y)
                    asm volatile("cp.async.bulk.global.shared::cta.bulk_group.L2::cache_hint [%0], [%1], %2, %3;"
                                 ::"l"(args.out + (size_t)row * D_), "r"(sb + i * XP), "n"(D_ * 2), "l"(OUTPOL) : "memory");
            }
            asm volatile("cp.async.bulk.commit_group;\ncp.async.bulk.wait_group 0;" ::: "memory");
        }
    } else {
        uint32_t cv[5] = {0, 0, 0, 0, 0}, tag0 = 0;
        if (blockIdx.x < 72) {
            uint32_t ws;
            int tid;
            asm volatile("mov.u32 %0, smem_raw;\nmov.u32 %1, %%tid.x;" : "=r"(ws), "=r"(tid));
            tid -= 128;
            ws += SM_Q + SLOT + tid * 16;
            const bf16* wrow = args.w_mod + (size_t)(tid >> 1) * (6 * D_) + (tid & 1) * 8 + blockIdx.x * 16;
#pragma unroll
            for (int i = 0; i < 5; i++)
                if (i < 4 || tid < 128) {
                    asm volatile("cp.async.cg.shared.global [%0], [%1], 16;" ::"r"(ws + i * 4096), "l"(wrow + (size_t)i * 128 * (6 * D_)) : "memory");
                    cv[i] = reinterpret_cast<const unsigned short*>(args.cvec)[(tid >> 1) + i * 128];
                }
            tag0 = load_tag(gs) - 1;
        }
        asm volatile("barrier.cluster.arrive.relaxed.aligned;" ::: "memory");
        asm volatile("setmaxnreg.inc.sync.aligned.u32 240;");
        const int lane = threadIdx.x & 31;
        const int cw = warp - 4;
        const int w = cw >> 2;
        const int tid = threadIdx.x - 128;
        float* red = reinterpret_cast<float*>(smem_raw + SM_RED);
        DBG_INIT();
        DBG_G(120);
        DBG_T(100);

        uint32_t tag;
        {

            if (blockIdx.x < 72) {
                const uint32_t ws = sb + SM_Q + SLOT + tid * 16;
                float sc[5], a[8];
#pragma unroll
                for (int i = 0; i < 5; i++) sc[i] = __uint_as_float(cv[i] << 16);
#pragma unroll
                for (int i = 0; i < 5; i++) sc[i] = rbf(sc[i] * sigmoidf_(sc[i]));
#pragma unroll
                for (int i = 0; i < 8; i++) a[i] = 0.f;
                anchor(bar_full + 504, sc[0] + sc[1] + sc[2] + sc[3] + sc[4] + 2.f);
                asm volatile("cp.async.wait_all;" ::: "memory");
#pragma unroll
                for (int i = 0; i < 5; i++) mod_fma(a, lds128(ws + (i < 4 || tid < 128 ? i * 4096 : 0)), sc[i]);
                const float v = mod_reduce(a, lane);
                if (lane < 16) red[cw * 16 + lane] = v;

                bar_sync(3, 256);
                if (tid < 8 * MREP) {
                    float v0 = 0.f, v1 = 0.f;
#pragma unroll
                    for (int i = 0; i < 8; i++) { v0 += red[i * 16 + (tid & 7)]; v1 += red[i * 16 + 8 + (tid & 7)]; }
                    st_relaxed64(&gs->mod1[(tid >> 3) * D_ + blockIdx.x * 8 + (tid & 1) * 4 + (tid & 2) + ((tid >> 2) & 1)], pack_bf16(v0, v1), tag0 + 1);
                }
            }
            DBG_G(106);
            asm volatile("barrier.cluster.wait.aligned;" ::: "memory");
            mbar_wait(bar_x, 0);
            tag = load_tag(gs);
            uint32_t x[20];
            float st[12];
            rows_load(x, sb + SM_Q + (lane & 15) * XP + (lane >> 4) * 16 + cw * 32, cw);
#pragma unroll
            for (int i = 0; i < 12; i++) st[i] = 0.f;
#pragma unroll
            for (int k = 0; k < 9; k++) stats_add(st, x[2 * k], x[2 * k + 1], 0x3f803f80u);
            uint32_t mean2;
            float dot;
            const float rsd = rows_stats(st, reinterpret_cast<float4*>(red + 128), cw, lane, mean2, dot);
            rows_normalise(x, x, mean2, rsd, lane, []() {});
            fence_regs(x);
            uint4* smod = reinterpret_cast<uint4*>(smem_raw + SM_Q + M_MOD);
            if (tid < D_ / 4) {
                const uint4* mp = reinterpret_cast<const uint4*>(gs->mod1 + ((blockIdx.x >> 1) & (MREP - 1)) * D_) + tid;
                poll2x2(mp, mp + D_ / 4, tag, smod[tid], smod[D_ / 4 + tid]);
            }
            bar_sync(3, 256);
            DBG_G(107);
            const uint2* mp = reinterpret_cast<const uint2*>(smod) + cw * 8 + (lane & 3);
#pragma unroll
            for (int k = 0; k < 9; k++) {
                const uint32_t c1 = badd2(pair_of(mp + D_ / 2, k, cw), 0x3f803f80u), sa = pair_of(mp, k, cw);
                x[2 * k] = badd2(bmul2(x[2 * k], c1), sa);
                if (x[2 * k] == 0) x[2 * k] = 0x8000u;
                x[2 * k + 1] = badd2(bmul2(x[2 * k + 1], c1), sa);
            }
            uint4* hdst = g_h + (size_t)(rg * 36 + cw) * 32 + lane;
#pragma unroll
            for (int ch = 0; ch < 4; ch++) st_relaxed(hdst + ch * 256, x[4 * ch], x[4 * ch + 1], x[4 * ch + 2], x[4 * ch + 3]);
            st_relaxed64(reinterpret_cast<uint2*>(g_h + (size_t)(rg * 36 + 32) * 32) + tid, x[16], x[17]);
            __syncwarp();
            if (SPARE && lane == 0) mbar_arrive(bar_pub);
            DBG_G(108);
        }

        uint32_t rel_base;
        asm("mapa.shared::cluster.u32 %0, %1, %2;" : "=r"(rel_base) : "r"(bar_empty), "r"(lane & 1));
        auto release = [&](uint32_t slot) { if (lane < 2) mbar_arrive_cluster(rel_base + 8 * slot); };
        uint32_t q[32], p[32];
        float s[64], o[64];

        uint4* qpark = reinterpret_cast<uint4*>(smem_raw + SM_Q - SLOT) + cw * 256 + lane;
        {
            uint32_t h[144];
            const uint4* hf = g_h + (size_t)(qb * 8 + cw) * (36 * 32) + lane;
            auto load_h = [&](auto lo, auto hi) {
#pragma unroll
                for (int ks = lo.value; ks < hi.value; ks++) {
                    const uint4 v = h_frag(hf, ks, lane);
                    h[4 * ks] = v.x; h[4 * ks + 1] = v.y; h[4 * ks + 2] = v.z; h[4 * ks + 3] = v.w;
                }
            };
            auto check_h = [&](auto lo, auto hi) {
                uint32_t it = 0;
#pragma unroll 1
                while (true) {
                    uint32_t mn = ~0u;
#pragma unroll
                    for (int ks = lo.value; ks < hi.value; ks++) mn = __vimin3_u32(mn, h[4 * ks], h[4 * ks + 2]);
                    if (!__any_sync(0xffffffffu, mn == 0) || ++it >= SPIN / 16) break;
                    load_h(lo, hi);
                }
            };
            if (!HSENT) flag_wait(&g_flag_h[(qb * 8 + cw) * 32], tag);
            if (HSENT) __nanosleep(HDELAY);
            load_h(IC<0>{}, IC<4>{});
            DBG_T(104); DBG_G(109);
#pragma unroll
            for (int i = 0; i < 64; i++) o[i] = 0.f;
            uint32_t e = E0;
#pragma unroll 1
            for (int hd = 1;; hd++) {
                fence_regs(o);
                auto group = [&](auto tc) {
                    constexpr int t = tc.value, k0 = t ? 8 * t - 4 : 0;
                    const bool first = t == 0 && hd == 1;
                    mbar_wait(first ? bar_w0 : bar_full + 8 * (e & 3), (e >> 2) & 1);
                    const uint32_t dv = desc_lo(t ? 0 : 8192, UNIT) + (first ? 6 : e & 3) * (SLOT / 16);
                    if (HSENT && hd == 1) check_h(IC<k0>{}, IC<8 * t + 4>{});
                    WG_FENCE();
#pragma unroll
                    for (int ks = k0; ks < 8 * t + 4; ks++)
                        mma_rs128<1>(o, h[4 * ks], h[4 * ks + 1], h[4 * ks + 2], h[4 * ks + 3], desc_of(dv + (ks - k0) * 128), ks);
                    WG_COMMIT();
                    if (hd == 1) { if (t == 0) {   } if (t == 1) {   } if (t == 2) {   } if (t == 3) {   } if (t == 4) {   } }
                    if (t < 4 && hd == 1) load_h(IC<8 * t + 4>{}, IC<t < 4 ? 8 * t + 12 : 0>{});
                    if (t > 0) { WG_WAIT(1); if (t > 1 || hd > 1) release((e - 1) & 3); }
                    e++;
                };
                group(IC<0>{}); group(IC<1>{}); group(IC<2>{}); group(IC<3>{});
                if (e == 19) break;
                group(IC<4>{});
                WG_WAIT(0);
                if (hd == 1) {     }
                fence_regs(o);
                release((e - 1) & 3);
#pragma unroll
                for (int i = 0; i < 8; i++)
                    qpark[hd * 2048 + i * 32] = make_uint4(pack_bf16(o[8 * i], o[8 * i + 1]), pack_bf16(o[8 * i + 2], o[8 * i + 3]),
                                                           pack_bf16(o[8 * i + 4], o[8 * i + 5]), pack_bf16(o[8 * i + 6], o[8 * i + 7]));
                if (SPARE && hd == 2) {
                    float (&u)[32] = reinterpret_cast<float (&)[32]>(o);
                    fence_regs(u);
#pragma unroll
                    for (int t = 0; t < 3; t++) {
                        mbar_wait(bar_full + 8 * t, 1);
                        WG_FENCE();
#pragma unroll
                        for (int ks = 0; ks < (t < 2 ? 16 : 4); ks++)
                            mma_rs64<1>(u, h[64 * t + 4 * ks], h[64 * t + 4 * ks + 1], h[64 * t + 4 * ks + 2], h[64 * t + 4 * ks + 3],
                                        desc_of(desc_lo(t * SLOT, UNIT) + ks * 128), ks | t);
                        WG_COMMIT();
                        if (t > 0) { WG_WAIT(1); release(t - 1); }
                    }
                    WG_WAIT(0);
                    fence_regs(u);
                    release(2);
                    e = 15;
#pragma unroll
                    for (int i = 0; i < 4; i++)
                        qpark[3 * 2048 + i * 32] = make_uint4(pack_bf16(u[8 * i], u[8 * i + 1]), pack_bf16(u[8 * i + 2], u[8 * i + 3]),
                                                              pack_bf16(u[8 * i + 4], u[8 * i + 5]), pack_bf16(u[8 * i + 6], u[8 * i + 7]));
                }
            }
#pragma unroll
            for (int i = 0; i < 8; i++) {
                const uint4 v = qpark[2048 + i * 32];
                q[4 * i] = v.x; q[4 * i + 1] = v.y; q[4 * i + 2] = v.z; q[4 * i + 3] = v.w;
            }
#pragma unroll
            for (int i = 0; i < 32; i++) p[i] = h[112 + i];
            mbar_wait(bar_full + 24, 0);
            WG_WAIT(0);
            fence_regs(o);
            release(2);
        }
        DBG_T(105);
        DBG_G(125);

        uint8_t* frag = reinterpret_cast<uint8_t*>(__shfl_sync(0xffffffffu, reinterpret_cast<unsigned long long>(g_frag + (size_t)(rg * 8 + cw) * WREG + lane * 16), lane));
        const uint4* qnext = reinterpret_cast<const uint4*>(__shfl_sync(0xffffffffu, reinterpret_cast<unsigned long long>(padd(smem_raw, SM_Q + tid * 16 + cw * 3584)), lane));
        uint8_t* odst = reinterpret_cast<uint8_t*>(const_cast<uint4*>(qnext));
        qnext -= 2048;
        float m0, m1, l0 = 0.25f, l1 = 0.25f, t0, t1;
        uint32_t bad = 0;
        const int lw = cw & 3;
        const uint32_t relw = lw == RW && lane < 8, handw = lw == HW || cw == HW2;
        auto release4 = [&](uint32_t off) {
            asm volatile("{\n.reg .pred p;\nsetp.ne.b32 p, %1, 0;\n@p mbarrier.arrive.shared::cluster.b64 _, [%0];\n}" ::"r"(rel_base + off), "r"(relw) : "memory"); };
        auto handoff = [&]() {
            asm volatile("{\n.reg .pred p;\nsetp.ne.b32 p, %1, 0;\n@p bar.arrive %0, 192;\n}" ::"r"(2 - w), "r"(handw) : "memory"); };
        if (cw == 4 + HW) bar_arrive(1, 192);
        auto finish = [&](auto lo, auto hi, uint32_t bit, auto sink) {
#pragma unroll
            for (int i = lo.value; i < hi.value; i++) {
                const uint32_t v0 = pack_bf16(o[8 * i] * t0, o[8 * i + 1] * t0), v1 = pack_bf16(o[8 * i + 2] * t1, o[8 * i + 3] * t1);
                const uint32_t v2 = pack_bf16(o[8 * i + 4] * t0, o[8 * i + 5] * t0), v3 = pack_bf16(o[8 * i + 6] * t1, o[8 * i + 7] * t1);
                if (i == 0 && fabsf(o[0] * t0) >= 0x1p-31f) bad |= bit << 8;
                sink(i, v0, v1, v2, v3);
            }
        };
        float lq[6];
        auto row_parts = [&]() {
#pragma unroll
            for (int i = 0; i < 3; i++) { lq[i] = __shfl_xor_sync(0xffffffffu, l0, i + 1); lq[3 + i] = __shfl_xor_sync(0xffffffffu, l1, i + 1); }
        };
        auto row_sums = [&](uint32_t bit) {
            t0 = (l0 + lq[0]) + (lq[1] + lq[2]); t1 = (l1 + lq[3]) + (lq[4] + lq[5]);
            if (!(t0 >= LMIN && t0 < LMAX && t1 >= LMIN && t1 < LMAX)) bad |= bit;
        };
        auto issue_pv = [&](uint32_t dlo, int acc, auto lo, auto hi) {
            if (lo.value == 0) asm volatile("{\n.reg .pred p;\nsetp.eq.b32 p, %0, 0;\n@p bar.sync 4, 160;\n}" ::"r"(w) : "memory");
#pragma unroll
            for (int ks = lo.value; ks < hi.value; ks++)
                mma_rs128<1>(o, p[4 * ks], p[4 * ks + 1], p[4 * ks + 2], p[4 * ks + 3], desc_of(dlo + ks * 128), ks ? 1 : acc);
            WG_COMMIT();
        };
#pragma unroll
        for (int i = 0; i < 64; i++) s[i] = 0.f;
        uint32_t dv_lo = desc_lo(0, UNIT), voff = 0;
        auto issue_qk = [&]() {
            const uint32_t dk = dv_lo ^ (desc_lo(0, UNIT) ^ desc_lo(3 * SLOT, 16));
            bar_sync(1 + w, 192);
            fence_regs(s); fence_regs(q); fence_regs(o); fence_regs(p);
            WG_FENCE();
#pragma unroll
            for (int ks = 0; ks < 8; ks++)
                mma_rs128<0>(s, q[4 * ks], q[4 * ks + 1], q[4 * ks + 2], q[4 * ks + 3], desc_of(dk + (ks >> 2) * 1024 + (ks & 3) * 2), ks != 0);
            WG_COMMIT();
        };
        auto to_frag = [&](int i, uint32_t v0, uint32_t v1, uint32_t v2, uint32_t v3) {
            *reinterpret_cast<uint4*>(odst + i * 512) = make_uint4(v0, v1, v2, v3); };
        int n = 0;
        auto scores_ready = [&]() {
            WG_WAIT(1);
            fence_regs(s); fence_regs(q);
        };
        auto pass_on = [&]() {
            release4(voff ^ 24);
            handoff();
        };
#pragma unroll 1
        for (;;) {
            {
                row_parts();
                row_sums(1u << (n >> 4));
                if (RPE == 1) anchor(bar_full + 504, t0 + t1);
                issue_qk();
                t0 = rcp_fast(t0); t1 = rcp_fast(t1);
                l0 = 0.f; l1 = 0.f;
                odst = n ? frag + ((n >> 4) - 1) * 4096 : odst;
                if (RPE) anchor(bar_full + 504, (t0 + t1) * __uint_as_float((bad ^ (uint32_t)(uintptr_t)odst) & 0x3fffffff));
                asm volatile("{\n.reg .pred p;\nsetp.ne.b32 p, %1, 0;\n@p mbarrier.arrive.shared::cta.b64 _, [%0];\n}"
                             ::"r"(bar_qfree + (n >> 1) - 8), "r"(lane ? 0 : n) : "memory");
                issue_pv(dv_lo, 1, IC<0>{}, IC<8>{});
                scores_ready();
                float a0 = fmaxf(s[0], s[1]), a1 = fmaxf(s[2], s[3]), a2 = fmaxf(s[4], s[5]), a3 = fmaxf(s[6], s[7]);
#pragma unroll
                for (int i = 1; i < MAXG; i++) {
                    a0 = fmaxf(a0, fmaxf(s[8 * i], s[8 * i + 1])); a1 = fmaxf(a1, fmaxf(s[8 * i + 2], s[8 * i + 3]));
                    a2 = fmaxf(a2, fmaxf(s[8 * i + 4], s[8 * i + 5])); a3 = fmaxf(a3, fmaxf(s[8 * i + 6], s[8 * i + 7]));
                }
                const uint32_t a = pack_bf16(fmaxf(a0, a2), fmaxf(a1, a3));
                const uint32_t b = bmax2(bmax2(a, __shfl_xor_sync(0xffffffffu, a, 1)), bmax2(__shfl_xor_sync(0xffffffffu, a, 2), __shfl_xor_sync(0xffffffffu, a, 3)));
                pass_on();
                m0 = fmaf(-CS, bf_lo(b), -POFF); m1 = fmaf(-CS, bf_hi(b), -POFF);
            }
#pragma unroll 1
            for (;;) {
                DBG_T(n);
#pragma unroll
                for (int i = 0; i < 4 * STAGE; i++) s[i] = fmaf(s[i], CS, (i & 2) ? m1 : m0);
#pragma unroll
                for (int i = 0; i < 4 * SPLIT; i++) s[i] = ex2(s[i]);
#pragma unroll
                for (int i = 0; i < SPLIT; i++) { l0 += s[4 * i] + s[4 * i + 1]; l1 += s[4 * i + 2] + s[4 * i + 3]; }
                if (STAGE < 16) {
                    m0 = fmaf(l0, 0.f, m0); m1 = fmaf(l1, 0.f, m1);
                }
                anchor(bar_full + 504, l0 + l1);
                WG_WAIT(0);
                fence_regs(o); fence_regs(p);
                release4(voff);
                dv_lo ^= 2 * SLOT / 16;
                voff ^= 16;
                n++;
#pragma unroll
                for (int i = 4 * STAGE; i < 64; i++) s[i] = fmaf(s[i], CS, (i & 2) ? m1 : m0);
#pragma unroll
                for (int i = 4 * SPLIT; i < 64; i++) s[i] = ex2(s[i]);
#pragma unroll
                for (int i = SPLIT; i < 16; i++) { l0 += s[4 * i] + s[4 * i + 1]; l1 += s[4 * i + 2] + s[4 * i + 3]; }
#pragma unroll
                for (int i = 0; i < 32; i++) p[i] = pack_bf16(s[2 * i], s[2 * i + 1]);
                const int jn = n & 15;
                if (!(((0x8003 | RCM | RCM << 1) >> jn) & 1)) {
                    issue_qk();
                    issue_pv(dv_lo, 1, IC<0>{}, IC<8>{});
                    scores_ready();
                    pass_on();
                    continue;
                }
                if (jn == 1) {
                    finish(IC<0>{}, IC<ESPLIT>{}, 1u << (n >> 4), to_frag);
                    issue_qk();
                    finish(IC<ESPLIT>{}, IC<8>{}, 1u << (n >> 4), to_frag);
                    WG_FENCE();
                    issue_pv(dv_lo, 0, IC<0>{}, IC<8>{});
                    scores_ready();
                    pass_on();
                    continue;
                }
                if (jn == 0) break;
                if (RCM && jn != 15) {
                    if ((RCM >> jn) & 1) {
                        row_parts();
                        row_sums(2u << (n >> 4));
                        const uint32_t e0 = __float_as_uint(t0) >> 23, e1 = __float_as_uint(t1) >> 23;
                        m0 -= __uint_as_float(0x4b000000u | e0) - (8388608.f + 127.f - POFF);
                        m1 -= __uint_as_float(0x4b000000u | e1) - (8388608.f + 127.f - POFF);
                        t0 = __uint_as_float((254 - (int)POFF - e0) << 23); t1 = __uint_as_float((254 - (int)POFF - e1) << 23);
                        l0 *= t0; l1 *= t1;
                    } else {
#pragma unroll
                        for (int i = 0; i < 64; i++) o[i] *= (i & 2) ? t1 : t0;
                    }
                    issue_qk();
                    issue_pv(dv_lo, 1, IC<0>{}, IC<8>{});
                    scores_ready();
                    pass_on();
                    continue;
                }
                if (SPARE && n == 47) mbar_wait(bar_q3, 0);
                qnext = n == 63 ? reinterpret_cast<const uint4*>(frag) : qnext + 2048;
                issue_qk();
                issue_pv(dv_lo, 1, IC<0>{}, IC<8>{});
                scores_ready();
                pass_on();
#pragma unroll
                for (int i = 0; i < 8; i++) {
                    const uint4 v = qnext[i * 32];
                    q[4 * i] = v.x; q[4 * i + 1] = v.y; q[4 * i + 2] = v.z; q[4 * i + 3] = v.w;
                }
            }
            if (n == 64) break;
        }
        DBG_T(64);
        uint32_t a1[32], a2[32];
        row_parts();
        bar_sync(1 + w, 192);
        fence_regs(o); fence_regs(p);
        WG_FENCE();
        issue_pv(desc_lo(3 * SLOT, UNIT), 1, IC<0>{}, IC<8>{});
        if (w == 0) handoff();
        row_sums(16);
        t0 = rcp_fast(t0); t1 = rcp_fast(t1);
        mbar_wait(bar_mod, 0);
        WG_WAIT(0);
        fence_regs(o); fence_regs(p);
        release(3);
        finish(IC<0>{}, IC<8>{}, 16, [&](int i, uint32_t v0, uint32_t v1, uint32_t v2, uint32_t v3) {
            p[4 * i] = v0; p[4 * i + 1] = v1; p[4 * i + 2] = v2; p[4 * i + 3] = v3; });
        bad = __reduce_or_sync(0xffffffffu, bad);
        bad = ((bad | ~(bad >> 8)) >> 1) & 15;
        if (__builtin_expect(bad != 0, 0)) {
            uint8_t* keep = g_keep + (size_t)(rg * 8 + cw) * 4096 + lane * 16;
            frag_store(keep, p);
            attn_fallback(bad, tag, frag, keep, args.wq, args.kc, args.vc);
            frag_load(q, frag); frag_load(p, keep);
        }
        DBG_T(80);
        DBG_G(124);

        const uint32_t eye = (lane >> 3) == (lane & 3) ? 0x3f80u << ((lane & 4) * 4) : 0;
        auto sum8 = [&](uint32_t* r, const uint4 (&v)[8]) {
            float d[16];
#pragma unroll
            for (int i = 0; i < 16; i++) d[i] = 0.f;
#pragma unroll
            for (int src = 0; src < 8; src++) {
                mma1688(d + 8 * (src & 1), v[src].x, v[src].y, eye);
                mma1688(d + 8 * (src & 1) + 4, v[src].z, v[src].w, eye);
            }
#pragma unroll
            for (int i = 0; i < 4; i++) r[i] = pack_bf16(d[2 * i] + d[8 + 2 * i], d[2 * i + 1] + d[9 + 2 * i]);
        };
        auto sum8_slot = [&](uint32_t* r, uint32_t e) {
            mbar_wait(bar_full + 8 * (e & 3), (e >> 2) & 1);
            uint4 v[8];
#pragma unroll
            for (int src = 0; src < 8; src++) v[src] = lds128(sb + (e & 3) * SLOT + w * (UNIT - 2048) + src * 2048 + tid * 16);
            sum8(r, v);
        };
        uint4 v2[8], v3[8], wf[27];
        uint2 u4[8], gw[9];
        uint32_t x1[20], xs, pa, ta;
        const uint8_t *mb, *mb4;
        int tid_;
        auto load_wf = [&](auto lo, auto hi) {
            const uint32_t wa = sb + SM_Q + ((cw & 1) * D_ + (cw >> 1) * 32 + (tid_ & 7) + (tid_ & 16) / 2) * 80 + (tid_ & 8) * 2;
#pragma unroll
            for (int i = lo.value; i < hi.value; i++)
                wf[i] = ldsm4t((i < 24 ? wa + ((i / 3 & 3) * 8 + i / 12) * 1280 : wa + (32 - (cw >> 1)) * 1280) + (i % 3) * 32);
        };
        uint32_t at[18];
        {
            float ua[32], ub[32];
            uint32_t e = 148, prev = 4;
            auto step = [&](float (&u)[32], const uint32_t (&a)[32], const uint32_t (&b)[32], int acc) {
                mbar_wait(bar_full + 8 * (e & 3), (e >> 2) & 1);
                const uint64_t dv = mkdesc(sb + (e & 3) * SLOT, UNIT, 1024);
                if (!acc) fence_regs(u);
                WG_FENCE();
#pragma unroll
                for (int ks = 0; ks < 8; ks++) mma_rs64<1>(u, a[4 * ks], a[4 * ks + 1], a[4 * ks + 2], a[4 * ks + 3], dv + ks * 128, ks | acc);
#pragma unroll
                for (int ks = 0; ks < 8; ks++) mma_rs64<1>(u, b[4 * ks], b[4 * ks + 1], b[4 * ks + 2], b[4 * ks + 3], dv + 1024 + ks * 128, 1);
                WG_COMMIT();
                WG_WAIT(1);
                if (prev < 4) release(prev);
                prev = e & 3;
                e++;
            };
            auto store = [&](float (&u)[32], uint8_t* dst) {
                fence_regs(u);
#pragma unroll
                for (int i = 0; i < 4; i++)
                    st_relaxed4(dst + i * 512, pack_bf16(u[8 * i], u[8 * i + 1]), pack_bf16(u[8 * i + 2], u[8 * i + 3]),
                                pack_bf16(u[8 * i + 4], u[8 * i + 5]), pack_bf16(u[8 * i + 6], u[8 * i + 7]));
            };
#pragma unroll
            for (int i = 0; i < 8; i++) at[i] = 0;
#pragma unroll
            for (int i = 0; i < 32; i++) { ua[i] = 0.f; ub[i] = 0.f; }
            fence_regs(q); fence_regs(p);
            step(ua, q, p, 0);
            frag_load(a1, frag + 4096);
            mbar_wait(bar_full + 8, 1);
            frag_load(a2, frag + 8192);
            step(ub, q, p, 0);
            WG_WAIT(0);
            release(1);
            prev = 4;
            fence_regs(a1); fence_regs(a2); fence_regs(ua); fence_regs(ub);
#pragma unroll 1
            for (int ch = 0; ch < 4; ch++) {
                step(ua, a1, a2, 1);
                if (ch > 0) {
                    if (ch >= 2) {
#pragma unroll
                        for (int i = 0; i < 4; i++) at[i] = at[4 + i];
                        sum8_slot(at + 4, e);
                        __syncwarp();
                        release(e & 3);
                        e++;
                        WG_WAIT(0);
                        release(prev);
                        prev = 4;
                    }
                    step(ub, q, p, 0);
                } else {
                    WG_WAIT(0);
                }
                store(ua, frag + ch * 4096);
                step(ub, a1, a2, 1);
                step(ua, q, p, 0);
                store(ub, frag + ch * 4096 + 2048);
                __syncwarp();
                if (lane == 0 && ch < 3) mbar_arrive(bar_pub + 8 + 8 * ch);
            }
            tid_ = __shfl_sync(0xffffffffu, tid, lane);
            mb = padd(g_frag, (qb * 64 + j) * WREG + 3 * 4096 + tid * 16);
            mb4 = padd(mb, 4096 + ((cw >> 1) - cw) * 512 + (cw & 1) * 8);
            step(ua, a1, a2, 1);
            xs = sb + (tid_ & 15) * XP + (tid_ & 16) + cw * 32;
            pa = sb + w * (UNIT - 2048) + tid_ * 16;
            ta = sb + (cw * 8 + (tid_ & 3)) * 8;
#pragma unroll
            for (int k = 0; k < 9; k++) {
                gw[k] = lds64(ta + SM_T + (k < 8 ? (k >> 1) * 64 + (k & 1) * 4 : 256 - cw * 4) * 8);
                if (!(tid_ & 4)) gw[k].y = 0x3f803f80u;
            }
            mbar_wait(bar_g, 0);
            load_wf(IC<0>{}, IC<WF0>{});
            mbar_wait(bar_full, 0);
            rows_load(x1, xs, cw);
            if (P2E) {
                mbar_wait(bar_full + 8, 0);
#pragma unroll
                for (int src = 0; src < 8; src++) v2[src] = lds128(pa + SLOT + src * 2048);
            }
            WG_WAIT(0);
            release(3);
            store(ua, frag + 4 * 4096);
        }
        DBG_T(81);
        DBG_G(122);

        {
        const int tid = tid_, lane = tid & 31;
        const int g8 = lane >> 2, qd = lane & 3, l16 = lane & 15;
        uint32_t h2[18], gb[9], k1, k2;
        float4* rec = reinterpret_cast<float4*>(red + 128);
        const uint2* candp = reinterpret_cast<const uint2*>(padd(g_cand, ((blockIdx.x & (CREP - 1)) * NCTA + (tid >> 1)) * 32 + (tid & 1) * 8));
        uint2 cd;
        auto stage_out = [&]() {
#pragma unroll
            for (int k = 0; k < 9; k++) {
                x1[2 * k] = badd2(x1[2 * k], bmul2(gb[k], h2[2 * k]));
                x1[2 * k + 1] = badd2(x1[2 * k + 1], bmul2(gb[k], h2[2 * k + 1]));
            }
#pragma unroll
            for (int ch = 0; ch < 4; ch++) stsm_x4(xs + ch * 256, x1[4 * ch], x1[4 * ch + 1], x1[4 * ch + 2], x1[4 * ch + 3]);
            asm volatile("stmatrix.sync.aligned.m8n8.x2.shared.b16 [%0], {%1, %2};" ::"r"(xs + 1024 - cw * 16), "r"(x1[16]), "r"(x1[17]) : "memory");
        };
        {
            uint32_t it = 0, miss;
            if (!P2E) {
                mbar_wait(bar_full + 8, 0);
#pragma unroll
                for (int src = 0; src < 8; src++) v2[src] = lds128(pa + SLOT + src * 2048);
            }
            sum8(at + 8, v2);
            float st[12];
#pragma unroll
            for (int i = 0; i < 12; i++) st[i] = 0.f;
            auto add_pair = [&](int k) {
                x1[2 * k] = badd2(x1[2 * k], bmul2(gw[k].x, at[2 * k]));
                x1[2 * k + 1] = badd2(x1[2 * k + 1], bmul2(gw[k].x, at[2 * k + 1]));
                stats_add(st, x1[2 * k], x1[2 * k + 1], gw[k].y);
            };
#pragma unroll
            for (int k = 0; k < 6; k++) add_pair(k);
            mbar_wait(bar_full + 16, 0);
#pragma unroll
            for (int src = 0; src < 8; src++) v3[src] = lds128(pa + 2 * SLOT + src * 2048);
#pragma unroll 1
            do {
                if (BO && it) __nanosleep(BO);
                miss = 0;
#pragma unroll
                for (int src = 0; src < 8; src++) reload16(v3[src], mb + (size_t)src * 8 * WREG, miss);
            } while (__any_sync(0xffffffffu, miss) && ++it < SPIN / 16);
            if (lane < 4) mbar_arrive_cluster(rel_base + 8 * (1 + (lane >> 1)));
            sum8(at + 12, v3);
            add_pair(6); add_pair(7);
            load_wf(IC<WF0>{}, IC<WF1>{});
            uint2 cs[9];
#pragma unroll
            for (int k = 0; k < 9; k++) cs[k] = lds64(ta + SM_TC + (k < 8 ? (k >> 1) * 64 + (k & 1) * 4 : 256 - cw * 4) * 8);
            mbar_wait(bar_pre, 0);
            mbar_wait(bar_full + 24, 0);
#pragma unroll
            for (int src = 0; src < 8; src++) u4[src] = lds64(sb + 3 * SLOT + src * 2048 + (cw >> 1) * 512 + lane * 16 + (cw & 1) * 8);
#pragma unroll 1
            do {
                if (BO && miss) __nanosleep(BO);
                miss = 0;
#pragma unroll
                for (int src = 0; src < 8; src++) reload8(u4[src], mb4 + (size_t)src * 8 * WREG, miss);
            } while (__any_sync(0xffffffffu, miss) && ++it < SPIN / 16);
            float d[8] = {0.f, 0.f, 0.f, 0.f, 0.f, 0.f, 0.f, 0.f};
#pragma unroll
            for (int i = 0; i < 4; i++) mma16816(d + 4 * (i & 1), u4[2 * i].x, u4[2 * i].y, u4[2 * i + 1].x, u4[2 * i + 1].y, eye, eye);
            at[16] = pack_bf16(d[0] + d[4], d[1] + d[5]); at[17] = pack_bf16(d[2] + d[6], d[3] + d[7]);
            add_pair(8);
            DBG_G(123);
            const float2 ws = *reinterpret_cast<const float2*>(smem_raw + SM_TS);
            uint4* cdst = padd(g_cand, CFULL ? ((tid >> 1) * NCTA + rg) * 32 + (tid & 1) * 16 : (tid * NCTA + rg) * 32);
            uint32_t mean2;
            float dot;
            const float rsd = rows_stats(st, rec, cw, lane, mean2, dot);
            const uint32_t b = __float_as_uint(fmaf(fmaf(-bf_lo(mean2), ws.x, dot), rsd, ws.y));
            const uint32_t key = (((b & 0x80000000u) ? ~b : (b | 0x80000000u)) | 2047u) - (rg * 16 + l16);
            top2(key, k1, k2);
            if (tid < (CFULL + 1) * CREP) st_relaxed(cdst, k1, tag, k2, tag);
            cd = ld_relaxed64(candp);
            rows_normalise(h2, x1, mean2, rsd, lane, [&]() {
#pragma unroll
                for (int k = 0; k < 9; k++) gb[k] = lds32(sb + SM_TG + (cw * 8 + qd + (k < 8 ? (k >> 1) * 64 + (k & 1) * 4 : 256 - cw * 4)) * 4);
                if (WFE) load_wf(IC<WF1>{}, IC<WF2>{});
            });
#pragma unroll
            for (int k = 0; k < 18; k++) h2[k] = badd2(bmul2(h2[k], cs[k >> 1].x), cs[k >> 1].y);
            const uint32_t r1 = ~k1 & 15, r2 = ~k2 & 15;
            uint32_t todo = ((r1 & 7) == g8) | ((r2 & 7) == g8) << 1;
#pragma unroll 1
            while (todo) {
                const bool second = !(todo & 1), hi = (second ? r2 : r1) & 8;
                uint4* dst = padd(g_rows, ((rg * 2 + second) * RSLOT + cw * 16 + qd) * 16);
                uint32_t r[18];
#pragma unroll
                for (int k = 0; k < 9; k++) { r[k] = hi ? h2[2 * k + 1] : h2[2 * k]; r[9 + k] = hi ? x1[2 * k + 1] : x1[2 * k]; }
                fence_regs(r);
                st_relaxed(dst, r[0], r[1], r[2], r[3]);
                st_relaxed(dst + 4, r[4], r[5], r[6], r[7]);
                st_relaxed64(reinterpret_cast<uint2*>(padd(dst, 2048 - cw * 224 - qd * 8)), r[8], r[17]);
                st_relaxed(dst + 8, r[9], r[10], r[11], r[12]);
                st_relaxed(dst + 12, r[13], r[14], r[15], r[16]);
                todo &= todo - 1;
            }
            __syncwarp();

            if (SO == 0) stage_out();
            if (!WFE) load_wf(IC<WF1>{}, IC<WF2>{});
        }
        DBG_G(110);
        float2* part = reinterpret_cast<float2*>(smem_raw + 3 * SLOT + UNIT);
        bf16* act = reinterpret_cast<bf16*>(smem_raw + 3 * SLOT + UNIT + 4096);
        {
            uint32_t it = 0;
            const bool own = (tid >> 1) == rg;
            const uint32_t ks = sb + 3 * SLOT + UNIT + 5120;
#pragma unroll 1
            while (cd.y != tag && !own && ++it < SPIN / 16) cd = ld_relaxed64(candp);
            asm volatile("st.shared.u32 [%0], %1;" ::"r"(ks + tid * 4), "r"(own ? (tid & 1) ? k2 : k1 : cd.x) : "memory");
            bar_sync(3, 256);
            DBG_G(111);
            const uint4 a = lds128(ks + lane * 16), b = lds128(ks + 512 + lane * 16);
            const uint32_t a1 = max(a.x, a.z), a2 = __vimax3_u32(min(a.x, a.z), a.y, a.w);
            const uint32_t b1 = max(b.x, b.z), b2 = __vimax3_u32(min(b.x, b.z), b.y, b.w);
            const uint32_t c1 = max(a1, b1), c2 = __vimax3_u32(min(a1, b1), a2, b2);
            k1 = __reduce_max_sync(0xffffffffu, c1);
            k2 = __reduce_max_sync(0xffffffffu, c1 == k1 ? c2 : c1);
        }
        const int sel0 = ~k1 & 2047, sel1 = ~k2 & 2047;
        const uint32_t slot0 = (sel0 >> 4) * 2, slot1 = (sel1 >> 4) * 2 + ((sel0 ^ sel1) < 16);
        uint4 b[9], b2[3];
        {
            const bool tk = cw < 4 ? cw & 2 : lane & 16;
            const int ri = cw < 4 ? tid & 63 : 64 + l16;
            const uint4* hp = padd(g_rows, ((tk ? slot1 : slot0) * RSLOT + (cw < 4 ? ri + (ri & 56) : ri + 64)) * 16);
            const uint32_t hs = sb + 3 * SLOT + UNIT + 8192;
            uint4 hr = make_uint4(cw < 5 ? ~0u : 0, 0, 0, 0);
            uint32_t it = 0, miss;
            reload16(hr, hp, miss);
            if (OUTP == 0 && SO == 0 && tid == 255) {
                reinterpret_cast<int2*>(red)[8] = make_int2(sel0, sel1);
                mbar_arrive(bar_out);
            }
            if (SO == 1) stage_out();
            load_wf(IC<WF2>{}, IC<27>{});
            mbar_wait(bar_full + 8, 1);
            mbar_wait(bar_full + 16, 1);
            {
                const uint32_t da = sb + (lane < 18 ? SLOT + lane * XP : 2 * SLOT + (lane - 18) * XP) + cw * 144;
                const uint32_t db = sb + 2 * SLOT + (14 + (lane & 3)) * XP + cw * 144 + (lane >> 3) * 16;
#pragma unroll
                for (int i = 0; i < 9; i++) b[i] = ldsm4t(da + i * 16);
#pragma unroll
                for (int i = 0; i < 3; i++) b2[i] = ldsm4t(db + i * 48);
            }
#pragma unroll 1
            do {
                miss = 0;
                reload16(hr, hp, miss);
            } while (__any_sync(0xffffffffu, miss) && ++it < SPIN / 16);
            if (cw < 5) asm volatile("st.shared.v4.u32 [%0], {%1, %2, %3, %4};" ::"r"(hs + (tk * 84 + ri) * 16), "r"(hr.x), "r"(hr.y), "r"(hr.z), "r"(hr.w) : "memory");
            bar_sync(3, 256);
            if (OUTP == 0 && SO == 1 && tid == 255) {
                reinterpret_cast<int2*>(red)[8] = make_int2(sel0, sel1);
                mbar_arrive(bar_out);
            }
            uint4 hv[4];
            uint32_t hw[2];
#pragma unroll
            for (int i = 0; i < 4; i++) hv[i] = lds128(hs + ((g8 & 1) * 84 + (cw >> 1) * 16 + qd + i * 4) * 16);
#pragma unroll
            for (int i = 0; i < 2; i++)
                hw[i] = lds32(hs + ((g8 & 1) * 84 + 64) * 16 + (cw >> 1) * 64 + qd * 8 + i * 32);
            DBG_G(112);
            float acc[24];
#pragma unroll
            for (int i = 0; i < 24; i++) acc[i] = 0.f;
#pragma unroll
            for (int i = 0; i < 27; i++) {
                const int ks = i / 3;
                mma16816(acc + 4 * (i % 6), wf[i].x, wf[i].y, wf[i].z, wf[i].w, ks == 8 ? hw[0] : (ks & 1) ? hv[ks >> 1 & 3].z : hv[ks >> 1 & 3].x,
                         ks == 8 ? hw[1] : (ks & 1) ? hv[ks >> 1 & 3].w : hv[ks >> 1 & 3].y);
            }
            if (qd == 0) {
#pragma unroll
                for (int i = 0; i < 5; i++) part[cw * 48 + i * 8 + g8] = make_float2(acc[2 * i] + acc[12 + 2 * i], acc[2 * i + 1] + acc[13 + 2 * i]);
            }
        }
        {
            uint2* dst = padd(g_ypart, ((((g8 & 1) * 36 + ((cw * 9) >> 1)) * NCTA + blockIdx.x) * 8 + (cw & 1) * 4 + qd) * 8);
            uint2* dst1 = dst + ((cw & 1) ? NCTA * 8 - 4 : 4);
            bar_sync(3, 256);

            {
                const float* pp = reinterpret_cast<const float*>(part) + ((blockIdx.x & 1) << 3) + (tid & 127);
                const float gs = rbf((pp[0] + pp[192]) + (pp[384] + pp[576])), us = rbf((pp[96] + pp[288]) + (pp[480] + pp[672]));
                const float v = rbf(gs * sigmoidf_(gs)) * us;
                if (tid < 80) act[(tid & 1) * 56 + (tid >> 1)] = __float2bfloat16_rn(tid < 72 ? v : 0.f);
            }
            bar_sync(3, 256);
            DBG_G(113);
            const uint32_t ap = sb + 3 * SLOT + UNIT + 4096 + (lane & 1) * 112 + (lane >> 4) * 16;
            const uint4 a0 = ldsm4(ap), a1 = ldsm4(ap + 32), a2 = ldsm4(ap + 64);
            float y[36];
#pragma unroll
            for (int i = 0; i < 36; i++) y[i] = 0.f;
#pragma unroll
            for (int i = 0; i < 9; i++) {
                const uint32_t bl = i % 3 == 0 ? b2[i / 3].x : i % 3 == 1 ? b2[i / 3].y : b2[i / 3].z;
                mma16816(y + 4 * i, a0.x, a0.y, a0.z, a0.w, b[i].x, b[i].y);
                mma16816(y + 4 * i, a1.x, a1.y, a1.z, a1.w, b[i].z, b[i].w);
                mma1688(y + 4 * i, a2.x, a2.y, bl);
            }
#pragma unroll
            for (int i = 0; i < 9; i++)
                if (lane < 8) st_relaxed64(((i & 1) ? dst1 : dst) + (i >> 1) * (NCTA * 8), __float_as_uint(y[4 * i]), __float_as_uint(y[4 * i + 1]));
        }
        DBG_G(114);
        if (OUTP == 1 && tid == 255) {
            reinterpret_cast<int2*>(red)[8] = make_int2(sel0, sel1);
            mbar_arrive(bar_out);
        }
        if (blockIdx.x == 127 && tid == 0) gs->epoch[0] = tag;
        if (blockIdx.x < 72) {
            const int tok = blockIdx.x >= 36, grp = blockIdx.x - tok * 36, cp = grp * 8 + (lane & 7);
            const uint2* src = padd(g_ypart, (blockIdx.x * NCTA * 8 + tid) * 8);
            const uint8_t* hsrc = reinterpret_cast<const uint8_t*>(padd(g_rows, (tok ? slot1 : slot0) * (RSLOT * 16) +
                (grp < 32 ? (grp & 7) * 256 + (grp >> 4) * 64 + qd * 16 + (grp & 8) + (lane & 4) : 2048 + (cp - 256) * 8)));
            const uint8_t* xsrc = hsrc + (grp < 32 ? 128 : 4);
            uint32_t* dst = padd(reinterpret_cast<uint32_t*>(args.out), (tok ? sel1 : sel0) * (D_ * 2) + cp * 4);
            const uint32_t gb = reinterpret_cast<const uint32_t*>(smem_raw + SM_TG)[cp];
            const uint32_t ksel = ((tok ? k2 : k1) & ~2047u) | 1024u;
            const float sg = sigmoidf_(rbf(__uint_as_float((ksel & 0x80000000u) ? (ksel & 0x7fffffffu) : ~ksel)));
            uint2 v[4];
            uint32_t hv, xv, it = 0;
            bool miss;
#pragma unroll 1
            do {
#pragma unroll
                for (int i = 0; i < 4; i++) v[i] = ld_relaxed64(src + i * 256);
                hv = ld_relaxed32(hsrc);
                xv = ld_relaxed32(xsrc);
                miss = max(__vimax3_u32(v[0].x, v[1].x, v[2].x), __vimax3_u32(v[3].x, hv, xv)) == ~0u;
            } while (__any_sync(0xffffffffu, miss) && ++it < SPIN / 16);
            float y0 = (__uint_as_float(v[0].x) + __uint_as_float(v[1].x)) + (__uint_as_float(v[2].x) + __uint_as_float(v[3].x));
            float y1 = (__uint_as_float(v[0].y) + __uint_as_float(v[1].y)) + (__uint_as_float(v[2].y) + __uint_as_float(v[3].y));
            y0 += __shfl_xor_sync(0xffffffffu, y0, 8); y1 += __shfl_xor_sync(0xffffffffu, y1, 8);
            y0 += __shfl_xor_sync(0xffffffffu, y0, 16); y1 += __shfl_xor_sync(0xffffffffu, y1, 16);
            if (lane < 8) reinterpret_cast<float2*>(rec)[cw * 8 + lane] = make_float2(y0, y1);
            bar_sync(3, 256);
            if (cw == 0) {
                const float2 t0_ = reinterpret_cast<const float2*>(rec)[lane], t1_ = reinterpret_cast<const float2*>(rec)[32 + lane];
                y0 = t0_.x + t1_.x; y1 = t0_.y + t1_.y;
                y0 += __shfl_xor_sync(0xffffffffu, y0, 8); y1 += __shfl_xor_sync(0xffffffffu, y1, 8);
                y0 += __shfl_xor_sync(0xffffffffu, y0, 16); y1 += __shfl_xor_sync(0xffffffffu, y1, 16);
                const uint32_t y2 = bmul2(pack_bf16(y0, y1), pack_bf16(sg, sg));
                if (lane < 8) *dst = badd2(xv, bmul2(gb, badd2(hv, y2)));
            }
        }
        }
        DBG_T(88);
        DBG_G(121);
    }
}

typedef CUresult (*EncodeFn)(CUtensorMap*, CUtensorMapDataType, cuuint32_t, void*, const cuuint64_t*, const cuuint64_t*,
                             const cuuint32_t*, const cuuint32_t*, CUtensorMapInterleave, CUtensorMapSwizzle,
                             CUtensorMapL2promotion, CUtensorMapFloatOOBfill);

static void make_map(EncodeFn enc, CUtensorMap* m, const void* ptr, int rank, const cuuint64_t* dims,
                     const cuuint64_t* strides, const cuuint32_t* box, CUtensorMapSwizzle sw = CU_TENSOR_MAP_SWIZZLE_128B,
                     CUtensorMapDataType dt = CU_TENSOR_MAP_DATA_TYPE_BFLOAT16) {
    const cuuint32_t es[3] = {1, 1, 1};
    enc(m, dt, rank, const_cast<void*>(ptr), dims, strides, box, es,
        CU_TENSOR_MAP_INTERLEAVE_NONE, sw, CU_TENSOR_MAP_L2_PROMOTION_L2_128B,
        CU_TENSOR_MAP_FLOAT_OOB_FILL_NONE);
}

extern "C" void kernel_launch(void* const* d_in, const int* in_sizes, int n_in, void* d_out, int out_size) {
    const bf16* x = (const bf16*)d_in[0];
    const bf16* kc = (const bf16*)d_in[1];
    const bf16* vc = (const bf16*)d_in[2];
    const bf16* wq = (const bf16*)d_in[3];
    const bf16* wo = (const bf16*)d_in[4];
    const bf16* w_r = (const bf16*)d_in[6];
    const bf16* w_gate = (const bf16*)d_in[7];
    const bf16* w_up = (const bf16*)d_in[8];
    const bf16* w_down = (const bf16*)d_in[9];
    const bf16* cvec = (const bf16*)d_in[10];
    const bf16* w_mod = (const bf16*)d_in[11];
    bf16* out = (bf16*)d_out;

    void* fn = nullptr;
    cudaDriverEntryPointQueryResult qr;
    cudaGetDriverEntryPoint("cuTensorMapEncodeTiled", &fn, cudaEnableDefault, &qr);
    EncodeFn enc = (EncodeFn)fn;
    void* p_s;
    cudaGetSymbolAddress(&p_s, g_s);

    CUtensorMap tm_wq, tm_k, tm_v, tm_wo, tm_p, tm_x, tm_d, tm_g, tm_u;
    { cuuint64_t d[2] = {QD, D_}, s[1] = {QD * 2}; cuuint32_t b[2] = {64, 128}; make_map(enc, &tm_wq, wq, 2, d, s, b); }
    { cuuint64_t d[2] = {DH, HKV * S_}, s[1] = {DH * 2}; cuuint32_t b[2] = {64, 128};
      make_map(enc, &tm_k, kc, 2, d, s, b); make_map(enc, &tm_v, vc, 2, d, s, b); }
    { cuuint64_t d[2] = {D_, QD}, s[1] = {D_ * 2}; cuuint32_t b[2] = {64, 128}; make_map(enc, &tm_wo, wo, 2, d, s, b); }
    { cuuint64_t d[3] = {256, 160, NCTA}, s[2] = {1024, 8 * WREG}; cuuint32_t b[3] = {256, 2, 8};
      make_map(enc, &tm_p, ((Scratch*)p_s)->frag, 3, d, s, b, CU_TENSOR_MAP_SWIZZLE_NONE, CU_TENSOR_MAP_DATA_TYPE_UINT32); }
    { cuuint64_t d[2] = {D_ / 4, S_}, s[1] = {D_ * 2}; cuuint32_t b[2] = {XP / 8, 16};
      make_map(enc, &tm_x, x, 2, d, s, b, CU_TENSOR_MAP_SWIZZLE_NONE, CU_TENSOR_MAP_DATA_TYPE_UINT64); }
    { cuuint64_t d[2] = {D_ / 4, F_}, s[1] = {D_ * 2}; cuuint32_t b[2] = {XP / 8, 18};
      make_map(enc, &tm_d, w_down, 2, d, s, b, CU_TENSOR_MAP_SWIZZLE_NONE, CU_TENSOR_MAP_DATA_TYPE_UINT64); }
    { cuuint64_t d[2] = {F_, D_}, s[1] = {F_ * 2}; cuuint32_t b[2] = {40, 24};
      make_map(enc, &tm_g, w_gate, 2, d, s, b, CU_TENSOR_MAP_SWIZZLE_NONE); make_map(enc, &tm_u, w_up, 2, d, s, b, CU_TENSOR_MAP_SWIZZLE_NONE); }

    cudaFuncSetAttribute(fused_kernel<true>, cudaFuncAttributeMaxDynamicSharedMemorySize, SM_TOTAL);
    cudaFuncSetAttribute(fused_kernel<false>, cudaFuncAttributeMaxDynamicSharedMemorySize, SM_TOTAL);
    cudaLaunchConfig_t cfg = {};
    cfg.gridDim = NCTA + 4; cfg.blockDim = 384; cfg.dynamicSmemBytes = SM_TOTAL;
    cudaLaunchAttribute at;
    at.id = cudaLaunchAttributeClusterDimension; at.val.clusterDim.x = 2; at.val.clusterDim.y = 1; at.val.clusterDim.z = 1;
    cfg.attrs = &at; cfg.numAttrs = 1;
    int ncl = 0;
    if (cudaOccupancyMaxActiveClusters(&ncl, fused_kernel<true>, &cfg) != cudaSuccess) { ncl = 0; cudaGetLastError(); }
    Args args{w_mod, cvec, (Scratch*)p_s, out, x, kc, vc, wq, wo, w_r, w_down};
    if (USE_SPARE && ncl >= NCTA / 2 + 2)
        fused_kernel<true><<<NCTA + 4, 384, SM_TOTAL>>>(args, tm_wq, tm_k, tm_v, tm_wo, tm_p, tm_x, tm_d, tm_g, tm_u);
    else
        fused_kernel<false><<<NCTA, 384, SM_TOTAL>>>(args, tm_wq, tm_k, tm_v, tm_wo, tm_p, tm_x, tm_d, tm_g, tm_u);
}
```

```cpp
#include <cuda_runtime.h>
#include <cuda_bf16.h>
#include <cuda.h>
#include <stdint.h>
#include <math.h>

typedef __nv_bfloat16 bf16;

constexpr int S_ = 2048;
constexpr int D_ = 576;
constexpr int HQ = 32, HKV = 16, DH = 128;
constexpr int F_ = 4608;
constexpr int QD = HQ * DH;

constexpr int NCTA = 128;
constexpr int WREG = 5 * 4096;
constexpr int CREP = 8;
constexpr int RSLOT = 144;
constexpr int MREP = 4;
struct Scratch {
    unsigned int epoch[128];
    unsigned int flag_mod[NCTA];
    unsigned int flag_part[16 * 32];
    unsigned int flag_q3[16 * 32];
    unsigned int flag_h[NCTA * 32];
    uint2 mod1[MREP * D_];
    uint32_t mod2[4 * D_];
    uint4 cand[CREP * NCTA * 2];
    uint2 ypart[72 * NCTA * 8];
    uint4 h[2][NCTA * 36 * 32];
    uint4 q3[NCTA * 8 * 128];
    uint4 rows[NCTA * 2 * RSLOT];
    uint8_t frag[NCTA * 8 * WREG];
    uint8_t keep[NCTA * 8 * 4096];
};
__device__ __align__(1024) Scratch g_s;
#define g_h gs->h[tag & 1]
#define g_q3 gs->q3
#define g_keep gs->keep
#define g_flag_h gs->flag_h
#define g_flag_part gs->flag_part
#define g_flag_mod gs->flag_mod
#define g_flag_q3 gs->flag_q3
#define g_frag gs->frag
#define g_cand gs->cand
#define g_ypart gs->ypart
#define g_rows gs->rows

#define DBG_INIT()
#define DBG_P(i)
#define DBG_PG(i)
#define DBG_T(i)
#define DBG_G(i)

__device__ __forceinline__ uint32_t pack_bf16(float lo, float hi) {
    uint32_t r;
    asm("cvt.rn.bf16x2.f32 %0, %1, %2;" : "=r"(r) : "f"(hi), "f"(lo));
    return r;
}
__device__ __forceinline__ float rbf(float x) { return __uint_as_float(pack_bf16(0.f, x)); }
__device__ __forceinline__ float bf_lo(uint32_t v) { return __uint_as_float(v << 16); }
__device__ __forceinline__ float bf_hi(uint32_t v) { return __uint_as_float(v & 0xffff0000u); }
__device__ __forceinline__ float ex2(float x) {
    float y;
    asm("ex2.approx.ftz.f32 %0, %1;" : "=f"(y) : "f"(x));
    return y;
}
template <class T>
__device__ __forceinline__ T* padd(T* p, uint32_t off) {
    unsigned long long r;
    asm("{\n.reg .b32 l, h;\nmov.b64 {l, h}, %1;\nadd.cc.u32 l, l, %2;\naddc.u32 h, h, 0;\nmov.b64 %0, {l, h};\n}" : "=l"(r) : "l"(p), "r"(off));
    return reinterpret_cast<T*>(r);
}
__device__ __forceinline__ uint32_t smem_u32(const void* p) { return (uint32_t)__cvta_generic_to_shared(p); }
__device__ __forceinline__ void mbar_init(uint32_t bar, uint32_t cnt) {
    asm volatile("mbarrier.init.shared::cta.b64 [%0], %1;" ::"r"(bar), "r"(cnt) : "memory");
}
__device__ __forceinline__ void mbar_expect_tx(uint32_t bar, uint32_t bytes) {
    asm volatile("mbarrier.arrive.expect_tx.shared::cta.b64 _, [%0], %1;" ::"r"(bar), "r"(bytes) : "memory");
}
__device__ __forceinline__ void mbar_arrive(uint32_t bar) {
    asm volatile("mbarrier.arrive.shared::cta.b64 _, [%0];" ::"r"(bar) : "memory");
}
__device__ __forceinline__ void mbar_arrive_cluster(uint32_t cluster_addr) {
    asm volatile("mbarrier.arrive.shared::cluster.b64 _, [%0];" ::"r"(cluster_addr) : "memory");
}
constexpr uint32_t SPIN = 1u << 20;
__device__ __forceinline__ void mbar_wait(uint32_t bar, uint32_t parity) {
    asm volatile("{\n.reg .pred p;\n.reg .b32 c;\nmov.b32 c, 0;\n"
                 "W_%=:\nmbarrier.try_wait.parity.shared::cta.b64 p, [%0], %1;\n@p bra D_%=;\n"
                 "add.u32 c, c, 1;\nsetp.lt.u32 p, c, 0x100000;\n@p bra W_%=;\nD_%=:\n}"
                 ::"r"(bar), "r"(parity) : "memory");
}
__device__ __forceinline__ void anchor(uint32_t addr, float v) {
    asm volatile("{\n.reg .pred p;\nsetp.lt.f32 p, %1, 0f00000000;\n@p st.volatile.shared.f32 [%0], %1;\n}" ::"r"(addr), "f"(v) : "memory");
}
__device__ __forceinline__ void mbar_wait_sleep(uint32_t bar, uint32_t parity) {
    asm volatile("{\n.reg .pred p;\n.reg .b32 c;\nmov.b32 c, 0;\n"
                 "W_%=:\nmbarrier.try_wait.parity.shared::cta.b64 p, [%0], %1, 5000;\n@p bra D_%=;\n"
                 "add.u32 c, c, 1;\nsetp.lt.u32 p, c, 0x20000;\n@p bra W_%=;\nD_%=:\n}"
                 ::"r"(bar), "r"(parity) : "memory");
}
__device__ __forceinline__ uint32_t load_tag(const Scratch* gs) {
    uint32_t tag;
    asm volatile("ld.global.ca.u32 %0, [%1];" : "=r"(tag) : "l"(gs->epoch) : "memory");
    return tag + 1;
}
__device__ __forceinline__ uint4 ld_relaxed(const uint4* p) {
    uint4 v;
    asm volatile("ld.relaxed.gpu.global.v4.u32 {%0,%1,%2,%3}, [%4];" : "=r"(v.x), "=r"(v.y), "=r"(v.z), "=r"(v.w) : "l"(p) : "memory");
    return v;
}
__device__ __forceinline__ void st_relaxed(uint4* p, uint32_t a, uint32_t b, uint32_t c, uint32_t d) {
    asm volatile("{\n.reg .b64 u, v;\nmov.b64 u, {%1, %2};\nmov.b64 v, {%3, %4};\nst.relaxed.gpu.global.v2.b64 [%0], {u, v};\n}"
                 ::"l"(p), "r"(a), "r"(b), "r"(c), "r"(d) : "memory");
}
__device__ __forceinline__ void st_relaxed4(void* p, uint32_t a, uint32_t b, uint32_t c, uint32_t d) {
    asm volatile("st.relaxed.gpu.global.v4.u32 [%0], {%1, %2, %3, %4};" ::"l"(p), "r"(a), "r"(b), "r"(c), "r"(d) : "memory");
}
__device__ __forceinline__ uint2 ld_relaxed8(const void* p) {
    uint2 v;
    asm volatile("ld.relaxed.gpu.global.v2.u32 {%0,%1}, [%2];" : "=r"(v.x), "=r"(v.y) : "l"(p) : "memory");
    return v;
}
__device__ __forceinline__ uint2 ld_relaxed64(const uint2* p) {
    uint2 v;
    asm volatile("{\n.reg .b64 u;\nld.relaxed.gpu.global.b64 u, [%2];\nmov.b64 {%0, %1}, u;\n}" : "=r"(v.x), "=r"(v.y) : "l"(p) : "memory");
    return v;
}
__device__ __forceinline__ void st_relaxed64(uint2* p, uint32_t a, uint32_t b) {
    asm volatile("{\n.reg .b64 u;\nmov.b64 u, {%1, %2};\nst.relaxed.gpu.global.b64 [%0], u;\n}" ::"l"(p), "r"(a), "r"(b) : "memory");
}
__device__ __forceinline__ uint4 ld_relaxed2(const uint4* p) {
    uint4 v;
    asm volatile("{\n.reg .b64 u, w;\nld.relaxed.gpu.global.v2.b64 {u, w}, [%4];\nmov.b64 {%0, %1}, u;\nmov.b64 {%2, %3}, w;\n}"
                 : "=r"(v.x), "=r"(v.y), "=r"(v.z), "=r"(v.w) : "l"(p) : "memory");
    return v;
}
__device__ __forceinline__ void reload16(uint4& v, const void* p, uint32_t& miss) {
    asm volatile("{\n.reg .pred p;\n.reg .b32 m;\n.reg .b64 u, w;\nmax.u32 m, %0, %2;\nsetp.eq.u32 p, m, 0xffffffff;\n"
                 "mov.b64 u, {%0, %1};\nmov.b64 w, {%2, %3};\n@p ld.relaxed.gpu.global.v2.b64 {u, w}, [%5];\n"
                 "mov.b64 {%0, %1}, u;\nmov.b64 {%2, %3}, w;\n@p mov.u32 %4, 1;\n}"
                 : "+r"(v.x), "+r"(v.y), "+r"(v.z), "+r"(v.w), "+r"(miss) : "l"(p) : "memory");
}
__device__ __forceinline__ void reload8(uint2& v, const void* p, uint32_t& miss) {
    asm volatile("{\n.reg .pred p;\n.reg .b64 u;\nsetp.eq.u32 p, %0, 0xffffffff;\nmov.b64 u, {%0, %1};\n"
                 "@p ld.relaxed.gpu.global.b64 u, [%3];\nmov.b64 {%0, %1}, u;\n@p mov.u32 %2, 1;\n}"
                 : "+r"(v.x), "+r"(v.y), "+r"(miss) : "l"(p) : "memory");
}
__device__ __forceinline__ uint32_t ld_relaxed32(const void* p) {
    uint32_t v;
    asm volatile("ld.relaxed.gpu.global.u32 %0, [%1];" : "=r"(v) : "l"(p) : "memory");
    return v;
}
__device__ __forceinline__ void poll2x2(const uint4* p0, const uint4* p1, uint32_t tag, uint4& o0, uint4& o1) {
    uint4 v0, v1;
    uint32_t miss, it = 0;
#pragma unroll 1
    do {
        v0 = ld_relaxed2(p0); v1 = ld_relaxed2(p1);
        miss = (v0.y ^ tag) | (v0.w ^ tag) | (v1.y ^ tag) | (v1.w ^ tag);
    } while (miss && ++it < SPIN / 16);
    o0 = v0; o1 = v1;
}
__device__ __forceinline__ void flag_wait(const unsigned int* p, uint32_t tag) {
    uint32_t v, it = 0;
#pragma unroll 1
    do {
        asm volatile("ld.relaxed.gpu.global.u32 %0, [%1];" : "=r"(v) : "l"(p) : "memory");
    } while (__any_sync(0xffffffffu, v != tag) && ++it < SPIN / 16);
    asm volatile("fence.acquire.gpu;" ::: "memory");
    __syncwarp();
}
__device__ __forceinline__ bool elect() {
    uint32_t p;
    asm volatile("{\n.reg .pred p;\nelect.sync _|p, 0xffffffff;\nselp.u32 %0, 1, 0, p;\n}" : "=r"(p));
    return p;
}
__device__ __forceinline__ void flag_release(unsigned int* p, uint32_t tag) {
    asm volatile("st.release.gpu.global.u32 [%0], %1;" ::"l"(p), "r"(tag) : "memory");
}
__device__ __forceinline__ uint32_t touch(const void* p) {
    uint32_t v;
    asm volatile("ld.global.nc.L1::no_allocate.L2::128B.u32 %0, [%1];" : "=r"(v) : "l"(p));
    return v;
}
__device__ __forceinline__ void bar_sync(int id, int n) { asm volatile("bar.sync %0, %1;" ::"r"(id), "r"(n) : "memory"); }
__device__ __forceinline__ void bar_arrive(int id, int n) { asm volatile("bar.arrive %0, %1;" ::"r"(id), "r"(n) : "memory"); }

constexpr uint64_t EVICT_NORMAL = 0x1000000000000000ull, EVICT_FIRST = 0x12F0000000000000ull;
__device__ __forceinline__ void tma2d(uint32_t dst, const CUtensorMap* m, int c0, int c1, uint32_t bar) {
    asm volatile("cp.async.bulk.tensor.2d.shared::cluster.global.mbarrier::complete_tx::bytes.L2::cache_hint [%0], [%1, {%3, %4}], [%2], %5;"
                 ::"r"(dst), "l"(m), "r"(bar), "r"(c0), "r"(c1), "l"(EVICT_FIRST) : "memory");
}
__device__ __forceinline__ void tma2d_mc(uint32_t dst, const CUtensorMap* m, int c0, int c1, uint32_t bar, uint64_t pol) {
    asm volatile("cp.async.bulk.tensor.2d.shared::cluster.global.mbarrier::complete_tx::bytes.multicast::cluster.L2::cache_hint [%0], [%1, {%3, %4}], [%2], %5, %6;"
                 ::"r"(dst), "l"(m), "r"(bar), "r"(c0), "r"(c1), "h"((uint16_t)3), "l"(pol) : "memory");
}
__device__ __forceinline__ void tma3d(uint32_t dst, const CUtensorMap* m, int c0, int c1, int c2, uint32_t bar) {
    asm volatile("cp.async.bulk.tensor.3d.shared::cluster.global.mbarrier::complete_tx::bytes.L2::cache_hint [%0], [%1, {%3, %4, %5}], [%2], %6;"
                 ::"r"(dst), "l"(m), "r"(bar), "r"(c0), "r"(c1), "r"(c2), "l"(EVICT_FIRST) : "memory");
}
__device__ __forceinline__ void bulk_load(uint32_t dst, const void* src, uint32_t bytes, uint32_t bar) {
    asm volatile("cp.async.bulk.shared::cluster.global.mbarrier::complete_tx::bytes [%0], [%1], %2, [%3];"
                 ::"r"(dst), "l"(src), "r"(bytes), "r"(bar) : "memory");
}
__device__ __forceinline__ void l2_prefetch(const void* src, uint32_t bytes) {
    asm volatile("cp.async.bulk.prefetch.L2.global [%0], %1;" ::"l"(src), "r"(bytes) : "memory");
}
__device__ __forceinline__ uint32_t bmul2(uint32_t a, uint32_t b) { uint32_t r; asm("mul.rn.bf16x2 %0, %1, %2;" : "=r"(r) : "r"(a), "r"(b)); return r; }
__device__ __forceinline__ uint32_t badd2(uint32_t a, uint32_t b) { uint32_t r; asm("add.rn.bf16x2 %0, %1, %2;" : "=r"(r) : "r"(a), "r"(b)); return r; }
__device__ __forceinline__ uint32_t bsub2(uint32_t a, uint32_t b) { uint32_t r; asm("sub.rn.bf16x2 %0, %1, %2;" : "=r"(r) : "r"(a), "r"(b)); return r; }
__device__ __forceinline__ uint32_t bmax2(uint32_t a, uint32_t b) { uint32_t r; asm("max.bf16x2 %0, %1, %2;" : "=r"(r) : "r"(a), "r"(b)); return r; }
__device__ __forceinline__ uint32_t bfma2(uint32_t a, uint32_t b, uint32_t c) { uint32_t r; asm("fma.rn.bf16x2 %0, %1, %2, %3;" : "=r"(r) : "r"(a), "r"(b), "r"(c)); return r; }
__device__ __forceinline__ uint4 lds128(uint32_t a) { uint4 v; asm volatile("ld.shared.v4.u32 {%0,%1,%2,%3}, [%4];" : "=r"(v.x), "=r"(v.y), "=r"(v.z), "=r"(v.w) : "r"(a) : "memory"); return v; }
__device__ __forceinline__ uint2 lds64(uint32_t a) { uint2 v; asm volatile("ld.shared.v2.u32 {%0,%1}, [%2];" : "=r"(v.x), "=r"(v.y) : "r"(a) : "memory"); return v; }
__device__ __forceinline__ uint32_t lds32(uint32_t a) { uint32_t v; asm volatile("ld.shared.u32 %0, [%1];" : "=r"(v) : "r"(a) : "memory"); return v; }
__device__ __forceinline__ uint4 ldsm4(uint32_t a) {
    uint4 v;
    asm volatile("ldmatrix.sync.aligned.m8n8.x4.shared.b16 {%0,%1,%2,%3}, [%4];" : "=r"(v.x), "=r"(v.y), "=r"(v.z), "=r"(v.w) : "r"(a) : "memory");
    return v;
}
__device__ __forceinline__ uint4 ldsm4t(uint32_t a) {
    uint4 v;
    asm volatile("ldmatrix.sync.aligned.m8n8.x4.trans.shared.b16 {%0,%1,%2,%3}, [%4];" : "=r"(v.x), "=r"(v.y), "=r"(v.z), "=r"(v.w) : "r"(a) : "memory");
    return v;
}
__device__ __forceinline__ void mma1688(float* d, uint32_t a0, uint32_t a1, uint32_t b) {
    asm("mma.sync.aligned.m16n8k8.row.col.f32.bf16.bf16.f32 {%0,%1,%2,%3}, {%4,%5}, {%6}, {%0,%1,%2,%3};"
        : "+f"(d[0]), "+f"(d[1]), "+f"(d[2]), "+f"(d[3]) : "r"(a0), "r"(a1), "r"(b));
}
__device__ __forceinline__ void mma16816(float* d, uint32_t a0, uint32_t a1, uint32_t a2, uint32_t a3, uint32_t b0, uint32_t b1) {
    asm("mma.sync.aligned.m16n8k16.row.col.f32.bf16.bf16.f32 {%0,%1,%2,%3}, {%4,%5,%6,%7}, {%8,%9}, {%0,%1,%2,%3};"
                 : "+f"(d[0]), "+f"(d[1]), "+f"(d[2]), "+f"(d[3]) : "r"(a0), "r"(a1), "r"(a2), "r"(a3), "r"(b0), "r"(b1));
}
__device__ __forceinline__ void stsm_x4(uint32_t addr, uint32_t a, uint32_t b, uint32_t c, uint32_t d) {
    asm volatile("stmatrix.sync.aligned.m8n8.x4.shared.b16 [%0], {%1, %2, %3, %4};"
                 ::"r"(addr), "r"(a), "r"(b), "r"(c), "r"(d) : "memory");
}

__device__ __forceinline__ uint64_t mkdesc(uint32_t addr, uint32_t lbo, uint32_t sbo) {
    return (uint64_t)((addr & 0x3FFFF) >> 4) | ((uint64_t)(lbo >> 4) << 16) | ((uint64_t)(sbo >> 4) << 32) | (1ull << 62);
}
constexpr uint32_t SM0 = 1024;
__host__ __device__ constexpr uint32_t desc_lo(uint32_t off, uint32_t lbo) { return ((SM0 + off) >> 4) | ((lbo >> 4) << 16); }
__device__ __forceinline__ uint64_t desc_of(uint32_t lo) { return lo | (0x40000040ull << 32); }
#define WG_FENCE() asm volatile("wgmma.fence.sync.aligned;" ::: "memory")
#define WG_COMMIT() asm volatile("wgmma.commit_group.sync.aligned;" ::: "memory")
#define WG_WAIT(n) asm volatile("wgmma.wait_group.sync.aligned %0;" ::"n"(n) : "memory")

#define F8(a, i) "+f"(a[i]), "+f"(a[i + 1]), "+f"(a[i + 2]), "+f"(a[i + 3]), "+f"(a[i + 4]), "+f"(a[i + 5]), "+f"(a[i + 6]), "+f"(a[i + 7])
#define F16(a, i) F8(a, i), F8(a, i + 8)
#define F64(a) F16(a, 0), F16(a, 16), F16(a, 32), F16(a, 48)
#define F32(a) F16(a, 0), F16(a, 16)
#define L64 "%0,%1,%2,%3,%4,%5,%6,%7,%8,%9,%10,%11,%12,%13,%14,%15,%16,%17,%18,%19,%20,%21,%22,%23,%24,%25,%26,%27,%28,%29,%30,%31,%32,%33,%34,%35,%36,%37,%38,%39,%40,%41,%42,%43,%44,%45,%46,%47,%48,%49,%50,%51,%52,%53,%54,%55,%56,%57,%58,%59,%60,%61,%62,%63"
#define L32 "%0,%1,%2,%3,%4,%5,%6,%7,%8,%9,%10,%11,%12,%13,%14,%15,%16,%17,%18,%19,%20,%21,%22,%23,%24,%25,%26,%27,%28,%29,%30,%31"

template <int TB>
__device__ __forceinline__ void mma_rs128(float (&d)[64], uint32_t a0, uint32_t a1, uint32_t a2, uint32_t a3, uint64_t b, int acc) {
    asm volatile("{\n.reg .pred p;\nsetp.ne.b32 p, %69, 0;\n"
                 "wgmma.mma_async.sync.aligned.m64n128k16.f32.bf16.bf16 {" L64 "}, {%64,%65,%66,%67}, %68, p, 1, 1, %70;\n}"
                 : F64(d) : "r"(a0), "r"(a1), "r"(a2), "r"(a3), "l"(b), "r"(acc), "n"(TB));
}
template <int TB>
__device__ __forceinline__ void mma_rs64(float (&d)[32], uint32_t a0, uint32_t a1, uint32_t a2, uint32_t a3, uint64_t b, int acc) {
    asm volatile("{\n.reg .pred p;\nsetp.ne.b32 p, %37, 0;\n"
                 "wgmma.mma_async.sync.aligned.m64n64k16.f32.bf16.bf16 {" L32 "}, {%32,%33,%34,%35}, %36, p, 1, 1, %38;\n}"
                 : F32(d) : "r"(a0), "r"(a1), "r"(a2), "r"(a3), "l"(b), "r"(acc), "n"(TB));
}
template <int N>
__device__ __forceinline__ void fence_regs(float (&d)[N]) {
#pragma unroll
    for (int i = 0; i < N; i++) asm volatile("" : "+f"(d[i])::"memory");
}
template <int N>
__device__ __forceinline__ void fence_regs(uint32_t (&d)[N]) {
#pragma unroll
    for (int i = 0; i < N; i++) asm volatile("" : "+r"(d[i])::"memory");
}

template <int V> struct IC { static constexpr int value = V; };

constexpr int SLOT = 32768, UNIT = 16384;
constexpr int SM_Q = 4 * SLOT;
constexpr int SM_BAR = 7 * SLOT;
constexpr int SM_RED = SM_BAR + 512;
constexpr int SM_TOTAL = SM_BAR + 3072;
constexpr int XP = D_ * 2 + 16;
constexpr int M_MOD = 16 * XP;
constexpr int SM_T = SM_Q + 2 * D_ * 80, SM_TC = SM_T + D_ * 4, SM_TG = SM_TC + D_ * 4, SM_TS = SM_TG + D_ * 2;
constexpr float CS = 0.08838834764831845f * 1.4426950408889634f;
#define LMAX 0.5f
#define LMIN 0x1p-104f
#define USE_SPARE 1
#define MAXG 2
#define SPLIT 10
#define ESPLIT 2
#define PV1 8
#define RW 2
#define HW 2
#define HW2 1
#define XDELAY 200
#define QDELAY 300
#define TMPF 1
#define PFD0 2000
#define PFD1 400
#define HSENT 1
#define HDELAY 500
#define RCM 8
#define RPE 0
#define OSPLIT 6
#define STAGE 11
#define POFF 102.f
#define WF0 3
#define WF1 16
#define C3D 0
#define C4D 300
#define DD 300
#define P2E 0
#define BO 0
#define MAP 2
#define CFULL 0
#define WFE 1
#define OUTD 0
#define OUTPOL EVICT_FIRST
#define SO 0
#define WF2 22
#define OUTP 0
constexpr int PF_KV = 8, PF_WO = 120;

__device__ __forceinline__ int cluster_role() {
    int k = blockIdx.x >> 1;
    if (MAP == 0) return k & 63;
    if (MAP == 1) return (k & 7) * 8 + ((k >> 3) & 7);
    if (MAP == 3) {
        asm("mov.u32 %0, %%smid;" : "=r"(k));
        k >>= 1;
        const int r = ((k - 32) * 37) >> 8;
        return k < 32 ? (k & 7) * 8 + (k >> 3) : k < 60 ? (k - 31 - r * 7) * 8 + 4 + r : (k - 58) & 7;
    }
    const int r = ((k - 36) * 37) >> 8, i = k - 36 - r * 7;
    if (MAP == 4) return k < 4 ? 4 + k : k < 36 ? ((k - 4) & 7) * 8 + ((k - 4) >> 3) : (i + 1) * 8 + ((4 + r) & 7);
    return k < 4 ? 12 + k : k < 36 ? ((k - 4) & 7) * 8 + ((k - 4) >> 3) : (i + (i > 0)) * 8 + ((4 + r) & 7);
}

struct Args {
    const bf16 *w_mod, *cvec;
    Scratch* gs;
    bf16* out;
    const bf16 *x, *kc, *vc, *wq, *wo, *w_r, *w_down;
};

__device__ __forceinline__ void frag_store(uint8_t* p, const uint32_t (&a)[32]) {
#pragma unroll
    for (int i = 0; i < 8; i++)
        __stcg(reinterpret_cast<uint4*>(p + i * 512), make_uint4(a[4 * i], a[4 * i + 1], a[4 * i + 2], a[4 * i + 3]));
}
__device__ __forceinline__ void frag_load(uint32_t (&a)[32], const uint8_t* p) {
#pragma unroll
    for (int i = 0; i < 8; i++) {
        const uint4 v = __ldcg(reinterpret_cast<const uint4*>(p + i * 512));
        a[4 * i] = v.x; a[4 * i + 1] = v.y; a[4 * i + 2] = v.z; a[4 * i + 3] = v.w;
    }
}
__device__ __forceinline__ float quad_sum(float v) {
    v += __shfl_xor_sync(0xffffffffu, v, 1);
    return v + __shfl_xor_sync(0xffffffffu, v, 2);
}
__device__ __forceinline__ float quad_max(float v) {
    v = fmaxf(v, __shfl_xor_sync(0xffffffffu, v, 1));
    return fmaxf(v, __shfl_xor_sync(0xffffffffu, v, 2));
}
__device__ __forceinline__ float rcp_fast(float x) { float y; asm("rcp.approx.ftz.f32 %0, %1;" : "=f"(y) : "f"(x)); return y; }
__device__ __forceinline__ float sigmoidf_(float x) { return rcp_fast(1.f + ex2(-1.4426950408889634f * x)); }
__device__ __forceinline__ void top2(uint32_t k, uint32_t& k1, uint32_t& k2) {
    k1 = __reduce_max_sync(0xffffffffu, k);
    k2 = __reduce_max_sync(0xffffffffu, k == k1 ? 0 : k);
}

__device__ __forceinline__ void mod_fma(float (&a)[8], const uint4 w, float sc) {
    a[0] += sc * bf_lo(w.x); a[1] += sc * bf_hi(w.x); a[2] += sc * bf_lo(w.y); a[3] += sc * bf_hi(w.y);
    a[4] += sc * bf_lo(w.z); a[5] += sc * bf_hi(w.z); a[6] += sc * bf_lo(w.w); a[7] += sc * bf_hi(w.w);
}
__device__ __forceinline__ float mod_reduce(float (&a)[8], int lane) {
#pragma unroll
    for (int h = 4; h > 0; h >>= 1) {
        const bool up = lane & (8 / h);
#pragma unroll
        for (int i = 0; i < h; i++)
            a[i] = (up ? a[i + h] : a[i]) + __shfl_xor_sync(0xffffffffu, up ? a[i] : a[i + h], 8 / h);
    }
    return a[0] + __shfl_xor_sync(0xffffffffu, a[0], 16);
}

__device__ __forceinline__ float ln_stats(float sum, float sq, uint32_t& mean2) {
    const float mean = sum * (1.f / D_);
    const float var = fmaxf(fmaf(-mean, mean, sq * (1.f / D_)), 0.f);
    float sd;
    asm("sqrt.approx.ftz.f32 %0, %1;" : "=f"(sd) : "f"(rbf(rbf(var) + 1e-5f)));
    mean2 = pack_bf16(mean, mean);
    return rcp_fast(rbf(sd));
}
__device__ __forceinline__ uint32_t ln_pair(uint32_t x, uint32_t mean2, float rsd) {
    const uint32_t d = bsub2(x, mean2);
    return pack_bf16(bf_lo(d) * rsd, bf_hi(d) * rsd);
}
__device__ __forceinline__ void rows_load(uint32_t (&x)[20], uint32_t xs, int cw) {
#pragma unroll
    for (int ch = 0; ch < 5; ch++) {
        const uint4 v = ldsm4(ch < 4 ? xs + ch * 256 : xs + 1024 - cw * 16);
        x[4 * ch] = v.x; x[4 * ch + 1] = v.y; x[4 * ch + 2] = v.z; x[4 * ch + 3] = v.w;
    }
}
__device__ __forceinline__ void stats_add(float (&st)[12], uint32_t a, uint32_t b, uint32_t w) {
    mma1688(st, a, b, w);
    mma1688(st + 4, a, b, a);
    mma1688(st + 8, a, b, b);
}
__device__ __forceinline__ float rows_stats(const float (&st)[12], float4* rec, int cw, int lane, uint32_t& mean2, float& dot) {
    const int g8 = lane >> 2;
    if ((g8 >> 1) == (lane & 3)) {
        rec[cw * 16 + g8] = make_float4(st[0], (g8 & 1) ? st[5] : st[4], st[1], 0.f);
        rec[cw * 16 + 8 + g8] = make_float4(st[2], (g8 & 1) ? st[11] : st[10], st[3], 0.f);
    }
    bar_sync(3, 256);
    const float4* r = rec + (lane >> 4) * 64 + (lane & 15);
    const float4 s0 = r[0], s1 = r[16], s2 = r[32], s3 = r[48];
    const float sum = (s0.x + s1.x) + (s2.x + s3.x), sq = (s0.y + s1.y) + (s2.y + s3.y);
    dot = (s0.z + s1.z) + (s2.z + s3.z);
    dot += __shfl_xor_sync(0xffffffffu, dot, 16);
    return ln_stats(sum + __shfl_xor_sync(0xffffffffu, sum, 16), sq + __shfl_xor_sync(0xffffffffu, sq, 16), mean2);
}
template <class F>
__device__ __forceinline__ void rows_normalise(uint32_t* y, const uint32_t* x, uint32_t mean2, float rsd, int lane, F loads) {
    const int g8 = lane >> 2;
    const uint32_t ma2 = __shfl_sync(0xffffffffu, mean2, g8), mb2 = __shfl_sync(0xffffffffu, mean2, g8 + 8);
    const float ra = __shfl_sync(0xffffffffu, rsd, g8), rb = __shfl_sync(0xffffffffu, rsd, g8 + 8);
    loads();
#pragma unroll
    for (int k = 0; k < 9; k++) { y[2 * k] = ln_pair(x[2 * k], ma2, ra); y[2 * k + 1] = ln_pair(x[2 * k + 1], mb2, rb); }
}
__device__ __forceinline__ uint32_t pair_of(const uint2* mp, int k, int cw) {
    return (k < 8 ? mp[(k >> 1) * 64 + (k & 1) * 4] : (mp - cw * 4)[256]).x;
}

__device__ __forceinline__ uint4 h_frag(const uint4* hf, int ks, int lane) {
    if (ks < 32) return ld_relaxed2(hf + ks * 32);
    const uint2* p = reinterpret_cast<const uint2*>(padd(hf, 256 - lane * 8) + ks * 32 - 16);
    const uint2 a = ld_relaxed64(p), b = ld_relaxed64(p + 32);
    return make_uint4(a.x, a.y, b.x, b.y);
}

__device__ __noinline__ void attn_fallback(uint32_t bad, uint32_t tag, const Scratch* gs, uint8_t* frag, uint8_t* keep, const bf16* wq, const bf16* kc, const bf16* vc) {
  const int lane = threadIdx.x & 31, g8 = lane >> 2, qd = lane & 3;
  const int j = cluster_role() & 7, qb = (cluster_role() >> 3) * 2 + (blockIdx.x & 1);
  const uint4* hf = g_h + (size_t)(qb * 8 + (threadIdx.x >> 5) - 4) * (36 * 32) + lane;
#pragma unroll 1
  for (int t = 0; t < 4; t++) {
    if (!((bad >> t) & 1)) continue;
    const bf16 *wqp = wq + (4 * j + t) * DH, *kp = kc + (size_t)(2 * j + (t >> 1)) * S_ * DH, *vp = vc + (size_t)(2 * j + (t >> 1)) * S_ * DH;
    uint32_t q[32];
    float o[64];
#pragma unroll
    for (int i = 0; i < 64; i++) o[i] = 0.f;
#pragma unroll 1
    for (int ks = 0; ks < 36; ks++) {
        const uint4 a = h_frag(hf, ks, lane);
        const unsigned short* wr = reinterpret_cast<const unsigned short*>(wqp + (size_t)(ks * 16 + 2 * qd) * QD + g8);
#pragma unroll
        for (int dt = 0; dt < 16; dt++) {
            const uint32_t b0 = __ldg(wr + dt * 8) | ((uint32_t)__ldg(wr + dt * 8 + QD) << 16);
            const uint32_t b1 = __ldg(wr + dt * 8 + 8 * QD) | ((uint32_t)__ldg(wr + dt * 8 + 9 * QD) << 16);
            mma16816(o + 4 * dt, a.x, a.y, a.z, a.w, b0, b1);
        }
    }
#pragma unroll
    for (int i = 0; i < 32; i++) q[i] = pack_bf16(o[2 * i], o[2 * i + 1]);
#pragma unroll
    for (int i = 0; i < 64; i++) o[i] = 0.f;
    float m0 = -INFINITY, m1 = -INFINITY, l0 = 0.f, l1 = 0.f;
#pragma unroll 1
    for (int key = 0; key < S_; key += 16) {
        float sc[8];
#pragma unroll
        for (int i = 0; i < 8; i++) sc[i] = 0.f;
#pragma unroll
        for (int nt = 0; nt < 2; nt++) {
            const uint32_t* kr = reinterpret_cast<const uint32_t*>(kp + (size_t)(key + nt * 8 + g8) * DH) + qd;
#pragma unroll
            for (int ks = 0; ks < 8; ks++)
                mma16816(sc + 4 * nt, q[4 * ks], q[4 * ks + 1], q[4 * ks + 2], q[4 * ks + 3], __ldg(kr + ks * 8), __ldg(kr + ks * 8 + 4));
        }
        const float n0 = quad_max(fmaxf(fmaxf(m0, fmaxf(sc[0], sc[1])), fmaxf(sc[4], sc[5])));
        const float n1 = quad_max(fmaxf(fmaxf(m1, fmaxf(sc[2], sc[3])), fmaxf(sc[6], sc[7])));
        const float f0 = ex2((m0 - n0) * CS), f1 = ex2((m1 - n1) * CS);
        m0 = n0; m1 = n1;
#pragma unroll
        for (int i = 0; i < 8; i++) sc[i] = ex2((sc[i] - ((i & 2) ? n1 : n0)) * CS);
        l0 = l0 * f0 + (sc[0] + sc[1]) + (sc[4] + sc[5]);
        l1 = l1 * f1 + (sc[2] + sc[3]) + (sc[6] + sc[7]);
        const uint32_t e0 = pack_bf16(sc[0], sc[1]), e1 = pack_bf16(sc[2], sc[3]), e2 = pack_bf16(sc[4], sc[5]), e3 = pack_bf16(sc[6], sc[7]);
        const unsigned short* vr = reinterpret_cast<const unsigned short*>(vp + (size_t)(key + 2 * qd) * DH + g8);
#pragma unroll
        for (int dt = 0; dt < 16; dt++) {
            o[4 * dt] *= f0; o[4 * dt + 1] *= f0; o[4 * dt + 2] *= f1; o[4 * dt + 3] *= f1;
            const uint32_t b0 = __ldg(vr + dt * 8) | ((uint32_t)__ldg(vr + dt * 8 + DH) << 16);
            const uint32_t b1 = __ldg(vr + dt * 8 + 8 * DH) | ((uint32_t)__ldg(vr + dt * 8 + 9 * DH) << 16);
            mma16816(o + 4 * dt, e0, e1, e2, e3, b0, b1);
        }
    }
    const float i0 = 1.f / quad_sum(l0), i1 = 1.f / quad_sum(l1);
#pragma unroll
    for (int i = 0; i < 16; i++) {
        q[2 * i] = pack_bf16(o[4 * i] * i0, o[4 * i + 1] * i0);
        q[2 * i + 1] = pack_bf16(o[4 * i + 2] * i1, o[4 * i + 3] * i1);
    }
    frag_store(t < 3 ? frag + t * 4096 : keep, q);
  }
}

__device__ __forceinline__ void spare_q3(Scratch* gs, uint32_t sb, uint32_t bar_full, uint32_t bar_empty, int lane, int cw) {
    const uint32_t tag = load_tag(gs);
    uint32_t rel_base, e = 3;
    asm("mapa.shared::cluster.u32 %0, %1, %2;" : "=r"(rel_base) : "r"(bar_empty), "r"(lane & 1));
#pragma unroll 1
    for (int qb = blockIdx.x - NCTA; qb < 16; qb += 4) {
        uint32_t h[144];
        float o[64];
        flag_wait(&g_flag_h[(qb * 8 + cw) * 32], tag);
        const uint4* hf = g_h + (size_t)(qb * 8 + cw) * (36 * 32) + lane;
#pragma unroll
        for (int ks = 0; ks < 36; ks++) {
            const uint4 v = h_frag(hf, ks, lane);
            h[4 * ks] = v.x; h[4 * ks + 1] = v.y; h[4 * ks + 2] = v.z; h[4 * ks + 3] = v.w;
        }
#pragma unroll
        for (int i = 0; i < 64; i++) o[i] = 0.f;
#pragma unroll 1
        for (int v = 0; v < 4; v++) {
            fence_regs(o);
#pragma unroll
            for (int t = 0; t < 5; t++) {
                mbar_wait(bar_full + 8 * (e & 3), (e >> 2) & 1);
                const uint64_t dv = mkdesc(sb + (e & 3) * SLOT, UNIT, 1024);
                WG_FENCE();
#pragma unroll
                for (int ks = 0; ks < (t < 4 ? 8 : 4); ks++)
                    mma_rs128<1>(o, h[32 * t + 4 * ks], h[32 * t + 4 * ks + 1], h[32 * t + 4 * ks + 2], h[32 * t + 4 * ks + 3], dv + ks * 128, ks | t);
                WG_COMMIT();
                if (t > 0) { WG_WAIT(1); if (lane < 2) mbar_arrive_cluster(rel_base + 8 * ((e - 1) & 3)); }
                e++;
            }
            WG_WAIT(0);
            fence_regs(o);
            if (lane < 2) mbar_arrive_cluster(rel_base + 8 * ((e - 1) & 3));
            uint4* dst = &g_q3[((qb * 8 + 2 * v) * 8 + cw) * 128 + lane];
#pragma unroll
            for (int i = 0; i < 8; i++)
                __stcg(dst + (i >> 2) * 1024 + (i & 3) * 32, make_uint4(pack_bf16(o[8 * i], o[8 * i + 1]), pack_bf16(o[8 * i + 2], o[8 * i + 3]),
                                                                        pack_bf16(o[8 * i + 4], o[8 * i + 5]), pack_bf16(o[8 * i + 6], o[8 * i + 7])));
        }
        bar_sync(3, 256);
        if (cw == 0 && lane == 0) flag_release(&g_flag_q3[qb * 32], tag);
        __syncwarp();
    }
}

template <bool SPARE>
__global__ void __cluster_dims__(2, 1, 1) __launch_bounds__(384, 1)
fused_kernel(const Args args, const __grid_constant__ CUtensorMap tm_wq,
             const __grid_constant__ CUtensorMap tm_k, const __grid_constant__ CUtensorMap tm_v,
             const __grid_constant__ CUtensorMap tm_wo, const __grid_constant__ CUtensorMap tm_p,
             const __grid_constant__ CUtensorMap tm_x, const __grid_constant__ CUtensorMap tm_d,
             const __grid_constant__ CUtensorMap tm_g, const __grid_constant__ CUtensorMap tm_u) {
    extern __shared__ __align__(1024) uint8_t smem_raw[];
    const uint32_t sb = smem_u32(smem_raw);
    Scratch* const gs = args.gs;
    const uint32_t bar_full = sb + SM_BAR;
    const uint32_t bar_g = bar_full + 8 * 4;
    const uint32_t bar_mod = bar_g + 8;
    const uint32_t bar_go = bar_mod + 8;
    const uint32_t bar_x = bar_go + 40;
    const uint32_t bar_empty = bar_x + 8;
    const uint32_t bar_pub = bar_empty + 8 * 4;
    const uint32_t bar_qfree = bar_pub + 32;
    const uint32_t bar_out = bar_qfree + 24;
    const uint32_t bar_q3 = bar_out + 8;
    const uint32_t bar_pre = bar_q3 + 16;
    const uint32_t bar_w0 = bar_q3 + 8;
    constexpr int E0 = SPARE ? 2 : 0;

    const int c = blockIdx.x & 1;
    const int role = cluster_role();
    const int j = role & 7;
    const int qb = (role >> 3) * 2 + c;
    const int rg = qb * 8 + j;
    const int warp = __shfl_sync(0xffffffffu, threadIdx.x >> 5, 0);

    if (SPARE && blockIdx.x >= NCTA && warp >= 4) {
        asm volatile("barrier.cluster.arrive.relaxed.aligned;" ::: "memory");
        asm volatile("setmaxnreg.inc.sync.aligned.u32 240;");
        asm volatile("barrier.cluster.wait.aligned;" ::: "memory");
        spare_q3(gs, sb, bar_full, bar_empty, threadIdx.x & 31, warp - 4);
        asm volatile("barrier.cluster.arrive.relaxed.aligned;\nbarrier.cluster.wait.aligned;" ::: "memory");
    } else if (warp < 4) {
        asm volatile("setmaxnreg.dec.sync.aligned.u32 24;");
        int lane;
        asm volatile("mov.u32 %0, %%laneid;" : "=r"(lane));
        if (warp == 2 && elect()) {
            if (TMPF) asm volatile("prefetch.tensormap [%0];" ::"l"(&tm_x) : "memory");
#pragma unroll
            for (int i = 0; i < 27; i++) mbar_init(bar_full + 8 * i, i < 12 || i >= 23 ? 1 : i < 16 ? 16 : 8);
#pragma unroll
            for (int i = 0; i <= E0; i++) {
                mbar_arrive(bar_full + 8 * i);
                asm volatile("mbarrier.arrive.shared::cta.b64 _, [%0], 16;" ::"r"(bar_empty + 8 * i) : "memory");
            }
            asm volatile("fence.mbarrier_init.release.cluster;" ::: "memory");
        }
        __syncwarp();
        asm volatile("barrier.cluster.arrive.relaxed.aligned;" ::: "memory");
        if (warp == 2 && !(SPARE && blockIdx.x >= NCTA)) {
            if (XDELAY) __nanosleep(XDELAY);
            if (elect()) {
                mbar_expect_tx(bar_x, 16 * XP);
                tma2d(sb + SM_Q, &tm_x, 0, rg * 16, bar_x);
            }
            __syncwarp();
        }
        asm volatile("barrier.cluster.wait.aligned;" ::: "memory");
        const uint32_t tag = load_tag(gs);
        if (SPARE && blockIdx.x >= NCTA) {
            if (warp == 1) {
#pragma unroll 1
                for (int e = 3; e < 83; e++) {
                    const int v = (e - 3) / 5;
                    mbar_wait_sleep(bar_empty + 8 * (e & 3), ~(e >> 2) & 1);
                    if (elect()) {
                        mbar_expect_tx(bar_full + 8 * (e & 3), SLOT);
                        tma2d_mc(sb + (e & 3) * SLOT + c * UNIT, &tm_wq, (8 * (v & 3) + 4 * c + 3) * DH + 64, (e - 3 - v * 5) * 128,
                                 bar_full + 8 * (e & 3), EVICT_NORMAL);
                    }
                }
            }
            __syncwarp();
            asm volatile("barrier.cluster.arrive.relaxed.aligned;\nbarrier.cluster.wait.aligned;" ::: "memory");
            return;
        }
        if (warp == 3) {
#pragma unroll 1
            for (int e = 4; e < 20; e++) {
                __nanosleep(e == 4 ? PFD0 : PFD1);
                const int hd = (e * 52) >> 8, row = (e - hd * 5) * 128 + qb * 8 + (lane >> 1);
                if (lane < 16 && row < D_)
                    asm volatile("prefetch.global.L2 [%0];" ::"l"(padd(args.wq, (row * QD + (4 * j + ((0x1320 >> (4 * hd)) & 3)) * DH + (lane & 1) * 64) * 2)) : "memory");
            }
            __syncwarp();
            mbar_wait_sleep(bar_go, 0);
#pragma unroll 1
            for (int unit = 72 + blockIdx.x; unit < 216; unit += NCTA) {
                float a[8];
#pragma unroll
                for (int i = 0; i < 8; i++) a[i] = 0.f;
#pragma unroll 1
                for (int k = lane >> 1; k < D_; k += 16) {
                    const float cv = __bfloat162float(*padd(args.cvec, k * 2));
                    mod_fma(a, __ldg(reinterpret_cast<const uint4*>(padd(args.w_mod, (k * (6 * D_) + unit * 16 + (lane & 1) * 8) * 2))), rbf(cv * sigmoidf_(cv)));
                }
                const float v = mod_reduce(a, lane), v1 = __shfl_down_sync(0xffffffffu, v, 8);
                if (lane < 8) *padd(gs->mod2, ((unit - 72) * 8 + (lane & 1) * 4 + (lane & 2) + (lane >> 2)) * 4) = pack_bf16(v, v1);
            }
            __syncwarp();
            if (lane == 0) flag_release(padd(g_flag_mod, blockIdx.x * 4), tag);
#pragma unroll 1
            for (int k = 0; k < 36 * HSENT; k++) {
                __nanosleep(200);
                __stcg(padd(gs->h[0], (~tag & 1) * (NCTA * 36 * 512) + ((rg * 36 + k) * 32 + lane) * 16), make_uint4(0, 0, 0, 0));
            }
            __syncwarp();
            mbar_wait_sleep(bar_qfree + 16, 0);
            __nanosleep(2000);
            {
                uint4 v;
                uint32_t it = 0;
#pragma unroll 1
                do {
                    v = ld_relaxed(reinterpret_cast<const uint4*>(padd(g_flag_mod, lane * 16)));
                } while (((v.x ^ tag) | (v.y ^ tag) | (v.z ^ tag) | (v.w ^ tag)) && ++it < SPIN / 16);
                asm volatile("fence.acquire.gpu;" ::: "memory");
            }
            __syncwarp();
            {
                float w1 = 0.f, w2 = 0.f;
#pragma unroll 1
                for (int k = lane; k < D_ / 2; k += 32) {
                    const uint32_t* mp = padd(gs->mod2, k * 4);
                    const uint32_t sv = __ldcg(mp + D_ / 2), c1 = badd2(__ldcg(mp + D_), 0x3f803f80u);
                    const uint32_t wr = *reinterpret_cast<const uint32_t*>(padd(args.w_r, k * 4)), wp = bmul2(c1, wr);
                    reinterpret_cast<uint2*>(smem_raw + SM_T)[k] = make_uint2(__ldcg(mp), wp);
                    reinterpret_cast<uint2*>(smem_raw + SM_TC)[k] = make_uint2(c1, sv);
                    reinterpret_cast<uint32_t*>(smem_raw + SM_TG)[k] = __ldcg(mp + 3 * D_ / 2);
                    w1 += bf_lo(wp) + bf_hi(wp);
                    w2 += bf_lo(sv) * bf_lo(wr) + bf_hi(sv) * bf_hi(wr);
                }
#pragma unroll 1
                for (int i = 1; i < 32; i <<= 1) { w1 += __shfl_xor_sync(0xffffffffu, w1, i); w2 += __shfl_xor_sync(0xffffffffu, w2, i); }
                *reinterpret_cast<float2*>(smem_raw + SM_TS) = make_float2(w1, w2);
            }
#pragma unroll
            for (int i = 0; i < 4; i++) reinterpret_cast<uint4*>(smem_raw + SM_RED)[lane + 32 * i] = make_uint4(~0u, ~0u, ~0u, ~0u);
            asm volatile("fence.proxy.async.shared::cta;" ::: "memory");
            __syncwarp();
            if (elect()) {
                uint8_t* mb = g_frag + (size_t)rg * 8 * WREG + 3 * 4096;
#pragma unroll 1
                for (int k = 0; k < 8; k++, mb += WREG) {
#pragma unroll
                    for (int i = 0; i < 3; i++)
                        asm volatile("cp.async.bulk.global.shared::cta.bulk_group [%0], [%1], 2048;" ::"l"(mb + i * 2048), "r"(sb + SM_RED) : "memory");
                    __nanosleep(500);
                }
                asm volatile("cp.async.bulk.commit_group;\ncp.async.bulk.wait_group 0;\nfence.proxy.async.global;" ::: "memory");
            }
            __syncwarp();
            if (lane == 0) mbar_arrive(bar_mod);
            __syncwarp();
            mbar_wait_sleep(bar_go + 8, 0);
            if (lane < 3) asm volatile("prefetch.tensormap [%0];" ::"l"(lane == 0 ? &tm_x : lane == 1 ? &tm_p : &tm_d) : "memory");
            __syncwarp();
#pragma unroll 1
            for (int i = 1; i < 4; i++) {
                mbar_wait(bar_pub + 8 * i, 0);
                unsigned int* flags = padd(g_flag_part, (qb * 32 + i * 8 - 8) * 4);
                if (elect()) { flag_release(padd(flags, j * 4), tag); DBG_PG(93); }
                __syncwarp();
                const uint32_t slot = i < 3 ? i + 1 : 1;
                flag_wait(padd(flags, (lane & 7) * 4), tag);
                asm volatile("fence.proxy.async.global;" ::: "memory");
                if (lane == 0 && i == 3) DBG_PG(101);
                mbar_wait(bar_go + 8 + 8 * i, 0);
                mbar_wait(bar_empty + 8 * slot, i != 1);
                if (elect()) {
                    mbar_expect_tx(bar_full + 8 * slot, SLOT);
                    tma3d(sb + slot * SLOT, &tm_p, 0, j * 20 + (i - 1) * 4, qb * 8, bar_full + 8 * slot);
                    tma3d(sb + slot * SLOT + UNIT, &tm_p, 0, j * 20 + (i - 1) * 4 + 2, qb * 8, bar_full + 8 * slot);
                }
            }
        } else if (warp == 0) {
#pragma unroll 1
            for (int i = 0; i < 48; i++) {
                if (i == 0 || i == 17 || i == 34) mbar_wait_sleep(bar_qfree + (i >> 4) * 8, 0);
                if (SPARE && i == 17) {
                    flag_wait(&g_flag_q3[qb * 32], tag);
                    if (elect()) {
                        asm volatile("fence.proxy.async.global;" ::: "memory");
                        mbar_expect_tx(bar_q3, UNIT);
#pragma unroll 1
                        for (int k = 0; k < 8; k++) bulk_load(sb + SM_Q + 2 * SLOT + k * 4096 + 2048, &g_q3[(rg * 8 + k) * 128], 2048, bar_q3);
                    }
                }
                __nanosleep(700);
                if (elect()) {
                    asm volatile("mbarrier.expect_tx.shared::cta.b64 [%0], %1;" ::"r"(bar_g), "n"(1920) : "memory");
                    tma2d(sb + SM_Q + i * 1920, i < 24 ? &tm_g : &tm_u, (blockIdx.x * 36) & ~7, (i < 24 ? i : i - 24) * 24, bar_g);
                }
            }
            if (elect()) mbar_arrive(bar_g);
#pragma unroll 1
            for (int i = 0; i < 18; i++) {
                __nanosleep(400);
                if (elect()) l2_prefetch(args.w_down + (size_t)(blockIdx.x * 36 + i * 2) * D_, 4 * D_);
            }
            __syncwarp();
            mbar_wait_sleep(bar_go + 8 * 2, 0);
            uint32_t acc = 0;
#pragma unroll 1
            for (int k = lane; k < 16 * 9; k += 32) acc |= touch(padd(args.x, (rg * 16 * D_ + k * 64) * 2));
            if (acc == 0) reinterpret_cast<volatile uint32_t*>(smem_raw + SM_BAR)[127] = acc;
            __syncwarp();
            mbar_wait_sleep(bar_go + 8 * 4, 0);
            uint4* rp = padd(g_rows, (rg * 2 * RSLOT + lane) * 16);
#pragma unroll
            for (int k = 0; k < 9; k++) rp[k * 32] = make_uint4(~0u, ~0u, ~0u, ~0u);
            if (blockIdx.x < 72) {
                uint4* yp = reinterpret_cast<uint4*>(padd(g_ypart, blockIdx.x * NCTA * 64 + lane * 16));
#pragma unroll
                for (int k = 0; k < 16; k++) yp[k * 32] = make_uint4(~0u, ~0u, ~0u, ~0u);
            }
            asm volatile("fence.acq_rel.gpu;" ::: "memory");
            __syncwarp();
            if (lane == 0) mbar_arrive(bar_pre);
        } else if (warp == 1) {
            __nanosleep(QDELAY);
            uint32_t go = bar_go;
            uint64_t marks = 24 | 151 << 8 | 154 << 16 | 159ull << 24 | 165ull << 32;
#pragma unroll 1
            for (int e = E0; e < 168; e++) {
                const CUtensorMap* tm;
                int c0, c1;
                uint64_t pol = EVICT_FIRST;
                if (e == 158 || e == 163) continue;
                if (e < 21 && e != 19) {
                    const int i = SPARE && e < 12 ? e - 2 : e - (e == 20), hd = (i * 52) >> 8;
                    tm = &tm_wq; c0 = (4 * j + ((0x1320 >> (4 * hd)) & 3)) * DH + c * 64; c1 = (i - hd * 5) * 128 - 64;
                    if (SPARE && e >= 12 && e < 15) { c0 = (4 * j + 3) * DH; c1 = (2 * (e - 12) + c) * 128; }
                } else if (e < 148) {
                    const int i = max(e - 20, 0);
                    const bool isk = i == 0 || ((i & 1) && i < 127);
                    const int n = isk ? (i + 1) >> 1 : (i - 1) >> 1;
                    tm = isk ? &tm_k : &tm_v; c0 = c * 64; c1 = (2 * j + (n >> 5)) * S_ + (n & 15) * 128;
                    if (!(i & 32)) pol = EVICT_NORMAL;
                } else {
                    int i = e - 148 - (e > 158) - (e > 163);
                    tm = &tm_wo; c0 = (i >> 1) * 64; c1 = (4 * j + ((i & 1) ? 1 + c : 3 * c)) * DH;
                }
                const uint32_t fb = e == E0 ? bar_w0 : bar_full + 8 * (e & 3), d = sb + (e == E0 ? 6 : e & 3) * SLOT;
                if (e >= 24 && e < 152) mbar_wait_sleep(bar_empty + 8 * (e & 3), ~(e >> 2) & 1);
                else if (e != E0) mbar_wait(bar_empty + 8 * (e & 3), ~(e >> 2) & 1);
                if (elect()) {
                    mbar_expect_tx(fb, SLOT);
                    tma2d_mc(d + c * UNIT, tm, c0, c1, fb, pol);
                    const int i = e - PF_KV;
                    if (i >= 0 && i < 128 && !(i & 32))
                        l2_prefetch(((i & 1) ? args.vc : args.kc) + (size_t)((2 * j + (i >> 6)) * S_ + (i & 30) * 64) * DH + qb * 1024, 2048);
                    if (e >= PF_WO && e < PF_WO + 18) l2_prefetch(args.wo + (size_t)blockIdx.x * (QD * D_ / NCTA) + (e - PF_WO) * 1024, 2048);
                    if (e == (marks & 255)) mbar_arrive(go);
                }
                if (e == (marks & 255)) { go += 8; marks >>= 8; }
            }
            asm volatile("fence.proxy.async.global;" ::: "memory");
            mbar_wait(bar_empty, 1);
            if (elect()) {
                mbar_expect_tx(bar_full, 16 * XP);
                tma2d(sb, &tm_x, 0, rg * 16, bar_full);
            }
            mbar_wait(bar_empty + 16, 1);
            if (C3D) __nanosleep(C3D);
            if (elect()) {
                mbar_expect_tx(bar_full + 16, SLOT);
                tma3d(sb + 2 * SLOT, &tm_p, 0, j * 20 + 12, qb * 8, bar_full + 16);
                tma3d(sb + 2 * SLOT + UNIT, &tm_p, 0, j * 20 + 14, qb * 8, bar_full + 16);
            }
            mbar_wait(bar_empty + 24, 1);
            if (C4D) __nanosleep(C4D);
            if (elect()) {
                mbar_expect_tx(bar_full + 24, UNIT);
                tma3d(sb + 3 * SLOT, &tm_p, 0, j * 20 + 16, qb * 8, bar_full + 24);
            }
            mbar_wait(bar_empty + 8, 0);
            mbar_wait(bar_empty + 16, 0);
            if (DD) __nanosleep(DD);
            if (elect()) {
#pragma unroll
                for (int i = 1; i < 3; i++) {
                    mbar_expect_tx(bar_full + 8 * i, 18 * XP);
                    tma2d(sb + i * SLOT, &tm_d, 0, blockIdx.x * 36 + (i - 1) * 18, bar_full + 8 * i);
                }
            }
        } else {
            if (lane < 3) asm volatile("prefetch.tensormap [%0];" ::"l"(lane == 0 ? &tm_k : lane == 1 ? &tm_v : &tm_wo) : "memory");
            if (SPARE && HSENT) {
                mbar_wait_sleep(bar_pub, 0);
                if (lane == 0) flag_release(padd(g_flag_h, rg * 128), tag);
                __syncwarp();
            }
            bar_sync(1, 192);
#pragma unroll 1
            for (uint32_t e = 20; e < 148; e++) {
                mbar_wait_sleep(bar_full + 8 * (e & 3), (e >> 2) & 1);
                if (e & 1) bar_sync(1, 192);
                if (!(e & 1) || e == 147) bar_sync(4, 160);
            }
#pragma unroll 1
            for (uint32_t e = 148; e < 168; e++) {
                mbar_wait(bar_full + 8 * (e & 3), (e >> 2) & 1);
                if (e != 158 && e != 163) bar_sync(1, 192);
            }
        }
        __syncwarp();
        mbar_wait_sleep(bar_out, 0);
        if (OUTD) __nanosleep(OUTD);
        if (elect()) {
            asm volatile("fence.proxy.async.shared::cta;" ::: "memory");
            const int2 sel = reinterpret_cast<const int2*>(smem_raw + SM_RED)[8];
#pragma unroll 1
            for (int i = warp; i < 16; i += 4) {
                const int row = rg * 16 + i;
                if (row != sel.x && row != sel.y)
                    asm volatile("cp.async.bulk.global.shared::cta.bulk_group.L2::cache_hint [%0], [%1], %2, %3;"
                                 ::"l"(args.out + (size_t)row * D_), "r"(sb + i * XP), "n"(D_ * 2), "l"(OUTPOL) : "memory");
            }
            asm volatile("cp.async.bulk.commit_group;\ncp.async.bulk.wait_group 0;" ::: "memory");
        }
    } else {
        uint32_t cv[5] = {0, 0, 0, 0, 0}, tag0 = 0;
        if (blockIdx.x < 72) {
            uint32_t ws;
            int tid;
            asm volatile("mov.u32 %0, smem_raw;\nmov.u32 %1, %%tid.x;" : "=r"(ws), "=r"(tid));
            tid -= 128;
            ws += SM_Q + SLOT + tid * 16;
            const bf16* wrow = args.w_mod + (size_t)(tid >> 1) * (6 * D_) + (tid & 1) * 8 + blockIdx.x * 16;
#pragma unroll
            for (int i = 0; i < 5; i++)
                if (i < 4 || tid < 128) {
                    asm volatile("cp.async.cg.shared.global [%0], [%1], 16;" ::"r"(ws + i * 4096), "l"(wrow + (size_t)i * 128 * (6 * D_)) : "memory");
                    cv[i] = reinterpret_cast<const unsigned short*>(args.cvec)[(tid >> 1) + i * 128];
                }
            tag0 = load_tag(gs) - 1;
        }
        asm volatile("barrier.cluster.arrive.relaxed.aligned;" ::: "memory");
        asm volatile("setmaxnreg.inc.sync.aligned.u32 240;");
        const int lane = threadIdx.x & 31;
        const int cw = warp - 4;
        const int w = cw >> 2;
        const int tid = threadIdx.x - 128;
        float* red = reinterpret_cast<float*>(smem_raw + SM_RED);
        DBG_INIT();
        DBG_G(120);
        DBG_T(100);

        uint32_t tag;
        {

            if (blockIdx.x < 72) {
                const uint32_t ws = sb + SM_Q + SLOT + tid * 16;
                float sc[5], a[8];
#pragma unroll
                for (int i = 0; i < 5; i++) sc[i] = __uint_as_float(cv[i] << 16);
#pragma unroll
                for (int i = 0; i < 5; i++) sc[i] = rbf(sc[i] * sigmoidf_(sc[i]));
#pragma unroll
                for (int i = 0; i < 8; i++) a[i] = 0.f;
                anchor(bar_full + 504, sc[0] + sc[1] + sc[2] + sc[3] + sc[4] + 2.f);
                asm volatile("cp.async.wait_all;" ::: "memory");
#pragma unroll
                for (int i = 0; i < 5; i++) mod_fma(a, lds128(ws + (i < 4 || tid < 128 ? i * 4096 : 0)), sc[i]);
                const float v = mod_reduce(a, lane);
                if (lane < 16) red[cw * 16 + lane] = v;

                bar_sync(3, 256);
                if (tid < 8 * MREP) {
                    float v0 = 0.f, v1 = 0.f;
#pragma unroll
                    for (int i = 0; i < 8; i++) { v0 += red[i * 16 + (tid & 7)]; v1 += red[i * 16 + 8 + (tid & 7)]; }
                    st_relaxed64(&gs->mod1[(tid >> 3) * D_ + blockIdx.x * 8 + (tid & 1) * 4 + (tid & 2) + ((tid >> 2) & 1)], pack_bf16(v0, v1), tag0 + 1);
                }
            }
            DBG_G(106);
            asm volatile("barrier.cluster.wait.aligned;" ::: "memory");
            mbar_wait(bar_x, 0);
            tag = load_tag(gs);
            uint32_t x[20];
            float st[12];
            rows_load(x, sb + SM_Q + (lane & 15) * XP + (lane >> 4) * 16 + cw * 32, cw);
#pragma unroll
            for (int i = 0; i < 12; i++) st[i] = 0.f;
#pragma unroll
            for (int k = 0; k < 9; k++) stats_add(st, x[2 * k], x[2 * k + 1], 0x3f803f80u);
            uint32_t mean2;
            float dot;
            const float rsd = rows_stats(st, reinterpret_cast<float4*>(red + 128), cw, lane, mean2, dot);
            rows_normalise(x, x, mean2, rsd, lane, []() {});
            fence_regs(x);
            uint4* smod = reinterpret_cast<uint4*>(smem_raw + SM_Q + M_MOD);
            if (tid < D_ / 4) {
                const uint4* mp = reinterpret_cast<const uint4*>(gs->mod1 + ((blockIdx.x >> 1) & (MREP - 1)) * D_) + tid;
                poll2x2(mp, mp + D_ / 4, tag, smod[tid], smod[D_ / 4 + tid]);
            }
            bar_sync(3, 256);
            DBG_G(107);
            const uint2* mp = reinterpret_cast<const uint2*>(smod) + cw * 8 + (lane & 3);
#pragma unroll
            for (int k = 0; k < 9; k++) {
                const uint32_t c1 = badd2(pair_of(mp + D_ / 2, k, cw), 0x3f803f80u), sa = pair_of(mp, k, cw);
                x[2 * k] = badd2(bmul2(x[2 * k], c1), sa);
                if (x[2 * k] == 0) x[2 * k] = 0x8000u;
                x[2 * k + 1] = badd2(bmul2(x[2 * k + 1], c1), sa);
            }
            uint4* hdst = g_h + (size_t)(rg * 36 + cw) * 32 + lane;
#pragma unroll
            for (int ch = 0; ch < 4; ch++) st_relaxed(hdst + ch * 256, x[4 * ch], x[4 * ch + 1], x[4 * ch + 2], x[4 * ch + 3]);
            st_relaxed64(reinterpret_cast<uint2*>(g_h + (size_t)(rg * 36 + 32) * 32) + tid, x[16], x[17]);
            __syncwarp();
            if (SPARE && lane == 0) mbar_arrive(bar_pub);
            DBG_G(108);
        }

        uint32_t rel_base;
        asm("mapa.shared::cluster.u32 %0, %1, %2;" : "=r"(rel_base) : "r"(bar_empty), "r"(lane & 1));
        auto release = [&](uint32_t slot) { if (lane < 2) mbar_arrive_cluster(rel_base + 8 * slot); };
        uint32_t q[32], p[32];
        float s[64], o[64];

        uint4* qpark = reinterpret_cast<uint4*>(smem_raw + SM_Q - SLOT) + cw * 256 + lane;
        {
            uint32_t h[144];
            const uint4* hf = g_h + (size_t)(qb * 8 + cw) * (36 * 32) + lane;
            auto load_h = [&](auto lo, auto hi) {
#pragma unroll
                for (int ks = lo.value; ks < hi.value; ks++) {
                    const uint4 v = h_frag(hf, ks, lane);
                    h[4 * ks] = v.x; h[4 * ks + 1] = v.y; h[4 * ks + 2] = v.z; h[4 * ks + 3] = v.w;
                }
            };
            auto check_h = [&](auto lo, auto hi) {
                uint32_t it = 0;
#pragma unroll 1
                while (true) {
                    uint32_t mn = ~0u;
#pragma unroll
                    for (int ks = lo.value; ks < hi.value; ks++) mn = __vimin3_u32(mn, h[4 * ks], h[4 * ks + 2]);
                    if (!__any_sync(0xffffffffu, mn == 0) || ++it >= SPIN / 16) break;
                    load_h(lo, hi);
                }
            };
            if (!HSENT) flag_wait(&g_flag_h[(qb * 8 + cw) * 32], tag);
            if (HSENT) __nanosleep(HDELAY);
            load_h(IC<0>{}, IC<4>{});
            DBG_T(104); DBG_G(109);
#pragma unroll
            for (int i = 0; i < 64; i++) o[i] = 0.f;
            uint32_t e = E0;
#pragma unroll 1
            for (int hd = 1;; hd++) {
                fence_regs(o);
                auto group = [&](auto tc) {
                    constexpr int t = tc.value, k0 = t ? 8 * t - 4 : 0;
                    const bool first = t == 0 && hd == 1;
                    mbar_wait(first ? bar_w0 : bar_full + 8 * (e & 3), (e >> 2) & 1);
                    const uint32_t dv = desc_lo(t ? 0 : 8192, UNIT) + (first ? 6 : e & 3) * (SLOT / 16);
                    if (HSENT && hd == 1) check_h(IC<k0>{}, IC<8 * t + 4>{});
                    WG_FENCE();
#pragma unroll
                    for (int ks = k0; ks < 8 * t + 4; ks++)
                        mma_rs128<1>(o, h[4 * ks], h[4 * ks + 1], h[4 * ks + 2], h[4 * ks + 3], desc_of(dv + (ks - k0) * 128), ks);
                    WG_COMMIT();
                    if (hd == 1) { if (t == 0) {   } if (t == 1) {   } if (t == 2) {   } if (t == 3) {   } if (t == 4) {   } }
                    if (t < 4 && hd == 1) load_h(IC<8 * t + 4>{}, IC<t < 4 ? 8 * t + 12 : 0>{});
                    if (t > 0) { WG_WAIT(1); if (t > 1 || hd > 1) release((e - 1) & 3); }
                    e++;
                };
                group(IC<0>{}); group(IC<1>{}); group(IC<2>{}); group(IC<3>{});
                if (e == 19) break;
                group(IC<4>{});
                WG_WAIT(0);
                if (hd == 1) {     }
                fence_regs(o);
                release((e - 1) & 3);
#pragma unroll
                for (int i = 0; i < 8; i++)
                    qpark[hd * 2048 + i * 32] = make_uint4(pack_bf16(o[8 * i], o[8 * i + 1]), pack_bf16(o[8 * i + 2], o[8 * i + 3]),
                                                           pack_bf16(o[8 * i + 4], o[8 * i + 5]), pack_bf16(o[8 * i + 6], o[8 * i + 7]));
                if (SPARE && hd == 2) {
                    float (&u)[32] = reinterpret_cast<float (&)[32]>(o);
                    fence_regs(u);
#pragma unroll
                    for (int t = 0; t < 3; t++) {
                        mbar_wait(bar_full + 8 * t, 1);
                        WG_FENCE();
#pragma unroll
                        for (int ks = 0; ks < (t < 2 ? 16 : 4); ks++)
                            mma_rs64<1>(u, h[64 * t + 4 * ks], h[64 * t + 4 * ks + 1], h[64 * t + 4 * ks + 2], h[64 * t + 4 * ks + 3],
                                        desc_of(desc_lo(t * SLOT, UNIT) + ks * 128), ks | t);
                        WG_COMMIT();
                        if (t > 0) { WG_WAIT(1); release(t - 1); }
                    }
                    WG_WAIT(0);
                    fence_regs(u);
                    release(2);
                    e = 15;
#pragma unroll
                    for (int i = 0; i < 4; i++)
                        qpark[3 * 2048 + i * 32] = make_uint4(pack_bf16(u[8 * i], u[8 * i + 1]), pack_bf16(u[8 * i + 2], u[8 * i + 3]),
                                                              pack_bf16(u[8 * i + 4], u[8 * i + 5]), pack_bf16(u[8 * i + 6], u[8 * i + 7]));
                }
            }
#pragma unroll
            for (int i = 0; i < 8; i++) {
                const uint4 v = qpark[2048 + i * 32];
                q[4 * i] = v.x; q[4 * i + 1] = v.y; q[4 * i + 2] = v.z; q[4 * i + 3] = v.w;
            }
#pragma unroll
            for (int i = 0; i < 32; i++) p[i] = h[112 + i];
            mbar_wait(bar_full + 24, 0);
            WG_WAIT(0);
            fence_regs(o);
            release(2);
        }
        DBG_T(105);
        DBG_G(125);

        uint8_t* frag = reinterpret_cast<uint8_t*>(__shfl_sync(0xffffffffu, reinterpret_cast<unsigned long long>(g_frag + (size_t)(rg * 8 + cw) * WREG + lane * 16), lane));
        const uint4* qnext = reinterpret_cast<const uint4*>(__shfl_sync(0xffffffffu, reinterpret_cast<unsigned long long>(padd(smem_raw, SM_Q + tid * 16 + cw * 3584)), lane));
        uint8_t* odst = reinterpret_cast<uint8_t*>(const_cast<uint4*>(qnext));
        qnext -= 2048;
        float m0, m1, l0 = 0.25f, l1 = 0.25f, t0, t1;
        uint32_t bad = 0;
        const int lw = cw & 3;
        const uint32_t relw = lw == RW && lane < 8, handw = lw == HW || cw == HW2;
        auto release4 = [&](uint32_t off) {
            asm volatile("{\n.reg .pred p;\nsetp.ne.b32 p, %1, 0;\n@p mbarrier.arrive.shared::cluster.b64 _, [%0];\n}" ::"r"(rel_base + off), "r"(relw) : "memory"); };
        auto handoff = [&]() {
            asm volatile("{\n.reg .pred p;\nsetp.ne.b32 p, %1, 0;\n@p bar.arrive %0, 192;\n}" ::"r"(2 - w), "r"(handw) : "memory"); };
        if (cw == 4 + HW) bar_arrive(1, 192);
        auto finish = [&](auto lo, auto hi, uint32_t bit, auto sink) {
#pragma unroll
            for (int i = lo.value; i < hi.value; i++) {
                const uint32_t v0 = pack_bf16(o[8 * i] * t0, o[8 * i + 1] * t0), v1 = pack_bf16(o[8 * i + 2] * t1, o[8 * i + 3] * t1);
                const uint32_t v2 = pack_bf16(o[8 * i + 4] * t0, o[8 * i + 5] * t0), v3 = pack_bf16(o[8 * i + 6] * t1, o[8 * i + 7] * t1);
                if (i == 0 && fabsf(o[0] * t0) >= 0x1p-31f) bad |= bit << 8;
                sink(i, v0, v1, v2, v3);
            }
        };
        float lq[6];
        auto row_parts = [&]() {
#pragma unroll
            for (int i = 0; i < 3; i++) { lq[i] = __shfl_xor_sync(0xffffffffu, l0, i + 1); lq[3 + i] = __shfl_xor_sync(0xffffffffu, l1, i + 1); }
        };
        auto row_sums = [&](uint32_t bit) {
            t0 = (l0 + lq[0]) + (lq[1] + lq[2]); t1 = (l1 + lq[3]) + (lq[4] + lq[5]);
            if (!(t0 >= LMIN && t0 < LMAX && t1 >= LMIN && t1 < LMAX)) bad |= bit;
        };
        auto issue_pv = [&](uint32_t dlo, int acc, auto lo, auto hi) {
            if (lo.value == 0) asm volatile("{\n.reg .pred p;\nsetp.eq.b32 p, %0, 0;\n@p bar.sync 4, 160;\n}" ::"r"(w) : "memory");
#pragma unroll
            for (int ks = lo.value; ks < hi.value; ks++)
                mma_rs128<1>(o, p[4 * ks], p[4 * ks + 1], p[4 * ks + 2], p[4 * ks + 3], desc_of(dlo + ks * 128), ks ? 1 : acc);
            WG_COMMIT();
        };
#pragma unroll
        for (int i = 0; i < 64; i++) s[i] = 0.f;
        uint32_t dv_lo = desc_lo(0, UNIT), voff = 0;
        auto issue_qk = [&]() {
            const uint32_t dk = dv_lo ^ (desc_lo(0, UNIT) ^ desc_lo(3 * SLOT, 16));
            bar_sync(1 + w, 192);
            fence_regs(s); fence_regs(q); fence_regs(o); fence_regs(p);
            WG_FENCE();
#pragma unroll
            for (int ks = 0; ks < 8; ks++)
                mma_rs128<0>(s, q[4 * ks], q[4 * ks + 1], q[4 * ks + 2], q[4 * ks + 3], desc_of(dk + (ks >> 2) * 1024 + (ks & 3) * 2), ks != 0);
            WG_COMMIT();
        };
        auto to_frag = [&](int i, uint32_t v0, uint32_t v1, uint32_t v2, uint32_t v3) {
            *reinterpret_cast<uint4*>(odst + i * 512) = make_uint4(v0, v1, v2, v3); };
        int n = 0;
        auto scores_ready = [&]() {
            WG_WAIT(1);
            fence_regs(s); fence_regs(q);
        };
        auto pass_on = [&]() {
            release4(voff ^ 24);
            handoff();
        };
#pragma unroll 1
        for (;;) {
            {
                row_parts();
                row_sums(1u << (n >> 4));
                if (RPE == 1) anchor(bar_full + 504, t0 + t1);
                issue_qk();
                t0 = rcp_fast(t0); t1 = rcp_fast(t1);
                l0 = 0.f; l1 = 0.f;
                odst = n ? frag + ((n >> 4) - 1) * 4096 : odst;
                if (RPE) anchor(bar_full + 504, (t0 + t1) * __uint_as_float((bad ^ (uint32_t)(uintptr_t)odst) & 0x3fffffff));
                asm volatile("{\n.reg .pred p;\nsetp.ne.b32 p, %1, 0;\n@p mbarrier.arrive.shared::cta.b64 _, [%0];\n}"
                             ::"r"(bar_qfree + (n >> 1) - 8), "r"(lane ? 0 : n) : "memory");
                issue_pv(dv_lo, 1, IC<0>{}, IC<8>{});
                scores_ready();
                float a0 = fmaxf(s[0], s[1]), a1 = fmaxf(s[2], s[3]), a2 = fmaxf(s[4], s[5]), a3 = fmaxf(s[6], s[7]);
#pragma unroll
                for (int i = 1; i < MAXG; i++) {
                    a0 = fmaxf(a0, fmaxf(s[8 * i], s[8 * i + 1])); a1 = fmaxf(a1, fmaxf(s[8 * i + 2], s[8 * i + 3]));
                    a2 = fmaxf(a2, fmaxf(s[8 * i + 4], s[8 * i + 5])); a3 = fmaxf(a3, fmaxf(s[8 * i + 6], s[8 * i + 7]));
                }
                const uint32_t a = pack_bf16(fmaxf(a0, a2), fmaxf(a1, a3));
                const uint32_t b = bmax2(bmax2(a, __shfl_xor_sync(0xffffffffu, a, 1)), bmax2(__shfl_xor_sync(0xffffffffu, a, 2), __shfl_xor_sync(0xffffffffu, a, 3)));
                pass_on();
                m0 = fmaf(-CS, bf_lo(b), -POFF); m1 = fmaf(-CS, bf_hi(b), -POFF);
            }
#pragma unroll 1
            for (;;) {
                DBG_T(n);
#pragma unroll
                for (int i = 0; i < 4 * STAGE; i++) s[i] = fmaf(s[i], CS, (i & 2) ? m1 : m0);
#pragma unroll
                for (int i = 0; i < 4 * SPLIT; i++) s[i] = ex2(s[i]);
#pragma unroll
                for (int i = 0; i < SPLIT; i++) { l0 += s[4 * i] + s[4 * i + 1]; l1 += s[4 * i + 2] + s[4 * i + 3]; }
                if (STAGE < 16) {
                    m0 = fmaf(l0, 0.f, m0); m1 = fmaf(l1, 0.f, m1);
                }
                anchor(bar_full + 504, l0 + l1);
                WG_WAIT(0);
                fence_regs(o); fence_regs(p);
                release4(voff);
                dv_lo ^= 2 * SLOT / 16;
                voff ^= 16;
                n++;
#pragma unroll
                for (int i = 4 * STAGE; i < 64; i++) s[i] = fmaf(s[i], CS, (i & 2) ? m1 : m0);
#pragma unroll
                for (int i = 4 * SPLIT; i < 64; i++) s[i] = ex2(s[i]);
#pragma unroll
                for (int i = SPLIT; i < 16; i++) { l0 += s[4 * i] + s[4 * i + 1]; l1 += s[4 * i + 2] + s[4 * i + 3]; }
#pragma unroll
                for (int i = 0; i < 32; i++) p[i] = pack_bf16(s[2 * i], s[2 * i + 1]);
                const int jn = n & 15;
                if (!(((0x8003 | RCM | RCM << 1) >> jn) & 1)) {
                    issue_qk();
                    issue_pv(dv_lo, 1, IC<0>{}, IC<8>{});
                    scores_ready();
                    pass_on();
                    continue;
                }
                if (jn == 1) {
                    finish(IC<0>{}, IC<ESPLIT>{}, 1u << (n >> 4), to_frag);
                    issue_qk();
                    finish(IC<ESPLIT>{}, IC<8>{}, 1u << (n >> 4), to_frag);
                    WG_FENCE();
                    issue_pv(dv_lo, 0, IC<0>{}, IC<8>{});
                    scores_ready();
                    pass_on();
                    continue;
                }
                if (jn == 0) break;
                if (RCM && jn != 15) {
                    if ((RCM >> jn) & 1) {
                        row_parts();
                        row_sums(2u << (n >> 4));
                        const uint32_t e0 = __float_as_uint(t0) >> 23, e1 = __float_as_uint(t1) >> 23;
                        m0 -= __uint_as_float(0x4b000000u | e0) - (8388608.f + 127.f - POFF);
                        m1 -= __uint_as_float(0x4b000000u | e1) - (8388608.f + 127.f - POFF);
                        t0 = __uint_as_float((254 - (int)POFF - e0) << 23); t1 = __uint_as_float((254 - (int)POFF - e1) << 23);
                        l0 *= t0; l1 *= t1;
                    } else {
#pragma unroll
                        for (int i = 0; i < 64; i++) o[i] *= (i & 2) ? t1 : t0;
                    }
                    issue_qk();
                    issue_pv(dv_lo, 1, IC<0>{}, IC<8>{});
                    scores_ready();
                    pass_on();
                    continue;
                }
                if (SPARE && n == 47) mbar_wait(bar_q3, 0);
                qnext = n == 63 ? reinterpret_cast<const uint4*>(frag) : qnext + 2048;
                issue_qk();
                issue_pv(dv_lo, 1, IC<0>{}, IC<8>{});
                scores_ready();
                pass_on();
#pragma unroll
                for (int i = 0; i < 8; i++) {
                    const uint4 v = qnext[i * 32];
                    q[4 * i] = v.x; q[4 * i + 1] = v.y; q[4 * i + 2] = v.z; q[4 * i + 3] = v.w;
                }
            }
            if (n == 64) break;
        }
        DBG_T(64);
        uint32_t a1[32], a2[32];
        row_parts();
        frag_load(a1, frag + 4096);
        frag_load(a2, frag + 8192);
        bar_sync(1 + w, 192);
        fence_regs(o); fence_regs(p);
        WG_FENCE();
        issue_pv(desc_lo(3 * SLOT, UNIT), 1, IC<0>{}, IC<8>{});
        handoff();
        row_sums(16);
        t0 = rcp_fast(t0); t1 = rcp_fast(t1);
        mbar_wait(bar_mod, 0);
        WG_WAIT(0);
        fence_regs(o); fence_regs(p);
        release4(24);
        finish(IC<0>{}, IC<8>{}, 16, [&](int i, uint32_t v0, uint32_t v1, uint32_t v2, uint32_t v3) {
            p[4 * i] = v0; p[4 * i + 1] = v1; p[4 * i + 2] = v2; p[4 * i + 3] = v3; });
        bad = __reduce_or_sync(0xffffffffu, bad);
        bad = ((bad | ~(bad >> 8)) >> 1) & 15;
        if (__builtin_expect(bad != 0, 0)) {
            uint8_t* keep = g_keep + (size_t)(rg * 8 + cw) * 4096 + lane * 16;
            frag_store(keep, p);
            attn_fallback(bad, tag, gs, frag, keep, args.wq, args.kc, args.vc);
            frag_load(q, frag); frag_load(a1, frag + 4096); frag_load(a2, frag + 8192); frag_load(p, keep);
        }
        DBG_T(80);
        DBG_G(124);

        const uint32_t eye = (lane >> 3) == (lane & 3) ? 0x3f80u << ((lane & 4) * 4) : 0;
        auto sum8 = [&](uint32_t* r, const uint4 (&v)[8]) {
            float d[16];
#pragma unroll
            for (int i = 0; i < 16; i++) d[i] = 0.f;
#pragma unroll
            for (int src = 0; src < 8; src++) {
                mma1688(d + 8 * (src & 1), v[src].x, v[src].y, eye);
                mma1688(d + 8 * (src & 1) + 4, v[src].z, v[src].w, eye);
            }
#pragma unroll
            for (int i = 0; i < 4; i++) r[i] = pack_bf16(d[2 * i] + d[8 + 2 * i], d[2 * i + 1] + d[9 + 2 * i]);
        };
        uint4 v2[8], v3[8], wf[27];
        uint2 u4[8], gw[9];
        uint32_t x1[20], xs, pa, ta;
        const uint8_t *mb, *mb4;
        int tid_;
        auto load_wf = [&](auto lo, auto hi) {
            const uint32_t wa = sb + SM_Q + ((cw & 1) * D_ + (cw >> 1) * 32 + (tid_ & 7) + (tid_ & 16) / 2) * 80 + (tid_ & 8) * 2;
#pragma unroll
            for (int i = lo.value; i < hi.value; i++)
                wf[i] = ldsm4t((i < 24 ? wa + ((i / 3 & 3) * 8 + i / 12) * 1280 : wa + (32 - (cw >> 1)) * 1280) + (i % 3) * 32);
        };
        uint32_t at[18];
        {
            float (&u)[32] = reinterpret_cast<float (&)[32]>(o);
            uint32_t off = 0;
            auto turn = [&](const uint32_t (&a)[32], const uint32_t (&b)[32], int acc) {
                const uint64_t dv = desc_of(desc_lo(0, UNIT) + off * (SLOT / 128));
                bar_sync(1 + w, 192);
                fence_regs(u);
                WG_FENCE();
#pragma unroll
                for (int ks = 0; ks < 16; ks++) {
                    const uint32_t* f = ks < 8 ? &a[4 * ks] : &b[4 * ks - 32];
                    mma_rs64<1>(u, f[0], f[1], f[2], f[3], dv + ks * 128, ks | acc);
                    if (ks == OSPLIT - 1) WG_COMMIT();
                }
                WG_COMMIT();
                WG_WAIT(1);
            };
            auto done = [&]() {
                WG_WAIT(0);
                fence_regs(u);
                release4(off);
                off = (off + 8) & 24;
            };
            auto store = [&](uint8_t* dst) {
#pragma unroll
                for (int i = 0; i < 4; i++)
                    st_relaxed4(dst + i * 512, pack_bf16(u[8 * i], u[8 * i + 1]), pack_bf16(u[8 * i + 2], u[8 * i + 3]),
                                pack_bf16(u[8 * i + 4], u[8 * i + 5]), pack_bf16(u[8 * i + 6], u[8 * i + 7]));
            };
            tid_ = __shfl_sync(0xffffffffu, tid, lane);
            pa = sb + w * (UNIT - 2048) + tid_ * 16;
#pragma unroll
            for (int i = 0; i < 8; i++) at[i] = 0;
            fence_regs(q); fence_regs(p);
            uint8_t* dst = frag;
#pragma unroll 1
            for (int k = 0; k < 8; k++, dst += 2048) {
                const uint32_t poff = off;
                const bool sum = (0xa0 >> k) & 1;
                if (sum) off = (off + 8) & 24;
                turn(q, p, 0);
                handoff();
                if (sum) {
                    uint4 v[8];
#pragma unroll
                    for (int src = 0; src < 8; src++) v[src] = lds128(pa + poff * (SLOT / 8) + src * 2048);
                    __syncwarp();
                    release(poff >> 3);
                    done();
                    float d[8];
#pragma unroll
                    for (int i = 0; i < 8; i++) {
                        float t[8];
#pragma unroll
                        for (int src = 0; src < 8; src++) {
                            const uint32_t x = i < 2 ? v[src].x : i < 4 ? v[src].y : i < 6 ? v[src].z : v[src].w;
                            t[src] = (i & 1) ? bf_hi(x) : bf_lo(x);
                        }
                        d[i] = ((t[0] + t[2]) + (t[4] + t[6])) + ((t[1] + t[3]) + (t[5] + t[7]));
                    }
#pragma unroll
                    for (int i = 0; i < 4; i++) { at[i] = at[4 + i]; at[4 + i] = pack_bf16(d[2 * i], d[2 * i + 1]); }
                } else {
                    done();
                }
                turn(a1, a2, 1);
                handoff();
                done();
                store(dst);
                __syncwarp();
                asm volatile("{\n.reg .pred p;\nsetp.ne.b32 p, %1, 0;\n@p mbarrier.arrive.shared::cta.b64 _, [%0];\n}"
                             ::"r"(bar_pub + 4 + 4 * k), "r"(lane ? 0 : (0x2a >> k) & 1) : "memory");
            }
            turn(q, p, 0);
            handoff();
            mb = padd(g_frag, (qb * 64 + j) * WREG + 3 * 4096 + tid_ * 16);
            mb4 = padd(mb, 4096 + ((cw >> 1) - cw) * 512 + (cw & 1) * 8);
            xs = sb + (tid_ & 15) * XP + (tid_ & 16) + cw * 32;
            ta = sb + (cw * 8 + (tid_ & 3)) * 8;
#pragma unroll
            for (int k = 0; k < 9; k++) {
                gw[k] = lds64(ta + SM_T + (k < 8 ? (k >> 1) * 64 + (k & 1) * 4 : 256 - cw * 4) * 8);
                if (!(tid_ & 4)) gw[k].y = 0x3f803f80u;
            }
            mbar_wait(bar_g, 0);
            done();
            load_wf(IC<0>{}, IC<WF0>{});
            turn(a1, a2, 1);
            if (w == 0) handoff();
            if (P2E) {
                mbar_wait(bar_full + 8, 0);
#pragma unroll
                for (int src = 0; src < 8; src++) v2[src] = lds128(pa + SLOT + src * 2048);
            }
            done();
            store(dst);
            mbar_wait(bar_full, 0);
            rows_load(x1, xs, cw);
            if (w == 0) bar_sync(5, 256); else bar_arrive(5, 256);
        }
        DBG_T(81);
        DBG_G(122);

        {
        const int tid = tid_, lane = tid & 31;
        const int g8 = lane >> 2, qd = lane & 3, l16 = lane & 15;
        uint32_t h2[18], gb[9], k1, k2;
        float4* rec = reinterpret_cast<float4*>(red + 128);
        const uint2* candp = reinterpret_cast<const uint2*>(padd(g_cand, ((blockIdx.x & (CREP - 1)) * NCTA + (tid >> 1)) * 32 + (tid & 1) * 8));
        uint2 cd;
        auto stage_out = [&]() {
#pragma unroll
            for (int k = 0; k < 9; k++) {
                x1[2 * k] = badd2(x1[2 * k], bmul2(gb[k], h2[2 * k]));
                x1[2 * k + 1] = badd2(x1[2 * k + 1], bmul2(gb[k], h2[2 * k + 1]));
            }
#pragma unroll
            for (int ch = 0; ch < 4; ch++) stsm_x4(xs + ch * 256, x1[4 * ch], x1[4 * ch + 1], x1[4 * ch + 2], x1[4 * ch + 3]);
            asm volatile("stmatrix.sync.aligned.m8n8.x2.shared.b16 [%0], {%1, %2};" ::"r"(xs + 1024 - cw * 16), "r"(x1[16]), "r"(x1[17]) : "memory");
        };
        {
            uint32_t it = 0, miss;
            if (!P2E) {
                mbar_wait(bar_full + 8, 0);
#pragma unroll
                for (int src = 0; src < 8; src++) v2[src] = lds128(pa + SLOT + src * 2048);
            }
            sum8(at + 8, v2);
            float st[12];
#pragma unroll
            for (int i = 0; i < 12; i++) st[i] = 0.f;
            auto add_pair = [&](int k) {
                x1[2 * k] = badd2(x1[2 * k], bmul2(gw[k].x, at[2 * k]));
                x1[2 * k + 1] = badd2(x1[2 * k + 1], bmul2(gw[k].x, at[2 * k + 1]));
                stats_add(st, x1[2 * k], x1[2 * k + 1], gw[k].y);
            };
#pragma unroll
            for (int k = 0; k < 6; k++) add_pair(k);
            mbar_wait(bar_full + 16, 0);
#pragma unroll
            for (int src = 0; src < 8; src++) v3[src] = lds128(pa + 2 * SLOT + src * 2048);
#pragma unroll 1
            do {
                if (BO && it) __nanosleep(BO);
                miss = 0;
#pragma unroll
                for (int src = 0; src < 8; src++) reload16(v3[src], mb + (size_t)src * 8 * WREG, miss);
            } while (__any_sync(0xffffffffu, miss) && ++it < SPIN / 16);
            if (lane < 4) mbar_arrive_cluster(rel_base + 8 * (1 + (lane >> 1)));
            sum8(at + 12, v3);
            add_pair(6); add_pair(7);
            load_wf(IC<WF0>{}, IC<WF1>{});
            uint2 cs[9];
#pragma unroll
            for (int k = 0; k < 9; k++) cs[k] = lds64(ta + SM_TC + (k < 8 ? (k >> 1) * 64 + (k & 1) * 4 : 256 - cw * 4) * 8);
            mbar_wait(bar_pre, 0);
            mbar_wait(bar_full + 24, 0);
#pragma unroll
            for (int src = 0; src < 8; src++) u4[src] = lds64(sb + 3 * SLOT + src * 2048 + (cw >> 1) * 512 + lane * 16 + (cw & 1) * 8);
#pragma unroll 1
            do {
                if (BO && miss) __nanosleep(BO);
                miss = 0;
#pragma unroll
                for (int src = 0; src < 8; src++) reload8(u4[src], mb4 + (size_t)src * 8 * WREG, miss);
            } while (__any_sync(0xffffffffu, miss) && ++it < SPIN / 16);
            float d[8] = {0.f, 0.f, 0.f, 0.f, 0.f, 0.f, 0.f, 0.f};
#pragma unroll
            for (int i = 0; i < 4; i++) mma16816(d + 4 * (i & 1), u4[2 * i].x, u4[2 * i].y, u4[2 * i + 1].x, u4[2 * i + 1].y, eye, eye);
            at[16] = pack_bf16(d[0] + d[4], d[1] + d[5]); at[17] = pack_bf16(d[2] + d[6], d[3] + d[7]);
            add_pair(8);
            DBG_G(123);
            const float2 ws = *reinterpret_cast<const float2*>(smem_raw + SM_TS);
            uint4* cdst = padd(g_cand, CFULL ? ((tid >> 1) * NCTA + rg) * 32 + (tid & 1) * 16 : (tid * NCTA + rg) * 32);
            uint32_t mean2;
            float dot;
            const float rsd = rows_stats(st, rec, cw, lane, mean2, dot);
            const uint32_t b = __float_as_uint(fmaf(fmaf(-bf_lo(mean2), ws.x, dot), rsd, ws.y));
            const uint32_t key = (((b & 0x80000000u) ? ~b : (b | 0x80000000u)) | 2047u) - (rg * 16 + l16);
            top2(key, k1, k2);
            if (tid < (CFULL + 1) * CREP) st_relaxed(cdst, k1, tag, k2, tag);
            cd = ld_relaxed64(candp);
            rows_normalise(h2, x1, mean2, rsd, lane, [&]() {
#pragma unroll
                for (int k = 0; k < 9; k++) gb[k] = lds32(sb + SM_TG + (cw * 8 + qd + (k < 8 ? (k >> 1) * 64 + (k & 1) * 4 : 256 - cw * 4)) * 4);
                if (WFE) load_wf(IC<WF1>{}, IC<WF2>{});
            });
#pragma unroll
            for (int k = 0; k < 18; k++) h2[k] = badd2(bmul2(h2[k], cs[k >> 1].x), cs[k >> 1].y);
            const uint32_t r1 = ~k1 & 15, r2 = ~k2 & 15;
            uint32_t todo = ((r1 & 7) == g8) | ((r2 & 7) == g8) << 1;
#pragma unroll 1
            while (todo) {
                const bool second = !(todo & 1), hi = (second ? r2 : r1) & 8;
                uint4* dst = padd(g_rows, ((rg * 2 + second) * RSLOT + cw * 16 + qd) * 16);
                uint32_t r[18];
#pragma unroll
                for (int k = 0; k < 9; k++) { r[k] = hi ? h2[2 * k + 1] : h2[2 * k]; r[9 + k] = hi ? x1[2 * k + 1] : x1[2 * k]; }
                fence_regs(r);
                st_relaxed(dst, r[0], r[1], r[2], r[3]);
                st_relaxed(dst + 4, r[4], r[5], r[6], r[7]);
                st_relaxed64(reinterpret_cast<uint2*>(padd(dst, 2048 - cw * 224 - qd * 8)), r[8], r[17]);
                st_relaxed(dst + 8, r[9], r[10], r[11], r[12]);
                st_relaxed(dst + 12, r[13], r[14], r[15], r[16]);
                todo &= todo - 1;
            }
            __syncwarp();

            if (SO == 0) stage_out();
            if (!WFE) load_wf(IC<WF1>{}, IC<WF2>{});
        }
        DBG_G(110);
        float2* part = reinterpret_cast<float2*>(smem_raw + 3 * SLOT + UNIT);
        bf16* act = reinterpret_cast<bf16*>(smem_raw + 3 * SLOT + UNIT + 4096);
        {
            uint32_t it = 0;
            const bool own = (tid >> 1) == rg;
            const uint32_t ks = sb + 3 * SLOT + UNIT + 5120;
#pragma unroll 1
            while (cd.y != tag && !own && ++it < SPIN / 16) cd = ld_relaxed64(candp);
            asm volatile("st.shared.u32 [%0], %1;" ::"r"(ks + tid * 4), "r"(own ? (tid & 1) ? k2 : k1 : cd.x) : "memory");
            bar_sync(3, 256);
            DBG_G(111);
            const uint4 a = lds128(ks + lane * 16), b = lds128(ks + 512 + lane * 16);
            const uint32_t a1 = max(a.x, a.z), a2 = __vimax3_u32(min(a.x, a.z), a.y, a.w);
            const uint32_t b1 = max(b.x, b.z), b2 = __vimax3_u32(min(b.x, b.z), b.y, b.w);
            const uint32_t c1 = max(a1, b1), c2 = __vimax3_u32(min(a1, b1), a2, b2);
            k1 = __reduce_max_sync(0xffffffffu, c1);
            k2 = __reduce_max_sync(0xffffffffu, c1 == k1 ? c2 : c1);
        }
        const int sel0 = ~k1 & 2047, sel1 = ~k2 & 2047;
        const uint32_t slot0 = (sel0 >> 4) * 2, slot1 = (sel1 >> 4) * 2 + ((sel0 ^ sel1) < 16);
        uint4 b[9], b2[3];
        {
            const bool tk = cw < 4 ? cw & 2 : lane & 16;
            const int ri = cw < 4 ? tid & 63 : 64 + l16;
            const uint4* hp = padd(g_rows, ((tk ? slot1 : slot0) * RSLOT + (cw < 4 ? ri + (ri & 56) : ri + 64)) * 16);
            const uint32_t hs = sb + 3 * SLOT + UNIT + 8192;
            uint4 hr = make_uint4(cw < 5 ? ~0u : 0, 0, 0, 0);
            uint32_t it = 0, miss;
            reload16(hr, hp, miss);
            if (OUTP == 0 && SO == 0 && tid == 255) {
                reinterpret_cast<int2*>(red)[8] = make_int2(sel0, sel1);
                mbar_arrive(bar_out);
            }
            if (SO == 1) stage_out();
            load_wf(IC<WF2>{}, IC<27>{});
            mbar_wait(bar_full + 8, 1);
            mbar_wait(bar_full + 16, 1);
            {
                const uint32_t da = sb + (lane < 18 ? SLOT + lane * XP : 2 * SLOT + (lane - 18) * XP) + cw * 144;
                const uint32_t db = sb + 2 * SLOT + (14 + (lane & 3)) * XP + cw * 144 + (lane >> 3) * 16;
#pragma unroll
                for (int i = 0; i < 9; i++) b[i] = ldsm4t(da + i * 16);
#pragma unroll
                for (int i = 0; i < 3; i++) b2[i] = ldsm4t(db + i * 48);
            }
#pragma unroll 1
            do {
                miss = 0;
                reload16(hr, hp, miss);
            } while (__any_sync(0xffffffffu, miss) && ++it < SPIN / 16);
            if (cw < 5) asm volatile("st.shared.v4.u32 [%0], {%1, %2, %3, %4};" ::"r"(hs + (tk * 84 + ri) * 16), "r"(hr.x), "r"(hr.y), "r"(hr.z), "r"(hr.w) : "memory");
            bar_sync(3, 256);
            if (OUTP == 0 && SO == 1 && tid == 255) {
                reinterpret_cast<int2*>(red)[8] = make_int2(sel0, sel1);
                mbar_arrive(bar_out);
            }
            uint4 hv[4];
            uint32_t hw[2];
#pragma unroll
            for (int i = 0; i < 4; i++) hv[i] = lds128(hs + ((g8 & 1) * 84 + (cw >> 1) * 16 + qd + i * 4) * 16);
#pragma unroll
            for (int i = 0; i < 2; i++)
                hw[i] = lds32(hs + ((g8 & 1) * 84 + 64) * 16 + (cw >> 1) * 64 + qd * 8 + i * 32);
            DBG_G(112);
            float acc[24];
#pragma unroll
            for (int i = 0; i < 24; i++) acc[i] = 0.f;
#pragma unroll
            for (int i = 0; i < 27; i++) {
                const int ks = i / 3;
                mma16816(acc + 4 * (i % 6), wf[i].x, wf[i].y, wf[i].z, wf[i].w, ks == 8 ? hw[0] : (ks & 1) ? hv[ks >> 1 & 3].z : hv[ks >> 1 & 3].x,
                         ks == 8 ? hw[1] : (ks & 1) ? hv[ks >> 1 & 3].w : hv[ks >> 1 & 3].y);
            }
            if (qd == 0) {
#pragma unroll
                for (int i = 0; i < 5; i++) part[cw * 48 + i * 8 + g8] = make_float2(acc[2 * i] + acc[12 + 2 * i], acc[2 * i + 1] + acc[13 + 2 * i]);
            }
        }
        {
            uint2* dst = padd(g_ypart, ((((g8 & 1) * 36 + ((cw * 9) >> 1)) * NCTA + blockIdx.x) * 8 + (cw & 1) * 4 + qd) * 8);
            uint2* dst1 = dst + ((cw & 1) ? NCTA * 8 - 4 : 4);
            bar_sync(3, 256);

            {
                const float* pp = reinterpret_cast<const float*>(part) + ((blockIdx.x & 1) << 3) + (tid & 127);
                const float gs = rbf((pp[0] + pp[192]) + (pp[384] + pp[576])), us = rbf((pp[96] + pp[288]) + (pp[480] + pp[672]));
                const float v = rbf(gs * sigmoidf_(gs)) * us;
                if (tid < 80) act[(tid & 1) * 56 + (tid >> 1)] = __float2bfloat16_rn(tid < 72 ? v : 0.f);
            }
            bar_sync(3, 256);
            DBG_G(113);
            const uint32_t ap = sb + 3 * SLOT + UNIT + 4096 + (lane & 1) * 112 + (lane >> 4) * 16;
            const uint4 a0 = ldsm4(ap), a1 = ldsm4(ap + 32), a2 = ldsm4(ap + 64);
            float y[36];
#pragma unroll
            for (int i = 0; i < 36; i++) y[i] = 0.f;
#pragma unroll
            for (int i = 0; i < 9; i++) {
                const uint32_t bl = i % 3 == 0 ? b2[i / 3].x : i % 3 == 1 ? b2[i / 3].y : b2[i / 3].z;
                mma16816(y + 4 * i, a0.x, a0.y, a0.z, a0.w, b[i].x, b[i].y);
                mma16816(y + 4 * i, a1.x, a1.y, a1.z, a1.w, b[i].z, b[i].w);
                mma1688(y + 4 * i, a2.x, a2.y, bl);
            }
#pragma unroll
            for (int i = 0; i < 9; i++)
                if (lane < 8) st_relaxed64(((i & 1) ? dst1 : dst) + (i >> 1) * (NCTA * 8), __float_as_uint(y[4 * i]), __float_as_uint(y[4 * i + 1]));
        }
        DBG_G(114);
        if (OUTP == 1 && tid == 255) {
            reinterpret_cast<int2*>(red)[8] = make_int2(sel0, sel1);
            mbar_arrive(bar_out);
        }
        if (blockIdx.x == 127 && tid == 0) gs->epoch[0] = tag;
        if (blockIdx.x < 72) {
            const int tok = blockIdx.x >= 36, grp = blockIdx.x - tok * 36, cp = grp * 8 + (lane & 7);
            const uint2* src = padd(g_ypart, (blockIdx.x * NCTA * 8 + tid) * 8);
            const uint8_t* hsrc = reinterpret_cast<const uint8_t*>(padd(g_rows, (tok ? slot1 : slot0) * (RSLOT * 16) +
                (grp < 32 ? (grp & 7) * 256 + (grp >> 4) * 64 + qd * 16 + (grp & 8) + (lane & 4) : 2048 + (cp - 256) * 8)));
            const uint8_t* xsrc = hsrc + (grp < 32 ? 128 : 4);
            uint32_t* dst = padd(reinterpret_cast<uint32_t*>(args.out), (tok ? sel1 : sel0) * (D_ * 2) + cp * 4);
            const uint32_t gb = reinterpret_cast<const uint32_t*>(smem_raw + SM_TG)[cp];
            const uint32_t ksel = ((tok ? k2 : k1) & ~2047u) | 1024u;
            const float sg = sigmoidf_(rbf(__uint_as_float((ksel & 0x80000000u) ? (ksel & 0x7fffffffu) : ~ksel)));
            uint2 v[4];
            uint32_t hv, xv, it = 0;
            bool miss;
#pragma unroll 1
            do {
#pragma unroll
                for (int i = 0; i < 4; i++) v[i] = ld_relaxed64(src + i * 256);
                hv = ld_relaxed32(hsrc);
                xv = ld_relaxed32(xsrc);
                miss = max(__vimax3_u32(v[0].x, v[1].x, v[2].x), __vimax3_u32(v[3].x, hv, xv)) == ~0u;
            } while (__any_sync(0xffffffffu, miss) && ++it < SPIN / 16);
            float y0 = (__uint_as_float(v[0].x) + __uint_as_float(v[1].x)) + (__uint_as_float(v[2].x) + __uint_as_float(v[3].x));
            float y1 = (__uint_as_float(v[0].y) + __uint_as_float(v[1].y)) + (__uint_as_float(v[2].y) + __uint_as_float(v[3].y));
            y0 += __shfl_xor_sync(0xffffffffu, y0, 8); y1 += __shfl_xor_sync(0xffffffffu, y1, 8);
            y0 += __shfl_xor_sync(0xffffffffu, y0, 16); y1 += __shfl_xor_sync(0xffffffffu, y1, 16);
            if (lane < 8) reinterpret_cast<float2*>(rec)[cw * 8 + lane] = make_float2(y0, y1);
            bar_sync(3, 256);
            if (cw == 0) {
                const float2 t0_ = reinterpret_cast<const float2*>(rec)[lane], t1_ = reinterpret_cast<const float2*>(rec)[32 + lane];
                y0 = t0_.x + t1_.x; y1 = t0_.y + t1_.y;
                y0 += __shfl_xor_sync(0xffffffffu, y0, 8); y1 += __shfl_xor_sync(0xffffffffu, y1, 8);
                y0 += __shfl_xor_sync(0xffffffffu, y0, 16); y1 += __shfl_xor_sync(0xffffffffu, y1, 16);
                const uint32_t y2 = bmul2(pack_bf16(y0, y1), pack_bf16(sg, sg));
                if (lane < 8) *dst = badd2(xv, bmul2(gb, badd2(hv, y2)));
            }
        }
        }
        DBG_T(88);
        DBG_G(121);
    }
}

typedef CUresult (*EncodeFn)(CUtensorMap*, CUtensorMapDataType, cuuint32_t, void*, const cuuint64_t*, const cuuint64_t*,
                             const cuuint32_t*, const cuuint32_t*, CUtensorMapInterleave, CUtensorMapSwizzle,
                             CUtensorMapL2promotion, CUtensorMapFloatOOBfill);

static void make_map(EncodeFn enc, CUtensorMap* m, const void* ptr, int rank, const cuuint64_t* dims,
                     const cuuint64_t* strides, const cuuint32_t* box, CUtensorMapSwizzle sw = CU_TENSOR_MAP_SWIZZLE_128B,
                     CUtensorMapDataType dt = CU_TENSOR_MAP_DATA_TYPE_BFLOAT16) {
    const cuuint32_t es[3] = {1, 1, 1};
    enc(m, dt, rank, const_cast<void*>(ptr), dims, strides, box, es,
        CU_TENSOR_MAP_INTERLEAVE_NONE, sw, CU_TENSOR_MAP_L2_PROMOTION_L2_128B,
        CU_TENSOR_MAP_FLOAT_OOB_FILL_NONE);
}

extern "C" void kernel_launch(void* const* d_in, const int* in_sizes, int n_in, void* d_out, int out_size) {
    const bf16* x = (const bf16*)d_in[0];
    const bf16* kc = (const bf16*)d_in[1];
    const bf16* vc = (const bf16*)d_in[2];
    const bf16* wq = (const bf16*)d_in[3];
    const bf16* wo = (const bf16*)d_in[4];
    const bf16* w_r = (const bf16*)d_in[6];
    const bf16* w_gate = (const bf16*)d_in[7];
    const bf16* w_up = (const bf16*)d_in[8];
    const bf16* w_down = (const bf16*)d_in[9];
    const bf16* cvec = (const bf16*)d_in[10];
    const bf16* w_mod = (const bf16*)d_in[11];
    bf16* out = (bf16*)d_out;

    void* fn = nullptr;
    cudaDriverEntryPointQueryResult qr;
    cudaGetDriverEntryPoint("cuTensorMapEncodeTiled", &fn, cudaEnableDefault, &qr);
    EncodeFn enc = (EncodeFn)fn;
    void* p_s;
    cudaGetSymbolAddress(&p_s, g_s);

    CUtensorMap tm_wq, tm_k, tm_v, tm_wo, tm_p, tm_x, tm_d, tm_g, tm_u;
    { cuuint64_t d[2] = {QD, D_}, s[1] = {QD * 2}; cuuint32_t b[2] = {64, 128}; make_map(enc, &tm_wq, wq, 2, d, s, b); }
    { cuuint64_t d[2] = {DH, HKV * S_}, s[1] = {DH * 2}; cuuint32_t b[2] = {64, 128};
      make_map(enc, &tm_k, kc, 2, d, s, b); make_map(enc, &tm_v, vc, 2, d, s, b); }
    { cuuint64_t d[2] = {D_, QD}, s[1] = {D_ * 2}; cuuint32_t b[2] = {64, 128}; make_map(enc, &tm_wo, wo, 2, d, s, b); }
    { cuuint64_t d[3] = {256, 160, NCTA}, s[2] = {1024, 8 * WREG}; cuuint32_t b[3] = {256, 2, 8};
      make_map(enc, &tm_p, ((Scratch*)p_s)->frag, 3, d, s, b, CU_TENSOR_MAP_SWIZZLE_NONE, CU_TENSOR_MAP_DATA_TYPE_UINT32); }
    { cuuint64_t d[2] = {D_ / 4, S_}, s[1] = {D_ * 2}; cuuint32_t b[2] = {XP / 8, 16};
      make_map(enc, &tm_x, x, 2, d, s, b, CU_TENSOR_MAP_SWIZZLE_NONE, CU_TENSOR_MAP_DATA_TYPE_UINT64); }
    { cuuint64_t d[2] = {D_ / 4, F_}, s[1] = {D_ * 2}; cuuint32_t b[2] = {XP / 8, 18};
      make_map(enc, &tm_d, w_down, 2, d, s, b, CU_TENSOR_MAP_SWIZZLE_NONE, CU_TENSOR_MAP_DATA_TYPE_UINT64); }
    { cuuint64_t d[2] = {F_, D_}, s[1] = {F_ * 2}; cuuint32_t b[2] = {40, 24};
      make_map(enc, &tm_g, w_gate, 2, d, s, b, CU_TENSOR_MAP_SWIZZLE_NONE); make_map(enc, &tm_u, w_up, 2, d, s, b, CU_TENSOR_MAP_SWIZZLE_NONE); }

    cudaFuncSetAttribute(fused_kernel<true>, cudaFuncAttributeMaxDynamicSharedMemorySize, SM_TOTAL);
    cudaFuncSetAttribute(fused_kernel<false>, cudaFuncAttributeMaxDynamicSharedMemorySize, SM_TOTAL);
    cudaLaunchConfig_t cfg = {};
    cfg.gridDim = NCTA + 4; cfg.blockDim = 384; cfg.dynamicSmemBytes = SM_TOTAL;
    cudaLaunchAttribute at;
    at.id = cudaLaunchAttributeClusterDimension; at.val.clusterDim.x = 2; at.val.clusterDim.y = 1; at.val.clusterDim.z = 1;
    cfg.attrs = &at; cfg.numAttrs = 1;
    int ncl = 0;
    if (cudaOccupancyMaxActiveClusters(&ncl, fused_kernel<true>, &cfg) != cudaSuccess) { ncl = 0; cudaGetLastError(); }
    Args args{w_mod, cvec, (Scratch*)p_s, out, x, kc, vc, wq, wo, w_r, w_down};
    if (USE_SPARE && ncl >= NCTA / 2 + 2)
        fused_kernel<true><<<NCTA + 4, 384, SM_TOTAL>>>(args, tm_wq, tm_k, tm_v, tm_wo, tm_p, tm_x, tm_d, tm_g, tm_u);
    else
        fused_kernel<false><<<NCTA, 384, SM_TOTAL>>>(args, tm_wq, tm_k, tm_v, tm_wo, tm_p, tm_x, tm_d, tm_g, tm_u);
}
```

```cpp
#include <cuda_runtime.h>
#include <cuda_bf16.h>
#include <cuda.h>
#include <stdint.h>
#include <math.h>

typedef __nv_bfloat16 bf16;

constexpr int S_ = 2048;
constexpr int D_ = 576;
constexpr int HQ = 32, HKV = 16, DH = 128;
constexpr int F_ = 4608;
constexpr int QD = HQ * DH;

constexpr int NCTA = 128;
constexpr int WREG = 5 * 4096;
constexpr int CREP = 8;
constexpr int RSLOT = 144;
constexpr int MREP = 4;
struct Scratch {
    unsigned int epoch[128];
    unsigned int flag_mod[NCTA];
    unsigned int flag_part[16 * 32];
    unsigned int flag_q3[16 * 32];
    unsigned int flag_h[NCTA * 32];
    uint2 mod1[MREP * D_];
    uint32_t mod2[4 * D_];
    uint4 cand[CREP * NCTA * 2];
    uint2 ypart[72 * NCTA * 8];
    uint4 h[2][NCTA * 36 * 32];
    uint4 q3[NCTA * 8 * 128];
    uint4 rows[NCTA * 2 * RSLOT];
    uint8_t frag[NCTA * 8 * WREG];
    uint8_t keep[NCTA * 8 * 4096];
};
__device__ __align__(1024) Scratch g_s;
#define g_h gs->h[tag & 1]
#define g_q3 gs->q3
#define g_keep gs->keep
#define g_flag_h gs->flag_h
#define g_flag_part gs->flag_part
#define g_flag_mod gs->flag_mod
#define g_flag_q3 gs->flag_q3
#define g_frag gs->frag
#define g_cand gs->cand
#define g_ypart gs->ypart
#define g_rows gs->rows

#define DBG_INIT()
#define DBG_P(i)
#define DBG_PG(i)
#define DBG_T(i)
#define DBG_G(i)

__device__ __forceinline__ uint32_t pack_bf16(float lo, float hi) {
    uint32_t r;
    asm("cvt.rn.bf16x2.f32 %0, %1, %2;" : "=r"(r) : "f"(hi), "f"(lo));
    return r;
}
__device__ __forceinline__ float rbf(float x) { return __uint_as_float(pack_bf16(0.f, x)); }
__device__ __forceinline__ float bf_lo(uint32_t v) { return __uint_as_float(v << 16); }
__device__ __forceinline__ float bf_hi(uint32_t v) { return __uint_as_float(v & 0xffff0000u); }
__device__ __forceinline__ float ex2(float x) {
    float y;
    asm("ex2.approx.ftz.f32 %0, %1;" : "=f"(y) : "f"(x));
    return y;
}
template <class T>
__device__ __forceinline__ T* padd(T* p, uint32_t off) {
    unsigned long long r;
    asm("{\n.reg .b32 l, h;\nmov.b64 {l, h}, %1;\nadd.cc.u32 l, l, %2;\naddc.u32 h, h, 0;\nmov.b64 %0, {l, h};\n}" : "=l"(r) : "l"(p), "r"(off));
    return reinterpret_cast<T*>(r);
}
__device__ __forceinline__ uint32_t smem_u32(const void* p) { return (uint32_t)__cvta_generic_to_shared(p); }
__device__ __forceinline__ void mbar_init(uint32_t bar, uint32_t cnt) {
    asm volatile("mbarrier.init.shared::cta.b64 [%0], %1;" ::"r"(bar), "r"(cnt) : "memory");
}
__device__ __forceinline__ void mbar_expect_tx(uint32_t bar, uint32_t bytes) {
    asm volatile("mbarrier.arrive.expect_tx.shared::cta.b64 _, [%0], %1;" ::"r"(bar), "r"(bytes) : "memory");
}
__device__ __forceinline__ void mbar_arrive(uint32_t bar) {
    asm volatile("mbarrier.arrive.shared::cta.b64 _, [%0];" ::"r"(bar) : "memory");
}
__device__ __forceinline__ void mbar_arrive_cluster(uint32_t cluster_addr) {
    asm volatile("mbarrier.arrive.shared::cluster.b64 _, [%0];" ::"r"(cluster_addr) : "memory");
}
constexpr uint32_t SPIN = 1u << 20;
__device__ __forceinline__ void mbar_wait(uint32_t bar, uint32_t parity) {
    asm volatile("{\n.reg .pred p;\n.reg .b32 c;\nmov.b32 c, 0;\n"
                 "W_%=:\nmbarrier.try_wait.parity.shared::cta.b64 p, [%0], %1;\n@p bra D_%=;\n"
                 "add.u32 c, c, 1;\nsetp.lt.u32 p, c, 0x100000;\n@p bra W_%=;\nD_%=:\n}"
                 ::"r"(bar), "r"(parity) : "memory");
}
__device__ __forceinline__ void anchor(uint32_t addr, float v) {
    asm volatile("{\n.reg .pred p;\nsetp.lt.f32 p, %1, 0f00000000;\n@p st.volatile.shared.f32 [%0], %1;\n}" ::"r"(addr), "f"(v) : "memory");
}
__device__ __forceinline__ void hold(float& a, float& b) {
    asm volatile("{\n.reg .pred p;\n.reg .b64 t;\n.reg .b32 l, h;\nmov.u64 t, %%clock64;\nmov.b64 {l, h}, t;\nsetp.eq.u32 p, h, 0xffffffff;\n"
                 "@p mov.f32 %0, 0f00000000;\n@p mov.f32 %1, 0f00000000;\n}" : "+f"(a), "+f"(b) :: "memory");
}
__device__ __forceinline__ void mbar_wait_sleep(uint32_t bar, uint32_t parity) {
    asm volatile("{\n.reg .pred p;\n.reg .b32 c;\nmov.b32 c, 0;\n"
                 "W_%=:\nmbarrier.try_wait.parity.shared::cta.b64 p, [%0], %1, 5000;\n@p bra D_%=;\n"
                 "add.u32 c, c, 1;\nsetp.lt.u32 p, c, 0x20000;\n@p bra W_%=;\nD_%=:\n}"
                 ::"r"(bar), "r"(parity) : "memory");
}
__device__ __forceinline__ uint32_t load_tag(const Scratch* gs) {
    uint32_t tag;
    asm volatile("ld.global.ca.u32 %0, [%1];" : "=r"(tag) : "l"(gs->epoch) : "memory");
    return tag + 1;
}
__device__ __forceinline__ uint4 ld_relaxed(const uint4* p) {
    uint4 v;
    asm volatile("ld.relaxed.gpu.global.v4.u32 {%0,%1,%2,%3}, [%4];" : "=r"(v.x), "=r"(v.y), "=r"(v.z), "=r"(v.w) : "l"(p) : "memory");
    return v;
}
__device__ __forceinline__ void st_relaxed(uint4* p, uint32_t a, uint32_t b, uint32_t c, uint32_t d) {
    asm volatile("{\n.reg .b64 u, v;\nmov.b64 u, {%1, %2};\nmov.b64 v, {%3, %4};\nst.relaxed.gpu.global.v2.b64 [%0], {u, v};\n}"
                 ::"l"(p), "r"(a), "r"(b), "r"(c), "r"(d) : "memory");
}
__device__ __forceinline__ void st_relaxed4(void* p, uint32_t a, uint32_t b, uint32_t c, uint32_t d) {
    asm volatile("st.relaxed.gpu.global.v4.u32 [%0], {%1, %2, %3, %4};" ::"l"(p), "r"(a), "r"(b), "r"(c), "r"(d) : "memory");
}
__device__ __forceinline__ uint2 ld_relaxed8(const void* p) {
    uint2 v;
    asm volatile("ld.relaxed.gpu.global.v2.u32 {%0,%1}, [%2];" : "=r"(v.x), "=r"(v.y) : "l"(p) : "memory");
    return v;
}
__device__ __forceinline__ uint2 ld_relaxed64(const uint2* p) {
    uint2 v;
    asm volatile("{\n.reg .b64 u;\nld.relaxed.gpu.global.b64 u, [%2];\nmov.b64 {%0, %1}, u;\n}" : "=r"(v.x), "=r"(v.y) : "l"(p) : "memory");
    return v;
}
__device__ __forceinline__ void st_relaxed64(uint2* p, uint32_t a, uint32_t b) {
    asm volatile("{\n.reg .b64 u;\nmov.b64 u, {%1, %2};\nst.relaxed.gpu.global.b64 [%0], u;\n}" ::"l"(p), "r"(a), "r"(b) : "memory");
}
__device__ __forceinline__ uint4 ld_relaxed2(const uint4* p) {
    uint4 v;
    asm volatile("{\n.reg .b64 u, w;\nld.relaxed.gpu.global.v2.b64 {u, w}, [%4];\nmov.b64 {%0, %1}, u;\nmov.b64 {%2, %3}, w;\n}"
                 : "=r"(v.x), "=r"(v.y), "=r"(v.z), "=r"(v.w) : "l"(p) : "memory");
    return v;
}
__device__ __forceinline__ void reload16(uint4& v, const void* p, uint32_t& miss) {
    asm volatile("{\n.reg .pred p;\n.reg .b32 m;\n.reg .b64 u, w;\nmax.u32 m, %0, %2;\nsetp.eq.u32 p, m, 0xffffffff;\n"
                 "mov.b64 u, {%0, %1};\nmov.b64 w, {%2, %3};\n@p ld.relaxed.gpu.global.v2.b64 {u, w}, [%5];\n"
                 "mov.b64 {%0, %1}, u;\nmov.b64 {%2, %3}, w;\n@p mov.u32 %4, 1;\n}"
                 : "+r"(v.x), "+r"(v.y), "+r"(v.z), "+r"(v.w), "+r"(miss) : "l"(p) : "memory");
}
__device__ __forceinline__ void reload8(uint2& v, const void* p, uint32_t& miss) {
    asm volatile("{\n.reg .pred p;\n.reg .b64 u;\nsetp.eq.u32 p, %0, 0xffffffff;\nmov.b64 u, {%0, %1};\n"
                 "@p ld.relaxed.gpu.global.b64 u, [%3];\nmov.b64 {%0, %1}, u;\n@p mov.u32 %2, 1;\n}"
                 : "+r"(v.x), "+r"(v.y), "+r"(miss) : "l"(p) : "memory");
}
__device__ __forceinline__ uint32_t ld_relaxed32(const void* p) {
    uint32_t v;
    asm volatile("ld.relaxed.gpu.global.u32 %0, [%1];" : "=r"(v) : "l"(p) : "memory");
    return v;
}
__device__ __forceinline__ void poll2x2(const uint4* p0, const uint4* p1, uint32_t tag, uint4& o0, uint4& o1) {
    uint4 v0, v1;
    uint32_t miss, it = 0;
#pragma unroll 1
    do {
        v0 = ld_relaxed2(p0); v1 = ld_relaxed2(p1);
        miss = (v0.y ^ tag) | (v0.w ^ tag) | (v1.y ^ tag) | (v1.w ^ tag);
    } while (miss && ++it < SPIN / 16);
    o0 = v0; o1 = v1;
}
__device__ __forceinline__ void flag_wait(const unsigned int* p, uint32_t tag) {
    uint32_t v, it = 0;
#pragma unroll 1
    do {
        asm volatile("ld.relaxed.gpu.global.u32 %0, [%1];" : "=r"(v) : "l"(p) : "memory");
    } while (__any_sync(0xffffffffu, v != tag) && ++it < SPIN / 16);
    asm volatile("fence.acquire.gpu;" ::: "memory");
    __syncwarp();
}
__device__ __forceinline__ bool elect() {
    uint32_t p;
    asm volatile("{\n.reg .pred p;\nelect.sync _|p, 0xffffffff;\nselp.u32 %0, 1, 0, p;\n}" : "=r"(p));
    return p;
}
__device__ __forceinline__ void flag_release(unsigned int* p, uint32_t tag) {
    asm volatile("st.release.gpu.global.u32 [%0], %1;" ::"l"(p), "r"(tag) : "memory");
}
__device__ __forceinline__ uint32_t touch(const void* p) {
    uint32_t v;
    asm volatile("ld.global.nc.L1::no_allocate.L2::128B.u32 %0, [%1];" : "=r"(v) : "l"(p));
    return v;
}
__device__ __forceinline__ void bar_sync(int id, int n) { asm volatile("bar.sync %0, %1;" ::"r"(id), "r"(n) : "memory"); }
__device__ __forceinline__ void bar_arrive(int id, int n) { asm volatile("bar.arrive %0, %1;" ::"r"(id), "r"(n) : "memory"); }

constexpr uint64_t EVICT_NORMAL = 0x1000000000000000ull, EVICT_FIRST = 0x12F0000000000000ull;
__device__ __forceinline__ void tma2d(uint32_t dst, const CUtensorMap* m, int c0, int c1, uint32_t bar) {
    asm volatile("cp.async.bulk.tensor.2d.shared::cluster.global.mbarrier::complete_tx::bytes.L2::cache_hint [%0], [%1, {%3, %4}], [%2], %5;"
                 ::"r"(dst), "l"(m), "r"(bar), "r"(c0), "r"(c1), "l"(EVICT_FIRST) : "memory");
}
__device__ __forceinline__ void tma2d_mc(uint32_t dst, const CUtensorMap* m, int c0, int c1, uint32_t bar, uint64_t pol) {
    asm volatile("cp.async.bulk.tensor.2d.shared::cluster.global.mbarrier::complete_tx::bytes.multicast::cluster.L2::cache_hint [%0], [%1, {%3, %4}], [%2], %5, %6;"
                 ::"r"(dst), "l"(m), "r"(bar), "r"(c0), "r"(c1), "h"((uint16_t)3), "l"(pol) : "memory");
}
__device__ __forceinline__ void tma3d(uint32_t dst, const CUtensorMap* m, int c0, int c1, int c2, uint32_t bar) {
    asm volatile("cp.async.bulk.tensor.3d.shared::cluster.global.mbarrier::complete_tx::bytes.L2::cache_hint [%0], [%1, {%3, %4, %5}], [%2], %6;"
                 ::"r"(dst), "l"(m), "r"(bar), "r"(c0), "r"(c1), "r"(c2), "l"(EVICT_FIRST) : "memory");
}
__device__ __forceinline__ void bulk_load(uint32_t dst, const void* src, uint32_t bytes, uint32_t bar) {
    asm volatile("cp.async.bulk.shared::cluster.global.mbarrier::complete_tx::bytes [%0], [%1], %2, [%3];"
                 ::"r"(dst), "l"(src), "r"(bytes), "r"(bar) : "memory");
}
__device__ __forceinline__ void l2_prefetch(const void* src, uint32_t bytes) {
    asm volatile("cp.async.bulk.prefetch.L2.global [%0], %1;" ::"l"(src), "r"(bytes) : "memory");
}
__device__ __forceinline__ uint32_t bmul2(uint32_t a, uint32_t b) { uint32_t r; asm("mul.rn.bf16x2 %0, %1, %2;" : "=r"(r) : "r"(a), "r"(b)); return r; }
__device__ __forceinline__ uint32_t badd2(uint32_t a, uint32_t b) { uint32_t r; asm("add.rn.bf16x2 %0, %1, %2;" : "=r"(r) : "r"(a), "r"(b)); return r; }
__device__ __forceinline__ uint32_t bsub2(uint32_t a, uint32_t b) { uint32_t r; asm("sub.rn.bf16x2 %0, %1, %2;" : "=r"(r) : "r"(a), "r"(b)); return r; }
__device__ __forceinline__ uint32_t bmax2(uint32_t a, uint32_t b) { uint32_t r; asm("max.bf16x2 %0, %1, %2;" : "=r"(r) : "r"(a), "r"(b)); return r; }
__device__ __forceinline__ uint32_t bfma2(uint32_t a, uint32_t b, uint32_t c) { uint32_t r; asm("fma.rn.bf16x2 %0, %1, %2, %3;" : "=r"(r) : "r"(a), "r"(b), "r"(c)); return r; }
__device__ __forceinline__ uint4 lds128(uint32_t a) { uint4 v; asm volatile("ld.shared.v4.u32 {%0,%1,%2,%3}, [%4];" : "=r"(v.x), "=r"(v.y), "=r"(v.z), "=r"(v.w) : "r"(a) : "memory"); return v; }
__device__ __forceinline__ uint2 lds64(uint32_t a) { uint2 v; asm volatile("ld.shared.v2.u32 {%0,%1}, [%2];" : "=r"(v.x), "=r"(v.y) : "r"(a) : "memory"); return v; }
__device__ __forceinline__ uint32_t lds32(uint32_t a) { uint32_t v; asm volatile("ld.shared.u32 %0, [%1];" : "=r"(v) : "r"(a) : "memory"); return v; }
__device__ __forceinline__ uint4 ldsm4(uint32_t a) {
    uint4 v;
    asm volatile("ldmatrix.sync.aligned.m8n8.x4.shared.b16 {%0,%1,%2,%3}, [%4];" : "=r"(v.x), "=r"(v.y), "=r"(v.z), "=r"(v.w) : "r"(a) : "memory");
    return v;
}
__device__ __forceinline__ uint4 ldsm4t(uint32_t a) {
    uint4 v;
    asm volatile("ldmatrix.sync.aligned.m8n8.x4.trans.shared.b16 {%0,%1,%2,%3}, [%4];" : "=r"(v.x), "=r"(v.y), "=r"(v.z), "=r"(v.w) : "r"(a) : "memory");
    return v;
}
__device__ __forceinline__ void mma1688(float* d, uint32_t a0, uint32_t a1, uint32_t b) {
    asm("mma.sync.aligned.m16n8k8.row.col.f32.bf16.bf16.f32 {%0,%1,%2,%3}, {%4,%5}, {%6}, {%0,%1,%2,%3};"
        : "+f"(d[0]), "+f"(d[1]), "+f"(d[2]), "+f"(d[3]) : "r"(a0), "r"(a1), "r"(b));
}
__device__ __forceinline__ void mma16816(float* d, uint32_t a0, uint32_t a1, uint32_t a2, uint32_t a3, uint32_t b0, uint32_t b1) {
    asm("mma.sync.aligned.m16n8k16.row.col.f32.bf16.bf16.f32 {%0,%1,%2,%3}, {%4,%5,%6,%7}, {%8,%9}, {%0,%1,%2,%3};"
                 : "+f"(d[0]), "+f"(d[1]), "+f"(d[2]), "+f"(d[3]) : "r"(a0), "r"(a1), "r"(a2), "r"(a3), "r"(b0), "r"(b1));
}
__device__ __forceinline__ void stsm_x4(uint32_t addr, uint32_t a, uint32_t b, uint32_t c, uint32_t d) {
    asm volatile("stmatrix.sync.aligned.m8n8.x4.shared.b16 [%0], {%1, %2, %3, %4};"
                 ::"r"(addr), "r"(a), "r"(b), "r"(c), "r"(d) : "memory");
}

__device__ __forceinline__ uint64_t mkdesc(uint32_t addr, uint32_t lbo, uint32_t sbo) {
    return (uint64_t)((addr & 0x3FFFF) >> 4) | ((uint64_t)(lbo >> 4) << 16) | ((uint64_t)(sbo >> 4) << 32) | (1ull << 62);
}
constexpr uint32_t SM0 = 1024;
__host__ __device__ constexpr uint32_t desc_lo(uint32_t off, uint32_t lbo) { return ((SM0 + off) >> 4) | ((lbo >> 4) << 16); }
__device__ __forceinline__ uint64_t desc_of(uint32_t lo) { return lo | (0x40000040ull << 32); }
#define WG_FENCE() asm volatile("wgmma.fence.sync.aligned;" ::: "memory")
#define WG_COMMIT() asm volatile("wgmma.commit_group.sync.aligned;" ::: "memory")
#define WG_WAIT(n) asm volatile("wgmma.wait_group.sync.aligned %0;" ::"n"(n) : "memory")

#define F8(a, i) "+f"(a[i]), "+f"(a[i + 1]), "+f"(a[i + 2]), "+f"(a[i + 3]), "+f"(a[i + 4]), "+f"(a[i + 5]), "+f"(a[i + 6]), "+f"(a[i + 7])
#define F16(a, i) F8(a, i), F8(a, i + 8)
#define F64(a) F16(a, 0), F16(a, 16), F16(a, 32), F16(a, 48)
#define F32(a) F16(a, 0), F16(a, 16)
#define L64 "%0,%1,%2,%3,%4,%5,%6,%7,%8,%9,%10,%11,%12,%13,%14,%15,%16,%17,%18,%19,%20,%21,%22,%23,%24,%25,%26,%27,%28,%29,%30,%31,%32,%33,%34,%35,%36,%37,%38,%39,%40,%41,%42,%43,%44,%45,%46,%47,%48,%49,%50,%51,%52,%53,%54,%55,%56,%57,%58,%59,%60,%61,%62,%63"
#define L32 "%0,%1,%2,%3,%4,%5,%6,%7,%8,%9,%10,%11,%12,%13,%14,%15,%16,%17,%18,%19,%20,%21,%22,%23,%24,%25,%26,%27,%28,%29,%30,%31"

template <int TB>
__device__ __forceinline__ void mma_rs128(float (&d)[64], uint32_t a0, uint32_t a1, uint32_t a2, uint32_t a3, uint64_t b, int acc) {
    asm volatile("{\n.reg .pred p;\nsetp.ne.b32 p, %69, 0;\n"
                 "wgmma.mma_async.sync.aligned.m64n128k16.f32.bf16.bf16 {" L64 "}, {%64,%65,%66,%67}, %68, p, 1, 1, %70;\n}"
                 : F64(d) : "r"(a0), "r"(a1), "r"(a2), "r"(a3), "l"(b), "r"(acc), "n"(TB));
}
template <int TB>
__device__ __forceinline__ void mma_rs64(float (&d)[32], uint32_t a0, uint32_t a1, uint32_t a2, uint32_t a3, uint64_t b, int acc) {
    asm volatile("{\n.reg .pred p;\nsetp.ne.b32 p, %37, 0;\n"
                 "wgmma.mma_async.sync.aligned.m64n64k16.f32.bf16.bf16 {" L32 "}, {%32,%33,%34,%35}, %36, p, 1, 1, %38;\n}"
                 : F32(d) : "r"(a0), "r"(a1), "r"(a2), "r"(a3), "l"(b), "r"(acc), "n"(TB));
}
template <int N>
__device__ __forceinline__ void fence_regs(float (&d)[N]) {
#pragma unroll
    for (int i = 0; i < N; i++) asm volatile("" : "+f"(d[i])::"memory");
}
template <int N>
__device__ __forceinline__ void fence_regs(uint32_t (&d)[N]) {
#pragma unroll
    for (int i = 0; i < N; i++) asm volatile("" : "+r"(d[i])::"memory");
}

template <int V> struct IC { static constexpr int value = V; };

constexpr int SLOT = 32768, UNIT = 16384;
constexpr int SM_Q = 4 * SLOT;
constexpr int SM_BAR = 7 * SLOT;
constexpr int SM_RED = SM_BAR + 512;
constexpr int SM_TOTAL = SM_BAR + 3072;
constexpr int XP = D_ * 2 + 16;
constexpr int M_MOD = 16 * XP;
constexpr int SM_T = SM_Q + 2 * D_ * 80, SM_TC = SM_T + D_ * 4, SM_TG = SM_TC + D_ * 4, SM_TS = SM_TG + D_ * 2;
constexpr float CS = 0.08838834764831845f * 1.4426950408889634f;
#define LMAX 0.5f
#define LMIN 0x1p-104f
#define USE_SPARE 1
#define MAXG 2
#define SPLIT 10
#define ESPLIT 3
#define PV1 8
#define RW 2
#define HW 2
#define HW2 1
#define XDELAY 200
#define QDELAY 300
#define TMPF 1
#define PFD0 2000
#define PFD1 400
#define HSENT 1
#define HDELAY 500
#define RCM 16
#define RPE 2
#define OSPLIT 6
#define HOLD 1
#define STAGE 11
#define POFF 102.f
#define WF0 3
#define WF1 16
#define C3D 0
#define C4D 300
#define DD 300
#define P2E 0
#define BO 0
#define MAP 2
#define CFULL 0
#define WFE 1
#define OUTD 0
#define OUTPOL EVICT_FIRST
#define SO 0
#define WF2 22
#define OUTP 0
constexpr int PF_KV = 8, PF_WO = 120;

__device__ __forceinline__ int cluster_role() {
    int k = blockIdx.x >> 1;
    if (MAP == 0) return k & 63;
    if (MAP == 1) return (k & 7) * 8 + ((k >> 3) & 7);
    if (MAP == 3) {
        asm("mov.u32 %0, %%smid;" : "=r"(k));
        k >>= 1;
        const int r = ((k - 32) * 37) >> 8;
        return k < 32 ? (k & 7) * 8 + (k >> 3) : k < 60 ? (k - 31 - r * 7) * 8 + 4 + r : (k - 58) & 7;
    }
    const int r = ((k - 36) * 37) >> 8, i = k - 36 - r * 7;
    if (MAP == 4) return k < 4 ? 4 + k : k < 36 ? ((k - 4) & 7) * 8 + ((k - 4) >> 3) : (i + 1) * 8 + ((4 + r) & 7);
    return k < 4 ? 12 + k : k < 36 ? ((k - 4) & 7) * 8 + ((k - 4) >> 3) : (i + (i > 0)) * 8 + ((4 + r) & 7);
}

struct Args {
    const bf16 *w_mod, *cvec;
    Scratch* gs;
    bf16* out;
    const bf16 *x, *kc, *vc, *wq, *wo, *w_r, *w_down;
};

__device__ __forceinline__ void frag_store(uint8_t* p, const uint32_t (&a)[32]) {
#pragma unroll
    for (int i = 0; i < 8; i++)
        __stcg(reinterpret_cast<uint4*>(p + i * 512), make_uint4(a[4 * i], a[4 * i + 1], a[4 * i + 2], a[4 * i + 3]));
}
__device__ __forceinline__ void frag_load(uint32_t (&a)[32], const uint8_t* p) {
#pragma unroll
    for (int i = 0; i < 8; i++) {
        const uint4 v = __ldcg(reinterpret_cast<const uint4*>(p + i * 512));
        a[4 * i] = v.x; a[4 * i + 1] = v.y; a[4 * i + 2] = v.z; a[4 * i + 3] = v.w;
    }
}
__device__ __forceinline__ float quad_sum(float v) {
    v += __shfl_xor_sync(0xffffffffu, v, 1);
    return v + __shfl_xor_sync(0xffffffffu, v, 2);
}
__device__ __forceinline__ float quad_max(float v) {
    v = fmaxf(v, __shfl_xor_sync(0xffffffffu, v, 1));
    return fmaxf(v, __shfl_xor_sync(0xffffffffu, v, 2));
}
__device__ __forceinline__ float rcp_fast(float x) { float y; asm("rcp.approx.ftz.f32 %0, %1;" : "=f"(y) : "f"(x)); return y; }
__device__ __forceinline__ float sigmoidf_(float x) { return rcp_fast(1.f + ex2(-1.4426950408889634f * x)); }
__device__ __forceinline__ void top2(uint32_t k, uint32_t& k1, uint32_t& k2) {
    k1 = __reduce_max_sync(0xffffffffu, k);
    k2 = __reduce_max_sync(0xffffffffu, k == k1 ? 0 : k);
}

__device__ __forceinline__ void mod_fma(float (&a)[8], const uint4 w, float sc) {
    a[0] += sc * bf_lo(w.x); a[1] += sc * bf_hi(w.x); a[2] += sc * bf_lo(w.y); a[3] += sc * bf_hi(w.y);
    a[4] += sc * bf_lo(w.z); a[5] += sc * bf_hi(w.z); a[6] += sc * bf_lo(w.w); a[7] += sc * bf_hi(w.w);
}
__device__ __forceinline__ float mod_reduce(float (&a)[8], int lane) {
#pragma unroll
    for (int h = 4; h > 0; h >>= 1) {
        const bool up = lane & (8 / h);
#pragma unroll
        for (int i = 0; i < h; i++)
            a[i] = (up ? a[i + h] : a[i]) + __shfl_xor_sync(0xffffffffu, up ? a[i] : a[i + h], 8 / h);
    }
    return a[0] + __shfl_xor_sync(0xffffffffu, a[0], 16);
}

__device__ __forceinline__ float ln_stats(float sum, float sq, uint32_t& mean2) {
    const float mean = sum * (1.f / D_);
    const float var = fmaxf(fmaf(-mean, mean, sq * (1.f / D_)), 0.f);
    float sd;
    asm("sqrt.approx.ftz.f32 %0, %1;" : "=f"(sd) : "f"(rbf(rbf(var) + 1e-5f)));
    mean2 = pack_bf16(mean, mean);
    return rcp_fast(rbf(sd));
}
__device__ __forceinline__ uint32_t ln_pair(uint32_t x, uint32_t mean2, float rsd) {
    const uint32_t d = bsub2(x, mean2);
    return pack_bf16(bf_lo(d) * rsd, bf_hi(d) * rsd);
}
__device__ __forceinline__ void rows_load(uint32_t (&x)[20], uint32_t xs, int cw) {
#pragma unroll
    for (int ch = 0; ch < 5; ch++) {
        const uint4 v = ldsm4(ch < 4 ? xs + ch * 256 : xs + 1024 - cw * 16);
        x[4 * ch] = v.x; x[4 * ch + 1] = v.y; x[4 * ch + 2] = v.z; x[4 * ch + 3] = v.w;
    }
}
__device__ __forceinline__ void stats_add(float (&st)[12], uint32_t a, uint32_t b, uint32_t w) {
    mma1688(st, a, b, w);
    mma1688(st + 4, a, b, a);
    mma1688(st + 8, a, b, b);
}
__device__ __forceinline__ float rows_stats(const float (&st)[12], float4* rec, int cw, int lane, uint32_t& mean2, float& dot) {
    const int g8 = lane >> 2;
    if ((g8 >> 1) == (lane & 3)) {
        rec[cw * 16 + g8] = make_float4(st[0], (g8 & 1) ? st[5] : st[4], st[1], 0.f);
        rec[cw * 16 + 8 + g8] = make_float4(st[2], (g8 & 1) ? st[11] : st[10], st[3], 0.f);
    }
    bar_sync(3, 256);
    const float4* r = rec + (lane >> 4) * 64 + (lane & 15);
    const float4 s0 = r[0], s1 = r[16], s2 = r[32], s3 = r[48];
    const float sum = (s0.x + s1.x) + (s2.x + s3.x), sq = (s0.y + s1.y) + (s2.y + s3.y);
    dot = (s0.z + s1.z) + (s2.z + s3.z);
    dot += __shfl_xor_sync(0xffffffffu, dot, 16);
    return ln_stats(sum + __shfl_xor_sync(0xffffffffu, sum, 16), sq + __shfl_xor_sync(0xffffffffu, sq, 16), mean2);
}
template <class F>
__device__ __forceinline__ void rows_normalise(uint32_t* y, const uint32_t* x, uint32_t mean2, float rsd, int lane, F loads) {
    const int g8 = lane >> 2;
    const uint32_t ma2 = __shfl_sync(0xffffffffu, mean2, g8), mb2 = __shfl_sync(0xffffffffu, mean2, g8 + 8);
    const float ra = __shfl_sync(0xffffffffu, rsd, g8), rb = __shfl_sync(0xffffffffu, rsd, g8 + 8);
    loads();
#pragma unroll
    for (int k = 0; k < 9; k++) { y[2 * k] = ln_pair(x[2 * k], ma2, ra); y[2 * k + 1] = ln_pair(x[2 * k + 1], mb2, rb); }
}
__device__ __forceinline__ uint32_t pair_of(const uint2* mp, int k, int cw) {
    return (k < 8 ? mp[(k >> 1) * 64 + (k & 1) * 4] : (mp - cw * 4)[256]).x;
}

__device__ __forceinline__ uint4 h_frag(const uint4* hf, int ks, int lane) {
    if (ks < 32) return ld_relaxed2(hf + ks * 32);
    const uint2* p = reinterpret_cast<const uint2*>(padd(hf, 256 - lane * 8) + ks * 32 - 16);
    const uint2 a = ld_relaxed64(p), b = ld_relaxed64(p + 32);
    return make_uint4(a.x, a.y, b.x, b.y);
}

__device__ __noinline__ void attn_fallback(uint32_t bad, uint32_t tag, const Scratch* gs, uint8_t* frag, uint8_t* keep, const bf16* wq, const bf16* kc, const bf16* vc) {
  const int lane = threadIdx.x & 31, g8 = lane >> 2, qd = lane & 3;
  const int j = cluster_role() & 7, qb = (cluster_role() >> 3) * 2 + (blockIdx.x & 1);
  const uint4* hf = g_h + (size_t)(qb * 8 + (threadIdx.x >> 5) - 4) * (36 * 32) + lane;
#pragma unroll 1
  for (int t = 0; t < 4; t++) {
    if (!((bad >> t) & 1)) continue;
    const bf16 *wqp = wq + (4 * j + t) * DH, *kp = kc + (size_t)(2 * j + (t >> 1)) * S_ * DH, *vp = vc + (size_t)(2 * j + (t >> 1)) * S_ * DH;
    uint32_t q[32];
    float o[64];
#pragma unroll
    for (int i = 0; i < 64; i++) o[i] = 0.f;
#pragma unroll 1
    for (int ks = 0; ks < 36; ks++) {
        const uint4 a = h_frag(hf, ks, lane);
        const unsigned short* wr = reinterpret_cast<const unsigned short*>(wqp + (size_t)(ks * 16 + 2 * qd) * QD + g8);
#pragma unroll
        for (int dt = 0; dt < 16; dt++) {
            const uint32_t b0 = __ldg(wr + dt * 8) | ((uint32_t)__ldg(wr + dt * 8 + QD) << 16);
            const uint32_t b1 = __ldg(wr + dt * 8 + 8 * QD) | ((uint32_t)__ldg(wr + dt * 8 + 9 * QD) << 16);
            mma16816(o + 4 * dt, a.x, a.y, a.z, a.w, b0, b1);
        }
    }
#pragma unroll
    for (int i = 0; i < 32; i++) q[i] = pack_bf16(o[2 * i], o[2 * i + 1]);
#pragma unroll
    for (int i = 0; i < 64; i++) o[i] = 0.f;
    float m0 = -INFINITY, m1 = -INFINITY, l0 = 0.f, l1 = 0.f;
#pragma unroll 1
    for (int key = 0; key < S_; key += 16) {
        float sc[8];
#pragma unroll
        for (int i = 0; i < 8; i++) sc[i] = 0.f;
#pragma unroll
        for (int nt = 0; nt < 2; nt++) {
            const uint32_t* kr = reinterpret_cast<const uint32_t*>(kp + (size_t)(key + nt * 8 + g8) * DH) + qd;
#pragma unroll
            for (int ks = 0; ks < 8; ks++)
                mma16816(sc + 4 * nt, q[4 * ks], q[4 * ks + 1], q[4 * ks + 2], q[4 * ks + 3], __ldg(kr + ks * 8), __ldg(kr + ks * 8 + 4));
        }
        const float n0 = quad_max(fmaxf(fmaxf(m0, fmaxf(sc[0], sc[1])), fmaxf(sc[4], sc[5])));
        const float n1 = quad_max(fmaxf(fmaxf(m1, fmaxf(sc[2], sc[3])), fmaxf(sc[6], sc[7])));
        const float f0 = ex2((m0 - n0) * CS), f1 = ex2((m1 - n1) * CS);
        m0 = n0; m1 = n1;
#pragma unroll
        for (int i = 0; i < 8; i++) sc[i] = ex2((sc[i] - ((i & 2) ? n1 : n0)) * CS);
        l0 = l0 * f0 + (sc[0] + sc[1]) + (sc[4] + sc[5]);
        l1 = l1 * f1 + (sc[2] + sc[3]) + (sc[6] + sc[7]);
        const uint32_t e0 = pack_bf16(sc[0], sc[1]), e1 = pack_bf16(sc[2], sc[3]), e2 = pack_bf16(sc[4], sc[5]), e3 = pack_bf16(sc[6], sc[7]);
        const unsigned short* vr = reinterpret_cast<const unsigned short*>(vp + (size_t)(key + 2 * qd) * DH + g8);
#pragma unroll
        for (int dt = 0; dt < 16; dt++) {
            o[4 * dt] *= f0; o[4 * dt + 1] *= f0; o[4 * dt + 2] *= f1; o[4 * dt + 3] *= f1;
            const uint32_t b0 = __ldg(vr + dt * 8) | ((uint32_t)__ldg(vr + dt * 8 + DH) << 16);
            const uint32_t b1 = __ldg(vr + dt * 8 + 8 * DH) | ((uint32_t)__ldg(vr + dt * 8 + 9 * DH) << 16);
            mma16816(o + 4 * dt, e0, e1, e2, e3, b0, b1);
        }
    }
    const float i0 = 1.f / quad_sum(l0), i1 = 1.f / quad_sum(l1);
#pragma unroll
    for (int i = 0; i < 16; i++) {
        q[2 * i] = pack_bf16(o[4 * i] * i0, o[4 * i + 1] * i0);
        q[2 * i + 1] = pack_bf16(o[4 * i + 2] * i1, o[4 * i + 3] * i1);
    }
    frag_store(t < 3 ? frag + t * 4096 : keep, q);
  }
}

__device__ __forceinline__ void spare_q3(Scratch* gs, uint32_t sb, uint32_t bar_full, uint32_t bar_empty, int lane, int cw) {
    const uint32_t tag = load_tag(gs);
    uint32_t rel_base, e = 3;
    asm("mapa.shared::cluster.u32 %0, %1, %2;" : "=r"(rel_base) : "r"(bar_empty), "r"(lane & 1));
#pragma unroll 1
    for (int qb = blockIdx.x - NCTA; qb < 16; qb += 4) {
        uint32_t h[144];
        float o[64];
        flag_wait(&g_flag_h[(qb * 8 + cw) * 32], tag);
        const uint4* hf = g_h + (size_t)(qb * 8 + cw) * (36 * 32) + lane;
#pragma unroll
        for (int ks = 0; ks < 36; ks++) {
            const uint4 v = h_frag(hf, ks, lane);
            h[4 * ks] = v.x; h[4 * ks + 1] = v.y; h[4 * ks + 2] = v.z; h[4 * ks + 3] = v.w;
        }
#pragma unroll
        for (int i = 0; i < 64; i++) o[i] = 0.f;
#pragma unroll 1
        for (int v = 0; v < 4; v++) {
            fence_regs(o);
#pragma unroll
            for (int t = 0; t < 5; t++) {
                mbar_wait(bar_full + 8 * (e & 3), (e >> 2) & 1);
                const uint64_t dv = mkdesc(sb + (e & 3) * SLOT, UNIT, 1024);
                WG_FENCE();
#pragma unroll
                for (int ks = 0; ks < (t < 4 ? 8 : 4); ks++)
                    mma_rs128<1>(o, h[32 * t + 4 * ks], h[32 * t + 4 * ks + 1], h[32 * t + 4 * ks + 2], h[32 * t + 4 * ks + 3], dv + ks * 128, ks | t);
                WG_COMMIT();
                if (t > 0) { WG_WAIT(1); if (lane < 2) mbar_arrive_cluster(rel_base + 8 * ((e - 1) & 3)); }
                e++;
            }
            WG_WAIT(0);
            fence_regs(o);
            if (lane < 2) mbar_arrive_cluster(rel_base + 8 * ((e - 1) & 3));
            uint4* dst = &g_q3[((qb * 8 + 2 * v) * 8 + cw) * 128 + lane];
#pragma unroll
            for (int i = 0; i < 8; i++)
                __stcg(dst + (i >> 2) * 1024 + (i & 3) * 32, make_uint4(pack_bf16(o[8 * i], o[8 * i + 1]), pack_bf16(o[8 * i + 2], o[8 * i + 3]),
                                                                        pack_bf16(o[8 * i + 4], o[8 * i + 5]), pack_bf16(o[8 * i + 6], o[8 * i + 7])));
        }
        bar_sync(3, 256);
        if (cw == 0 && lane == 0) flag_release(&g_flag_q3[qb * 32], tag);
        __syncwarp();
    }
}

template <bool SPARE>
__global__ void __cluster_dims__(2, 1, 1) __launch_bounds__(384, 1)
fused_kernel(const Args args, const __grid_constant__ CUtensorMap tm_wq,
             const __grid_constant__ CUtensorMap tm_k, const __grid_constant__ CUtensorMap tm_v,
             const __grid_constant__ CUtensorMap tm_wo, const __grid_constant__ CUtensorMap tm_p,
             const __grid_constant__ CUtensorMap tm_x, const __grid_constant__ CUtensorMap tm_d,
             const __grid_constant__ CUtensorMap tm_g, const __grid_constant__ CUtensorMap tm_u) {
    extern __shared__ __align__(1024) uint8_t smem_raw[];
    const uint32_t sb = smem_u32(smem_raw);
    Scratch* const gs = args.gs;
    const uint32_t bar_full = sb + SM_BAR;
    const uint32_t bar_g = bar_full + 8 * 4;
    const uint32_t bar_mod = bar_g + 8;
    const uint32_t bar_go = bar_mod + 8;
    const uint32_t bar_x = bar_go + 40;
    const uint32_t bar_empty = bar_x + 8;
    const uint32_t bar_pub = bar_empty + 8 * 4;
    const uint32_t bar_qfree = bar_pub + 32;
    const uint32_t bar_out = bar_qfree + 24;
    const uint32_t bar_q3 = bar_out + 8;
    const uint32_t bar_pre = bar_q3 + 16;
    const uint32_t bar_w0 = bar_q3 + 8;
    constexpr int E0 = SPARE ? 2 : 0;

    const int c = blockIdx.x & 1;
    const int role = cluster_role();
    const int j = role & 7;
    const int qb = (role >> 3) * 2 + c;
    const int rg = qb * 8 + j;
    const int warp = __shfl_sync(0xffffffffu, threadIdx.x >> 5, 0);

    if (SPARE && blockIdx.x >= NCTA && warp >= 4) {
        asm volatile("barrier.cluster.arrive.relaxed.aligned;" ::: "memory");
        asm volatile("setmaxnreg.inc.sync.aligned.u32 240;");
        asm volatile("barrier.cluster.wait.aligned;" ::: "memory");
        spare_q3(gs, sb, bar_full, bar_empty, threadIdx.x & 31, warp - 4);
        asm volatile("barrier.cluster.arrive.relaxed.aligned;\nbarrier.cluster.wait.aligned;" ::: "memory");
    } else if (warp < 4) {
        asm volatile("setmaxnreg.dec.sync.aligned.u32 24;");
        int lane;
        asm volatile("mov.u32 %0, %%laneid;" : "=r"(lane));
        if (warp == 2 && elect()) {
            if (TMPF) asm volatile("prefetch.tensormap [%0];" ::"l"(&tm_x) : "memory");
#pragma unroll
            for (int i = 0; i < 27; i++) mbar_init(bar_full + 8 * i, i < 12 || i >= 23 ? 1 : i < 16 ? 16 : 8);
#pragma unroll
            for (int i = 0; i <= E0; i++) {
                mbar_arrive(bar_full + 8 * i);
                asm volatile("mbarrier.arrive.shared::cta.b64 _, [%0], 16;" ::"r"(bar_empty + 8 * i) : "memory");
            }
            asm volatile("fence.mbarrier_init.release.cluster;" ::: "memory");
        }
        __syncwarp();
        asm volatile("barrier.cluster.arrive.relaxed.aligned;" ::: "memory");
        if (warp == 2 && !(SPARE && blockIdx.x >= NCTA)) {
            if (XDELAY) __nanosleep(XDELAY);
            if (elect()) {
                mbar_expect_tx(bar_x, 16 * XP);
                tma2d(sb + SM_Q, &tm_x, 0, rg * 16, bar_x);
            }
            __syncwarp();
        }
        asm volatile("barrier.cluster.wait.aligned;" ::: "memory");
        const uint32_t tag = load_tag(gs);
        if (SPARE && blockIdx.x >= NCTA) {
            if (warp == 1) {
#pragma unroll 1
                for (int e = 3; e < 83; e++) {
                    const int v = (e - 3) / 5;
                    mbar_wait_sleep(bar_empty + 8 * (e & 3), ~(e >> 2) & 1);
                    if (elect()) {
                        mbar_expect_tx(bar_full + 8 * (e & 3), SLOT);
                        tma2d_mc(sb + (e & 3) * SLOT + c * UNIT, &tm_wq, (8 * (v & 3) + 4 * c + 3) * DH + 64, (e - 3 - v * 5) * 128,
                                 bar_full + 8 * (e & 3), EVICT_NORMAL);
                    }
                }
            }
            __syncwarp();
            asm volatile("barrier.cluster.arrive.relaxed.aligned;\nbarrier.cluster.wait.aligned;" ::: "memory");
            return;
        }
        if (warp == 3) {
#pragma unroll 1
            for (int e = 4; e < 20; e++) {
                __nanosleep(e == 4 ? PFD0 : PFD1);
                const int hd = (e * 52) >> 8, row = (e - hd * 5) * 128 + qb * 8 + (lane >> 1);
                if (lane < 16 && row < D_)
                    asm volatile("prefetch.global.L2 [%0];" ::"l"(padd(args.wq, (row * QD + (4 * j + ((0x1320 >> (4 * hd)) & 3)) * DH + (lane & 1) * 64) * 2)) : "memory");
            }
            __syncwarp();
            mbar_wait_sleep(bar_go, 0);
#pragma unroll 1
            for (int unit = 72 + blockIdx.x; unit < 216; unit += NCTA) {
                float a[8];
#pragma unroll
                for (int i = 0; i < 8; i++) a[i] = 0.f;
#pragma unroll 1
                for (int k = lane >> 1; k < D_; k += 16) {
                    const float cv = __bfloat162float(*padd(args.cvec, k * 2));
                    mod_fma(a, __ldg(reinterpret_cast<const uint4*>(padd(args.w_mod, (k * (6 * D_) + unit * 16 + (lane & 1) * 8) * 2))), rbf(cv * sigmoidf_(cv)));
                }
                const float v = mod_reduce(a, lane), v1 = __shfl_down_sync(0xffffffffu, v, 8);
                if (lane < 8) *padd(gs->mod2, ((unit - 72) * 8 + (lane & 1) * 4 + (lane & 2) + (lane >> 2)) * 4) = pack_bf16(v, v1);
            }
            __syncwarp();
            if (lane == 0) flag_release(padd(g_flag_mod, blockIdx.x * 4), tag);
#pragma unroll 1
            for (int k = 0; k < 36 * HSENT; k++) {
                __nanosleep(200);
                __stcg(padd(gs->h[0], (~tag & 1) * (NCTA * 36 * 512) + ((rg * 36 + k) * 32 + lane) * 16), make_uint4(0, 0, 0, 0));
            }
            __syncwarp();
            mbar_wait_sleep(bar_qfree + 16, 0);
            __nanosleep(2000);
            {
                uint4 v;
                uint32_t it = 0;
#pragma unroll 1
                do {
                    v = ld_relaxed(reinterpret_cast<const uint4*>(padd(g_flag_mod, lane * 16)));
                } while (((v.x ^ tag) | (v.y ^ tag) | (v.z ^ tag) | (v.w ^ tag)) && ++it < SPIN / 16);
                asm volatile("fence.acquire.gpu;" ::: "memory");
            }
            __syncwarp();
            {
                float w1 = 0.f, w2 = 0.f;
#pragma unroll 1
                for (int k = lane; k < D_ / 2; k += 32) {
                    const uint32_t* mp = padd(gs->mod2, k * 4);
                    const uint32_t sv = __ldcg(mp + D_ / 2), c1 = badd2(__ldcg(mp + D_), 0x3f803f80u);
                    const uint32_t wr = *reinterpret_cast<const uint32_t*>(padd(args.w_r, k * 4)), wp = bmul2(c1, wr);
                    reinterpret_cast<uint2*>(smem_raw + SM_T)[k] = make_uint2(__ldcg(mp), wp);
                    reinterpret_cast<uint2*>(smem_raw + SM_TC)[k] = make_uint2(c1, sv);
                    reinterpret_cast<uint32_t*>(smem_raw + SM_TG)[k] = __ldcg(mp + 3 * D_ / 2);
                    w1 += bf_lo(wp) + bf_hi(wp);
                    w2 += bf_lo(sv) * bf_lo(wr) + bf_hi(sv) * bf_hi(wr);
                }
#pragma unroll 1
                for (int i = 1; i < 32; i <<= 1) { w1 += __shfl_xor_sync(0xffffffffu, w1, i); w2 += __shfl_xor_sync(0xffffffffu, w2, i); }
                *reinterpret_cast<float2*>(smem_raw + SM_TS) = make_float2(w1, w2);
            }
#pragma unroll
            for (int i = 0; i < 4; i++) reinterpret_cast<uint4*>(smem_raw + SM_RED)[lane + 32 * i] = make_uint4(~0u, ~0u, ~0u, ~0u);
            asm volatile("fence.proxy.async.shared::cta;" ::: "memory");
            __syncwarp();
            if (elect()) {
                uint8_t* mb = g_frag + (size_t)rg * 8 * WREG + 3 * 4096;
#pragma unroll 1
                for (int k = 0; k < 8; k++, mb += WREG) {
#pragma unroll
                    for (int i = 0; i < 3; i++)
                        asm volatile("cp.async.bulk.global.shared::cta.bulk_group [%0], [%1], 2048;" ::"l"(mb + i * 2048), "r"(sb + SM_RED) : "memory");
                    __nanosleep(500);
                }
                asm volatile("cp.async.bulk.commit_group;\ncp.async.bulk.wait_group 0;\nfence.proxy.async.global;" ::: "memory");
            }
            __syncwarp();
            if (lane == 0) mbar_arrive(bar_mod);
            __syncwarp();
            mbar_wait_sleep(bar_go + 8, 0);
            if (lane < 3) asm volatile("prefetch.tensormap [%0];" ::"l"(lane == 0 ? &tm_x : lane == 1 ? &tm_p : &tm_d) : "memory");
            __syncwarp();
#pragma unroll 1
            for (int i = 1; i < 4; i++) {
                mbar_wait(bar_pub + 8 * i, 0);
                unsigned int* flags = padd(g_flag_part, (qb * 32 + i * 8 - 8) * 4);
                if (elect()) { flag_release(padd(flags, j * 4), tag); DBG_PG(93); }
                __syncwarp();
                const uint32_t slot = i < 3 ? i + 1 : 1;
                flag_wait(padd(flags, (lane & 7) * 4), tag);
                asm volatile("fence.proxy.async.global;" ::: "memory");
                if (lane == 0 && i == 3) DBG_PG(101);
                mbar_wait(bar_go + 8 + 8 * i, 0);
                mbar_wait(bar_empty + 8 * slot, i != 1);
                if (elect()) {
                    mbar_expect_tx(bar_full + 8 * slot, SLOT);
                    tma3d(sb + slot * SLOT, &tm_p, 0, j * 20 + (i - 1) * 4, qb * 8, bar_full + 8 * slot);
                    tma3d(sb + slot * SLOT + UNIT, &tm_p, 0, j * 20 + (i - 1) * 4 + 2, qb * 8, bar_full + 8 * slot);
                }
            }
        } else if (warp == 0) {
#pragma unroll 1
            for (int i = 0; i < 48; i++) {
                if (i == 0 || i == 17 || i == 34) mbar_wait_sleep(bar_qfree + (i >> 4) * 8, 0);
                if (SPARE && i == 17) {
                    flag_wait(&g_flag_q3[qb * 32], tag);
                    if (elect()) {
                        asm volatile("fence.proxy.async.global;" ::: "memory");
                        mbar_expect_tx(bar_q3, UNIT);
#pragma unroll 1
                        for (int k = 0; k < 8; k++) bulk_load(sb + SM_Q + 2 * SLOT + k * 4096 + 2048, &g_q3[(rg * 8 + k) * 128], 2048, bar_q3);
                    }
                }
                __nanosleep(700);
                if (elect()) {
                    asm volatile("mbarrier.expect_tx.shared::cta.b64 [%0], %1;" ::"r"(bar_g), "n"(1920) : "memory");
                    tma2d(sb + SM_Q + i * 1920, i < 24 ? &tm_g : &tm_u, (blockIdx.x * 36) & ~7, (i < 24 ? i : i - 24) * 24, bar_g);
                }
            }
            if (elect()) mbar_arrive(bar_g);
#pragma unroll 1
            for (int i = 0; i < 18; i++) {
                __nanosleep(400);
                if (elect()) l2_prefetch(args.w_down + (size_t)(blockIdx.x * 36 + i * 2) * D_, 4 * D_);
            }
            __syncwarp();
            mbar_wait_sleep(bar_go + 8 * 2, 0);
            uint32_t acc = 0;
#pragma unroll 1
            for (int k = lane; k < 16 * 9; k += 32) acc |= touch(padd(args.x, (rg * 16 * D_ + k * 64) * 2));
            if (acc == 0) reinterpret_cast<volatile uint32_t*>(smem_raw + SM_BAR)[127] = acc;
            __syncwarp();
            mbar_wait_sleep(bar_go + 8 * 4, 0);
            uint4* rp = padd(g_rows, (rg * 2 * RSLOT + lane) * 16);
#pragma unroll
            for (int k = 0; k < 9; k++) rp[k * 32] = make_uint4(~0u, ~0u, ~0u, ~0u);
            if (blockIdx.x < 72) {
                uint4* yp = reinterpret_cast<uint4*>(padd(g_ypart, blockIdx.x * NCTA * 64 + lane * 16));
#pragma unroll
                for (int k = 0; k < 16; k++) yp[k * 32] = make_uint4(~0u, ~0u, ~0u, ~0u);
            }
            asm volatile("fence.acq_rel.gpu;" ::: "memory");
            __syncwarp();
            if (lane == 0) mbar_arrive(bar_pre);
        } else if (warp == 1) {
            __nanosleep(QDELAY);
            uint32_t go = bar_go;
            uint64_t marks = 24 | 151 << 8 | 154 << 16 | 159ull << 24 | 165ull << 32;
#pragma unroll 1
            for (int e = E0; e < 168; e++) {
                const CUtensorMap* tm;
                int c0, c1;
                uint64_t pol = EVICT_FIRST;
                if (e == 158 || e == 163) continue;
                if (e < 21 && e != 19) {
                    const int i = SPARE && e < 12 ? e - 2 : e - (e == 20), hd = (i * 52) >> 8;
                    tm = &tm_wq; c0 = (4 * j + ((0x1320 >> (4 * hd)) & 3)) * DH + c * 64; c1 = (i - hd * 5) * 128 - 64;
                    if (SPARE && e >= 12 && e < 15) { c0 = (4 * j + 3) * DH; c1 = (2 * (e - 12) + c) * 128; }
                } else if (e < 148) {
                    const int i = max(e - 20, 0);
                    const bool isk = i == 0 || ((i & 1) && i < 127);
                    const int n = isk ? (i + 1) >> 1 : (i - 1) >> 1;
                    tm = isk ? &tm_k : &tm_v; c0 = c * 64; c1 = (2 * j + (n >> 5)) * S_ + (n & 15) * 128;
                    if (!(i & 32)) pol = EVICT_NORMAL;
                } else {
                    int i = e - 148 - (e > 158) - (e > 163);
                    tm = &tm_wo; c0 = (i >> 1) * 64; c1 = (4 * j + ((i & 1) ? 1 + c : 3 * c)) * DH;
                }
                const uint32_t fb = e == E0 ? bar_w0 : bar_full + 8 * (e & 3), d = sb + (e == E0 ? 6 : e & 3) * SLOT;
                if (e >= 24 && e < 152) mbar_wait_sleep(bar_empty + 8 * (e & 3), ~(e >> 2) & 1);
                else if (e != E0) mbar_wait(bar_empty + 8 * (e & 3), ~(e >> 2) & 1);
                if (elect()) {
                    mbar_expect_tx(fb, SLOT);
                    tma2d_mc(d + c * UNIT, tm, c0, c1, fb, pol);
                    const int i = e - PF_KV;
                    if (i >= 0 && i < 128 && !(i & 32))
                        l2_prefetch(((i & 1) ? args.vc : args.kc) + (size_t)((2 * j + (i >> 6)) * S_ + (i & 30) * 64) * DH + qb * 1024, 2048);
                    if (e >= PF_WO && e < PF_WO + 18) l2_prefetch(args.wo + (size_t)blockIdx.x * (QD * D_ / NCTA) + (e - PF_WO) * 1024, 2048);
                    if (e == (marks & 255)) mbar_arrive(go);
                }
                if (e == (marks & 255)) { go += 8; marks >>= 8; }
            }
            asm volatile("fence.proxy.async.global;" ::: "memory");
            mbar_wait(bar_empty, 1);
            if (elect()) {
                mbar_expect_tx(bar_full, 16 * XP);
                tma2d(sb, &tm_x, 0, rg * 16, bar_full);
            }
            mbar_wait(bar_empty + 16, 1);
            if (C3D) __nanosleep(C3D);
            if (elect()) {
                mbar_expect_tx(bar_full + 16, SLOT);
                tma3d(sb + 2 * SLOT, &tm_p, 0, j * 20 + 12, qb * 8, bar_full + 16);
                tma3d(sb + 2 * SLOT + UNIT, &tm_p, 0, j * 20 + 14, qb * 8, bar_full + 16);
            }
            mbar_wait(bar_empty + 24, 1);
            if (C4D) __nanosleep(C4D);
            if (elect()) {
                mbar_expect_tx(bar_full + 24, UNIT);
                tma3d(sb + 3 * SLOT, &tm_p, 0, j * 20 + 16, qb * 8, bar_full + 24);
            }
            mbar_wait(bar_empty + 8, 0);
            mbar_wait(bar_empty + 16, 0);
            if (DD) __nanosleep(DD);
            if (elect()) {
#pragma unroll
                for (int i = 1; i < 3; i++) {
                    mbar_expect_tx(bar_full + 8 * i, 18 * XP);
                    tma2d(sb + i * SLOT, &tm_d, 0, blockIdx.x * 36 + (i - 1) * 18, bar_full + 8 * i);
                }
            }
        } else {
            if (lane < 3) asm volatile("prefetch.tensormap [%0];" ::"l"(lane == 0 ? &tm_k : lane == 1 ? &tm_v : &tm_wo) : "memory");
            if (SPARE && HSENT) {
                mbar_wait_sleep(bar_pub, 0);
                if (lane == 0) flag_release(padd(g_flag_h, rg * 128), tag);
                __syncwarp();
            }
            bar_sync(1, 192);
#pragma unroll 1
            for (uint32_t e = 20; e < 148; e++) {
                mbar_wait_sleep(bar_full + 8 * (e & 3), (e >> 2) & 1);
                if (e & 1) bar_sync(1, 192);
                if (!(e & 1) || e == 147) bar_sync(4, 160);
            }
#pragma unroll 1
            for (uint32_t e = 148; e < 168; e++) {
                mbar_wait(bar_full + 8 * (e & 3), (e >> 2) & 1);
                if (e != 158 && e != 163) bar_sync(1, 192);
            }
        }
        __syncwarp();
        mbar_wait_sleep(bar_out, 0);
        if (OUTD) __nanosleep(OUTD);
        if (elect()) {
            asm volatile("fence.proxy.async.shared::cta;" ::: "memory");
            const int2 sel = reinterpret_cast<const int2*>(smem_raw + SM_RED)[8];
#pragma unroll 1
            for (int i = warp; i < 16; i += 4) {
                const int row = rg * 16 + i;
                if (row != sel.x && row != sel.y)
                    asm volatile("cp.async.bulk.global.shared::cta.bulk_group.L2::cache_hint [%0], [%1], %2, %3;"
                                 ::"l"(args.out + (size_t)row * D_), "r"(sb + i * XP), "n"(D_ * 2), "l"(OUTPOL) : "memory");
            }
            asm volatile("cp.async.bulk.commit_group;\ncp.async.bulk.wait_group 0;" ::: "memory");
        }
    } else {
        uint32_t cv[5] = {0, 0, 0, 0, 0}, tag0 = 0;
        if (blockIdx.x < 72) {
            uint32_t ws;
            int tid;
            asm volatile("mov.u32 %0, smem_raw;\nmov.u32 %1, %%tid.x;" : "=r"(ws), "=r"(tid));
            tid -= 128;
            ws += SM_Q + SLOT + tid * 16;
            const bf16* wrow = args.w_mod + (size_t)(tid >> 1) * (6 * D_) + (tid & 1) * 8 + blockIdx.x * 16;
#pragma unroll
            for (int i = 0; i < 5; i++)
                if (i < 4 || tid < 128) {
                    asm volatile("cp.async.cg.shared.global [%0], [%1], 16;" ::"r"(ws + i * 4096), "l"(wrow + (size_t)i * 128 * (6 * D_)) : "memory");
                    cv[i] = reinterpret_cast<const unsigned short*>(args.cvec)[(tid >> 1) + i * 128];
                }
            tag0 = load_tag(gs) - 1;
        }
        asm volatile("barrier.cluster.arrive.relaxed.aligned;" ::: "memory");
        asm volatile("setmaxnreg.inc.sync.aligned.u32 240;");
        const int lane = threadIdx.x & 31;
        const int cw = warp - 4;
        const int w = cw >> 2;
        const int tid = threadIdx.x - 128;
        float* red = reinterpret_cast<float*>(smem_raw + SM_RED);
        DBG_INIT();
        DBG_G(120);
        DBG_T(100);

        uint32_t tag;
        {

            if (blockIdx.x < 72) {
                const uint32_t ws = sb + SM_Q + SLOT + tid * 16;
                float sc[5], a[8];
#pragma unroll
                for (int i = 0; i < 5; i++) sc[i] = __uint_as_float(cv[i] << 16);
#pragma unroll
                for (int i = 0; i < 5; i++) sc[i] = rbf(sc[i] * sigmoidf_(sc[i]));
#pragma unroll
                for (int i = 0; i < 8; i++) a[i] = 0.f;
                anchor(bar_full + 504, sc[0] + sc[1] + sc[2] + sc[3] + sc[4] + 2.f);
                asm volatile("cp.async.wait_all;" ::: "memory");
#pragma unroll
                for (int i = 0; i < 5; i++) mod_fma(a, lds128(ws + (i < 4 || tid < 128 ? i * 4096 : 0)), sc[i]);
                const float v = mod_reduce(a, lane);
                if (lane < 16) red[cw * 16 + lane] = v;

                bar_sync(3, 256);
                if (tid < 8 * MREP) {
                    float v0 = 0.f, v1 = 0.f;
#pragma unroll
                    for (int i = 0; i < 8; i++) { v0 += red[i * 16 + (tid & 7)]; v1 += red[i * 16 + 8 + (tid & 7)]; }
                    st_relaxed64(&gs->mod1[(tid >> 3) * D_ + blockIdx.x * 8 + (tid & 1) * 4 + (tid & 2) + ((tid >> 2) & 1)], pack_bf16(v0, v1), tag0 + 1);
                }
            }
            DBG_G(106);
            asm volatile("barrier.cluster.wait.aligned;" ::: "memory");
            mbar_wait(bar_x, 0);
            tag = load_tag(gs);
            uint32_t x[20];
            float st[12];
            rows_load(x, sb + SM_Q + (lane & 15) * XP + (lane >> 4) * 16 + cw * 32, cw);
#pragma unroll
            for (int i = 0; i < 12; i++) st[i] = 0.f;
#pragma unroll
            for (int k = 0; k < 9; k++) stats_add(st, x[2 * k], x[2 * k + 1], 0x3f803f80u);
            uint32_t mean2;
            float dot;
            const float rsd = rows_stats(st, reinterpret_cast<float4*>(red + 128), cw, lane, mean2, dot);
            rows_normalise(x, x, mean2, rsd, lane, []() {});
            fence_regs(x);
            uint4* smod = reinterpret_cast<uint4*>(smem_raw + SM_Q + M_MOD);
            if (tid < D_ / 4) {
                const uint4* mp = reinterpret_cast<const uint4*>(gs->mod1 + ((blockIdx.x >> 1) & (MREP - 1)) * D_) + tid;
                poll2x2(mp, mp + D_ / 4, tag, smod[tid], smod[D_ / 4 + tid]);
            }
            bar_sync(3, 256);
            DBG_G(107);
            const uint2* mp = reinterpret_cast<const uint2*>(smod) + cw * 8 + (lane & 3);
#pragma unroll
            for (int k = 0; k < 9; k++) {
                const uint32_t c1 = badd2(pair_of(mp + D_ / 2, k, cw), 0x3f803f80u), sa = pair_of(mp, k, cw);
                x[2 * k] = badd2(bmul2(x[2 * k], c1), sa);
                if (x[2 * k] == 0) x[2 * k] = 0x8000u;
                x[2 * k + 1] = badd2(bmul2(x[2 * k + 1], c1), sa);
            }
            uint4* hdst = g_h + (size_t)(rg * 36 + cw) * 32 + lane;
#pragma unroll
            for (int ch = 0; ch < 4; ch++) st_relaxed(hdst + ch * 256, x[4 * ch], x[4 * ch + 1], x[4 * ch + 2], x[4 * ch + 3]);
            st_relaxed64(reinterpret_cast<uint2*>(g_h + (size_t)(rg * 36 + 32) * 32) + tid, x[16], x[17]);
            __syncwarp();
            if (SPARE && lane == 0) mbar_arrive(bar_pub);
            DBG_G(108);
        }

        uint32_t rel_base;
        asm("mapa.shared::cluster.u32 %0, %1, %2;" : "=r"(rel_base) : "r"(bar_empty), "r"(lane & 1));
        auto release = [&](uint32_t slot) { if (lane < 2) mbar_arrive_cluster(rel_base + 8 * slot); };
        uint32_t q[32], p[32];
        float s[64], o[64];

        uint4* qpark = reinterpret_cast<uint4*>(smem_raw + SM_Q - SLOT) + cw * 256 + lane;
        {
            uint32_t h[144];
            const uint4* hf = g_h + (size_t)(qb * 8 + cw) * (36 * 32) + lane;
            auto load_h = [&](auto lo, auto hi) {
#pragma unroll
                for (int ks = lo.value; ks < hi.value; ks++) {
                    const uint4 v = h_frag(hf, ks, lane);
                    h[4 * ks] = v.x; h[4 * ks + 1] = v.y; h[4 * ks + 2] = v.z; h[4 * ks + 3] = v.w;
                }
            };
            auto check_h = [&](auto lo, auto hi) {
                uint32_t it = 0;
#pragma unroll 1
                while (true) {
                    uint32_t mn = ~0u;
#pragma unroll
                    for (int ks = lo.value; ks < hi.value; ks++) mn = __vimin3_u32(mn, h[4 * ks], h[4 * ks + 2]);
                    if (!__any_sync(0xffffffffu, mn == 0) || ++it >= SPIN / 16) break;
                    load_h(lo, hi);
                }
            };
            if (!HSENT) flag_wait(&g_flag_h[(qb * 8 + cw) * 32], tag);
            if (HSENT) __nanosleep(HDELAY);
            load_h(IC<0>{}, IC<4>{});
            DBG_T(104); DBG_G(109);
#pragma unroll
            for (int i = 0; i < 64; i++) o[i] = 0.f;
            uint32_t e = E0;
#pragma unroll 1
            for (int hd = 1;; hd++) {
                fence_regs(o);
                auto group = [&](auto tc) {
                    constexpr int t = tc.value, k0 = t ? 8 * t - 4 : 0;
                    const bool first = t == 0 && hd == 1;
                    mbar_wait(first ? bar_w0 : bar_full + 8 * (e & 3), (e >> 2) & 1);
                    const uint32_t dv = desc_lo(t ? 0 : 8192, UNIT) + (first ? 6 : e & 3) * (SLOT / 16);
                    if (HSENT && hd == 1) check_h(IC<k0>{}, IC<8 * t + 4>{});
                    WG_FENCE();
#pragma unroll
                    for (int ks = k0; ks < 8 * t + 4; ks++)
                        mma_rs128<1>(o, h[4 * ks], h[4 * ks + 1], h[4 * ks + 2], h[4 * ks + 3], desc_of(dv + (ks - k0) * 128), ks);
                    WG_COMMIT();
                    if (hd == 1) { if (t == 0) {   } if (t == 1) {   } if (t == 2) {   } if (t == 3) {   } if (t == 4) {   } }
                    if (t < 4 && hd == 1) load_h(IC<8 * t + 4>{}, IC<t < 4 ? 8 * t + 12 : 0>{});
                    if (t > 0) { WG_WAIT(1); if (t > 1 || hd > 1) release((e - 1) & 3); }
                    e++;
                };
                group(IC<0>{}); group(IC<1>{}); group(IC<2>{}); group(IC<3>{});
                if (e == 19) break;
                group(IC<4>{});
                WG_WAIT(0);
                if (hd == 1) {     }
                fence_regs(o);
                release((e - 1) & 3);
#pragma unroll
                for (int i = 0; i < 8; i++)
                    qpark[hd * 2048 + i * 32] = make_uint4(pack_bf16(o[8 * i], o[8 * i + 1]), pack_bf16(o[8 * i + 2], o[8 * i + 3]),
                                                           pack_bf16(o[8 * i + 4], o[8 * i + 5]), pack_bf16(o[8 * i + 6], o[8 * i + 7]));
                if (SPARE && hd == 2) {
                    float (&u)[32] = reinterpret_cast<float (&)[32]>(o);
                    fence_regs(u);
#pragma unroll
                    for (int t = 0; t < 3; t++) {
                        mbar_wait(bar_full + 8 * t, 1);
                        WG_FENCE();
#pragma unroll
                        for (int ks = 0; ks < (t < 2 ? 16 : 4); ks++)
                            mma_rs64<1>(u, h[64 * t + 4 * ks], h[64 * t + 4 * ks + 1], h[64 * t + 4 * ks + 2], h[64 * t + 4 * ks + 3],
                                        desc_of(desc_lo(t * SLOT, UNIT) + ks * 128), ks | t);
                        WG_COMMIT();
                        if (t > 0) { WG_WAIT(1); release(t - 1); }
                    }
                    WG_WAIT(0);
                    fence_regs(u);
                    release(2);
                    e = 15;
#pragma unroll
                    for (int i = 0; i < 4; i++)
                        qpark[3 * 2048 + i * 32] = make_uint4(pack_bf16(u[8 * i], u[8 * i + 1]), pack_bf16(u[8 * i + 2], u[8 * i + 3]),
                                                              pack_bf16(u[8 * i + 4], u[8 * i + 5]), pack_bf16(u[8 * i + 6], u[8 * i + 7]));
                }
            }
#pragma unroll
            for (int i = 0; i < 8; i++) {
                const uint4 v = qpark[2048 + i * 32];
                q[4 * i] = v.x; q[4 * i + 1] = v.y; q[4 * i + 2] = v.z; q[4 * i + 3] = v.w;
            }
#pragma unroll
            for (int i = 0; i < 32; i++) p[i] = h[112 + i];
            mbar_wait(bar_full + 24, 0);
            WG_WAIT(0);
            fence_regs(o);
            release(2);
        }
        DBG_T(105);
        DBG_G(125);

        uint8_t* frag = reinterpret_cast<uint8_t*>(__shfl_sync(0xffffffffu, reinterpret_cast<unsigned long long>(g_frag + (size_t)(rg * 8 + cw) * WREG + lane * 16), lane));
        const uint4* qnext = reinterpret_cast<const uint4*>(__shfl_sync(0xffffffffu, reinterpret_cast<unsigned long long>(padd(smem_raw, SM_Q + tid * 16 + cw * 3584)), lane));
        uint8_t* odst = reinterpret_cast<uint8_t*>(const_cast<uint4*>(qnext));
        qnext -= 2048;
        float m0, m1, l0 = 0.25f, l1 = 0.25f, t0, t1;
        uint32_t bad = 0;
        const int lw = cw & 3;
        const uint32_t relw = lw == RW && lane < 8, handw = lw == HW || cw == HW2;
        auto release4 = [&](uint32_t off) {
            asm volatile("{\n.reg .pred p;\nsetp.ne.b32 p, %1, 0;\n@p mbarrier.arrive.shared::cluster.b64 _, [%0];\n}" ::"r"(rel_base + off), "r"(relw) : "memory"); };
        auto handoff = [&]() {
            asm volatile("{\n.reg .pred p;\nsetp.ne.b32 p, %1, 0;\n@p bar.arrive %0, 192;\n}" ::"r"(2 - w), "r"(handw) : "memory"); };
        if (cw == 4 + HW) bar_arrive(1, 192);
        auto finish = [&](auto lo, auto hi, uint32_t bit, auto sink) {
#pragma unroll
            for (int i = lo.value; i < hi.value; i++) {
                const uint32_t v0 = pack_bf16(o[8 * i] * t0, o[8 * i + 1] * t0), v1 = pack_bf16(o[8 * i + 2] * t1, o[8 * i + 3] * t1);
                const uint32_t v2 = pack_bf16(o[8 * i + 4] * t0, o[8 * i + 5] * t0), v3 = pack_bf16(o[8 * i + 6] * t1, o[8 * i + 7] * t1);
                if (i == 0 && fabsf(o[0] * t0) >= 0x1p-31f) bad |= bit << 8;
                sink(i, v0, v1, v2, v3);
            }
        };
        float lq[6];
        auto row_parts = [&]() {
#pragma unroll
            for (int i = 0; i < 3; i++) { lq[i] = __shfl_xor_sync(0xffffffffu, l0, i + 1); lq[3 + i] = __shfl_xor_sync(0xffffffffu, l1, i + 1); }
        };
        auto row_sums = [&](uint32_t bit) {
            t0 = (l0 + lq[0]) + (lq[1] + lq[2]); t1 = (l1 + lq[3]) + (lq[4] + lq[5]);
            if (!(t0 >= LMIN && t0 < LMAX && t1 >= LMIN && t1 < LMAX)) bad |= bit;
        };
        auto issue_pv = [&](uint32_t dlo, int acc, auto lo, auto hi) {
            if (lo.value == 0) asm volatile("{\n.reg .pred p;\nsetp.eq.b32 p, %0, 0;\n@p bar.sync 4, 160;\n}" ::"r"(w) : "memory");
#pragma unroll
            for (int ks = lo.value; ks < hi.value; ks++)
                mma_rs128<1>(o, p[4 * ks], p[4 * ks + 1], p[4 * ks + 2], p[4 * ks + 3], desc_of(dlo + ks * 128), ks ? 1 : acc);
            WG_COMMIT();
        };
#pragma unroll
        for (int i = 0; i < 64; i++) s[i] = 0.f;
        uint32_t dv_lo = desc_lo(0, UNIT), voff = 0;
        auto issue_qk = [&]() {
            const uint32_t dk = dv_lo ^ (desc_lo(0, UNIT) ^ desc_lo(3 * SLOT, 16));
            bar_sync(1 + w, 192);
            fence_regs(s); fence_regs(q); fence_regs(o); fence_regs(p);
            WG_FENCE();
#pragma unroll
            for (int ks = 0; ks < 8; ks++)
                mma_rs128<0>(s, q[4 * ks], q[4 * ks + 1], q[4 * ks + 2], q[4 * ks + 3], desc_of(dk + (ks >> 2) * 1024 + (ks & 3) * 2), ks != 0);
            WG_COMMIT();
        };
        auto to_frag = [&](int i, uint32_t v0, uint32_t v1, uint32_t v2, uint32_t v3) {
            *reinterpret_cast<uint4*>(odst + i * 512) = make_uint4(v0, v1, v2, v3); };
        int n = 0;
        auto scores_ready = [&]() {
            WG_WAIT(1);
            fence_regs(s); fence_regs(q);
        };
        auto pass_on = [&]() {
            release4(voff ^ 24);
            handoff();
        };
#pragma unroll 1
        for (;;) {
            {
                if (RPE) {
                    asm volatile("st.shared.v2.f32 [%0], {%1, %2};" ::"r"(sb + SM_RED + tid * 8), "f"(l0), "f"(l1) : "memory");
                    __syncwarp();
                    const uint4 a = lds128(sb + SM_RED + (tid & ~3) * 8), b = lds128(sb + SM_RED + (tid & ~3) * 8 + 16);
                    l0 = __uint_as_float(a.x); lq[0] = __uint_as_float(a.z); lq[1] = __uint_as_float(b.x); lq[2] = __uint_as_float(b.z);
                    l1 = __uint_as_float(a.y); lq[3] = __uint_as_float(a.w); lq[4] = __uint_as_float(b.y); lq[5] = __uint_as_float(b.w);
                } else {
                    row_parts();
                }
                issue_qk();
                if (RPE == 2) hold(l0, l1);
                row_sums(1u << (n >> 4));
                t0 = rcp_fast(t0); t1 = rcp_fast(t1);
                l0 = 0.f; l1 = 0.f;
                odst = n ? frag + ((n >> 4) - 1) * 4096 : odst;
                if (RPE) anchor(bar_full + 504, (t0 + t1) * __uint_as_float((bad ^ (uint32_t)(uintptr_t)odst) & 0x3fffffff));
                asm volatile("{\n.reg .pred p;\nsetp.ne.b32 p, %1, 0;\n@p mbarrier.arrive.shared::cta.b64 _, [%0];\n}"
                             ::"r"(bar_qfree + (n >> 1) - 8), "r"(lane ? 0 : n) : "memory");
                issue_pv(dv_lo, 1, IC<0>{}, IC<8>{});
                scores_ready();
                float a0 = fmaxf(s[0], s[1]), a1 = fmaxf(s[2], s[3]), a2 = fmaxf(s[4], s[5]), a3 = fmaxf(s[6], s[7]);
#pragma unroll
                for (int i = 1; i < MAXG; i++) {
                    a0 = fmaxf(a0, fmaxf(s[8 * i], s[8 * i + 1])); a1 = fmaxf(a1, fmaxf(s[8 * i + 2], s[8 * i + 3]));
                    a2 = fmaxf(a2, fmaxf(s[8 * i + 4], s[8 * i + 5])); a3 = fmaxf(a3, fmaxf(s[8 * i + 6], s[8 * i + 7]));
                }
                const uint32_t a = pack_bf16(fmaxf(a0, a2), fmaxf(a1, a3));
                const uint32_t b = bmax2(bmax2(a, __shfl_xor_sync(0xffffffffu, a, 1)), bmax2(__shfl_xor_sync(0xffffffffu, a, 2), __shfl_xor_sync(0xffffffffu, a, 3)));
                pass_on();
                m0 = fmaf(-CS, bf_lo(b), -POFF); m1 = fmaf(-CS, bf_hi(b), -POFF);
            }
#pragma unroll 1
            for (;;) {
                DBG_T(n);
#pragma unroll
                for (int i = 0; i < 4 * STAGE; i++) s[i] = fmaf(s[i], CS, (i & 2) ? m1 : m0);
#pragma unroll
                for (int i = 0; i < 4 * SPLIT; i++) s[i] = ex2(s[i]);
#pragma unroll
                for (int i = 0; i < SPLIT; i++) { l0 += s[4 * i] + s[4 * i + 1]; l1 += s[4 * i + 2] + s[4 * i + 3]; }
                if (STAGE < 16) {
                    m0 = fmaf(l0, 0.f, m0); m1 = fmaf(l1, 0.f, m1);
                }
                anchor(bar_full + 504, l0 + l1);
                WG_WAIT(0);
                fence_regs(o); fence_regs(p);
                release4(voff);
                dv_lo ^= 2 * SLOT / 16;
                voff ^= 16;
                n++;
#pragma unroll
                for (int i = 4 * STAGE; i < 64; i++) s[i] = fmaf(s[i], CS, (i & 2) ? m1 : m0);
#pragma unroll
                for (int i = 4 * SPLIT; i < 64; i++) s[i] = ex2(s[i]);
#pragma unroll
                for (int i = SPLIT; i < 16; i++) { l0 += s[4 * i] + s[4 * i + 1]; l1 += s[4 * i + 2] + s[4 * i + 3]; }
#pragma unroll
                for (int i = 0; i < 32; i++) p[i] = pack_bf16(s[2 * i], s[2 * i + 1]);
                const int jn = n & 15;
                if (!(((0x8003 | RCM | RCM << 1) >> jn) & 1)) {
                    issue_qk();
                    issue_pv(dv_lo, 1, IC<0>{}, IC<8>{});
                    scores_ready();
                    pass_on();
                    continue;
                }
                if (jn == 1) {
                    finish(IC<0>{}, IC<ESPLIT>{}, 1u << (n >> 4), to_frag);
                    issue_qk();
                    if (HOLD) hold(t0, t1);
                    finish(IC<ESPLIT>{}, IC<8>{}, 1u << (n >> 4), to_frag);
                    WG_FENCE();
                    issue_pv(dv_lo, 0, IC<0>{}, IC<8>{});
                    scores_ready();
                    pass_on();
                    continue;
                }
                if (jn == 0) break;
                if (RCM && jn != 15) {
                    if ((RCM >> jn) & 1) {
                        row_parts();
                        row_sums(2u << (n >> 4));
                        const uint32_t e0 = __float_as_uint(t0) >> 23, e1 = __float_as_uint(t1) >> 23;
                        m0 -= __uint_as_float(0x4b000000u | e0) - (8388608.f + 127.f - POFF);
                        m1 -= __uint_as_float(0x4b000000u | e1) - (8388608.f + 127.f - POFF);
                        t0 = __uint_as_float((254 - (int)POFF - e0) << 23); t1 = __uint_as_float((254 - (int)POFF - e1) << 23);
                        l0 *= t0; l1 *= t1;
                    } else {
#pragma unroll
                        for (int i = 0; i < 64; i++) o[i] *= (i & 2) ? t1 : t0;
                    }
                    issue_qk();
                    issue_pv(dv_lo, 1, IC<0>{}, IC<8>{});
                    scores_ready();
                    pass_on();
                    continue;
                }
                if (SPARE && n == 47) mbar_wait(bar_q3, 0);
                qnext = n == 63 ? reinterpret_cast<const uint4*>(frag) : qnext + 2048;
                issue_qk();
                issue_pv(dv_lo, 1, IC<0>{}, IC<8>{});
                scores_ready();
                pass_on();
#pragma unroll
                for (int i = 0; i < 8; i++) {
                    const uint4 v = qnext[i * 32];
                    q[4 * i] = v.x; q[4 * i + 1] = v.y; q[4 * i + 2] = v.z; q[4 * i + 3] = v.w;
                }
            }
            if (n == 64) break;
        }
        DBG_T(64);
        uint32_t a1[32], a2[32];
        row_parts();
        frag_load(a1, frag + 4096);
        frag_load(a2, frag + 8192);
        bar_sync(1 + w, 192);
        fence_regs(o); fence_regs(p);
        WG_FENCE();
        issue_pv(desc_lo(3 * SLOT, UNIT), 1, IC<0>{}, IC<8>{});
        handoff();
        row_sums(16);
        t0 = rcp_fast(t0); t1 = rcp_fast(t1);
        mbar_wait(bar_mod, 0);
        WG_WAIT(0);
        fence_regs(o); fence_regs(p);
        release4(24);
        finish(IC<0>{}, IC<8>{}, 16, [&](int i, uint32_t v0, uint32_t v1, uint32_t v2, uint32_t v3) {
            p[4 * i] = v0; p[4 * i + 1] = v1; p[4 * i + 2] = v2; p[4 * i + 3] = v3; });
        bad = __reduce_or_sync(0xffffffffu, bad);
        bad = ((bad | ~(bad >> 8)) >> 1) & 15;
        if (__builtin_expect(bad != 0, 0)) {
            uint8_t* keep = g_keep + (size_t)(rg * 8 + cw) * 4096 + lane * 16;
            frag_store(keep, p);
            attn_fallback(bad, tag, gs, frag, keep, args.wq, args.kc, args.vc);
            frag_load(q, frag); frag_load(a1, frag + 4096); frag_load(a2, frag + 8192); frag_load(p, keep);
        }
        DBG_T(80);
        DBG_G(124);

        const uint32_t eye = (lane >> 3) == (lane & 3) ? 0x3f80u << ((lane & 4) * 4) : 0;
        auto sum8 = [&](uint32_t* r, const uint4 (&v)[8]) {
            float d[16];
#pragma unroll
            for (int i = 0; i < 16; i++) d[i] = 0.f;
#pragma unroll
            for (int src = 0; src < 8; src++) {
                mma1688(d + 8 * (src & 1), v[src].x, v[src].y, eye);
                mma1688(d + 8 * (src & 1) + 4, v[src].z, v[src].w, eye);
            }
#pragma unroll
            for (int i = 0; i < 4; i++) r[i] = pack_bf16(d[2 * i] + d[8 + 2 * i], d[2 * i + 1] + d[9 + 2 * i]);
        };
        uint4 v2[8], v3[8], wf[27];
        uint2 u4[8], gw[9];
        uint32_t x1[20], xs, pa, ta;
        const uint8_t *mb, *mb4;
        int tid_;
        auto load_wf = [&](auto lo, auto hi) {
            const uint32_t wa = sb + SM_Q + ((cw & 1) * D_ + (cw >> 1) * 32 + (tid_ & 7) + (tid_ & 16) / 2) * 80 + (tid_ & 8) * 2;
#pragma unroll
            for (int i = lo.value; i < hi.value; i++)
                wf[i] = ldsm4t((i < 24 ? wa + ((i / 3 & 3) * 8 + i / 12) * 1280 : wa + (32 - (cw >> 1)) * 1280) + (i % 3) * 32);
        };
        uint32_t at[18];
        {
            float (&u)[32] = reinterpret_cast<float (&)[32]>(o);
            uint32_t off = 0;
            auto turn = [&](const uint32_t (&a)[32], const uint32_t (&b)[32], int acc) {
                const uint64_t dv = desc_of(desc_lo(0, UNIT) + off * (SLOT / 128));
                bar_sync(1 + w, 192);
                fence_regs(u);
                WG_FENCE();
#pragma unroll
                for (int ks = 0; ks < 16; ks++) {
                    const uint32_t* f = ks < 8 ? &a[4 * ks] : &b[4 * ks - 32];
                    mma_rs64<1>(u, f[0], f[1], f[2], f[3], dv + ks * 128, ks | acc);
                    if (ks == OSPLIT - 1) WG_COMMIT();
                }
                WG_COMMIT();
                WG_WAIT(1);
            };
            auto done = [&]() {
                WG_WAIT(0);
                fence_regs(u);
                release4(off);
                off = (off + 8) & 24;
            };
            auto store = [&](uint8_t* dst) {
#pragma unroll
                for (int i = 0; i < 4; i++)
                    st_relaxed4(dst + i * 512, pack_bf16(u[8 * i], u[8 * i + 1]), pack_bf16(u[8 * i + 2], u[8 * i + 3]),
                                pack_bf16(u[8 * i + 4], u[8 * i + 5]), pack_bf16(u[8 * i + 6], u[8 * i + 7]));
            };
            tid_ = __shfl_sync(0xffffffffu, tid, lane);
            pa = sb + w * (UNIT - 2048) + tid_ * 16;
#pragma unroll
            for (int i = 0; i < 8; i++) at[i] = 0;
            fence_regs(q); fence_regs(p);
            uint8_t* dst = frag;
#pragma unroll 1
            for (int k = 0; k < 8; k++, dst += 2048) {
                const uint32_t poff = off;
                const bool sum = (0xa0 >> k) & 1;
                if (sum) off = (off + 8) & 24;
                turn(q, p, 0);
                handoff();
                if (sum) {
                    uint4 v[8];
#pragma unroll
                    for (int src = 0; src < 8; src++) v[src] = lds128(pa + poff * (SLOT / 8) + src * 2048);
                    __syncwarp();
                    release(poff >> 3);
                    done();
                    float d[8];
#pragma unroll
                    for (int i = 0; i < 8; i++) {
                        float t[8];
#pragma unroll
                        for (int src = 0; src < 8; src++) {
                            const uint32_t x = i < 2 ? v[src].x : i < 4 ? v[src].y : i < 6 ? v[src].z : v[src].w;
                            t[src] = (i & 1) ? bf_hi(x) : bf_lo(x);
                        }
                        d[i] = ((t[0] + t[2]) + (t[4] + t[6])) + ((t[1] + t[3]) + (t[5] + t[7]));
                    }
#pragma unroll
                    for (int i = 0; i < 4; i++) { at[i] = at[4 + i]; at[4 + i] = pack_bf16(d[2 * i], d[2 * i + 1]); }
                } else {
                    done();
                }
                turn(a1, a2, 1);
                handoff();
                done();
                store(dst);
                __syncwarp();
                asm volatile("{\n.reg .pred p;\nsetp.ne.b32 p, %1, 0;\n@p mbarrier.arrive.shared::cta.b64 _, [%0];\n}"
                             ::"r"(bar_pub + 4 + 4 * k), "r"(lane ? 0 : (0x2a >> k) & 1) : "memory");
            }
            turn(q, p, 0);
            handoff();
            mb = padd(g_frag, (qb * 64 + j) * WREG + 3 * 4096 + tid_ * 16);
            mb4 = padd(mb, 4096 + ((cw >> 1) - cw) * 512 + (cw & 1) * 8);
            xs = sb + (tid_ & 15) * XP + (tid_ & 16) + cw * 32;
            ta = sb + (cw * 8 + (tid_ & 3)) * 8;
#pragma unroll
            for (int k = 0; k < 9; k++) {
                gw[k] = lds64(ta + SM_T + (k < 8 ? (k >> 1) * 64 + (k & 1) * 4 : 256 - cw * 4) * 8);
                if (!(tid_ & 4)) gw[k].y = 0x3f803f80u;
            }
            mbar_wait(bar_g, 0);
            done();
            load_wf(IC<0>{}, IC<WF0>{});
            turn(a1, a2, 1);
            if (w == 0) handoff();
            if (P2E) {
                mbar_wait(bar_full + 8, 0);
#pragma unroll
                for (int src = 0; src < 8; src++) v2[src] = lds128(pa + SLOT + src * 2048);
            }
            done();
            store(dst);
            mbar_wait(bar_full, 0);
            rows_load(x1, xs, cw);
            if (w == 0) bar_sync(5, 256); else bar_arrive(5, 256);
        }
        DBG_T(81);
        DBG_G(122);

        {
        const int tid = tid_, lane = tid & 31;
        const int g8 = lane >> 2, qd = lane & 3, l16 = lane & 15;
        uint32_t h2[18], gb[9], k1, k2;
        float4* rec = reinterpret_cast<float4*>(red + 128);
        const uint2* candp = reinterpret_cast<const uint2*>(padd(g_cand, ((blockIdx.x & (CREP - 1)) * NCTA + (tid >> 1)) * 32 + (tid & 1) * 8));
        uint2 cd;
        auto stage_out = [&]() {
#pragma unroll
            for (int k = 0; k < 9; k++) {
                x1[2 * k] = badd2(x1[2 * k], bmul2(gb[k], h2[2 * k]));
                x1[2 * k + 1] = badd2(x1[2 * k + 1], bmul2(gb[k], h2[2 * k + 1]));
            }
#pragma unroll
            for (int ch = 0; ch < 4; ch++) stsm_x4(xs + ch * 256, x1[4 * ch], x1[4 * ch + 1], x1[4 * ch + 2], x1[4 * ch + 3]);
            asm volatile("stmatrix.sync.aligned.m8n8.x2.shared.b16 [%0], {%1, %2};" ::"r"(xs + 1024 - cw * 16), "r"(x1[16]), "r"(x1[17]) : "memory");
        };
        {
            uint32_t it = 0, miss;
            if (!P2E) {
                mbar_wait(bar_full + 8, 0);
#pragma unroll
                for (int src = 0; src < 8; src++) v2[src] = lds128(pa + SLOT + src * 2048);
            }
            sum8(at + 8, v2);
            float st[12];
#pragma unroll
            for (int i = 0; i < 12; i++) st[i] = 0.f;
            auto add_pair = [&](int k) {
                x1[2 * k] = badd2(x1[2 * k], bmul2(gw[k].x, at[2 * k]));
                x1[2 * k + 1] = badd2(x1[2 * k + 1], bmul2(gw[k].x, at[2 * k + 1]));
                stats_add(st, x1[2 * k], x1[2 * k + 1], gw[k].y);
            };
#pragma unroll
            for (int k = 0; k < 6; k++) add_pair(k);
            mbar_wait(bar_full + 16, 0);
#pragma unroll
            for (int src = 0; src < 8; src++) v3[src] = lds128(pa + 2 * SLOT + src * 2048);
#pragma unroll 1
            do {
                if (BO && it) __nanosleep(BO);
                miss = 0;
#pragma unroll
                for (int src = 0; src < 8; src++) reload16(v3[src], mb + (size_t)src * 8 * WREG, miss);
            } while (__any_sync(0xffffffffu, miss) && ++it < SPIN / 16);
            if (lane < 4) mbar_arrive_cluster(rel_base + 8 * (1 + (lane >> 1)));
            sum8(at + 12, v3);
            add_pair(6); add_pair(7);
            load_wf(IC<WF0>{}, IC<WF1>{});
            uint2 cs[9];
#pragma unroll
            for (int k = 0; k < 9; k++) cs[k] = lds64(ta + SM_TC + (k < 8 ? (k >> 1) * 64 + (k & 1) * 4 : 256 - cw * 4) * 8);
            mbar_wait(bar_pre, 0);
            mbar_wait(bar_full + 24, 0);
#pragma unroll
            for (int src = 0; src < 8; src++) u4[src] = lds64(sb + 3 * SLOT + src * 2048 + (cw >> 1) * 512 + lane * 16 + (cw & 1) * 8);
#pragma unroll 1
            do {
                if (BO && miss) __nanosleep(BO);
                miss = 0;
#pragma unroll
                for (int src = 0; src < 8; src++) reload8(u4[src], mb4 + (size_t)src * 8 * WREG, miss);
            } while (__any_sync(0xffffffffu, miss) && ++it < SPIN / 16);
            float d[8] = {0.f, 0.f, 0.f, 0.f, 0.f, 0.f, 0.f, 0.f};
#pragma unroll
            for (int i = 0; i < 4; i++) mma16816(d + 4 * (i & 1), u4[2 * i].x, u4[2 * i].y, u4[2 * i + 1].x, u4[2 * i + 1].y, eye, eye);
            at[16] = pack_bf16(d[0] + d[4], d[1] + d[5]); at[17] = pack_bf16(d[2] + d[6], d[3] + d[7]);
            add_pair(8);
            DBG_G(123);
            const float2 ws = *reinterpret_cast<const float2*>(smem_raw + SM_TS);
            uint4* cdst = padd(g_cand, CFULL ? ((tid >> 1) * NCTA + rg) * 32 + (tid & 1) * 16 : (tid * NCTA + rg) * 32);
            uint32_t mean2;
            float dot;
            const float rsd = rows_stats(st, rec, cw, lane, mean2, dot);
            const uint32_t b = __float_as_uint(fmaf(fmaf(-bf_lo(mean2), ws.x, dot), rsd, ws.y));
            const uint32_t key = (((b & 0x80000000u) ? ~b : (b | 0x80000000u)) | 2047u) - (rg * 16 + l16);
            top2(key, k1, k2);
            if (tid < (CFULL + 1) * CREP) st_relaxed(cdst, k1, tag, k2, tag);
            cd = ld_relaxed64(candp);
            rows_normalise(h2, x1, mean2, rsd, lane, [&]() {
#pragma unroll
                for (int k = 0; k < 9; k++) gb[k] = lds32(sb + SM_TG + (cw * 8 + qd + (k < 8 ? (k >> 1) * 64 + (k & 1) * 4 : 256 - cw * 4)) * 4);
                if (WFE) load_wf(IC<WF1>{}, IC<WF2>{});
            });
#pragma unroll
            for (int k = 0; k < 18; k++) h2[k] = badd2(bmul2(h2[k], cs[k >> 1].x), cs[k >> 1].y);
            const uint32_t r1 = ~k1 & 15, r2 = ~k2 & 15;
            uint32_t todo = ((r1 & 7) == g8) | ((r2 & 7) == g8) << 1;
#pragma unroll 1
            while (todo) {
                const bool second = !(todo & 1), hi = (second ? r2 : r1) & 8;
                uint4* dst = padd(g_rows, ((rg * 2 + second) * RSLOT + cw * 16 + qd) * 16);
                uint32_t r[18];
#pragma unroll
                for (int k = 0; k < 9; k++) { r[k] = hi ? h2[2 * k + 1] : h2[2 * k]; r[9 + k] = hi ? x1[2 * k + 1] : x1[2 * k]; }
                fence_regs(r);
                st_relaxed(dst, r[0], r[1], r[2], r[3]);
                st_relaxed(dst + 4, r[4], r[5], r[6], r[7]);
                st_relaxed64(reinterpret_cast<uint2*>(padd(dst, 2048 - cw * 224 - qd * 8)), r[8], r[17]);
                st_relaxed(dst + 8, r[9], r[10], r[11], r[12]);
                st_relaxed(dst + 12, r[13], r[14], r[15], r[16]);
                todo &= todo - 1;
            }
            __syncwarp();

            if (SO == 0) stage_out();
            if (!WFE) load_wf(IC<WF1>{}, IC<WF2>{});
        }
        DBG_G(110);
        float2* part = reinterpret_cast<float2*>(smem_raw + 3 * SLOT + UNIT);
        bf16* act = reinterpret_cast<bf16*>(smem_raw + 3 * SLOT + UNIT + 4096);
        {
            uint32_t it = 0;
            const bool own = (tid >> 1) == rg;
            const uint32_t ks = sb + 3 * SLOT + UNIT + 5120;
#pragma unroll 1
            while (cd.y != tag && !own && ++it < SPIN / 16) cd = ld_relaxed64(candp);
            asm volatile("st.shared.u32 [%0], %1;" ::"r"(ks + tid * 4), "r"(own ? (tid & 1) ? k2 : k1 : cd.x) : "memory");
            bar_sync(3, 256);
            DBG_G(111);
            const uint4 a = lds128(ks + lane * 16), b = lds128(ks + 512 + lane * 16);
            const uint32_t a1 = max(a.x, a.z), a2 = __vimax3_u32(min(a.x, a.z), a.y, a.w);
            const uint32_t b1 = max(b.x, b.z), b2 = __vimax3_u32(min(b.x, b.z), b.y, b.w);
            const uint32_t c1 = max(a1, b1), c2 = __vimax3_u32(min(a1, b1), a2, b2);
            k1 = __reduce_max_sync(0xffffffffu, c1);
            k2 = __reduce_max_sync(0xffffffffu, c1 == k1 ? c2 : c1);
        }
        const int sel0 = ~k1 & 2047, sel1 = ~k2 & 2047;
        const uint32_t slot0 = (sel0 >> 4) * 2, slot1 = (sel1 >> 4) * 2 + ((sel0 ^ sel1) < 16);
        uint4 b[9], b2[3];
        {
            const bool tk = cw < 4 ? cw & 2 : lane & 16;
            const int ri = cw < 4 ? tid & 63 : 64 + l16;
            const uint4* hp = padd(g_rows, ((tk ? slot1 : slot0) * RSLOT + (cw < 4 ? ri + (ri & 56) : ri + 64)) * 16);
            const uint32_t hs = sb + 3 * SLOT + UNIT + 8192;
            uint4 hr = make_uint4(cw < 5 ? ~0u : 0, 0, 0, 0);
            uint32_t it = 0, miss;
            reload16(hr, hp, miss);
            if (OUTP == 0 && SO == 0 && tid == 255) {
                reinterpret_cast<int2*>(red)[8] = make_int2(sel0, sel1);
                mbar_arrive(bar_out);
            }
            if (SO == 1) stage_out();
            load_wf(IC<WF2>{}, IC<27>{});
            mbar_wait(bar_full + 8, 1);
            mbar_wait(bar_full + 16, 1);
            {
                const uint32_t da = sb + (lane < 18 ? SLOT + lane * XP : 2 * SLOT + (lane - 18) * XP) + cw * 144;
                const uint32_t db = sb + 2 * SLOT + (14 + (lane & 3)) * XP + cw * 144 + (lane >> 3) * 16;
#pragma unroll
                for (int i = 0; i < 9; i++) b[i] = ldsm4t(da + i * 16);
#pragma unroll
                for (int i = 0; i < 3; i++) b2[i] = ldsm4t(db + i * 48);
            }
#pragma unroll 1
            do {
                miss = 0;
                reload16(hr, hp, miss);
            } while (__any_sync(0xffffffffu, miss) && ++it < SPIN / 16);
            if (cw < 5) asm volatile("st.shared.v4.u32 [%0], {%1, %2, %3, %4};" ::"r"(hs + (tk * 84 + ri) * 16), "r"(hr.x), "r"(hr.y), "r"(hr.z), "r"(hr.w) : "memory");
            bar_sync(3, 256);
            if (OUTP == 0 && SO == 1 && tid == 255) {
                reinterpret_cast<int2*>(red)[8] = make_int2(sel0, sel1);
                mbar_arrive(bar_out);
            }
            uint4 hv[4];
            uint32_t hw[2];
#pragma unroll
            for (int i = 0; i < 4; i++) hv[i] = lds128(hs + ((g8 & 1) * 84 + (cw >> 1) * 16 + qd + i * 4) * 16);
#pragma unroll
            for (int i = 0; i < 2; i++)
                hw[i] = lds32(hs + ((g8 & 1) * 84 + 64) * 16 + (cw >> 1) * 64 + qd * 8 + i * 32);
            DBG_G(112);
            float acc[24];
#pragma unroll
            for (int i = 0; i < 24; i++) acc[i] = 0.f;
#pragma unroll
            for (int i = 0; i < 27; i++) {
                const int ks = i / 3;
                mma16816(acc + 4 * (i % 6), wf[i].x, wf[i].y, wf[i].z, wf[i].w, ks == 8 ? hw[0] : (ks & 1) ? hv[ks >> 1 & 3].z : hv[ks >> 1 & 3].x,
                         ks == 8 ? hw[1] : (ks & 1) ? hv[ks >> 1 & 3].w : hv[ks >> 1 & 3].y);
            }
            if (qd == 0) {
#pragma unroll
                for (int i = 0; i < 5; i++) part[cw * 48 + i * 8 + g8] = make_float2(acc[2 * i] + acc[12 + 2 * i], acc[2 * i + 1] + acc[13 + 2 * i]);
            }
        }
        {
            uint2* dst = padd(g_ypart, ((((g8 & 1) * 36 + ((cw * 9) >> 1)) * NCTA + blockIdx.x) * 8 + (cw & 1) * 4 + qd) * 8);
            uint2* dst1 = dst + ((cw & 1) ? NCTA * 8 - 4 : 4);
            bar_sync(3, 256);

            {
                const float* pp = reinterpret_cast<const float*>(part) + ((blockIdx.x & 1) << 3) + (tid & 127);
                const float gs = rbf((pp[0] + pp[192]) + (pp[384] + pp[576])), us = rbf((pp[96] + pp[288]) + (pp[480] + pp[672]));
                const float v = rbf(gs * sigmoidf_(gs)) * us;
                if (tid < 80) act[(tid & 1) * 56 + (tid >> 1)] = __float2bfloat16_rn(tid < 72 ? v : 0.f);
            }
            bar_sync(3, 256);
            DBG_G(113);
            const uint32_t ap = sb + 3 * SLOT + UNIT + 4096 + (lane & 1) * 112 + (lane >> 4) * 16;
            const uint4 a0 = ldsm4(ap), a1 = ldsm4(ap + 32), a2 = ldsm4(ap + 64);
            float y[36];
#pragma unroll
            for (int i = 0; i < 36; i++) y[i] = 0.f;
#pragma unroll
            for (int i = 0; i < 9; i++) {
                const uint32_t bl = i % 3 == 0 ? b2[i / 3].x : i % 3 == 1 ? b2[i / 3].y : b2[i / 3].z;
                mma16816(y + 4 * i, a0.x, a0.y, a0.z, a0.w, b[i].x, b[i].y);
                mma16816(y + 4 * i, a1.x, a1.y, a1.z, a1.w, b[i].z, b[i].w);
                mma1688(y + 4 * i, a2.x, a2.y, bl);
            }
#pragma unroll
            for (int i = 0; i < 9; i++)
                if (lane < 8) st_relaxed64(((i & 1) ? dst1 : dst) + (i >> 1) * (NCTA * 8), __float_as_uint(y[4 * i]), __float_as_uint(y[4 * i + 1]));
        }
        DBG_G(114);
        if (OUTP == 1 && tid == 255) {
            reinterpret_cast<int2*>(red)[8] = make_int2(sel0, sel1);
            mbar_arrive(bar_out);
        }
        if (blockIdx.x == 127 && tid == 0) gs->epoch[0] = tag;
        if (blockIdx.x < 72) {
            const int tok = blockIdx.x >= 36, grp = blockIdx.x - tok * 36, cp = grp * 8 + (lane & 7);
            const uint2* src = padd(g_ypart, (blockIdx.x * NCTA * 8 + tid) * 8);
            const uint8_t* hsrc = reinterpret_cast<const uint8_t*>(padd(g_rows, (tok ? slot1 : slot0) * (RSLOT * 16) +
                (grp < 32 ? (grp & 7) * 256 + (grp >> 4) * 64 + qd * 16 + (grp & 8) + (lane & 4) : 2048 + (cp - 256) * 8)));
            const uint8_t* xsrc = hsrc + (grp < 32 ? 128 : 4);
            uint32_t* dst = padd(reinterpret_cast<uint32_t*>(args.out), (tok ? sel1 : sel0) * (D_ * 2) + cp * 4);
            const uint32_t gb = reinterpret_cast<const uint32_t*>(smem_raw + SM_TG)[cp];
            const uint32_t ksel = ((tok ? k2 : k1) & ~2047u) | 1024u;
            const float sg = sigmoidf_(rbf(__uint_as_float((ksel & 0x80000000u) ? (ksel & 0x7fffffffu) : ~ksel)));
            uint2 v[4];
            uint32_t hv, xv, it = 0;
            bool miss;
#pragma unroll 1
            do {
#pragma unroll
                for (int i = 0; i < 4; i++) v[i] = ld_relaxed64(src + i * 256);
                hv = ld_relaxed32(hsrc);
                xv = ld_relaxed32(xsrc);
                miss = max(__vimax3_u32(v[0].x, v[1].x, v[2].x), __vimax3_u32(v[3].x, hv, xv)) == ~0u;
            } while (__any_sync(0xffffffffu, miss) && ++it < SPIN / 16);
            float y0 = (__uint_as_float(v[0].x) + __uint_as_float(v[1].x)) + (__uint_as_float(v[2].x) + __uint_as_float(v[3].x));
            float y1 = (__uint_as_float(v[0].y) + __uint_as_float(v[1].y)) + (__uint_as_float(v[2].y) + __uint_as_float(v[3].y));
            y0 += __shfl_xor_sync(0xffffffffu, y0, 8); y1 += __shfl_xor_sync(0xffffffffu, y1, 8);
            y0 += __shfl_xor_sync(0xffffffffu, y0, 16); y1 += __shfl_xor_sync(0xffffffffu, y1, 16);
            if (lane < 8) reinterpret_cast<float2*>(rec)[cw * 8 + lane] = make_float2(y0, y1);
            bar_sync(3, 256);
            if (cw == 0) {
                const float2 t0_ = reinterpret_cast<const float2*>(rec)[lane], t1_ = reinterpret_cast<const float2*>(rec)[32 + lane];
                y0 = t0_.x + t1_.x; y1 = t0_.y + t1_.y;
                y0 += __shfl_xor_sync(0xffffffffu, y0, 8); y1 += __shfl_xor_sync(0xffffffffu, y1, 8);
                y0 += __shfl_xor_sync(0xffffffffu, y0, 16); y1 += __shfl_xor_sync(0xffffffffu, y1, 16);
                const uint32_t y2 = bmul2(pack_bf16(y0, y1), pack_bf16(sg, sg));
                if (lane < 8) *dst = badd2(xv, bmul2(gb, badd2(hv, y2)));
            }
        }
        }
        DBG_T(88);
        DBG_G(121);
    }
}

typedef CUresult (*EncodeFn)(CUtensorMap*, CUtensorMapDataType, cuuint32_t, void*, const cuuint64_t*, const cuuint64_t*,
                             const cuuint32_t*, const cuuint32_t*, CUtensorMapInterleave, CUtensorMapSwizzle,
                             CUtensorMapL2promotion, CUtensorMapFloatOOBfill);

static void make_map(EncodeFn enc, CUtensorMap* m, const void* ptr, int rank, const cuuint64_t* dims,
                     const cuuint64_t* strides, const cuuint32_t* box, CUtensorMapSwizzle sw = CU_TENSOR_MAP_SWIZZLE_128B,
                     CUtensorMapDataType dt = CU_TENSOR_MAP_DATA_TYPE_BFLOAT16) {
    const cuuint32_t es[3] = {1, 1, 1};
    enc(m, dt, rank, const_cast<void*>(ptr), dims, strides, box, es,
        CU_TENSOR_MAP_INTERLEAVE_NONE, sw, CU_TENSOR_MAP_L2_PROMOTION_L2_128B,
        CU_TENSOR_MAP_FLOAT_OOB_FILL_NONE);
}

extern "C" void kernel_launch(void* const* d_in, const int* in_sizes, int n_in, void* d_out, int out_size) {
    const bf16* x = (const bf16*)d_in[0];
    const bf16* kc = (const bf16*)d_in[1];
    const bf16* vc = (const bf16*)d_in[2];
    const bf16* wq = (const bf16*)d_in[3];
    const bf16* wo = (const bf16*)d_in[4];
    const bf16* w_r = (const bf16*)d_in[6];
    const bf16* w_gate = (const bf16*)d_in[7];
    const bf16* w_up = (const bf16*)d_in[8];
    const bf16* w_down = (const bf16*)d_in[9];
    const bf16* cvec = (const bf16*)d_in[10];
    const bf16* w_mod = (const bf16*)d_in[11];
    bf16* out = (bf16*)d_out;

    void* fn = nullptr;
    cudaDriverEntryPointQueryResult qr;
    cudaGetDriverEntryPoint("cuTensorMapEncodeTiled", &fn, cudaEnableDefault, &qr);
    EncodeFn enc = (EncodeFn)fn;
    void* p_s;
    cudaGetSymbolAddress(&p_s, g_s);

    CUtensorMap tm_wq, tm_k, tm_v, tm_wo, tm_p, tm_x, tm_d, tm_g, tm_u;
    { cuuint64_t d[2] = {QD, D_}, s[1] = {QD * 2}; cuuint32_t b[2] = {64, 128}; make_map(enc, &tm_wq, wq, 2, d, s, b); }
    { cuuint64_t d[2] = {DH, HKV * S_}, s[1] = {DH * 2}; cuuint32_t b[2] = {64, 128};
      make_map(enc, &tm_k, kc, 2, d, s, b); make_map(enc, &tm_v, vc, 2, d, s, b); }
    { cuuint64_t d[2] = {D_, QD}, s[1] = {D_ * 2}; cuuint32_t b[2] = {64, 128}; make_map(enc, &tm_wo, wo, 2, d, s, b); }
    { cuuint64_t d[3] = {256, 160, NCTA}, s[2] = {1024, 8 * WREG}; cuuint32_t b[3] = {256, 2, 8};
      make_map(enc, &tm_p, ((Scratch*)p_s)->frag, 3, d, s, b, CU_TENSOR_MAP_SWIZZLE_NONE, CU_TENSOR_MAP_DATA_TYPE_UINT32); }
    { cuuint64_t d[2] = {D_ / 4, S_}, s[1] = {D_ * 2}; cuuint32_t b[2] = {XP / 8, 16};
      make_map(enc, &tm_x, x, 2, d, s, b, CU_TENSOR_MAP_SWIZZLE_NONE, CU_TENSOR_MAP_DATA_TYPE_UINT64); }
    { cuuint64_t d[2] = {D_ / 4, F_}, s[1] = {D_ * 2}; cuuint32_t b[2] = {XP / 8, 18};
      make_map(enc, &tm_d, w_down, 2, d, s, b, CU_TENSOR_MAP_SWIZZLE_NONE, CU_TENSOR_MAP_DATA_TYPE_UINT64); }
    { cuuint64_t d[2] = {F_, D_}, s[1] = {F_ * 2}; cuuint32_t b[2] = {40, 24};
      make_map(enc, &tm_g, w_gate, 2, d, s, b, CU_TENSOR_MAP_SWIZZLE_NONE); make_map(enc, &tm_u, w_up, 2, d, s, b, CU_TENSOR_MAP_SWIZZLE_NONE); }

    cudaFuncSetAttribute(fused_kernel<true>, cudaFuncAttributeMaxDynamicSharedMemorySize, SM_TOTAL);
    cudaFuncSetAttribute(fused_kernel<false>, cudaFuncAttributeMaxDynamicSharedMemorySize, SM_TOTAL);
    cudaLaunchConfig_t cfg = {};
    cfg.gridDim = NCTA + 4; cfg.blockDim = 384; cfg.dynamicSmemBytes = SM_TOTAL;
    cudaLaunchAttribute at;
    at.id = cudaLaunchAttributeClusterDimension; at.val.clusterDim.x = 2; at.val.clusterDim.y = 1; at.val.clusterDim.z = 1;
    cfg.attrs = &at; cfg.numAttrs = 1;
    int ncl = 0;
    if (cudaOccupancyMaxActiveClusters(&ncl, fused_kernel<true>, &cfg) != cudaSuccess) { ncl = 0; cudaGetLastError(); }
    Args args{w_mod, cvec, (Scratch*)p_s, out, x, kc, vc, wq, wo, w_r, w_down};
    if (USE_SPARE && ncl >= NCTA / 2 + 2)
        fused_kernel<true><<<NCTA + 4, 384, SM_TOTAL>>>(args, tm_wq, tm_k, tm_v, tm_wo, tm_p, tm_x, tm_d, tm_g, tm_u);
    else
        fused_kernel<false><<<NCTA, 384, SM_TOTAL>>>(args, tm_wq, tm_k, tm_v, tm_wo, tm_p, tm_x, tm_d, tm_g, tm_u);
}
```

```cpp
#include <cuda_runtime.h>
#include <cuda_bf16.h>
#include <cuda.h>
#include <stdint.h>
#include <math.h>

typedef __nv_bfloat16 bf16;

constexpr int S_ = 2048;
constexpr int D_ = 576;
constexpr int HQ = 32, HKV = 16, DH = 128;
constexpr int F_ = 4608;
constexpr int QD = HQ * DH;

constexpr int NCTA = 128;
constexpr int WREG = 5 * 4096;
constexpr int CREP = 8;
constexpr int RSLOT = 144;
constexpr int MREP = 4;
struct Scratch {
    unsigned int epoch[128];
    unsigned int flag_mod[NCTA];
    unsigned int flag_part[16 * 32];
    unsigned int flag_q3[16 * 32];
    unsigned int flag_h[NCTA * 32];
    uint2 mod1[MREP * D_];
    uint32_t mod2[4 * D_];
    uint4 cand[CREP * NCTA * 2];
    uint2 ypart[72 * NCTA * 8];
    uint4 h[2][NCTA * 36 * 32];
    uint4 q3[NCTA * 8 * 128];
    uint4 rows[NCTA * 2 * RSLOT];
    uint8_t frag[NCTA * 8 * WREG];
    uint8_t keep[NCTA * 8 * 4096];
};
__device__ __align__(1024) Scratch g_s;
#define g_h gs->h[tag & 1]
#define g_q3 gs->q3
#define g_keep gs->keep
#define g_flag_h gs->flag_h
#define g_flag_part gs->flag_part
#define g_flag_mod gs->flag_mod
#define g_flag_q3 gs->flag_q3
#define g_frag gs->frag
#define g_cand gs->cand
#define g_ypart gs->ypart
#define g_rows gs->rows

#define DBG_INIT()
#define DBG_P(i)
#define DBG_PG(i)
#define DBG_T(i)
#define DBG_G(i)

__device__ __forceinline__ uint32_t pack_bf16(float lo, float hi) {
    uint32_t r;
    asm("cvt.rn.bf16x2.f32 %0, %1, %2;" : "=r"(r) : "f"(hi), "f"(lo));
    return r;
}
__device__ __forceinline__ float rbf(float x) { return __uint_as_float(pack_bf16(0.f, x)); }
__device__ __forceinline__ float bf_lo(uint32_t v) { return __uint_as_float(v << 16); }
__device__ __forceinline__ float bf_hi(uint32_t v) { return __uint_as_float(v & 0xffff0000u); }
__device__ __forceinline__ float ex2(float x) {
    float y;
    asm("ex2.approx.ftz.f32 %0, %1;" : "=f"(y) : "f"(x));
    return y;
}
template <class T>
__device__ __forceinline__ T* padd(T* p, uint32_t off) {
    unsigned long long r;
    asm("{\n.reg .b32 l, h;\nmov.b64 {l, h}, %1;\nadd.cc.u32 l, l, %2;\naddc.u32 h, h, 0;\nmov.b64 %0, {l, h};\n}" : "=l"(r) : "l"(p), "r"(off));
    return reinterpret_cast<T*>(r);
}
__device__ __forceinline__ uint32_t smem_u32(const void* p) { return (uint32_t)__cvta_generic_to_shared(p); }
__device__ __forceinline__ void mbar_init(uint32_t bar, uint32_t cnt) {
    asm volatile("mbarrier.init.shared::cta.b64 [%0], %1;" ::"r"(bar), "r"(cnt) : "memory");
}
__device__ __forceinline__ void mbar_expect_tx(uint32_t bar, uint32_t bytes) {
    asm volatile("mbarrier.arrive.expect_tx.shared::cta.b64 _, [%0], %1;" ::"r"(bar), "r"(bytes) : "memory");
}
__device__ __forceinline__ void mbar_arrive(uint32_t bar) {
    asm volatile("mbarrier.arrive.shared::cta.b64 _, [%0];" ::"r"(bar) : "memory");
}
__device__ __forceinline__ void mbar_arrive_cluster(uint32_t cluster_addr) {
    asm volatile("mbarrier.arrive.shared::cluster.b64 _, [%0];" ::"r"(cluster_addr) : "memory");
}
constexpr uint32_t SPIN = 1u << 20;
__device__ __forceinline__ void mbar_wait(uint32_t bar, uint32_t parity) {
    asm volatile("{\n.reg .pred p;\n.reg .b32 c;\nmov.b32 c, 0;\n"
                 "W_%=:\nmbarrier.try_wait.parity.shared::cta.b64 p, [%0], %1;\n@p bra D_%=;\n"
                 "add.u32 c, c, 1;\nsetp.lt.u32 p, c, 0x100000;\n@p bra W_%=;\nD_%=:\n}"
                 ::"r"(bar), "r"(parity) : "memory");
}
__device__ __forceinline__ void anchor(uint32_t addr, float v) {
    asm volatile("{\n.reg .pred p;\nsetp.lt.f32 p, %1, 0f00000000;\n@p st.volatile.shared.f32 [%0], %1;\n}" ::"r"(addr), "f"(v) : "memory");
}
__device__ __forceinline__ void anchor(uint32_t addr, uint32_t v) {
    asm volatile("{\n.reg .pred p;\nsetp.eq.u32 p, %1, 0xffffffff;\n@p st.volatile.shared.u32 [%0], %1;\n}" ::"r"(addr), "r"(v) : "memory");
}
__device__ __forceinline__ void hold(float& a, float& b) {
    asm volatile("{\n.reg .pred p;\n.reg .b64 t;\n.reg .b32 l, h;\nmov.u64 t, %%clock64;\nmov.b64 {l, h}, t;\nsetp.eq.u32 p, h, 0xffffffff;\n"
                 "@p mov.f32 %0, 0f00000000;\n@p mov.f32 %1, 0f00000000;\n}" : "+f"(a), "+f"(b) :: "memory");
}
__device__ __forceinline__ void mbar_wait_sleep(uint32_t bar, uint32_t parity) {
    asm volatile("{\n.reg .pred p;\n.reg .b32 c;\nmov.b32 c, 0;\n"
                 "W_%=:\nmbarrier.try_wait.parity.shared::cta.b64 p, [%0], %1, 5000;\n@p bra D_%=;\n"
                 "add.u32 c, c, 1;\nsetp.lt.u32 p, c, 0x20000;\n@p bra W_%=;\nD_%=:\n}"
                 ::"r"(bar), "r"(parity) : "memory");
}
__device__ __forceinline__ uint32_t load_tag(const Scratch* gs) {
    uint32_t tag;
    asm volatile("ld.global.ca.u32 %0, [%1];" : "=r"(tag) : "l"(gs->epoch) : "memory");
    return tag + 1;
}
__device__ __forceinline__ uint4 ld_relaxed(const uint4* p) {
    uint4 v;
    asm volatile("ld.relaxed.gpu.global.v4.u32 {%0,%1,%2,%3}, [%4];" : "=r"(v.x), "=r"(v.y), "=r"(v.z), "=r"(v.w) : "l"(p) : "memory");
    return v;
}
__device__ __forceinline__ void st_relaxed(uint4* p, uint32_t a, uint32_t b, uint32_t c, uint32_t d) {
    asm volatile("{\n.reg .b64 u, v;\nmov.b64 u, {%1, %2};\nmov.b64 v, {%3, %4};\nst.relaxed.gpu.global.v2.b64 [%0], {u, v};\n}"
                 ::"l"(p), "r"(a), "r"(b), "r"(c), "r"(d) : "memory");
}
__device__ __forceinline__ void st_relaxed4(void* p, uint32_t a, uint32_t b, uint32_t c, uint32_t d) {
    asm volatile("st.relaxed.gpu.global.v4.u32 [%0], {%1, %2, %3, %4};" ::"l"(p), "r"(a), "r"(b), "r"(c), "r"(d) : "memory");
}
__device__ __forceinline__ uint2 ld_relaxed8(const void* p) {
    uint2 v;
    asm volatile("ld.relaxed.gpu.global.v2.u32 {%0,%1}, [%2];" : "=r"(v.x), "=r"(v.y) : "l"(p) : "memory");
    return v;
}
__device__ __forceinline__ uint2 ld_relaxed64(const uint2* p) {
    uint2 v;
    asm volatile("{\n.reg .b64 u;\nld.relaxed.gpu.global.b64 u, [%2];\nmov.b64 {%0, %1}, u;\n}" : "=r"(v.x), "=r"(v.y) : "l"(p) : "memory");
    return v;
}
__device__ __forceinline__ void st_relaxed64(uint2* p, uint32_t a, uint32_t b) {
    asm volatile("{\n.reg .b64 u;\nmov.b64 u, {%1, %2};\nst.relaxed.gpu.global.b64 [%0], u;\n}" ::"l"(p), "r"(a), "r"(b) : "memory");
}
__device__ __forceinline__ uint4 ld_relaxed2(const uint4* p) {
    uint4 v;
    asm volatile("{\n.reg .b64 u, w;\nld.relaxed.gpu.global.v2.b64 {u, w}, [%4];\nmov.b64 {%0, %1}, u;\nmov.b64 {%2, %3}, w;\n}"
                 : "=r"(v.x), "=r"(v.y), "=r"(v.z), "=r"(v.w) : "l"(p) : "memory");
    return v;
}
__device__ __forceinline__ void reload16(uint4& v, const void* p, uint32_t& miss) {
    asm volatile("{\n.reg .pred p;\n.reg .b32 m;\n.reg .b64 u, w;\nmax.u32 m, %0, %2;\nsetp.eq.u32 p, m, 0xffffffff;\n"
                 "mov.b64 u, {%0, %1};\nmov.b64 w, {%2, %3};\n@p ld.relaxed.gpu.global.v2.b64 {u, w}, [%5];\n"
                 "mov.b64 {%0, %1}, u;\nmov.b64 {%2, %3}, w;\n@p mov.u32 %4, 1;\n}"
                 : "+r"(v.x), "+r"(v.y), "+r"(v.z), "+r"(v.w), "+r"(miss) : "l"(p) : "memory");
}
__device__ __forceinline__ void reload8(uint2& v, const void* p, uint32_t& miss) {
    asm volatile("{\n.reg .pred p;\n.reg .b64 u;\nsetp.eq.u32 p, %0, 0xffffffff;\nmov.b64 u, {%0, %1};\n"
                 "@p ld.relaxed.gpu.global.b64 u, [%3];\nmov.b64 {%0, %1}, u;\n@p mov.u32 %2, 1;\n}"
                 : "+r"(v.x), "+r"(v.y), "+r"(miss) : "l"(p) : "memory");
}
__device__ __forceinline__ uint32_t ld_relaxed32(const void* p) {
    uint32_t v;
    asm volatile("ld.relaxed.gpu.global.u32 %0, [%1];" : "=r"(v) : "l"(p) : "memory");
    return v;
}
__device__ __forceinline__ void flag_wait(const unsigned int* p, uint32_t tag) {
    uint32_t v, it = 0;
#pragma unroll 1
    do {
        asm volatile("ld.relaxed.gpu.global.u32 %0, [%1];" : "=r"(v) : "l"(p) : "memory");
    } while (__any_sync(0xffffffffu, v != tag) && ++it < SPIN / 16);
    asm volatile("fence.acquire.gpu;" ::: "memory");
    __syncwarp();
}
__device__ __forceinline__ bool elect() {
    uint32_t p;
    asm volatile("{\n.reg .pred p;\nelect.sync _|p, 0xffffffff;\nselp.u32 %0, 1, 0, p;\n}" : "=r"(p));
    return p;
}
__device__ __forceinline__ void flag_release(unsigned int* p, uint32_t tag) {
    asm volatile("st.release.gpu.global.u32 [%0], %1;" ::"l"(p), "r"(tag) : "memory");
}
__device__ __forceinline__ uint32_t touch(const void* p) {
    uint32_t v;
    asm volatile("ld.global.nc.L1::no_allocate.L2::128B.u32 %0, [%1];" : "=r"(v) : "l"(p));
    return v;
}
__device__ __forceinline__ void bar_sync(int id, int n) { asm volatile("bar.sync %0, %1;" ::"r"(id), "r"(n) : "memory"); }
__device__ __forceinline__ void bar_arrive(int id, int n) { asm volatile("bar.arrive %0, %1;" ::"r"(id), "r"(n) : "memory"); }

constexpr uint64_t EVICT_NORMAL = 0x1000000000000000ull, EVICT_FIRST = 0x12F0000000000000ull;
__device__ __forceinline__ void tma2d(uint32_t dst, const CUtensorMap* m, int c0, int c1, uint32_t bar) {
    asm volatile("cp.async.bulk.tensor.2d.shared::cluster.global.mbarrier::complete_tx::bytes.L2::cache_hint [%0], [%1, {%3, %4}], [%2], %5;"
                 ::"r"(dst), "l"(m), "r"(bar), "r"(c0), "r"(c1), "l"(EVICT_FIRST) : "memory");
}
__device__ __forceinline__ void tma2d_mc(uint32_t dst, const CUtensorMap* m, int c0, int c1, uint32_t bar, uint64_t pol) {
    asm volatile("cp.async.bulk.tensor.2d.shared::cluster.global.mbarrier::complete_tx::bytes.multicast::cluster.L2::cache_hint [%0], [%1, {%3, %4}], [%2], %5, %6;"
                 ::"r"(dst), "l"(m), "r"(bar), "r"(c0), "r"(c1), "h"((uint16_t)3), "l"(pol) : "memory");
}
__device__ __forceinline__ void tma3d(uint32_t dst, const CUtensorMap* m, int c0, int c1, int c2, uint32_t bar) {
    asm volatile("cp.async.bulk.tensor.3d.shared::cluster.global.mbarrier::complete_tx::bytes.L2::cache_hint [%0], [%1, {%3, %4, %5}], [%2], %6;"
                 ::"r"(dst), "l"(m), "r"(bar), "r"(c0), "r"(c1), "r"(c2), "l"(EVICT_FIRST) : "memory");
}
__device__ __forceinline__ void bulk_load(uint32_t dst, const void* src, uint32_t bytes, uint32_t bar) {
    asm volatile("cp.async.bulk.shared::cluster.global.mbarrier::complete_tx::bytes [%0], [%1], %2, [%3];"
                 ::"r"(dst), "l"(src), "r"(bytes), "r"(bar) : "memory");
}
__device__ __forceinline__ void l2_prefetch(const void* src, uint32_t bytes) {
    asm volatile("cp.async.bulk.prefetch.L2.global [%0], %1;" ::"l"(src), "r"(bytes) : "memory");
}
__device__ __forceinline__ uint32_t bmul2(uint32_t a, uint32_t b) { uint32_t r; asm("mul.rn.bf16x2 %0, %1, %2;" : "=r"(r) : "r"(a), "r"(b)); return r; }
__device__ __forceinline__ uint32_t badd2(uint32_t a, uint32_t b) { uint32_t r; asm("add.rn.bf16x2 %0, %1, %2;" : "=r"(r) : "r"(a), "r"(b)); return r; }
__device__ __forceinline__ uint32_t bsub2(uint32_t a, uint32_t b) { uint32_t r; asm("sub.rn.bf16x2 %0, %1, %2;" : "=r"(r) : "r"(a), "r"(b)); return r; }
__device__ __forceinline__ uint32_t bmax2(uint32_t a, uint32_t b) { uint32_t r; asm("max.bf16x2 %0, %1, %2;" : "=r"(r) : "r"(a), "r"(b)); return r; }
__device__ __forceinline__ uint32_t bfma2(uint32_t a, uint32_t b, uint32_t c) { uint32_t r; asm("fma.rn.bf16x2 %0, %1, %2, %3;" : "=r"(r) : "r"(a), "r"(b), "r"(c)); return r; }
__device__ __forceinline__ uint4 lds128(uint32_t a) { uint4 v; asm volatile("ld.shared.v4.u32 {%0,%1,%2,%3}, [%4];" : "=r"(v.x), "=r"(v.y), "=r"(v.z), "=r"(v.w) : "r"(a) : "memory"); return v; }
__device__ __forceinline__ uint2 lds64(uint32_t a) { uint2 v; asm volatile("ld.shared.v2.u32 {%0,%1}, [%2];" : "=r"(v.x), "=r"(v.y) : "r"(a) : "memory"); return v; }
__device__ __forceinline__ uint32_t lds32(uint32_t a) { uint32_t v; asm volatile("ld.shared.u32 %0, [%1];" : "=r"(v) : "r"(a) : "memory"); return v; }
__device__ __forceinline__ uint4 ldsm4(uint32_t a) {
    uint4 v;
    asm volatile("ldmatrix.sync.aligned.m8n8.x4.shared.b16 {%0,%1,%2,%3}, [%4];" : "=r"(v.x), "=r"(v.y), "=r"(v.z), "=r"(v.w) : "r"(a) : "memory");
    return v;
}
__device__ __forceinline__ uint4 ldsm4t(uint32_t a) {
    uint4 v;
    asm volatile("ldmatrix.sync.aligned.m8n8.x4.trans.shared.b16 {%0,%1,%2,%3}, [%4];" : "=r"(v.x), "=r"(v.y), "=r"(v.z), "=r"(v.w) : "r"(a) : "memory");
    return v;
}
__device__ __forceinline__ void mma1688(float* d, uint32_t a0, uint32_t a1, uint32_t b) {
    asm("mma.sync.aligned.m16n8k8.row.col.f32.bf16.bf16.f32 {%0,%1,%2,%3}, {%4,%5}, {%6}, {%0,%1,%2,%3};"
        : "+f"(d[0]), "+f"(d[1]), "+f"(d[2]), "+f"(d[3]) : "r"(a0), "r"(a1), "r"(b));
}
__device__ __forceinline__ void mma16816(float* d, uint32_t a0, uint32_t a1, uint32_t a2, uint32_t a3, uint32_t b0, uint32_t b1) {
    asm("mma.sync.aligned.m16n8k16.row.col.f32.bf16.bf16.f32 {%0,%1,%2,%3}, {%4,%5,%6,%7}, {%8,%9}, {%0,%1,%2,%3};"
                 : "+f"(d[0]), "+f"(d[1]), "+f"(d[2]), "+f"(d[3]) : "r"(a0), "r"(a1), "r"(a2), "r"(a3), "r"(b0), "r"(b1));
}
__device__ __forceinline__ void stsm_x4(uint32_t addr, uint32_t a, uint32_t b, uint32_t c, uint32_t d) {
    asm volatile("stmatrix.sync.aligned.m8n8.x4.shared.b16 [%0], {%1, %2, %3, %4};"
                 ::"r"(addr), "r"(a), "r"(b), "r"(c), "r"(d) : "memory");
}

__device__ __forceinline__ uint64_t mkdesc(uint32_t addr, uint32_t lbo, uint32_t sbo) {
    return (uint64_t)((addr & 0x3FFFF) >> 4) | ((uint64_t)(lbo >> 4) << 16) | ((uint64_t)(sbo >> 4) << 32) | (1ull << 62);
}
constexpr uint32_t SM0 = 1024;
__host__ __device__ constexpr uint32_t desc_lo(uint32_t off, uint32_t lbo) { return ((SM0 + off) >> 4) | ((lbo >> 4) << 16); }
__device__ __forceinline__ uint64_t desc_of(uint32_t lo) { return lo | (0x40000040ull << 32); }
#define WG_FENCE() asm volatile("wgmma.fence.sync.aligned;" ::: "memory")
#define WG_COMMIT() asm volatile("wgmma.commit_group.sync.aligned;" ::: "memory")
#define WG_WAIT(n) asm volatile("wgmma.wait_group.sync.aligned %0;" ::"n"(n) : "memory")

#define F8(a, i) "+f"(a[i]), "+f"(a[i + 1]), "+f"(a[i + 2]), "+f"(a[i + 3]), "+f"(a[i + 4]), "+f"(a[i + 5]), "+f"(a[i + 6]), "+f"(a[i + 7])
#define F16(a, i) F8(a, i), F8(a, i + 8)
#define F64(a) F16(a, 0), F16(a, 16), F16(a, 32), F16(a, 48)
#define F32(a) F16(a, 0), F16(a, 16)
#define L64 "%0,%1,%2,%3,%4,%5,%6,%7,%8,%9,%10,%11,%12,%13,%14,%15,%16,%17,%18,%19,%20,%21,%22,%23,%24,%25,%26,%27,%28,%29,%30,%31,%32,%33,%34,%35,%36,%37,%38,%39,%40,%41,%42,%43,%44,%45,%46,%47,%48,%49,%50,%51,%52,%53,%54,%55,%56,%57,%58,%59,%60,%61,%62,%63"
#define L32 "%0,%1,%2,%3,%4,%5,%6,%7,%8,%9,%10,%11,%12,%13,%14,%15,%16,%17,%18,%19,%20,%21,%22,%23,%24,%25,%26,%27,%28,%29,%30,%31"

template <int TB>
__device__ __forceinline__ void mma_rs128(float (&d)[64], uint32_t a0, uint32_t a1, uint32_t a2, uint32_t a3, uint64_t b, int acc) {
    asm volatile("{\n.reg .pred p;\nsetp.ne.b32 p, %69, 0;\n"
                 "wgmma.mma_async.sync.aligned.m64n128k16.f32.bf16.bf16 {" L64 "}, {%64,%65,%66,%67}, %68, p, 1, 1, %70;\n}"
                 : F64(d) : "r"(a0), "r"(a1), "r"(a2), "r"(a3), "l"(b), "r"(acc), "n"(TB));
}
template <int TB>
__device__ __forceinline__ void mma_rs64(float (&d)[32], uint32_t a0, uint32_t a1, uint32_t a2, uint32_t a3, uint64_t b, int acc) {
    asm volatile("{\n.reg .pred p;\nsetp.ne.b32 p, %37, 0;\n"
                 "wgmma.mma_async.sync.aligned.m64n64k16.f32.bf16.bf16 {" L32 "}, {%32,%33,%34,%35}, %36, p, 1, 1, %38;\n}"
                 : F32(d) : "r"(a0), "r"(a1), "r"(a2), "r"(a3), "l"(b), "r"(acc), "n"(TB));
}
template <int N>
__device__ __forceinline__ void fence_regs(float (&d)[N]) {
#pragma unroll
    for (int i = 0; i < N; i++) asm volatile("" : "+f"(d[i])::"memory");
}
template <int N>
__device__ __forceinline__ void fence_regs(uint32_t (&d)[N]) {
#pragma unroll
    for (int i = 0; i < N; i++) asm volatile("" : "+r"(d[i])::"memory");
}

template <int V> struct IC { static constexpr int value = V; };

constexpr int SLOT = 32768, UNIT = 16384;
constexpr int SM_Q = 4 * SLOT;
constexpr int SM_BAR = 7 * SLOT;
constexpr int SM_RED = SM_BAR + 512;
constexpr int SM_TOTAL = SM_BAR + 3072;
constexpr int XP = D_ * 2 + 16;
constexpr int M_MOD = 16 * XP;
constexpr int SM_T = SM_Q + 2 * D_ * 80, SM_TC = SM_T + D_ * 4, SM_TG = SM_TC + D_ * 4, SM_TS = SM_TG + D_ * 2;
constexpr float CS = 0.08838834764831845f * 1.4426950408889634f;
#define LMAX 0.5f
#define LMIN 0x1p-104f
#define USE_SPARE 1
#define MAXG 2
#define SPLIT 10
#define ESPLIT 3
#define PV1 8
#define RW 2
#define HW 2
#define HW2 1
#define XDELAY 200
#define QDELAY 300
#define TMPF 1
#define PFD0 2000
#define PFD1 400
#define HDELAY 300
#define RCM 16
#define RPE 2
#define OSPLIT 6
#define HOLD 1
#define STAGE 11
#define POFF 102.f
#define WF0 3
#define WF1 16
#define C3D 0
#define C4D 300
#define DD 300
#define P2E 0
#define BO 0
#define MAP 2
#define CFULL 0
#define WFE 1
#define OUTD 0
#define OUTPOL EVICT_FIRST
#define SO 0
#define WF2 22
#define OUTP 0
constexpr int PF_KV = 8, PF_WO = 120;

__device__ __forceinline__ int cluster_role() {
    int k;
    asm volatile("mov.u32 %0, %%ctaid.x;" : "=r"(k));
    k >>= 1;
    if (MAP == 0) return k & 63;
    if (MAP == 1) return (k & 7) * 8 + ((k >> 3) & 7);
    if (MAP == 3) {
        asm("mov.u32 %0, %%smid;" : "=r"(k));
        k >>= 1;
        const int r = ((k - 32) * 37) >> 8;
        return k < 32 ? (k & 7) * 8 + (k >> 3) : k < 60 ? (k - 31 - r * 7) * 8 + 4 + r : (k - 58) & 7;
    }
    const int r = ((k - 36) * 37) >> 8, i = k - 36 - r * 7;
    if (MAP == 4) return k < 4 ? 4 + k : k < 36 ? ((k - 4) & 7) * 8 + ((k - 4) >> 3) : (i + 1) * 8 + ((4 + r) & 7);
    return k < 4 ? 12 + k : k < 36 ? ((k - 4) & 7) * 8 + ((k - 4) >> 3) : (i + (i > 0)) * 8 + ((4 + r) & 7);
}

struct Args {
    const bf16 *w_mod, *cvec;
    Scratch* gs;
    bf16* out;
    const bf16 *x, *kc, *vc, *wq, *wo, *w_r, *w_down;
};

__device__ __forceinline__ void frag_store(uint8_t* p, const uint32_t (&a)[32]) {
#pragma unroll
    for (int i = 0; i < 8; i++)
        __stcg(reinterpret_cast<uint4*>(p + i * 512), make_uint4(a[4 * i], a[4 * i + 1], a[4 * i + 2], a[4 * i + 3]));
}
__device__ __forceinline__ void frag_load(uint32_t (&a)[32], const uint8_t* p) {
#pragma unroll
    for (int i = 0; i < 8; i++) {
        const uint4 v = __ldcg(reinterpret_cast<const uint4*>(p + i * 512));
        a[4 * i] = v.x; a[4 * i + 1] = v.y; a[4 * i + 2] = v.z; a[4 * i + 3] = v.w;
    }
}
__device__ __forceinline__ float quad_sum(float v) {
    v += __shfl_xor_sync(0xffffffffu, v, 1);
    return v + __shfl_xor_sync(0xffffffffu, v, 2);
}
__device__ __forceinline__ float quad_max(float v) {
    v = fmaxf(v, __shfl_xor_sync(0xffffffffu, v, 1));
    return fmaxf(v, __shfl_xor_sync(0xffffffffu, v, 2));
}
__device__ __forceinline__ float rcp_fast(float x) { float y; asm("rcp.approx.ftz.f32 %0, %1;" : "=f"(y) : "f"(x)); return y; }
__device__ __forceinline__ float sigmoidf_(float x) { return rcp_fast(1.f + ex2(-1.4426950408889634f * x)); }
__device__ __forceinline__ void top2(uint32_t k, uint32_t& k1, uint32_t& k2) {
    k1 = __reduce_max_sync(0xffffffffu, k);
    k2 = __reduce_max_sync(0xffffffffu, k == k1 ? 0 : k);
}

__device__ __forceinline__ void mod_fma(float (&a)[8], const uint4 w, float sc) {
    a[0] += sc * bf_lo(w.x); a[1] += sc * bf_hi(w.x); a[2] += sc * bf_lo(w.y); a[3] += sc * bf_hi(w.y);
    a[4] += sc * bf_lo(w.z); a[5] += sc * bf_hi(w.z); a[6] += sc * bf_lo(w.w); a[7] += sc * bf_hi(w.w);
}
__device__ __forceinline__ float mod_reduce(float (&a)[8], int lane) {
#pragma unroll
    for (int h = 4; h > 0; h >>= 1) {
        const bool up = lane & (8 / h);
#pragma unroll
        for (int i = 0; i < h; i++)
            a[i] = (up ? a[i + h] : a[i]) + __shfl_xor_sync(0xffffffffu, up ? a[i] : a[i + h], 8 / h);
    }
    return a[0] + __shfl_xor_sync(0xffffffffu, a[0], 16);
}

__device__ __forceinline__ float ln_stats(float sum, float sq, uint32_t& mean2) {
    const float mean = sum * (1.f / D_);
    const float var = fmaxf(fmaf(-mean, mean, sq * (1.f / D_)), 0.f);
    float sd;
    asm("sqrt.approx.ftz.f32 %0, %1;" : "=f"(sd) : "f"(rbf(rbf(var) + 1e-5f)));
    mean2 = pack_bf16(mean, mean);
    return rcp_fast(rbf(sd));
}
__device__ __forceinline__ uint32_t ln_pair(uint32_t x, uint32_t mean2, float rsd) {
    const uint32_t d = bsub2(x, mean2);
    return pack_bf16(bf_lo(d) * rsd, bf_hi(d) * rsd);
}
__device__ __forceinline__ void rows_load(uint32_t (&x)[20], uint32_t xs, int cw) {
#pragma unroll
    for (int ch = 0; ch < 5; ch++) {
        const uint4 v = ldsm4(ch < 4 ? xs + ch * 256 : xs + 1024 - cw * 16);
        x[4 * ch] = v.x; x[4 * ch + 1] = v.y; x[4 * ch + 2] = v.z; x[4 * ch + 3] = v.w;
    }
}
__device__ __forceinline__ void stats_add(float (&st)[12], uint32_t a, uint32_t b, uint32_t w) {
    mma1688(st, a, b, w);
    mma1688(st + 4, a, b, a);
    mma1688(st + 8, a, b, b);
}
__device__ __forceinline__ float rows_stats(const float (&st)[12], float4* rec, int cw, int lane, uint32_t& mean2, float& dot) {
    const int g8 = lane >> 2;
    if ((g8 >> 1) == (lane & 3)) {
        rec[cw * 16 + g8] = make_float4(st[0], (g8 & 1) ? st[5] : st[4], st[1], 0.f);
        rec[cw * 16 + 8 + g8] = make_float4(st[2], (g8 & 1) ? st[11] : st[10], st[3], 0.f);
    }
    bar_sync(3, 256);
    const float4* r = rec + (lane >> 4) * 64 + (lane & 15);
    const float4 s0 = r[0], s1 = r[16], s2 = r[32], s3 = r[48];
    const float sum = (s0.x + s1.x) + (s2.x + s3.x), sq = (s0.y + s1.y) + (s2.y + s3.y);
    dot = (s0.z + s1.z) + (s2.z + s3.z);
    dot += __shfl_xor_sync(0xffffffffu, dot, 16);
    return ln_stats(sum + __shfl_xor_sync(0xffffffffu, sum, 16), sq + __shfl_xor_sync(0xffffffffu, sq, 16), mean2);
}
template <class F>
__device__ __forceinline__ void rows_normalise(uint32_t* y, const uint32_t* x, uint32_t mean2, float rsd, int lane, F loads) {
    const int g8 = lane >> 2;
    const uint32_t ma2 = __shfl_sync(0xffffffffu, mean2, g8), mb2 = __shfl_sync(0xffffffffu, mean2, g8 + 8);
    const float ra = __shfl_sync(0xffffffffu, rsd, g8), rb = __shfl_sync(0xffffffffu, rsd, g8 + 8);
    loads();
#pragma unroll
    for (int k = 0; k < 9; k++) { y[2 * k] = ln_pair(x[2 * k], ma2, ra); y[2 * k + 1] = ln_pair(x[2 * k + 1], mb2, rb); }
}

__device__ __forceinline__ uint4 h_frag(const uint4* hf, int ks, int lane) {
    if (ks < 32) return ld_relaxed2(hf + ks * 32);
    const uint2* p = reinterpret_cast<const uint2*>(padd(hf, 256 - lane * 8) + ks * 32 - 16);
    const uint2 a = ld_relaxed64(p), b = ld_relaxed64(p + 32);
    return make_uint4(a.x, a.y, b.x, b.y);
}

__device__ __noinline__ void attn_fallback(uint32_t bad, uint32_t tag, const Scratch* gs, uint8_t* frag, uint8_t* keep, const bf16* wq, const bf16* kc, const bf16* vc) {
  const int lane = threadIdx.x & 31, g8 = lane >> 2, qd = lane & 3;
  const int role = cluster_role(), j = role & 7, qb = (role >> 3) * 2 + (blockIdx.x & 1);
  const uint4* hf = g_h + (size_t)(qb * 8 + (threadIdx.x >> 5) - 4) * (36 * 32) + lane;
#pragma unroll 1
  for (int t = 0; t < 4; t++) {
    if (!((bad >> t) & 1)) continue;
    const bf16 *wqp = wq + (4 * j + t) * DH, *kp = kc + (size_t)(2 * j + (t >> 1)) * S_ * DH, *vp = vc + (size_t)(2 * j + (t >> 1)) * S_ * DH;
    uint32_t q[32];
    float o[64];
#pragma unroll
    for (int i = 0; i < 64; i++) o[i] = 0.f;
#pragma unroll 1
    for (int ks = 0; ks < 36; ks++) {
        const uint4 a = h_frag(hf, ks, lane);
        const unsigned short* wr = reinterpret_cast<const unsigned short*>(wqp + (size_t)(ks * 16 + 2 * qd) * QD + g8);
#pragma unroll
        for (int dt = 0; dt < 16; dt++) {
            const uint32_t b0 = __ldg(wr + dt * 8) | ((uint32_t)__ldg(wr + dt * 8 + QD) << 16);
            const uint32_t b1 = __ldg(wr + dt * 8 + 8 * QD) | ((uint32_t)__ldg(wr + dt * 8 + 9 * QD) << 16);
            mma16816(o + 4 * dt, a.x, a.y, a.z, a.w, b0, b1);
        }
    }
#pragma unroll
    for (int i = 0; i < 32; i++) q[i] = pack_bf16(o[2 * i], o[2 * i + 1]);
#pragma unroll
    for (int i = 0; i < 64; i++) o[i] = 0.f;
    float m0 = -INFINITY, m1 = -INFINITY, l0 = 0.f, l1 = 0.f;
#pragma unroll 1
    for (int key = 0; key < S_; key += 16) {
        float sc[8];
#pragma unroll
        for (int i = 0; i < 8; i++) sc[i] = 0.f;
#pragma unroll
        for (int nt = 0; nt < 2; nt++) {
            const uint32_t* kr = reinterpret_cast<const uint32_t*>(kp + (size_t)(key + nt * 8 + g8) * DH) + qd;
#pragma unroll
            for (int ks = 0; ks < 8; ks++)
                mma16816(sc + 4 * nt, q[4 * ks], q[4 * ks + 1], q[4 * ks + 2], q[4 * ks + 3], __ldg(kr + ks * 8), __ldg(kr + ks * 8 + 4));
        }
        const float n0 = quad_max(fmaxf(fmaxf(m0, fmaxf(sc[0], sc[1])), fmaxf(sc[4], sc[5])));
        const float n1 = quad_max(fmaxf(fmaxf(m1, fmaxf(sc[2], sc[3])), fmaxf(sc[6], sc[7])));
        const float f0 = ex2((m0 - n0) * CS), f1 = ex2((m1 - n1) * CS);
        m0 = n0; m1 = n1;
#pragma unroll
        for (int i = 0; i < 8; i++) sc[i] = ex2((sc[i] - ((i & 2) ? n1 : n0)) * CS);
        l0 = l0 * f0 + (sc[0] + sc[1]) + (sc[4] + sc[5]);
        l1 = l1 * f1 + (sc[2] + sc[3]) + (sc[6] + sc[7]);
        const uint32_t e0 = pack_bf16(sc[0], sc[1]), e1 = pack_bf16(sc[2], sc[3]), e2 = pack_bf16(sc[4], sc[5]), e3 = pack_bf16(sc[6], sc[7]);
        const unsigned short* vr = reinterpret_cast<const unsigned short*>(vp + (size_t)(key + 2 * qd) * DH + g8);
#pragma unroll
        for (int dt = 0; dt < 16; dt++) {
            o[4 * dt] *= f0; o[4 * dt + 1] *= f0; o[4 * dt + 2] *= f1; o[4 * dt + 3] *= f1;
            const uint32_t b0 = __ldg(vr + dt * 8) | ((uint32_t)__ldg(vr + dt * 8 + DH) << 16);
            const uint32_t b1 = __ldg(vr + dt * 8 + 8 * DH) | ((uint32_t)__ldg(vr + dt * 8 + 9 * DH) << 16);
            mma16816(o + 4 * dt, e0, e1, e2, e3, b0, b1);
        }
    }
    const float i0 = 1.f / quad_sum(l0), i1 = 1.f / quad_sum(l1);
#pragma unroll
    for (int i = 0; i < 16; i++) {
        q[2 * i] = pack_bf16(o[4 * i] * i0, o[4 * i + 1] * i0);
        q[2 * i + 1] = pack_bf16(o[4 * i + 2] * i1, o[4 * i + 3] * i1);
    }
    frag_store(t < 3 ? frag + t * 4096 : keep, q);
  }
}

__device__ __forceinline__ void spare_q3(Scratch* gs, uint32_t sb, uint32_t bar_full, uint32_t bar_empty, int lane, int cw) {
    const uint32_t tag = load_tag(gs);
    uint32_t rel_base, e = 3;
    asm("mapa.shared::cluster.u32 %0, %1, %2;" : "=r"(rel_base) : "r"(bar_empty), "r"(lane & 1));
#pragma unroll 1
    for (int qb = blockIdx.x - NCTA; qb < 16; qb += 4) {
        uint32_t h[144];
        float o[64];
        flag_wait(&g_flag_h[(qb * 8 + cw) * 32], tag);
        const uint4* hf = g_h + (size_t)(qb * 8 + cw) * (36 * 32) + lane;
#pragma unroll
        for (int ks = 0; ks < 36; ks++) {
            const uint4 v = h_frag(hf, ks, lane);
            h[4 * ks] = v.x; h[4 * ks + 1] = v.y; h[4 * ks + 2] = v.z; h[4 * ks + 3] = v.w;
        }
#pragma unroll
        for (int i = 0; i < 64; i++) o[i] = 0.f;
#pragma unroll 1
        for (int v = 0; v < 4; v++) {
            fence_regs(o);
#pragma unroll
            for (int t = 0; t < 5; t++) {
                mbar_wait(bar_full + 8 * (e & 3), (e >> 2) & 1);
                const uint64_t dv = mkdesc(sb + (e & 3) * SLOT, UNIT, 1024);
                WG_FENCE();
#pragma unroll
                for (int ks = 0; ks < (t < 4 ? 8 : 4); ks++)
                    mma_rs128<1>(o, h[32 * t + 4 * ks], h[32 * t + 4 * ks + 1], h[32 * t + 4 * ks + 2], h[32 * t + 4 * ks + 3], dv + ks * 128, ks | t);
                WG_COMMIT();
                if (t > 0) { WG_WAIT(1); if (lane < 2) mbar_arrive_cluster(rel_base + 8 * ((e - 1) & 3)); }
                e++;
            }
            WG_WAIT(0);
            fence_regs(o);
            if (lane < 2) mbar_arrive_cluster(rel_base + 8 * ((e - 1) & 3));
            uint4* dst = &g_q3[((qb * 8 + 2 * v) * 8 + cw) * 128 + lane];
#pragma unroll
            for (int i = 0; i < 8; i++)
                __stcg(dst + (i >> 2) * 1024 + (i & 3) * 32, make_uint4(pack_bf16(o[8 * i], o[8 * i + 1]), pack_bf16(o[8 * i + 2], o[8 * i + 3]),
                                                                        pack_bf16(o[8 * i + 4], o[8 * i + 5]), pack_bf16(o[8 * i + 6], o[8 * i + 7])));
        }
        bar_sync(3, 256);
        if (cw == 0 && lane == 0) flag_release(&g_flag_q3[qb * 32], tag);
        __syncwarp();
    }
}

template <bool SPARE>
__global__ void __cluster_dims__(2, 1, 1) __launch_bounds__(384, 1)
fused_kernel(const Args args, const __grid_constant__ CUtensorMap tm_wq,
             const __grid_constant__ CUtensorMap tm_k, const __grid_constant__ CUtensorMap tm_v,
             const __grid_constant__ CUtensorMap tm_wo, const __grid_constant__ CUtensorMap tm_p,
             const __grid_constant__ CUtensorMap tm_x, const __grid_constant__ CUtensorMap tm_d,
             const __grid_constant__ CUtensorMap tm_g, const __grid_constant__ CUtensorMap tm_u) {
    extern __shared__ __align__(1024) uint8_t smem_raw[];
    const uint32_t sb = smem_u32(smem_raw);
    Scratch* const gs = args.gs;
    const uint32_t bar_full = sb + SM_BAR;
    const uint32_t bar_g = bar_full + 8 * 4;
    const uint32_t bar_mod = bar_g + 8;
    const uint32_t bar_go = bar_mod + 8;
    const uint32_t bar_x = bar_go + 40;
    const uint32_t bar_empty = bar_x + 8;
    const uint32_t bar_pub = bar_empty + 8 * 4;
    const uint32_t bar_qfree = bar_pub + 32;
    const uint32_t bar_out = bar_qfree + 24;
    const uint32_t bar_q3 = bar_out + 8;
    const uint32_t bar_pre = bar_q3 + 16;
    const uint32_t bar_w0 = bar_q3 + 8;
    constexpr int E0 = SPARE ? 2 : 0;

    const int c = blockIdx.x & 1;
#define ROLES() const int role = cluster_role(), j = role & 7, qb = (role >> 3) * 2 + c, rg = qb * 8 + j
    const int warp = __shfl_sync(0xffffffffu, threadIdx.x >> 5, 0);

    if (SPARE && blockIdx.x >= NCTA && warp >= 4) {
        asm volatile("barrier.cluster.arrive.relaxed.aligned;" ::: "memory");
        asm volatile("setmaxnreg.inc.sync.aligned.u32 240;");
        asm volatile("barrier.cluster.wait.aligned;" ::: "memory");
        spare_q3(gs, sb, bar_full, bar_empty, threadIdx.x & 31, warp - 4);
        asm volatile("barrier.cluster.arrive.relaxed.aligned;\nbarrier.cluster.wait.aligned;" ::: "memory");
    } else if (warp < 4) {
        asm volatile("setmaxnreg.dec.sync.aligned.u32 24;");
        ROLES();
        int lane;
        asm volatile("mov.u32 %0, %%laneid;" : "=r"(lane));
        if (warp == 2 && elect()) {
            if (TMPF) asm volatile("prefetch.tensormap [%0];" ::"l"(&tm_x) : "memory");
#pragma unroll
            for (int i = 0; i < 27; i++) mbar_init(bar_full + 8 * i, i < 12 || i >= 23 ? 1 : i < 16 ? 16 : 8);
#pragma unroll
            for (int i = 0; i <= E0; i++) {
                mbar_arrive(bar_full + 8 * i);
                asm volatile("mbarrier.arrive.shared::cta.b64 _, [%0], 16;" ::"r"(bar_empty + 8 * i) : "memory");
            }
            asm volatile("fence.mbarrier_init.release.cluster;" ::: "memory");
        }
        __syncwarp();
        asm volatile("barrier.cluster.arrive.relaxed.aligned;" ::: "memory");
        if (warp == 2 && !(SPARE && blockIdx.x >= NCTA)) {
            if (XDELAY) __nanosleep(XDELAY);
            if (elect()) {
                mbar_expect_tx(bar_x, 16 * XP);
                tma2d(sb + SM_Q, &tm_x, 0, rg * 16, bar_x);
            }
            __syncwarp();
        }
        asm volatile("barrier.cluster.wait.aligned;" ::: "memory");
        const uint32_t tag = load_tag(gs);
        if (SPARE && blockIdx.x >= NCTA) {
            if (warp == 1) {
#pragma unroll 1
                for (int e = 3; e < 83; e++) {
                    const int v = (e - 3) / 5;
                    mbar_wait_sleep(bar_empty + 8 * (e & 3), ~(e >> 2) & 1);
                    if (elect()) {
                        mbar_expect_tx(bar_full + 8 * (e & 3), SLOT);
                        tma2d_mc(sb + (e & 3) * SLOT + c * UNIT, &tm_wq, (8 * (v & 3) + 4 * c + 3) * DH + 64, (e - 3 - v * 5) * 128,
                                 bar_full + 8 * (e & 3), EVICT_NORMAL);
                    }
                }
            }
            __syncwarp();
            asm volatile("barrier.cluster.arrive.relaxed.aligned;\nbarrier.cluster.wait.aligned;" ::: "memory");
            return;
        }
        if (warp == 3) {
#pragma unroll 1
            for (int e = 4; e < 20; e++) {
                __nanosleep(e == 4 ? PFD0 : PFD1);
                const int hd = (e * 52) >> 8, row = (e - hd * 5) * 128 + qb * 8 + (lane >> 1);
                if (lane < 16 && row < D_)
                    asm volatile("prefetch.global.L2 [%0];" ::"l"(padd(args.wq, (row * QD + (4 * j + ((0x1320 >> (4 * hd)) & 3)) * DH + (lane & 1) * 64) * 2)) : "memory");
            }
            __syncwarp();
            mbar_wait_sleep(bar_go, 0);
#pragma unroll 1
            for (int unit = 72 + blockIdx.x; unit < 216; unit += NCTA) {
                float a[8];
#pragma unroll
                for (int i = 0; i < 8; i++) a[i] = 0.f;
#pragma unroll 1
                for (int k = lane >> 1; k < D_; k += 16) {
                    const float cv = __bfloat162float(*padd(args.cvec, k * 2));
                    mod_fma(a, __ldg(reinterpret_cast<const uint4*>(padd(args.w_mod, (k * (6 * D_) + unit * 16 + (lane & 1) * 8) * 2))), rbf(cv * sigmoidf_(cv)));
                }
                const float v = mod_reduce(a, lane), v1 = __shfl_down_sync(0xffffffffu, v, 8);
                if (lane < 8) *padd(gs->mod2, ((unit - 72) * 8 + (lane & 1) * 4 + (lane & 2) + (lane >> 2)) * 4) = pack_bf16(v, v1);
            }
            __syncwarp();
            if (lane == 0) flag_release(padd(g_flag_mod, blockIdx.x * 4), tag);
#pragma unroll 1
            for (int k = 0; k < 36; k++) {
                __nanosleep(200);
                __stcg(padd(gs->h[0], (~tag & 1) * (NCTA * 36 * 512) + ((rg * 36 + k) * 32 + lane) * 16), make_uint4(0, 0, 0, 0));
            }
            __syncwarp();
            mbar_wait_sleep(bar_qfree + 16, 0);
            __nanosleep(2000);
            {
                uint4 v;
                uint32_t it = 0;
#pragma unroll 1
                do {
                    v = ld_relaxed(reinterpret_cast<const uint4*>(padd(g_flag_mod, lane * 16)));
                } while (((v.x ^ tag) | (v.y ^ tag) | (v.z ^ tag) | (v.w ^ tag)) && ++it < SPIN / 16);
                asm volatile("fence.acquire.gpu;" ::: "memory");
            }
            __syncwarp();
            {
                float w1 = 0.f, w2 = 0.f;
#pragma unroll 1
                for (int k = lane; k < D_ / 2; k += 32) {
                    const uint32_t* mp = padd(gs->mod2, k * 4);
                    const uint32_t sv = __ldcg(mp + D_ / 2), c1 = badd2(__ldcg(mp + D_), 0x3f803f80u);
                    const uint32_t wr = *reinterpret_cast<const uint32_t*>(padd(args.w_r, k * 4)), wp = bmul2(c1, wr);
                    reinterpret_cast<uint2*>(smem_raw + SM_T)[k] = make_uint2(__ldcg(mp), wp);
                    reinterpret_cast<uint2*>(smem_raw + SM_TC)[k] = make_uint2(c1, sv);
                    reinterpret_cast<uint32_t*>(smem_raw + SM_TG)[k] = __ldcg(mp + 3 * D_ / 2);
                    w1 += bf_lo(wp) + bf_hi(wp);
                    w2 += bf_lo(sv) * bf_lo(wr) + bf_hi(sv) * bf_hi(wr);
                }
#pragma unroll 1
                for (int i = 1; i < 32; i <<= 1) { w1 += __shfl_xor_sync(0xffffffffu, w1, i); w2 += __shfl_xor_sync(0xffffffffu, w2, i); }
                *reinterpret_cast<float2*>(smem_raw + SM_TS) = make_float2(w1, w2);
            }
#pragma unroll
            for (int i = 0; i < 4; i++) reinterpret_cast<uint4*>(smem_raw + SM_RED)[lane + 32 * i] = make_uint4(~0u, ~0u, ~0u, ~0u);
            asm volatile("fence.proxy.async.shared::cta;" ::: "memory");
            __syncwarp();
            if (elect()) {
                uint8_t* mb = g_frag + (size_t)rg * 8 * WREG + 3 * 4096;
#pragma unroll 1
                for (int k = 0; k < 8; k++, mb += WREG) {
#pragma unroll
                    for (int i = 0; i < 3; i++)
                        asm volatile("cp.async.bulk.global.shared::cta.bulk_group [%0], [%1], 2048;" ::"l"(mb + i * 2048), "r"(sb + SM_RED) : "memory");
                    __nanosleep(500);
                }
                asm volatile("cp.async.bulk.commit_group;\ncp.async.bulk.wait_group 0;\nfence.proxy.async.global;" ::: "memory");
            }
            __syncwarp();
            if (lane == 0) mbar_arrive(bar_mod);
            __syncwarp();
            mbar_wait_sleep(bar_go + 8, 0);
            if (elect()) asm volatile("prefetch.tensormap [%0];\nprefetch.tensormap [%1];\nprefetch.tensormap [%2];" ::"l"(&tm_x), "l"(&tm_p), "l"(&tm_d) : "memory");
            __syncwarp();
#pragma unroll 1
            for (int i = 1; i < 4; i++) {
                mbar_wait(bar_pub + 8 * i, 0);
                unsigned int* flags = padd(g_flag_part, (qb * 32 + i * 8 - 8) * 4);
                if (elect()) { flag_release(padd(flags, j * 4), tag); DBG_PG(93); }
                __syncwarp();
                const uint32_t slot = i < 3 ? i + 1 : 1;
                flag_wait(padd(flags, (lane & 7) * 4), tag);
                asm volatile("fence.proxy.async.global;" ::: "memory");
                if (lane == 0 && i == 3) DBG_PG(101);
                mbar_wait(bar_go + 8 + 8 * i, 0);
                mbar_wait(bar_empty + 8 * slot, i != 1);
                if (elect()) {
                    mbar_expect_tx(bar_full + 8 * slot, SLOT);
                    tma3d(sb + slot * SLOT, &tm_p, 0, j * 20 + (i - 1) * 4, qb * 8, bar_full + 8 * slot);
                    tma3d(sb + slot * SLOT + UNIT, &tm_p, 0, j * 20 + (i - 1) * 4 + 2, qb * 8, bar_full + 8 * slot);
                }
            }
        } else if (warp == 0) {
#pragma unroll 1
            for (int i = 0; i < 48; i++) {
                if (i == 0 || i == 17 || i == 34) mbar_wait_sleep(bar_qfree + (i >> 4) * 8, 0);
                if (SPARE && i == 17) {
                    flag_wait(&g_flag_q3[qb * 32], tag);
                    if (elect()) {
                        asm volatile("fence.proxy.async.global;" ::: "memory");
                        mbar_expect_tx(bar_q3, UNIT);
#pragma unroll 1
                        for (int k = 0; k < 8; k++) bulk_load(sb + SM_Q + 2 * SLOT + k * 4096 + 2048, &g_q3[(rg * 8 + k) * 128], 2048, bar_q3);
                    }
                }
                __nanosleep(700);
                if (elect()) {
                    asm volatile("mbarrier.expect_tx.shared::cta.b64 [%0], %1;" ::"r"(bar_g), "n"(1920) : "memory");
                    tma2d(sb + SM_Q + i * 1920, i < 24 ? &tm_g : &tm_u, (blockIdx.x * 36) & ~7, (i < 24 ? i : i - 24) * 24, bar_g);
                }
            }
            if (elect()) mbar_arrive(bar_g);
#pragma unroll 1
            for (int i = 0; i < 18; i++) {
                __nanosleep(400);
                if (elect()) l2_prefetch(args.w_down + (size_t)(blockIdx.x * 36 + i * 2) * D_, 4 * D_);
            }
            __syncwarp();
            mbar_wait_sleep(bar_go + 8 * 2, 0);
            uint32_t acc = 0;
#pragma unroll 1
            for (int k = lane; k < 16 * 9; k += 32) acc |= touch(padd(args.x, (rg * 16 * D_ + k * 64) * 2));
            if (acc == 0) reinterpret_cast<volatile uint32_t*>(smem_raw + SM_BAR)[127] = acc;
            __syncwarp();
            mbar_wait_sleep(bar_go + 8 * 4, 0);
            uint4* rp = padd(g_rows, (rg * 2 * RSLOT + lane) * 16);
#pragma unroll
            for (int k = 0; k < 9; k++) rp[k * 32] = make_uint4(~0u, ~0u, ~0u, ~0u);
            if (blockIdx.x < 72) {
                uint4* yp = reinterpret_cast<uint4*>(padd(g_ypart, blockIdx.x * NCTA * 64 + lane * 16));
#pragma unroll
                for (int k = 0; k < 16; k++) yp[k * 32] = make_uint4(~0u, ~0u, ~0u, ~0u);
            }
            asm volatile("fence.acq_rel.gpu;" ::: "memory");
            __syncwarp();
            if (lane == 0) mbar_arrive(bar_pre);
        } else if (warp == 1) {
            __nanosleep(QDELAY);
            uint32_t go = bar_go;
            uint64_t marks = 24 | 151 << 8 | 154 << 16 | 159ull << 24 | 165ull << 32;
#pragma unroll 1
            for (int e = E0; e < 168; e++) {
                const CUtensorMap* tm;
                int c0, c1;
                uint64_t pol = EVICT_FIRST;
                if (e == 158 || e == 163) continue;
                if (e < 21 && e != 19) {
                    const int i = SPARE && e < 12 ? e - 2 : e - (e == 20), hd = (i * 52) >> 8;
                    tm = &tm_wq; c0 = (4 * j + ((0x1320 >> (4 * hd)) & 3)) * DH + c * 64; c1 = (i - hd * 5) * 128 - 64;
                    if (SPARE && e >= 12 && e < 15) { c0 = (4 * j + 3) * DH; c1 = (2 * (e - 12) + c) * 128; }
                } else if (e < 148) {
                    const int i = max(e - 20, 0);
                    const bool isk = i == 0 || ((i & 1) && i < 127);
                    const int n = isk ? (i + 1) >> 1 : (i - 1) >> 1;
                    tm = isk ? &tm_k : &tm_v; c0 = c * 64; c1 = (2 * j + (n >> 5)) * S_ + (n & 15) * 128;
                    if (!(i & 32)) pol = EVICT_NORMAL;
                } else {
                    int i = e - 148 - (e > 158) - (e > 163);
                    tm = &tm_wo; c0 = (i >> 1) * 64; c1 = (4 * j + ((i & 1) ? 1 + c : 3 * c)) * DH;
                }
                const uint32_t fb = e == E0 ? bar_w0 : bar_full + 8 * (e & 3), d = sb + (e == E0 ? 6 : e & 3) * SLOT;
                if (e >= 24 && e < 152) mbar_wait_sleep(bar_empty + 8 * (e & 3), ~(e >> 2) & 1);
                else if (e != E0) mbar_wait(bar_empty + 8 * (e & 3), ~(e >> 2) & 1);
                if (elect()) {
                    mbar_expect_tx(fb, SLOT);
                    tma2d_mc(d + c * UNIT, tm, c0, c1, fb, pol);
                    const int i = e - PF_KV;
                    if (i >= 0 && i < 128 && !(i & 32))
                        l2_prefetch(((i & 1) ? args.vc : args.kc) + (size_t)((2 * j + (i >> 6)) * S_ + (i & 30) * 64) * DH + qb * 1024, 2048);
                    if (e >= PF_WO && e < PF_WO + 18) l2_prefetch(args.wo + (size_t)blockIdx.x * (QD * D_ / NCTA) + (e - PF_WO) * 1024, 2048);
                    if (e == (marks & 255)) mbar_arrive(go);
                }
                if (e == (marks & 255)) { go += 8; marks >>= 8; }
            }
            asm volatile("fence.proxy.async.global;" ::: "memory");
            mbar_wait(bar_empty, 1);
            if (elect()) {
                mbar_expect_tx(bar_full, 16 * XP);
                tma2d(sb, &tm_x, 0, rg * 16, bar_full);
            }
            mbar_wait(bar_empty + 16, 1);
            if (C3D) __nanosleep(C3D);
            if (elect()) {
                mbar_expect_tx(bar_full + 16, SLOT);
                tma3d(sb + 2 * SLOT, &tm_p, 0, j * 20 + 12, qb * 8, bar_full + 16);
                tma3d(sb + 2 * SLOT + UNIT, &tm_p, 0, j * 20 + 14, qb * 8, bar_full + 16);
            }
            mbar_wait(bar_empty + 24, 1);
            if (C4D) __nanosleep(C4D);
            if (elect()) {
                mbar_expect_tx(bar_full + 24, UNIT);
                tma3d(sb + 3 * SLOT, &tm_p, 0, j * 20 + 16, qb * 8, bar_full + 24);
            }
            mbar_wait(bar_empty + 8, 0);
            mbar_wait(bar_empty + 16, 0);
            if (DD) __nanosleep(DD);
            if (elect()) {
#pragma unroll
                for (int i = 1; i < 3; i++) {
                    mbar_expect_tx(bar_full + 8 * i, 18 * XP);
                    tma2d(sb + i * SLOT, &tm_d, 0, blockIdx.x * 36 + (i - 1) * 18, bar_full + 8 * i);
                }
            }
        } else {
            if (elect()) asm volatile("prefetch.tensormap [%0];\nprefetch.tensormap [%1];\nprefetch.tensormap [%2];" ::"l"(&tm_k), "l"(&tm_v), "l"(&tm_wo) : "memory");
            if (SPARE) {
                mbar_wait_sleep(bar_pub, 0);
                if (lane == 0) flag_release(padd(g_flag_h, rg * 128), tag);
                __syncwarp();
            }
            bar_sync(1, 192);
#pragma unroll 1
            for (uint32_t e = 20; e < 148; e++) {
                mbar_wait_sleep(bar_full + 8 * (e & 3), (e >> 2) & 1);
                if (e & 1) bar_sync(1, 192);
                if (!(e & 1) || e == 147) bar_sync(4, 160);
            }
#pragma unroll 1
            for (uint32_t e = 148; e < 168; e++) {
                mbar_wait(bar_full + 8 * (e & 3), (e >> 2) & 1);
                if (e != 158 && e != 163) bar_sync(1, 192);
            }
        }
        __syncwarp();
        mbar_wait_sleep(bar_out, 0);
        if (OUTD) __nanosleep(OUTD);
        if (elect()) {
            asm volatile("fence.proxy.async.shared::cta;" ::: "memory");
            const int2 sel = reinterpret_cast<const int2*>(smem_raw + SM_RED)[8];
#pragma unroll 1
            for (int i = warp; i < 16; i += 4) {
                const int row = rg * 16 + i;
                if (row != sel.x && row != sel.y)
                    asm volatile("cp.async.bulk.global.shared::cta.bulk_group.L2::cache_hint [%0], [%1], %2, %3;"
                                 ::"l"(args.out + (size_t)row * D_), "r"(sb + i * XP), "n"(D_ * 2), "l"(OUTPOL) : "memory");
            }
            asm volatile("cp.async.bulk.commit_group;\ncp.async.bulk.wait_group 0;" ::: "memory");
        }
    } else {
        uint32_t cv[2] = {0, 0}, tag = load_tag(gs) - 1;
        if (blockIdx.x < 72) {
            uint32_t ws;
            int tid;
            asm volatile("mov.u32 %0, smem_raw;\nmov.u32 %1, %%tid.x;" : "=r"(ws), "=r"(tid));
            tid -= 128;
            ws += SM_Q + SLOT + tid * 16;
            const uint32_t* cp = padd(reinterpret_cast<const uint32_t*>(args.cvec), (tid & 0xe0) + (tid & 7) * 4);
            cv[0] = *padd(cp, (tid & 24) * 32);
            if (tid < 128) cv[1] = cp[256];
            const bf16* wrow = args.w_mod + (size_t)(tid >> 1) * (6 * D_) + (tid & 1) * 8 + blockIdx.x * 16;
#pragma unroll
            for (int i = 0; i < 5; i++)
                if (i < 4 || tid < 128)
                    asm volatile("cp.async.cg.shared.global [%0], [%1], 16;" ::"r"(ws + i * 4096), "l"(wrow + (size_t)i * 128 * (6 * D_)) : "memory");
        }
        asm volatile("barrier.cluster.arrive.relaxed.aligned;" ::: "memory");
        asm volatile("setmaxnreg.inc.sync.aligned.u32 240;");
        const int lane = threadIdx.x & 31;
        const int cw = warp - 4;
        const int w = cw >> 2;
        const int tid = threadIdx.x - 128;
        ROLES();
        float* red = reinterpret_cast<float*>(smem_raw + SM_RED);
        DBG_INIT();
        DBG_G(120);
        DBG_T(100);

        {
            if (blockIdx.x < 72) {
                uint32_t sa[10];
#pragma unroll
                for (int i = 0; i < 2; i++) {
                    const float lo = bf_lo(cv[i]), hi = bf_hi(cv[i]);
                    cv[i] = pack_bf16(lo * sigmoidf_(lo), hi * sigmoidf_(hi));
                }
#pragma unroll
                for (int i = 0; i < 10; i++) sa[i] = __shfl_sync(0xffffffffu, cv[i >> 3], (i & 7) * 4 + (lane & 3));
                uint2* mdst = &gs->mod1[(tid >> 3) * D_ + blockIdx.x * 8 + (tid & 7)];
                anchor(bar_full + 504, sa[0] & sa[1] & sa[2] & sa[3] & sa[4] & sa[5] & sa[6] & sa[7] & sa[8] & sa[9] & (uint32_t)(uintptr_t)mdst & (uint32_t)((uintptr_t)mdst >> 32));
                asm volatile("cp.async.wait_all;" ::: "memory");
                __syncwarp();
                const uint32_t ws = sb + SM_Q + SLOT + cw * 512 + (lane & 15) * 32 + (lane & 16);
                float d[16];
#pragma unroll
                for (int i = 0; i < 16; i++) d[i] = 0.f;
#pragma unroll
                for (int i = 0; i < 5; i++) {
                    const uint4 b = ldsm4t(ws + (i < 4 || cw < 4 ? i * 4096 : 0));
                    mma16816(d + 8 * (i & 1), sa[2 * i], sa[2 * i], sa[2 * i + 1], sa[2 * i + 1], b.x, b.y);
                    mma16816(d + 8 * (i & 1) + 4, sa[2 * i], sa[2 * i], sa[2 * i + 1], sa[2 * i + 1], b.z, b.w);
                }
                if (lane < 8) reinterpret_cast<float2*>(red)[lane * 8 + cw] = (lane & 4) ? make_float2(d[4] + d[12], d[5] + d[13]) : make_float2(d[0] + d[8], d[1] + d[9]);
                bar_sync(3, 256);
                if (tid < 8 * MREP) {
                    const float4* r = reinterpret_cast<const float4*>(red) + (tid & 7) * 4;
                    const float4 r0 = r[0], r1 = r[1], r2 = r[2], r3 = r[3];
                    st_relaxed64(mdst, pack_bf16(((r0.x + r0.z) + (r1.x + r1.z)) + ((r2.x + r2.z) + (r3.x + r3.z)),
                                                 ((r0.y + r0.w) + (r1.y + r1.w)) + ((r2.y + r2.w) + (r3.y + r3.w))), tag + 1);
                }
            }
            DBG_G(106);
            asm volatile("barrier.cluster.wait.aligned;" ::: "memory");
            mbar_wait(bar_x, 0);
            asm volatile("add.u32 %0, %0, 1;" : "+r"(tag));
            uint32_t x[20];
            float st[12], st2[12];
            rows_load(x, sb + SM_Q + (lane & 15) * XP + (lane >> 4) * 16 + cw * 32, cw);
#pragma unroll
            for (int i = 0; i < 12; i++) { st[i] = 0.f; st2[i] = 0.f; }
#pragma unroll
            for (int k = 0; k < 9; k++) stats_add((k & 1) ? st2 : st, x[2 * k], x[2 * k + 1], 0x3f803f80u);
#pragma unroll
            for (int i = 0; i < 12; i++) st[i] += st2[i];
            uint32_t mean2;
            float dot;
            const float rsd = rows_stats(st, reinterpret_cast<float4*>(red + 128), cw, lane, mean2, dot);
            const uint4* mp = reinterpret_cast<const uint4*>(gs->mod1 + ((blockIdx.x >> 1) & (MREP - 1)) * D_) + min(tid, D_ / 4 - 1);
            uint4 v0 = make_uint4(0, tag, 0, tag), v1 = v0;
            auto look = [&]() {
                asm volatile("{\n.reg .pred p;\n.reg .b64 a, b, c, d;\nsetp.lt.s32 p, %9, 5;\nmov.b64 a, {%0, %1};\nmov.b64 b, {%2, %3};\n"
                             "mov.b64 c, {%4, %5};\nmov.b64 d, {%6, %7};\n@p ld.relaxed.gpu.global.v2.b64 {a, b}, [%8];\n"
                             "@p ld.relaxed.gpu.global.v2.b64 {c, d}, [%8 + 2304];\n"
                             "mov.b64 {%0, %1}, a;\nmov.b64 {%2, %3}, b;\nmov.b64 {%4, %5}, c;\nmov.b64 {%6, %7}, d;\n}"
                             : "+r"(v0.x), "+r"(v0.y), "+r"(v0.z), "+r"(v0.w), "+r"(v1.x), "+r"(v1.y), "+r"(v1.z), "+r"(v1.w)
                             : "l"(mp), "r"(cw) : "memory");
            };
            rows_normalise(x, x, mean2, rsd, lane, look);
            fence_regs(x);
            uint32_t it = 0;
#pragma unroll 1
            while (((v0.y ^ tag) | (v0.w ^ tag) | (v1.y ^ tag) | (v1.w ^ tag)) && ++it < SPIN / 16) look();
            uint4* smod = reinterpret_cast<uint4*>(smem_raw + SM_Q + M_MOD);
            if (tid < D_ / 4) smod[tid] = make_uint4(badd2(v1.x, 0x3f803f80u), v0.x, badd2(v1.z, 0x3f803f80u), v0.z);
            uint4* hdst = g_h + (size_t)(rg * 36 + cw) * 32 + lane;
            uint2* hdst2 = reinterpret_cast<uint2*>(g_h + (size_t)(rg * 36 + 32) * 32) + tid;
            bar_sync(3, 256);
            DBG_G(107);
#pragma unroll
            for (int k = 0; k < 9; k++) {
                const uint2 cs = lds64(sb + SM_Q + M_MOD + (cw * 8 + (lane & 3) + (k < 8 ? (k >> 1) * 64 + (k & 1) * 4 : 256 - cw * 4)) * 8);
                const uint32_t c1 = cs.x, sa = cs.y;
                x[2 * k] = badd2(bmul2(x[2 * k], c1), sa);
                if (x[2 * k] == 0) x[2 * k] = 0x8000u;
                x[2 * k + 1] = badd2(bmul2(x[2 * k + 1], c1), sa);
            }
#pragma unroll
            for (int ch = 0; ch < 4; ch++) st_relaxed4(hdst + ch * 256, x[4 * ch], x[4 * ch + 1], x[4 * ch + 2], x[4 * ch + 3]);
            st_relaxed64(hdst2, x[16], x[17]);
            __syncwarp();
            if (SPARE && lane == 0) mbar_arrive(bar_pub);
            DBG_G(108);
        }

        uint32_t rel_base;
        asm("mapa.shared::cluster.u32 %0, %1, %2;" : "=r"(rel_base) : "r"(bar_empty), "r"(lane & 1));
        auto release = [&](uint32_t slot) { if (lane < 2) mbar_arrive_cluster(rel_base + 8 * slot); };
        uint32_t q[32], p[32];
        float s[64], o[64];

        uint4* qpark = reinterpret_cast<uint4*>(smem_raw + SM_Q - SLOT) + cw * 256 + lane;
        {
            uint32_t h[144];
            const uint4* hf = g_h + (size_t)(qb * 8 + cw) * (36 * 32) + lane;
            auto load_h = [&](auto lo, auto hi) {
#pragma unroll
                for (int ks = lo.value; ks < hi.value; ks++) {
                    const uint4 v = h_frag(hf, ks, lane);
                    h[4 * ks] = v.x; h[4 * ks + 1] = v.y; h[4 * ks + 2] = v.z; h[4 * ks + 3] = v.w;
                }
            };
            auto check_h = [&](auto lo, auto hi) {
                uint32_t it = 0;
#pragma unroll 1
                while (true) {
                    uint32_t mn = ~0u;
#pragma unroll
                    for (int ks = lo.value; ks < hi.value; ks++) mn = __vimin3_u32(mn, h[4 * ks], h[4 * ks + 2]);
                    if (!__any_sync(0xffffffffu, mn == 0) || ++it >= SPIN / 16) break;
                    load_h(lo, hi);
                }
            };
            __nanosleep(HDELAY);
            load_h(IC<0>{}, IC<4>{});
            DBG_T(104); DBG_G(109);
#pragma unroll
            for (int i = 0; i < 64; i++) o[i] = 0.f;
            uint32_t e = E0;
#pragma unroll 1
            for (int hd = 1;; hd++) {
                fence_regs(o);
                auto group = [&](auto tc) {
                    constexpr int t = tc.value, k0 = t ? 8 * t - 4 : 0;
                    const bool first = t == 0 && hd == 1;
                    mbar_wait(first ? bar_w0 : bar_full + 8 * (e & 3), (e >> 2) & 1);
                    const uint32_t dv = desc_lo(t ? 0 : 8192, UNIT) + (first ? 6 : e & 3) * (SLOT / 16);
                    if (hd == 1) check_h(IC<k0>{}, IC<8 * t + 4>{});
                    WG_FENCE();
#pragma unroll
                    for (int ks = k0; ks < 8 * t + 4; ks++)
                        mma_rs128<1>(o, h[4 * ks], h[4 * ks + 1], h[4 * ks + 2], h[4 * ks + 3], desc_of(dv + (ks - k0) * 128), ks);
                    WG_COMMIT();
                    if (hd == 1) { if (t == 0) {   } if (t == 1) {   } if (t == 2) {   } if (t == 3) {   } if (t == 4) {   } }
                    if (t < 4 && hd == 1) load_h(IC<8 * t + 4>{}, IC<t < 4 ? 8 * t + 12 : 0>{});
                    if (t > 0) { WG_WAIT(1); if (t > 1 || hd > 1) release((e - 1) & 3); }
                    e++;
                };
                group(IC<0>{}); group(IC<1>{}); group(IC<2>{}); group(IC<3>{});
                if (e == 19) break;
                group(IC<4>{});
                WG_WAIT(0);
                if (hd == 1) {     }
                fence_regs(o);
                release((e - 1) & 3);
#pragma unroll
                for (int i = 0; i < 8; i++)
                    qpark[hd * 2048 + i * 32] = make_uint4(pack_bf16(o[8 * i], o[8 * i + 1]), pack_bf16(o[8 * i + 2], o[8 * i + 3]),
                                                           pack_bf16(o[8 * i + 4], o[8 * i + 5]), pack_bf16(o[8 * i + 6], o[8 * i + 7]));
                if (SPARE && hd == 2) {
                    float (&u)[32] = reinterpret_cast<float (&)[32]>(o);
                    fence_regs(u);
#pragma unroll
                    for (int t = 0; t < 3; t++) {
                        mbar_wait(bar_full + 8 * t, 1);
                        WG_FENCE();
#pragma unroll
                        for (int ks = 0; ks < (t < 2 ? 16 : 4); ks++)
                            mma_rs64<1>(u, h[64 * t + 4 * ks], h[64 * t + 4 * ks + 1], h[64 * t + 4 * ks + 2], h[64 * t + 4 * ks + 3],
                                        desc_of(desc_lo(t * SLOT, UNIT) + ks * 128), ks | t);
                        WG_COMMIT();
                        if (t > 0) { WG_WAIT(1); release(t - 1); }
                    }
                    WG_WAIT(0);
                    fence_regs(u);
                    release(2);
                    e = 15;
#pragma unroll
                    for (int i = 0; i < 4; i++)
                        qpark[3 * 2048 + i * 32] = make_uint4(pack_bf16(u[8 * i], u[8 * i + 1]), pack_bf16(u[8 * i + 2], u[8 * i + 3]),
                                                              pack_bf16(u[8 * i + 4], u[8 * i + 5]), pack_bf16(u[8 * i + 6], u[8 * i + 7]));
                }
            }
#pragma unroll
            for (int i = 0; i < 8; i++) {
                const uint4 v = qpark[2048 + i * 32];
                q[4 * i] = v.x; q[4 * i + 1] = v.y; q[4 * i + 2] = v.z; q[4 * i + 3] = v.w;
            }
#pragma unroll
            for (int i = 0; i < 32; i++) p[i] = h[112 + i];
            mbar_wait(bar_full + 24, 0);
            WG_WAIT(0);
            fence_regs(o);
            release(2);
        }
        DBG_T(105);
        DBG_G(125);

        uint8_t* frag = reinterpret_cast<uint8_t*>(__shfl_sync(0xffffffffu, reinterpret_cast<unsigned long long>(g_frag + (size_t)(rg * 8 + cw) * WREG + lane * 16), lane));
        const uint4* qnext = reinterpret_cast<const uint4*>(__shfl_sync(0xffffffffu, reinterpret_cast<unsigned long long>(padd(smem_raw, SM_Q + tid * 16 + cw * 3584)), lane));
        uint8_t* odst = reinterpret_cast<uint8_t*>(const_cast<uint4*>(qnext));
        qnext -= 2048;
        float m0, m1, l0 = 0.25f, l1 = 0.25f, t0, t1;
        uint32_t bad = 0;
        const int lw = cw & 3;
        const uint32_t relw = lw == RW && lane < 8, handw = lw == HW || cw == HW2;
        auto release4 = [&](uint32_t off) {
            asm volatile("{\n.reg .pred p;\nsetp.ne.b32 p, %1, 0;\n@p mbarrier.arrive.shared::cluster.b64 _, [%0];\n}" ::"r"(rel_base + off), "r"(relw) : "memory"); };
        auto handoff = [&]() {
            asm volatile("{\n.reg .pred p;\nsetp.ne.b32 p, %1, 0;\n@p bar.arrive %0, 192;\n}" ::"r"(2 - w), "r"(handw) : "memory"); };
        if (cw == 4 + HW) bar_arrive(1, 192);
        auto finish = [&](auto lo, auto hi, uint32_t bit, auto sink) {
#pragma unroll
            for (int i = lo.value; i < hi.value; i++) {
                const uint32_t v0 = pack_bf16(o[8 * i] * t0, o[8 * i + 1] * t0), v1 = pack_bf16(o[8 * i + 2] * t1, o[8 * i + 3] * t1);
                const uint32_t v2 = pack_bf16(o[8 * i + 4] * t0, o[8 * i + 5] * t0), v3 = pack_bf16(o[8 * i + 6] * t1, o[8 * i + 7] * t1);
                if (i == 0 && fabsf(o[0] * t0) >= 0x1p-31f) bad |= bit << 8;
                sink(i, v0, v1, v2, v3);
            }
        };
        float lq[6];
        auto row_parts = [&]() {
#pragma unroll
            for (int i = 0; i < 3; i++) { lq[i] = __shfl_xor_sync(0xffffffffu, l0, i + 1); lq[3 + i] = __shfl_xor_sync(0xffffffffu, l1, i + 1); }
        };
        auto row_sums = [&](uint32_t bit) {
            t0 = (l0 + lq[0]) + (lq[1] + lq[2]); t1 = (l1 + lq[3]) + (lq[4] + lq[5]);
            if (!(t0 >= LMIN && t0 < LMAX && t1 >= LMIN && t1 < LMAX)) bad |= bit;
        };
        auto issue_pv = [&](uint32_t dlo, int acc, auto lo, auto hi) {
            if (lo.value == 0) asm volatile("{\n.reg .pred p;\nsetp.eq.b32 p, %0, 0;\n@p bar.sync 4, 160;\n}" ::"r"(w) : "memory");
#pragma unroll
            for (int ks = lo.value; ks < hi.value; ks++)
                mma_rs128<1>(o, p[4 * ks], p[4 * ks + 1], p[4 * ks + 2], p[4 * ks + 3], desc_of(dlo + ks * 128), ks ? 1 : acc);
            WG_COMMIT();
        };
#pragma unroll
        for (int i = 0; i < 64; i++) s[i] = 0.f;
        uint32_t dv_lo = desc_lo(0, UNIT), voff = 0;
        auto issue_qk = [&]() {
            const uint32_t dk = dv_lo ^ (desc_lo(0, UNIT) ^ desc_lo(3 * SLOT, 16));
            bar_sync(1 + w, 192);
            fence_regs(s); fence_regs(q); fence_regs(o); fence_regs(p);
            WG_FENCE();
#pragma unroll
            for (int ks = 0; ks < 8; ks++)
                mma_rs128<0>(s, q[4 * ks], q[4 * ks + 1], q[4 * ks + 2], q[4 * ks + 3], desc_of(dk + (ks >> 2) * 1024 + (ks & 3) * 2), ks != 0);
            WG_COMMIT();
        };
        auto to_frag = [&](int i, uint32_t v0, uint32_t v1, uint32_t v2, uint32_t v3) {
            *reinterpret_cast<uint4*>(odst + i * 512) = make_uint4(v0, v1, v2, v3); };
        int n = 0;
        auto scores_ready = [&]() {
            WG_WAIT(1);
            fence_regs(s); fence_regs(q);
        };
        auto pass_on = [&]() {
            release4(voff ^ 24);
            handoff();
        };
#pragma unroll 1
        for (;;) {
            {
                if (RPE) {
                    asm volatile("st.shared.v2.f32 [%0], {%1, %2};" ::"r"(sb + SM_RED + tid * 8), "f"(l0), "f"(l1) : "memory");
                    __syncwarp();
                    const uint4 a = lds128(sb + SM_RED + (tid & ~3) * 8), b = lds128(sb + SM_RED + (tid & ~3) * 8 + 16);
                    l0 = __uint_as_float(a.x); lq[0] = __uint_as_float(a.z); lq[1] = __uint_as_float(b.x); lq[2] = __uint_as_float(b.z);
                    l1 = __uint_as_float(a.y); lq[3] = __uint_as_float(a.w); lq[4] = __uint_as_float(b.y); lq[5] = __uint_as_float(b.w);
                } else {
                    row_parts();
                }
                issue_qk();
                if (RPE == 2) hold(l0, l1);
                row_sums(1u << (n >> 4));
                t0 = rcp_fast(t0); t1 = rcp_fast(t1);
                l0 = 0.f; l1 = 0.f;
                odst = n ? frag + ((n >> 4) - 1) * 4096 : odst;
                if (RPE) anchor(bar_full + 504, (t0 + t1) * __uint_as_float((bad ^ (uint32_t)(uintptr_t)odst) & 0x3fffffff));
                asm volatile("{\n.reg .pred p;\nsetp.ne.b32 p, %1, 0;\n@p mbarrier.arrive.shared::cta.b64 _, [%0];\n}"
                             ::"r"(bar_qfree + (n >> 1) - 8), "r"(lane ? 0 : n) : "memory");
                issue_pv(dv_lo, 1, IC<0>{}, IC<8>{});
                scores_ready();
                float a0 = fmaxf(s[0], s[1]), a1 = fmaxf(s[2], s[3]), a2 = fmaxf(s[4], s[5]), a3 = fmaxf(s[6], s[7]);
#pragma unroll
                for (int i = 1; i < MAXG; i++) {
                    a0 = fmaxf(a0, fmaxf(s[8 * i], s[8 * i + 1])); a1 = fmaxf(a1, fmaxf(s[8 * i + 2], s[8 * i + 3]));
                    a2 = fmaxf(a2, fmaxf(s[8 * i + 4], s[8 * i + 5])); a3 = fmaxf(a3, fmaxf(s[8 * i + 6], s[8 * i + 7]));
                }
                const uint32_t a = pack_bf16(fmaxf(a0, a2), fmaxf(a1, a3));
                const uint32_t b = bmax2(bmax2(a, __shfl_xor_sync(0xffffffffu, a, 1)), bmax2(__shfl_xor_sync(0xffffffffu, a, 2), __shfl_xor_sync(0xffffffffu, a, 3)));
                pass_on();
                m0 = fmaf(-CS, bf_lo(b), -POFF); m1 = fmaf(-CS, bf_hi(b), -POFF);
            }
#pragma unroll 1
            for (;;) {
                DBG_T(n);
#pragma unroll
                for (int i = 0; i < 4 * STAGE; i++) s[i] = fmaf(s[i], CS, (i & 2) ? m1 : m0);
#pragma unroll
                for (int i = 0; i < 4 * SPLIT; i++) s[i] = ex2(s[i]);
#pragma unroll
                for (int i = 0; i < SPLIT; i++) { l0 += s[4 * i] + s[4 * i + 1]; l1 += s[4 * i + 2] + s[4 * i + 3]; }
                if (STAGE < 16) {
                    m0 = fmaf(l0, 0.f, m0); m1 = fmaf(l1, 0.f, m1);
                }
                anchor(bar_full + 504, l0 + l1);
                WG_WAIT(0);
                fence_regs(o); fence_regs(p);
                release4(voff);
                dv_lo ^= 2 * SLOT / 16;
                voff ^= 16;
                n++;
#pragma unroll
                for (int i = 4 * STAGE; i < 64; i++) s[i] = fmaf(s[i], CS, (i & 2) ? m1 : m0);
#pragma unroll
                for (int i = 4 * SPLIT; i < 64; i++) s[i] = ex2(s[i]);
#pragma unroll
                for (int i = SPLIT; i < 16; i++) { l0 += s[4 * i] + s[4 * i + 1]; l1 += s[4 * i + 2] + s[4 * i + 3]; }
#pragma unroll
                for (int i = 0; i < 32; i++) p[i] = pack_bf16(s[2 * i], s[2 * i + 1]);
                const int jn = n & 15;
                if (!(((0x8003 | RCM | RCM << 1) >> jn) & 1)) {
                    issue_qk();
                    issue_pv(dv_lo, 1, IC<0>{}, IC<8>{});
                    scores_ready();
                    pass_on();
                    continue;
                }
                if (jn == 1) {
                    finish(IC<0>{}, IC<ESPLIT>{}, 1u << (n >> 4), to_frag);
                    issue_qk();
                    if (HOLD) hold(t0, t1);
                    finish(IC<ESPLIT>{}, IC<8>{}, 1u << (n >> 4), to_frag);
                    WG_FENCE();
                    issue_pv(dv_lo, 0, IC<0>{}, IC<8>{});
                    scores_ready();
                    pass_on();
                    continue;
                }
                if (jn == 0) break;
                if (RCM && jn != 15) {
                    if ((RCM >> jn) & 1) {
                        row_parts();
                        row_sums(2u << (n >> 4));
                        const uint32_t e0 = __float_as_uint(t0) >> 23, e1 = __float_as_uint(t1) >> 23;
                        m0 -= __uint_as_float(0x4b000000u | e0) - (8388608.f + 127.f - POFF);
                        m1 -= __uint_as_float(0x4b000000u | e1) - (8388608.f + 127.f - POFF);
                        t0 = __uint_as_float((254 - (int)POFF - e0) << 23); t1 = __uint_as_float((254 - (int)POFF - e1) << 23);
                        l0 *= t0; l1 *= t1;
                    } else {
#pragma unroll
                        for (int i = 0; i < 64; i++) o[i] *= (i & 2) ? t1 : t0;
                    }
                    issue_qk();
                    issue_pv(dv_lo, 1, IC<0>{}, IC<8>{});
                    scores_ready();
                    pass_on();
                    continue;
                }
                if (SPARE && n == 47) mbar_wait(bar_q3, 0);
                qnext = n == 63 ? reinterpret_cast<const uint4*>(frag) : qnext + 2048;
                issue_qk();
                issue_pv(dv_lo, 1, IC<0>{}, IC<8>{});
                scores_ready();
                pass_on();
#pragma unroll
                for (int i = 0; i < 8; i++) {
                    const uint4 v = qnext[i * 32];
                    q[4 * i] = v.x; q[4 * i + 1] = v.y; q[4 * i + 2] = v.z; q[4 * i + 3] = v.w;
                }
            }
            if (n == 64) break;
        }
        DBG_T(64);
        uint32_t a1[32], a2[32];
        row_parts();
        frag_load(a1, frag + 4096);
        frag_load(a2, frag + 8192);
        bar_sync(1 + w, 192);
        fence_regs(o); fence_regs(p);
        WG_FENCE();
        issue_pv(desc_lo(3 * SLOT, UNIT), 1, IC<0>{}, IC<8>{});
        handoff();
        row_sums(16);
        t0 = rcp_fast(t0); t1 = rcp_fast(t1);
        mbar_wait(bar_mod, 0);
        WG_WAIT(0);
        fence_regs(o); fence_regs(p);
        release4(24);
        finish(IC<0>{}, IC<8>{}, 16, [&](int i, uint32_t v0, uint32_t v1, uint32_t v2, uint32_t v3) {
            p[4 * i] = v0; p[4 * i + 1] = v1; p[4 * i + 2] = v2; p[4 * i + 3] = v3; });
        bad = __reduce_or_sync(0xffffffffu, bad);
        bad = ((bad | ~(bad >> 8)) >> 1) & 15;
        if (__builtin_expect(bad != 0, 0)) {
            uint8_t* keep = g_keep + (size_t)(rg * 8 + cw) * 4096 + lane * 16;
            frag_store(keep, p);
            attn_fallback(bad, tag, gs, frag, keep, args.wq, args.kc, args.vc);
            frag_load(q, frag); frag_load(a1, frag + 4096); frag_load(a2, frag + 8192); frag_load(p, keep);
        }
        DBG_T(80);
        DBG_G(124);

        const uint32_t eye = (lane >> 3) == (lane & 3) ? 0x3f80u << ((lane & 4) * 4) : 0;
        auto sum8 = [&](uint32_t* r, const uint4 (&v)[8]) {
            float d[16];
#pragma unroll
            for (int i = 0; i < 16; i++) d[i] = 0.f;
#pragma unroll
            for (int src = 0; src < 8; src++) {
                mma1688(d + 8 * (src & 1), v[src].x, v[src].y, eye);
                mma1688(d + 8 * (src & 1) + 4, v[src].z, v[src].w, eye);
            }
#pragma unroll
            for (int i = 0; i < 4; i++) r[i] = pack_bf16(d[2 * i] + d[8 + 2 * i], d[2 * i + 1] + d[9 + 2 * i]);
        };
        uint4 v2[8], v3[8], wf[27];
        uint2 u4[8], gw[9];
        uint32_t x1[20], xs, pa, ta;
        const uint8_t *mb, *mb4;
        int tid_;
        auto load_wf = [&](auto lo, auto hi) {
            const uint32_t wa = sb + SM_Q + ((cw & 1) * D_ + (cw >> 1) * 32 + (tid_ & 7) + (tid_ & 16) / 2) * 80 + (tid_ & 8) * 2;
#pragma unroll
            for (int i = lo.value; i < hi.value; i++)
                wf[i] = ldsm4t((i < 24 ? wa + ((i / 3 & 3) * 8 + i / 12) * 1280 : wa + (32 - (cw >> 1)) * 1280) + (i % 3) * 32);
        };
        uint32_t at[18];
        {
            float (&u)[32] = reinterpret_cast<float (&)[32]>(o);
            uint32_t off = 0;
            auto turn = [&](const uint32_t (&a)[32], const uint32_t (&b)[32], int acc) {
                const uint64_t dv = desc_of(desc_lo(0, UNIT) + off * (SLOT / 128));
                bar_sync(1 + w, 192);
                fence_regs(u);
                WG_FENCE();
#pragma unroll
                for (int ks = 0; ks < 16; ks++) {
                    const uint32_t* f = ks < 8 ? &a[4 * ks] : &b[4 * ks - 32];
                    mma_rs64<1>(u, f[0], f[1], f[2], f[3], dv + ks * 128, ks | acc);
                    if (ks == OSPLIT - 1) WG_COMMIT();
                }
                WG_COMMIT();
                WG_WAIT(1);
            };
            auto done = [&]() {
                WG_WAIT(0);
                fence_regs(u);
                release4(off);
                off = (off + 8) & 24;
            };
            auto store = [&](uint8_t* dst) {
#pragma unroll
                for (int i = 0; i < 4; i++)
                    st_relaxed4(dst + i * 512, pack_bf16(u[8 * i], u[8 * i + 1]), pack_bf16(u[8 * i + 2], u[8 * i + 3]),
                                pack_bf16(u[8 * i + 4], u[8 * i + 5]), pack_bf16(u[8 * i + 6], u[8 * i + 7]));
            };
            tid_ = __shfl_sync(0xffffffffu, tid, lane);
            pa = sb + w * (UNIT - 2048) + tid_ * 16;
#pragma unroll
            for (int i = 0; i < 8; i++) at[i] = 0;
            fence_regs(q); fence_regs(p);
            uint8_t* dst = frag;
#pragma unroll 1
            for (int k = 0; k < 8; k++, dst += 2048) {
                const uint32_t poff = off;
                const bool sum = (0xa0 >> k) & 1;
                if (sum) off = (off + 8) & 24;
                turn(q, p, 0);
                handoff();
                if (sum) {
                    uint4 v[8];
#pragma unroll
                    for (int src = 0; src < 8; src++) v[src] = lds128(pa + poff * (SLOT / 8) + src * 2048);
                    __syncwarp();
                    release(poff >> 3);
                    done();
                    float d[8];
#pragma unroll
                    for (int i = 0; i < 8; i++) {
                        float t[8];
#pragma unroll
                        for (int src = 0; src < 8; src++) {
                            const uint32_t x = i < 2 ? v[src].x : i < 4 ? v[src].y : i < 6 ? v[src].z : v[src].w;
                            t[src] = (i & 1) ? bf_hi(x) : bf_lo(x);
                        }
                        d[i] = ((t[0] + t[2]) + (t[4] + t[6])) + ((t[1] + t[3]) + (t[5] + t[7]));
                    }
#pragma unroll
                    for (int i = 0; i < 4; i++) { at[i] = at[4 + i]; at[4 + i] = pack_bf16(d[2 * i], d[2 * i + 1]); }
                } else {
                    done();
                }
                turn(a1, a2, 1);
                handoff();
                done();
                store(dst);
                __syncwarp();
                asm volatile("{\n.reg .pred p;\nsetp.ne.b32 p, %1, 0;\n@p mbarrier.arrive.shared::cta.b64 _, [%0];\n}"
                             ::"r"(bar_pub + 4 + 4 * k), "r"(lane ? 0 : (0x2a >> k) & 1) : "memory");
            }
            turn(q, p, 0);
            handoff();
            mb = padd(g_frag, (qb * 64 + j) * WREG + 3 * 4096 + tid_ * 16);
            mb4 = padd(mb, 4096 + ((cw >> 1) - cw) * 512 + (cw & 1) * 8);
            xs = sb + (tid_ & 15) * XP + (tid_ & 16) + cw * 32;
            ta = sb + (cw * 8 + (tid_ & 3)) * 8;
#pragma unroll
            for (int k = 0; k < 9; k++) {
                gw[k] = lds64(ta + SM_T + (k < 8 ? (k >> 1) * 64 + (k & 1) * 4 : 256 - cw * 4) * 8);
                if (!(tid_ & 4)) gw[k].y = 0x3f803f80u;
            }
            mbar_wait(bar_g, 0);
            done();
            load_wf(IC<0>{}, IC<WF0>{});
            turn(a1, a2, 1);
            if (w == 0) handoff();
            if (P2E) {
                mbar_wait(bar_full + 8, 0);
#pragma unroll
                for (int src = 0; src < 8; src++) v2[src] = lds128(pa + SLOT + src * 2048);
            }
            done();
            store(dst);
            mbar_wait(bar_full, 0);
            rows_load(x1, xs, cw);
            if (w == 0) bar_sync(5, 256); else bar_arrive(5, 256);
        }
        DBG_T(81);
        DBG_G(122);

        {
        const int tid = tid_, lane = tid & 31;
        const int g8 = lane >> 2, qd = lane & 3, l16 = lane & 15;
        uint32_t h2[18], gb[9], k1, k2;
        float4* rec = reinterpret_cast<float4*>(red + 128);
        const uint2* candp = reinterpret_cast<const uint2*>(padd(g_cand, ((blockIdx.x & (CREP - 1)) * NCTA + (tid >> 1)) * 32 + (tid & 1) * 8));
        uint2 cd;
        auto stage_out = [&]() {
#pragma unroll
            for (int k = 0; k < 9; k++) {
                x1[2 * k] = badd2(x1[2 * k], bmul2(gb[k], h2[2 * k]));
                x1[2 * k + 1] = badd2(x1[2 * k + 1], bmul2(gb[k], h2[2 * k + 1]));
            }
#pragma unroll
            for (int ch = 0; ch < 4; ch++) stsm_x4(xs + ch * 256, x1[4 * ch], x1[4 * ch + 1], x1[4 * ch + 2], x1[4 * ch + 3]);
            asm volatile("stmatrix.sync.aligned.m8n8.x2.shared.b16 [%0], {%1, %2};" ::"r"(xs + 1024 - cw * 16), "r"(x1[16]), "r"(x1[17]) : "memory");
        };
        {
            uint32_t it = 0, miss;
            if (!P2E) {
                mbar_wait(bar_full + 8, 0);
#pragma unroll
                for (int src = 0; src < 8; src++) v2[src] = lds128(pa + SLOT + src * 2048);
            }
            sum8(at + 8, v2);
            float st[12];
#pragma unroll
            for (int i = 0; i < 12; i++) st[i] = 0.f;
            auto add_pair = [&](int k) {
                x1[2 * k] = badd2(x1[2 * k], bmul2(gw[k].x, at[2 * k]));
                x1[2 * k + 1] = badd2(x1[2 * k + 1], bmul2(gw[k].x, at[2 * k + 1]));
                stats_add(st, x1[2 * k], x1[2 * k + 1], gw[k].y);
            };
#pragma unroll
            for (int k = 0; k < 6; k++) add_pair(k);
            mbar_wait(bar_full + 16, 0);
#pragma unroll
            for (int src = 0; src < 8; src++) v3[src] = lds128(pa + 2 * SLOT + src * 2048);
#pragma unroll 1
            do {
                if (BO && it) __nanosleep(BO);
                miss = 0;
#pragma unroll
                for (int src = 0; src < 8; src++) reload16(v3[src], mb + (size_t)src * 8 * WREG, miss);
            } while (__any_sync(0xffffffffu, miss) && ++it < SPIN / 16);
            if (lane < 4) mbar_arrive_cluster(rel_base + 8 * (1 + (lane >> 1)));
            sum8(at + 12, v3);
            add_pair(6); add_pair(7);
            load_wf(IC<WF0>{}, IC<WF1>{});
            uint2 cs[9];
#pragma unroll
            for (int k = 0; k < 9; k++) cs[k] = lds64(ta + SM_TC + (k < 8 ? (k >> 1) * 64 + (k & 1) * 4 : 256 - cw * 4) * 8);
            mbar_wait(bar_pre, 0);
            mbar_wait(bar_full + 24, 0);
#pragma unroll
            for (int src = 0; src < 8; src++) u4[src] = lds64(sb + 3 * SLOT + src * 2048 + (cw >> 1) * 512 + lane * 16 + (cw & 1) * 8);
#pragma unroll 1
            do {
                if (BO && miss) __nanosleep(BO);
                miss = 0;
#pragma unroll
                for (int src = 0; src < 8; src++) reload8(u4[src], mb4 + (size_t)src * 8 * WREG, miss);
            } while (__any_sync(0xffffffffu, miss) && ++it < SPIN / 16);
            float d[8] = {0.f, 0.f, 0.f, 0.f, 0.f, 0.f, 0.f, 0.f};
#pragma unroll
            for (int i = 0; i < 4; i++) mma16816(d + 4 * (i & 1), u4[2 * i].x, u4[2 * i].y, u4[2 * i + 1].x, u4[2 * i + 1].y, eye, eye);
            at[16] = pack_bf16(d[0] + d[4], d[1] + d[5]); at[17] = pack_bf16(d[2] + d[6], d[3] + d[7]);
            add_pair(8);
            DBG_G(123);
            const float2 ws = *reinterpret_cast<const float2*>(smem_raw + SM_TS);
            uint4* cdst = padd(g_cand, CFULL ? ((tid >> 1) * NCTA + rg) * 32 + (tid & 1) * 16 : (tid * NCTA + rg) * 32);
            uint32_t mean2;
            float dot;
            const float rsd = rows_stats(st, rec, cw, lane, mean2, dot);
            const uint32_t b = __float_as_uint(fmaf(fmaf(-bf_lo(mean2), ws.x, dot), rsd, ws.y));
            const uint32_t key = (((b & 0x80000000u) ? ~b : (b | 0x80000000u)) | 2047u) - (rg * 16 + l16);
            top2(key, k1, k2);
            if (tid < (CFULL + 1) * CREP) st_relaxed(cdst, k1, tag, k2, tag);
            cd = ld_relaxed64(candp);
            rows_normalise(h2, x1, mean2, rsd, lane, [&]() {
#pragma unroll
                for (int k = 0; k < 9; k++) gb[k] = lds32(sb + SM_TG + (cw * 8 + qd + (k < 8 ? (k >> 1) * 64 + (k & 1) * 4 : 256 - cw * 4)) * 4);
                if (WFE) load_wf(IC<WF1>{}, IC<WF2>{});
            });
#pragma unroll
            for (int k = 0; k < 18; k++) h2[k] = badd2(bmul2(h2[k], cs[k >> 1].x), cs[k >> 1].y);
            const uint32_t r1 = ~k1 & 15, r2 = ~k2 & 15;
            uint32_t todo = ((r1 & 7) == g8) | ((r2 & 7) == g8) << 1;
#pragma unroll 1
            while (todo) {
                const bool second = !(todo & 1), hi = (second ? r2 : r1) & 8;
                uint4* dst = padd(g_rows, ((rg * 2 + second) * RSLOT + cw * 16 + qd) * 16);
                uint32_t r[18];
#pragma unroll
                for (int k = 0; k < 9; k++) { r[k] = hi ? h2[2 * k + 1] : h2[2 * k]; r[9 + k] = hi ? x1[2 * k + 1] : x1[2 * k]; }
                fence_regs(r);
                st_relaxed(dst, r[0], r[1], r[2], r[3]);
                st_relaxed(dst + 4, r[4], r[5], r[6], r[7]);
                st_relaxed64(reinterpret_cast<uint2*>(padd(dst, 2048 - cw * 224 - qd * 8)), r[8], r[17]);
                st_relaxed(dst + 8, r[9], r[10], r[11], r[12]);
                st_relaxed(dst + 12, r[13], r[14], r[15], r[16]);
                todo &= todo - 1;
            }
            __syncwarp();

            if (SO == 0) stage_out();
            if (!WFE) load_wf(IC<WF1>{}, IC<WF2>{});
        }
        DBG_G(110);
        float2* part = reinterpret_cast<float2*>(smem_raw + 3 * SLOT + UNIT);
        bf16* act = reinterpret_cast<bf16*>(smem_raw + 3 * SLOT + UNIT + 4096);
        {
            uint32_t it = 0;
            const bool own = (tid >> 1) == rg;
            const uint32_t ks = sb + 3 * SLOT + UNIT + 5120;
#pragma unroll 1
            while (cd.y != tag && !own && ++it < SPIN / 16) cd = ld_relaxed64(candp);
            asm volatile("st.shared.u32 [%0], %1;" ::"r"(ks + tid * 4), "r"(own ? (tid & 1) ? k2 : k1 : cd.x) : "memory");
            bar_sync(3, 256);
            DBG_G(111);
            const uint4 a = lds128(ks + lane * 16), b = lds128(ks + 512 + lane * 16);
            const uint32_t a1 = max(a.x, a.z), a2 = __vimax3_u32(min(a.x, a.z), a.y, a.w);
            const uint32_t b1 = max(b.x, b.z), b2 = __vimax3_u32(min(b.x, b.z), b.y, b.w);
            const uint32_t c1 = max(a1, b1), c2 = __vimax3_u32(min(a1, b1), a2, b2);
            k1 = __reduce_max_sync(0xffffffffu, c1);
            k2 = __reduce_max_sync(0xffffffffu, c1 == k1 ? c2 : c1);
        }
        const int sel0 = ~k1 & 2047, sel1 = ~k2 & 2047;
        const uint32_t slot0 = (sel0 >> 4) * 2, slot1 = (sel1 >> 4) * 2 + ((sel0 ^ sel1) < 16);
        uint4 b[9], b2[3];
        {
            const bool tk = cw < 4 ? cw & 2 : lane & 16;
            const int ri = cw < 4 ? tid & 63 : 64 + l16;
            const uint4* hp = padd(g_rows, ((tk ? slot1 : slot0) * RSLOT + (cw < 4 ? ri + (ri & 56) : ri + 64)) * 16);
            const uint32_t hs = sb + 3 * SLOT + UNIT + 8192;
            uint4 hr = make_uint4(cw < 5 ? ~0u : 0, 0, 0, 0);
            uint32_t it = 0, miss;
            reload16(hr, hp, miss);
            if (OUTP == 0 && SO == 0 && tid == 255) {
                reinterpret_cast<int2*>(red)[8] = make_int2(sel0, sel1);
                mbar_arrive(bar_out);
            }
            if (SO == 1) stage_out();
            load_wf(IC<WF2>{}, IC<27>{});
            mbar_wait(bar_full + 8, 1);
            mbar_wait(bar_full + 16, 1);
            {
                const uint32_t da = sb + (lane < 18 ? SLOT + lane * XP : 2 * SLOT + (lane - 18) * XP) + cw * 144;
                const uint32_t db = sb + 2 * SLOT + (14 + (lane & 3)) * XP + cw * 144 + (lane >> 3) * 16;
#pragma unroll
                for (int i = 0; i < 9; i++) b[i] = ldsm4t(da + i * 16);
#pragma unroll
                for (int i = 0; i < 3; i++) b2[i] = ldsm4t(db + i * 48);
            }
#pragma unroll 1
            do {
                miss = 0;
                reload16(hr, hp, miss);
            } while (__any_sync(0xffffffffu, miss) && ++it < SPIN / 16);
            if (cw < 5) asm volatile("st.shared.v4.u32 [%0], {%1, %2, %3, %4};" ::"r"(hs + (tk * 84 + ri) * 16), "r"(hr.x), "r"(hr.y), "r"(hr.z), "r"(hr.w) : "memory");
            bar_sync(3, 256);
            if (OUTP == 0 && SO == 1 && tid == 255) {
                reinterpret_cast<int2*>(red)[8] = make_int2(sel0, sel1);
                mbar_arrive(bar_out);
            }
            uint4 hv[4];
            uint32_t hw[2];
#pragma unroll
            for (int i = 0; i < 4; i++) hv[i] = lds128(hs + ((g8 & 1) * 84 + (cw >> 1) * 16 + qd + i * 4) * 16);
#pragma unroll
            for (int i = 0; i < 2; i++)
                hw[i] = lds32(hs + ((g8 & 1) * 84 + 64) * 16 + (cw >> 1) * 64 + qd * 8 + i * 32);
            DBG_G(112);
            float acc[24];
#pragma unroll
            for (int i = 0; i < 24; i++) acc[i] = 0.f;
#pragma unroll
            for (int i = 0; i < 27; i++) {
                const int ks = i / 3;
                mma16816(acc + 4 * (i % 6), wf[i].x, wf[i].y, wf[i].z, wf[i].w, ks == 8 ? hw[0] : (ks & 1) ? hv[ks >> 1 & 3].z : hv[ks >> 1 & 3].x,
                         ks == 8 ? hw[1] : (ks & 1) ? hv[ks >> 1 & 3].w : hv[ks >> 1 & 3].y);
            }
            if (qd == 0) {
#pragma unroll
                for (int i = 0; i < 5; i++) part[cw * 48 + i * 8 + g8] = make_float2(acc[2 * i] + acc[12 + 2 * i], acc[2 * i + 1] + acc[13 + 2 * i]);
            }
        }
        {
            uint2* dst = padd(g_ypart, ((((g8 & 1) * 36 + ((cw * 9) >> 1)) * NCTA + blockIdx.x) * 8 + (cw & 1) * 4 + qd) * 8);
            uint2* dst1 = dst + ((cw & 1) ? NCTA * 8 - 4 : 4);
            bar_sync(3, 256);

            {
                const float* pp = reinterpret_cast<const float*>(part) + ((blockIdx.x & 1) << 3) + (tid & 127);
                const float gs = rbf((pp[0] + pp[192]) + (pp[384] + pp[576])), us = rbf((pp[96] + pp[288]) + (pp[480] + pp[672]));
                const float v = rbf(gs * sigmoidf_(gs)) * us;
                if (tid < 80) act[(tid & 1) * 56 + (tid >> 1)] = __float2bfloat16_rn(tid < 72 ? v : 0.f);
            }
            bar_sync(3, 256);
            DBG_G(113);
            const uint32_t ap = sb + 3 * SLOT + UNIT + 4096 + (lane & 1) * 112 + (lane >> 4) * 16;
            const uint4 a0 = ldsm4(ap), a1 = ldsm4(ap + 32), a2 = ldsm4(ap + 64);
            float y[36];
#pragma unroll
            for (int i = 0; i < 36; i++) y[i] = 0.f;
#pragma unroll
            for (int i = 0; i < 9; i++) {
                const uint32_t bl = i % 3 == 0 ? b2[i / 3].x : i % 3 == 1 ? b2[i / 3].y : b2[i / 3].z;
                mma16816(y + 4 * i, a0.x, a0.y, a0.z, a0.w, b[i].x, b[i].y);
                mma16816(y + 4 * i, a1.x, a1.y, a1.z, a1.w, b[i].z, b[i].w);
                mma1688(y + 4 * i, a2.x, a2.y, bl);
            }
#pragma unroll
            for (int i = 0; i < 9; i++)
                if (lane < 8) st_relaxed64(((i & 1) ? dst1 : dst) + (i >> 1) * (NCTA * 8), __float_as_uint(y[4 * i]), __float_as_uint(y[4 * i + 1]));
        }
        DBG_G(114);
        if (OUTP == 1 && tid == 255) {
            reinterpret_cast<int2*>(red)[8] = make_int2(sel0, sel1);
            mbar_arrive(bar_out);
        }
        if (blockIdx.x == 127 && tid == 0) gs->epoch[0] = tag;
        if (blockIdx.x < 72) {
            const int tok = blockIdx.x >= 36, grp = blockIdx.x - tok * 36, cp = grp * 8 + (lane & 7);
            const uint2* src = padd(g_ypart, (blockIdx.x * NCTA * 8 + tid) * 8);
            const uint8_t* hsrc = reinterpret_cast<const uint8_t*>(padd(g_rows, (tok ? slot1 : slot0) * (RSLOT * 16) +
                (grp < 32 ? (grp & 7) * 256 + (grp >> 4) * 64 + qd * 16 + (grp & 8) + (lane & 4) : 2048 + (cp - 256) * 8)));
            const uint8_t* xsrc = hsrc + (grp < 32 ? 128 : 4);
            uint32_t* dst = padd(reinterpret_cast<uint32_t*>(args.out), (tok ? sel1 : sel0) * (D_ * 2) + cp * 4);
            const uint32_t gb = reinterpret_cast<const uint32_t*>(smem_raw + SM_TG)[cp];
            const uint32_t ksel = ((tok ? k2 : k1) & ~2047u) | 1024u;
            const float sg = sigmoidf_(rbf(__uint_as_float((ksel & 0x80000000u) ? (ksel & 0x7fffffffu) : ~ksel)));
            uint2 v[4];
            uint32_t hv, xv, it = 0;
            bool miss;
#pragma unroll 1
            do {
#pragma unroll
                for (int i = 0; i < 4; i++) v[i] = ld_relaxed64(src + i * 256);
                hv = ld_relaxed32(hsrc);
                xv = ld_relaxed32(xsrc);
                miss = max(__vimax3_u32(v[0].x, v[1].x, v[2].x), __vimax3_u32(v[3].x, hv, xv)) == ~0u;
            } while (__any_sync(0xffffffffu, miss) && ++it < SPIN / 16);
            float y0 = (__uint_as_float(v[0].x) + __uint_as_float(v[1].x)) + (__uint_as_float(v[2].x) + __uint_as_float(v[3].x));
            float y1 = (__uint_as_float(v[0].y) + __uint_as_float(v[1].y)) + (__uint_as_float(v[2].y) + __uint_as_float(v[3].y));
            y0 += __shfl_xor_sync(0xffffffffu, y0, 8); y1 += __shfl_xor_sync(0xffffffffu, y1, 8);
            y0 += __shfl_xor_sync(0xffffffffu, y0, 16); y1 += __shfl_xor_sync(0xffffffffu, y1, 16);
            if (lane < 8) reinterpret_cast<float2*>(rec)[cw * 8 + lane] = make_float2(y0, y1);
            bar_sync(3, 256);
            if (cw == 0) {
                const float2 t0_ = reinterpret_cast<const float2*>(rec)[lane], t1_ = reinterpret_cast<const float2*>(rec)[32 + lane];
                y0 = t0_.x + t1_.x; y1 = t0_.y + t1_.y;
                y0 += __shfl_xor_sync(0xffffffffu, y0, 8); y1 += __shfl_xor_sync(0xffffffffu, y1, 8);
                y0 += __shfl_xor_sync(0xffffffffu, y0, 16); y1 += __shfl_xor_sync(0xffffffffu, y1, 16);
                const uint32_t y2 = bmul2(pack_bf16(y0, y1), pack_bf16(sg, sg));
                if (lane < 8) *dst = badd2(xv, bmul2(gb, badd2(hv, y2)));
            }
        }
        }
        DBG_T(88);
        DBG_G(121);
    }
}

typedef CUresult (*EncodeFn)(CUtensorMap*, CUtensorMapDataType, cuuint32_t, void*, const cuuint64_t*, const cuuint64_t*,
                             const cuuint32_t*, const cuuint32_t*, CUtensorMapInterleave, CUtensorMapSwizzle,
                             CUtensorMapL2promotion, CUtensorMapFloatOOBfill);

static void make_map(EncodeFn enc, CUtensorMap* m, const void* ptr, int rank, const cuuint64_t* dims,
                     const cuuint64_t* strides, const cuuint32_t* box, CUtensorMapSwizzle sw = CU_TENSOR_MAP_SWIZZLE_128B,
                     CUtensorMapDataType dt = CU_TENSOR_MAP_DATA_TYPE_BFLOAT16) {
    const cuuint32_t es[3] = {1, 1, 1};
    enc(m, dt, rank, const_cast<void*>(ptr), dims, strides, box, es,
        CU_TENSOR_MAP_INTERLEAVE_NONE, sw, CU_TENSOR_MAP_L2_PROMOTION_L2_128B,
        CU_TENSOR_MAP_FLOAT_OOB_FILL_NONE);
}

extern "C" void kernel_launch(void* const* d_in, const int* in_sizes, int n_in, void* d_out, int out_size) {
    const bf16* x = (const bf16*)d_in[0];
    const bf16* kc = (const bf16*)d_in[1];
    const bf16* vc = (const bf16*)d_in[2];
    const bf16* wq = (const bf16*)d_in[3];
    const bf16* wo = (const bf16*)d_in[4];
    const bf16* w_r = (const bf16*)d_in[6];
    const bf16* w_gate = (const bf16*)d_in[7];
    const bf16* w_up = (const bf16*)d_in[8];
    const bf16* w_down = (const bf16*)d_in[9];
    const bf16* cvec = (const bf16*)d_in[10];
    const bf16* w_mod = (const bf16*)d_in[11];
    bf16* out = (bf16*)d_out;

    void* fn = nullptr;
    cudaDriverEntryPointQueryResult qr;
    cudaGetDriverEntryPoint("cuTensorMapEncodeTiled", &fn, cudaEnableDefault, &qr);
    EncodeFn enc = (EncodeFn)fn;
    void* p_s;
    cudaGetSymbolAddress(&p_s, g_s);

    CUtensorMap tm_wq, tm_k, tm_v, tm_wo, tm_p, tm_x, tm_d, tm_g, tm_u;
    { cuuint64_t d[2] = {QD, D_}, s[1] = {QD * 2}; cuuint32_t b[2] = {64, 128}; make_map(enc, &tm_wq, wq, 2, d, s, b); }
    { cuuint64_t d[2] = {DH, HKV * S_}, s[1] = {DH * 2}; cuuint32_t b[2] = {64, 128};
      make_map(enc, &tm_k, kc, 2, d, s, b); make_map(enc, &tm_v, vc, 2, d, s, b); }
    { cuuint64_t d[2] = {D_, QD}, s[1] = {D_ * 2}; cuuint32_t b[2] = {64, 128}; make_map(enc, &tm_wo, wo, 2, d, s, b); }
    { cuuint64_t d[3] = {256, 160, NCTA}, s[2] = {1024, 8 * WREG}; cuuint32_t b[3] = {256, 2, 8};
      make_map(enc, &tm_p, ((Scratch*)p_s)->frag, 3, d, s, b, CU_TENSOR_MAP_SWIZZLE_NONE, CU_TENSOR_MAP_DATA_TYPE_UINT32); }
    { cuuint64_t d[2] = {D_ / 4, S_}, s[1] = {D_ * 2}; cuuint32_t b[2] = {XP / 8, 16};
      make_map(enc, &tm_x, x, 2, d, s, b, CU_TENSOR_MAP_SWIZZLE_NONE, CU_TENSOR_MAP_DATA_TYPE_UINT64); }
    { cuuint64_t d[2] = {D_ / 4, F_}, s[1] = {D_ * 2}; cuuint32_t b[2] = {XP / 8, 18};
      make_map(enc, &tm_d, w_down, 2, d, s, b, CU_TENSOR_MAP_SWIZZLE_NONE, CU_TENSOR_MAP_DATA_TYPE_UINT64); }
    { cuuint64_t d[2] = {F_, D_}, s[1] = {F_ * 2}; cuuint32_t b[2] = {40, 24};
      make_map(enc, &tm_g, w_gate, 2, d, s, b, CU_TENSOR_MAP_SWIZZLE_NONE); make_map(enc, &tm_u, w_up, 2, d, s, b, CU_TENSOR_MAP_SWIZZLE_NONE); }

    cudaFuncSetAttribute(fused_kernel<true>, cudaFuncAttributeMaxDynamicSharedMemorySize, SM_TOTAL);
    cudaFuncSetAttribute(fused_kernel<false>, cudaFuncAttributeMaxDynamicSharedMemorySize, SM_TOTAL);
    cudaLaunchConfig_t cfg = {};
    cfg.gridDim = NCTA + 4; cfg.blockDim = 384; cfg.dynamicSmemBytes = SM_TOTAL;
    cudaLaunchAttribute at;
    at.id = cudaLaunchAttributeClusterDimension; at.val.clusterDim.x = 2; at.val.clusterDim.y = 1; at.val.clusterDim.z = 1;
    cfg.attrs = &at; cfg.numAttrs = 1;
    int ncl = 0;
    if (cudaOccupancyMaxActiveClusters(&ncl, fused_kernel<true>, &cfg) != cudaSuccess) { ncl = 0; cudaGetLastError(); }
    Args args{w_mod, cvec, (Scratch*)p_s, out, x, kc, vc, wq, wo, w_r, w_down};
    if (USE_SPARE && ncl >= NCTA / 2 + 2)
        fused_kernel<true><<<NCTA + 4, 384, SM_TOTAL>>>(args, tm_wq, tm_k, tm_v, tm_wo, tm_p, tm_x, tm_d, tm_g, tm_u);
    else
        fused_kernel<false><<<NCTA, 384, SM_TOTAL>>>(args, tm_wq, tm_k, tm_v, tm_wo, tm_p, tm_x, tm_d, tm_g, tm_u);
}
```

```cpp
#include <cuda_runtime.h>
#include <cuda_bf16.h>
#include <cuda.h>
#include <stdint.h>
#include <math.h>

typedef __nv_bfloat16 bf16;

constexpr int S_ = 2048;
constexpr int D_ = 576;
constexpr int HQ = 32, HKV = 16, DH = 128;
constexpr int F_ = 4608;
constexpr int QD = HQ * DH;

constexpr int NCTA = 128;
constexpr int WREG = 5 * 4096;
constexpr int CREP = 8;
constexpr int RSLOT = 144;
constexpr int MREP = 4;
struct Scratch {
    unsigned int epoch[128];
    unsigned int flag_mod[NCTA];
    unsigned int flag_part[16 * 32];
    unsigned int flag_q3[16 * 32];
    unsigned int flag_h[NCTA * 32];
    uint2 mod1[MREP * D_];
    uint32_t mod2[4 * D_];
    uint4 cand[CREP * NCTA * 2];
    uint2 ypart[72 * NCTA * 8];
    uint4 h[2][NCTA * 36 * 32];
    uint4 q3[NCTA * 8 * 128];
    uint4 rows[NCTA * 2 * RSLOT];
    uint8_t frag[NCTA * 8 * WREG];
    uint8_t keep[NCTA * 8 * 4096];
};
__device__ __align__(1024) Scratch g_s;
#define g_h gs->h[tag & 1]
#define g_q3 gs->q3
#define g_keep gs->keep
#define g_flag_h gs->flag_h
#define g_flag_part gs->flag_part
#define g_flag_mod gs->flag_mod
#define g_flag_q3 gs->flag_q3
#define g_frag gs->frag
#define g_cand gs->cand
#define g_ypart gs->ypart
#define g_rows gs->rows

#define DBG_INIT()
#define DBG_P(i)
#define DBG_PG(i)
#define DBG_T(i)
#define DBG_G(i)

__device__ __forceinline__ uint32_t pack_bf16(float lo, float hi) {
    uint32_t r;
    asm("cvt.rn.bf16x2.f32 %0, %1, %2;" : "=r"(r) : "f"(hi), "f"(lo));
    return r;
}
__device__ __forceinline__ float rbf(float x) { return __uint_as_float(pack_bf16(0.f, x)); }
__device__ __forceinline__ float bf_lo(uint32_t v) { return __uint_as_float(v << 16); }
__device__ __forceinline__ float bf_hi(uint32_t v) { return __uint_as_float(v & 0xffff0000u); }
__device__ __forceinline__ float ex2(float x) {
    float y;
    asm("ex2.approx.ftz.f32 %0, %1;" : "=f"(y) : "f"(x));
    return y;
}
template <class T>
__device__ __forceinline__ T* padd(T* p, uint32_t off) {
    unsigned long long r;
    asm("{\n.reg .b32 l, h;\nmov.b64 {l, h}, %1;\nadd.cc.u32 l, l, %2;\naddc.u32 h, h, 0;\nmov.b64 %0, {l, h};\n}" : "=l"(r) : "l"(p), "r"(off));
    return reinterpret_cast<T*>(r);
}
__device__ __forceinline__ uint32_t smem_u32(const void* p) { return (uint32_t)__cvta_generic_to_shared(p); }
__device__ __forceinline__ void mbar_init(uint32_t bar, uint32_t cnt) {
    asm volatile("mbarrier.init.shared::cta.b64 [%0], %1;" ::"r"(bar), "r"(cnt) : "memory");
}
__device__ __forceinline__ void mbar_expect_tx(uint32_t bar, uint32_t bytes) {
    asm volatile("mbarrier.arrive.expect_tx.shared::cta.b64 _, [%0], %1;" ::"r"(bar), "r"(bytes) : "memory");
}
__device__ __forceinline__ void mbar_arrive(uint32_t bar) {
    asm volatile("mbarrier.arrive.shared::cta.b64 _, [%0];" ::"r"(bar) : "memory");
}
__device__ __forceinline__ void mbar_arrive_cluster(uint32_t cluster_addr) {
    asm volatile("mbarrier.arrive.shared::cluster.b64 _, [%0];" ::"r"(cluster_addr) : "memory");
}
constexpr uint32_t SPIN = 1u << 20;
__device__ __forceinline__ void mbar_wait(uint32_t bar, uint32_t parity) {
    asm volatile("{\n.reg .pred p;\n.reg .b32 c;\nmov.b32 c, 0;\n"
                 "W_%=:\nmbarrier.try_wait.parity.shared::cta.b64 p, [%0], %1;\n"
                 "add.u32 c, c, 1;\nsetp.lt.and.u32 p, c, 0x100000, !p;\n@p bra W_%=;\n}"
                 ::"r"(bar), "r"(parity) : "memory");
}
__device__ __forceinline__ void anchor(uint32_t addr, float v) {
    asm volatile("{\n.reg .pred p;\nsetp.lt.f32 p, %1, 0f00000000;\n@p st.volatile.shared.f32 [%0], %1;\n}" ::"r"(addr), "f"(v) : "memory");
}
__device__ __forceinline__ void anchor(uint32_t addr, uint32_t v) {
    asm volatile("{\n.reg .pred p;\nsetp.eq.u32 p, %1, 0xffffffff;\n@p st.volatile.shared.u32 [%0], %1;\n}" ::"r"(addr), "r"(v) : "memory");
}
__device__ __forceinline__ void hold(float& a, float& b) {
    asm volatile("{\n.reg .pred p;\n.reg .b64 t;\n.reg .b32 l, h;\nmov.u64 t, %%clock64;\nmov.b64 {l, h}, t;\nsetp.eq.u32 p, h, 0xffffffff;\n"
                 "@p mov.f32 %0, 0f00000000;\n@p mov.f32 %1, 0f00000000;\n}" : "+f"(a), "+f"(b) :: "memory");
}
__device__ __forceinline__ void mbar_wait_sleep(uint32_t bar, uint32_t parity) {
    asm volatile("{\n.reg .pred p;\n.reg .b32 c;\nmov.b32 c, 0;\n"
                 "W_%=:\nmbarrier.try_wait.parity.shared::cta.b64 p, [%0], %1, 5000;\n"
                 "add.u32 c, c, 1;\nsetp.lt.and.u32 p, c, 0x20000, !p;\n@p bra W_%=;\n}"
                 ::"r"(bar), "r"(parity) : "memory");
}
__device__ __forceinline__ uint32_t load_tag(const Scratch* gs) {
    uint32_t tag;
    asm volatile("ld.global.ca.u32 %0, [%1];" : "=r"(tag) : "l"(gs->epoch) : "memory");
    return tag + 1;
}
__device__ __forceinline__ uint4 ld_relaxed(const uint4* p) {
    uint4 v;
    asm volatile("ld.relaxed.gpu.global.v4.u32 {%0,%1,%2,%3}, [%4];" : "=r"(v.x), "=r"(v.y), "=r"(v.z), "=r"(v.w) : "l"(p) : "memory");
    return v;
}
__device__ __forceinline__ void st_relaxed(uint4* p, uint32_t a, uint32_t b, uint32_t c, uint32_t d) {
    asm volatile("{\n.reg .b64 u, v;\nmov.b64 u, {%1, %2};\nmov.b64 v, {%3, %4};\nst.relaxed.gpu.global.v2.b64 [%0], {u, v};\n}"
                 ::"l"(p), "r"(a), "r"(b), "r"(c), "r"(d) : "memory");
}
__device__ __forceinline__ void st_relaxed4(void* p, uint32_t a, uint32_t b, uint32_t c, uint32_t d) {
    asm volatile("st.relaxed.gpu.global.v4.u32 [%0], {%1, %2, %3, %4};" ::"l"(p), "r"(a), "r"(b), "r"(c), "r"(d) : "memory");
}
__device__ __forceinline__ uint2 ld_relaxed8(const void* p) {
    uint2 v;
    asm volatile("ld.relaxed.gpu.global.v2.u32 {%0,%1}, [%2];" : "=r"(v.x), "=r"(v.y) : "l"(p) : "memory");
    return v;
}
__device__ __forceinline__ uint2 ld_relaxed64(const uint2* p) {
    uint2 v;
    asm volatile("{\n.reg .b64 u;\nld.relaxed.gpu.global.b64 u, [%2];\nmov.b64 {%0, %1}, u;\n}" : "=r"(v.x), "=r"(v.y) : "l"(p) : "memory");
    return v;
}
__device__ __forceinline__ void st_relaxed64(uint2* p, uint32_t a, uint32_t b) {
    asm volatile("{\n.reg .b64 u;\nmov.b64 u, {%1, %2};\nst.relaxed.gpu.global.b64 [%0], u;\n}" ::"l"(p), "r"(a), "r"(b) : "memory");
}
__device__ __forceinline__ uint4 ld_relaxed2(const uint4* p) {
    uint4 v;
    asm volatile("{\n.reg .b64 u, w;\nld.relaxed.gpu.global.v2.b64 {u, w}, [%4];\nmov.b64 {%0, %1}, u;\nmov.b64 {%2, %3}, w;\n}"
                 : "=r"(v.x), "=r"(v.y), "=r"(v.z), "=r"(v.w) : "l"(p) : "memory");
    return v;
}
__device__ __forceinline__ void reload16(uint4& v, const void* p, uint32_t& miss) {
    asm volatile("{\n.reg .pred p;\n.reg .b32 m;\n.reg .b64 u, w;\nmax.u32 m, %0, %2;\nsetp.eq.u32 p, m, 0xffffffff;\n"
                 "mov.b64 u, {%0, %1};\nmov.b64 w, {%2, %3};\n@p ld.relaxed.gpu.global.v2.b64 {u, w}, [%5];\n"
                 "mov.b64 {%0, %1}, u;\nmov.b64 {%2, %3}, w;\n@p mov.u32 %4, 1;\n}"
                 : "+r"(v.x), "+r"(v.y), "+r"(v.z), "+r"(v.w), "+r"(miss) : "l"(p) : "memory");
}
__device__ __forceinline__ void reload8(uint2& v, const void* p, uint32_t& miss) {
    asm volatile("{\n.reg .pred p;\n.reg .b64 u;\nsetp.eq.u32 p, %0, 0xffffffff;\nmov.b64 u, {%0, %1};\n"
                 "@p ld.relaxed.gpu.global.b64 u, [%3];\nmov.b64 {%0, %1}, u;\n@p mov.u32 %2, 1;\n}"
                 : "+r"(v.x), "+r"(v.y), "+r"(miss) : "l"(p) : "memory");
}
__device__ __forceinline__ uint32_t ld_relaxed32(const void* p) {
    uint32_t v;
    asm volatile("ld.relaxed.gpu.global.u32 %0, [%1];" : "=r"(v) : "l"(p) : "memory");
    return v;
}
__device__ __forceinline__ void flag_wait(const unsigned int* p, uint32_t tag) {
    uint32_t v, it = 0;
#pragma unroll 1
    do {
        asm volatile("ld.relaxed.gpu.global.u32 %0, [%1];" : "=r"(v) : "l"(p) : "memory");
    } while (__any_sync(0xffffffffu, v != tag) && ++it < SPIN / 16);
    asm volatile("fence.acquire.gpu;" ::: "memory");
    __syncwarp();
}
__device__ __forceinline__ bool elect() {
    uint32_t p;
    asm volatile("{\n.reg .pred p;\nelect.sync _|p, 0xffffffff;\nselp.u32 %0, 1, 0, p;\n}" : "=r"(p));
    return p;
}
__device__ __forceinline__ void flag_release(unsigned int* p, uint32_t tag) {
    asm volatile("st.release.gpu.global.u32 [%0], %1;" ::"l"(p), "r"(tag) : "memory");
}
__device__ __forceinline__ uint32_t touch(const void* p) {
    uint32_t v;
    asm volatile("ld.global.nc.L1::no_allocate.L2::128B.u32 %0, [%1];" : "=r"(v) : "l"(p));
    return v;
}
__device__ __forceinline__ void bar_sync(int id, int n) { asm volatile("bar.sync %0, %1;" ::"r"(id), "r"(n) : "memory"); }
__device__ __forceinline__ void bar_arrive(int id, int n) { asm volatile("bar.arrive %0, %1;" ::"r"(id), "r"(n) : "memory"); }

constexpr uint64_t EVICT_NORMAL = 0x1000000000000000ull, EVICT_FIRST = 0x12F0000000000000ull;
__device__ __forceinline__ void tma2d(uint32_t dst, const CUtensorMap* m, int c0, int c1, uint32_t bar) {
    asm volatile("cp.async.bulk.tensor.2d.shared::cluster.global.mbarrier::complete_tx::bytes.L2::cache_hint [%0], [%1, {%3, %4}], [%2], %5;"
                 ::"r"(dst), "l"(m), "r"(bar), "r"(c0), "r"(c1), "l"(EVICT_FIRST) : "memory");
}
__device__ __forceinline__ void tma2d_mc(uint32_t dst, const CUtensorMap* m, int c0, int c1, uint32_t bar, uint64_t pol) {
    asm volatile("cp.async.bulk.tensor.2d.shared::cluster.global.mbarrier::complete_tx::bytes.multicast::cluster.L2::cache_hint [%0], [%1, {%3, %4}], [%2], %5, %6;"
                 ::"r"(dst), "l"(m), "r"(bar), "r"(c0), "r"(c1), "h"((uint16_t)3), "l"(pol) : "memory");
}
__device__ __forceinline__ void tma3d(uint32_t dst, const CUtensorMap* m, int c0, int c1, int c2, uint32_t bar) {
    asm volatile("cp.async.bulk.tensor.3d.shared::cluster.global.mbarrier::complete_tx::bytes.L2::cache_hint [%0], [%1, {%3, %4, %5}], [%2], %6;"
                 ::"r"(dst), "l"(m), "r"(bar), "r"(c0), "r"(c1), "r"(c2), "l"(EVICT_FIRST) : "memory");
}
__device__ __forceinline__ void bulk_load(uint32_t dst, const void* src, uint32_t bytes, uint32_t bar) {
    asm volatile("cp.async.bulk.shared::cluster.global.mbarrier::complete_tx::bytes [%0], [%1], %2, [%3];"
                 ::"r"(dst), "l"(src), "r"(bytes), "r"(bar) : "memory");
}
__device__ __forceinline__ void l2_prefetch(const void* src, uint32_t bytes) {
    asm volatile("cp.async.bulk.prefetch.L2.global [%0], %1;" ::"l"(src), "r"(bytes) : "memory");
}
__device__ __forceinline__ uint32_t bmul2(uint32_t a, uint32_t b) { uint32_t r; asm("mul.rn.bf16x2 %0, %1, %2;" : "=r"(r) : "r"(a), "r"(b)); return r; }
__device__ __forceinline__ uint32_t badd2(uint32_t a, uint32_t b) { uint32_t r; asm("add.rn.bf16x2 %0, %1, %2;" : "=r"(r) : "r"(a), "r"(b)); return r; }
__device__ __forceinline__ uint32_t bsub2(uint32_t a, uint32_t b) { uint32_t r; asm("sub.rn.bf16x2 %0, %1, %2;" : "=r"(r) : "r"(a), "r"(b)); return r; }
__device__ __forceinline__ uint32_t bmax2(uint32_t a, uint32_t b) { uint32_t r; asm("max.bf16x2 %0, %1, %2;" : "=r"(r) : "r"(a), "r"(b)); return r; }
__device__ __forceinline__ uint32_t bfma2(uint32_t a, uint32_t b, uint32_t c) { uint32_t r; asm("fma.rn.bf16x2 %0, %1, %2, %3;" : "=r"(r) : "r"(a), "r"(b), "r"(c)); return r; }
__device__ __forceinline__ uint4 lds128(uint32_t a) { uint4 v; asm volatile("ld.shared.v4.u32 {%0,%1,%2,%3}, [%4];" : "=r"(v.x), "=r"(v.y), "=r"(v.z), "=r"(v.w) : "r"(a) : "memory"); return v; }
__device__ __forceinline__ uint2 lds64(uint32_t a) { uint2 v; asm volatile("ld.shared.v2.u32 {%0,%1}, [%2];" : "=r"(v.x), "=r"(v.y) : "r"(a) : "memory"); return v; }
__device__ __forceinline__ uint32_t lds32(uint32_t a) { uint32_t v; asm volatile("ld.shared.u32 %0, [%1];" : "=r"(v) : "r"(a) : "memory"); return v; }
__device__ __forceinline__ uint4 ldsm4(uint32_t a) {
    uint4 v;
    asm volatile("ldmatrix.sync.aligned.m8n8.x4.shared.b16 {%0,%1,%2,%3}, [%4];" : "=r"(v.x), "=r"(v.y), "=r"(v.z), "=r"(v.w) : "r"(a) : "memory");
    return v;
}
__device__ __forceinline__ uint4 ldsm4t(uint32_t a) {
    uint4 v;
    asm volatile("ldmatrix.sync.aligned.m8n8.x4.trans.shared.b16 {%0,%1,%2,%3}, [%4];" : "=r"(v.x), "=r"(v.y), "=r"(v.z), "=r"(v.w) : "r"(a) : "memory");
    return v;
}
__device__ __forceinline__ void mma1688(float* d, uint32_t a0, uint32_t a1, uint32_t b) {
    asm("mma.sync.aligned.m16n8k8.row.col.f32.bf16.bf16.f32 {%0,%1,%2,%3}, {%4,%5}, {%6}, {%0,%1,%2,%3};"
        : "+f"(d[0]), "+f"(d[1]), "+f"(d[2]), "+f"(d[3]) : "r"(a0), "r"(a1), "r"(b));
}
__device__ __forceinline__ void mma16816(float* d, uint32_t a0, uint32_t a1, uint32_t a2, uint32_t a3, uint32_t b0, uint32_t b1) {
    asm("mma.sync.aligned.m16n8k16.row.col.f32.bf16.bf16.f32 {%0,%1,%2,%3}, {%4,%5,%6,%7}, {%8,%9}, {%0,%1,%2,%3};"
                 : "+f"(d[0]), "+f"(d[1]), "+f"(d[2]), "+f"(d[3]) : "r"(a0), "r"(a1), "r"(a2), "r"(a3), "r"(b0), "r"(b1));
}
__device__ __forceinline__ void stsm_x4(uint32_t addr, uint32_t a, uint32_t b, uint32_t c, uint32_t d) {
    asm volatile("stmatrix.sync.aligned.m8n8.x4.shared.b16 [%0], {%1, %2, %3, %4};"
                 ::"r"(addr), "r"(a), "r"(b), "r"(c), "r"(d) : "memory");
}

__device__ __forceinline__ uint64_t mkdesc(uint32_t addr, uint32_t lbo, uint32_t sbo) {
    return (uint64_t)((addr & 0x3FFFF) >> 4) | ((uint64_t)(lbo >> 4) << 16) | ((uint64_t)(sbo >> 4) << 32) | (1ull << 62);
}
constexpr uint32_t SM0 = 1024;
__host__ __device__ constexpr uint32_t desc_lo(uint32_t off, uint32_t lbo) { return ((SM0 + off) >> 4) | ((lbo >> 4) << 16); }
#define WG_FENCE() asm volatile("wgmma.fence.sync.aligned;" ::: "memory")
#define WG_COMMIT() asm volatile("wgmma.commit_group.sync.aligned;" ::: "memory")
#define WG_WAIT(n) asm volatile("wgmma.wait_group.sync.aligned %0;" ::"n"(n) : "memory")

#define F8(a, i) "+f"(a[i]), "+f"(a[i + 1]), "+f"(a[i + 2]), "+f"(a[i + 3]), "+f"(a[i + 4]), "+f"(a[i + 5]), "+f"(a[i + 6]), "+f"(a[i + 7])
#define F16(a, i) F8(a, i), F8(a, i + 8)
#define F64(a) F16(a, 0), F16(a, 16), F16(a, 32), F16(a, 48)
#define F32(a) F16(a, 0), F16(a, 16)
#define L64 "%0,%1,%2,%3,%4,%5,%6,%7,%8,%9,%10,%11,%12,%13,%14,%15,%16,%17,%18,%19,%20,%21,%22,%23,%24,%25,%26,%27,%28,%29,%30,%31,%32,%33,%34,%35,%36,%37,%38,%39,%40,%41,%42,%43,%44,%45,%46,%47,%48,%49,%50,%51,%52,%53,%54,%55,%56,%57,%58,%59,%60,%61,%62,%63"
#define L32 "%0,%1,%2,%3,%4,%5,%6,%7,%8,%9,%10,%11,%12,%13,%14,%15,%16,%17,%18,%19,%20,%21,%22,%23,%24,%25,%26,%27,%28,%29,%30,%31"

template <int TB, int STEP = 128>
__device__ __forceinline__ void mma_rs128(float (&d)[64], uint32_t a0, uint32_t a1, uint32_t a2, uint32_t a3, uint64_t& b, int acc) {
    asm volatile("{\n.reg .pred p;\nsetp.ne.b32 p, %69, 0;\n"
                 "wgmma.mma_async.sync.aligned.m64n128k16.f32.bf16.bf16 {" L64 "}, {%65,%66,%67,%68}, %64, p, 1, 1, %70;\nadd.s64 %64, %64, %71;\n}"
                 : F64(d), "+l"(b) : "r"(a0), "r"(a1), "r"(a2), "r"(a3), "r"(acc), "n"(TB), "n"(STEP));
}
template <int TB>
__device__ __forceinline__ void mma_rs64(float (&d)[32], uint32_t a0, uint32_t a1, uint32_t a2, uint32_t a3, uint64_t& b, int acc) {
    asm volatile("{\n.reg .pred p;\nsetp.ne.b32 p, %37, 0;\n"
                 "wgmma.mma_async.sync.aligned.m64n64k16.f32.bf16.bf16 {" L32 "}, {%33,%34,%35,%36}, %32, p, 1, 1, %38;\nadd.s64 %32, %32, 128;\n}"
                 : F32(d), "+l"(b) : "r"(a0), "r"(a1), "r"(a2), "r"(a3), "r"(acc), "n"(TB));
}
template <int N>
__device__ __forceinline__ void fence_regs(float (&d)[N]) {
#pragma unroll
    for (int i = 0; i < N; i++) asm volatile("" : "+f"(d[i])::"memory");
}
template <int N>
__device__ __forceinline__ void fence_regs(uint32_t (&d)[N]) {
#pragma unroll
    for (int i = 0; i < N; i++) asm volatile("" : "+r"(d[i])::"memory");
}

template <int V> struct IC { static constexpr int value = V; };

constexpr int SLOT = 32768, UNIT = 16384;
constexpr int SM_Q = 4 * SLOT;
constexpr int SM_BAR = 7 * SLOT;
constexpr int SM_RED = SM_BAR + 512;
constexpr int SM_TOTAL = SM_BAR + 3072;
constexpr int XP = D_ * 2 + 16;
constexpr int M_MOD = 16 * XP;
constexpr int SM_T = SM_Q + 2 * D_ * 80, SM_TC = SM_T + D_ * 4, SM_TG = SM_TC + D_ * 4, SM_TS = SM_TG + D_ * 2;
constexpr float CS = 0.08838834764831845f * 1.4426950408889634f;
#define LMAX 0.5f
#define LMIN 0x1p-104f
#define USE_SPARE 1
#define MAXG 2
#define SPLIT 10
#define ESPLIT 3
#define PV1 8
#define RW 2
#define HW 2
#define HW2 1
#define XDELAY 200
#define QDELAY 300
#define TMPF 1
#define PFD0 2000
#define PFD1 400
#define HDELAY 300
#define RCM 16
#define RPE 2
#define OSPLIT 6
#define HOLD 1
#define STAGE 11
#define POFF 102.f
#define WF0 3
#define WF1 16
#define C3D 0
#define C4D 300
#define DD 300
#define P2E 0
#define BO 0
#define MAP 2
#define CFULL 0
#define WFE 1
#define OUTD 0
#define OUTPOL EVICT_FIRST
#define SO 0
#define WF2 22
#define OUTP 0
constexpr int PF_KV = 8, PF_WO = 120;

__device__ __forceinline__ int cluster_role() {
    int k;
    asm volatile("mov.u32 %0, %%ctaid.x;" : "=r"(k));
    k >>= 1;
    if (MAP == 0) return k & 63;
    if (MAP == 1) return (k & 7) * 8 + ((k >> 3) & 7);
    if (MAP == 3) {
        asm("mov.u32 %0, %%smid;" : "=r"(k));
        k >>= 1;
        const int r = ((k - 32) * 37) >> 8;
        return k < 32 ? (k & 7) * 8 + (k >> 3) : k < 60 ? (k - 31 - r * 7) * 8 + 4 + r : (k - 58) & 7;
    }
    const int r = ((k - 36) * 37) >> 8, i = k - 36 - r * 7;
    if (MAP == 4) return k < 4 ? 4 + k : k < 36 ? ((k - 4) & 7) * 8 + ((k - 4) >> 3) : (i + 1) * 8 + ((4 + r) & 7);
    return k < 4 ? 12 + k : k < 36 ? ((k - 4) & 7) * 8 + ((k - 4) >> 3) : (i + (i > 0)) * 8 + ((4 + r) & 7);
}

struct Args {
    const bf16 *w_mod, *cvec;
    Scratch* gs;
    uint64_t d0;
    bf16* out;
    const bf16 *x, *kc, *vc, *wq, *wo, *w_r, *w_down;
};

__device__ __forceinline__ void frag_store(uint8_t* p, const uint32_t (&a)[32]) {
#pragma unroll
    for (int i = 0; i < 8; i++)
        __stcg(reinterpret_cast<uint4*>(p + i * 512), make_uint4(a[4 * i], a[4 * i + 1], a[4 * i + 2], a[4 * i + 3]));
}
__device__ __forceinline__ void frag_load(uint32_t (&a)[32], const uint8_t* p) {
#pragma unroll
    for (int i = 0; i < 8; i++) {
        const uint4 v = __ldcg(reinterpret_cast<const uint4*>(p + i * 512));
        a[4 * i] = v.x; a[4 * i + 1] = v.y; a[4 * i + 2] = v.z; a[4 * i + 3] = v.w;
    }
}
__device__ __forceinline__ float quad_sum(float v) {
    v += __shfl_xor_sync(0xffffffffu, v, 1);
    return v + __shfl_xor_sync(0xffffffffu, v, 2);
}
__device__ __forceinline__ float quad_max(float v) {
    v = fmaxf(v, __shfl_xor_sync(0xffffffffu, v, 1));
    return fmaxf(v, __shfl_xor_sync(0xffffffffu, v, 2));
}
__device__ __forceinline__ float rcp_fast(float x) { float y; asm("rcp.approx.ftz.f32 %0, %1;" : "=f"(y) : "f"(x)); return y; }
__device__ __forceinline__ float sigmoidf_(float x) { return rcp_fast(1.f + ex2(-1.4426950408889634f * x)); }
__device__ __forceinline__ void top2(uint32_t k, uint32_t& k1, uint32_t& k2) {
    k1 = __reduce_max_sync(0xffffffffu, k);
    k2 = __reduce_max_sync(0xffffffffu, k == k1 ? 0 : k);
}

__device__ __forceinline__ void mod_fma(float (&a)[8], const uint4 w, float sc) {
    a[0] += sc * bf_lo(w.x); a[1] += sc * bf_hi(w.x); a[2] += sc * bf_lo(w.y); a[3] += sc * bf_hi(w.y);
    a[4] += sc * bf_lo(w.z); a[5] += sc * bf_hi(w.z); a[6] += sc * bf_lo(w.w); a[7] += sc * bf_hi(w.w);
}
__device__ __forceinline__ float mod_reduce(float (&a)[8], int lane) {
#pragma unroll
    for (int h = 4; h > 0; h >>= 1) {
        const bool up = lane & (8 / h);
#pragma unroll
        for (int i = 0; i < h; i++)
            a[i] = (up ? a[i + h] : a[i]) + __shfl_xor_sync(0xffffffffu, up ? a[i] : a[i + h], 8 / h);
    }
    return a[0] + __shfl_xor_sync(0xffffffffu, a[0], 16);
}

__device__ __forceinline__ float ln_stats(float sum, float sq, uint32_t& mean2) {
    const float mean = sum * (1.f / D_);
    const float var = fmaxf(fmaf(-mean, mean, sq * (1.f / D_)), 0.f);
    float sd;
    asm("sqrt.approx.ftz.f32 %0, %1;" : "=f"(sd) : "f"(rbf(rbf(var) + 1e-5f)));
    mean2 = pack_bf16(mean, mean);
    return rcp_fast(rbf(sd));
}
__device__ __forceinline__ uint32_t ln_pair(uint32_t x, uint32_t mean2, float rsd) {
    const uint32_t d = bsub2(x, mean2);
    return pack_bf16(bf_lo(d) * rsd, bf_hi(d) * rsd);
}
__device__ __forceinline__ void rows_load(uint32_t (&x)[20], uint32_t xs, int cw) {
#pragma unroll
    for (int ch = 0; ch < 5; ch++) {
        const uint4 v = ldsm4(ch < 4 ? xs + ch * 256 : xs + 1024 - cw * 16);
        x[4 * ch] = v.x; x[4 * ch + 1] = v.y; x[4 * ch + 2] = v.z; x[4 * ch + 3] = v.w;
    }
}
__device__ __forceinline__ void stats_add(float (&st)[12], uint32_t a, uint32_t b, uint32_t w) {
    mma1688(st, a, b, w);
    mma1688(st + 4, a, b, a);
    mma1688(st + 8, a, b, b);
}
__device__ __forceinline__ float rows_stats(const float (&st)[12], float4* rec, int cw, int lane, uint32_t& mean2, float& dot) {
    const int g8 = lane >> 2;
    if ((g8 >> 1) == (lane & 3)) {
        rec[cw * 16 + g8] = make_float4(st[0], (g8 & 1) ? st[5] : st[4], st[1], 0.f);
        rec[cw * 16 + 8 + g8] = make_float4(st[2], (g8 & 1) ? st[11] : st[10], st[3], 0.f);
    }
    bar_sync(3, 256);
    const float4* r = rec + (lane >> 4) * 64 + (lane & 15);
    const float4 s0 = r[0], s1 = r[16], s2 = r[32], s3 = r[48];
    const float sum = (s0.x + s1.x) + (s2.x + s3.x), sq = (s0.y + s1.y) + (s2.y + s3.y);
    dot = (s0.z + s1.z) + (s2.z + s3.z);
    dot += __shfl_xor_sync(0xffffffffu, dot, 16);
    return ln_stats(sum + __shfl_xor_sync(0xffffffffu, sum, 16), sq + __shfl_xor_sync(0xffffffffu, sq, 16), mean2);
}
template <class F>
__device__ __forceinline__ void rows_normalise(uint32_t* y, const uint32_t* x, uint32_t mean2, float rsd, int lane, F loads) {
    const int g8 = lane >> 2;
    const uint32_t ma2 = __shfl_sync(0xffffffffu, mean2, g8), mb2 = __shfl_sync(0xffffffffu, mean2, g8 + 8);
    const float ra = __shfl_sync(0xffffffffu, rsd, g8), rb = __shfl_sync(0xffffffffu, rsd, g8 + 8);
    loads();
#pragma unroll
    for (int k = 0; k < 9; k++) { y[2 * k] = ln_pair(x[2 * k], ma2, ra); y[2 * k + 1] = ln_pair(x[2 * k + 1], mb2, rb); }
}

__device__ __forceinline__ uint4 h_frag(const uint4* hf, int ks, int lane) {
    if (ks < 32) return ld_relaxed2(hf + ks * 32);
    const uint2* p = reinterpret_cast<const uint2*>(padd(hf, 256 - lane * 8) + ks * 32 - 16);
    const uint2 a = ld_relaxed64(p), b = ld_relaxed64(p + 32);
    return make_uint4(a.x, a.y, b.x, b.y);
}

__device__ __noinline__ void attn_fallback(uint32_t bad, uint32_t tag, const Scratch* gs, uint8_t* frag, uint8_t* keep, const bf16* wq, const bf16* kc, const bf16* vc) {
  const int lane = threadIdx.x & 31, g8 = lane >> 2, qd = lane & 3;
  const int role = cluster_role(), j = role & 7, qb = (role >> 3) * 2 + (blockIdx.x & 1);
  const uint4* hf = g_h + (size_t)(qb * 8 + (threadIdx.x >> 5) - 4) * (36 * 32) + lane;
#pragma unroll 1
  for (int t = 0; t < 4; t++) {
    if (!((bad >> t) & 1)) continue;
    const bf16 *wqp = wq + (4 * j + t) * DH, *kp = kc + (size_t)(2 * j + (t >> 1)) * S_ * DH, *vp = vc + (size_t)(2 * j + (t >> 1)) * S_ * DH;
    uint32_t q[32];
    float o[64];
#pragma unroll
    for (int i = 0; i < 64; i++) o[i] = 0.f;
#pragma unroll 1
    for (int ks = 0; ks < 36; ks++) {
        const uint4 a = h_frag(hf, ks, lane);
        const unsigned short* wr = reinterpret_cast<const unsigned short*>(wqp + (size_t)(ks * 16 + 2 * qd) * QD + g8);
#pragma unroll
        for (int dt = 0; dt < 16; dt++) {
            const uint32_t b0 = __ldg(wr + dt * 8) | ((uint32_t)__ldg(wr + dt * 8 + QD) << 16);
            const uint32_t b1 = __ldg(wr + dt * 8 + 8 * QD) | ((uint32_t)__ldg(wr + dt * 8 + 9 * QD) << 16);
            mma16816(o + 4 * dt, a.x, a.y, a.z, a.w, b0, b1);
        }
    }
#pragma unroll
    for (int i = 0; i < 32; i++) q[i] = pack_bf16(o[2 * i], o[2 * i + 1]);
#pragma unroll
    for (int i = 0; i < 64; i++) o[i] = 0.f;
    float m0 = -INFINITY, m1 = -INFINITY, l0 = 0.f, l1 = 0.f;
#pragma unroll 1
    for (int key = 0; key < S_; key += 16) {
        float sc[8];
#pragma unroll
        for (int i = 0; i < 8; i++) sc[i] = 0.f;
#pragma unroll
        for (int nt = 0; nt < 2; nt++) {
            const uint32_t* kr = reinterpret_cast<const uint32_t*>(kp + (size_t)(key + nt * 8 + g8) * DH) + qd;
#pragma unroll
            for (int ks = 0; ks < 8; ks++)
                mma16816(sc + 4 * nt, q[4 * ks], q[4 * ks + 1], q[4 * ks + 2], q[4 * ks + 3], __ldg(kr + ks * 8), __ldg(kr + ks * 8 + 4));
        }
        const float n0 = quad_max(fmaxf(fmaxf(m0, fmaxf(sc[0], sc[1])), fmaxf(sc[4], sc[5])));
        const float n1 = quad_max(fmaxf(fmaxf(m1, fmaxf(sc[2], sc[3])), fmaxf(sc[6], sc[7])));
        const float f0 = ex2((m0 - n0) * CS), f1 = ex2((m1 - n1) * CS);
        m0 = n0; m1 = n1;
#pragma unroll
        for (int i = 0; i < 8; i++) sc[i] = ex2((sc[i] - ((i & 2) ? n1 : n0)) * CS);
        l0 = l0 * f0 + (sc[0] + sc[1]) + (sc[4] + sc[5]);
        l1 = l1 * f1 + (sc[2] + sc[3]) + (sc[6] + sc[7]);
        const uint32_t e0 = pack_bf16(sc[0], sc[1]), e1 = pack_bf16(sc[2], sc[3]), e2 = pack_bf16(sc[4], sc[5]), e3 = pack_bf16(sc[6], sc[7]);
        const unsigned short* vr = reinterpret_cast<const unsigned short*>(vp + (size_t)(key + 2 * qd) * DH + g8);
#pragma unroll
        for (int dt = 0; dt < 16; dt++) {
            o[4 * dt] *= f0; o[4 * dt + 1] *= f0; o[4 * dt + 2] *= f1; o[4 * dt + 3] *= f1;
            const uint32_t b0 = __ldg(vr + dt * 8) | ((uint32_t)__ldg(vr + dt * 8 + DH) << 16);
            const uint32_t b1 = __ldg(vr + dt * 8 + 8 * DH) | ((uint32_t)__ldg(vr + dt * 8 + 9 * DH) << 16);
            mma16816(o + 4 * dt, e0, e1, e2, e3, b0, b1);
        }
    }
    const float i0 = 1.f / quad_sum(l0), i1 = 1.f / quad_sum(l1);
#pragma unroll
    for (int i = 0; i < 16; i++) {
        q[2 * i] = pack_bf16(o[4 * i] * i0, o[4 * i + 1] * i0);
        q[2 * i + 1] = pack_bf16(o[4 * i + 2] * i1, o[4 * i + 3] * i1);
    }
    frag_store(t < 3 ? frag + t * 4096 : keep, q);
  }
}

__device__ __forceinline__ void spare_q3(Scratch* gs, uint32_t sb, uint32_t bar_full, uint32_t bar_empty, int lane, int cw) {
    const uint32_t tag = load_tag(gs);
    uint32_t rel_base, e = 3;
    asm("mapa.shared::cluster.u32 %0, %1, %2;" : "=r"(rel_base) : "r"(bar_empty), "r"(lane & 1));
#pragma unroll 1
    for (int qb = blockIdx.x - NCTA; qb < 16; qb += 4) {
        uint32_t h[144];
        float o[64];
        flag_wait(&g_flag_h[(qb * 8 + cw) * 32], tag);
        const uint4* hf = g_h + (size_t)(qb * 8 + cw) * (36 * 32) + lane;
#pragma unroll
        for (int ks = 0; ks < 36; ks++) {
            const uint4 v = h_frag(hf, ks, lane);
            h[4 * ks] = v.x; h[4 * ks + 1] = v.y; h[4 * ks + 2] = v.z; h[4 * ks + 3] = v.w;
        }
#pragma unroll
        for (int i = 0; i < 64; i++) o[i] = 0.f;
#pragma unroll 1
        for (int v = 0; v < 4; v++) {
            fence_regs(o);
#pragma unroll
            for (int t = 0; t < 5; t++) {
                mbar_wait(bar_full + 8 * (e & 3), (e >> 2) & 1);
                uint64_t dv = mkdesc(sb + (e & 3) * SLOT, UNIT, 1024);
                WG_FENCE();
#pragma unroll
                for (int ks = 0; ks < (t < 4 ? 8 : 4); ks++)
                    mma_rs128<1>(o, h[32 * t + 4 * ks], h[32 * t + 4 * ks + 1], h[32 * t + 4 * ks + 2], h[32 * t + 4 * ks + 3], dv, ks | t);
                WG_COMMIT();
                if (t > 0) { WG_WAIT(1); if (lane < 2) mbar_arrive_cluster(rel_base + 8 * ((e - 1) & 3)); }
                e++;
            }
            WG_WAIT(0);
            fence_regs(o);
            if (lane < 2) mbar_arrive_cluster(rel_base + 8 * ((e - 1) & 3));
            uint4* dst = &g_q3[((qb * 8 + 2 * v) * 8 + cw) * 128 + lane];
#pragma unroll
            for (int i = 0; i < 8; i++)
                __stcg(dst + (i >> 2) * 1024 + (i & 3) * 32, make_uint4(pack_bf16(o[8 * i], o[8 * i + 1]), pack_bf16(o[8 * i + 2], o[8 * i + 3]),
                                                                        pack_bf16(o[8 * i + 4], o[8 * i + 5]), pack_bf16(o[8 * i + 6], o[8 * i + 7])));
        }
        bar_sync(3, 256);
        if (cw == 0 && lane == 0) flag_release(&g_flag_q3[qb * 32], tag);
        __syncwarp();
    }
}

template <bool SPARE>
__global__ void __cluster_dims__(2, 1, 1) __launch_bounds__(384, 1)
fused_kernel(const Args args, const __grid_constant__ CUtensorMap tm_wq,
             const __grid_constant__ CUtensorMap tm_k, const __grid_constant__ CUtensorMap tm_v,
             const __grid_constant__ CUtensorMap tm_wo, const __grid_constant__ CUtensorMap tm_p,
             const __grid_constant__ CUtensorMap tm_x, const __grid_constant__ CUtensorMap tm_d,
             const __grid_constant__ CUtensorMap tm_g, const __grid_constant__ CUtensorMap tm_u) {
    extern __shared__ __align__(1024) uint8_t smem_raw[];
    const uint32_t sb = smem_u32(smem_raw);
    Scratch* const gs = args.gs;
    const uint32_t bar_full = sb + SM_BAR;
    const uint32_t bar_g = bar_full + 8 * 4;
    const uint32_t bar_mod = bar_g + 8;
    const uint32_t bar_go = bar_mod + 8;
    const uint32_t bar_x = bar_go + 40;
    const uint32_t bar_empty = bar_x + 8;
    const uint32_t bar_pub = bar_empty + 8 * 4;
    const uint32_t bar_qfree = bar_pub + 32;
    const uint32_t bar_out = bar_qfree + 24;
    const uint32_t bar_q3 = bar_out + 8;
    const uint32_t bar_pre = bar_q3 + 16;
    const uint32_t bar_w0 = bar_q3 + 8;
    constexpr int E0 = SPARE ? 2 : 0;

    const int c = blockIdx.x & 1;
#define ROLES() const int role = cluster_role(), j = role & 7, qb = (role >> 3) * 2 + c, rg = qb * 8 + j
    const int warp = __shfl_sync(0xffffffffu, threadIdx.x >> 5, 0);

    if (SPARE && blockIdx.x >= NCTA && warp >= 4) {
        asm volatile("barrier.cluster.arrive.relaxed.aligned;" ::: "memory");
        asm volatile("setmaxnreg.inc.sync.aligned.u32 240;");
        asm volatile("barrier.cluster.wait.aligned;" ::: "memory");
        spare_q3(gs, sb, bar_full, bar_empty, threadIdx.x & 31, warp - 4);
        asm volatile("barrier.cluster.arrive.relaxed.aligned;\nbarrier.cluster.wait.aligned;" ::: "memory");
    } else if (warp < 4) {
        asm volatile("setmaxnreg.dec.sync.aligned.u32 24;");
        ROLES();
        int lane;
        asm volatile("mov.u32 %0, %%laneid;" : "=r"(lane));
        if (warp == 2 && elect()) {
            if (TMPF) asm volatile("prefetch.tensormap [%0];" ::"l"(&tm_x) : "memory");
#pragma unroll
            for (int i = 0; i < 27; i++) mbar_init(bar_full + 8 * i, i < 12 || i >= 23 + (SO == 2) ? 1 : i < 16 ? 16 : 8);
#pragma unroll
            for (int i = 0; i <= E0; i++) {
                mbar_arrive(bar_full + 8 * i);
                asm volatile("mbarrier.arrive.shared::cta.b64 _, [%0], 16;" ::"r"(bar_empty + 8 * i) : "memory");
            }
            asm volatile("fence.mbarrier_init.release.cluster;" ::: "memory");
        }
        __syncwarp();
        asm volatile("barrier.cluster.arrive.relaxed.aligned;" ::: "memory");
        if (warp == 2 && !(SPARE && blockIdx.x >= NCTA)) {
            if (XDELAY) __nanosleep(XDELAY);
            if (elect()) {
                mbar_expect_tx(bar_x, 16 * XP);
                tma2d(sb + SM_Q, &tm_x, 0, rg * 16, bar_x);
            }
            __syncwarp();
        }
        asm volatile("barrier.cluster.wait.aligned;" ::: "memory");
        const uint32_t tag = load_tag(gs);
        if (SPARE && blockIdx.x >= NCTA) {
            if (warp == 1) {
#pragma unroll 1
                for (int e = 3; e < 83; e++) {
                    const int v = (e - 3) / 5;
                    mbar_wait_sleep(bar_empty + 8 * (e & 3), ~(e >> 2) & 1);
                    if (elect()) {
                        mbar_expect_tx(bar_full + 8 * (e & 3), SLOT);
                        tma2d_mc(sb + (e & 3) * SLOT + c * UNIT, &tm_wq, (8 * (v & 3) + 4 * c + 3) * DH + 64, (e - 3 - v * 5) * 128,
                                 bar_full + 8 * (e & 3), EVICT_NORMAL);
                    }
                }
            }
            __syncwarp();
            asm volatile("barrier.cluster.arrive.relaxed.aligned;\nbarrier.cluster.wait.aligned;" ::: "memory");
            return;
        }
        if (warp == 3) {
#pragma unroll 1
            for (int e = 4; e < 20; e++) {
                __nanosleep(e == 4 ? PFD0 : PFD1);
                const int hd = (e * 52) >> 8, row = (e - hd * 5) * 128 + qb * 8 + (lane >> 1);
                if (lane < 16 && row < D_)
                    asm volatile("prefetch.global.L2 [%0];" ::"l"(padd(args.wq, (row * QD + (4 * j + ((0x1320 >> (4 * hd)) & 3)) * DH + (lane & 1) * 64) * 2)) : "memory");
            }
            __syncwarp();
            mbar_wait_sleep(bar_go, 0);
#pragma unroll 1
            for (int unit = 72 + blockIdx.x; unit < 216; unit += NCTA) {
                float a[8];
#pragma unroll
                for (int i = 0; i < 8; i++) a[i] = 0.f;
#pragma unroll 1
                for (int k = lane >> 1; k < D_; k += 16) {
                    const float cv = __bfloat162float(*padd(args.cvec, k * 2));
                    mod_fma(a, __ldg(reinterpret_cast<const uint4*>(padd(args.w_mod, (k * (6 * D_) + unit * 16 + (lane & 1) * 8) * 2))), rbf(cv * sigmoidf_(cv)));
                }
                const float v = mod_reduce(a, lane), v1 = __shfl_down_sync(0xffffffffu, v, 8);
                if (lane < 8) *padd(gs->mod2, ((unit - 72) * 8 + (lane & 1) * 4 + (lane & 2) + (lane >> 2)) * 4) = pack_bf16(v, v1);
            }
            __syncwarp();
            if (lane == 0) flag_release(padd(g_flag_mod, blockIdx.x * 4), tag);
#pragma unroll 1
            for (int k = 0; k < 36; k++) {
                __nanosleep(200);
                __stcg(padd(gs->h[0], (~tag & 1) * (NCTA * 36 * 512) + ((rg * 36 + k) * 32 + lane) * 16), make_uint4(0, 0, 0, 0));
            }
            __syncwarp();
            mbar_wait_sleep(bar_qfree + 16, 0);
            __nanosleep(2000);
            {
                uint4 v;
                uint32_t it = 0;
#pragma unroll 1
                do {
                    v = ld_relaxed(reinterpret_cast<const uint4*>(padd(g_flag_mod, lane * 16)));
                } while (((v.x ^ tag) | (v.y ^ tag) | (v.z ^ tag) | (v.w ^ tag)) && ++it < SPIN / 16);
                asm volatile("fence.acquire.gpu;" ::: "memory");
            }
            __syncwarp();
            {
                float w1 = 0.f, w2 = 0.f;
#pragma unroll 1
                for (int k = lane; k < D_ / 2; k += 32) {
                    const uint32_t* mp = padd(gs->mod2, k * 4);
                    const uint32_t sv = __ldcg(mp + D_ / 2), c1 = badd2(__ldcg(mp + D_), 0x3f803f80u);
                    const uint32_t wr = *reinterpret_cast<const uint32_t*>(padd(args.w_r, k * 4)), wp = bmul2(c1, wr);
                    reinterpret_cast<uint2*>(smem_raw + SM_T)[k] = make_uint2(__ldcg(mp), wp);
                    reinterpret_cast<uint2*>(smem_raw + SM_TC)[k] = make_uint2(c1, sv);
                    reinterpret_cast<uint32_t*>(smem_raw + SM_TG)[k] = __ldcg(mp + 3 * D_ / 2);
                    w1 += bf_lo(wp) + bf_hi(wp);
                    w2 += bf_lo(sv) * bf_lo(wr) + bf_hi(sv) * bf_hi(wr);
                }
#pragma unroll 1
                for (int i = 1; i < 32; i <<= 1) { w1 += __shfl_xor_sync(0xffffffffu, w1, i); w2 += __shfl_xor_sync(0xffffffffu, w2, i); }
                *reinterpret_cast<float2*>(smem_raw + SM_TS) = make_float2(w1, w2);
            }
#pragma unroll
            for (int i = 0; i < 4; i++) reinterpret_cast<uint4*>(smem_raw + SM_RED)[lane + 32 * i] = make_uint4(~0u, ~0u, ~0u, ~0u);
            asm volatile("fence.proxy.async.shared::cta;" ::: "memory");
            __syncwarp();
            if (elect()) {
                uint8_t* mb = g_frag + (size_t)rg * 8 * WREG + 3 * 4096;
#pragma unroll 1
                for (int k = 0; k < 8; k++, mb += WREG) {
#pragma unroll
                    for (int i = 0; i < 3; i++)
                        asm volatile("cp.async.bulk.global.shared::cta.bulk_group [%0], [%1], 2048;" ::"l"(mb + i * 2048), "r"(sb + SM_RED) : "memory");
                    __nanosleep(500);
                }
                asm volatile("cp.async.bulk.commit_group;\ncp.async.bulk.wait_group 0;\nfence.proxy.async.global;" ::: "memory");
            }
            __syncwarp();
            if (lane == 0) mbar_arrive(bar_mod);
            __syncwarp();
            mbar_wait_sleep(bar_go + 8, 0);
            if (elect()) asm volatile("prefetch.tensormap [%0];\nprefetch.tensormap [%1];\nprefetch.tensormap [%2];" ::"l"(&tm_x), "l"(&tm_p), "l"(&tm_d) : "memory");
            __syncwarp();
#pragma unroll 1
            for (int i = 1; i < 4; i++) {
                mbar_wait(bar_pub + 8 * i, 0);
                unsigned int* flags = padd(g_flag_part, (qb * 32 + i * 8 - 8) * 4);
                if (elect()) { flag_release(padd(flags, j * 4), tag); DBG_PG(93); }
                __syncwarp();
                const uint32_t slot = i < 3 ? i + 1 : 1;
                flag_wait(padd(flags, (lane & 7) * 4), tag);
                asm volatile("fence.proxy.async.global;" ::: "memory");
                if (lane == 0 && i == 3) DBG_PG(101);
                mbar_wait(bar_go + 8 + 8 * i, 0);
                mbar_wait(bar_empty + 8 * slot, i != 1);
                if (elect()) {
                    mbar_expect_tx(bar_full + 8 * slot, SLOT);
                    tma3d(sb + slot * SLOT, &tm_p, 0, j * 20 + (i - 1) * 4, qb * 8, bar_full + 8 * slot);
                    tma3d(sb + slot * SLOT + UNIT, &tm_p, 0, j * 20 + (i - 1) * 4 + 2, qb * 8, bar_full + 8 * slot);
                }
            }
        } else if (warp == 0) {
#pragma unroll 1
            for (int i = 0; i < 48; i++) {
                if (i == 0 || i == 17 || i == 34) mbar_wait_sleep(bar_qfree + (i >> 4) * 8, 0);
                if (SPARE && i == 17) {
                    flag_wait(&g_flag_q3[qb * 32], tag);
                    if (elect()) {
                        asm volatile("fence.proxy.async.global;" ::: "memory");
                        mbar_expect_tx(bar_q3, UNIT);
#pragma unroll 1
                        for (int k = 0; k < 8; k++) bulk_load(sb + SM_Q + 2 * SLOT + k * 4096 + 2048, &g_q3[(rg * 8 + k) * 128], 2048, bar_q3);
                    }
                }
                __nanosleep(700);
                if (elect()) {
                    asm volatile("mbarrier.expect_tx.shared::cta.b64 [%0], %1;" ::"r"(bar_g), "n"(1920) : "memory");
                    tma2d(sb + SM_Q + i * 1920, i < 24 ? &tm_g : &tm_u, (blockIdx.x * 36) & ~7, (i < 24 ? i : i - 24) * 24, bar_g);
                }
            }
            if (elect()) mbar_arrive(bar_g);
#pragma unroll 1
            for (int i = 0; i < 18; i++) {
                __nanosleep(400);
                if (elect()) l2_prefetch(args.w_down + (size_t)(blockIdx.x * 36 + i * 2) * D_, 4 * D_);
            }
            __syncwarp();
            mbar_wait_sleep(bar_go + 8 * 2, 0);
            uint32_t acc = 0;
#pragma unroll 1
            for (int k = lane; k < 16 * 9; k += 32) acc |= touch(padd(args.x, (rg * 16 * D_ + k * 64) * 2));
            if (acc == 0) reinterpret_cast<volatile uint32_t*>(smem_raw + SM_BAR)[127] = acc;
            __syncwarp();
            mbar_wait_sleep(bar_go + 8 * 4, 0);
            uint4* rp = padd(g_rows, (rg * 2 * RSLOT + lane) * 16);
#pragma unroll
            for (int k = 0; k < 9; k++) rp[k * 32] = make_uint4(~0u, ~0u, ~0u, ~0u);
            if (blockIdx.x < 72) {
                uint4* yp = reinterpret_cast<uint4*>(padd(g_ypart, blockIdx.x * NCTA * 64 + lane * 16));
#pragma unroll
                for (int k = 0; k < 16; k++) yp[k * 32] = make_uint4(~0u, ~0u, ~0u, ~0u);
            }
            asm volatile("fence.acq_rel.gpu;" ::: "memory");
            __syncwarp();
            if (lane == 0) mbar_arrive(bar_pre);
        } else if (warp == 1) {
            __nanosleep(QDELAY);
            uint32_t go = bar_go;
            uint64_t marks = 24 | 151 << 8 | 154 << 16 | 159ull << 24 | 165ull << 32;
#pragma unroll 1
            for (int e = E0; e < 168; e++) {
                const CUtensorMap* tm;
                int c0, c1;
                uint64_t pol = EVICT_FIRST;
                if (e == 158 || e == 163) continue;
                if (e < 21 && e != 19) {
                    const int i = SPARE && e < 12 ? e - 2 : e - (e == 20), hd = (i * 52) >> 8;
                    tm = &tm_wq; c0 = (4 * j + ((0x1320 >> (4 * hd)) & 3)) * DH + c * 64; c1 = (i - hd * 5) * 128 - 64;
                    if (SPARE && e >= 12 && e < 15) { c0 = (4 * j + 3) * DH; c1 = (2 * (e - 12) + c) * 128; }
                } else if (e < 148) {
                    const int i = max(e - 20, 0);
                    const bool isk = i == 0 || ((i & 1) && i < 127);
                    const int n = isk ? (i + 1) >> 1 : (i - 1) >> 1;
                    tm = isk ? &tm_k : &tm_v; c0 = c * 64; c1 = (2 * j + (n >> 5)) * S_ + (n & 15) * 128;
                    if (!(i & 32)) pol = EVICT_NORMAL;
                } else {
                    int i = e - 148 - (e > 158) - (e > 163);
                    tm = &tm_wo; c0 = (i >> 1) * 64; c1 = (4 * j + ((i & 1) ? 1 + c : 3 * c)) * DH;
                }
                const uint32_t fb = e == E0 ? bar_w0 : bar_full + 8 * (e & 3), d = sb + (e == E0 ? 6 : e & 3) * SLOT;
                if (e >= 24 && e < 152) mbar_wait_sleep(bar_empty + 8 * (e & 3), ~(e >> 2) & 1);
                else if (e != E0) mbar_wait(bar_empty + 8 * (e & 3), ~(e >> 2) & 1);
                if (elect()) {
                    mbar_expect_tx(fb, SLOT);
                    tma2d_mc(d + c * UNIT, tm, c0, c1, fb, pol);
                    const int i = e - PF_KV;
                    if (i >= 0 && i < 128 && !(i & 32))
                        l2_prefetch(((i & 1) ? args.vc : args.kc) + (size_t)((2 * j + (i >> 6)) * S_ + (i & 30) * 64) * DH + qb * 1024, 2048);
                    if (e >= PF_WO && e < PF_WO + 18) l2_prefetch(args.wo + (size_t)blockIdx.x * (QD * D_ / NCTA) + (e - PF_WO) * 1024, 2048);
                    if (e == (marks & 255)) mbar_arrive(go);
                }
                if (e == (marks & 255)) { go += 8; marks >>= 8; }
            }
            asm volatile("fence.proxy.async.global;" ::: "memory");
            mbar_wait(bar_empty, 1);
            if (elect()) {
                mbar_expect_tx(bar_full, 16 * XP);
                tma2d(sb, &tm_x, 0, rg * 16, bar_full);
            }
            mbar_wait(bar_empty + 16, 1);
            if (C3D) __nanosleep(C3D);
            if (elect()) {
                mbar_expect_tx(bar_full + 16, SLOT);
                tma3d(sb + 2 * SLOT, &tm_p, 0, j * 20 + 12, qb * 8, bar_full + 16);
                tma3d(sb + 2 * SLOT + UNIT, &tm_p, 0, j * 20 + 14, qb * 8, bar_full + 16);
            }
            mbar_wait(bar_empty + 24, 1);
            if (C4D) __nanosleep(C4D);
            if (elect()) {
                mbar_expect_tx(bar_full + 24, UNIT);
                tma3d(sb + 3 * SLOT, &tm_p, 0, j * 20 + 16, qb * 8, bar_full + 24);
            }
            mbar_wait(bar_empty + 8, 0);
            mbar_wait(bar_empty + 16, 0);
            if (DD) __nanosleep(DD);
            if (elect()) {
#pragma unroll
                for (int i = 1; i < 3; i++) {
                    mbar_expect_tx(bar_full + 8 * i, 18 * XP);
                    tma2d(sb + i * SLOT, &tm_d, 0, blockIdx.x * 36 + (i - 1) * 18, bar_full + 8 * i);
                }
            }
        } else {
            if (elect()) asm volatile("prefetch.tensormap [%0];\nprefetch.tensormap [%1];\nprefetch.tensormap [%2];" ::"l"(&tm_k), "l"(&tm_v), "l"(&tm_wo) : "memory");
            if (SPARE) {
                mbar_wait_sleep(bar_pub, 0);
                if (lane == 0) flag_release(padd(g_flag_h, rg * 128), tag);
                __syncwarp();
            }
            bar_sync(1, 192);
#pragma unroll 1
            for (uint32_t e = 20; e < 148; e++) {
                mbar_wait_sleep(bar_full + 8 * (e & 3), (e >> 2) & 1);
                if (e & 1) bar_sync(1, 192);
                if (!(e & 1) || e == 147) bar_sync(4, 160);
            }
#pragma unroll 1
            for (uint32_t e = 148; e < 168; e++) {
                mbar_wait(bar_full + 8 * (e & 3), (e >> 2) & 1);
                if (e != 158 && e != 163) bar_sync(1, 192);
            }
        }
        __syncwarp();
        mbar_wait_sleep(bar_out, 0);
        if (OUTD) __nanosleep(OUTD);
        if (elect()) {
            asm volatile("fence.proxy.async.shared::cta;" ::: "memory");
            const int2 sel = reinterpret_cast<const int2*>(smem_raw + SM_RED)[8];
#pragma unroll 1
            for (int i = warp; i < 16; i += 4) {
                const int row = rg * 16 + i;
                if (row != sel.x && row != sel.y)
                    asm volatile("cp.async.bulk.global.shared::cta.bulk_group.L2::cache_hint [%0], [%1], %2, %3;"
                                 ::"l"(args.out + (size_t)row * D_), "r"(sb + i * XP), "n"(D_ * 2), "l"(OUTPOL) : "memory");
            }
            asm volatile("cp.async.bulk.commit_group;\ncp.async.bulk.wait_group 0;" ::: "memory");
        }
    } else {
        uint32_t cv[2] = {0, 0}, tag = load_tag(gs) - 1;
        if (blockIdx.x < 72) {
            uint32_t ws;
            int tid;
            asm volatile("mov.u32 %0, smem_raw;\nmov.u32 %1, %%tid.x;" : "=r"(ws), "=r"(tid));
            tid -= 128;
            ws += SM_Q + SLOT + tid * 16;
            const uint32_t* cp = padd(reinterpret_cast<const uint32_t*>(args.cvec), (tid & 0xe0) + (tid & 7) * 4);
            cv[0] = *padd(cp, (tid & 24) * 32);
            if (tid < 128) cv[1] = cp[256];
            const bf16* wrow = args.w_mod + (size_t)(tid >> 1) * (6 * D_) + (tid & 1) * 8 + blockIdx.x * 16;
#pragma unroll
            for (int i = 0; i < 5; i++)
                if (i < 4 || tid < 128)
                    asm volatile("cp.async.cg.shared.global [%0], [%1], 16;" ::"r"(ws + i * 4096), "l"(wrow + (size_t)i * 128 * (6 * D_)) : "memory");
        }
        asm volatile("barrier.cluster.arrive.relaxed.aligned;" ::: "memory");
        asm volatile("setmaxnreg.inc.sync.aligned.u32 240;");
        const int lane = threadIdx.x & 31;
        const int cw = warp - 4;
        const int w = cw >> 2;
        const int tid = threadIdx.x - 128;
        ROLES();
        float* red = reinterpret_cast<float*>(smem_raw + SM_RED);
        DBG_INIT();
        DBG_G(120);
        DBG_T(100);

        {
            if (blockIdx.x < 72) {
                uint32_t sa[10];
#pragma unroll
                for (int i = 0; i < 2; i++) {
                    const float lo = bf_lo(cv[i]), hi = bf_hi(cv[i]);
                    cv[i] = pack_bf16(lo * sigmoidf_(lo), hi * sigmoidf_(hi));
                }
#pragma unroll
                for (int i = 0; i < 10; i++) sa[i] = __shfl_sync(0xffffffffu, cv[i >> 3], (i & 7) * 4 + (lane & 3));
                uint2* mdst = &gs->mod1[(tid >> 3) * D_ + blockIdx.x * 8 + (tid & 7)];
                anchor(bar_full + 504, sa[0] & sa[1] & sa[2] & sa[3] & sa[4] & sa[5] & sa[6] & sa[7] & sa[8] & sa[9] & (uint32_t)(uintptr_t)mdst & (uint32_t)((uintptr_t)mdst >> 32));
                asm volatile("cp.async.wait_all;" ::: "memory");
                __syncwarp();
                const uint32_t ws = sb + SM_Q + SLOT + cw * 512 + (lane & 15) * 32 + (lane & 16);
                float d[16];
#pragma unroll
                for (int i = 0; i < 16; i++) d[i] = 0.f;
#pragma unroll
                for (int i = 0; i < 5; i++) {
                    const uint4 b = ldsm4t(ws + (i < 4 || cw < 4 ? i * 4096 : 0));
                    mma16816(d + 8 * (i & 1), sa[2 * i], sa[2 * i], sa[2 * i + 1], sa[2 * i + 1], b.x, b.y);
                    mma16816(d + 8 * (i & 1) + 4, sa[2 * i], sa[2 * i], sa[2 * i + 1], sa[2 * i + 1], b.z, b.w);
                }
                if (lane < 8) reinterpret_cast<float2*>(red)[lane * 8 + cw] = (lane & 4) ? make_float2(d[4] + d[12], d[5] + d[13]) : make_float2(d[0] + d[8], d[1] + d[9]);
                bar_sync(3, 256);
                if (tid < 8 * MREP) {
                    const float4* r = reinterpret_cast<const float4*>(red) + (tid & 7) * 4;
                    const float4 r0 = r[0], r1 = r[1], r2 = r[2], r3 = r[3];
                    st_relaxed64(mdst, pack_bf16(((r0.x + r0.z) + (r1.x + r1.z)) + ((r2.x + r2.z) + (r3.x + r3.z)),
                                                 ((r0.y + r0.w) + (r1.y + r1.w)) + ((r2.y + r2.w) + (r3.y + r3.w))), tag + 1);
                }
            }
            DBG_G(106);
            asm volatile("barrier.cluster.wait.aligned;" ::: "memory");
            mbar_wait(bar_x, 0);
            asm volatile("add.u32 %0, %0, 1;" : "+r"(tag));
            uint32_t x[20];
            float st[12], st2[12];
            rows_load(x, sb + SM_Q + (lane & 15) * XP + (lane >> 4) * 16 + cw * 32, cw);
#pragma unroll
            for (int i = 0; i < 12; i++) { st[i] = 0.f; st2[i] = 0.f; }
#pragma unroll
            for (int k = 0; k < 9; k++) stats_add((k & 1) ? st2 : st, x[2 * k], x[2 * k + 1], 0x3f803f80u);
#pragma unroll
            for (int i = 0; i < 12; i++) st[i] += st2[i];
            uint32_t mean2;
            float dot;
            const float rsd = rows_stats(st, reinterpret_cast<float4*>(red + 128), cw, lane, mean2, dot);
            const uint4* mp = reinterpret_cast<const uint4*>(gs->mod1 + ((blockIdx.x >> 1) & (MREP - 1)) * D_) + min(tid, D_ / 4 - 1);
            uint4 v0 = make_uint4(0, tag, 0, tag), v1 = v0;
            auto look = [&]() {
                asm volatile("{\n.reg .pred p;\n.reg .b64 a, b, c, d;\nsetp.lt.s32 p, %9, 5;\nmov.b64 a, {%0, %1};\nmov.b64 b, {%2, %3};\n"
                             "mov.b64 c, {%4, %5};\nmov.b64 d, {%6, %7};\n@p ld.relaxed.gpu.global.v2.b64 {a, b}, [%8];\n"
                             "@p ld.relaxed.gpu.global.v2.b64 {c, d}, [%8 + 2304];\n"
                             "mov.b64 {%0, %1}, a;\nmov.b64 {%2, %3}, b;\nmov.b64 {%4, %5}, c;\nmov.b64 {%6, %7}, d;\n}"
                             : "+r"(v0.x), "+r"(v0.y), "+r"(v0.z), "+r"(v0.w), "+r"(v1.x), "+r"(v1.y), "+r"(v1.z), "+r"(v1.w)
                             : "l"(mp), "r"(cw) : "memory");
            };
            rows_normalise(x, x, mean2, rsd, lane, look);
            fence_regs(x);
            uint32_t it = 0;
#pragma unroll 1
            while (((v0.y ^ tag) | (v0.w ^ tag) | (v1.y ^ tag) | (v1.w ^ tag)) && ++it < SPIN / 16) look();
            uint4* smod = reinterpret_cast<uint4*>(smem_raw + SM_Q + M_MOD);
            if (tid < D_ / 4) smod[tid] = make_uint4(badd2(v1.x, 0x3f803f80u), v0.x, badd2(v1.z, 0x3f803f80u), v0.z);
            uint4* hdst = g_h + (size_t)(rg * 36 + cw) * 32 + lane;
            uint2* hdst2 = reinterpret_cast<uint2*>(g_h + (size_t)(rg * 36 + 32) * 32) + tid;
            bar_sync(3, 256);
            DBG_G(107);
#pragma unroll
            for (int k = 0; k < 9; k++) {
                const uint2 cs = lds64(sb + SM_Q + M_MOD + (cw * 8 + (lane & 3) + (k < 8 ? (k >> 1) * 64 + (k & 1) * 4 : 256 - cw * 4)) * 8);
                const uint32_t c1 = cs.x, sa = cs.y;
                x[2 * k] = badd2(bmul2(x[2 * k], c1), sa);
                if (x[2 * k] == 0) x[2 * k] = 0x8000u;
                x[2 * k + 1] = badd2(bmul2(x[2 * k + 1], c1), sa);
            }
#pragma unroll
            for (int ch = 0; ch < 4; ch++) st_relaxed4(hdst + ch * 256, x[4 * ch], x[4 * ch + 1], x[4 * ch + 2], x[4 * ch + 3]);
            st_relaxed64(hdst2, x[16], x[17]);
            __syncwarp();
            if (SPARE && lane == 0) mbar_arrive(bar_pub);
            DBG_G(108);
        }

        uint32_t rel_base;
        asm("mapa.shared::cluster.u32 %0, %1, %2;" : "=r"(rel_base) : "r"(bar_empty), "r"(lane & 1));
        auto release = [&](uint32_t slot) { if (lane < 2) mbar_arrive_cluster(rel_base + 8 * slot); };
        uint32_t q[32], p[32];
        float s[64], o[64];

        uint4* qpark = reinterpret_cast<uint4*>(smem_raw + SM_Q - SLOT) + cw * 256 + lane;
        {
            uint32_t h[144];
            const uint4* hf = g_h + (size_t)(qb * 8 + cw) * (36 * 32) + lane;
            auto load_h = [&](auto lo, auto hi) {
#pragma unroll
                for (int ks = lo.value; ks < hi.value; ks++) {
                    const uint4 v = h_frag(hf, ks, lane);
                    h[4 * ks] = v.x; h[4 * ks + 1] = v.y; h[4 * ks + 2] = v.z; h[4 * ks + 3] = v.w;
                }
            };
            auto check_h = [&](auto lo, auto hi) {
                uint32_t it = 0;
                bool miss;
#pragma unroll 1
                do {
                    uint32_t mn = ~0u;
#pragma unroll
                    for (int ks = lo.value; ks < hi.value; ks++) mn = __vimin3_u32(mn, h[4 * ks], h[4 * ks + 2]);
                    miss = __any_sync(0xffffffffu, mn == 0);
                    if (miss) load_h(lo, hi);
                    asm volatile("add.u32 %0, %0, 1;" : "+r"(it));
                } while (miss && it < SPIN / 16);
            };
            __nanosleep(HDELAY);
            load_h(IC<0>{}, IC<4>{});
            DBG_T(104); DBG_G(109);
#pragma unroll
            for (int i = 0; i < 64; i++) o[i] = 0.f;
            uint32_t e = E0;
#pragma unroll 1
            for (int hd = 1;; hd++) {
                fence_regs(o);
                auto group = [&](auto tc) {
                    constexpr int t = tc.value, k0 = t ? 8 * t - 4 : 0;
                    const bool first = t == 0 && hd == 1;
                    mbar_wait(first ? bar_w0 : bar_full + 8 * (e & 3), (e >> 2) & 1);
                    uint64_t dv = args.d0 + ((t ? 0 : 512) + (first ? 6 : e & 3) * (SLOT / 16));
                    if (hd == 1) check_h(IC<k0>{}, IC<8 * t + 4>{});
                    WG_FENCE();
#pragma unroll
                    for (int ks = k0; ks < 8 * t + 4; ks++)
                        mma_rs128<1>(o, h[4 * ks], h[4 * ks + 1], h[4 * ks + 2], h[4 * ks + 3], dv, ks);
                    WG_COMMIT();
                    if (hd == 1) { if (t == 0) {   } if (t == 1) {   } if (t == 2) {   } if (t == 3) {   } if (t == 4) {   } }
                    if (t < 4 && hd == 1) load_h(IC<8 * t + 4>{}, IC<t < 4 ? 8 * t + 12 : 0>{});
                    if (t > 0) { WG_WAIT(1); if (t > 1 || hd > 1) release((e - 1) & 3); }
                    e++;
                };
                group(IC<0>{}); group(IC<1>{}); group(IC<2>{}); group(IC<3>{});
                if (e == 19) break;
                group(IC<4>{});
                WG_WAIT(0);
                if (hd == 1) {     }
                fence_regs(o);
                release((e - 1) & 3);
#pragma unroll
                for (int i = 0; i < 8; i++)
                    qpark[hd * 2048 + i * 32] = make_uint4(pack_bf16(o[8 * i], o[8 * i + 1]), pack_bf16(o[8 * i + 2], o[8 * i + 3]),
                                                           pack_bf16(o[8 * i + 4], o[8 * i + 5]), pack_bf16(o[8 * i + 6], o[8 * i + 7]));
                if (SPARE && hd == 2) {
                    float (&u)[32] = reinterpret_cast<float (&)[32]>(o);
                    fence_regs(u);
#pragma unroll
                    for (int t = 0; t < 3; t++) {
                        mbar_wait(bar_full + 8 * t, 1);
                        uint64_t dv = args.d0 + t * (SLOT / 16);
                        WG_FENCE();
#pragma unroll
                        for (int ks = 0; ks < (t < 2 ? 16 : 4); ks++)
                            mma_rs64<1>(u, h[64 * t + 4 * ks], h[64 * t + 4 * ks + 1], h[64 * t + 4 * ks + 2], h[64 * t + 4 * ks + 3],
                                        dv, ks | t);
                        WG_COMMIT();
                        if (t > 0) { WG_WAIT(1); release(t - 1); }
                    }
                    WG_WAIT(0);
                    fence_regs(u);
                    release(2);
                    e = 15;
#pragma unroll
                    for (int i = 0; i < 4; i++)
                        qpark[3 * 2048 + i * 32] = make_uint4(pack_bf16(u[8 * i], u[8 * i + 1]), pack_bf16(u[8 * i + 2], u[8 * i + 3]),
                                                              pack_bf16(u[8 * i + 4], u[8 * i + 5]), pack_bf16(u[8 * i + 6], u[8 * i + 7]));
                }
            }
#pragma unroll
            for (int i = 0; i < 8; i++) {
                const uint4 v = qpark[2048 + i * 32];
                q[4 * i] = v.x; q[4 * i + 1] = v.y; q[4 * i + 2] = v.z; q[4 * i + 3] = v.w;
            }
#pragma unroll
            for (int i = 0; i < 32; i++) p[i] = h[112 + i];
            mbar_wait(bar_full + 24, 0);
            WG_WAIT(0);
            fence_regs(o);
            release(2);
        }
        DBG_T(105);
        DBG_G(125);

        uint8_t* frag = reinterpret_cast<uint8_t*>(__shfl_sync(0xffffffffu, reinterpret_cast<unsigned long long>(g_frag + (size_t)(rg * 8 + cw) * WREG + lane * 16), lane));
        const uint4* qnext = reinterpret_cast<const uint4*>(__shfl_sync(0xffffffffu, reinterpret_cast<unsigned long long>(padd(smem_raw, SM_Q + tid * 16 + cw * 3584)), lane));
        uint8_t* odst = reinterpret_cast<uint8_t*>(const_cast<uint4*>(qnext));
        qnext -= 2048;
        float m0, m1, l0 = 0.25f, l1 = 0.25f, t0, t1;
        uint32_t bad = 0;
        const int lw = cw & 3;
        const uint32_t relw = lw == RW && lane < 8, handw = lw == HW || cw == HW2;
        auto release4 = [&](uint32_t off) {
            asm volatile("{\n.reg .pred p;\nsetp.ne.b32 p, %1, 0;\n@p mbarrier.arrive.shared::cluster.b64 _, [%0];\n}" ::"r"(rel_base + off), "r"(relw) : "memory"); };
        auto handoff = [&]() {
            asm volatile("{\n.reg .pred p;\nsetp.ne.b32 p, %1, 0;\n@p bar.arrive %0, 192;\n}" ::"r"(2 - w), "r"(handw) : "memory"); };
        if (cw == 4 + HW) bar_arrive(1, 192);
        auto finish = [&](auto lo, auto hi, uint32_t bit, auto sink) {
#pragma unroll
            for (int i = lo.value; i < hi.value; i++) {
                const uint32_t v0 = pack_bf16(o[8 * i] * t0, o[8 * i + 1] * t0), v1 = pack_bf16(o[8 * i + 2] * t1, o[8 * i + 3] * t1);
                const uint32_t v2 = pack_bf16(o[8 * i + 4] * t0, o[8 * i + 5] * t0), v3 = pack_bf16(o[8 * i + 6] * t1, o[8 * i + 7] * t1);
                if (i == 0 && fabsf(o[0] * t0) >= 0x1p-31f) bad |= bit << 8;
                sink(i, v0, v1, v2, v3);
            }
        };
        float lq[6];
        auto row_parts = [&]() {
#pragma unroll
            for (int i = 0; i < 3; i++) { lq[i] = __shfl_xor_sync(0xffffffffu, l0, i + 1); lq[3 + i] = __shfl_xor_sync(0xffffffffu, l1, i + 1); }
        };
        auto row_sums = [&](uint32_t bit) {
            t0 = (l0 + lq[0]) + (lq[1] + lq[2]); t1 = (l1 + lq[3]) + (lq[4] + lq[5]);
            if (!(t0 >= LMIN && t0 < LMAX && t1 >= LMIN && t1 < LMAX)) bad |= bit;
        };
        auto issue_pv = [&](uint64_t dv, int acc, auto lo, auto hi) {
            if (lo.value == 0) asm volatile("{\n.reg .pred p;\nsetp.eq.b32 p, %0, 0;\n@p bar.sync 4, 160;\n}" ::"r"(w) : "memory");
#pragma unroll
            for (int ks = lo.value; ks < hi.value; ks++)
                mma_rs128<1>(o, p[4 * ks], p[4 * ks + 1], p[4 * ks + 2], p[4 * ks + 3], dv, ks ? 1 : acc);
            WG_COMMIT();
        };
#pragma unroll
        for (int i = 0; i < 64; i++) s[i] = 0.f;
        uint64_t dv_lo = args.d0;
        uint32_t voff = 0;
        auto issue_qk = [&]() {
            uint64_t dk = dv_lo ^ (desc_lo(0, UNIT) ^ desc_lo(3 * SLOT, 16));
            bar_sync(1 + w, 192);
            fence_regs(s); fence_regs(q); fence_regs(o); fence_regs(p);
            WG_FENCE();
#pragma unroll
            for (int ks = 0; ks < 8; ks++)
                if (ks == 3) mma_rs128<0, 1018>(s, q[4 * ks], q[4 * ks + 1], q[4 * ks + 2], q[4 * ks + 3], dk, 1);
                else mma_rs128<0, 2>(s, q[4 * ks], q[4 * ks + 1], q[4 * ks + 2], q[4 * ks + 3], dk, ks != 0);
            WG_COMMIT();
        };
        auto to_frag = [&](int i, uint32_t v0, uint32_t v1, uint32_t v2, uint32_t v3) {
            *reinterpret_cast<uint4*>(odst + i * 512) = make_uint4(v0, v1, v2, v3); };
        int n = 0;
        auto scores_ready = [&]() {
            WG_WAIT(1);
            fence_regs(s); fence_regs(q);
        };
        auto pass_on = [&]() {
            release4(voff ^ 24);
            handoff();
        };
#pragma unroll 1
        for (;;) {
            {
                if (RPE) {
                    asm volatile("st.shared.v2.f32 [%0], {%1, %2};" ::"r"(sb + SM_RED + tid * 8), "f"(l0), "f"(l1) : "memory");
                    __syncwarp();
                    const uint4 a = lds128(sb + SM_RED + (tid & ~3) * 8), b = lds128(sb + SM_RED + (tid & ~3) * 8 + 16);
                    l0 = __uint_as_float(a.x); lq[0] = __uint_as_float(a.z); lq[1] = __uint_as_float(b.x); lq[2] = __uint_as_float(b.z);
                    l1 = __uint_as_float(a.y); lq[3] = __uint_as_float(a.w); lq[4] = __uint_as_float(b.y); lq[5] = __uint_as_float(b.w);
                } else {
                    row_parts();
                }
                issue_qk();
                if (RPE == 2) hold(l0, l1);
                row_sums(1u << (n >> 4));
                t0 = rcp_fast(t0); t1 = rcp_fast(t1);
                l0 = 0.f; l1 = 0.f;
                odst = n ? frag + ((n >> 4) - 1) * 4096 : odst;
                if (RPE) anchor(bar_full + 504, (t0 + t1) * __uint_as_float((bad ^ (uint32_t)(uintptr_t)odst) & 0x3fffffff));
                asm volatile("{\n.reg .pred p;\nsetp.ne.b32 p, %1, 0;\n@p mbarrier.arrive.shared::cta.b64 _, [%0];\n}"
                             ::"r"(bar_qfree + (n >> 1) - 8), "r"(lane ? 0 : n) : "memory");
                issue_pv(dv_lo, 1, IC<0>{}, IC<8>{});
                scores_ready();
                float a0 = fmaxf(s[0], s[1]), a1 = fmaxf(s[2], s[3]), a2 = fmaxf(s[4], s[5]), a3 = fmaxf(s[6], s[7]);
#pragma unroll
                for (int i = 1; i < MAXG; i++) {
                    a0 = fmaxf(a0, fmaxf(s[8 * i], s[8 * i + 1])); a1 = fmaxf(a1, fmaxf(s[8 * i + 2], s[8 * i + 3]));
                    a2 = fmaxf(a2, fmaxf(s[8 * i + 4], s[8 * i + 5])); a3 = fmaxf(a3, fmaxf(s[8 * i + 6], s[8 * i + 7]));
                }
                const uint32_t a = pack_bf16(fmaxf(a0, a2), fmaxf(a1, a3));
                const uint32_t b = bmax2(bmax2(a, __shfl_xor_sync(0xffffffffu, a, 1)), bmax2(__shfl_xor_sync(0xffffffffu, a, 2), __shfl_xor_sync(0xffffffffu, a, 3)));
                pass_on();
                m0 = fmaf(-CS, bf_lo(b), -POFF); m1 = fmaf(-CS, bf_hi(b), -POFF);
            }
#pragma unroll 1
            for (;;) {
                DBG_T(n);
#pragma unroll
                for (int i = 0; i < 4 * STAGE; i++) s[i] = fmaf(s[i], CS, (i & 2) ? m1 : m0);
#pragma unroll
                for (int i = 0; i < 4 * SPLIT; i++) s[i] = ex2(s[i]);
#pragma unroll
                for (int i = 0; i < SPLIT; i++) { l0 += s[4 * i] + s[4 * i + 1]; l1 += s[4 * i + 2] + s[4 * i + 3]; }
                if (STAGE < 16) {
                    m0 = fmaf(l0, 0.f, m0); m1 = fmaf(l1, 0.f, m1);
                }
                anchor(bar_full + 504, l0 + l1);
                WG_WAIT(0);
                fence_regs(o); fence_regs(p);
                release4(voff);
                dv_lo ^= 2 * SLOT / 16;
                voff ^= 16;
                n++;
#pragma unroll
                for (int i = 4 * STAGE; i < 64; i++) s[i] = fmaf(s[i], CS, (i & 2) ? m1 : m0);
#pragma unroll
                for (int i = 4 * SPLIT; i < 64; i++) s[i] = ex2(s[i]);
#pragma unroll
                for (int i = SPLIT; i < 16; i++) { l0 += s[4 * i] + s[4 * i + 1]; l1 += s[4 * i + 2] + s[4 * i + 3]; }
#pragma unroll
                for (int i = 0; i < 32; i++) p[i] = pack_bf16(s[2 * i], s[2 * i + 1]);
                const int jn = n & 15;
                if (!(((0x8003 | RCM | RCM << 1) >> jn) & 1)) {
                    issue_qk();
                    issue_pv(dv_lo, 1, IC<0>{}, IC<8>{});
                    scores_ready();
                    pass_on();
                    continue;
                }
                if (jn == 1) {
                    finish(IC<0>{}, IC<ESPLIT>{}, 1u << (n >> 4), to_frag);
                    issue_qk();
                    if (HOLD) hold(t0, t1);
                    finish(IC<ESPLIT>{}, IC<8>{}, 1u << (n >> 4), to_frag);
                    WG_FENCE();
                    issue_pv(dv_lo, 0, IC<0>{}, IC<8>{});
                    scores_ready();
                    pass_on();
                    continue;
                }
                if (jn == 0) break;
                if (RCM && jn != 15) {
                    if ((RCM >> jn) & 1) {
                        row_parts();
                        row_sums(2u << (n >> 4));
                        const uint32_t e0 = __float_as_uint(t0) >> 23, e1 = __float_as_uint(t1) >> 23;
                        m0 -= __uint_as_float(0x4b000000u | e0) - (8388608.f + 127.f - POFF);
                        m1 -= __uint_as_float(0x4b000000u | e1) - (8388608.f + 127.f - POFF);
                        t0 = __uint_as_float((254 - (int)POFF - e0) << 23); t1 = __uint_as_float((254 - (int)POFF - e1) << 23);
                        l0 *= t0; l1 *= t1;
                    } else {
#pragma unroll
                        for (int i = 0; i < 64; i++) o[i] *= (i & 2) ? t1 : t0;
                    }
                    issue_qk();
                    issue_pv(dv_lo, 1, IC<0>{}, IC<8>{});
                    scores_ready();
                    pass_on();
                    continue;
                }
                if (SPARE && n == 47) mbar_wait(bar_q3, 0);
                qnext = n == 63 ? reinterpret_cast<const uint4*>(frag) : qnext + 2048;
                issue_qk();
                issue_pv(dv_lo, 1, IC<0>{}, IC<8>{});
                scores_ready();
                pass_on();
#pragma unroll
                for (int i = 0; i < 8; i++) {
                    const uint4 v = qnext[i * 32];
                    q[4 * i] = v.x; q[4 * i + 1] = v.y; q[4 * i + 2] = v.z; q[4 * i + 3] = v.w;
                }
            }
            if (n == 64) break;
        }
        DBG_T(64);
        uint32_t a1[32], a2[32];
        row_parts();
        frag_load(a1, frag + 4096);
        frag_load(a2, frag + 8192);
        bar_sync(1 + w, 192);
        fence_regs(o); fence_regs(p);
        WG_FENCE();
        issue_pv(args.d0 + 3 * SLOT / 16, 1, IC<0>{}, IC<8>{});
        handoff();
        row_sums(16);
        t0 = rcp_fast(t0); t1 = rcp_fast(t1);
        mbar_wait(bar_mod, 0);
        WG_WAIT(0);
        fence_regs(o); fence_regs(p);
        release4(24);
        finish(IC<0>{}, IC<8>{}, 16, [&](int i, uint32_t v0, uint32_t v1, uint32_t v2, uint32_t v3) {
            p[4 * i] = v0; p[4 * i + 1] = v1; p[4 * i + 2] = v2; p[4 * i + 3] = v3; });
        bad = __reduce_or_sync(0xffffffffu, bad);
        bad = ((bad | ~(bad >> 8)) >> 1) & 15;
        if (__builtin_expect(bad != 0, 0)) {
            uint8_t* keep = g_keep + (size_t)(rg * 8 + cw) * 4096 + lane * 16;
            frag_store(keep, p);
            attn_fallback(bad, tag, gs, frag, keep, args.wq, args.kc, args.vc);
            frag_load(q, frag); frag_load(a1, frag + 4096); frag_load(a2, frag + 8192); frag_load(p, keep);
        }
        DBG_T(80);
        DBG_G(124);

        const uint32_t eye = (lane >> 3) == (lane & 3) ? 0x3f80u << ((lane & 4) * 4) : 0;
        auto sum8 = [&](uint32_t* r, const uint4 (&v)[8]) {
            float d[16];
#pragma unroll
            for (int i = 0; i < 16; i++) d[i] = 0.f;
#pragma unroll
            for (int src = 0; src < 8; src++) {
                mma1688(d + 8 * (src & 1), v[src].x, v[src].y, eye);
                mma1688(d + 8 * (src & 1) + 4, v[src].z, v[src].w, eye);
            }
#pragma unroll
            for (int i = 0; i < 4; i++) r[i] = pack_bf16(d[2 * i] + d[8 + 2 * i], d[2 * i + 1] + d[9 + 2 * i]);
        };
        uint4 v2[8], v3[8], wf[27];
        uint2 u4[8], gw[9];
        uint32_t x1[20], xs, pa, ta;
        const uint8_t *mb, *mb4;
        int tid_;
        auto load_wf = [&](auto lo, auto hi) {
            const uint32_t wa = sb + SM_Q + ((cw & 1) * D_ + (cw >> 1) * 32 + (tid_ & 7) + (tid_ & 16) / 2) * 80 + (tid_ & 8) * 2;
#pragma unroll
            for (int i = lo.value; i < hi.value; i++)
                wf[i] = ldsm4t((i < 24 ? wa + ((i / 3 & 3) * 8 + i / 12) * 1280 : wa + (32 - (cw >> 1)) * 1280) + (i % 3) * 32);
        };
        uint32_t at[18];
        {
            float (&u)[32] = reinterpret_cast<float (&)[32]>(o);
            uint32_t off = 0;
            auto turn = [&](const uint32_t (&a)[32], const uint32_t (&b)[32], int acc) {
                uint64_t dv = args.d0 + off * (SLOT / 128);
                bar_sync(1 + w, 192);
                fence_regs(u);
                WG_FENCE();
#pragma unroll
                for (int ks = 0; ks < 16; ks++) {
                    const uint32_t* f = ks < 8 ? &a[4 * ks] : &b[4 * ks - 32];
                    mma_rs64<1>(u, f[0], f[1], f[2], f[3], dv, ks | acc);
                    if (ks == OSPLIT - 1) WG_COMMIT();
                }
                WG_COMMIT();
                WG_WAIT(1);
            };
            auto done = [&]() {
                WG_WAIT(0);
                fence_regs(u);
                release4(off);
                off = (off + 8) & 24;
            };
            auto store = [&](uint8_t* dst) {
#pragma unroll
                for (int i = 0; i < 4; i++)
                    st_relaxed4(dst + i * 512, pack_bf16(u[8 * i], u[8 * i + 1]), pack_bf16(u[8 * i + 2], u[8 * i + 3]),
                                pack_bf16(u[8 * i + 4], u[8 * i + 5]), pack_bf16(u[8 * i + 6], u[8 * i + 7]));
            };
            tid_ = __shfl_sync(0xffffffffu, tid, lane);
            pa = sb + w * (UNIT - 2048) + tid_ * 16;
#pragma unroll
            for (int i = 0; i < 8; i++) at[i] = 0;
            fence_regs(q); fence_regs(p);
            uint8_t* dst = frag;
#pragma unroll 1
            for (int k = 0; k < 8; k++, dst += 2048) {
                const uint32_t poff = off;
                const bool sum = (0xa0 >> k) & 1;
                if (sum) off = (off + 8) & 24;
                turn(q, p, 0);
                handoff();
                if (sum) {
                    uint4 v[8];
#pragma unroll
                    for (int src = 0; src < 8; src++) v[src] = lds128(pa + poff * (SLOT / 8) + src * 2048);
                    __syncwarp();
                    release(poff >> 3);
                    done();
                    float d[8];
#pragma unroll
                    for (int i = 0; i < 8; i++) {
                        float t[8];
#pragma unroll
                        for (int src = 0; src < 8; src++) {
                            const uint32_t x = i < 2 ? v[src].x : i < 4 ? v[src].y : i < 6 ? v[src].z : v[src].w;
                            t[src] = (i & 1) ? bf_hi(x) : bf_lo(x);
                        }
                        d[i] = ((t[0] + t[2]) + (t[4] + t[6])) + ((t[1] + t[3]) + (t[5] + t[7]));
                    }
#pragma unroll
                    for (int i = 0; i < 4; i++) { at[i] = at[4 + i]; at[4 + i] = pack_bf16(d[2 * i], d[2 * i + 1]); }
                } else {
                    done();
                }
                turn(a1, a2, 1);
                handoff();
                done();
                store(dst);
                __syncwarp();
                asm volatile("{\n.reg .pred p;\nsetp.ne.b32 p, %1, 0;\n@p mbarrier.arrive.shared::cta.b64 _, [%0];\n}"
                             ::"r"(bar_pub + 4 + 4 * k), "r"(lane ? 0 : (0x2a >> k) & 1) : "memory");
            }
            turn(q, p, 0);
            handoff();
            mb = padd(g_frag, (qb * 64 + j) * WREG + 3 * 4096 + tid_ * 16);
            mb4 = padd(mb, 4096 + ((cw >> 1) - cw) * 512 + (cw & 1) * 8);
            xs = sb + (tid_ & 15) * XP + (tid_ & 16) + cw * 32;
            ta = sb + (cw * 8 + (tid_ & 3)) * 8;
#pragma unroll
            for (int k = 0; k < 9; k++) {
                gw[k] = lds64(ta + SM_T + (k < 8 ? (k >> 1) * 64 + (k & 1) * 4 : 256 - cw * 4) * 8);
                if (!(tid_ & 4)) gw[k].y = 0x3f803f80u;
            }
            mbar_wait(bar_g, 0);
            done();
            load_wf(IC<0>{}, IC<WF0>{});
            turn(a1, a2, 1);
            if (w == 0) handoff();
            if (P2E) {
                mbar_wait(bar_full + 8, 0);
#pragma unroll
                for (int src = 0; src < 8; src++) v2[src] = lds128(pa + SLOT + src * 2048);
            }
            done();
            store(dst);
            mbar_wait(bar_full, 0);
            rows_load(x1, xs, cw);
            if (w == 0) bar_sync(5, 256); else bar_arrive(5, 256);
        }
        DBG_T(81);
        DBG_G(122);

        {
        const int tid = tid_, lane = tid & 31;
        const int g8 = lane >> 2, qd = lane & 3, l16 = lane & 15;
        uint32_t h2[18], gb[9], k1, k2;
        float4* rec = reinterpret_cast<float4*>(red + 128);
        const uint2* candp = reinterpret_cast<const uint2*>(padd(g_cand, ((blockIdx.x & (CREP - 1)) * NCTA + (tid >> 1)) * 32 + (tid & 1) * 8));
        uint2 cd;
        auto stage_out = [&]() {
#pragma unroll
            for (int k = 0; k < 9; k++) {
                x1[2 * k] = badd2(x1[2 * k], bmul2(gb[k], h2[2 * k]));
                x1[2 * k + 1] = badd2(x1[2 * k + 1], bmul2(gb[k], h2[2 * k + 1]));
            }
#pragma unroll
            for (int ch = 0; ch < 4; ch++) stsm_x4(xs + ch * 256, x1[4 * ch], x1[4 * ch + 1], x1[4 * ch + 2], x1[4 * ch + 3]);
            asm volatile("stmatrix.sync.aligned.m8n8.x2.shared.b16 [%0], {%1, %2};" ::"r"(xs + 1024 - cw * 16), "r"(x1[16]), "r"(x1[17]) : "memory");
        };
        {
            uint32_t it = 0, miss;
            if (!P2E) {
                mbar_wait(bar_full + 8, 0);
#pragma unroll
                for (int src = 0; src < 8; src++) v2[src] = lds128(pa + SLOT + src * 2048);
            }
            sum8(at + 8, v2);
            float st[12];
#pragma unroll
            for (int i = 0; i < 12; i++) st[i] = 0.f;
            auto add_pair = [&](int k) {
                x1[2 * k] = badd2(x1[2 * k], bmul2(gw[k].x, at[2 * k]));
                x1[2 * k + 1] = badd2(x1[2 * k + 1], bmul2(gw[k].x, at[2 * k + 1]));
                stats_add(st, x1[2 * k], x1[2 * k + 1], gw[k].y);
            };
#pragma unroll
            for (int k = 0; k < 6; k++) add_pair(k);
            mbar_wait(bar_full + 16, 0);
#pragma unroll
            for (int src = 0; src < 8; src++) v3[src] = lds128(pa + 2 * SLOT + src * 2048);
#pragma unroll 1
            do {
                if (BO && it) __nanosleep(BO);
                miss = 0;
#pragma unroll
                for (int src = 0; src < 8; src++) reload16(v3[src], mb + (size_t)src * 8 * WREG, miss);
            } while (__any_sync(0xffffffffu, miss) && ++it < SPIN / 16);
            if (lane < 4) mbar_arrive_cluster(rel_base + 8 * (1 + (lane >> 1)));
            sum8(at + 12, v3);
            add_pair(6); add_pair(7);
            load_wf(IC<WF0>{}, IC<WF1>{});
            uint2 cs[9];
#pragma unroll
            for (int k = 0; k < 9; k++) cs[k] = lds64(ta + SM_TC + (k < 8 ? (k >> 1) * 64 + (k & 1) * 4 : 256 - cw * 4) * 8);
            mbar_wait(bar_pre, 0);
            mbar_wait(bar_full + 24, 0);
#pragma unroll
            for (int src = 0; src < 8; src++) u4[src] = lds64(sb + 3 * SLOT + src * 2048 + (cw >> 1) * 512 + lane * 16 + (cw & 1) * 8);
#pragma unroll 1
            do {
                if (BO && miss) __nanosleep(BO);
                miss = 0;
#pragma unroll
                for (int src = 0; src < 8; src++) reload8(u4[src], mb4 + (size_t)src * 8 * WREG, miss);
            } while (__any_sync(0xffffffffu, miss) && ++it < SPIN / 16);
            float d[8] = {0.f, 0.f, 0.f, 0.f, 0.f, 0.f, 0.f, 0.f};
#pragma unroll
            for (int i = 0; i < 4; i++) mma16816(d + 4 * (i & 1), u4[2 * i].x, u4[2 * i].y, u4[2 * i + 1].x, u4[2 * i + 1].y, eye, eye);
            at[16] = pack_bf16(d[0] + d[4], d[1] + d[5]); at[17] = pack_bf16(d[2] + d[6], d[3] + d[7]);
            add_pair(8);
            DBG_G(123);
            const float2 ws = *reinterpret_cast<const float2*>(smem_raw + SM_TS);
            uint4* cdst = padd(g_cand, CFULL ? ((tid >> 1) * NCTA + rg) * 32 + (tid & 1) * 16 : (tid * NCTA + rg) * 32);
            uint32_t mean2;
            float dot;
            const float rsd = rows_stats(st, rec, cw, lane, mean2, dot);
            const uint32_t b = __float_as_uint(fmaf(fmaf(-bf_lo(mean2), ws.x, dot), rsd, ws.y));
            const uint32_t key = (((b & 0x80000000u) ? ~b : (b | 0x80000000u)) | 2047u) - (rg * 16 + l16);
            top2(key, k1, k2);
            if (tid < (CFULL + 1) * CREP) st_relaxed(cdst, k1, tag, k2, tag);
            cd = ld_relaxed64(candp);
            rows_normalise(h2, x1, mean2, rsd, lane, [&]() {
#pragma unroll
                for (int k = 0; k < 9; k++) gb[k] = lds32(sb + SM_TG + (cw * 8 + qd + (k < 8 ? (k >> 1) * 64 + (k & 1) * 4 : 256 - cw * 4)) * 4);
                if (WFE) load_wf(IC<WF1>{}, IC<WF2>{});
            });
#pragma unroll
            for (int k = 0; k < 18; k++) h2[k] = badd2(bmul2(h2[k], cs[k >> 1].x), cs[k >> 1].y);
            const uint32_t r1 = ~k1 & 15, r2 = ~k2 & 15;
            uint32_t todo = ((r1 & 7) == g8) | ((r2 & 7) == g8) << 1;
#pragma unroll 1
            while (todo) {
                const bool second = !(todo & 1), hi = (second ? r2 : r1) & 8;
                uint4* dst = padd(g_rows, ((rg * 2 + second) * RSLOT + cw * 16 + qd) * 16);
                uint32_t r[18];
#pragma unroll
                for (int k = 0; k < 9; k++) { r[k] = hi ? h2[2 * k + 1] : h2[2 * k]; r[9 + k] = hi ? x1[2 * k + 1] : x1[2 * k]; }
                fence_regs(r);
                st_relaxed(dst, r[0], r[1], r[2], r[3]);
                st_relaxed(dst + 4, r[4], r[5], r[6], r[7]);
                st_relaxed64(reinterpret_cast<uint2*>(padd(dst, 2048 - cw * 224 - qd * 8)), r[8], r[17]);
                st_relaxed(dst + 8, r[9], r[10], r[11], r[12]);
                st_relaxed(dst + 12, r[13], r[14], r[15], r[16]);
                todo &= todo - 1;
            }
            __syncwarp();

            if (SO == 0) stage_out();
            if (!WFE) load_wf(IC<WF1>{}, IC<WF2>{});
        }
        DBG_G(110);
        float2* part = reinterpret_cast<float2*>(smem_raw + 3 * SLOT + UNIT);
        bf16* act = reinterpret_cast<bf16*>(smem_raw + 3 * SLOT + UNIT + 4096);
        {
            uint32_t it = 0;
            const bool own = (tid >> 1) == rg;
            const uint32_t ks = sb + 3 * SLOT + UNIT + 5120;
#pragma unroll 1
            while (cd.y != tag && !own && ++it < SPIN / 16) cd = ld_relaxed64(candp);
            asm volatile("st.shared.u32 [%0], %1;" ::"r"(ks + tid * 4), "r"(own ? (tid & 1) ? k2 : k1 : cd.x) : "memory");
            bar_sync(3, 256);
            DBG_G(111);
            const uint4 a = lds128(ks + lane * 16), b = lds128(ks + 512 + lane * 16);
            const uint32_t a1 = max(a.x, a.z), a2 = __vimax3_u32(min(a.x, a.z), a.y, a.w);
            const uint32_t b1 = max(b.x, b.z), b2 = __vimax3_u32(min(b.x, b.z), b.y, b.w);
            const uint32_t c1 = max(a1, b1), c2 = __vimax3_u32(min(a1, b1), a2, b2);
            k1 = __reduce_max_sync(0xffffffffu, c1);
            k2 = __reduce_max_sync(0xffffffffu, c1 == k1 ? c2 : c1);
        }
        const int sel0 = ~k1 & 2047, sel1 = ~k2 & 2047;
        const uint32_t slot0 = (sel0 >> 4) * 2, slot1 = (sel1 >> 4) * 2 + ((sel0 ^ sel1) < 16);
        uint4 b[9], b2[3];
        {
            const bool tk = cw < 4 ? cw & 2 : lane & 16;
            const int ri = cw < 4 ? tid & 63 : 64 + l16;
            const uint4* hp = padd(g_rows, ((tk ? slot1 : slot0) * RSLOT + (cw < 4 ? ri + (ri & 56) : ri + 64)) * 16);
            const uint32_t hs = sb + 3 * SLOT + UNIT + 8192;
            uint4 hr = make_uint4(cw < 5 ? ~0u : 0, 0, 0, 0);
            uint32_t it = 0, miss;
            reload16(hr, hp, miss);
            if (OUTP == 0 && SO == 0 && tid == 255) {
                reinterpret_cast<int2*>(red)[8] = make_int2(sel0, sel1);
                mbar_arrive(bar_out);
            }
            if (SO) stage_out();
            if (SO == 2) {
                __syncwarp();
                if (lane == 0) {
                    reinterpret_cast<int2*>(red)[8] = make_int2(sel0, sel1);
                    mbar_arrive(bar_out);
                }
            }
            load_wf(IC<WF2>{}, IC<27>{});
            mbar_wait(bar_full + 8, 1);
            mbar_wait(bar_full + 16, 1);
            {
                const uint32_t da = sb + (lane < 18 ? SLOT + lane * XP : 2 * SLOT + (lane - 18) * XP) + cw * 144;
                const uint32_t db = sb + 2 * SLOT + (14 + (lane & 3)) * XP + cw * 144 + (lane >> 3) * 16;
#pragma unroll
                for (int i = 0; i < 9; i++) b[i] = ldsm4t(da + i * 16);
#pragma unroll
                for (int i = 0; i < 3; i++) b2[i] = ldsm4t(db + i * 48);
            }
#pragma unroll 1
            do {
                miss = 0;
                reload16(hr, hp, miss);
            } while (__any_sync(0xffffffffu, miss) && ++it < SPIN / 16);
            if (cw < 5) asm volatile("st.shared.v4.u32 [%0], {%1, %2, %3, %4};" ::"r"(hs + (tk * 84 + ri) * 16), "r"(hr.x), "r"(hr.y), "r"(hr.z), "r"(hr.w) : "memory");
            bar_sync(3, 256);
            if (OUTP == 0 && SO == 1 && tid == 255) {
                reinterpret_cast<int2*>(red)[8] = make_int2(sel0, sel1);
                mbar_arrive(bar_out);
            }
            uint4 hv[4];
            uint32_t hw[2];
#pragma unroll
            for (int i = 0; i < 4; i++) hv[i] = lds128(hs + ((g8 & 1) * 84 + (cw >> 1) * 16 + qd + i * 4) * 16);
#pragma unroll
            for (int i = 0; i < 2; i++)
                hw[i] = lds32(hs + ((g8 & 1) * 84 + 64) * 16 + (cw >> 1) * 64 + qd * 8 + i * 32);
            DBG_G(112);
            float acc[24];
#pragma unroll
            for (int i = 0; i < 24; i++) acc[i] = 0.f;
#pragma unroll
            for (int i = 0; i < 27; i++) {
                const int ks = i / 3;
                mma16816(acc + 4 * (i % 6), wf[i].x, wf[i].y, wf[i].z, wf[i].w, ks == 8 ? hw[0] : (ks & 1) ? hv[ks >> 1 & 3].z : hv[ks >> 1 & 3].x,
                         ks == 8 ? hw[1] : (ks & 1) ? hv[ks >> 1 & 3].w : hv[ks >> 1 & 3].y);
            }
            if (qd == 0) {
#pragma unroll
                for (int i = 0; i < 5; i++) part[cw * 48 + i * 8 + g8] = make_float2(acc[2 * i] + acc[12 + 2 * i], acc[2 * i + 1] + acc[13 + 2 * i]);
            }
        }
        {
            uint2* dst = padd(g_ypart, ((((g8 & 1) * 36 + ((cw * 9) >> 1)) * NCTA + blockIdx.x) * 8 + (cw & 1) * 4 + qd) * 8);
            uint2* dst1 = dst + ((cw & 1) ? NCTA * 8 - 4 : 4);
            bar_sync(3, 256);

            {
                const float* pp = reinterpret_cast<const float*>(part) + ((blockIdx.x & 1) << 3) + (tid & 127);
                const float gs = rbf((pp[0] + pp[192]) + (pp[384] + pp[576])), us = rbf((pp[96] + pp[288]) + (pp[480] + pp[672]));
                const float v = rbf(gs * sigmoidf_(gs)) * us;
                if (tid < 80) act[(tid & 1) * 56 + (tid >> 1)] = __float2bfloat16_rn(tid < 72 ? v : 0.f);
            }
            bar_sync(3, 256);
            DBG_G(113);
            const uint32_t ap = sb + 3 * SLOT + UNIT + 4096 + (lane & 1) * 112 + (lane >> 4) * 16;
            const uint4 a0 = ldsm4(ap), a1 = ldsm4(ap + 32), a2 = ldsm4(ap + 64);
            float y[36];
#pragma unroll
            for (int i = 0; i < 36; i++) y[i] = 0.f;
#pragma unroll
            for (int i = 0; i < 9; i++) {
                const uint32_t bl = i % 3 == 0 ? b2[i / 3].x : i % 3 == 1 ? b2[i / 3].y : b2[i / 3].z;
                mma16816(y + 4 * i, a0.x, a0.y, a0.z, a0.w, b[i].x, b[i].y);
                mma16816(y + 4 * i, a1.x, a1.y, a1.z, a1.w, b[i].z, b[i].w);
                mma1688(y + 4 * i, a2.x, a2.y, bl);
            }
#pragma unroll
            for (int i = 0; i < 9; i++)
                if (lane < 8) st_relaxed64(((i & 1) ? dst1 : dst) + (i >> 1) * (NCTA * 8), __float_as_uint(y[4 * i]), __float_as_uint(y[4 * i + 1]));
        }
        DBG_G(114);
        if (OUTP == 1 && tid == 255) {
            reinterpret_cast<int2*>(red)[8] = make_int2(sel0, sel1);
            mbar_arrive(bar_out);
        }
        if (blockIdx.x == 127 && tid == 0) gs->epoch[0] = tag;
        if (blockIdx.x < 72) {
            const int tok = blockIdx.x >= 36, grp = blockIdx.x - tok * 36, cp = grp * 8 + (lane & 7);
            const uint2* src = padd(g_ypart, (blockIdx.x * NCTA * 8 + tid) * 8);
            const uint8_t* hsrc = reinterpret_cast<const uint8_t*>(padd(g_rows, (tok ? slot1 : slot0) * (RSLOT * 16) +
                (grp < 32 ? (grp & 7) * 256 + (grp >> 4) * 64 + qd * 16 + (grp & 8) + (lane & 4) : 2048 + (cp - 256) * 8)));
            const uint8_t* xsrc = hsrc + (grp < 32 ? 128 : 4);
            uint32_t* dst = padd(reinterpret_cast<uint32_t*>(args.out), (tok ? sel1 : sel0) * (D_ * 2) + cp * 4);
            const uint32_t gb = reinterpret_cast<const uint32_t*>(smem_raw + SM_TG)[cp];
            const uint32_t ksel = ((tok ? k2 : k1) & ~2047u) | 1024u;
            const float sg = sigmoidf_(rbf(__uint_as_float((ksel & 0x80000000u) ? (ksel & 0x7fffffffu) : ~ksel)));
            uint2 v[4];
            uint32_t hv, xv, it = 0;
            bool miss;
#pragma unroll 1
            do {
#pragma unroll
                for (int i = 0; i < 4; i++) v[i] = ld_relaxed64(src + i * 256);
                hv = ld_relaxed32(hsrc);
                xv = ld_relaxed32(xsrc);
                miss = max(__vimax3_u32(v[0].x, v[1].x, v[2].x), __vimax3_u32(v[3].x, hv, xv)) == ~0u;
            } while (__any_sync(0xffffffffu, miss) && ++it < SPIN / 16);
            float y0 = (__uint_as_float(v[0].x) + __uint_as_float(v[1].x)) + (__uint_as_float(v[2].x) + __uint_as_float(v[3].x));
            float y1 = (__uint_as_float(v[0].y) + __uint_as_float(v[1].y)) + (__uint_as_float(v[2].y) + __uint_as_float(v[3].y));
            y0 += __shfl_xor_sync(0xffffffffu, y0, 8); y1 += __shfl_xor_sync(0xffffffffu, y1, 8);
            y0 += __shfl_xor_sync(0xffffffffu, y0, 16); y1 += __shfl_xor_sync(0xffffffffu, y1, 16);
            if (lane < 8) reinterpret_cast<float2*>(rec)[cw * 8 + lane] = make_float2(y0, y1);
            bar_sync(3, 256);
            if (cw == 0) {
                const float2 t0_ = reinterpret_cast<const float2*>(rec)[lane], t1_ = reinterpret_cast<const float2*>(rec)[32 + lane];
                y0 = t0_.x + t1_.x; y1 = t0_.y + t1_.y;
                y0 += __shfl_xor_sync(0xffffffffu, y0, 8); y1 += __shfl_xor_sync(0xffffffffu, y1, 8);
                y0 += __shfl_xor_sync(0xffffffffu, y0, 16); y1 += __shfl_xor_sync(0xffffffffu, y1, 16);
                const uint32_t y2 = bmul2(pack_bf16(y0, y1), pack_bf16(sg, sg));
                if (lane < 8) *dst = badd2(xv, bmul2(gb, badd2(hv, y2)));
            }
        }
        }
        DBG_T(88);
        DBG_G(121);
    }
}

typedef CUresult (*EncodeFn)(CUtensorMap*, CUtensorMapDataType, cuuint32_t, void*, const cuuint64_t*, const cuuint64_t*,
                             const cuuint32_t*, const cuuint32_t*, CUtensorMapInterleave, CUtensorMapSwizzle,
                             CUtensorMapL2promotion, CUtensorMapFloatOOBfill);

static void make_map(EncodeFn enc, CUtensorMap* m, const void* ptr, int rank, const cuuint64_t* dims,
                     const cuuint64_t* strides, const cuuint32_t* box, CUtensorMapSwizzle sw = CU_TENSOR_MAP_SWIZZLE_128B,
                     CUtensorMapDataType dt = CU_TENSOR_MAP_DATA_TYPE_BFLOAT16) {
    const cuuint32_t es[3] = {1, 1, 1};
    enc(m, dt, rank, const_cast<void*>(ptr), dims, strides, box, es,
        CU_TENSOR_MAP_INTERLEAVE_NONE, sw, CU_TENSOR_MAP_L2_PROMOTION_L2_128B,
        CU_TENSOR_MAP_FLOAT_OOB_FILL_NONE);
}

extern "C" void kernel_launch(void* const* d_in, const int* in_sizes, int n_in, void* d_out, int out_size) {
    const bf16* x = (const bf16*)d_in[0];
    const bf16* kc = (const bf16*)d_in[1];
    const bf16* vc = (const bf16*)d_in[2];
    const bf16* wq = (const bf16*)d_in[3];
    const bf16* wo = (const bf16*)d_in[4];
    const bf16* w_r = (const bf16*)d_in[6];
    const bf16* w_gate = (const bf16*)d_in[7];
    const bf16* w_up = (const bf16*)d_in[8];
    const bf16* w_down = (const bf16*)d_in[9];
    const bf16* cvec = (const bf16*)d_in[10];
    const bf16* w_mod = (const bf16*)d_in[11];
    bf16* out = (bf16*)d_out;

    void* fn = nullptr;
    cudaDriverEntryPointQueryResult qr;
    cudaGetDriverEntryPoint("cuTensorMapEncodeTiled", &fn, cudaEnableDefault, &qr);
    EncodeFn enc = (EncodeFn)fn;
    void* p_s;
    cudaGetSymbolAddress(&p_s, g_s);

    CUtensorMap tm_wq, tm_k, tm_v, tm_wo, tm_p, tm_x, tm_d, tm_g, tm_u;
    { cuuint64_t d[2] = {QD, D_}, s[1] = {QD * 2}; cuuint32_t b[2] = {64, 128}; make_map(enc, &tm_wq, wq, 2, d, s, b); }
    { cuuint64_t d[2] = {DH, HKV * S_}, s[1] = {DH * 2}; cuuint32_t b[2] = {64, 128};
      make_map(enc, &tm_k, kc, 2, d, s, b); make_map(enc, &tm_v, vc, 2, d, s, b); }
    { cuuint64_t d[2] = {D_, QD}, s[1] = {D_ * 2}; cuuint32_t b[2] = {64, 128}; make_map(enc, &tm_wo, wo, 2, d, s, b); }
    { cuuint64_t d[3] = {256, 160, NCTA}, s[2] = {1024, 8 * WREG}; cuuint32_t b[3] = {256, 2, 8};
      make_map(enc, &tm_p, ((Scratch*)p_s)->frag, 3, d, s, b, CU_TENSOR_MAP_SWIZZLE_NONE, CU_TENSOR_MAP_DATA_TYPE_UINT32); }
    { cuuint64_t d[2] = {D_ / 4, S_}, s[1] = {D_ * 2}; cuuint32_t b[2] = {XP / 8, 16};
      make_map(enc, &tm_x, x, 2, d, s, b, CU_TENSOR_MAP_SWIZZLE_NONE, CU_TENSOR_MAP_DATA_TYPE_UINT64); }
    { cuuint64_t d[2] = {D_ / 4, F_}, s[1] = {D_ * 2}; cuuint32_t b[2] = {XP / 8, 18};
      make_map(enc, &tm_d, w_down, 2, d, s, b, CU_TENSOR_MAP_SWIZZLE_NONE, CU_TENSOR_MAP_DATA_TYPE_UINT64); }
    { cuuint64_t d[2] = {F_, D_}, s[1] = {F_ * 2}; cuuint32_t b[2] = {40, 24};
      make_map(enc, &tm_g, w_gate, 2, d, s, b, CU_TENSOR_MAP_SWIZZLE_NONE); make_map(enc, &tm_u, w_up, 2, d, s, b, CU_TENSOR_MAP_SWIZZLE_NONE); }

    cudaFuncSetAttribute(fused_kernel<true>, cudaFuncAttributeMaxDynamicSharedMemorySize, SM_TOTAL);
    cudaFuncSetAttribute(fused_kernel<false>, cudaFuncAttributeMaxDynamicSharedMemorySize, SM_TOTAL);
    cudaLaunchConfig_t cfg = {};
    cfg.gridDim = NCTA + 4; cfg.blockDim = 384; cfg.dynamicSmemBytes = SM_TOTAL;
    cudaLaunchAttribute at;
    at.id = cudaLaunchAttributeClusterDimension; at.val.clusterDim.x = 2; at.val.clusterDim.y = 1; at.val.clusterDim.z = 1;
    cfg.attrs = &at; cfg.numAttrs = 1;
    int ncl = 0;
    if (cudaOccupancyMaxActiveClusters(&ncl, fused_kernel<true>, &cfg) != cudaSuccess) { ncl = 0; cudaGetLastError(); }
    Args args{w_mod, cvec, (Scratch*)p_s, desc_lo(0, UNIT) | (0x40000040ull << 32), out, x, kc, vc, wq, wo, w_r, w_down};
    if (USE_SPARE && ncl >= NCTA / 2 + 2)
        fused_kernel<true><<<NCTA + 4, 384, SM_TOTAL>>>(args, tm_wq, tm_k, tm_v, tm_wo, tm_p, tm_x, tm_d, tm_g, tm_u);
    else
        fused_kernel<false><<<NCTA, 384, SM_TOTAL>>>(args, tm_wq, tm_k, tm_v, tm_wo, tm_p, tm_x, tm_d, tm_g, tm_u);
}
```

```cpp
#include <cuda_runtime.h>
#include <cuda_bf16.h>
#include <cuda.h>
#include <stdint.h>
#include <math.h>

typedef __nv_bfloat16 bf16;

constexpr int S_ = 2048;
constexpr int D_ = 576;
constexpr int HQ = 32, HKV = 16, DH = 128;
constexpr int F_ = 4608;
constexpr int QD = HQ * DH;

constexpr int NCTA = 128;
constexpr int WREG = 5 * 4096;
constexpr int CREP = 8;
constexpr int RSLOT = 192;
constexpr int MREP = 4;
struct Scratch {
    unsigned int epoch[128];
    unsigned int flag_mod[NCTA];
    unsigned int flag_part[16 * 32];
    unsigned int flag_q3[16 * 32];
    unsigned int flag_h[NCTA * 32];
    uint2 mod1[MREP * D_];
    uint32_t mod2[4 * D_];
    uint4 cand[CREP * NCTA * 2];
    uint2 ypart[72 * NCTA * 8];
    uint4 h[2][NCTA * 36 * 32];
    uint4 q3[NCTA * 8 * 128];
    uint4 rows[NCTA * 2 * RSLOT];
    uint8_t frag[NCTA * 8 * WREG];
    uint8_t keep[NCTA * 8 * 4096];
};
__device__ __align__(1024) Scratch g_s;
#define g_h gs->h[tag & 1]
#define g_q3 gs->q3
#define g_keep gs->keep
#define g_flag_h gs->flag_h
#define g_flag_part gs->flag_part
#define g_flag_mod gs->flag_mod
#define g_flag_q3 gs->flag_q3
#define g_frag gs->frag
#define g_cand gs->cand
#define g_ypart gs->ypart
#define g_rows gs->rows

#define DBG_INIT()
#define DBG_P(i)
#define DBG_PG(i)
#define DBG_T(i)
#define DBG_G(i)

__device__ __forceinline__ uint32_t pack_bf16(float lo, float hi) {
    uint32_t r;
    asm("cvt.rn.bf16x2.f32 %0, %1, %2;" : "=r"(r) : "f"(hi), "f"(lo));
    return r;
}
__device__ __forceinline__ float rbf(float x) { return __uint_as_float(pack_bf16(0.f, x)); }
__device__ __forceinline__ float bf_lo(uint32_t v) { return __uint_as_float(v << 16); }
__device__ __forceinline__ float bf_hi(uint32_t v) { return __uint_as_float(v & 0xffff0000u); }
__device__ __forceinline__ float ex2(float x) {
    float y;
    asm("ex2.approx.ftz.f32 %0, %1;" : "=f"(y) : "f"(x));
    return y;
}
template <class T>
__device__ __forceinline__ T* padd(T* p, uint32_t off) {
    unsigned long long r;
    asm("{\n.reg .b32 l, h;\nmov.b64 {l, h}, %1;\nadd.cc.u32 l, l, %2;\naddc.u32 h, h, 0;\nmov.b64 %0, {l, h};\n}" : "=l"(r) : "l"(p), "r"(off));
    return reinterpret_cast<T*>(r);
}
__device__ __forceinline__ uint32_t smem_u32(const void* p) { return (uint32_t)__cvta_generic_to_shared(p); }
__device__ __forceinline__ void mbar_init(uint32_t bar, uint32_t cnt) {
    asm volatile("mbarrier.init.shared::cta.b64 [%0], %1;" ::"r"(bar), "r"(cnt) : "memory");
}
__device__ __forceinline__ void mbar_expect_tx(uint32_t bar, uint32_t bytes) {
    asm volatile("mbarrier.arrive.expect_tx.shared::cta.b64 _, [%0], %1;" ::"r"(bar), "r"(bytes) : "memory");
}
__device__ __forceinline__ void mbar_arrive(uint32_t bar) {
    asm volatile("mbarrier.arrive.shared::cta.b64 _, [%0];" ::"r"(bar) : "memory");
}
__device__ __forceinline__ void mbar_arrive_cluster(uint32_t cluster_addr) {
    asm volatile("mbarrier.arrive.shared::cluster.b64 _, [%0];" ::"r"(cluster_addr) : "memory");
}
constexpr uint32_t SPIN = 1u << 20;
__device__ __forceinline__ void mbar_wait(uint32_t bar, uint32_t parity) {
    asm volatile("{\n.reg .pred p;\n.reg .b32 c;\nmov.b32 c, 0;\n"
                 "W_%=:\nmbarrier.try_wait.parity.shared::cta.b64 p, [%0], %1;\n"
                 "add.u32 c, c, 1;\nsetp.lt.and.u32 p, c, 0x100000, !p;\n@p bra W_%=;\n}"
                 ::"r"(bar), "r"(parity) : "memory");
}
__device__ __forceinline__ void anchor(uint32_t addr, float v) {
    asm volatile("{\n.reg .pred p;\nsetp.lt.f32 p, %1, 0f00000000;\n@p st.volatile.shared.f32 [%0], %1;\n}" ::"r"(addr), "f"(v) : "memory");
}
__device__ __forceinline__ void anchor(uint32_t addr, uint32_t v) {
    asm volatile("{\n.reg .pred p;\nsetp.eq.u32 p, %1, 0xffffffff;\n@p st.volatile.shared.u32 [%0], %1;\n}" ::"r"(addr), "r"(v) : "memory");
}
__device__ __forceinline__ void hold(float& a, float& b) {
    asm volatile("{\n.reg .pred p;\n.reg .b64 t;\n.reg .b32 l, h;\nmov.u64 t, %%clock64;\nmov.b64 {l, h}, t;\nsetp.eq.u32 p, h, 0xffffffff;\n"
                 "@p mov.f32 %0, 0f00000000;\n@p mov.f32 %1, 0f00000000;\n}" : "+f"(a), "+f"(b) :: "memory");
}
__device__ __forceinline__ void mbar_wait_sleep(uint32_t bar, uint32_t parity) {
    asm volatile("{\n.reg .pred p;\n.reg .b32 c;\nmov.b32 c, 0;\n"
                 "W_%=:\nmbarrier.try_wait.parity.shared::cta.b64 p, [%0], %1, 5000;\n"
                 "add.u32 c, c, 1;\nsetp.lt.and.u32 p, c, 0x20000, !p;\n@p bra W_%=;\n}"
                 ::"r"(bar), "r"(parity) : "memory");
}
__device__ __forceinline__ uint32_t load_tag(const Scratch* gs) {
    uint32_t tag;
    asm volatile("ld.global.ca.u32 %0, [%1];" : "=r"(tag) : "l"(gs->epoch) : "memory");
    return tag + 1;
}
__device__ __forceinline__ uint4 ld_relaxed(const uint4* p) {
    uint4 v;
    asm volatile("ld.relaxed.gpu.global.v4.u32 {%0,%1,%2,%3}, [%4];" : "=r"(v.x), "=r"(v.y), "=r"(v.z), "=r"(v.w) : "l"(p) : "memory");
    return v;
}
__device__ __forceinline__ void st_relaxed(uint4* p, uint32_t a, uint32_t b, uint32_t c, uint32_t d) {
    asm volatile("{\n.reg .b64 u, v;\nmov.b64 u, {%1, %2};\nmov.b64 v, {%3, %4};\nst.relaxed.gpu.global.v2.b64 [%0], {u, v};\n}"
                 ::"l"(p), "r"(a), "r"(b), "r"(c), "r"(d) : "memory");
}
__device__ __forceinline__ void st_relaxed4(void* p, uint32_t a, uint32_t b, uint32_t c, uint32_t d) {
    asm volatile("st.relaxed.gpu.global.v4.u32 [%0], {%1, %2, %3, %4};" ::"l"(p), "r"(a), "r"(b), "r"(c), "r"(d) : "memory");
}
__device__ __forceinline__ uint2 ld_relaxed8(const void* p) {
    uint2 v;
    asm volatile("ld.relaxed.gpu.global.v2.u32 {%0,%1}, [%2];" : "=r"(v.x), "=r"(v.y) : "l"(p) : "memory");
    return v;
}
__device__ __forceinline__ uint2 ld_relaxed64(const uint2* p) {
    uint2 v;
    asm volatile("{\n.reg .b64 u;\nld.relaxed.gpu.global.b64 u, [%2];\nmov.b64 {%0, %1}, u;\n}" : "=r"(v.x), "=r"(v.y) : "l"(p) : "memory");
    return v;
}
__device__ __forceinline__ void st_relaxed64(uint2* p, uint32_t a, uint32_t b) {
    asm volatile("{\n.reg .b64 u;\nmov.b64 u, {%1, %2};\nst.relaxed.gpu.global.b64 [%0], u;\n}" ::"l"(p), "r"(a), "r"(b) : "memory");
}
__device__ __forceinline__ uint4 ld_relaxed2(const uint4* p) {
    uint4 v;
    asm volatile("{\n.reg .b64 u, w;\nld.relaxed.gpu.global.v2.b64 {u, w}, [%4];\nmov.b64 {%0, %1}, u;\nmov.b64 {%2, %3}, w;\n}"
                 : "=r"(v.x), "=r"(v.y), "=r"(v.z), "=r"(v.w) : "l"(p) : "memory");
    return v;
}
__device__ __forceinline__ void reload16(uint4& v, const void* p, uint32_t& miss) {
    asm volatile("{\n.reg .pred p;\n.reg .b32 m;\n.reg .b64 u, w;\nmax.u32 m, %0, %2;\nsetp.eq.u32 p, m, 0xffffffff;\n"
                 "mov.b64 u, {%0, %1};\nmov.b64 w, {%2, %3};\n@p ld.relaxed.gpu.global.v2.b64 {u, w}, [%5];\n"
                 "mov.b64 {%0, %1}, u;\nmov.b64 {%2, %3}, w;\n@p mov.u32 %4, 1;\n}"
                 : "+r"(v.x), "+r"(v.y), "+r"(v.z), "+r"(v.w), "+r"(miss) : "l"(p) : "memory");
}
__device__ __forceinline__ void reload8(uint2& v, const void* p, uint32_t& miss) {
    asm volatile("{\n.reg .pred p;\n.reg .b64 u;\nsetp.eq.u32 p, %0, 0xffffffff;\nmov.b64 u, {%0, %1};\n"
                 "@p ld.relaxed.gpu.global.b64 u, [%3];\nmov.b64 {%0, %1}, u;\n@p mov.u32 %2, 1;\n}"
                 : "+r"(v.x), "+r"(v.y), "+r"(miss) : "l"(p) : "memory");
}
__device__ __forceinline__ uint32_t ld_relaxed32(const void* p) {
    uint32_t v;
    asm volatile("ld.relaxed.gpu.global.u32 %0, [%1];" : "=r"(v) : "l"(p) : "memory");
    return v;
}
__device__ __forceinline__ void flag_wait(const unsigned int* p, uint32_t tag) {
    uint32_t v, it = 0;
#pragma unroll 1
    do {
        asm volatile("ld.relaxed.gpu.global.u32 %0, [%1];" : "=r"(v) : "l"(p) : "memory");
    } while (__any_sync(0xffffffffu, v != tag) && ++it < SPIN / 16);
    asm volatile("fence.acquire.gpu;" ::: "memory");
    __syncwarp();
}
__device__ __forceinline__ bool elect() {
    uint32_t p;
    asm volatile("{\n.reg .pred p;\nelect.sync _|p, 0xffffffff;\nselp.u32 %0, 1, 0, p;\n}" : "=r"(p));
    return p;
}
__device__ __forceinline__ void flag_release(unsigned int* p, uint32_t tag) {
    asm volatile("st.release.gpu.global.u32 [%0], %1;" ::"l"(p), "r"(tag) : "memory");
}
__device__ __forceinline__ uint32_t touch(const void* p) {
    uint32_t v;
    asm volatile("ld.global.nc.L1::no_allocate.L2::128B.u32 %0, [%1];" : "=r"(v) : "l"(p));
    return v;
}
__device__ __forceinline__ void bar_sync(int id, int n) { asm volatile("bar.sync %0, %1;" ::"r"(id), "r"(n) : "memory"); }
__device__ __forceinline__ void bar_arrive(int id, int n) { asm volatile("bar.arrive %0, %1;" ::"r"(id), "r"(n) : "memory"); }

constexpr uint64_t EVICT_NORMAL = 0x1000000000000000ull, EVICT_FIRST = 0x12F0000000000000ull;
__device__ __forceinline__ void tma2d(uint32_t dst, const CUtensorMap* m, int c0, int c1, uint32_t bar) {
    asm volatile("cp.async.bulk.tensor.2d.shared::cluster.global.mbarrier::complete_tx::bytes.L2::cache_hint [%0], [%1, {%3, %4}], [%2], %5;"
                 ::"r"(dst), "l"(m), "r"(bar), "r"(c0), "r"(c1), "l"(EVICT_FIRST) : "memory");
}
__device__ __forceinline__ void tma2d_mc(uint32_t dst, const CUtensorMap* m, int c0, int c1, uint32_t bar, uint64_t pol) {
    asm volatile("cp.async.bulk.tensor.2d.shared::cluster.global.mbarrier::complete_tx::bytes.multicast::cluster.L2::cache_hint [%0], [%1, {%3, %4}], [%2], %5, %6;"
                 ::"r"(dst), "l"(m), "r"(bar), "r"(c0), "r"(c1), "h"((uint16_t)3), "l"(pol) : "memory");
}
__device__ __forceinline__ void tma3d(uint32_t dst, const CUtensorMap* m, int c0, int c1, int c2, uint32_t bar) {
    asm volatile("cp.async.bulk.tensor.3d.shared::cluster.global.mbarrier::complete_tx::bytes.L2::cache_hint [%0], [%1, {%3, %4, %5}], [%2], %6;"
                 ::"r"(dst), "l"(m), "r"(bar), "r"(c0), "r"(c1), "r"(c2), "l"(EVICT_FIRST) : "memory");
}
__device__ __forceinline__ void bulk_load(uint32_t dst, const void* src, uint32_t bytes, uint32_t bar) {
    asm volatile("cp.async.bulk.shared::cluster.global.mbarrier::complete_tx::bytes [%0], [%1], %2, [%3];"
                 ::"r"(dst), "l"(src), "r"(bytes), "r"(bar) : "memory");
}
__device__ __forceinline__ void l2_prefetch(const void* src, uint32_t bytes) {
    asm volatile("cp.async.bulk.prefetch.L2.global [%0], %1;" ::"l"(src), "r"(bytes) : "memory");
}
__device__ __forceinline__ uint32_t bmul2(uint32_t a, uint32_t b) { uint32_t r; asm("mul.rn.bf16x2 %0, %1, %2;" : "=r"(r) : "r"(a), "r"(b)); return r; }
__device__ __forceinline__ uint32_t badd2(uint32_t a, uint32_t b) { uint32_t r; asm("add.rn.bf16x2 %0, %1, %2;" : "=r"(r) : "r"(a), "r"(b)); return r; }
__device__ __forceinline__ uint32_t bsub2(uint32_t a, uint32_t b) { uint32_t r; asm("sub.rn.bf16x2 %0, %1, %2;" : "=r"(r) : "r"(a), "r"(b)); return r; }
__device__ __forceinline__ uint32_t bmax2(uint32_t a, uint32_t b) { uint32_t r; asm("max.bf16x2 %0, %1, %2;" : "=r"(r) : "r"(a), "r"(b)); return r; }
__device__ __forceinline__ uint32_t bfma2(uint32_t a, uint32_t b, uint32_t c) { uint32_t r; asm("fma.rn.bf16x2 %0, %1, %2, %3;" : "=r"(r) : "r"(a), "r"(b), "r"(c)); return r; }
__device__ __forceinline__ uint4 lds128(uint32_t a) { uint4 v; asm volatile("ld.shared.v4.u32 {%0,%1,%2,%3}, [%4];" : "=r"(v.x), "=r"(v.y), "=r"(v.z), "=r"(v.w) : "r"(a) : "memory"); return v; }
__device__ __forceinline__ uint2 lds64(uint32_t a) { uint2 v; asm volatile("ld.shared.v2.u32 {%0,%1}, [%2];" : "=r"(v.x), "=r"(v.y) : "r"(a) : "memory"); return v; }
__device__ __forceinline__ uint32_t lds32(uint32_t a) { uint32_t v; asm volatile("ld.shared.u32 %0, [%1];" : "=r"(v) : "r"(a) : "memory"); return v; }
__device__ __forceinline__ uint4 ldsm4(uint32_t a) {
    uint4 v;
    asm volatile("ldmatrix.sync.aligned.m8n8.x4.shared.b16 {%0,%1,%2,%3}, [%4];" : "=r"(v.x), "=r"(v.y), "=r"(v.z), "=r"(v.w) : "r"(a) : "memory");
    return v;
}
__device__ __forceinline__ uint4 ldsm4t(uint32_t a) {
    uint4 v;
    asm volatile("ldmatrix.sync.aligned.m8n8.x4.trans.shared.b16 {%0,%1,%2,%3}, [%4];" : "=r"(v.x), "=r"(v.y), "=r"(v.z), "=r"(v.w) : "r"(a) : "memory");
    return v;
}
__device__ __forceinline__ void mma1688(float* d, uint32_t a0, uint32_t a1, uint32_t b) {
    asm("mma.sync.aligned.m16n8k8.row.col.f32.bf16.bf16.f32 {%0,%1,%2,%3}, {%4,%5}, {%6}, {%0,%1,%2,%3};"
        : "+f"(d[0]), "+f"(d[1]), "+f"(d[2]), "+f"(d[3]) : "r"(a0), "r"(a1), "r"(b));
}
__device__ __forceinline__ void mma16816(float* d, uint32_t a0, uint32_t a1, uint32_t a2, uint32_t a3, uint32_t b0, uint32_t b1) {
    asm("mma.sync.aligned.m16n8k16.row.col.f32.bf16.bf16.f32 {%0,%1,%2,%3}, {%4,%5,%6,%7}, {%8,%9}, {%0,%1,%2,%3};"
                 : "+f"(d[0]), "+f"(d[1]), "+f"(d[2]), "+f"(d[3]) : "r"(a0), "r"(a1), "r"(a2), "r"(a3), "r"(b0), "r"(b1));
}
__device__ __forceinline__ void stsm_x4(uint32_t addr, uint32_t a, uint32_t b, uint32_t c, uint32_t d) {
    asm volatile("stmatrix.sync.aligned.m8n8.x4.shared.b16 [%0], {%1, %2, %3, %4};"
                 ::"r"(addr), "r"(a), "r"(b), "r"(c), "r"(d) : "memory");
}

__device__ __forceinline__ uint64_t mkdesc(uint32_t addr, uint32_t lbo, uint32_t sbo) {
    return (uint64_t)((addr & 0x3FFFF) >> 4) | ((uint64_t)(lbo >> 4) << 16) | ((uint64_t)(sbo >> 4) << 32) | (1ull << 62);
}
constexpr uint32_t SM0 = 1024;
__host__ __device__ constexpr uint32_t desc_lo(uint32_t off, uint32_t lbo) { return ((SM0 + off) >> 4) | ((lbo >> 4) << 16); }
#define WG_FENCE() asm volatile("wgmma.fence.sync.aligned;" ::: "memory")
#define WG_COMMIT() asm volatile("wgmma.commit_group.sync.aligned;" ::: "memory")
#define WG_WAIT(n) asm volatile("wgmma.wait_group.sync.aligned %0;" ::"n"(n) : "memory")

#define F8(a, i) "+f"(a[i]), "+f"(a[i + 1]), "+f"(a[i + 2]), "+f"(a[i + 3]), "+f"(a[i + 4]), "+f"(a[i + 5]), "+f"(a[i + 6]), "+f"(a[i + 7])
#define F16(a, i) F8(a, i), F8(a, i + 8)
#define F64(a) F16(a, 0), F16(a, 16), F16(a, 32), F16(a, 48)
#define F32(a) F16(a, 0), F16(a, 16)
#define L64 "%0,%1,%2,%3,%4,%5,%6,%7,%8,%9,%10,%11,%12,%13,%14,%15,%16,%17,%18,%19,%20,%21,%22,%23,%24,%25,%26,%27,%28,%29,%30,%31,%32,%33,%34,%35,%36,%37,%38,%39,%40,%41,%42,%43,%44,%45,%46,%47,%48,%49,%50,%51,%52,%53,%54,%55,%56,%57,%58,%59,%60,%61,%62,%63"
#define L32 "%0,%1,%2,%3,%4,%5,%6,%7,%8,%9,%10,%11,%12,%13,%14,%15,%16,%17,%18,%19,%20,%21,%22,%23,%24,%25,%26,%27,%28,%29,%30,%31"

template <int TB, int STEP = 128>
__device__ __forceinline__ void mma_rs128(float (&d)[64], uint32_t a0, uint32_t a1, uint32_t a2, uint32_t a3, uint64_t& b, int acc) {
    asm volatile("{\n.reg .pred p;\nsetp.ne.b32 p, %69, 0;\n"
                 "wgmma.mma_async.sync.aligned.m64n128k16.f32.bf16.bf16 {" L64 "}, {%65,%66,%67,%68}, %64, p, 1, 1, %70;\nadd.s64 %64, %64, %71;\n}"
                 : F64(d), "+l"(b) : "r"(a0), "r"(a1), "r"(a2), "r"(a3), "r"(acc), "n"(TB), "n"(STEP));
}
template <int TB>
__device__ __forceinline__ void mma_rs64(float (&d)[32], uint32_t a0, uint32_t a1, uint32_t a2, uint32_t a3, uint64_t& b, int acc) {
    asm volatile("{\n.reg .pred p;\nsetp.ne.b32 p, %37, 0;\n"
                 "wgmma.mma_async.sync.aligned.m64n64k16.f32.bf16.bf16 {" L32 "}, {%33,%34,%35,%36}, %32, p, 1, 1, %38;\nadd.s64 %32, %32, 128;\n}"
                 : F32(d), "+l"(b) : "r"(a0), "r"(a1), "r"(a2), "r"(a3), "r"(acc), "n"(TB));
}
template <int N>
__device__ __forceinline__ void fence_regs(float (&d)[N]) {
#pragma unroll
    for (int i = 0; i < N; i++) asm volatile("" : "+f"(d[i])::"memory");
}
template <int N>
__device__ __forceinline__ void fence_regs(uint32_t (&d)[N]) {
#pragma unroll
    for (int i = 0; i < N; i++) asm volatile("" : "+r"(d[i])::"memory");
}

template <int V> struct IC { static constexpr int value = V; };

constexpr int SLOT = 32768, UNIT = 16384;
constexpr int SM_Q = 4 * SLOT;
constexpr int SM_BAR = 7 * SLOT;
constexpr int SM_RED = SM_BAR + 512;
constexpr int SM_TOTAL = SM_BAR + 3072;
constexpr int XP = D_ * 2 + 16;
constexpr int M_MOD = 16 * XP;
constexpr int SM_T = SM_Q + 2 * D_ * 80, SM_TC = SM_T + D_ * 4, SM_TG = SM_TC + D_ * 4, SM_TS = SM_TG + D_ * 2;
constexpr float CS = 0.08838834764831845f * 1.4426950408889634f;
#define LMAX 0.5f
#define LMIN 0x1p-104f
#define USE_SPARE 1
#define MAXG 2
#define SPLIT 10
#define ESPLIT 3
#define PV1 8
#define RW 2
#define HW 2
#define HW2 1
#define XDELAY 200
#define QDELAY 300
#define TMPF 1
#define PFD0 2000
#define PFD1 400
#define HDELAY 300
#define RCM 16
#define RPE 2
#define OSPLIT 6
#define HOLD 1
#define STAGE 11
#define POFF 102.f
#define WF0 3
#define WF1 13
#define C3D 0
#define C4D 300
#define DD 300
#define P2E 0
#define BO 0
#define MAP 2
#define CFULL 0
#define WFE 1
#define OUTD 0
#define OUTPOL EVICT_FIRST
#define WF2 19
constexpr int PF_KV = 8, PF_WO = 120;

__device__ __forceinline__ int cluster_role() {
    int k;
    asm volatile("mov.u32 %0, %%ctaid.x;" : "=r"(k));
    k >>= 1;
    if (MAP == 0) return k & 63;
    if (MAP == 1) return (k & 7) * 8 + ((k >> 3) & 7);
    if (MAP == 3) {
        asm("mov.u32 %0, %%smid;" : "=r"(k));
        k >>= 1;
        const int r = ((k - 32) * 37) >> 8;
        return k < 32 ? (k & 7) * 8 + (k >> 3) : k < 60 ? (k - 31 - r * 7) * 8 + 4 + r : (k - 58) & 7;
    }
    const int r = ((k - 36) * 37) >> 8, i = k - 36 - r * 7;
    if (MAP == 4) return k < 4 ? 4 + k : k < 36 ? ((k - 4) & 7) * 8 + ((k - 4) >> 3) : (i + 1) * 8 + ((4 + r) & 7);
    return k < 4 ? 12 + k : k < 36 ? ((k - 4) & 7) * 8 + ((k - 4) >> 3) : (i + (i > 0)) * 8 + ((4 + r) & 7);
}

struct Args {
    const bf16 *w_mod, *cvec;
    Scratch* gs;
    uint64_t d0;
    bf16* out;
    const bf16 *x, *kc, *vc, *wq, *wo, *w_r, *w_down;
};

__device__ __forceinline__ void frag_store(uint8_t* p, const uint32_t (&a)[32]) {
#pragma unroll
    for (int i = 0; i < 8; i++)
        __stcg(reinterpret_cast<uint4*>(p + i * 512), make_uint4(a[4 * i], a[4 * i + 1], a[4 * i + 2], a[4 * i + 3]));
}
__device__ __forceinline__ void frag_load(uint32_t (&a)[32], const uint8_t* p) {
#pragma unroll
    for (int i = 0; i < 8; i++) {
        const uint4 v = __ldcg(reinterpret_cast<const uint4*>(p + i * 512));
        a[4 * i] = v.x; a[4 * i + 1] = v.y; a[4 * i + 2] = v.z; a[4 * i + 3] = v.w;
    }
}
__device__ __forceinline__ float quad_sum(float v) {
    v += __shfl_xor_sync(0xffffffffu, v, 1);
    return v + __shfl_xor_sync(0xffffffffu, v, 2);
}
__device__ __forceinline__ float quad_max(float v) {
    v = fmaxf(v, __shfl_xor_sync(0xffffffffu, v, 1));
    return fmaxf(v, __shfl_xor_sync(0xffffffffu, v, 2));
}
__device__ __forceinline__ float rcp_fast(float x) { float y; asm("rcp.approx.ftz.f32 %0, %1;" : "=f"(y) : "f"(x)); return y; }
__device__ __forceinline__ float sigmoidf_(float x) { return rcp_fast(1.f + ex2(-1.4426950408889634f * x)); }
__device__ __forceinline__ void top2(uint32_t k, uint32_t& k1, uint32_t& k2) {
    k1 = __reduce_max_sync(0xffffffffu, k);
    k2 = __reduce_max_sync(0xffffffffu, k == k1 ? 0 : k);
}

__device__ __forceinline__ void mod_fma(float (&a)[8], const uint4 w, float sc) {
    a[0] += sc * bf_lo(w.x); a[1] += sc * bf_hi(w.x); a[2] += sc * bf_lo(w.y); a[3] += sc * bf_hi(w.y);
    a[4] += sc * bf_lo(w.z); a[5] += sc * bf_hi(w.z); a[6] += sc * bf_lo(w.w); a[7] += sc * bf_hi(w.w);
}
__device__ __forceinline__ float mod_reduce(float (&a)[8], int lane) {
#pragma unroll
    for (int h = 4; h > 0; h >>= 1) {
        const bool up = lane & (8 / h);
#pragma unroll
        for (int i = 0; i < h; i++)
            a[i] = (up ? a[i + h] : a[i]) + __shfl_xor_sync(0xffffffffu, up ? a[i] : a[i + h], 8 / h);
    }
    return a[0] + __shfl_xor_sync(0xffffffffu, a[0], 16);
}

__device__ __forceinline__ float ln_stats(float sum, float sq, uint32_t& mean2) {
    const float mean = sum * (1.f / D_);
    const float var = fmaxf(fmaf(-mean, mean, sq * (1.f / D_)), 0.f);
    float sd;
    asm("sqrt.approx.ftz.f32 %0, %1;" : "=f"(sd) : "f"(rbf(rbf(var) + 1e-5f)));
    mean2 = pack_bf16(mean, mean);
    return rcp_fast(rbf(sd));
}
__device__ __forceinline__ uint32_t ln_pair(uint32_t x, uint32_t mean2, float rsd) {
    const uint32_t d = bsub2(x, mean2);
    return pack_bf16(bf_lo(d) * rsd, bf_hi(d) * rsd);
}
__device__ __forceinline__ void rows_load(uint32_t (&x)[20], uint32_t xs, int cw) {
#pragma unroll
    for (int ch = 0; ch < 5; ch++) {
        const uint4 v = ldsm4(ch < 4 ? xs + ch * 256 : xs + 1024 - cw * 16);
        x[4 * ch] = v.x; x[4 * ch + 1] = v.y; x[4 * ch + 2] = v.z; x[4 * ch + 3] = v.w;
    }
}
__device__ __forceinline__ void stats_add(float (&st)[12], uint32_t a, uint32_t b, uint32_t w) {
    mma1688(st, a, b, w);
    mma1688(st + 4, a, b, a);
    mma1688(st + 8, a, b, b);
}
__device__ __forceinline__ float rows_stats(const float (&st)[12], float4* rec, int cw, int lane, uint32_t& mean2, float& dot) {
    const int g8 = lane >> 2;
    if ((g8 >> 1) == (lane & 3)) {
        rec[cw * 16 + g8] = make_float4(st[0], (g8 & 1) ? st[5] : st[4], st[1], 0.f);
        rec[cw * 16 + 8 + g8] = make_float4(st[2], (g8 & 1) ? st[11] : st[10], st[3], 0.f);
    }
    bar_sync(3, 256);
    const float4* r = rec + (lane >> 4) * 64 + (lane & 15);
    const float4 s0 = r[0], s1 = r[16], s2 = r[32], s3 = r[48];
    const float sum = (s0.x + s1.x) + (s2.x + s3.x), sq = (s0.y + s1.y) + (s2.y + s3.y);
    dot = (s0.z + s1.z) + (s2.z + s3.z);
    dot += __shfl_xor_sync(0xffffffffu, dot, 16);
    return ln_stats(sum + __shfl_xor_sync(0xffffffffu, sum, 16), sq + __shfl_xor_sync(0xffffffffu, sq, 16), mean2);
}
template <class F>
__device__ __forceinline__ void rows_normalise(uint32_t* y, const uint32_t* x, uint32_t mean2, float rsd, int lane, F loads) {
    const int g8 = lane >> 2;
    const uint32_t ma2 = __shfl_sync(0xffffffffu, mean2, g8), mb2 = __shfl_sync(0xffffffffu, mean2, g8 + 8);
    const float ra = __shfl_sync(0xffffffffu, rsd, g8), rb = __shfl_sync(0xffffffffu, rsd, g8 + 8);
    loads();
#pragma unroll
    for (int k = 0; k < 9; k++) { y[2 * k] = ln_pair(x[2 * k], ma2, ra); y[2 * k + 1] = ln_pair(x[2 * k + 1], mb2, rb); }
}

__device__ __forceinline__ uint4 h_frag(const uint4* hf, int ks, int lane) {
    if (ks < 32) return ld_relaxed2(hf + ks * 32);
    const uint2* p = reinterpret_cast<const uint2*>(padd(hf, 256 - lane * 8) + ks * 32 - 16);
    const uint2 a = ld_relaxed64(p), b = ld_relaxed64(p + 32);
    return make_uint4(a.x, a.y, b.x, b.y);
}

__device__ __noinline__ void attn_fallback(uint32_t bad, uint32_t tag, const Scratch* gs, uint8_t* frag, uint8_t* keep, const bf16* wq, const bf16* kc, const bf16* vc) {
  const int lane = threadIdx.x & 31, g8 = lane >> 2, qd = lane & 3;
  const int role = cluster_role(), j = role & 7, qb = (role >> 3) * 2 + (blockIdx.x & 1);
  const uint4* hf = g_h + (size_t)(qb * 8 + (threadIdx.x >> 5) - 4) * (36 * 32) + lane;
#pragma unroll 1
  for (int t = 0; t < 4; t++) {
    if (!((bad >> t) & 1)) continue;
    const bf16 *wqp = wq + (4 * j + t) * DH, *kp = kc + (size_t)(2 * j + (t >> 1)) * S_ * DH, *vp = vc + (size_t)(2 * j + (t >> 1)) * S_ * DH;
    uint32_t q[32];
    float o[64];
#pragma unroll
    for (int i = 0; i < 64; i++) o[i] = 0.f;
#pragma unroll 1
    for (int ks = 0; ks < 36; ks++) {
        const uint4 a = h_frag(hf, ks, lane);
        const unsigned short* wr = reinterpret_cast<const unsigned short*>(wqp + (size_t)(ks * 16 + 2 * qd) * QD + g8);
#pragma unroll
        for (int dt = 0; dt < 16; dt++) {
            const uint32_t b0 = __ldg(wr + dt * 8) | ((uint32_t)__ldg(wr + dt * 8 + QD) << 16);
            const uint32_t b1 = __ldg(wr + dt * 8 + 8 * QD) | ((uint32_t)__ldg(wr + dt * 8 + 9 * QD) << 16);
            mma16816(o + 4 * dt, a.x, a.y, a.z, a.w, b0, b1);
        }
    }
#pragma unroll
    for (int i = 0; i < 32; i++) q[i] = pack_bf16(o[2 * i], o[2 * i + 1]);
#pragma unroll
    for (int i = 0; i < 64; i++) o[i] = 0.f;
    float m0 = -INFINITY, m1 = -INFINITY, l0 = 0.f, l1 = 0.f;
#pragma unroll 1
    for (int key = 0; key < S_; key += 16) {
        float sc[8];
#pragma unroll
        for (int i = 0; i < 8; i++) sc[i] = 0.f;
#pragma unroll
        for (int nt = 0; nt < 2; nt++) {
            const uint32_t* kr = reinterpret_cast<const uint32_t*>(kp + (size_t)(key + nt * 8 + g8) * DH) + qd;
#pragma unroll
            for (int ks = 0; ks < 8; ks++)
                mma16816(sc + 4 * nt, q[4 * ks], q[4 * ks + 1], q[4 * ks + 2], q[4 * ks + 3], __ldg(kr + ks * 8), __ldg(kr + ks * 8 + 4));
        }
        const float n0 = quad_max(fmaxf(fmaxf(m0, fmaxf(sc[0], sc[1])), fmaxf(sc[4], sc[5])));
        const float n1 = quad_max(fmaxf(fmaxf(m1, fmaxf(sc[2], sc[3])), fmaxf(sc[6], sc[7])));
        const float f0 = ex2((m0 - n0) * CS), f1 = ex2((m1 - n1) * CS);
        m0 = n0; m1 = n1;
#pragma unroll
        for (int i = 0; i < 8; i++) sc[i] = ex2((sc[i] - ((i & 2) ? n1 : n0)) * CS);
        l0 = l0 * f0 + (sc[0] + sc[1]) + (sc[4] + sc[5]);
        l1 = l1 * f1 + (sc[2] + sc[3]) + (sc[6] + sc[7]);
        const uint32_t e0 = pack_bf16(sc[0], sc[1]), e1 = pack_bf16(sc[2], sc[3]), e2 = pack_bf16(sc[4], sc[5]), e3 = pack_bf16(sc[6], sc[7]);
        const unsigned short* vr = reinterpret_cast<const unsigned short*>(vp + (size_t)(key + 2 * qd) * DH + g8);
#pragma unroll
        for (int dt = 0; dt < 16; dt++) {
            o[4 * dt] *= f0; o[4 * dt + 1] *= f0; o[4 * dt + 2] *= f1; o[4 * dt + 3] *= f1;
            const uint32_t b0 = __ldg(vr + dt * 8) | ((uint32_t)__ldg(vr + dt * 8 + DH) << 16);
            const uint32_t b1 = __ldg(vr + dt * 8 + 8 * DH) | ((uint32_t)__ldg(vr + dt * 8 + 9 * DH) << 16);
            mma16816(o + 4 * dt, e0, e1, e2, e3, b0, b1);
        }
    }
    const float i0 = 1.f / quad_sum(l0), i1 = 1.f / quad_sum(l1);
#pragma unroll
    for (int i = 0; i < 16; i++) {
        q[2 * i] = pack_bf16(o[4 * i] * i0, o[4 * i + 1] * i0);
        q[2 * i + 1] = pack_bf16(o[4 * i + 2] * i1, o[4 * i + 3] * i1);
    }
    frag_store(t < 3 ? frag + t * 4096 : keep, q);
  }
}

__device__ __forceinline__ void spare_q3(Scratch* gs, uint32_t sb, uint32_t bar_full, uint32_t bar_empty, int lane, int cw) {
    const uint32_t tag = load_tag(gs);
    uint32_t rel_base, e = 3;
    asm("mapa.shared::cluster.u32 %0, %1, %2;" : "=r"(rel_base) : "r"(bar_empty), "r"(lane & 1));
#pragma unroll 1
    for (int qb = blockIdx.x - NCTA; qb < 16; qb += 4) {
        uint32_t h[144];
        float o[64];
        flag_wait(&g_flag_h[(qb * 8 + cw) * 32], tag);
        const uint4* hf = g_h + (size_t)(qb * 8 + cw) * (36 * 32) + lane;
#pragma unroll
        for (int ks = 0; ks < 36; ks++) {
            const uint4 v = h_frag(hf, ks, lane);
            h[4 * ks] = v.x; h[4 * ks + 1] = v.y; h[4 * ks + 2] = v.z; h[4 * ks + 3] = v.w;
        }
#pragma unroll
        for (int i = 0; i < 64; i++) o[i] = 0.f;
#pragma unroll 1
        for (int v = 0; v < 4; v++) {
            fence_regs(o);
#pragma unroll
            for (int t = 0; t < 5; t++) {
                mbar_wait(bar_full + 8 * (e & 3), (e >> 2) & 1);
                uint64_t dv = mkdesc(sb + (e & 3) * SLOT, UNIT, 1024);
                WG_FENCE();
#pragma unroll
                for (int ks = 0; ks < (t < 4 ? 8 : 4); ks++)
                    mma_rs128<1>(o, h[32 * t + 4 * ks], h[32 * t + 4 * ks + 1], h[32 * t + 4 * ks + 2], h[32 * t + 4 * ks + 3], dv, ks | t);
                WG_COMMIT();
                if (t > 0) { WG_WAIT(1); if (lane < 2) mbar_arrive_cluster(rel_base + 8 * ((e - 1) & 3)); }
                e++;
            }
            WG_WAIT(0);
            fence_regs(o);
            if (lane < 2) mbar_arrive_cluster(rel_base + 8 * ((e - 1) & 3));
            uint4* dst = &g_q3[((qb * 8 + 2 * v) * 8 + cw) * 128 + lane];
#pragma unroll
            for (int i = 0; i < 8; i++)
                __stcg(dst + (i >> 2) * 1024 + (i & 3) * 32, make_uint4(pack_bf16(o[8 * i], o[8 * i + 1]), pack_bf16(o[8 * i + 2], o[8 * i + 3]),
                                                                        pack_bf16(o[8 * i + 4], o[8 * i + 5]), pack_bf16(o[8 * i + 6], o[8 * i + 7])));
        }
        bar_sync(3, 256);
        if (cw == 0 && lane == 0) flag_release(&g_flag_q3[qb * 32], tag);
        __syncwarp();
    }
}

template <bool SPARE>
__global__ void __cluster_dims__(2, 1, 1) __launch_bounds__(384, 1)
fused_kernel(const Args args, const __grid_constant__ CUtensorMap tm_wq,
             const __grid_constant__ CUtensorMap tm_k, const __grid_constant__ CUtensorMap tm_v,
             const __grid_constant__ CUtensorMap tm_wo, const __grid_constant__ CUtensorMap tm_p,
             const __grid_constant__ CUtensorMap tm_x, const __grid_constant__ CUtensorMap tm_d,
             const __grid_constant__ CUtensorMap tm_g, const __grid_constant__ CUtensorMap tm_u) {
    extern __shared__ __align__(1024) uint8_t smem_raw[];
    const uint32_t sb = smem_u32(smem_raw);
    Scratch* const gs = args.gs;
    const uint32_t bar_full = sb + SM_BAR;
    const uint32_t bar_g = bar_full + 8 * 4;
    const uint32_t bar_mod = bar_g + 8;
    const uint32_t bar_go = bar_mod + 8;
    const uint32_t bar_x = bar_go + 40;
    const uint32_t bar_empty = bar_x + 8;
    const uint32_t bar_pub = bar_empty + 8 * 4;
    const uint32_t bar_qfree = bar_pub + 32;
    const uint32_t bar_out = bar_qfree + 24;
    const uint32_t bar_q3 = bar_out + 8;
    const uint32_t bar_pre = bar_q3 + 16;
    const uint32_t bar_w0 = bar_q3 + 8;
    constexpr int E0 = SPARE ? 2 : 0;

    const int c = blockIdx.x & 1;
#define ROLES() const int role = cluster_role(), j = role & 7, qb = (role >> 3) * 2 + c, rg = qb * 8 + j
    const int warp = __shfl_sync(0xffffffffu, threadIdx.x >> 5, 0);

    if (SPARE && blockIdx.x >= NCTA && warp >= 4) {
        asm volatile("barrier.cluster.arrive.relaxed.aligned;" ::: "memory");
        asm volatile("setmaxnreg.inc.sync.aligned.u32 240;");
        asm volatile("barrier.cluster.wait.aligned;" ::: "memory");
        spare_q3(gs, sb, bar_full, bar_empty, threadIdx.x & 31, warp - 4);
        asm volatile("barrier.cluster.arrive.relaxed.aligned;\nbarrier.cluster.wait.aligned;" ::: "memory");
    } else if (warp < 4) {
        asm volatile("setmaxnreg.dec.sync.aligned.u32 24;");
        ROLES();
        int lane;
        asm volatile("mov.u32 %0, %%laneid;" : "=r"(lane));
        if (warp == 2 && elect()) {
            if (TMPF) asm volatile("prefetch.tensormap [%0];" ::"l"(&tm_x) : "memory");
#pragma unroll
            for (int i = 0; i < 27; i++) mbar_init(bar_full + 8 * i, i < 12 || i >= 23 ? 1 : i < 16 ? 16 : 8);
#pragma unroll
            for (int i = 0; i <= E0; i++) {
                mbar_arrive(bar_full + 8 * i);
                asm volatile("mbarrier.arrive.shared::cta.b64 _, [%0], 16;" ::"r"(bar_empty + 8 * i) : "memory");
            }
            asm volatile("fence.mbarrier_init.release.cluster;" ::: "memory");
        }
        __syncwarp();
        asm volatile("barrier.cluster.arrive.relaxed.aligned;" ::: "memory");
        if (warp == 2 && !(SPARE && blockIdx.x >= NCTA)) {
            if (XDELAY) __nanosleep(XDELAY);
            if (elect()) {
                mbar_expect_tx(bar_x, 16 * XP);
                tma2d(sb + SM_Q, &tm_x, 0, rg * 16, bar_x);
            }
            __syncwarp();
        }
        asm volatile("barrier.cluster.wait.aligned;" ::: "memory");
        const uint32_t tag = load_tag(gs);
        if (SPARE && blockIdx.x >= NCTA) {
            if (warp == 1) {
#pragma unroll 1
                for (int e = 3; e < 83; e++) {
                    const int v = (e - 3) / 5;
                    mbar_wait_sleep(bar_empty + 8 * (e & 3), ~(e >> 2) & 1);
                    if (elect()) {
                        mbar_expect_tx(bar_full + 8 * (e & 3), SLOT);
                        tma2d_mc(sb + (e & 3) * SLOT + c * UNIT, &tm_wq, (8 * (v & 3) + 4 * c + 3) * DH + 64, (e - 3 - v * 5) * 128,
                                 bar_full + 8 * (e & 3), EVICT_NORMAL);
                    }
                }
            }
            __syncwarp();
            asm volatile("barrier.cluster.arrive.relaxed.aligned;\nbarrier.cluster.wait.aligned;" ::: "memory");
            return;
        }
        if (warp == 3) {
#pragma unroll 1
            for (int e = 4; e < 20; e++) {
                __nanosleep(e == 4 ? PFD0 : PFD1);
                const int hd = (e * 52) >> 8, row = (e - hd * 5) * 128 + qb * 8 + (lane >> 1);
                if (lane < 16 && row < D_)
                    asm volatile("prefetch.global.L2 [%0];" ::"l"(padd(args.wq, (row * QD + (4 * j + ((0x1320 >> (4 * hd)) & 3)) * DH + (lane & 1) * 64) * 2)) : "memory");
            }
            __syncwarp();
            mbar_wait_sleep(bar_go, 0);
#pragma unroll 1
            for (int unit = 72 + blockIdx.x; unit < 216; unit += NCTA) {
                float a[8];
#pragma unroll
                for (int i = 0; i < 8; i++) a[i] = 0.f;
#pragma unroll 1
                for (int k = lane >> 1; k < D_; k += 16) {
                    const float cv = __bfloat162float(*padd(args.cvec, k * 2));
                    mod_fma(a, __ldg(reinterpret_cast<const uint4*>(padd(args.w_mod, (k * (6 * D_) + unit * 16 + (lane & 1) * 8) * 2))), rbf(cv * sigmoidf_(cv)));
                }
                const float v = mod_reduce(a, lane), v1 = __shfl_down_sync(0xffffffffu, v, 8);
                if (lane < 8) *padd(gs->mod2, ((unit - 72) * 8 + (lane & 1) * 4 + (lane & 2) + (lane >> 2)) * 4) = pack_bf16(v, v1);
            }
            __syncwarp();
            if (lane == 0) flag_release(padd(g_flag_mod, blockIdx.x * 4), tag);
#pragma unroll 1
            for (int k = 0; k < 36; k++) {
                __nanosleep(200);
                __stcg(padd(gs->h[0], (~tag & 1) * (NCTA * 36 * 512) + ((rg * 36 + k) * 32 + lane) * 16), make_uint4(0, 0, 0, 0));
            }
            __syncwarp();
            mbar_wait_sleep(bar_qfree + 16, 0);
            __nanosleep(2000);
            {
                uint4 v;
                uint32_t it = 0;
#pragma unroll 1
                do {
                    v = ld_relaxed(reinterpret_cast<const uint4*>(padd(g_flag_mod, lane * 16)));
                } while (((v.x ^ tag) | (v.y ^ tag) | (v.z ^ tag) | (v.w ^ tag)) && ++it < SPIN / 16);
                asm volatile("fence.acquire.gpu;" ::: "memory");
            }
            __syncwarp();
            {
                float w1 = 0.f, w2 = 0.f;
#pragma unroll 1
                for (int k = lane; k < D_ / 2; k += 32) {
                    const uint32_t* mp = padd(gs->mod2, k * 4);
                    const uint32_t sv = __ldcg(mp + D_ / 2), c1 = badd2(__ldcg(mp + D_), 0x3f803f80u);
                    const uint32_t wr = *reinterpret_cast<const uint32_t*>(padd(args.w_r, k * 4)), wp = bmul2(c1, wr);
                    reinterpret_cast<uint2*>(smem_raw + SM_T)[k] = make_uint2(__ldcg(mp), wp);
                    reinterpret_cast<uint2*>(smem_raw + SM_TC)[k] = make_uint2(c1, sv);
                    reinterpret_cast<uint32_t*>(smem_raw + SM_TG)[k] = __ldcg(mp + 3 * D_ / 2);
                    w1 += bf_lo(wp) + bf_hi(wp);
                    w2 += bf_lo(sv) * bf_lo(wr) + bf_hi(sv) * bf_hi(wr);
                }
#pragma unroll 1
                for (int i = 1; i < 32; i <<= 1) { w1 += __shfl_xor_sync(0xffffffffu, w1, i); w2 += __shfl_xor_sync(0xffffffffu, w2, i); }
                *reinterpret_cast<float2*>(smem_raw + SM_TS) = make_float2(w1, w2);
            }
#pragma unroll
            for (int i = 0; i < 4; i++) reinterpret_cast<uint4*>(smem_raw + SM_RED)[lane + 32 * i] = make_uint4(~0u, ~0u, ~0u, ~0u);
            asm volatile("fence.proxy.async.shared::cta;" ::: "memory");
            __syncwarp();
            if (elect()) {
                uint8_t* mb = g_frag + (size_t)rg * 8 * WREG + 3 * 4096;
#pragma unroll 1
                for (int k = 0; k < 8; k++, mb += WREG) {
#pragma unroll
                    for (int i = 0; i < 3; i++)
                        asm volatile("cp.async.bulk.global.shared::cta.bulk_group [%0], [%1], 2048;" ::"l"(mb + i * 2048), "r"(sb + SM_RED) : "memory");
                    __nanosleep(500);
                }
                asm volatile("cp.async.bulk.commit_group;\ncp.async.bulk.wait_group 0;\nfence.proxy.async.global;" ::: "memory");
            }
            __syncwarp();
            if (lane == 0) mbar_arrive(bar_mod);
            __syncwarp();
            mbar_wait_sleep(bar_go + 8, 0);
            if (elect()) asm volatile("prefetch.tensormap [%0];\nprefetch.tensormap [%1];\nprefetch.tensormap [%2];" ::"l"(&tm_x), "l"(&tm_p), "l"(&tm_d) : "memory");
            __syncwarp();
#pragma unroll 1
            for (int i = 1; i < 4; i++) {
                mbar_wait(bar_pub + 8 * i, 0);
                unsigned int* flags = padd(g_flag_part, (qb * 32 + i * 8 - 8) * 4);
                if (elect()) { flag_release(padd(flags, j * 4), tag); DBG_PG(93); }
                __syncwarp();
                const uint32_t slot = i < 3 ? i + 1 : 1;
                flag_wait(padd(flags, (lane & 7) * 4), tag);
                asm volatile("fence.proxy.async.global;" ::: "memory");
                if (lane == 0 && i == 3) DBG_PG(101);
                mbar_wait(bar_go + 8 + 8 * i, 0);
                mbar_wait(bar_empty + 8 * slot, i != 1);
                if (elect()) {
                    mbar_expect_tx(bar_full + 8 * slot, SLOT);
                    tma3d(sb + slot * SLOT, &tm_p, 0, j * 20 + (i - 1) * 4, qb * 8, bar_full + 8 * slot);
                    tma3d(sb + slot * SLOT + UNIT, &tm_p, 0, j * 20 + (i - 1) * 4 + 2, qb * 8, bar_full + 8 * slot);
                }
            }
        } else if (warp == 0) {
#pragma unroll 1
            for (int i = 0; i < 48; i++) {
                if (i == 0 || i == 17 || i == 34) mbar_wait_sleep(bar_qfree + (i >> 4) * 8, 0);
                if (SPARE && i == 17) {
                    flag_wait(&g_flag_q3[qb * 32], tag);
                    if (elect()) {
                        asm volatile("fence.proxy.async.global;" ::: "memory");
                        mbar_expect_tx(bar_q3, UNIT);
#pragma unroll 1
                        for (int k = 0; k < 8; k++) bulk_load(sb + SM_Q + 2 * SLOT + k * 4096 + 2048, &g_q3[(rg * 8 + k) * 128], 2048, bar_q3);
                    }
                }
                __nanosleep(700);
                if (elect()) {
                    asm volatile("mbarrier.expect_tx.shared::cta.b64 [%0], %1;" ::"r"(bar_g), "n"(1920) : "memory");
                    tma2d(sb + SM_Q + i * 1920, i < 24 ? &tm_g : &tm_u, (blockIdx.x * 36) & ~7, (i < 24 ? i : i - 24) * 24, bar_g);
                }
            }
            if (elect()) mbar_arrive(bar_g);
#pragma unroll 1
            for (int i = 0; i < 18; i++) {
                __nanosleep(400);
                if (elect()) l2_prefetch(args.w_down + (size_t)(blockIdx.x * 36 + i * 2) * D_, 4 * D_);
            }
            __syncwarp();
            mbar_wait_sleep(bar_go + 8 * 2, 0);
            uint32_t acc = 0;
#pragma unroll 1
            for (int k = lane; k < 16 * 9; k += 32) acc |= touch(padd(args.x, (rg * 16 * D_ + k * 64) * 2));
            if (acc == 0) reinterpret_cast<volatile uint32_t*>(smem_raw + SM_BAR)[127] = acc;
            __syncwarp();
            mbar_wait_sleep(bar_go + 8 * 4, 0);
            uint4* rp = padd(g_rows, (rg * 2 * RSLOT + lane) * 16);
#pragma unroll
            for (int k = 0; k < 12; k++) rp[k * 32] = make_uint4(~0u, ~0u, ~0u, ~0u);
            if (blockIdx.x < 72) {
                uint4* yp = reinterpret_cast<uint4*>(padd(g_ypart, blockIdx.x * NCTA * 64 + lane * 16));
#pragma unroll
                for (int k = 0; k < 16; k++) yp[k * 32] = make_uint4(~0u, ~0u, ~0u, ~0u);
            }
            asm volatile("fence.acq_rel.gpu;" ::: "memory");
            __syncwarp();
            if (lane == 0) mbar_arrive(bar_pre);
        } else if (warp == 1) {
            __nanosleep(QDELAY);
            uint32_t go = bar_go;
            uint64_t marks = 24 | 151 << 8 | 154 << 16 | 159ull << 24 | 165ull << 32;
#pragma unroll 1
            for (int e = E0; e < 168; e++) {
                const CUtensorMap* tm;
                int c0, c1;
                uint64_t pol = EVICT_FIRST;
                if (e == 158 || e == 163) continue;
                if (e < 21 && e != 19) {
                    const int i = SPARE && e < 12 ? e - 2 : e - (e == 20), hd = (i * 52) >> 8;
                    tm = &tm_wq; c0 = (4 * j + ((0x1320 >> (4 * hd)) & 3)) * DH + c * 64; c1 = (i - hd * 5) * 128 - 64;
                    if (SPARE && e >= 12 && e < 15) { c0 = (4 * j + 3) * DH; c1 = (2 * (e - 12) + c) * 128; }
                } else if (e < 148) {
                    const int i = max(e - 20, 0);
                    const bool isk = i == 0 || ((i & 1) && i < 127);
                    const int n = isk ? (i + 1) >> 1 : (i - 1) >> 1;
                    tm = isk ? &tm_k : &tm_v; c0 = c * 64; c1 = (2 * j + (n >> 5)) * S_ + (n & 15) * 128;
                    if (!(i & 32)) pol = EVICT_NORMAL;
                } else {
                    int i = e - 148 - (e > 158) - (e > 163);
                    tm = &tm_wo; c0 = (i >> 1) * 64; c1 = (4 * j + ((i & 1) ? 1 + c : 3 * c)) * DH;
                }
                const uint32_t fb = e == E0 ? bar_w0 : bar_full + 8 * (e & 3), d = sb + (e == E0 ? 6 : e & 3) * SLOT;
                if (e >= 24 && e < 152) mbar_wait_sleep(bar_empty + 8 * (e & 3), ~(e >> 2) & 1);
                else if (e != E0) mbar_wait(bar_empty + 8 * (e & 3), ~(e >> 2) & 1);
                if (elect()) {
                    mbar_expect_tx(fb, SLOT);
                    tma2d_mc(d + c * UNIT, tm, c0, c1, fb, pol);
                    const int i = e - PF_KV;
                    if (i >= 0 && i < 128 && !(i & 32))
                        l2_prefetch(((i & 1) ? args.vc : args.kc) + (size_t)((2 * j + (i >> 6)) * S_ + (i & 30) * 64) * DH + qb * 1024, 2048);
                    if (e >= PF_WO && e < PF_WO + 18) l2_prefetch(args.wo + (size_t)blockIdx.x * (QD * D_ / NCTA) + (e - PF_WO) * 1024, 2048);
                    if (e == (marks & 255)) mbar_arrive(go);
                }
                if (e == (marks & 255)) { go += 8; marks >>= 8; }
            }
            asm volatile("fence.proxy.async.global;" ::: "memory");
            mbar_wait(bar_empty, 1);
            if (elect()) {
                mbar_expect_tx(bar_full, 16 * XP);
                tma2d(sb, &tm_x, 0, rg * 16, bar_full);
            }
            mbar_wait(bar_empty + 16, 1);
            if (C3D) __nanosleep(C3D);
            if (elect()) {
                mbar_expect_tx(bar_full + 16, SLOT);
                tma3d(sb + 2 * SLOT, &tm_p, 0, j * 20 + 12, qb * 8, bar_full + 16);
                tma3d(sb + 2 * SLOT + UNIT, &tm_p, 0, j * 20 + 14, qb * 8, bar_full + 16);
            }
            mbar_wait(bar_empty + 24, 1);
            if (C4D) __nanosleep(C4D);
            if (elect()) {
                mbar_expect_tx(bar_full + 24, UNIT);
                tma3d(sb + 3 * SLOT, &tm_p, 0, j * 20 + 16, qb * 8, bar_full + 24);
            }
            mbar_wait(bar_empty + 8, 0);
            mbar_wait(bar_empty + 16, 0);
            if (DD) __nanosleep(DD);
            if (elect()) {
#pragma unroll
                for (int i = 1; i < 3; i++) {
                    mbar_expect_tx(bar_full + 8 * i, 18 * XP);
                    tma2d(sb + i * SLOT, &tm_d, 0, blockIdx.x * 36 + (i - 1) * 18, bar_full + 8 * i);
                }
            }
        } else {
            if (elect()) asm volatile("prefetch.tensormap [%0];\nprefetch.tensormap [%1];\nprefetch.tensormap [%2];" ::"l"(&tm_k), "l"(&tm_v), "l"(&tm_wo) : "memory");
            if (SPARE) {
                mbar_wait_sleep(bar_pub, 0);
                if (lane == 0) flag_release(padd(g_flag_h, rg * 128), tag);
                __syncwarp();
            }
            bar_sync(1, 192);
#pragma unroll 1
            for (uint32_t e = 20; e < 148; e++) {
                mbar_wait_sleep(bar_full + 8 * (e & 3), (e >> 2) & 1);
                if (e & 1) bar_sync(1, 192);
                if (!(e & 1) || e == 147) bar_sync(4, 160);
            }
#pragma unroll 1
            for (uint32_t e = 148; e < 168; e++) {
                mbar_wait(bar_full + 8 * (e & 3), (e >> 2) & 1);
                if (e != 158 && e != 163) bar_sync(1, 192);
            }
        }
        __syncwarp();
        mbar_wait_sleep(bar_out, 0);
        if (OUTD) __nanosleep(OUTD);
        if (elect()) {
            asm volatile("fence.proxy.async.shared::cta;" ::: "memory");
            const int2 sel = reinterpret_cast<const int2*>(smem_raw + SM_RED)[8];
#pragma unroll 1
            for (int i = warp; i < 16; i += 4) {
                const int row = rg * 16 + i;
                if (row != sel.x && row != sel.y)
                    asm volatile("cp.async.bulk.global.shared::cta.bulk_group.L2::cache_hint [%0], [%1], %2, %3;"
                                 ::"l"(args.out + (size_t)row * D_), "r"(sb + i * XP), "n"(D_ * 2), "l"(OUTPOL) : "memory");
            }
            asm volatile("cp.async.bulk.commit_group;\ncp.async.bulk.wait_group 0;" ::: "memory");
        }
    } else {
        uint32_t cv[2] = {0, 0}, tag = load_tag(gs) - 1;
        if (blockIdx.x < 72) {
            uint32_t ws;
            int tid;
            asm volatile("mov.u32 %0, smem_raw;\nmov.u32 %1, %%tid.x;" : "=r"(ws), "=r"(tid));
            tid -= 128;
            ws += SM_Q + SLOT + tid * 16;
            const uint32_t* cp = padd(reinterpret_cast<const uint32_t*>(args.cvec), (tid & 0xe0) + (tid & 7) * 4);
            cv[0] = *padd(cp, (tid & 24) * 32);
            if (tid < 128) cv[1] = cp[256];
            const bf16* wrow = args.w_mod + (size_t)(tid >> 1) * (6 * D_) + (tid & 1) * 8 + blockIdx.x * 16;
#pragma unroll
            for (int i = 0; i < 5; i++)
                if (i < 4 || tid < 128)
                    asm volatile("cp.async.cg.shared.global [%0], [%1], 16;" ::"r"(ws + i * 4096), "l"(wrow + (size_t)i * 128 * (6 * D_)) : "memory");
        }
        asm volatile("barrier.cluster.arrive.relaxed.aligned;" ::: "memory");
        asm volatile("setmaxnreg.inc.sync.aligned.u32 240;");
        const int lane = threadIdx.x & 31;
        const int cw = warp - 4;
        const int w = cw >> 2;
        const int tid = threadIdx.x - 128;
        ROLES();
        float* red = reinterpret_cast<float*>(smem_raw + SM_RED);
        DBG_INIT();
        DBG_G(120);
        DBG_T(100);

        {
            if (blockIdx.x < 72) {
                uint32_t sa[10];
#pragma unroll
                for (int i = 0; i < 2; i++) {
                    const float lo = bf_lo(cv[i]), hi = bf_hi(cv[i]);
                    cv[i] = pack_bf16(lo * sigmoidf_(lo), hi * sigmoidf_(hi));
                }
#pragma unroll
                for (int i = 0; i < 10; i++) sa[i] = __shfl_sync(0xffffffffu, cv[i >> 3], (i & 7) * 4 + (lane & 3));
                uint2* mdst = &gs->mod1[(tid >> 3) * D_ + blockIdx.x * 8 + (tid & 7)];
                anchor(bar_full + 504, sa[0] & sa[1] & sa[2] & sa[3] & sa[4] & sa[5] & sa[6] & sa[7] & sa[8] & sa[9] & (uint32_t)(uintptr_t)mdst & (uint32_t)((uintptr_t)mdst >> 32));
                asm volatile("cp.async.wait_all;" ::: "memory");
                __syncwarp();
                const uint32_t ws = sb + SM_Q + SLOT + cw * 512 + (lane & 15) * 32 + (lane & 16);
                float d[16];
#pragma unroll
                for (int i = 0; i < 16; i++) d[i] = 0.f;
#pragma unroll
                for (int i = 0; i < 5; i++) {
                    const uint4 b = ldsm4t(ws + (i < 4 || cw < 4 ? i * 4096 : 0));
                    mma16816(d + 8 * (i & 1), sa[2 * i], sa[2 * i], sa[2 * i + 1], sa[2 * i + 1], b.x, b.y);
                    mma16816(d + 8 * (i & 1) + 4, sa[2 * i], sa[2 * i], sa[2 * i + 1], sa[2 * i + 1], b.z, b.w);
                }
                if (lane < 8) reinterpret_cast<float2*>(red)[lane * 8 + cw] = (lane & 4) ? make_float2(d[4] + d[12], d[5] + d[13]) : make_float2(d[0] + d[8], d[1] + d[9]);
                bar_sync(3, 256);
                if (tid < 8 * MREP) {
                    const float4* r = reinterpret_cast<const float4*>(red) + (tid & 7) * 4;
                    const float4 r0 = r[0], r1 = r[1], r2 = r[2], r3 = r[3];
                    st_relaxed64(mdst, pack_bf16(((r0.x + r0.z) + (r1.x + r1.z)) + ((r2.x + r2.z) + (r3.x + r3.z)),
                                                 ((r0.y + r0.w) + (r1.y + r1.w)) + ((r2.y + r2.w) + (r3.y + r3.w))), tag + 1);
                }
            }
            DBG_G(106);
            asm volatile("barrier.cluster.wait.aligned;" ::: "memory");
            mbar_wait(bar_x, 0);
            asm volatile("add.u32 %0, %0, 1;" : "+r"(tag));
            uint32_t x[20];
            float st[12], st2[12];
            rows_load(x, sb + SM_Q + (lane & 15) * XP + (lane >> 4) * 16 + cw * 32, cw);
#pragma unroll
            for (int i = 0; i < 12; i++) { st[i] = 0.f; st2[i] = 0.f; }
#pragma unroll
            for (int k = 0; k < 9; k++) stats_add((k & 1) ? st2 : st, x[2 * k], x[2 * k + 1], 0x3f803f80u);
#pragma unroll
            for (int i = 0; i < 12; i++) st[i] += st2[i];
            uint32_t mean2;
            float dot;
            const float rsd = rows_stats(st, reinterpret_cast<float4*>(red + 128), cw, lane, mean2, dot);
            const uint4* mp = reinterpret_cast<const uint4*>(gs->mod1 + ((blockIdx.x >> 1) & (MREP - 1)) * D_) + min(tid, D_ / 4 - 1);
            uint4 v0 = make_uint4(0, tag, 0, tag), v1 = v0;
            auto look = [&]() {
                asm volatile("{\n.reg .pred p;\n.reg .b64 a, b, c, d;\nsetp.lt.s32 p, %9, 5;\nmov.b64 a, {%0, %1};\nmov.b64 b, {%2, %3};\n"
                             "mov.b64 c, {%4, %5};\nmov.b64 d, {%6, %7};\n@p ld.relaxed.gpu.global.v2.b64 {a, b}, [%8];\n"
                             "@p ld.relaxed.gpu.global.v2.b64 {c, d}, [%8 + 2304];\n"
                             "mov.b64 {%0, %1}, a;\nmov.b64 {%2, %3}, b;\nmov.b64 {%4, %5}, c;\nmov.b64 {%6, %7}, d;\n}"
                             : "+r"(v0.x), "+r"(v0.y), "+r"(v0.z), "+r"(v0.w), "+r"(v1.x), "+r"(v1.y), "+r"(v1.z), "+r"(v1.w)
                             : "l"(mp), "r"(cw) : "memory");
            };
            rows_normalise(x, x, mean2, rsd, lane, look);
            fence_regs(x);
            uint32_t it = 0;
#pragma unroll 1
            while (((v0.y ^ tag) | (v0.w ^ tag) | (v1.y ^ tag) | (v1.w ^ tag)) && ++it < SPIN / 16) look();
            uint4* smod = reinterpret_cast<uint4*>(smem_raw + SM_Q + M_MOD);
            if (tid < D_ / 4) smod[tid] = make_uint4(badd2(v1.x, 0x3f803f80u), v0.x, badd2(v1.z, 0x3f803f80u), v0.z);
            uint4* hdst = g_h + (size_t)(rg * 36 + cw) * 32 + lane;
            uint2* hdst2 = reinterpret_cast<uint2*>(g_h + (size_t)(rg * 36 + 32) * 32) + tid;
            bar_sync(3, 256);
            DBG_G(107);
#pragma unroll
            for (int k = 0; k < 9; k++) {
                const uint2 cs = lds64(sb + SM_Q + M_MOD + (cw * 8 + (lane & 3) + (k < 8 ? (k >> 1) * 64 + (k & 1) * 4 : 256 - cw * 4)) * 8);
                const uint32_t c1 = cs.x, sa = cs.y;
                x[2 * k] = badd2(bmul2(x[2 * k], c1), sa);
                if (x[2 * k] == 0) x[2 * k] = 0x8000u;
                x[2 * k + 1] = badd2(bmul2(x[2 * k + 1], c1), sa);
            }
#pragma unroll
            for (int ch = 0; ch < 4; ch++) st_relaxed4(hdst + ch * 256, x[4 * ch], x[4 * ch + 1], x[4 * ch + 2], x[4 * ch + 3]);
            st_relaxed64(hdst2, x[16], x[17]);
            __syncwarp();
            if (SPARE && lane == 0) mbar_arrive(bar_pub);
            DBG_G(108);
        }

        uint32_t rel_base;
        asm("mapa.shared::cluster.u32 %0, %1, %2;" : "=r"(rel_base) : "r"(bar_empty), "r"(lane & 1));
        auto release = [&](uint32_t slot) { if (lane < 2) mbar_arrive_cluster(rel_base + 8 * slot); };
        uint32_t q[32], p[32];
        float s[64], o[64];

        uint4* qpark = reinterpret_cast<uint4*>(smem_raw + SM_Q - SLOT) + cw * 256 + lane;
        {
            uint32_t h[144];
            const uint4* hf = g_h + (size_t)(qb * 8 + cw) * (36 * 32) + lane;
            auto load_h = [&](auto lo, auto hi) {
#pragma unroll
                for (int ks = lo.value; ks < hi.value; ks++) {
                    const uint4 v = h_frag(hf, ks, lane);
                    h[4 * ks] = v.x; h[4 * ks + 1] = v.y; h[4 * ks + 2] = v.z; h[4 * ks + 3] = v.w;
                }
            };
            auto check_h = [&](auto lo, auto hi) {
                uint32_t it = 0;
                bool miss;
#pragma unroll 1
                do {
                    uint32_t mn = ~0u;
#pragma unroll
                    for (int ks = lo.value; ks < hi.value; ks++) mn = __vimin3_u32(mn, h[4 * ks], h[4 * ks + 2]);
                    miss = __any_sync(0xffffffffu, mn == 0);
                    if (miss) load_h(lo, hi);
                    asm volatile("add.u32 %0, %0, 1;" : "+r"(it));
                } while (miss && it < SPIN / 16);
            };
            __nanosleep(HDELAY);
            load_h(IC<0>{}, IC<4>{});
            DBG_T(104); DBG_G(109);
#pragma unroll
            for (int i = 0; i < 64; i++) o[i] = 0.f;
            uint32_t e = E0;
#pragma unroll 1
            for (int hd = 1;; hd++) {
                fence_regs(o);
                auto group = [&](auto tc) {
                    constexpr int t = tc.value, k0 = t ? 8 * t - 4 : 0;
                    const bool first = t == 0 && hd == 1;
                    mbar_wait(first ? bar_w0 : bar_full + 8 * (e & 3), (e >> 2) & 1);
                    uint64_t dv = args.d0 + ((t ? 0 : 512) + (first ? 6 : e & 3) * (SLOT / 16));
                    if (hd == 1) check_h(IC<k0>{}, IC<8 * t + 4>{});
                    WG_FENCE();
#pragma unroll
                    for (int ks = k0; ks < 8 * t + 4; ks++)
                        mma_rs128<1>(o, h[4 * ks], h[4 * ks + 1], h[4 * ks + 2], h[4 * ks + 3], dv, ks);
                    WG_COMMIT();
                    if (hd == 1) { if (t == 0) {   } if (t == 1) {   } if (t == 2) {   } if (t == 3) {   } if (t == 4) {   } }
                    if (t < 4 && hd == 1) load_h(IC<8 * t + 4>{}, IC<t < 4 ? 8 * t + 12 : 0>{});
                    if (t > 0) { WG_WAIT(1); if (t > 1 || hd > 1) release((e - 1) & 3); }
                    e++;
                };
                group(IC<0>{}); group(IC<1>{}); group(IC<2>{}); group(IC<3>{});
                if (e == 19) break;
                group(IC<4>{});
                WG_WAIT(0);
                if (hd == 1) {     }
                fence_regs(o);
                release((e - 1) & 3);
#pragma unroll
                for (int i = 0; i < 8; i++)
                    qpark[hd * 2048 + i * 32] = make_uint4(pack_bf16(o[8 * i], o[8 * i + 1]), pack_bf16(o[8 * i + 2], o[8 * i + 3]),
                                                           pack_bf16(o[8 * i + 4], o[8 * i + 5]), pack_bf16(o[8 * i + 6], o[8 * i + 7]));
                if (SPARE && hd == 2) {
                    float (&u)[32] = reinterpret_cast<float (&)[32]>(o);
                    fence_regs(u);
#pragma unroll
                    for (int t = 0; t < 3; t++) {
                        mbar_wait(bar_full + 8 * t, 1);
                        uint64_t dv = args.d0 + t * (SLOT / 16);
                        WG_FENCE();
#pragma unroll
                        for (int ks = 0; ks < (t < 2 ? 16 : 4); ks++)
                            mma_rs64<1>(u, h[64 * t + 4 * ks], h[64 * t + 4 * ks + 1], h[64 * t + 4 * ks + 2], h[64 * t + 4 * ks + 3],
                                        dv, ks | t);
                        WG_COMMIT();
                        if (t > 0) { WG_WAIT(1); release(t - 1); }
                    }
                    WG_WAIT(0);
                    fence_regs(u);
                    release(2);
                    e = 15;
#pragma unroll
                    for (int i = 0; i < 4; i++)
                        qpark[3 * 2048 + i * 32] = make_uint4(pack_bf16(u[8 * i], u[8 * i + 1]), pack_bf16(u[8 * i + 2], u[8 * i + 3]),
                                                              pack_bf16(u[8 * i + 4], u[8 * i + 5]), pack_bf16(u[8 * i + 6], u[8 * i + 7]));
                }
            }
#pragma unroll
            for (int i = 0; i < 8; i++) {
                const uint4 v = qpark[2048 + i * 32];
                q[4 * i] = v.x; q[4 * i + 1] = v.y; q[4 * i + 2] = v.z; q[4 * i + 3] = v.w;
            }
#pragma unroll
            for (int i = 0; i < 32; i++) p[i] = h[112 + i];
            mbar_wait(bar_full + 24, 0);
            WG_WAIT(0);
            fence_regs(o);
            release(2);
        }
        DBG_T(105);
        DBG_G(125);

        uint8_t* frag = reinterpret_cast<uint8_t*>(__shfl_sync(0xffffffffu, reinterpret_cast<unsigned long long>(g_frag + (size_t)(rg * 8 + cw) * WREG + lane * 16), lane));
        const uint4* qnext = reinterpret_cast<const uint4*>(__shfl_sync(0xffffffffu, reinterpret_cast<unsigned long long>(padd(smem_raw, SM_Q + tid * 16 + cw * 3584)), lane));
        uint8_t* odst = reinterpret_cast<uint8_t*>(const_cast<uint4*>(qnext));
        qnext -= 2048;
        float m0, m1, l0 = 0.25f, l1 = 0.25f, t0, t1;
        uint32_t bad = 0;
        const int lw = cw & 3;
        const uint32_t relw = lw == RW && lane < 8, handw = lw == HW || cw == HW2;
        auto release4 = [&](uint32_t off) {
            asm volatile("{\n.reg .pred p;\nsetp.ne.b32 p, %1, 0;\n@p mbarrier.arrive.shared::cluster.b64 _, [%0];\n}" ::"r"(rel_base + off), "r"(relw) : "memory"); };
        auto handoff = [&]() {
            asm volatile("{\n.reg .pred p;\nsetp.ne.b32 p, %1, 0;\n@p bar.arrive %0, 192;\n}" ::"r"(2 - w), "r"(handw) : "memory"); };
        if (cw == 4 + HW) bar_arrive(1, 192);
        auto finish = [&](auto lo, auto hi, uint32_t bit, auto sink) {
#pragma unroll
            for (int i = lo.value; i < hi.value; i++) {
                const uint32_t v0 = pack_bf16(o[8 * i] * t0, o[8 * i + 1] * t0), v1 = pack_bf16(o[8 * i + 2] * t1, o[8 * i + 3] * t1);
                const uint32_t v2 = pack_bf16(o[8 * i + 4] * t0, o[8 * i + 5] * t0), v3 = pack_bf16(o[8 * i + 6] * t1, o[8 * i + 7] * t1);
                if (i == 0 && fabsf(o[0] * t0) >= 0x1p-31f) bad |= bit << 8;
                sink(i, v0, v1, v2, v3);
            }
        };
        float lq[6];
        auto row_parts = [&]() {
#pragma unroll
            for (int i = 0; i < 3; i++) { lq[i] = __shfl_xor_sync(0xffffffffu, l0, i + 1); lq[3 + i] = __shfl_xor_sync(0xffffffffu, l1, i + 1); }
        };
        auto row_sums = [&](uint32_t bit) {
            t0 = (l0 + lq[0]) + (lq[1] + lq[2]); t1 = (l1 + lq[3]) + (lq[4] + lq[5]);
            if (!(t0 >= LMIN && t0 < LMAX && t1 >= LMIN && t1 < LMAX)) bad |= bit;
        };
        auto issue_pv = [&](uint64_t dv, int acc, auto lo, auto hi) {
            if (lo.value == 0) asm volatile("{\n.reg .pred p;\nsetp.eq.b32 p, %0, 0;\n@p bar.sync 4, 160;\n}" ::"r"(w) : "memory");
#pragma unroll
            for (int ks = lo.value; ks < hi.value; ks++)
                mma_rs128<1>(o, p[4 * ks], p[4 * ks + 1], p[4 * ks + 2], p[4 * ks + 3], dv, ks ? 1 : acc);
            WG_COMMIT();
        };
#pragma unroll
        for (int i = 0; i < 64; i++) s[i] = 0.f;
        uint64_t dv_lo = args.d0;
        uint32_t voff = 0;
        auto issue_qk = [&]() {
            uint64_t dk = dv_lo ^ (desc_lo(0, UNIT) ^ desc_lo(3 * SLOT, 16));
            bar_sync(1 + w, 192);
            fence_regs(s); fence_regs(q); fence_regs(o); fence_regs(p);
            WG_FENCE();
#pragma unroll
            for (int ks = 0; ks < 8; ks++)
                if (ks == 3) mma_rs128<0, 1018>(s, q[4 * ks], q[4 * ks + 1], q[4 * ks + 2], q[4 * ks + 3], dk, 1);
                else mma_rs128<0, 2>(s, q[4 * ks], q[4 * ks + 1], q[4 * ks + 2], q[4 * ks + 3], dk, ks != 0);
            WG_COMMIT();
        };
        auto to_frag = [&](int i, uint32_t v0, uint32_t v1, uint32_t v2, uint32_t v3) {
            *reinterpret_cast<uint4*>(odst + i * 512) = make_uint4(v0, v1, v2, v3); };
        int n = 0;
        auto scores_ready = [&]() {
            WG_WAIT(1);
            fence_regs(s); fence_regs(q);
        };
        auto pass_on = [&]() {
            release4(voff ^ 24);
            handoff();
        };
#pragma unroll 1
        for (;;) {
            {
                if (RPE) {
                    asm volatile("st.shared.v2.f32 [%0], {%1, %2};" ::"r"(sb + SM_RED + tid * 8), "f"(l0), "f"(l1) : "memory");
                    __syncwarp();
                    const uint4 a = lds128(sb + SM_RED + (tid & ~3) * 8), b = lds128(sb + SM_RED + (tid & ~3) * 8 + 16);
                    l0 = __uint_as_float(a.x); lq[0] = __uint_as_float(a.z); lq[1] = __uint_as_float(b.x); lq[2] = __uint_as_float(b.z);
                    l1 = __uint_as_float(a.y); lq[3] = __uint_as_float(a.w); lq[4] = __uint_as_float(b.y); lq[5] = __uint_as_float(b.w);
                } else {
                    row_parts();
                }
                issue_qk();
                if (RPE == 2) hold(l0, l1);
                row_sums(1u << (n >> 4));
                t0 = rcp_fast(t0); t1 = rcp_fast(t1);
                l0 = 0.f; l1 = 0.f;
                odst = n ? frag + ((n >> 4) - 1) * 4096 : odst;
                if (RPE) anchor(bar_full + 504, (t0 + t1) * __uint_as_float((bad ^ (uint32_t)(uintptr_t)odst) & 0x3fffffff));
                asm volatile("{\n.reg .pred p;\nsetp.ne.b32 p, %1, 0;\n@p mbarrier.arrive.shared::cta.b64 _, [%0];\n}"
                             ::"r"(bar_qfree + (n >> 1) - 8), "r"(lane ? 0 : n) : "memory");
                issue_pv(dv_lo, 1, IC<0>{}, IC<8>{});
                scores_ready();
                float a0 = fmaxf(s[0], s[1]), a1 = fmaxf(s[2], s[3]), a2 = fmaxf(s[4], s[5]), a3 = fmaxf(s[6], s[7]);
#pragma unroll
                for (int i = 1; i < MAXG; i++) {
                    a0 = fmaxf(a0, fmaxf(s[8 * i], s[8 * i + 1])); a1 = fmaxf(a1, fmaxf(s[8 * i + 2], s[8 * i + 3]));
                    a2 = fmaxf(a2, fmaxf(s[8 * i + 4], s[8 * i + 5])); a3 = fmaxf(a3, fmaxf(s[8 * i + 6], s[8 * i + 7]));
                }
                const uint32_t a = pack_bf16(fmaxf(a0, a2), fmaxf(a1, a3));
                const uint32_t b = bmax2(bmax2(a, __shfl_xor_sync(0xffffffffu, a, 1)), bmax2(__shfl_xor_sync(0xffffffffu, a, 2), __shfl_xor_sync(0xffffffffu, a, 3)));
                pass_on();
                m0 = fmaf(-CS, bf_lo(b), -POFF); m1 = fmaf(-CS, bf_hi(b), -POFF);
            }
#pragma unroll 1
            for (;;) {
                DBG_T(n);
#pragma unroll
                for (int i = 0; i < 4 * STAGE; i++) s[i] = fmaf(s[i], CS, (i & 2) ? m1 : m0);
#pragma unroll
                for (int i = 0; i < 4 * SPLIT; i++) s[i] = ex2(s[i]);
#pragma unroll
                for (int i = 0; i < SPLIT; i++) { l0 += s[4 * i] + s[4 * i + 1]; l1 += s[4 * i + 2] + s[4 * i + 3]; }
                if (STAGE < 16) {
                    m0 = fmaf(l0, 0.f, m0); m1 = fmaf(l1, 0.f, m1);
                }
                anchor(bar_full + 504, l0 + l1);
                WG_WAIT(0);
                fence_regs(o); fence_regs(p);
                release4(voff);
                dv_lo ^= 2 * SLOT / 16;
                voff ^= 16;
                n++;
#pragma unroll
                for (int i = 4 * STAGE; i < 64; i++) s[i] = fmaf(s[i], CS, (i & 2) ? m1 : m0);
#pragma unroll
                for (int i = 4 * SPLIT; i < 64; i++) s[i] = ex2(s[i]);
#pragma unroll
                for (int i = SPLIT; i < 16; i++) { l0 += s[4 * i] + s[4 * i + 1]; l1 += s[4 * i + 2] + s[4 * i + 3]; }
#pragma unroll
                for (int i = 0; i < 32; i++) p[i] = pack_bf16(s[2 * i], s[2 * i + 1]);
                const int jn = n & 15;
                if (!(((0x8003 | RCM | RCM << 1) >> jn) & 1)) {
                    issue_qk();
                    issue_pv(dv_lo, 1, IC<0>{}, IC<8>{});
                    scores_ready();
                    pass_on();
                    continue;
                }
                if (jn == 1) {
                    finish(IC<0>{}, IC<ESPLIT>{}, 1u << (n >> 4), to_frag);
                    issue_qk();
                    if (HOLD) hold(t0, t1);
                    finish(IC<ESPLIT>{}, IC<8>{}, 1u << (n >> 4), to_frag);
                    WG_FENCE();
                    issue_pv(dv_lo, 0, IC<0>{}, IC<8>{});
                    scores_ready();
                    pass_on();
                    continue;
                }
                if (jn == 0) break;
                if (RCM && jn != 15) {
                    if ((RCM >> jn) & 1) {
                        row_parts();
                        row_sums(2u << (n >> 4));
                        const uint32_t e0 = __float_as_uint(t0) >> 23, e1 = __float_as_uint(t1) >> 23;
                        m0 -= __uint_as_float(0x4b000000u | e0) - (8388608.f + 127.f - POFF);
                        m1 -= __uint_as_float(0x4b000000u | e1) - (8388608.f + 127.f - POFF);
                        t0 = __uint_as_float((254 - (int)POFF - e0) << 23); t1 = __uint_as_float((254 - (int)POFF - e1) << 23);
                        l0 *= t0; l1 *= t1;
                    } else {
#pragma unroll
                        for (int i = 0; i < 64; i++) o[i] *= (i & 2) ? t1 : t0;
                    }
                    issue_qk();
                    issue_pv(dv_lo, 1, IC<0>{}, IC<8>{});
                    scores_ready();
                    pass_on();
                    continue;
                }
                if (SPARE && n == 47) mbar_wait(bar_q3, 0);
                qnext = n == 63 ? reinterpret_cast<const uint4*>(frag) : qnext + 2048;
                issue_qk();
                issue_pv(dv_lo, 1, IC<0>{}, IC<8>{});
                scores_ready();
                pass_on();
#pragma unroll
                for (int i = 0; i < 8; i++) {
                    const uint4 v = qnext[i * 32];
                    q[4 * i] = v.x; q[4 * i + 1] = v.y; q[4 * i + 2] = v.z; q[4 * i + 3] = v.w;
                }
            }
            if (n == 64) break;
        }
        DBG_T(64);
        uint32_t a1[32], a2[32];
        row_parts();
        frag_load(a1, frag + 4096);
        frag_load(a2, frag + 8192);
        bar_sync(1 + w, 192);
        fence_regs(o); fence_regs(p);
        WG_FENCE();
        issue_pv(args.d0 + 3 * SLOT / 16, 1, IC<0>{}, IC<8>{});
        handoff();
        row_sums(16);
        t0 = rcp_fast(t0); t1 = rcp_fast(t1);
        mbar_wait(bar_mod, 0);
        WG_WAIT(0);
        fence_regs(o); fence_regs(p);
        release4(24);
        finish(IC<0>{}, IC<8>{}, 16, [&](int i, uint32_t v0, uint32_t v1, uint32_t v2, uint32_t v3) {
            p[4 * i] = v0; p[4 * i + 1] = v1; p[4 * i + 2] = v2; p[4 * i + 3] = v3; });
        bad = __reduce_or_sync(0xffffffffu, bad);
        bad = ((bad | ~(bad >> 8)) >> 1) & 15;
        if (__builtin_expect(bad != 0, 0)) {
            uint8_t* keep = g_keep + (size_t)(rg * 8 + cw) * 4096 + lane * 16;
            frag_store(keep, p);
            attn_fallback(bad, tag, gs, frag, keep, args.wq, args.kc, args.vc);
            frag_load(q, frag); frag_load(a1, frag + 4096); frag_load(a2, frag + 8192); frag_load(p, keep);
        }
        DBG_T(80);
        DBG_G(124);

        const uint32_t eye = (lane >> 3) == (lane & 3) ? 0x3f80u << ((lane & 4) * 4) : 0;
        auto sum8 = [&](uint32_t* r, const uint4 (&v)[8]) {
            float d[16];
#pragma unroll
            for (int i = 0; i < 16; i++) d[i] = 0.f;
#pragma unroll
            for (int src = 0; src < 8; src++) {
                mma1688(d + 8 * (src & 1), v[src].x, v[src].y, eye);
                mma1688(d + 8 * (src & 1) + 4, v[src].z, v[src].w, eye);
            }
#pragma unroll
            for (int i = 0; i < 4; i++) r[i] = pack_bf16(d[2 * i] + d[8 + 2 * i], d[2 * i + 1] + d[9 + 2 * i]);
        };
        uint4 v2[8], v3[8], wf[23];
        uint2 u4[8], gw[9];
        uint32_t x1[20], xs, pa, ta;
        const uint8_t *mb, *mb4;
        int tid_;
        auto load_wf = [&](auto lo, auto hi) {
            const uint32_t wa = sb + SM_Q + ((tid_ & 8) * (D_ / 8) + cw * 16 + (tid_ & 7) + (tid_ & 16) / 2) * 80;
            const uint32_t wb = wa + (512 - cw * 8) * 80 - (tid_ & 16) * 39;
#pragma unroll
            for (int i = lo.value; i < hi.value; i++) wf[i] = ldsm4t(i < 20 ? wa + (i / 5) * 10240 + (i % 5) * 16 : wb + (i - 20) * 32);
        };
        uint32_t at[18];
        {
            float (&u)[32] = reinterpret_cast<float (&)[32]>(o);
            uint32_t off = 0;
            auto turn = [&](const uint32_t (&a)[32], const uint32_t (&b)[32], int acc) {
                uint64_t dv = args.d0 + off * (SLOT / 128);
                bar_sync(1 + w, 192);
                fence_regs(u);
                WG_FENCE();
#pragma unroll
                for (int ks = 0; ks < 16; ks++) {
                    const uint32_t* f = ks < 8 ? &a[4 * ks] : &b[4 * ks - 32];
                    mma_rs64<1>(u, f[0], f[1], f[2], f[3], dv, ks | acc);
                    if (ks == OSPLIT - 1) WG_COMMIT();
                }
                WG_COMMIT();
                WG_WAIT(1);
            };
            auto done = [&]() {
                WG_WAIT(0);
                fence_regs(u);
                release4(off);
                off = (off + 8) & 24;
            };
            auto store = [&](uint8_t* dst) {
#pragma unroll
                for (int i = 0; i < 4; i++)
                    st_relaxed4(dst + i * 512, pack_bf16(u[8 * i], u[8 * i + 1]), pack_bf16(u[8 * i + 2], u[8 * i + 3]),
                                pack_bf16(u[8 * i + 4], u[8 * i + 5]), pack_bf16(u[8 * i + 6], u[8 * i + 7]));
            };
            tid_ = __shfl_sync(0xffffffffu, tid, lane);
            pa = sb + w * (UNIT - 2048) + tid_ * 16;
#pragma unroll
            for (int i = 0; i < 8; i++) at[i] = 0;
            fence_regs(q); fence_regs(p);
            uint8_t* dst = frag;
#pragma unroll 1
            for (int k = 0; k < 8; k++, dst += 2048) {
                const uint32_t poff = off;
                const bool sum = (0xa0 >> k) & 1;
                if (sum) off = (off + 8) & 24;
                turn(q, p, 0);
                handoff();
                if (sum) {
                    uint4 v[8];
#pragma unroll
                    for (int src = 0; src < 8; src++) v[src] = lds128(pa + poff * (SLOT / 8) + src * 2048);
                    __syncwarp();
                    release(poff >> 3);
                    done();
                    float d[8];
#pragma unroll
                    for (int i = 0; i < 8; i++) {
                        float t[8];
#pragma unroll
                        for (int src = 0; src < 8; src++) {
                            const uint32_t x = i < 2 ? v[src].x : i < 4 ? v[src].y : i < 6 ? v[src].z : v[src].w;
                            t[src] = (i & 1) ? bf_hi(x) : bf_lo(x);
                        }
                        d[i] = ((t[0] + t[2]) + (t[4] + t[6])) + ((t[1] + t[3]) + (t[5] + t[7]));
                    }
#pragma unroll
                    for (int i = 0; i < 4; i++) { at[i] = at[4 + i]; at[4 + i] = pack_bf16(d[2 * i], d[2 * i + 1]); }
                } else {
                    done();
                }
                turn(a1, a2, 1);
                handoff();
                done();
                store(dst);
                __syncwarp();
                asm volatile("{\n.reg .pred p;\nsetp.ne.b32 p, %1, 0;\n@p mbarrier.arrive.shared::cta.b64 _, [%0];\n}"
                             ::"r"(bar_pub + 4 + 4 * k), "r"(lane ? 0 : (0x2a >> k) & 1) : "memory");
            }
            turn(q, p, 0);
            handoff();
            mb = padd(g_frag, (qb * 64 + j) * WREG + 3 * 4096 + tid_ * 16);
            mb4 = padd(mb, 4096 + ((cw >> 1) - cw) * 512 + (cw & 1) * 8);
            xs = sb + (tid_ & 15) * XP + (tid_ & 16) + cw * 32;
            ta = sb + (cw * 8 + (tid_ & 3)) * 8;
#pragma unroll
            for (int k = 0; k < 9; k++) {
                gw[k] = lds64(ta + SM_T + (k < 8 ? (k >> 1) * 64 + (k & 1) * 4 : 256 - cw * 4) * 8);
                if (!(tid_ & 4)) gw[k].y = 0x3f803f80u;
            }
            mbar_wait(bar_g, 0);
            done();
            load_wf(IC<0>{}, IC<WF0>{});
            turn(a1, a2, 1);
            if (w == 0) handoff();
            if (P2E) {
                mbar_wait(bar_full + 8, 0);
#pragma unroll
                for (int src = 0; src < 8; src++) v2[src] = lds128(pa + SLOT + src * 2048);
            }
            done();
            store(dst);
            mbar_wait(bar_full, 0);
            rows_load(x1, xs, cw);
            if (w == 0) bar_sync(5, 256); else bar_arrive(5, 256);
        }
        DBG_T(81);
        DBG_G(122);

        {
        const int tid = tid_, lane = tid & 31;
        const int g8 = lane >> 2, qd = lane & 3, l16 = lane & 15;
        uint32_t h2[18], gb[9], k1, k2;
        float4* rec = reinterpret_cast<float4*>(red + 128);
        const uint2* candp = reinterpret_cast<const uint2*>(padd(g_cand, ((blockIdx.x & (CREP - 1)) * NCTA + (tid >> 1)) * 32 + (tid & 1) * 8));
        uint2 cd;
        auto stage_out = [&]() {
#pragma unroll
            for (int k = 0; k < 9; k++) {
                x1[2 * k] = badd2(x1[2 * k], bmul2(gb[k], h2[2 * k]));
                x1[2 * k + 1] = badd2(x1[2 * k + 1], bmul2(gb[k], h2[2 * k + 1]));
            }
#pragma unroll
            for (int ch = 0; ch < 4; ch++) stsm_x4(xs + ch * 256, x1[4 * ch], x1[4 * ch + 1], x1[4 * ch + 2], x1[4 * ch + 3]);
            asm volatile("stmatrix.sync.aligned.m8n8.x2.shared.b16 [%0], {%1, %2};" ::"r"(xs + 1024 - cw * 16), "r"(x1[16]), "r"(x1[17]) : "memory");
        };
        {
            uint32_t it = 0, miss;
            if (!P2E) {
                mbar_wait(bar_full + 8, 0);
#pragma unroll
                for (int src = 0; src < 8; src++) v2[src] = lds128(pa + SLOT + src * 2048);
            }
            sum8(at + 8, v2);
            float st[12];
#pragma unroll
            for (int i = 0; i < 12; i++) st[i] = 0.f;
            auto add_pair = [&](int k) {
                x1[2 * k] = badd2(x1[2 * k], bmul2(gw[k].x, at[2 * k]));
                x1[2 * k + 1] = badd2(x1[2 * k + 1], bmul2(gw[k].x, at[2 * k + 1]));
                stats_add(st, x1[2 * k], x1[2 * k + 1], gw[k].y);
            };
#pragma unroll
            for (int k = 0; k < 6; k++) add_pair(k);
            mbar_wait(bar_full + 16, 0);
#pragma unroll
            for (int src = 0; src < 8; src++) v3[src] = lds128(pa + 2 * SLOT + src * 2048);
#pragma unroll 1
            do {
                if (BO && it) __nanosleep(BO);
                miss = 0;
#pragma unroll
                for (int src = 0; src < 8; src++) reload16(v3[src], mb + (size_t)src * 8 * WREG, miss);
            } while (__any_sync(0xffffffffu, miss) && ++it < SPIN / 16);
            if (lane < 4) mbar_arrive_cluster(rel_base + 8 * (1 + (lane >> 1)));
            sum8(at + 12, v3);
            add_pair(6); add_pair(7);
            load_wf(IC<WF0>{}, IC<WF1>{});
            uint2 cs[9];
#pragma unroll
            for (int k = 0; k < 9; k++) cs[k] = lds64(ta + SM_TC + (k < 8 ? (k >> 1) * 64 + (k & 1) * 4 : 256 - cw * 4) * 8);
            mbar_wait(bar_pre, 0);
            mbar_wait(bar_full + 24, 0);
#pragma unroll
            for (int src = 0; src < 8; src++) u4[src] = lds64(sb + 3 * SLOT + src * 2048 + (cw >> 1) * 512 + lane * 16 + (cw & 1) * 8);
#pragma unroll 1
            do {
                if (BO && miss) __nanosleep(BO);
                miss = 0;
#pragma unroll
                for (int src = 0; src < 8; src++) reload8(u4[src], mb4 + (size_t)src * 8 * WREG, miss);
            } while (__any_sync(0xffffffffu, miss) && ++it < SPIN / 16);
            float d[8] = {0.f, 0.f, 0.f, 0.f, 0.f, 0.f, 0.f, 0.f};
#pragma unroll
            for (int i = 0; i < 4; i++) mma16816(d + 4 * (i & 1), u4[2 * i].x, u4[2 * i].y, u4[2 * i + 1].x, u4[2 * i + 1].y, eye, eye);
            at[16] = pack_bf16(d[0] + d[4], d[1] + d[5]); at[17] = pack_bf16(d[2] + d[6], d[3] + d[7]);
            add_pair(8);
            DBG_G(123);
            const float2 ws = *reinterpret_cast<const float2*>(smem_raw + SM_TS);
            uint4* cdst = padd(g_cand, CFULL ? ((tid >> 1) * NCTA + rg) * 32 + (tid & 1) * 16 : (tid * NCTA + rg) * 32);
            uint32_t mean2;
            float dot;
            const float rsd = rows_stats(st, rec, cw, lane, mean2, dot);
            const uint32_t b = __float_as_uint(fmaf(fmaf(-bf_lo(mean2), ws.x, dot), rsd, ws.y));
            const uint32_t key = (((b & 0x80000000u) ? ~b : (b | 0x80000000u)) | 2047u) - (rg * 16 + l16);
            top2(key, k1, k2);
            if (tid < (CFULL + 1) * CREP) st_relaxed(cdst, k1, tag, k2, tag);
            cd = ld_relaxed64(candp);
            rows_normalise(h2, x1, mean2, rsd, lane, [&]() {
#pragma unroll
                for (int k = 0; k < 9; k++) gb[k] = lds32(sb + SM_TG + (cw * 8 + qd + (k < 8 ? (k >> 1) * 64 + (k & 1) * 4 : 256 - cw * 4)) * 4);
                if (WFE) load_wf(IC<WF1>{}, IC<WF2>{});
            });
#pragma unroll
            for (int k = 0; k < 18; k++) h2[k] = badd2(bmul2(h2[k], cs[k >> 1].x), cs[k >> 1].y);
            const uint32_t r1 = ~k1 & 15, r2 = ~k2 & 15;
            uint32_t todo = ((r1 & 7) == g8) | ((r2 & 7) == g8) << 1;
#pragma unroll 1
            while (todo) {
                const bool second = !(todo & 1), hi = (second ? r2 : r1) & 8;
                uint4* dst = padd(g_rows, ((rg * 2 + second) * RSLOT + cw * 24 + qd) * 16);
                uint32_t r[18];
#pragma unroll
                for (int k = 0; k < 9; k++) { r[k] = hi ? h2[2 * k + 1] : h2[2 * k]; r[9 + k] = hi ? x1[2 * k + 1] : x1[2 * k]; }
                fence_regs(r);
                st_relaxed(dst, r[0], r[1], r[2], r[3]);
                st_relaxed(dst + 8, r[4], r[5], r[6], r[7]);
                st_relaxed64(reinterpret_cast<uint2*>(padd(dst, 256 - qd * 8)), r[8], r[17]);
                st_relaxed(dst + 4, r[9], r[10], r[11], r[12]);
                st_relaxed(dst + 12, r[13], r[14], r[15], r[16]);
                todo &= todo - 1;
            }
            __syncwarp();

            stage_out();
            if (!WFE) load_wf(IC<WF1>{}, IC<WF2>{});
        }
        DBG_G(110);
        float4* part = reinterpret_cast<float4*>(smem_raw + 3 * SLOT + UNIT + 8192);
        bf16* act = reinterpret_cast<bf16*>(smem_raw + 3 * SLOT + UNIT + 4096);
        {
            uint32_t it = 0;
            const bool own = (tid >> 1) == rg;
            const uint32_t ks = sb + 3 * SLOT + UNIT + 5120;
#pragma unroll 1
            while (cd.y != tag && !own && ++it < SPIN / 16) cd = ld_relaxed64(candp);
            asm volatile("st.shared.u32 [%0], %1;" ::"r"(ks + tid * 4), "r"(own ? (tid & 1) ? k2 : k1 : cd.x) : "memory");
            bar_sync(3, 256);
            DBG_G(111);
            const uint4 a = lds128(ks + lane * 16), b = lds128(ks + 512 + lane * 16);
            const uint32_t a1 = max(a.x, a.z), a2 = __vimax3_u32(min(a.x, a.z), a.y, a.w);
            const uint32_t b1 = max(b.x, b.z), b2 = __vimax3_u32(min(b.x, b.z), b.y, b.w);
            const uint32_t c1 = max(a1, b1), c2 = __vimax3_u32(min(a1, b1), a2, b2);
            k1 = __reduce_max_sync(0xffffffffu, c1);
            k2 = __reduce_max_sync(0xffffffffu, c1 == k1 ? c2 : c1);
        }
        const int sel0 = ~k1 & 2047, sel1 = ~k2 & 2047;
        const uint32_t slot0 = (sel0 >> 4) * 2, slot1 = (sel1 >> 4) * 2 + ((sel0 ^ sel1) < 16);
        uint4 da[13];
        {
            const uint4* hp = padd(g_rows, (((g8 & 1) ? slot1 : slot0) * RSLOT + cw * 24 + qd) * 16);
            const uint2* hp2 = reinterpret_cast<const uint2*>(padd(hp, 256 - qd * 8));
            uint4 hv[2] = {ld_relaxed2(hp), ld_relaxed2(hp + 8)};
            uint2 hw = ld_relaxed64(hp2);
            if (tid == 255) {
                reinterpret_cast<int2*>(red)[8] = make_int2(sel0, sel1);
                mbar_arrive(bar_out);
            }
            load_wf(IC<WF2>{}, IC<23>{});
            mbar_wait(bar_full + 8, 1);
            mbar_wait(bar_full + 16, 1);
            {
                const int r = (lane & 7) + (lane & 16) / 2;
                const uint32_t d0 = sb + SLOT + r * XP + cw * 144 + (lane & 8) * 2, d1 = d0 + (r < 2 ? 16 * XP : SLOT - 2 * XP);
                const uint32_t d2 = sb + 2 * SLOT + (14 + (lane & 3)) * XP + cw * 144 + (lane >> 3) * 16;
#pragma unroll
                for (int i = 0; i < 13; i++) da[i] = ldsm4t(i < 10 ? ((i & 1) ? d1 : d0) + (i >> 1) * 32 : d2 + (i - 10) * 64);
            }
            uint32_t it = 0, miss;
#pragma unroll 1
            do {
                miss = 0;
                reload16(hv[0], hp, miss);
                reload16(hv[1], hp + 8, miss);
                reload8(hw, hp2, miss);
            } while (__any_sync(0xffffffffu, miss) && ++it < SPIN / 16);
            DBG_G(112);
            float acc[20];
#pragma unroll
            for (int i = 0; i < 20; i++) acc[i] = 0.f;
#pragma unroll
            for (int i = 0; i < 5; i++) mma1688(acc + 4 * i, (i & 1) ? wf[20 + i / 2].z : wf[20 + i / 2].x, (i & 1) ? wf[20 + i / 2].w : wf[20 + i / 2].y, hw.x);
#pragma unroll
            for (int i = 0; i < 20; i++)
                mma16816(acc + 4 * (i % 5), wf[i].x, wf[i].y, wf[i].z, wf[i].w, (i / 5 & 1) ? hv[i / 10].z : hv[i / 10].x, (i / 5 & 1) ? hv[i / 10].w : hv[i / 10].y);
            if (qd == 0) {
#pragma unroll
                for (int i = 0; i < 5; i++) part[cw * 40 + i * 8 + g8] = make_float4(acc[4 * i], acc[4 * i + 1], acc[4 * i + 2], acc[4 * i + 3]);
            }
        }
        {
            uint2* dst = padd(g_ypart, ((cw * 9 * NCTA + blockIdx.x) * 8 + g8) * 8);
            bar_sync(3, 256);
            if (cw < 5) {
                const float* pp = reinterpret_cast<const float*>(part) + ((blockIdx.x & 1) << 4) + tid;
                const float g = rbf(((pp[0] + pp[160]) + (pp[320] + pp[480])) + ((pp[640] + pp[800]) + (pp[960] + pp[1120])));
                const float v = rbf(g * sigmoidf_(g)) * __shfl_down_sync(0xffffffffu, g, 2);
                if (!(tid & 2)) act[(tid & 1) * 56 + (tid >> 2)] = __float2bfloat16_rn(tid < 144 ? v : 0.f);
            }
            bar_sync(3, 256);
            DBG_G(113);
            const uint32_t ap = sb + 3 * SLOT + UNIT + 4096 + (lane & 1) * 112 + (lane >> 3) * 16;
            const uint4 b0 = ldsm4(ap);
            const uint32_t b1 = lds32(sb + 3 * SLOT + UNIT + 4096 + (g8 & 1) * 112 + 64 + qd * 4);
            float y[20];
#pragma unroll
            for (int i = 0; i < 20; i++) y[i] = 0.f;
#pragma unroll
            for (int i = 0; i < 5; i++) {
                mma16816(y + 4 * i, da[2 * i].x, da[2 * i].y, da[2 * i].z, da[2 * i].w, b0.x, b0.y);
                mma16816(y + 4 * i, da[2 * i + 1].x, da[2 * i + 1].y, da[2 * i + 1].z, da[2 * i + 1].w, b0.z, b0.w);
                mma1688(y + 4 * i, (i & 1) ? da[10 + i / 2].z : da[10 + i / 2].x, (i & 1) ? da[10 + i / 2].w : da[10 + i / 2].y, b1);
            }
#pragma unroll
            for (int i = 0; i < 9; i++)
                asm volatile("{\n.reg .pred p;\nsetp.eq.b32 p, %3, 0;\n@p st.relaxed.gpu.global.v2.f32 [%0], {%1, %2};\n}"
                             ::"l"(dst + i * (NCTA * 8)), "f"(y[2 * i]), "f"(y[2 * i + 1]), "r"(qd) : "memory");
        }
        DBG_G(114);
        if (blockIdx.x == 127 && tid == 0) gs->epoch[0] = tag;
        if (blockIdx.x < 72) {
            const int G = blockIdx.x, tok = g8 & 1, cp = G * 4 + qd;
            const uint2* src = padd(g_ypart, (blockIdx.x * NCTA * 8 + tid) * 8);
            const uint8_t* hsrc = reinterpret_cast<const uint8_t*>(padd(g_rows, (tok ? slot1 : slot0) * (RSLOT * 16) +
                (G < 64 ? (G >> 1 & 7) * 384 + (G >> 5) * 128 + qd * 16 + (G >> 1 & 8) + (G & 1) * 4 : (G - 64) * 384 + 256 + qd * 8)));
            const uint8_t* xsrc = hsrc + (G < 64 ? 64 : 4);
            uint32_t* dst = padd(reinterpret_cast<uint32_t*>(args.out), (tok ? sel1 : sel0) * (D_ * 2) + cp * 4);
            const uint32_t gb = reinterpret_cast<const uint32_t*>(smem_raw + SM_TG)[cp];
            const uint32_t ksel = ((tok ? k2 : k1) & ~2047u) | 1024u;
            const float sg = sigmoidf_(rbf(__uint_as_float((ksel & 0x80000000u) ? (ksel & 0x7fffffffu) : ~ksel)));
            uint2 v[4];
            uint32_t hv, xv, it = 0;
            bool miss;
#pragma unroll 1
            do {
#pragma unroll
                for (int i = 0; i < 4; i++) v[i] = ld_relaxed64(src + i * 256);
                hv = ld_relaxed32(hsrc);
                xv = ld_relaxed32(xsrc);
                miss = max(__vimax3_u32(v[0].x, v[1].x, v[2].x), __vimax3_u32(v[3].x, hv, xv)) == ~0u;
            } while (__any_sync(0xffffffffu, miss) && ++it < SPIN / 16);
            float y0 = (__uint_as_float(v[0].x) + __uint_as_float(v[1].x)) + (__uint_as_float(v[2].x) + __uint_as_float(v[3].x));
            float y1 = (__uint_as_float(v[0].y) + __uint_as_float(v[1].y)) + (__uint_as_float(v[2].y) + __uint_as_float(v[3].y));
            y0 += __shfl_xor_sync(0xffffffffu, y0, 8); y1 += __shfl_xor_sync(0xffffffffu, y1, 8);
            y0 += __shfl_xor_sync(0xffffffffu, y0, 16); y1 += __shfl_xor_sync(0xffffffffu, y1, 16);
            if (lane < 8) reinterpret_cast<float2*>(rec)[cw * 8 + lane] = make_float2(y0, y1);
            bar_sync(3, 256);
            if (cw == 0) {
                const float4 t0_ = rec[(lane >> 3) * 4 + qd], t1_ = rec[16 + (lane >> 3) * 4 + qd];
                y0 = tok ? t0_.y + t1_.y : t0_.x + t1_.x; y1 = tok ? t0_.w + t1_.w : t0_.z + t1_.z;
                y0 += __shfl_xor_sync(0xffffffffu, y0, 8); y1 += __shfl_xor_sync(0xffffffffu, y1, 8);
                y0 += __shfl_xor_sync(0xffffffffu, y0, 16); y1 += __shfl_xor_sync(0xffffffffu, y1, 16);
                const uint32_t y2 = bmul2(pack_bf16(y0, y1), pack_bf16(sg, sg));
                if (lane < 8) *dst = badd2(xv, bmul2(gb, badd2(hv, y2)));
            }
        }
        }
        DBG_T(88);
        DBG_G(121);
    }
}

typedef CUresult (*EncodeFn)(CUtensorMap*, CUtensorMapDataType, cuuint32_t, void*, const cuuint64_t*, const cuuint64_t*,
                             const cuuint32_t*, const cuuint32_t*, CUtensorMapInterleave, CUtensorMapSwizzle,
                             CUtensorMapL2promotion, CUtensorMapFloatOOBfill);

static void make_map(EncodeFn enc, CUtensorMap* m, const void* ptr, int rank, const cuuint64_t* dims,
                     const cuuint64_t* strides, const cuuint32_t* box, CUtensorMapSwizzle sw = CU_TENSOR_MAP_SWIZZLE_128B,
                     CUtensorMapDataType dt = CU_TENSOR_MAP_DATA_TYPE_BFLOAT16) {
    const cuuint32_t es[3] = {1, 1, 1};
    enc(m, dt, rank, const_cast<void*>(ptr), dims, strides, box, es,
        CU_TENSOR_MAP_INTERLEAVE_NONE, sw, CU_TENSOR_MAP_L2_PROMOTION_L2_128B,
        CU_TENSOR_MAP_FLOAT_OOB_FILL_NONE);
}

extern "C" void kernel_launch(void* const* d_in, const int* in_sizes, int n_in, void* d_out, int out_size) {
    const bf16* x = (const bf16*)d_in[0];
    const bf16* kc = (const bf16*)d_in[1];
    const bf16* vc = (const bf16*)d_in[2];
    const bf16* wq = (const bf16*)d_in[3];
    const bf16* wo = (const bf16*)d_in[4];
    const bf16* w_r = (const bf16*)d_in[6];
    const bf16* w_gate = (const bf16*)d_in[7];
    const bf16* w_up = (const bf16*)d_in[8];
    const bf16* w_down = (const bf16*)d_in[9];
    const bf16* cvec = (const bf16*)d_in[10];
    const bf16* w_mod = (const bf16*)d_in[11];
    bf16* out = (bf16*)d_out;

    void* fn = nullptr;
    cudaDriverEntryPointQueryResult qr;
    cudaGetDriverEntryPoint("cuTensorMapEncodeTiled", &fn, cudaEnableDefault, &qr);
    EncodeFn enc = (EncodeFn)fn;
    void* p_s;
    cudaGetSymbolAddress(&p_s, g_s);

    CUtensorMap tm_wq, tm_k, tm_v, tm_wo, tm_p, tm_x, tm_d, tm_g, tm_u;
    { cuuint64_t d[2] = {QD, D_}, s[1] = {QD * 2}; cuuint32_t b[2] = {64, 128}; make_map(enc, &tm_wq, wq, 2, d, s, b); }
    { cuuint64_t d[2] = {DH, HKV * S_}, s[1] = {DH * 2}; cuuint32_t b[2] = {64, 128};
      make_map(enc, &tm_k, kc, 2, d, s, b); make_map(enc, &tm_v, vc, 2, d, s, b); }
    { cuuint64_t d[2] = {D_, QD}, s[1] = {D_ * 2}; cuuint32_t b[2] = {64, 128}; make_map(enc, &tm_wo, wo, 2, d, s, b); }
    { cuuint64_t d[3] = {256, 160, NCTA}, s[2] = {1024, 8 * WREG}; cuuint32_t b[3] = {256, 2, 8};
      make_map(enc, &tm_p, ((Scratch*)p_s)->frag, 3, d, s, b, CU_TENSOR_MAP_SWIZZLE_NONE, CU_TENSOR_MAP_DATA_TYPE_UINT32); }
    { cuuint64_t d[2] = {D_ / 4, S_}, s[1] = {D_ * 2}; cuuint32_t b[2] = {XP / 8, 16};
      make_map(enc, &tm_x, x, 2, d, s, b, CU_TENSOR_MAP_SWIZZLE_NONE, CU_TENSOR_MAP_DATA_TYPE_UINT64); }
    { cuuint64_t d[2] = {D_ / 4, F_}, s[1] = {D_ * 2}; cuuint32_t b[2] = {XP / 8, 18};
      make_map(enc, &tm_d, w_down, 2, d, s, b, CU_TENSOR_MAP_SWIZZLE_NONE, CU_TENSOR_MAP_DATA_TYPE_UINT64); }
    { cuuint64_t d[2] = {F_, D_}, s[1] = {F_ * 2}; cuuint32_t b[2] = {40, 24};
      make_map(enc, &tm_g, w_gate, 2, d, s, b, CU_TENSOR_MAP_SWIZZLE_NONE); make_map(enc, &tm_u, w_up, 2, d, s, b, CU_TENSOR_MAP_SWIZZLE_NONE); }

    cudaFuncSetAttribute(fused_kernel<true>, cudaFuncAttributeMaxDynamicSharedMemorySize, SM_TOTAL);
    cudaFuncSetAttribute(fused_kernel<false>, cudaFuncAttributeMaxDynamicSharedMemorySize, SM_TOTAL);
    cudaLaunchConfig_t cfg = {};
    cfg.gridDim = NCTA + 4; cfg.blockDim = 384; cfg.dynamicSmemBytes = SM_TOTAL;
    cudaLaunchAttribute at;
    at.id = cudaLaunchAttributeClusterDimension; at.val.clusterDim.x = 2; at.val.clusterDim.y = 1; at.val.clusterDim.z = 1;
    cfg.attrs = &at; cfg.numAttrs = 1;
    int ncl = 0;
    if (cudaOccupancyMaxActiveClusters(&ncl, fused_kernel<true>, &cfg) != cudaSuccess) { ncl = 0; cudaGetLastError(); }
    Args args{w_mod, cvec, (Scratch*)p_s, desc_lo(0, UNIT) | (0x40000040ull << 32), out, x, kc, vc, wq, wo, w_r, w_down};
    if (USE_SPARE && ncl >= NCTA / 2 + 2)
        fused_kernel<true><<<NCTA + 4, 384, SM_TOTAL>>>(args, tm_wq, tm_k, tm_v, tm_wo, tm_p, tm_x, tm_d, tm_g, tm_u);
    else
        fused_kernel<false><<<NCTA, 384, SM_TOTAL>>>(args, tm_wq, tm_k, tm_v, tm_wo, tm_p, tm_x, tm_d, tm_g, tm_u);
}
```

```cpp
#include <cuda_runtime.h>
#include <cuda_bf16.h>
#include <cuda.h>
#include <stdint.h>
#include <math.h>

typedef __nv_bfloat16 bf16;

constexpr int S_ = 2048;
constexpr int D_ = 576;
constexpr int HQ = 32, HKV = 16, DH = 128;
constexpr int F_ = 4608;
constexpr int QD = HQ * DH;

constexpr int NCTA = 128;
constexpr int WREG = 5 * 4096;
constexpr int CREP = 8;
constexpr int RSLOT = 192;
constexpr int MREP = 4;
struct Scratch {
    unsigned int epoch[128];
    unsigned int flag_mod[NCTA];
    unsigned int flag_part[16 * 32];
    unsigned int flag_q3[16 * 32];
    unsigned int flag_h[NCTA * 32];
    uint2 mod1[MREP * D_];
    uint32_t mod2[4 * D_];
    uint4 cand[CREP * NCTA * 2];
    uint2 ypart[72 * NCTA * 8];
    uint4 h[2][NCTA * 36 * 32];
    uint4 q3[NCTA * 8 * 128];
    uint4 rows[NCTA * 2 * RSLOT];
    uint8_t frag[NCTA * 8 * WREG];
    uint8_t keep[NCTA * 8 * 4096];
};
__device__ __align__(1024) Scratch g_s;
#define g_h gs->h[tag & 1]
#define g_q3 gs->q3
#define g_keep gs->keep
#define g_flag_h gs->flag_h
#define g_flag_part gs->flag_part
#define g_flag_mod gs->flag_mod
#define g_flag_q3 gs->flag_q3
#define g_frag gs->frag
#define g_cand gs->cand
#define g_ypart gs->ypart
#define g_rows gs->rows

#define DBG_INIT()
#define DBG_P(i)
#define DBG_PG(i)
#define DBG_T(i)
#define DBG_G(i)

__device__ __forceinline__ uint32_t pack_bf16(float lo, float hi) {
    uint32_t r;
    asm("cvt.rn.bf16x2.f32 %0, %1, %2;" : "=r"(r) : "f"(hi), "f"(lo));
    return r;
}
__device__ __forceinline__ float rbf(float x) { return __uint_as_float(pack_bf16(0.f, x)); }
__device__ __forceinline__ float bf_lo(uint32_t v) { return __uint_as_float(v << 16); }
__device__ __forceinline__ float bf_hi(uint32_t v) { return __uint_as_float(v & 0xffff0000u); }
__device__ __forceinline__ float ex2(float x) {
    float y;
    asm("ex2.approx.ftz.f32 %0, %1;" : "=f"(y) : "f"(x));
    return y;
}
template <class T>
__device__ __forceinline__ T* padd(T* p, uint32_t off) {
    unsigned long long r;
    asm("{\n.reg .b32 l, h;\nmov.b64 {l, h}, %1;\nadd.cc.u32 l, l, %2;\naddc.u32 h, h, 0;\nmov.b64 %0, {l, h};\n}" : "=l"(r) : "l"(p), "r"(off));
    return reinterpret_cast<T*>(r);
}
__device__ __forceinline__ uint32_t smem_u32(const void* p) { return (uint32_t)__cvta_generic_to_shared(p); }
__device__ __forceinline__ void mbar_init(uint32_t bar, uint32_t cnt) {
    asm volatile("mbarrier.init.shared::cta.b64 [%0], %1;" ::"r"(bar), "r"(cnt) : "memory");
}
__device__ __forceinline__ void mbar_expect_tx(uint32_t bar, uint32_t bytes) {
    asm volatile("mbarrier.arrive.expect_tx.shared::cta.b64 _, [%0], %1;" ::"r"(bar), "r"(bytes) : "memory");
}
__device__ __forceinline__ void mbar_arrive(uint32_t bar) {
    asm volatile("mbarrier.arrive.shared::cta.b64 _, [%0];" ::"r"(bar) : "memory");
}
__device__ __forceinline__ void mbar_arrive_cluster(uint32_t cluster_addr) {
    asm volatile("mbarrier.arrive.shared::cluster.b64 _, [%0];" ::"r"(cluster_addr) : "memory");
}
constexpr uint32_t SPIN = 1u << 20;
__device__ __forceinline__ void mbar_wait(uint32_t bar, uint32_t parity) {
    asm volatile("{\n.reg .pred p;\n.reg .b32 c;\nmov.b32 c, 0;\n"
                 "W_%=:\nmbarrier.try_wait.parity.shared::cta.b64 p, [%0], %1;\n"
                 "add.u32 c, c, 1;\nsetp.lt.and.u32 p, c, 0x100000, !p;\n@p bra W_%=;\n}"
                 ::"r"(bar), "r"(parity) : "memory");
}
__device__ __forceinline__ void anchor(uint32_t addr, float v) {
    asm volatile("{\n.reg .pred p;\nsetp.lt.f32 p, %1, 0f00000000;\n@p st.volatile.shared.f32 [%0], %1;\n}" ::"r"(addr), "f"(v) : "memory");
}
__device__ __forceinline__ void anchor(uint32_t addr, uint32_t v) {
    asm volatile("{\n.reg .pred p;\nsetp.eq.u32 p, %1, 0xffffffff;\n@p st.volatile.shared.u32 [%0], %1;\n}" ::"r"(addr), "r"(v) : "memory");
}
__device__ __forceinline__ void hold(float& a, float& b) {
    asm volatile("{\n.reg .pred p;\n.reg .b64 t;\n.reg .b32 l, h;\nmov.u64 t, %%clock64;\nmov.b64 {l, h}, t;\nsetp.eq.u32 p, h, 0xffffffff;\n"
                 "@p mov.f32 %0, 0f00000000;\n@p mov.f32 %1, 0f00000000;\n}" : "+f"(a), "+f"(b) :: "memory");
}
__device__ __forceinline__ void mbar_wait_sleep(uint32_t bar, uint32_t parity) {
    asm volatile("{\n.reg .pred p;\n.reg .b32 c;\nmov.b32 c, 0;\n"
                 "W_%=:\nmbarrier.try_wait.parity.shared::cta.b64 p, [%0], %1, 5000;\n"
                 "add.u32 c, c, 1;\nsetp.lt.and.u32 p, c, 0x20000, !p;\n@p bra W_%=;\n}"
                 ::"r"(bar), "r"(parity) : "memory");
}
__device__ __forceinline__ uint32_t load_tag(const Scratch* gs) {
    uint32_t tag;
    asm volatile("ld.global.ca.u32 %0, [%1];" : "=r"(tag) : "l"(gs->epoch) : "memory");
    return tag + 1;
}
__device__ __forceinline__ uint4 ld_relaxed(const uint4* p) {
    uint4 v;
    asm volatile("ld.relaxed.gpu.global.v4.u32 {%0,%1,%2,%3}, [%4];" : "=r"(v.x), "=r"(v.y), "=r"(v.z), "=r"(v.w) : "l"(p) : "memory");
    return v;
}
__device__ __forceinline__ void st_relaxed(uint4* p, uint32_t a, uint32_t b, uint32_t c, uint32_t d) {
    asm volatile("{\n.reg .b64 u, v;\nmov.b64 u, {%1, %2};\nmov.b64 v, {%3, %4};\nst.relaxed.gpu.global.v2.b64 [%0], {u, v};\n}"
                 ::"l"(p), "r"(a), "r"(b), "r"(c), "r"(d) : "memory");
}
__device__ __forceinline__ void st_relaxed4(void* p, uint32_t a, uint32_t b, uint32_t c, uint32_t d) {
    asm volatile("st.relaxed.gpu.global.v4.u32 [%0], {%1, %2, %3, %4};" ::"l"(p), "r"(a), "r"(b), "r"(c), "r"(d) : "memory");
}
__device__ __forceinline__ uint2 ld_relaxed8(const void* p) {
    uint2 v;
    asm volatile("ld.relaxed.gpu.global.v2.u32 {%0,%1}, [%2];" : "=r"(v.x), "=r"(v.y) : "l"(p) : "memory");
    return v;
}
__device__ __forceinline__ uint2 ld_relaxed64(const uint2* p) {
    uint2 v;
    asm volatile("{\n.reg .b64 u;\nld.relaxed.gpu.global.b64 u, [%2];\nmov.b64 {%0, %1}, u;\n}" : "=r"(v.x), "=r"(v.y) : "l"(p) : "memory");
    return v;
}
__device__ __forceinline__ void st_relaxed64(uint2* p, uint32_t a, uint32_t b) {
    asm volatile("{\n.reg .b64 u;\nmov.b64 u, {%1, %2};\nst.relaxed.gpu.global.b64 [%0], u;\n}" ::"l"(p), "r"(a), "r"(b) : "memory");
}
__device__ __forceinline__ uint4 ld_relaxed2(const uint4* p) {
    uint4 v;
    asm volatile("{\n.reg .b64 u, w;\nld.relaxed.gpu.global.v2.b64 {u, w}, [%4];\nmov.b64 {%0, %1}, u;\nmov.b64 {%2, %3}, w;\n}"
                 : "=r"(v.x), "=r"(v.y), "=r"(v.z), "=r"(v.w) : "l"(p) : "memory");
    return v;
}
__device__ __forceinline__ void reload16(uint4& v, const void* p, uint32_t& miss) {
    asm volatile("{\n.reg .pred p;\n.reg .b32 m;\n.reg .b64 u, w;\nmax.u32 m, %0, %2;\nsetp.eq.u32 p, m, 0xffffffff;\n"
                 "mov.b64 u, {%0, %1};\nmov.b64 w, {%2, %3};\n@p ld.relaxed.gpu.global.v2.b64 {u, w}, [%5];\n"
                 "mov.b64 {%0, %1}, u;\nmov.b64 {%2, %3}, w;\n@p mov.u32 %4, 1;\n}"
                 : "+r"(v.x), "+r"(v.y), "+r"(v.z), "+r"(v.w), "+r"(miss) : "l"(p) : "memory");
}
__device__ __forceinline__ void reload8(uint2& v, const void* p, uint32_t& miss) {
    asm volatile("{\n.reg .pred p;\n.reg .b64 u;\nsetp.eq.u32 p, %0, 0xffffffff;\nmov.b64 u, {%0, %1};\n"
                 "@p ld.relaxed.gpu.global.b64 u, [%3];\nmov.b64 {%0, %1}, u;\n@p mov.u32 %2, 1;\n}"
                 : "+r"(v.x), "+r"(v.y), "+r"(miss) : "l"(p) : "memory");
}
__device__ __forceinline__ uint32_t ld_relaxed32(const void* p) {
    uint32_t v;
    asm volatile("ld.relaxed.gpu.global.u32 %0, [%1];" : "=r"(v) : "l"(p) : "memory");
    return v;
}
__device__ __forceinline__ void flag_wait(const unsigned int* p, uint32_t tag) {
    uint32_t v, it = 0;
#pragma unroll 1
    do {
        asm volatile("ld.relaxed.gpu.global.u32 %0, [%1];" : "=r"(v) : "l"(p) : "memory");
    } while (__any_sync(0xffffffffu, v != tag) && ++it < SPIN / 16);
    asm volatile("fence.acquire.gpu;" ::: "memory");
    __syncwarp();
}
__device__ __forceinline__ bool elect() {
    uint32_t p;
    asm volatile("{\n.reg .pred p;\nelect.sync _|p, 0xffffffff;\nselp.u32 %0, 1, 0, p;\n}" : "=r"(p));
    return p;
}
__device__ __forceinline__ void flag_release(unsigned int* p, uint32_t tag) {
    asm volatile("st.release.gpu.global.u32 [%0], %1;" ::"l"(p), "r"(tag) : "memory");
}
__device__ __forceinline__ uint32_t touch(const void* p) {
    uint32_t v;
    asm volatile("ld.global.nc.L1::no_allocate.L2::128B.u32 %0, [%1];" : "=r"(v) : "l"(p));
    return v;
}
__device__ __forceinline__ void bar_sync(int id, int n) { asm volatile("bar.sync %0, %1;" ::"r"(id), "r"(n) : "memory"); }
__device__ __forceinline__ void bar_arrive(int id, int n) { asm volatile("bar.arrive %0, %1;" ::"r"(id), "r"(n) : "memory"); }

constexpr uint64_t EVICT_NORMAL = 0x1000000000000000ull, EVICT_FIRST = 0x12F0000000000000ull;
__device__ __forceinline__ void tma2d(uint32_t dst, const CUtensorMap* m, int c0, int c1, uint32_t bar) {
    asm volatile("cp.async.bulk.tensor.2d.shared::cluster.global.mbarrier::complete_tx::bytes.L2::cache_hint [%0], [%1, {%3, %4}], [%2], %5;"
                 ::"r"(dst), "l"(m), "r"(bar), "r"(c0), "r"(c1), "l"(EVICT_FIRST) : "memory");
}
__device__ __forceinline__ void tma2d_mc(uint32_t dst, const CUtensorMap* m, int c0, int c1, uint32_t bar, uint64_t pol) {
    asm volatile("cp.async.bulk.tensor.2d.shared::cluster.global.mbarrier::complete_tx::bytes.multicast::cluster.L2::cache_hint [%0], [%1, {%3, %4}], [%2], %5, %6;"
                 ::"r"(dst), "l"(m), "r"(bar), "r"(c0), "r"(c1), "h"((uint16_t)3), "l"(pol) : "memory");
}
__device__ __forceinline__ void tma3d(uint32_t dst, const CUtensorMap* m, int c0, int c1, int c2, uint32_t bar) {
    asm volatile("cp.async.bulk.tensor.3d.shared::cluster.global.mbarrier::complete_tx::bytes.L2::cache_hint [%0], [%1, {%3, %4, %5}], [%2], %6;"
                 ::"r"(dst), "l"(m), "r"(bar), "r"(c0), "r"(c1), "r"(c2), "l"(EVICT_FIRST) : "memory");
}
__device__ __forceinline__ void bulk_load(uint32_t dst, const void* src, uint32_t bytes, uint32_t bar) {
    asm volatile("cp.async.bulk.shared::cluster.global.mbarrier::complete_tx::bytes [%0], [%1], %2, [%3];"
                 ::"r"(dst), "l"(src), "r"(bytes), "r"(bar) : "memory");
}
__device__ __forceinline__ void l2_prefetch(const void* src, uint32_t bytes) {
    asm volatile("cp.async.bulk.prefetch.L2.global [%0], %1;" ::"l"(src), "r"(bytes) : "memory");
}
__device__ __forceinline__ uint32_t bmul2(uint32_t a, uint32_t b) { uint32_t r; asm("mul.rn.bf16x2 %0, %1, %2;" : "=r"(r) : "r"(a), "r"(b)); return r; }
__device__ __forceinline__ uint32_t badd2(uint32_t a, uint32_t b) { uint32_t r; asm("add.rn.bf16x2 %0, %1, %2;" : "=r"(r) : "r"(a), "r"(b)); return r; }
__device__ __forceinline__ uint32_t bsub2(uint32_t a, uint32_t b) { uint32_t r; asm("sub.rn.bf16x2 %0, %1, %2;" : "=r"(r) : "r"(a), "r"(b)); return r; }
__device__ __forceinline__ uint32_t bmax2(uint32_t a, uint32_t b) { uint32_t r; asm("max.bf16x2 %0, %1, %2;" : "=r"(r) : "r"(a), "r"(b)); return r; }
__device__ __forceinline__ uint32_t bfma2(uint32_t a, uint32_t b, uint32_t c) { uint32_t r; asm("fma.rn.bf16x2 %0, %1, %2, %3;" : "=r"(r) : "r"(a), "r"(b), "r"(c)); return r; }
__device__ __forceinline__ uint4 lds128(uint32_t a) { uint4 v; asm volatile("ld.shared.v4.u32 {%0,%1,%2,%3}, [%4];" : "=r"(v.x), "=r"(v.y), "=r"(v.z), "=r"(v.w) : "r"(a) : "memory"); return v; }
__device__ __forceinline__ uint2 lds64(uint32_t a) { uint2 v; asm volatile("ld.shared.v2.u32 {%0,%1}, [%2];" : "=r"(v.x), "=r"(v.y) : "r"(a) : "memory"); return v; }
__device__ __forceinline__ uint32_t lds32(uint32_t a) { uint32_t v; asm volatile("ld.shared.u32 %0, [%1];" : "=r"(v) : "r"(a) : "memory"); return v; }
__device__ __forceinline__ uint4 ldsm4(uint32_t a) {
    uint4 v;
    asm volatile("ldmatrix.sync.aligned.m8n8.x4.shared.b16 {%0,%1,%2,%3}, [%4];" : "=r"(v.x), "=r"(v.y), "=r"(v.z), "=r"(v.w) : "r"(a) : "memory");
    return v;
}
__device__ __forceinline__ uint4 ldsm4t(uint32_t a) {
    uint4 v;
    asm volatile("ldmatrix.sync.aligned.m8n8.x4.trans.shared.b16 {%0,%1,%2,%3}, [%4];" : "=r"(v.x), "=r"(v.y), "=r"(v.z), "=r"(v.w) : "r"(a) : "memory");
    return v;
}
__device__ __forceinline__ void mma1688(float* d, uint32_t a0, uint32_t a1, uint32_t b) {
    asm("mma.sync.aligned.m16n8k8.row.col.f32.bf16.bf16.f32 {%0,%1,%2,%3}, {%4,%5}, {%6}, {%0,%1,%2,%3};"
        : "+f"(d[0]), "+f"(d[1]), "+f"(d[2]), "+f"(d[3]) : "r"(a0), "r"(a1), "r"(b));
}
__device__ __forceinline__ void mma16816(float* d, uint32_t a0, uint32_t a1, uint32_t a2, uint32_t a3, uint32_t b0, uint32_t b1) {
    asm("mma.sync.aligned.m16n8k16.row.col.f32.bf16.bf16.f32 {%0,%1,%2,%3}, {%4,%5,%6,%7}, {%8,%9}, {%0,%1,%2,%3};"
                 : "+f"(d[0]), "+f"(d[1]), "+f"(d[2]), "+f"(d[3]) : "r"(a0), "r"(a1), "r"(a2), "r"(a3), "r"(b0), "r"(b1));
}
__device__ __forceinline__ void stsm_x4(uint32_t addr, uint32_t a, uint32_t b, uint32_t c, uint32_t d) {
    asm volatile("stmatrix.sync.aligned.m8n8.x4.shared.b16 [%0], {%1, %2, %3, %4};"
                 ::"r"(addr), "r"(a), "r"(b), "r"(c), "r"(d) : "memory");
}

__device__ __forceinline__ uint64_t mkdesc(uint32_t addr, uint32_t lbo, uint32_t sbo) {
    return (uint64_t)((addr & 0x3FFFF) >> 4) | ((uint64_t)(lbo >> 4) << 16) | ((uint64_t)(sbo >> 4) << 32) | (1ull << 62);
}
constexpr uint32_t SM0 = 1024;
__host__ __device__ constexpr uint32_t desc_lo(uint32_t off, uint32_t lbo) { return ((SM0 + off) >> 4) | ((lbo >> 4) << 16); }
#define WG_FENCE() asm volatile("wgmma.fence.sync.aligned;" ::: "memory")
#define WG_COMMIT() asm volatile("wgmma.commit_group.sync.aligned;" ::: "memory")
#define WG_WAIT(n) asm volatile("wgmma.wait_group.sync.aligned %0;" ::"n"(n) : "memory")

#define F8(a, i) "+f"(a[i]), "+f"(a[i + 1]), "+f"(a[i + 2]), "+f"(a[i + 3]), "+f"(a[i + 4]), "+f"(a[i + 5]), "+f"(a[i + 6]), "+f"(a[i + 7])
#define F16(a, i) F8(a, i), F8(a, i + 8)
#define F64(a) F16(a, 0), F16(a, 16), F16(a, 32), F16(a, 48)
#define F32(a) F16(a, 0), F16(a, 16)
#define L64 "%0,%1,%2,%3,%4,%5,%6,%7,%8,%9,%10,%11,%12,%13,%14,%15,%16,%17,%18,%19,%20,%21,%22,%23,%24,%25,%26,%27,%28,%29,%30,%31,%32,%33,%34,%35,%36,%37,%38,%39,%40,%41,%42,%43,%44,%45,%46,%47,%48,%49,%50,%51,%52,%53,%54,%55,%56,%57,%58,%59,%60,%61,%62,%63"
#define L32 "%0,%1,%2,%3,%4,%5,%6,%7,%8,%9,%10,%11,%12,%13,%14,%15,%16,%17,%18,%19,%20,%21,%22,%23,%24,%25,%26,%27,%28,%29,%30,%31"

template <int TB, int STEP = 128>
__device__ __forceinline__ void mma_rs128(float (&d)[64], uint32_t a0, uint32_t a1, uint32_t a2, uint32_t a3, uint64_t& b, int acc) {
    asm volatile("{\n.reg .pred p;\nsetp.ne.b32 p, %69, 0;\n"
                 "wgmma.mma_async.sync.aligned.m64n128k16.f32.bf16.bf16 {" L64 "}, {%65,%66,%67,%68}, %64, p, 1, 1, %70;\nadd.s64 %64, %64, %71;\n}"
                 : F64(d), "+l"(b) : "r"(a0), "r"(a1), "r"(a2), "r"(a3), "r"(acc), "n"(TB), "n"(STEP));
}
template <int TB>
__device__ __forceinline__ void mma_rs64(float (&d)[32], uint32_t a0, uint32_t a1, uint32_t a2, uint32_t a3, uint64_t& b, int acc) {
    asm volatile("{\n.reg .pred p;\nsetp.ne.b32 p, %37, 0;\n"
                 "wgmma.mma_async.sync.aligned.m64n64k16.f32.bf16.bf16 {" L32 "}, {%33,%34,%35,%36}, %32, p, 1, 1, %38;\nadd.s64 %32, %32, 128;\n}"
                 : F32(d), "+l"(b) : "r"(a0), "r"(a1), "r"(a2), "r"(a3), "r"(acc), "n"(TB));
}
template <int N>
__device__ __forceinline__ void fence_regs(float (&d)[N]) {
#pragma unroll
    for (int i = 0; i < N; i++) asm volatile("" : "+f"(d[i])::"memory");
}
template <int N>
__device__ __forceinline__ void fence_regs(uint32_t (&d)[N]) {
#pragma unroll
    for (int i = 0; i < N; i++) asm volatile("" : "+r"(d[i])::"memory");
}

template <int V> struct IC { static constexpr int value = V; };

constexpr int SLOT = 32768, UNIT = 16384;
constexpr int SM_Q = 4 * SLOT;
constexpr int SM_BAR = 7 * SLOT;
constexpr int SM_RED = SM_BAR + 512;
constexpr int SM_TOTAL = SM_BAR + 3072;
constexpr int XP = D_ * 2 + 16;
constexpr int M_MOD = 16 * XP;
constexpr int SM_T = SM_Q + 2 * D_ * 80, SM_TC = SM_T + D_ * 4, SM_TG = SM_TC + D_ * 4, SM_TS = SM_TG + D_ * 2;
constexpr float CS = 0.08838834764831845f * 1.4426950408889634f;
#define LMAX 0.5f
#define LMIN 0x1p-104f
#define USE_SPARE 1
#define MAXG 2
#define SPLIT 10
#define ESPLIT 3
#define PV1 8
#define RW 2
#define HW 2
#define HW2 1
#define XDELAY 200
#define QDELAY 300
#define TMPF 1
#define PFD0 2000
#define PFD1 400
#define HDELAY 300
#define RCM 16
#define RPE 2
#define OSPLIT 6
#define HOLD 1
#define DL 6
#define STAGE 11
#define POFF 102.f
#define WF0 3
#define WF1 13
#define C3D 0
#define C4D 300
#define DD 300
#define P2E 0
#define BO 0
#define MAP 2
#define CFULL 0
#define WFE 1
#define OUTD 0
#define OUTPOL EVICT_FIRST
#define WF2 19
constexpr int PF_KV = 8, PF_WO = 120;

__device__ __forceinline__ int cluster_role() {
    int k;
    asm volatile("mov.u32 %0, %%ctaid.x;" : "=r"(k));
    k >>= 1;
    if (MAP == 0) return k & 63;
    if (MAP == 1) return (k & 7) * 8 + ((k >> 3) & 7);
    if (MAP == 3) {
        asm("mov.u32 %0, %%smid;" : "=r"(k));
        k >>= 1;
        const int r = ((k - 32) * 37) >> 8;
        return k < 32 ? (k & 7) * 8 + (k >> 3) : k < 60 ? (k - 31 - r * 7) * 8 + 4 + r : (k - 58) & 7;
    }
    const int r = ((k - 36) * 37) >> 8, i = k - 36 - r * 7;
    if (MAP == 4) return k < 4 ? 4 + k : k < 36 ? ((k - 4) & 7) * 8 + ((k - 4) >> 3) : (i + 1) * 8 + ((4 + r) & 7);
    return k < 4 ? 12 + k : k < 36 ? ((k - 4) & 7) * 8 + ((k - 4) >> 3) : (i + (i > 0)) * 8 + ((4 + r) & 7);
}

struct Args {
    const bf16 *w_mod, *cvec;
    Scratch* gs;
    uint64_t d0;
    bf16* out;
    const bf16 *x, *kc, *vc, *wq, *wo, *w_r, *w_down;
};

__device__ __forceinline__ void frag_store(uint8_t* p, const uint32_t (&a)[32]) {
#pragma unroll
    for (int i = 0; i < 8; i++)
        __stcg(reinterpret_cast<uint4*>(p + i * 512), make_uint4(a[4 * i], a[4 * i + 1], a[4 * i + 2], a[4 * i + 3]));
}
__device__ __forceinline__ void frag_load(uint32_t (&a)[32], const uint8_t* p) {
#pragma unroll
    for (int i = 0; i < 8; i++) {
        const uint4 v = __ldcg(reinterpret_cast<const uint4*>(p + i * 512));
        a[4 * i] = v.x; a[4 * i + 1] = v.y; a[4 * i + 2] = v.z; a[4 * i + 3] = v.w;
    }
}
__device__ __forceinline__ float quad_sum(float v) {
    v += __shfl_xor_sync(0xffffffffu, v, 1);
    return v + __shfl_xor_sync(0xffffffffu, v, 2);
}
__device__ __forceinline__ float quad_max(float v) {
    v = fmaxf(v, __shfl_xor_sync(0xffffffffu, v, 1));
    return fmaxf(v, __shfl_xor_sync(0xffffffffu, v, 2));
}
__device__ __forceinline__ float rcp_fast(float x) { float y; asm("rcp.approx.ftz.f32 %0, %1;" : "=f"(y) : "f"(x)); return y; }
__device__ __forceinline__ float sigmoidf_(float x) { return rcp_fast(1.f + ex2(-1.4426950408889634f * x)); }
__device__ __forceinline__ void top2(uint32_t k, uint32_t& k1, uint32_t& k2) {
    k1 = __reduce_max_sync(0xffffffffu, k);
    k2 = __reduce_max_sync(0xffffffffu, k == k1 ? 0 : k);
}

__device__ __forceinline__ void mod_fma(float (&a)[8], const uint4 w, float sc) {
    a[0] += sc * bf_lo(w.x); a[1] += sc * bf_hi(w.x); a[2] += sc * bf_lo(w.y); a[3] += sc * bf_hi(w.y);
    a[4] += sc * bf_lo(w.z); a[5] += sc * bf_hi(w.z); a[6] += sc * bf_lo(w.w); a[7] += sc * bf_hi(w.w);
}
__device__ __forceinline__ float mod_reduce(float (&a)[8], int lane) {
#pragma unroll
    for (int h = 4; h > 0; h >>= 1) {
        const bool up = lane & (8 / h);
#pragma unroll
        for (int i = 0; i < h; i++)
            a[i] = (up ? a[i + h] : a[i]) + __shfl_xor_sync(0xffffffffu, up ? a[i] : a[i + h], 8 / h);
    }
    return a[0] + __shfl_xor_sync(0xffffffffu, a[0], 16);
}

__device__ __forceinline__ float ln_stats(float sum, float sq, uint32_t& mean2) {
    const float mean = sum * (1.f / D_);
    const float var = fmaxf(fmaf(-mean, mean, sq * (1.f / D_)), 0.f);
    float sd;
    asm("sqrt.approx.ftz.f32 %0, %1;" : "=f"(sd) : "f"(rbf(rbf(var) + 1e-5f)));
    mean2 = pack_bf16(mean, mean);
    return rcp_fast(rbf(sd));
}
__device__ __forceinline__ uint32_t ln_pair(uint32_t x, uint32_t mean2, float rsd) {
    const uint32_t d = bsub2(x, mean2);
    return pack_bf16(bf_lo(d) * rsd, bf_hi(d) * rsd);
}
__device__ __forceinline__ void rows_load(uint32_t (&x)[20], uint32_t xs, int cw) {
#pragma unroll
    for (int ch = 0; ch < 5; ch++) {
        const uint4 v = ldsm4(ch < 4 ? xs + ch * 256 : xs + 1024 - cw * 16);
        x[4 * ch] = v.x; x[4 * ch + 1] = v.y; x[4 * ch + 2] = v.z; x[4 * ch + 3] = v.w;
    }
}
__device__ __forceinline__ void stats_add(float (&st)[12], uint32_t a, uint32_t b, uint32_t w) {
    mma1688(st, a, b, w);
    mma1688(st + 4, a, b, a);
    mma1688(st + 8, a, b, b);
}
__device__ __forceinline__ float rows_stats(const float (&st)[12], float4* rec, int cw, int lane, uint32_t& mean2, float& dot) {
    const int g8 = lane >> 2;
    if ((g8 >> 1) == (lane & 3)) {
        rec[cw * 16 + g8] = make_float4(st[0], (g8 & 1) ? st[5] : st[4], st[1], 0.f);
        rec[cw * 16 + 8 + g8] = make_float4(st[2], (g8 & 1) ? st[11] : st[10], st[3], 0.f);
    }
    bar_sync(3, 256);
    const float4* r = rec + (lane >> 4) * 64 + (lane & 15);
    const float4 s0 = r[0], s1 = r[16], s2 = r[32], s3 = r[48];
    const float sum = (s0.x + s1.x) + (s2.x + s3.x), sq = (s0.y + s1.y) + (s2.y + s3.y);
    dot = (s0.z + s1.z) + (s2.z + s3.z);
    dot += __shfl_xor_sync(0xffffffffu, dot, 16);
    return ln_stats(sum + __shfl_xor_sync(0xffffffffu, sum, 16), sq + __shfl_xor_sync(0xffffffffu, sq, 16), mean2);
}
template <class F>
__device__ __forceinline__ void rows_normalise(uint32_t* y, const uint32_t* x, uint32_t mean2, float rsd, int lane, F loads) {
    const int g8 = lane >> 2;
    const uint32_t ma2 = __shfl_sync(0xffffffffu, mean2, g8), mb2 = __shfl_sync(0xffffffffu, mean2, g8 + 8);
    const float ra = __shfl_sync(0xffffffffu, rsd, g8), rb = __shfl_sync(0xffffffffu, rsd, g8 + 8);
    loads();
#pragma unroll
    for (int k = 0; k < 9; k++) { y[2 * k] = ln_pair(x[2 * k], ma2, ra); y[2 * k + 1] = ln_pair(x[2 * k + 1], mb2, rb); }
}

__device__ __forceinline__ uint4 h_frag(const uint4* hf, int ks, int lane) {
    if (ks < 32) return ld_relaxed2(hf + ks * 32);
    const uint2* p = reinterpret_cast<const uint2*>(padd(hf, 256 - lane * 8) + ks * 32 - 16);
    const uint2 a = ld_relaxed64(p), b = ld_relaxed64(p + 32);
    return make_uint4(a.x, a.y, b.x, b.y);
}

__device__ __noinline__ void attn_fallback(uint32_t bad, uint32_t tag, const Scratch* gs, uint8_t* frag, uint8_t* keep, const bf16* wq, const bf16* kc, const bf16* vc) {
  const int lane = threadIdx.x & 31, g8 = lane >> 2, qd = lane & 3;
  const int role = cluster_role(), j = role & 7, qb = (role >> 3) * 2 + (blockIdx.x & 1);
  const uint4* hf = g_h + (size_t)(qb * 8 + (threadIdx.x >> 5) - 4) * (36 * 32) + lane;
#pragma unroll 1
  for (int t = 0; t < 4; t++) {
    if (!((bad >> t) & 1)) continue;
    const bf16 *wqp = wq + (4 * j + t) * DH, *kp = kc + (size_t)(2 * j + (t >> 1)) * S_ * DH, *vp = vc + (size_t)(2 * j + (t >> 1)) * S_ * DH;
    uint32_t q[32];
    float o[64];
#pragma unroll
    for (int i = 0; i < 64; i++) o[i] = 0.f;
#pragma unroll 1
    for (int ks = 0; ks < 36; ks++) {
        const uint4 a = h_frag(hf, ks, lane);
        const unsigned short* wr = reinterpret_cast<const unsigned short*>(wqp + (size_t)(ks * 16 + 2 * qd) * QD + g8);
#pragma unroll
        for (int dt = 0; dt < 16; dt++) {
            const uint32_t b0 = __ldg(wr + dt * 8) | ((uint32_t)__ldg(wr + dt * 8 + QD) << 16);
            const uint32_t b1 = __ldg(wr + dt * 8 + 8 * QD) | ((uint32_t)__ldg(wr + dt * 8 + 9 * QD) << 16);
            mma16816(o + 4 * dt, a.x, a.y, a.z, a.w, b0, b1);
        }
    }
#pragma unroll
    for (int i = 0; i < 32; i++) q[i] = pack_bf16(o[2 * i], o[2 * i + 1]);
#pragma unroll
    for (int i = 0; i < 64; i++) o[i] = 0.f;
    float m0 = -INFINITY, m1 = -INFINITY, l0 = 0.f, l1 = 0.f;
#pragma unroll 1
    for (int key = 0; key < S_; key += 16) {
        float sc[8];
#pragma unroll
        for (int i = 0; i < 8; i++) sc[i] = 0.f;
#pragma unroll
        for (int nt = 0; nt < 2; nt++) {
            const uint32_t* kr = reinterpret_cast<const uint32_t*>(kp + (size_t)(key + nt * 8 + g8) * DH) + qd;
#pragma unroll
            for (int ks = 0; ks < 8; ks++)
                mma16816(sc + 4 * nt, q[4 * ks], q[4 * ks + 1], q[4 * ks + 2], q[4 * ks + 3], __ldg(kr + ks * 8), __ldg(kr + ks * 8 + 4));
        }
        const float n0 = quad_max(fmaxf(fmaxf(m0, fmaxf(sc[0], sc[1])), fmaxf(sc[4], sc[5])));
        const float n1 = quad_max(fmaxf(fmaxf(m1, fmaxf(sc[2], sc[3])), fmaxf(sc[6], sc[7])));
        const float f0 = ex2((m0 - n0) * CS), f1 = ex2((m1 - n1) * CS);
        m0 = n0; m1 = n1;
#pragma unroll
        for (int i = 0; i < 8; i++) sc[i] = ex2((sc[i] - ((i & 2) ? n1 : n0)) * CS);
        l0 = l0 * f0 + (sc[0] + sc[1]) + (sc[4] + sc[5]);
        l1 = l1 * f1 + (sc[2] + sc[3]) + (sc[6] + sc[7]);
        const uint32_t e0 = pack_bf16(sc[0], sc[1]), e1 = pack_bf16(sc[2], sc[3]), e2 = pack_bf16(sc[4], sc[5]), e3 = pack_bf16(sc[6], sc[7]);
        const unsigned short* vr = reinterpret_cast<const unsigned short*>(vp + (size_t)(key + 2 * qd) * DH + g8);
#pragma unroll
        for (int dt = 0; dt < 16; dt++) {
            o[4 * dt] *= f0; o[4 * dt + 1] *= f0; o[4 * dt + 2] *= f1; o[4 * dt + 3] *= f1;
            const uint32_t b0 = __ldg(vr + dt * 8) | ((uint32_t)__ldg(vr + dt * 8 + DH) << 16);
            const uint32_t b1 = __ldg(vr + dt * 8 + 8 * DH) | ((uint32_t)__ldg(vr + dt * 8 + 9 * DH) << 16);
            mma16816(o + 4 * dt, e0, e1, e2, e3, b0, b1);
        }
    }
    const float i0 = 1.f / quad_sum(l0), i1 = 1.f / quad_sum(l1);
#pragma unroll
    for (int i = 0; i < 16; i++) {
        q[2 * i] = pack_bf16(o[4 * i] * i0, o[4 * i + 1] * i0);
        q[2 * i + 1] = pack_bf16(o[4 * i + 2] * i1, o[4 * i + 3] * i1);
    }
    frag_store(t < 3 ? frag + t * 4096 : keep, q);
  }
}

__device__ __forceinline__ void spare_q3(Scratch* gs, uint32_t sb, uint32_t bar_full, uint32_t bar_empty, int lane, int cw) {
    const uint32_t tag = load_tag(gs);
    uint32_t rel_base, e = 3;
    asm("mapa.shared::cluster.u32 %0, %1, %2;" : "=r"(rel_base) : "r"(bar_empty), "r"(lane & 1));
#pragma unroll 1
    for (int qb = blockIdx.x - NCTA; qb < 16; qb += 4) {
        uint32_t h[144];
        float o[64];
        flag_wait(&g_flag_h[(qb * 8 + cw) * 32], tag);
        const uint4* hf = g_h + (size_t)(qb * 8 + cw) * (36 * 32) + lane;
#pragma unroll
        for (int ks = 0; ks < 36; ks++) {
            const uint4 v = h_frag(hf, ks, lane);
            h[4 * ks] = v.x; h[4 * ks + 1] = v.y; h[4 * ks + 2] = v.z; h[4 * ks + 3] = v.w;
        }
#pragma unroll
        for (int i = 0; i < 64; i++) o[i] = 0.f;
#pragma unroll 1
        for (int v = 0; v < 4; v++) {
            fence_regs(o);
#pragma unroll
            for (int t = 0; t < 5; t++) {
                mbar_wait(bar_full + 8 * (e & 3), (e >> 2) & 1);
                uint64_t dv = mkdesc(sb + (e & 3) * SLOT, UNIT, 1024);
                WG_FENCE();
#pragma unroll
                for (int ks = 0; ks < (t < 4 ? 8 : 4); ks++)
                    mma_rs128<1>(o, h[32 * t + 4 * ks], h[32 * t + 4 * ks + 1], h[32 * t + 4 * ks + 2], h[32 * t + 4 * ks + 3], dv, ks | t);
                WG_COMMIT();
                if (t > 0) { WG_WAIT(1); if (lane < 2) mbar_arrive_cluster(rel_base + 8 * ((e - 1) & 3)); }
                e++;
            }
            WG_WAIT(0);
            fence_regs(o);
            if (lane < 2) mbar_arrive_cluster(rel_base + 8 * ((e - 1) & 3));
            uint4* dst = &g_q3[((qb * 8 + 2 * v) * 8 + cw) * 128 + lane];
#pragma unroll
            for (int i = 0; i < 8; i++)
                __stcg(dst + (i >> 2) * 1024 + (i & 3) * 32, make_uint4(pack_bf16(o[8 * i], o[8 * i + 1]), pack_bf16(o[8 * i + 2], o[8 * i + 3]),
                                                                        pack_bf16(o[8 * i + 4], o[8 * i + 5]), pack_bf16(o[8 * i + 6], o[8 * i + 7])));
        }
        bar_sync(3, 256);
        if (cw == 0 && lane == 0) flag_release(&g_flag_q3[qb * 32], tag);
        __syncwarp();
    }
}

template <bool SPARE>
__global__ void __cluster_dims__(2, 1, 1) __launch_bounds__(384, 1)
fused_kernel(const Args args, const __grid_constant__ CUtensorMap tm_wq,
             const __grid_constant__ CUtensorMap tm_k, const __grid_constant__ CUtensorMap tm_v,
             const __grid_constant__ CUtensorMap tm_wo, const __grid_constant__ CUtensorMap tm_p,
             const __grid_constant__ CUtensorMap tm_x, const __grid_constant__ CUtensorMap tm_d,
             const __grid_constant__ CUtensorMap tm_g, const __grid_constant__ CUtensorMap tm_u) {
    extern __shared__ __align__(1024) uint8_t smem_raw[];
    const uint32_t sb = smem_u32(smem_raw);
    Scratch* const gs = args.gs;
    const uint32_t bar_full = sb + SM_BAR;
    const uint32_t bar_g = bar_full + 8 * 4;
    const uint32_t bar_mod = bar_g + 8;
    const uint32_t bar_go = bar_mod + 8;
    const uint32_t bar_x = bar_go + 40;
    const uint32_t bar_empty = bar_x + 8;
    const uint32_t bar_pub = bar_empty + 8 * 4;
    const uint32_t bar_qfree = bar_pub + 32;
    const uint32_t bar_out = bar_qfree + 24;
    const uint32_t bar_q3 = bar_out + 8;
    const uint32_t bar_pre = bar_q3 + 16;
    const uint32_t bar_w0 = bar_q3 + 8;
    constexpr int E0 = SPARE ? 2 : 0;

    const int c = blockIdx.x & 1;
#define ROLES() const int role = cluster_role(), j = role & 7, qb = (role >> 3) * 2 + c, rg = qb * 8 + j
    const int warp = __shfl_sync(0xffffffffu, threadIdx.x >> 5, 0);

    if (SPARE && blockIdx.x >= NCTA && warp >= 4) {
        asm volatile("barrier.cluster.arrive.relaxed.aligned;" ::: "memory");
        asm volatile("setmaxnreg.inc.sync.aligned.u32 240;");
        asm volatile("barrier.cluster.wait.aligned;" ::: "memory");
        spare_q3(gs, sb, bar_full, bar_empty, threadIdx.x & 31, warp - 4);
        asm volatile("barrier.cluster.arrive.relaxed.aligned;\nbarrier.cluster.wait.aligned;" ::: "memory");
    } else if (warp < 4) {
        asm volatile("setmaxnreg.dec.sync.aligned.u32 24;");
        ROLES();
        int lane;
        asm volatile("mov.u32 %0, %%laneid;" : "=r"(lane));
        if (warp == 2 && elect()) {
            if (TMPF) asm volatile("prefetch.tensormap [%0];" ::"l"(&tm_x) : "memory");
#pragma unroll
            for (int i = 0; i < 27; i++) mbar_init(bar_full + 8 * i, i < 12 || i >= 23 ? 1 : i < 16 ? 16 : 8);
#pragma unroll
            for (int i = 0; i <= E0; i++) {
                mbar_arrive(bar_full + 8 * i);
                asm volatile("mbarrier.arrive.shared::cta.b64 _, [%0], 16;" ::"r"(bar_empty + 8 * i) : "memory");
            }
            asm volatile("fence.mbarrier_init.release.cluster;" ::: "memory");
        }
        __syncwarp();
        asm volatile("barrier.cluster.arrive.relaxed.aligned;" ::: "memory");
        if (warp == 2 && !(SPARE && blockIdx.x >= NCTA)) {
            if (XDELAY) __nanosleep(XDELAY);
            if (elect()) {
                mbar_expect_tx(bar_x, 16 * XP);
                tma2d(sb + SM_Q, &tm_x, 0, rg * 16, bar_x);
            }
            __syncwarp();
        }
        asm volatile("barrier.cluster.wait.aligned;" ::: "memory");
        const uint32_t tag = load_tag(gs);
        if (SPARE && blockIdx.x >= NCTA) {
            if (warp == 1) {
#pragma unroll 1
                for (int e = 3; e < 83; e++) {
                    const int v = (e - 3) / 5;
                    mbar_wait_sleep(bar_empty + 8 * (e & 3), ~(e >> 2) & 1);
                    if (elect()) {
                        mbar_expect_tx(bar_full + 8 * (e & 3), SLOT);
                        tma2d_mc(sb + (e & 3) * SLOT + c * UNIT, &tm_wq, (8 * (v & 3) + 4 * c + 3) * DH + 64, (e - 3 - v * 5) * 128,
                                 bar_full + 8 * (e & 3), EVICT_NORMAL);
                    }
                }
            }
            __syncwarp();
            asm volatile("barrier.cluster.arrive.relaxed.aligned;\nbarrier.cluster.wait.aligned;" ::: "memory");
            return;
        }
        if (warp == 3) {
#pragma unroll 1
            for (int e = 4; e < 20; e++) {
                __nanosleep(e == 4 ? PFD0 : PFD1);
                const int hd = (e * 52) >> 8, row = (e - hd * 5) * 128 + qb * 8 + (lane >> 1);
                if (lane < 16 && row < D_)
                    asm volatile("prefetch.global.L2 [%0];" ::"l"(padd(args.wq, (row * QD + (4 * j + ((0x1320 >> (4 * hd)) & 3)) * DH + (lane & 1) * 64) * 2)) : "memory");
            }
            __syncwarp();
            mbar_wait_sleep(bar_go, 0);
#pragma unroll 1
            for (int unit = 72 + blockIdx.x; unit < 216; unit += NCTA) {
                float a[8];
#pragma unroll
                for (int i = 0; i < 8; i++) a[i] = 0.f;
#pragma unroll 1
                for (int k = lane >> 1; k < D_; k += 16) {
                    const float cv = __bfloat162float(*padd(args.cvec, k * 2));
                    mod_fma(a, __ldg(reinterpret_cast<const uint4*>(padd(args.w_mod, (k * (6 * D_) + unit * 16 + (lane & 1) * 8) * 2))), rbf(cv * sigmoidf_(cv)));
                }
                const float v = mod_reduce(a, lane), v1 = __shfl_down_sync(0xffffffffu, v, 8);
                if (lane < 8) *padd(gs->mod2, ((unit - 72) * 8 + (lane & 1) * 4 + (lane & 2) + (lane >> 2)) * 4) = pack_bf16(v, v1);
            }
            __syncwarp();
            if (lane == 0) flag_release(padd(g_flag_mod, blockIdx.x * 4), tag);
#pragma unroll 1
            for (int k = 0; k < 36; k++) {
                __nanosleep(200);
                __stcg(padd(gs->h[0], (~tag & 1) * (NCTA * 36 * 512) + ((rg * 36 + k) * 32 + lane) * 16), make_uint4(0, 0, 0, 0));
            }
            __syncwarp();
            mbar_wait_sleep(bar_qfree + 16, 0);
            __nanosleep(2000);
            {
                uint4 v;
                uint32_t it = 0;
#pragma unroll 1
                do {
                    v = ld_relaxed(reinterpret_cast<const uint4*>(padd(g_flag_mod, lane * 16)));
                } while (((v.x ^ tag) | (v.y ^ tag) | (v.z ^ tag) | (v.w ^ tag)) && ++it < SPIN / 16);
                asm volatile("fence.acquire.gpu;" ::: "memory");
            }
            __syncwarp();
            {
                float w1 = 0.f, w2 = 0.f;
#pragma unroll 1
                for (int k = lane; k < D_ / 2; k += 32) {
                    const uint32_t* mp = padd(gs->mod2, k * 4);
                    const uint32_t sv = __ldcg(mp + D_ / 2), c1 = badd2(__ldcg(mp + D_), 0x3f803f80u);
                    const uint32_t wr = *reinterpret_cast<const uint32_t*>(padd(args.w_r, k * 4)), wp = bmul2(c1, wr);
                    reinterpret_cast<uint2*>(smem_raw + SM_T)[k] = make_uint2(__ldcg(mp), wp);
                    reinterpret_cast<uint2*>(smem_raw + SM_TC)[k] = make_uint2(c1, sv);
                    reinterpret_cast<uint32_t*>(smem_raw + SM_TG)[k] = __ldcg(mp + 3 * D_ / 2);
                    w1 += bf_lo(wp) + bf_hi(wp);
                    w2 += bf_lo(sv) * bf_lo(wr) + bf_hi(sv) * bf_hi(wr);
                }
#pragma unroll 1
                for (int i = 1; i < 32; i <<= 1) { w1 += __shfl_xor_sync(0xffffffffu, w1, i); w2 += __shfl_xor_sync(0xffffffffu, w2, i); }
                *reinterpret_cast<float2*>(smem_raw + SM_TS) = make_float2(w1, w2);
            }
#pragma unroll
            for (int i = 0; i < 4; i++) reinterpret_cast<uint4*>(smem_raw + SM_RED)[lane + 32 * i] = make_uint4(~0u, ~0u, ~0u, ~0u);
            asm volatile("fence.proxy.async.shared::cta;" ::: "memory");
            __syncwarp();
            if (elect()) {
                uint8_t* mb = g_frag + (size_t)rg * 8 * WREG + 3 * 4096;
#pragma unroll 1
                for (int k = 0; k < 8; k++, mb += WREG) {
#pragma unroll
                    for (int i = 0; i < 3; i++)
                        asm volatile("cp.async.bulk.global.shared::cta.bulk_group [%0], [%1], 2048;" ::"l"(mb + i * 2048), "r"(sb + SM_RED) : "memory");
                    __nanosleep(500);
                }
                asm volatile("cp.async.bulk.commit_group;\ncp.async.bulk.wait_group 0;\nfence.proxy.async.global;" ::: "memory");
            }
            __syncwarp();
            if (lane == 0) mbar_arrive(bar_mod);
            __syncwarp();
            mbar_wait_sleep(bar_go + 8, 0);
            if (elect()) asm volatile("prefetch.tensormap [%0];\nprefetch.tensormap [%1];\nprefetch.tensormap [%2];" ::"l"(&tm_x), "l"(&tm_p), "l"(&tm_d) : "memory");
            __syncwarp();
#pragma unroll 1
            for (int i = 1; i < 4; i++) {
                mbar_wait(bar_pub + 8 * i, 0);
                unsigned int* flags = padd(g_flag_part, (qb * 32 + i * 8 - 8) * 4);
                if (elect()) { flag_release(padd(flags, j * 4), tag); DBG_PG(93); }
                __syncwarp();
                const uint32_t slot = i < 3 ? i + 1 : 1;
                flag_wait(padd(flags, (lane & 7) * 4), tag);
                asm volatile("fence.proxy.async.global;" ::: "memory");
                if (lane == 0 && i == 3) DBG_PG(101);
                mbar_wait(bar_go + 8 + 8 * i, 0);
                mbar_wait(bar_empty + 8 * slot, i != 1);
                if (elect()) {
                    mbar_expect_tx(bar_full + 8 * slot, SLOT);
                    tma3d(sb + slot * SLOT, &tm_p, 0, j * 20 + (i - 1) * 4, qb * 8, bar_full + 8 * slot);
                    tma3d(sb + slot * SLOT + UNIT, &tm_p, 0, j * 20 + (i - 1) * 4 + 2, qb * 8, bar_full + 8 * slot);
                }
            }
        } else if (warp == 0) {
#pragma unroll 1
            for (int i = 0; i < 48; i++) {
                if (i == 0 || i == 17 || i == 34) mbar_wait_sleep(bar_qfree + (i >> 4) * 8, 0);
                if (SPARE && i == 17) {
                    flag_wait(&g_flag_q3[qb * 32], tag);
                    if (elect()) {
                        asm volatile("fence.proxy.async.global;" ::: "memory");
                        mbar_expect_tx(bar_q3, UNIT);
#pragma unroll 1
                        for (int k = 0; k < 8; k++) bulk_load(sb + SM_Q + 2 * SLOT + k * 4096 + 2048, &g_q3[(rg * 8 + k) * 128], 2048, bar_q3);
                    }
                }
                __nanosleep(700);
                if (elect()) {
                    asm volatile("mbarrier.expect_tx.shared::cta.b64 [%0], %1;" ::"r"(bar_g), "n"(1920) : "memory");
                    tma2d(sb + SM_Q + i * 1920, i < 24 ? &tm_g : &tm_u, (blockIdx.x * 36) & ~7, (i < 24 ? i : i - 24) * 24, bar_g);
                }
            }
            if (elect()) mbar_arrive(bar_g);
#pragma unroll 1
            for (int i = 0; i < 18; i++) {
                __nanosleep(400);
                if (elect()) l2_prefetch(args.w_down + (size_t)(blockIdx.x * 36 + i * 2) * D_, 4 * D_);
            }
            __syncwarp();
            mbar_wait_sleep(bar_go + 8 * 2, 0);
            uint32_t acc = 0;
#pragma unroll 1
            for (int k = lane; k < 16 * 9; k += 32) acc |= touch(padd(args.x, (rg * 16 * D_ + k * 64) * 2));
            if (acc == 0) reinterpret_cast<volatile uint32_t*>(smem_raw + SM_BAR)[127] = acc;
            __syncwarp();
            mbar_wait_sleep(bar_go + 8 * 4, 0);
            uint4* rp = padd(g_rows, (rg * 2 * RSLOT + lane) * 16);
#pragma unroll
            for (int k = 0; k < 12; k++) rp[k * 32] = make_uint4(~0u, ~0u, ~0u, ~0u);
            if (blockIdx.x < 72) {
                uint4* yp = reinterpret_cast<uint4*>(padd(g_ypart, blockIdx.x * NCTA * 64 + lane * 16));
#pragma unroll
                for (int k = 0; k < 16; k++) yp[k * 32] = make_uint4(~0u, ~0u, ~0u, ~0u);
            }
            asm volatile("fence.acq_rel.gpu;" ::: "memory");
            __syncwarp();
            if (lane == 0) mbar_arrive(bar_pre);
        } else if (warp == 1) {
            __nanosleep(QDELAY);
            uint32_t go = bar_go;
            uint64_t marks = 24 | 151 << 8 | 154 << 16 | 159ull << 24 | 165ull << 32;
#pragma unroll 1
            for (int e = E0; e < 168; e++) {
                const CUtensorMap* tm;
                int c0, c1;
                uint64_t pol = EVICT_FIRST;
                if (e == 158 || e == 163) continue;
                if (e < 21 && e != 19) {
                    const int i = SPARE && e < 12 ? e - 2 : e - (e == 20), hd = (i * 52) >> 8;
                    tm = &tm_wq; c0 = (4 * j + ((0x1320 >> (4 * hd)) & 3)) * DH + c * 64; c1 = (i - hd * 5) * 128 - 64;
                    if (SPARE && e >= 12 && e < 15) { c0 = (4 * j + 3) * DH; c1 = (2 * (e - 12) + c) * 128; }
                } else if (e < 148) {
                    const int i = max(e - 20, 0);
                    const bool isk = i == 0 || ((i & 1) && i < 127);
                    const int n = isk ? (i + 1) >> 1 : (i - 1) >> 1;
                    tm = isk ? &tm_k : &tm_v; c0 = c * 64; c1 = (2 * j + (n >> 5)) * S_ + (n & 15) * 128;
                    if (!(i & 32)) pol = EVICT_NORMAL;
                } else {
                    int i = e - 148 - (e > 158) - (e > 163);
                    tm = &tm_wo; c0 = (i >> 1) * 64; c1 = (4 * j + ((i & 1) ? 1 + c : 3 * c)) * DH;
                }
                const uint32_t fb = e == E0 ? bar_w0 : bar_full + 8 * (e & 3), d = sb + (e == E0 ? 6 : e & 3) * SLOT;
                if (e >= 24 && e < 152) mbar_wait_sleep(bar_empty + 8 * (e & 3), ~(e >> 2) & 1);
                else if (e != E0) mbar_wait(bar_empty + 8 * (e & 3), ~(e >> 2) & 1);
                if (elect()) {
                    mbar_expect_tx(fb, SLOT);
                    tma2d_mc(d + c * UNIT, tm, c0, c1, fb, pol);
                    const int i = e - PF_KV;
                    if (i >= 0 && i < 128 && !(i & 32))
                        l2_prefetch(((i & 1) ? args.vc : args.kc) + (size_t)((2 * j + (i >> 6)) * S_ + (i & 30) * 64) * DH + qb * 1024, 2048);
                    if (e >= PF_WO && e < PF_WO + 18) l2_prefetch(args.wo + (size_t)blockIdx.x * (QD * D_ / NCTA) + (e - PF_WO) * 1024, 2048);
                    if (e == (marks & 255)) mbar_arrive(go);
                }
                if (e == (marks & 255)) { go += 8; marks >>= 8; }
            }
            asm volatile("fence.proxy.async.global;" ::: "memory");
            mbar_wait(bar_empty, 1);
            if (elect()) {
                mbar_expect_tx(bar_full, 16 * XP);
                tma2d(sb, &tm_x, 0, rg * 16, bar_full);
            }
            mbar_wait(bar_empty + 16, 1);
            if (C3D) __nanosleep(C3D);
            if (elect()) {
                mbar_expect_tx(bar_full + 16, SLOT);
                tma3d(sb + 2 * SLOT, &tm_p, 0, j * 20 + 12, qb * 8, bar_full + 16);
                tma3d(sb + 2 * SLOT + UNIT, &tm_p, 0, j * 20 + 14, qb * 8, bar_full + 16);
            }
            mbar_wait(bar_empty + 24, 1);
            if (C4D) __nanosleep(C4D);
            if (elect()) {
                mbar_expect_tx(bar_full + 24, UNIT);
                tma3d(sb + 3 * SLOT, &tm_p, 0, j * 20 + 16, qb * 8, bar_full + 24);
            }
            mbar_wait(bar_empty + 8, 0);
            mbar_wait(bar_empty + 16, 0);
            if (DD) __nanosleep(DD);
            if (elect()) {
#pragma unroll
                for (int i = 1; i < 3; i++) {
                    mbar_expect_tx(bar_full + 8 * i, 18 * XP);
                    tma2d(sb + i * SLOT, &tm_d, 0, blockIdx.x * 36 + (i - 1) * 18, bar_full + 8 * i);
                }
            }
        } else {
            if (elect()) asm volatile("prefetch.tensormap [%0];\nprefetch.tensormap [%1];\nprefetch.tensormap [%2];" ::"l"(&tm_k), "l"(&tm_v), "l"(&tm_wo) : "memory");
            if (SPARE) {
                mbar_wait_sleep(bar_pub, 0);
                if (lane == 0) flag_release(padd(g_flag_h, rg * 128), tag);
                __syncwarp();
            }
            bar_sync(1, 192);
#pragma unroll 1
            for (uint32_t e = 20; e < 148; e++) {
                mbar_wait_sleep(bar_full + 8 * (e & 3), (e >> 2) & 1);
                if (e & 1) bar_sync(1, 192);
                if (!(e & 1) || e == 147) bar_sync(4, 160);
            }
#pragma unroll 1
            for (uint32_t e = 148; e < 168; e++) {
                mbar_wait(bar_full + 8 * (e & 3), (e >> 2) & 1);
                if (e != 158 && e != 163) bar_sync(1, 192);
            }
        }
        __syncwarp();
        mbar_wait_sleep(bar_out, 0);
        if (OUTD) __nanosleep(OUTD);
        if (elect()) {
            asm volatile("fence.proxy.async.shared::cta;" ::: "memory");
            const int2 sel = reinterpret_cast<const int2*>(smem_raw + SM_RED)[8];
#pragma unroll 1
            for (int i = warp; i < 16; i += 4) {
                const int row = rg * 16 + i;
                if (row != sel.x && row != sel.y)
                    asm volatile("cp.async.bulk.global.shared::cta.bulk_group.L2::cache_hint [%0], [%1], %2, %3;"
                                 ::"l"(args.out + (size_t)row * D_), "r"(sb + i * XP), "n"(D_ * 2), "l"(OUTPOL) : "memory");
            }
            asm volatile("cp.async.bulk.commit_group;\ncp.async.bulk.wait_group.read 0;" ::: "memory");
        }
    } else {
        uint32_t cv[2] = {0, 0}, tag = load_tag(gs) - 1;
        if (blockIdx.x < 72) {
            uint32_t ws;
            int tid;
            asm volatile("mov.u32 %0, smem_raw;\nmov.u32 %1, %%tid.x;" : "=r"(ws), "=r"(tid));
            tid -= 128;
            ws += SM_Q + SLOT + tid * 16;
            const uint32_t* cp = padd(reinterpret_cast<const uint32_t*>(args.cvec), (tid & 0xe0) + (tid & 7) * 4);
            cv[0] = *padd(cp, (tid & 24) * 32);
            if (tid < 128) cv[1] = cp[256];
            const bf16* wrow = args.w_mod + (size_t)(tid >> 1) * (6 * D_) + (tid & 1) * 8 + blockIdx.x * 16;
#pragma unroll
            for (int i = 0; i < 5; i++)
                if (i < 4 || tid < 128)
                    asm volatile("cp.async.cg.shared.global [%0], [%1], 16;" ::"r"(ws + i * 4096), "l"(wrow + (size_t)i * 128 * (6 * D_)) : "memory");
        }
        asm volatile("barrier.cluster.arrive.relaxed.aligned;" ::: "memory");
        asm volatile("setmaxnreg.inc.sync.aligned.u32 240;");
        const int lane = threadIdx.x & 31;
        const int cw = warp - 4;
        const int w = cw >> 2;
        const int tid = threadIdx.x - 128;
        ROLES();
        float* red = reinterpret_cast<float*>(smem_raw + SM_RED);
        DBG_INIT();
        DBG_G(120);
        DBG_T(100);

        {
            if (blockIdx.x < 72) {
                uint32_t sa[10];
#pragma unroll
                for (int i = 0; i < 2; i++) {
                    const float lo = bf_lo(cv[i]), hi = bf_hi(cv[i]);
                    cv[i] = pack_bf16(lo * sigmoidf_(lo), hi * sigmoidf_(hi));
                }
#pragma unroll
                for (int i = 0; i < 10; i++) sa[i] = __shfl_sync(0xffffffffu, cv[i >> 3], (i & 7) * 4 + (lane & 3));
                uint2* mdst = &gs->mod1[(tid >> 3) * D_ + blockIdx.x * 8 + (tid & 7)];
                anchor(bar_full + 504, sa[0] & sa[1] & sa[2] & sa[3] & sa[4] & sa[5] & sa[6] & sa[7] & sa[8] & sa[9] & (uint32_t)(uintptr_t)mdst & (uint32_t)((uintptr_t)mdst >> 32));
                asm volatile("cp.async.wait_all;" ::: "memory");
                __syncwarp();
                const uint32_t ws = sb + SM_Q + SLOT + cw * 512 + (lane & 15) * 32 + (lane & 16);
                float d[16];
#pragma unroll
                for (int i = 0; i < 16; i++) d[i] = 0.f;
#pragma unroll
                for (int i = 0; i < 5; i++) {
                    const uint4 b = ldsm4t(ws + (i < 4 || cw < 4 ? i * 4096 : 0));
                    mma16816(d + 8 * (i & 1), sa[2 * i], sa[2 * i], sa[2 * i + 1], sa[2 * i + 1], b.x, b.y);
                    mma16816(d + 8 * (i & 1) + 4, sa[2 * i], sa[2 * i], sa[2 * i + 1], sa[2 * i + 1], b.z, b.w);
                }
                if (lane < 8) reinterpret_cast<float2*>(red)[lane * 8 + cw] = (lane & 4) ? make_float2(d[4] + d[12], d[5] + d[13]) : make_float2(d[0] + d[8], d[1] + d[9]);
                bar_sync(3, 256);
                if (tid < 8 * MREP) {
                    const float4* r = reinterpret_cast<const float4*>(red) + (tid & 7) * 4;
                    const float4 r0 = r[0], r1 = r[1], r2 = r[2], r3 = r[3];
                    st_relaxed64(mdst, pack_bf16(((r0.x + r0.z) + (r1.x + r1.z)) + ((r2.x + r2.z) + (r3.x + r3.z)),
                                                 ((r0.y + r0.w) + (r1.y + r1.w)) + ((r2.y + r2.w) + (r3.y + r3.w))), tag + 1);
                }
            }
            DBG_G(106);
            asm volatile("barrier.cluster.wait.aligned;" ::: "memory");
            mbar_wait(bar_x, 0);
            asm volatile("add.u32 %0, %0, 1;" : "+r"(tag));
            uint32_t x[20];
            float st[12], st2[12];
            rows_load(x, sb + SM_Q + (lane & 15) * XP + (lane >> 4) * 16 + cw * 32, cw);
#pragma unroll
            for (int i = 0; i < 12; i++) { st[i] = 0.f; st2[i] = 0.f; }
#pragma unroll
            for (int k = 0; k < 9; k++) stats_add((k & 1) ? st2 : st, x[2 * k], x[2 * k + 1], 0x3f803f80u);
#pragma unroll
            for (int i = 0; i < 12; i++) st[i] += st2[i];
            uint32_t mean2;
            float dot;
            const float rsd = rows_stats(st, reinterpret_cast<float4*>(red + 128), cw, lane, mean2, dot);
            const uint4* mp = reinterpret_cast<const uint4*>(gs->mod1 + ((blockIdx.x >> 1) & (MREP - 1)) * D_) + min(tid, D_ / 4 - 1);
            uint4 v0 = make_uint4(0, tag, 0, tag), v1 = v0;
            auto look = [&]() {
                asm volatile("{\n.reg .pred p;\n.reg .b64 a, b, c, d;\nsetp.lt.s32 p, %9, 5;\nmov.b64 a, {%0, %1};\nmov.b64 b, {%2, %3};\n"
                             "mov.b64 c, {%4, %5};\nmov.b64 d, {%6, %7};\n@p ld.relaxed.gpu.global.v2.b64 {a, b}, [%8];\n"
                             "@p ld.relaxed.gpu.global.v2.b64 {c, d}, [%8 + 2304];\n"
                             "mov.b64 {%0, %1}, a;\nmov.b64 {%2, %3}, b;\nmov.b64 {%4, %5}, c;\nmov.b64 {%6, %7}, d;\n}"
                             : "+r"(v0.x), "+r"(v0.y), "+r"(v0.z), "+r"(v0.w), "+r"(v1.x), "+r"(v1.y), "+r"(v1.z), "+r"(v1.w)
                             : "l"(mp), "r"(cw) : "memory");
            };
            rows_normalise(x, x, mean2, rsd, lane, look);
            fence_regs(x);
            uint32_t it = 0;
#pragma unroll 1
            while (((v0.y ^ tag) | (v0.w ^ tag) | (v1.y ^ tag) | (v1.w ^ tag)) && ++it < SPIN / 16) look();
            uint4* smod = reinterpret_cast<uint4*>(smem_raw + SM_Q + M_MOD);
            if (tid < D_ / 4) smod[tid] = make_uint4(badd2(v1.x, 0x3f803f80u), v0.x, badd2(v1.z, 0x3f803f80u), v0.z);
            uint4* hdst = g_h + (size_t)(rg * 36 + cw) * 32 + lane;
            uint2* hdst2 = reinterpret_cast<uint2*>(g_h + (size_t)(rg * 36 + 32) * 32) + tid;
            bar_sync(3, 256);
            DBG_G(107);
#pragma unroll
            for (int k = 0; k < 9; k++) {
                const uint2 cs = lds64(sb + SM_Q + M_MOD + (cw * 8 + (lane & 3) + (k < 8 ? (k >> 1) * 64 + (k & 1) * 4 : 256 - cw * 4)) * 8);
                const uint32_t c1 = cs.x, sa = cs.y;
                x[2 * k] = badd2(bmul2(x[2 * k], c1), sa);
                if (x[2 * k] == 0) x[2 * k] = 0x8000u;
                x[2 * k + 1] = badd2(bmul2(x[2 * k + 1], c1), sa);
            }
#pragma unroll
            for (int ch = 0; ch < 4; ch++) st_relaxed4(hdst + ch * 256, x[4 * ch], x[4 * ch + 1], x[4 * ch + 2], x[4 * ch + 3]);
            st_relaxed64(hdst2, x[16], x[17]);
            __syncwarp();
            if (SPARE && lane == 0) mbar_arrive(bar_pub);
            DBG_G(108);
        }

        uint32_t rel_base;
        asm("mapa.shared::cluster.u32 %0, %1, %2;" : "=r"(rel_base) : "r"(bar_empty), "r"(lane & 1));
        auto release = [&](uint32_t slot) { if (lane < 2) mbar_arrive_cluster(rel_base + 8 * slot); };
        uint32_t q[32], p[32];
        float s[64], o[64];

        uint4* qpark = reinterpret_cast<uint4*>(smem_raw + SM_Q - SLOT) + cw * 256 + lane;
        {
            uint32_t h[144];
            const uint4* hf = g_h + (size_t)(qb * 8 + cw) * (36 * 32) + lane;
            auto load_h = [&](auto lo, auto hi) {
#pragma unroll
                for (int ks = lo.value; ks < hi.value; ks++) {
                    const uint4 v = h_frag(hf, ks, lane);
                    h[4 * ks] = v.x; h[4 * ks + 1] = v.y; h[4 * ks + 2] = v.z; h[4 * ks + 3] = v.w;
                }
            };
            auto check_h = [&](auto lo, auto hi) {
                uint32_t it = 0;
                bool miss;
#pragma unroll 1
                do {
                    uint32_t mn = ~0u;
#pragma unroll
                    for (int ks = lo.value; ks < hi.value; ks++) mn = __vimin3_u32(mn, h[4 * ks], h[4 * ks + 2]);
                    miss = __any_sync(0xffffffffu, mn == 0);
                    if (miss) load_h(lo, hi);
                    asm volatile("add.u32 %0, %0, 1;" : "+r"(it));
                } while (miss && it < SPIN / 16);
            };
            __nanosleep(HDELAY);
            load_h(IC<0>{}, IC<4>{});
            DBG_T(104); DBG_G(109);
#pragma unroll
            for (int i = 0; i < 64; i++) o[i] = 0.f;
            uint32_t e = E0;
#pragma unroll 1
            for (int hd = 1;; hd++) {
                fence_regs(o);
                auto group = [&](auto tc) {
                    constexpr int t = tc.value, k0 = t ? 8 * t - 4 : 0;
                    const bool first = t == 0 && hd == 1;
                    mbar_wait(first ? bar_w0 : bar_full + 8 * (e & 3), (e >> 2) & 1);
                    uint64_t dv = args.d0 + ((t ? 0 : 512) + (first ? 6 : e & 3) * (SLOT / 16));
                    if (hd == 1) check_h(IC<k0>{}, IC<8 * t + 4>{});
                    WG_FENCE();
#pragma unroll
                    for (int ks = k0; ks < 8 * t + 4; ks++)
                        mma_rs128<1>(o, h[4 * ks], h[4 * ks + 1], h[4 * ks + 2], h[4 * ks + 3], dv, ks);
                    WG_COMMIT();
                    if (hd == 1) { if (t == 0) {   } if (t == 1) {   } if (t == 2) {   } if (t == 3) {   } if (t == 4) {   } }
                    if (t < 4 && hd == 1) load_h(IC<8 * t + 4>{}, IC<t < 4 ? 8 * t + 12 : 0>{});
                    if (t > 0) { WG_WAIT(1); if (t > 1 || hd > 1) release((e - 1) & 3); }
                    e++;
                };
                group(IC<0>{}); group(IC<1>{}); group(IC<2>{}); group(IC<3>{});
                if (e == 19) break;
                group(IC<4>{});
                WG_WAIT(0);
                if (hd == 1) {     }
                fence_regs(o);
                release((e - 1) & 3);
#pragma unroll
                for (int i = 0; i < 8; i++)
                    qpark[hd * 2048 + i * 32] = make_uint4(pack_bf16(o[8 * i], o[8 * i + 1]), pack_bf16(o[8 * i + 2], o[8 * i + 3]),
                                                           pack_bf16(o[8 * i + 4], o[8 * i + 5]), pack_bf16(o[8 * i + 6], o[8 * i + 7]));
                if (SPARE && hd == 2) {
                    float (&u)[32] = reinterpret_cast<float (&)[32]>(o);
                    fence_regs(u);
#pragma unroll
                    for (int t = 0; t < 3; t++) {
                        mbar_wait(bar_full + 8 * t, 1);
                        uint64_t dv = args.d0 + t * (SLOT / 16);
                        WG_FENCE();
#pragma unroll
                        for (int ks = 0; ks < (t < 2 ? 16 : 4); ks++)
                            mma_rs64<1>(u, h[64 * t + 4 * ks], h[64 * t + 4 * ks + 1], h[64 * t + 4 * ks + 2], h[64 * t + 4 * ks + 3],
                                        dv, ks | t);
                        WG_COMMIT();
                        if (t > 0) { WG_WAIT(1); release(t - 1); }
                    }
                    WG_WAIT(0);
                    fence_regs(u);
                    release(2);
                    e = 15;
#pragma unroll
                    for (int i = 0; i < 4; i++)
                        qpark[3 * 2048 + i * 32] = make_uint4(pack_bf16(u[8 * i], u[8 * i + 1]), pack_bf16(u[8 * i + 2], u[8 * i + 3]),
                                                              pack_bf16(u[8 * i + 4], u[8 * i + 5]), pack_bf16(u[8 * i + 6], u[8 * i + 7]));
                }
            }
#pragma unroll
            for (int i = 0; i < 8; i++) {
                const uint4 v = qpark[2048 + i * 32];
                q[4 * i] = v.x; q[4 * i + 1] = v.y; q[4 * i + 2] = v.z; q[4 * i + 3] = v.w;
            }
#pragma unroll
            for (int i = 0; i < 32; i++) p[i] = h[112 + i];
            mbar_wait(bar_full + 24, 0);
            WG_WAIT(0);
            fence_regs(o);
            release(2);
        }
        DBG_T(105);
        DBG_G(125);

        uint8_t* frag = reinterpret_cast<uint8_t*>(__shfl_sync(0xffffffffu, reinterpret_cast<unsigned long long>(g_frag + (size_t)(rg * 8 + cw) * WREG + lane * 16), lane));
        const uint4* qnext = reinterpret_cast<const uint4*>(__shfl_sync(0xffffffffu, reinterpret_cast<unsigned long long>(padd(smem_raw, SM_Q + tid * 16 + cw * 3584)), lane));
        uint8_t* odst = reinterpret_cast<uint8_t*>(const_cast<uint4*>(qnext));
        qnext -= 2048;
        float m0, m1, l0 = 0.25f, l1 = 0.25f, t0, t1;
        uint32_t bad = 0;
        const int lw = cw & 3;
        const uint32_t relw = lw == RW && lane < 8, handw = lw == HW || cw == HW2;
        auto release4 = [&](uint32_t off) {
            asm volatile("{\n.reg .pred p;\nsetp.ne.b32 p, %1, 0;\n@p mbarrier.arrive.shared::cluster.b64 _, [%0];\n}" ::"r"(rel_base + off), "r"(relw) : "memory"); };
        auto handoff = [&]() {
            asm volatile("{\n.reg .pred p;\nsetp.ne.b32 p, %1, 0;\n@p bar.arrive %0, 192;\n}" ::"r"(2 - w), "r"(handw) : "memory"); };
        if (cw == 4 + HW) bar_arrive(1, 192);
        auto finish = [&](auto lo, auto hi, uint32_t bit, auto sink) {
#pragma unroll
            for (int i = lo.value; i < hi.value; i++) {
                const uint32_t v0 = pack_bf16(o[8 * i] * t0, o[8 * i + 1] * t0), v1 = pack_bf16(o[8 * i + 2] * t1, o[8 * i + 3] * t1);
                const uint32_t v2 = pack_bf16(o[8 * i + 4] * t0, o[8 * i + 5] * t0), v3 = pack_bf16(o[8 * i + 6] * t1, o[8 * i + 7] * t1);
                if (i == 0 && fabsf(o[0] * t0) >= 0x1p-31f) bad |= bit << 8;
                sink(i, v0, v1, v2, v3);
            }
        };
        float lq[6];
        auto row_parts = [&]() {
#pragma unroll
            for (int i = 0; i < 3; i++) { lq[i] = __shfl_xor_sync(0xffffffffu, l0, i + 1); lq[3 + i] = __shfl_xor_sync(0xffffffffu, l1, i + 1); }
        };
        auto row_sums = [&](uint32_t bit) {
            t0 = (l0 + lq[0]) + (lq[1] + lq[2]); t1 = (l1 + lq[3]) + (lq[4] + lq[5]);
            if (!(t0 >= LMIN && t0 < LMAX && t1 >= LMIN && t1 < LMAX)) bad |= bit;
        };
        auto issue_pv = [&](uint64_t dv, int acc, auto lo, auto hi) {
            if (lo.value == 0) asm volatile("{\n.reg .pred p;\nsetp.eq.b32 p, %0, 0;\n@p bar.sync 4, 160;\n}" ::"r"(w) : "memory");
#pragma unroll
            for (int ks = lo.value; ks < hi.value; ks++)
                mma_rs128<1>(o, p[4 * ks], p[4 * ks + 1], p[4 * ks + 2], p[4 * ks + 3], dv, ks ? 1 : acc);
            WG_COMMIT();
        };
#pragma unroll
        for (int i = 0; i < 64; i++) s[i] = 0.f;
        uint64_t dv_lo = args.d0;
        uint32_t voff = 0;
        auto issue_qk = [&]() {
            uint64_t dk = dv_lo ^ (desc_lo(0, UNIT) ^ desc_lo(3 * SLOT, 16));
            bar_sync(1 + w, 192);
            fence_regs(s); fence_regs(q); fence_regs(o); fence_regs(p);
            WG_FENCE();
#pragma unroll
            for (int ks = 0; ks < 8; ks++)
                if (ks == 3) mma_rs128<0, 1018>(s, q[4 * ks], q[4 * ks + 1], q[4 * ks + 2], q[4 * ks + 3], dk, 1);
                else mma_rs128<0, 2>(s, q[4 * ks], q[4 * ks + 1], q[4 * ks + 2], q[4 * ks + 3], dk, ks != 0);
            WG_COMMIT();
        };
        auto to_frag = [&](int i, uint32_t v0, uint32_t v1, uint32_t v2, uint32_t v3) {
            *reinterpret_cast<uint4*>(odst + i * 512) = make_uint4(v0, v1, v2, v3); };
        int n = 0;
        auto scores_ready = [&]() {
            WG_WAIT(1);
            fence_regs(s); fence_regs(q);
        };
        auto pass_on = [&]() {
            release4(voff ^ 24);
            handoff();
        };
#pragma unroll 1
        for (;;) {
            {
                if (RPE) {
                    asm volatile("st.shared.v2.f32 [%0], {%1, %2};" ::"r"(sb + SM_RED + tid * 8), "f"(l0), "f"(l1) : "memory");
                    __syncwarp();
                    const uint4 a = lds128(sb + SM_RED + (tid & ~3) * 8), b = lds128(sb + SM_RED + (tid & ~3) * 8 + 16);
                    l0 = __uint_as_float(a.x); lq[0] = __uint_as_float(a.z); lq[1] = __uint_as_float(b.x); lq[2] = __uint_as_float(b.z);
                    l1 = __uint_as_float(a.y); lq[3] = __uint_as_float(a.w); lq[4] = __uint_as_float(b.y); lq[5] = __uint_as_float(b.w);
                } else {
                    row_parts();
                }
                issue_qk();
                if (RPE == 2) hold(l0, l1);
                row_sums(1u << (n >> 4));
                t0 = rcp_fast(t0); t1 = rcp_fast(t1);
                l0 = 0.f; l1 = 0.f;
                odst = n ? frag + ((n >> 4) - 1) * 4096 : odst;
                qnext = n == 48 ? reinterpret_cast<const uint4*>(frag) : qnext + 2048;
                if (RPE) anchor(bar_full + 504, (t0 + t1) * __uint_as_float((bad ^ (uint32_t)(uintptr_t)odst ^ (uint32_t)(uintptr_t)qnext) & 0x3fffffff));
                asm volatile("{\n.reg .pred p;\nsetp.ne.b32 p, %1, 0;\n@p mbarrier.arrive.shared::cta.b64 _, [%0];\n}"
                             ::"r"(bar_qfree + (n >> 1) - 8), "r"(lane ? 0 : n) : "memory");
                issue_pv(dv_lo, 1, IC<0>{}, IC<8>{});
                scores_ready();
                float a0 = fmaxf(s[0], s[1]), a1 = fmaxf(s[2], s[3]), a2 = fmaxf(s[4], s[5]), a3 = fmaxf(s[6], s[7]);
#pragma unroll
                for (int i = 1; i < MAXG; i++) {
                    a0 = fmaxf(a0, fmaxf(s[8 * i], s[8 * i + 1])); a1 = fmaxf(a1, fmaxf(s[8 * i + 2], s[8 * i + 3]));
                    a2 = fmaxf(a2, fmaxf(s[8 * i + 4], s[8 * i + 5])); a3 = fmaxf(a3, fmaxf(s[8 * i + 6], s[8 * i + 7]));
                }
                const uint32_t a = pack_bf16(fmaxf(a0, a2), fmaxf(a1, a3));
                const uint32_t b = bmax2(bmax2(a, __shfl_xor_sync(0xffffffffu, a, 1)), bmax2(__shfl_xor_sync(0xffffffffu, a, 2), __shfl_xor_sync(0xffffffffu, a, 3)));
                pass_on();
                m0 = fmaf(-CS, bf_lo(b), -POFF); m1 = fmaf(-CS, bf_hi(b), -POFF);
            }
#pragma unroll 1
            for (;;) {
                DBG_T(n);
#pragma unroll
                for (int i = 0; i < 4 * STAGE; i++) s[i] = fmaf(s[i], CS, (i & 2) ? m1 : m0);
#pragma unroll
                for (int i = 0; i < 4 * SPLIT; i++) s[i] = ex2(s[i]);
#pragma unroll
                for (int i = 0; i < SPLIT; i++) { l0 += s[4 * i] + s[4 * i + 1]; l1 += s[4 * i + 2] + s[4 * i + 3]; }
                if (STAGE < 16) {
                    m0 = fmaf(l0, 0.f, m0); m1 = fmaf(l1, 0.f, m1);
                }
                anchor(bar_full + 504, l0 + l1);
                WG_WAIT(0);
                fence_regs(o); fence_regs(p);
                release4(voff);
                dv_lo ^= 2 * SLOT / 16;
                voff ^= 16;
                n++;
#pragma unroll
                for (int i = 4 * STAGE; i < 64; i++) s[i] = fmaf(s[i], CS, (i & 2) ? m1 : m0);
#pragma unroll
                for (int i = 4 * SPLIT; i < 64; i++) s[i] = ex2(s[i]);
#pragma unroll
                for (int i = SPLIT; i < 16; i++) { l0 += s[4 * i] + s[4 * i + 1]; l1 += s[4 * i + 2] + s[4 * i + 3]; }
#pragma unroll
                for (int i = 0; i < 32; i++) p[i] = pack_bf16(s[2 * i], s[2 * i + 1]);
                const int jn = n & 15;
                if (jn > 1) {
                    issue_qk();
                    if (((0x8000 | RCM | RCM << 1) >> jn) & 1) {
                        if ((RCM << 1 >> jn) & 1) {
#pragma unroll
                            for (int i = 0; i < 64; i++) o[i] *= (i & 2) ? t1 : t0;
                        }
                        if ((RCM >> jn) & 1) {
                            row_parts();
                            row_sums(2u << (n >> 4));
                            const uint32_t e0 = __float_as_uint(t0) >> 23, e1 = __float_as_uint(t1) >> 23;
                            m0 -= __uint_as_float(0x4b000000u | e0) - (8388608.f + 127.f - POFF);
                            m1 -= __uint_as_float(0x4b000000u | e1) - (8388608.f + 127.f - POFF);
                            t0 = __uint_as_float((254 - (int)POFF - e0) << 23); t1 = __uint_as_float((254 - (int)POFF - e1) << 23);
                            l0 *= t0; l1 *= t1;
                        }
                        if (SPARE && n == 47) mbar_wait(bar_q3, 0);
                    }
                    fence_regs(o);
                    WG_FENCE();
                    issue_pv(dv_lo, 1, IC<0>{}, IC<8>{});
                    scores_ready();
                    pass_on();
                    if (jn != 15) continue;
#pragma unroll
                    for (int i = 0; i < 8; i++) {
                        const uint4 v = qnext[i * 32];
                        q[4 * i] = v.x; q[4 * i + 1] = v.y; q[4 * i + 2] = v.z; q[4 * i + 3] = v.w;
                    }
                    continue;
                }
                if (jn == 0) break;
                finish(IC<0>{}, IC<ESPLIT>{}, 1u << (n >> 4), to_frag);
                issue_qk();
                if (HOLD) hold(t0, t1);
                finish(IC<ESPLIT>{}, IC<8>{}, 1u << (n >> 4), to_frag);
                WG_FENCE();
                issue_pv(dv_lo, 0, IC<0>{}, IC<8>{});
                scores_ready();
                pass_on();
            }
            if (n == 64) break;
        }
        DBG_T(64);
        uint32_t a1[32], a2[32];
        row_parts();
        frag_load(a1, frag + 4096);
        frag_load(a2, frag + 8192);
        bar_sync(1 + w, 192);
        fence_regs(o); fence_regs(p);
        WG_FENCE();
        issue_pv(args.d0 + 3 * SLOT / 16, 1, IC<0>{}, IC<8>{});
        handoff();
        row_sums(16);
        t0 = rcp_fast(t0); t1 = rcp_fast(t1);
        mbar_wait(bar_mod, 0);
        WG_WAIT(0);
        fence_regs(o); fence_regs(p);
        release4(24);
        finish(IC<0>{}, IC<8>{}, 16, [&](int i, uint32_t v0, uint32_t v1, uint32_t v2, uint32_t v3) {
            p[4 * i] = v0; p[4 * i + 1] = v1; p[4 * i + 2] = v2; p[4 * i + 3] = v3; });
        bad = __reduce_or_sync(0xffffffffu, bad);
        bad = ((bad | ~(bad >> 8)) >> 1) & 15;
        if (__builtin_expect(bad != 0, 0)) {
            uint8_t* keep = g_keep + (size_t)(rg * 8 + cw) * 4096 + lane * 16;
            frag_store(keep, p);
            attn_fallback(bad, tag, gs, frag, keep, args.wq, args.kc, args.vc);
            frag_load(q, frag); frag_load(a1, frag + 4096); frag_load(a2, frag + 8192); frag_load(p, keep);
        }
        DBG_T(80);
        DBG_G(124);

        const uint32_t eye = (lane >> 3) == (lane & 3) ? 0x3f80u << ((lane & 4) * 4) : 0;
        auto sum8 = [&](uint32_t* r, const uint4 (&v)[8]) {
            float d[16];
#pragma unroll
            for (int i = 0; i < 16; i++) d[i] = 0.f;
#pragma unroll
            for (int src = 0; src < 8; src++) {
                mma1688(d + 8 * (src & 1), v[src].x, v[src].y, eye);
                mma1688(d + 8 * (src & 1) + 4, v[src].z, v[src].w, eye);
            }
#pragma unroll
            for (int i = 0; i < 4; i++) r[i] = pack_bf16(d[2 * i] + d[8 + 2 * i], d[2 * i + 1] + d[9 + 2 * i]);
        };
        uint4 v2[8], v3[8], wf[23];
        uint2 u4[8], gw[9];
        uint32_t x1[20], xs, pa, ta;
        const uint8_t *mb, *mb4;
        int tid_;
        auto load_wf = [&](auto lo, auto hi) {
            const uint32_t wa = sb + SM_Q + ((tid_ & 8) * (D_ / 8) + cw * 16 + (tid_ & 7) + (tid_ & 16) / 2) * 80;
            const uint32_t wb = wa + (512 - cw * 8) * 80 - (tid_ & 16) * 39;
#pragma unroll
            for (int i = lo.value; i < hi.value; i++) wf[i] = ldsm4t(i < 20 ? wa + (i / 5) * 10240 + (i % 5) * 16 : wb + (i - 20) * 32);
        };
        uint32_t at[18];
        {
            float (&u)[32] = reinterpret_cast<float (&)[32]>(o);
            uint32_t off = 0;
            auto turn = [&](const uint32_t (&a)[32], const uint32_t (&b)[32], int acc) {
                uint64_t dv = args.d0 + off * (SLOT / 128);
                bar_sync(1 + w, 192);
                fence_regs(u);
                WG_FENCE();
#pragma unroll
                for (int ks = 0; ks < 16; ks++) {
                    const uint32_t* f = ks < 8 ? &a[4 * ks] : &b[4 * ks - 32];
                    mma_rs64<1>(u, f[0], f[1], f[2], f[3], dv, ks | acc);
                    if (ks == OSPLIT - 1) WG_COMMIT();
                }
                WG_COMMIT();
                WG_WAIT(1);
            };
            auto done = [&]() {
                WG_WAIT(0);
                fence_regs(u);
                release4(off);
                off = (off + 8) & 24;
            };
            auto store = [&](uint8_t* dst) {
#pragma unroll
                for (int i = 0; i < 4; i++)
                    st_relaxed4(dst + i * 512, pack_bf16(u[8 * i], u[8 * i + 1]), pack_bf16(u[8 * i + 2], u[8 * i + 3]),
                                pack_bf16(u[8 * i + 4], u[8 * i + 5]), pack_bf16(u[8 * i + 6], u[8 * i + 7]));
            };
            tid_ = __shfl_sync(0xffffffffu, tid, lane);
            pa = sb + w * (UNIT - 2048) + tid_ * 16;
#pragma unroll
            for (int i = 0; i < 8; i++) at[i] = 0;
            fence_regs(q); fence_regs(p);
            uint8_t* dst = frag;
#pragma unroll 1
            for (int k = 0; k < 8; k++, dst += 2048) {
                const uint32_t poff = off;
                const bool sum = (0xa0 >> k) & 1;
                if (sum) off = (off + 8) & 24;
                turn(q, p, 0);
                handoff();
                if (sum) {
                    uint4 v[8];
#pragma unroll
                    for (int src = 0; src < 8; src++) v[src] = lds128(pa + poff * (SLOT / 8) + src * 2048);
                    __syncwarp();
                    release(poff >> 3);
                    done();
                    float d[8];
#pragma unroll
                    for (int i = 0; i < 8; i++) {
                        float t[8];
#pragma unroll
                        for (int src = 0; src < 8; src++) {
                            const uint32_t x = i < 2 ? v[src].x : i < 4 ? v[src].y : i < 6 ? v[src].z : v[src].w;
                            t[src] = (i & 1) ? bf_hi(x) : bf_lo(x);
                        }
                        d[i] = ((t[0] + t[2]) + (t[4] + t[6])) + ((t[1] + t[3]) + (t[5] + t[7]));
                    }
#pragma unroll
                    for (int i = 0; i < 4; i++) { at[i] = at[4 + i]; at[4 + i] = pack_bf16(d[2 * i], d[2 * i + 1]); }
                } else {
                    done();
                }
                turn(a1, a2, 1);
                handoff();
                done();
                store(dst);
                __syncwarp();
                asm volatile("{\n.reg .pred p;\nsetp.ne.b32 p, %1, 0;\n@p mbarrier.arrive.shared::cta.b64 _, [%0];\n}"
                             ::"r"(bar_pub + 4 + 4 * k), "r"(lane ? 0 : (0x2a >> k) & 1) : "memory");
            }
            turn(q, p, 0);
            handoff();
            mb = padd(g_frag, (qb * 64 + j) * WREG + 3 * 4096 + tid_ * 16);
            mb4 = padd(mb, 4096 + ((cw >> 1) - cw) * 512 + (cw & 1) * 8);
            xs = sb + (tid_ & 15) * XP + (tid_ & 16) + cw * 32;
            ta = sb + (cw * 8 + (tid_ & 3)) * 8;
#pragma unroll
            for (int k = 0; k < 9; k++) {
                gw[k] = lds64(ta + SM_T + (k < 8 ? (k >> 1) * 64 + (k & 1) * 4 : 256 - cw * 4) * 8);
                if (!(tid_ & 4)) gw[k].y = 0x3f803f80u;
            }
            mbar_wait(bar_g, 0);
            done();
            load_wf(IC<0>{}, IC<WF0>{});
            turn(a1, a2, 1);
            if (w == 0) handoff();
            if (P2E) {
                mbar_wait(bar_full + 8, 0);
#pragma unroll
                for (int src = 0; src < 8; src++) v2[src] = lds128(pa + SLOT + src * 2048);
            }
            done();
            store(dst);
            mbar_wait(bar_full, 0);
            rows_load(x1, xs, cw);
            if (w == 0) bar_sync(5, 256); else bar_arrive(5, 256);
        }
        DBG_T(81);
        DBG_G(122);

        {
        const int tid = tid_, lane = tid & 31;
        const int g8 = lane >> 2, qd = lane & 3, l16 = lane & 15;
        uint32_t h2[18], gb[9], k1, k2;
        float4* rec = reinterpret_cast<float4*>(red + 128);
        const uint2* candp = reinterpret_cast<const uint2*>(padd(g_cand, ((blockIdx.x & (CREP - 1)) * NCTA + (tid >> 1)) * 32 + (tid & 1) * 8));
        uint2 cd;
        auto stage_out = [&]() {
#pragma unroll
            for (int k = 0; k < 9; k++) {
                x1[2 * k] = badd2(x1[2 * k], bmul2(gb[k], h2[2 * k]));
                x1[2 * k + 1] = badd2(x1[2 * k + 1], bmul2(gb[k], h2[2 * k + 1]));
            }
#pragma unroll
            for (int ch = 0; ch < 4; ch++) stsm_x4(xs + ch * 256, x1[4 * ch], x1[4 * ch + 1], x1[4 * ch + 2], x1[4 * ch + 3]);
            asm volatile("stmatrix.sync.aligned.m8n8.x2.shared.b16 [%0], {%1, %2};" ::"r"(xs + 1024 - cw * 16), "r"(x1[16]), "r"(x1[17]) : "memory");
        };
        {
            uint32_t it = 0, miss;
            if (!P2E) {
                mbar_wait(bar_full + 8, 0);
#pragma unroll
                for (int src = 0; src < 8; src++) v2[src] = lds128(pa + SLOT + src * 2048);
            }
            sum8(at + 8, v2);
            float st[12];
#pragma unroll
            for (int i = 0; i < 12; i++) st[i] = 0.f;
            auto add_pair = [&](int k) {
                x1[2 * k] = badd2(x1[2 * k], bmul2(gw[k].x, at[2 * k]));
                x1[2 * k + 1] = badd2(x1[2 * k + 1], bmul2(gw[k].x, at[2 * k + 1]));
                stats_add(st, x1[2 * k], x1[2 * k + 1], gw[k].y);
            };
#pragma unroll
            for (int k = 0; k < 6; k++) add_pair(k);
            mbar_wait(bar_full + 16, 0);
#pragma unroll
            for (int src = 0; src < 8; src++) v3[src] = lds128(pa + 2 * SLOT + src * 2048);
#pragma unroll 1
            do {
                if (BO && it) __nanosleep(BO);
                miss = 0;
#pragma unroll
                for (int src = 0; src < 8; src++) reload16(v3[src], mb + (size_t)src * 8 * WREG, miss);
            } while (__any_sync(0xffffffffu, miss) && ++it < SPIN / 16);
            if (lane < 4) mbar_arrive_cluster(rel_base + 8 * (1 + (lane >> 1)));
            sum8(at + 12, v3);
            add_pair(6); add_pair(7);
            load_wf(IC<WF0>{}, IC<WF1>{});
            uint2 cs[9];
#pragma unroll
            for (int k = 0; k < 9; k++) cs[k] = lds64(ta + SM_TC + (k < 8 ? (k >> 1) * 64 + (k & 1) * 4 : 256 - cw * 4) * 8);
            mbar_wait(bar_pre, 0);
            mbar_wait(bar_full + 24, 0);
#pragma unroll
            for (int src = 0; src < 8; src++) u4[src] = lds64(sb + 3 * SLOT + src * 2048 + (cw >> 1) * 512 + lane * 16 + (cw & 1) * 8);
#pragma unroll 1
            do {
                if (BO && miss) __nanosleep(BO);
                miss = 0;
#pragma unroll
                for (int src = 0; src < 8; src++) reload8(u4[src], mb4 + (size_t)src * 8 * WREG, miss);
            } while (__any_sync(0xffffffffu, miss) && ++it < SPIN / 16);
            float d[8] = {0.f, 0.f, 0.f, 0.f, 0.f, 0.f, 0.f, 0.f};
#pragma unroll
            for (int i = 0; i < 4; i++) mma16816(d + 4 * (i & 1), u4[2 * i].x, u4[2 * i].y, u4[2 * i + 1].x, u4[2 * i + 1].y, eye, eye);
            at[16] = pack_bf16(d[0] + d[4], d[1] + d[5]); at[17] = pack_bf16(d[2] + d[6], d[3] + d[7]);
            add_pair(8);
            DBG_G(123);
            const float2 ws = *reinterpret_cast<const float2*>(smem_raw + SM_TS);
            uint4* cdst = padd(g_cand, CFULL ? ((tid >> 1) * NCTA + rg) * 32 + (tid & 1) * 16 : (tid * NCTA + rg) * 32);
            uint32_t mean2;
            float dot;
            const float rsd = rows_stats(st, rec, cw, lane, mean2, dot);
            const uint32_t b = __float_as_uint(fmaf(fmaf(-bf_lo(mean2), ws.x, dot), rsd, ws.y));
            const uint32_t key = (((b & 0x80000000u) ? ~b : (b | 0x80000000u)) | 2047u) - (rg * 16 + l16);
            top2(key, k1, k2);
            if (tid < (CFULL + 1) * CREP) st_relaxed(cdst, k1, tag, k2, tag);
            cd = ld_relaxed64(candp);
            rows_normalise(h2, x1, mean2, rsd, lane, [&]() {
#pragma unroll
                for (int k = 0; k < 9; k++) gb[k] = lds32(sb + SM_TG + (cw * 8 + qd + (k < 8 ? (k >> 1) * 64 + (k & 1) * 4 : 256 - cw * 4)) * 4);
                if (WFE) load_wf(IC<WF1>{}, IC<WF2>{});
            });
#pragma unroll
            for (int k = 0; k < 18; k++) h2[k] = badd2(bmul2(h2[k], cs[k >> 1].x), cs[k >> 1].y);
            const uint32_t r1 = ~k1 & 15, r2 = ~k2 & 15;
            uint32_t todo = ((r1 & 7) == g8) | ((r2 & 7) == g8) << 1;
#pragma unroll 1
            while (todo) {
                const bool second = !(todo & 1), hi = (second ? r2 : r1) & 8;
                uint4* dst = padd(g_rows, ((rg * 2 + second) * RSLOT + cw * 24 + qd) * 16);
                uint32_t r[18];
#pragma unroll
                for (int k = 0; k < 9; k++) { r[k] = hi ? h2[2 * k + 1] : h2[2 * k]; r[9 + k] = hi ? x1[2 * k + 1] : x1[2 * k]; }
                fence_regs(r);
                st_relaxed(dst, r[0], r[1], r[2], r[3]);
                st_relaxed(dst + 8, r[4], r[5], r[6], r[7]);
                st_relaxed64(reinterpret_cast<uint2*>(padd(dst, 256 - qd * 8)), r[8], r[17]);
                st_relaxed(dst + 4, r[9], r[10], r[11], r[12]);
                st_relaxed(dst + 12, r[13], r[14], r[15], r[16]);
                todo &= todo - 1;
            }
            __syncwarp();

            stage_out();
            if (!WFE) load_wf(IC<WF1>{}, IC<WF2>{});
        }
        DBG_G(110);
        float4* part = reinterpret_cast<float4*>(smem_raw + 3 * SLOT + UNIT + 8192);
        bf16* act = reinterpret_cast<bf16*>(smem_raw + 3 * SLOT + UNIT + 4096);
        {
            uint32_t it = 0;
            const bool own = (tid >> 1) == rg;
            const uint32_t ks = sb + 3 * SLOT + UNIT + 5120;
#pragma unroll 1
            while (cd.y != tag && !own && ++it < SPIN / 16) cd = ld_relaxed64(candp);
            asm volatile("st.shared.u32 [%0], %1;" ::"r"(ks + tid * 4), "r"(own ? (tid & 1) ? k2 : k1 : cd.x) : "memory");
            bar_sync(3, 256);
            DBG_G(111);
            const uint4 a = lds128(ks + lane * 16), b = lds128(ks + 512 + lane * 16);
            const uint32_t a1 = max(a.x, a.z), a2 = __vimax3_u32(min(a.x, a.z), a.y, a.w);
            const uint32_t b1 = max(b.x, b.z), b2 = __vimax3_u32(min(b.x, b.z), b.y, b.w);
            const uint32_t c1 = max(a1, b1), c2 = __vimax3_u32(min(a1, b1), a2, b2);
            k1 = __reduce_max_sync(0xffffffffu, c1);
            k2 = __reduce_max_sync(0xffffffffu, c1 == k1 ? c2 : c1);
        }
        const int sel0 = ~k1 & 2047, sel1 = ~k2 & 2047;
        const uint32_t slot0 = (sel0 >> 4) * 2, slot1 = (sel1 >> 4) * 2 + ((sel0 ^ sel1) < 16);
        uint4 da[13];
        {
            const uint4* hp = padd(g_rows, (((g8 & 1) ? slot1 : slot0) * RSLOT + cw * 24 + qd) * 16);
            const uint2* hp2 = reinterpret_cast<const uint2*>(padd(hp, 256 - qd * 8));
            uint4 hv[2] = {ld_relaxed2(hp), ld_relaxed2(hp + 8)};
            uint2 hw = ld_relaxed64(hp2);
            if (tid == 255) {
                reinterpret_cast<int2*>(red)[8] = make_int2(sel0, sel1);
                mbar_arrive(bar_out);
            }
            load_wf(IC<WF2>{}, IC<23>{});
            mbar_wait(bar_full + 8, 1);
            mbar_wait(bar_full + 16, 1);
            auto load_d = [&](auto lo, auto hi) {
                const int r = (lane & 7) + (lane & 16) / 2;
                const uint32_t d0 = sb + SLOT + r * XP + cw * 144 + (lane & 8) * 2, d1 = d0 + (r < 2 ? 16 * XP : SLOT - 2 * XP);
                const uint32_t d2 = sb + 2 * SLOT + (14 + (lane & 3)) * XP + cw * 144 + (lane >> 3) * 16;
#pragma unroll
                for (int i = lo.value; i < hi.value; i++) da[i] = ldsm4t(i < 10 ? ((i & 1) ? d1 : d0) + (i >> 1) * 32 : d2 + (i - 10) * 64);
            };
            load_d(IC<0>{}, IC<DL>{});
            uint32_t it = 0, miss;
#pragma unroll 1
            do {
                miss = 0;
                reload16(hv[0], hp, miss);
                reload16(hv[1], hp + 8, miss);
                reload8(hw, hp2, miss);
            } while (__any_sync(0xffffffffu, miss) && ++it < SPIN / 16);
            DBG_G(112);
            load_d(IC<DL>{}, IC<13>{});
            float acc[20];
#pragma unroll
            for (int i = 0; i < 20; i++) acc[i] = 0.f;
#pragma unroll
            for (int i = 0; i < 5; i++) mma1688(acc + 4 * i, (i & 1) ? wf[20 + i / 2].z : wf[20 + i / 2].x, (i & 1) ? wf[20 + i / 2].w : wf[20 + i / 2].y, hw.x);
#pragma unroll
            for (int i = 0; i < 20; i++)
                mma16816(acc + 4 * (i % 5), wf[i].x, wf[i].y, wf[i].z, wf[i].w, (i / 5 & 1) ? hv[i / 10].z : hv[i / 10].x, (i / 5 & 1) ? hv[i / 10].w : hv[i / 10].y);
            if (qd == 0) {
#pragma unroll
                for (int i = 0; i < 5; i++) part[cw * 40 + i * 8 + g8] = make_float4(acc[4 * i], acc[4 * i + 1], acc[4 * i + 2], acc[4 * i + 3]);
            }
        }
        {
            uint2* dst = padd(g_ypart, ((cw * 9 * NCTA + blockIdx.x) * 8 + g8) * 8);
            bar_sync(3, 256);
            if (cw < 5) {
                const float* pp = reinterpret_cast<const float*>(part) + ((blockIdx.x & 1) << 4) + tid;
                const float g = rbf(((pp[0] + pp[160]) + (pp[320] + pp[480])) + ((pp[640] + pp[800]) + (pp[960] + pp[1120])));
                const float v = rbf(g * sigmoidf_(g)) * __shfl_down_sync(0xffffffffu, g, 2);
                if (!(tid & 2)) act[(tid & 1) * 56 + (tid >> 2)] = __float2bfloat16_rn(tid < 144 ? v : 0.f);
            }
            bar_sync(3, 256);
            DBG_G(113);
            const uint32_t ap = sb + 3 * SLOT + UNIT + 4096 + (lane & 1) * 112 + (lane >> 3) * 16;
            const uint4 b0 = ldsm4(ap);
            const uint32_t b1 = lds32(sb + 3 * SLOT + UNIT + 4096 + (g8 & 1) * 112 + 64 + qd * 4);
            float y[20];
#pragma unroll
            for (int i = 0; i < 20; i++) y[i] = 0.f;
#pragma unroll
            for (int i = 0; i < 5; i++) {
                mma16816(y + 4 * i, da[2 * i].x, da[2 * i].y, da[2 * i].z, da[2 * i].w, b0.x, b0.y);
                mma16816(y + 4 * i, da[2 * i + 1].x, da[2 * i + 1].y, da[2 * i + 1].z, da[2 * i + 1].w, b0.z, b0.w);
                mma1688(y + 4 * i, (i & 1) ? da[10 + i / 2].z : da[10 + i / 2].x, (i & 1) ? da[10 + i / 2].w : da[10 + i / 2].y, b1);
            }
#pragma unroll
            for (int i = 0; i < 9; i++)
                asm volatile("{\n.reg .pred p;\nsetp.eq.b32 p, %3, 0;\n@p st.relaxed.gpu.global.v2.f32 [%0], {%1, %2};\n}"
                             ::"l"(dst + i * (NCTA * 8)), "f"(y[2 * i]), "f"(y[2 * i + 1]), "r"(qd) : "memory");
        }
        DBG_G(114);
        if (blockIdx.x == 127 && tid == 0) gs->epoch[0] = tag;
        if (blockIdx.x < 72) {
            const int G = blockIdx.x, tok = g8 & 1, cp = G * 4 + qd;
            const uint2* src = padd(g_ypart, (blockIdx.x * NCTA * 8 + tid) * 8);
            const uint8_t* hsrc = reinterpret_cast<const uint8_t*>(padd(g_rows, (tok ? slot1 : slot0) * (RSLOT * 16) +
                (G < 64 ? (G >> 1 & 7) * 384 + (G >> 5) * 128 + qd * 16 + (G >> 1 & 8) + (G & 1) * 4 : (G - 64) * 384 + 256 + qd * 8)));
            const uint8_t* xsrc = hsrc + (G < 64 ? 64 : 4);
            uint32_t* dst = padd(reinterpret_cast<uint32_t*>(args.out), (tok ? sel1 : sel0) * (D_ * 2) + cp * 4);
            const uint32_t gb = reinterpret_cast<const uint32_t*>(smem_raw + SM_TG)[cp];
            const uint32_t ksel = ((tok ? k2 : k1) & ~2047u) | 1024u;
            const float sg = sigmoidf_(rbf(__uint_as_float((ksel & 0x80000000u) ? (ksel & 0x7fffffffu) : ~ksel)));
            uint2 v[4];
            uint32_t hv, xv, it = 0;
            bool miss;
#pragma unroll 1
            do {
#pragma unroll
                for (int i = 0; i < 4; i++) v[i] = ld_relaxed64(src + i * 256);
                hv = ld_relaxed32(hsrc);
                xv = ld_relaxed32(xsrc);
                miss = max(__vimax3_u32(v[0].x, v[1].x, v[2].x), __vimax3_u32(v[3].x, hv, xv)) == ~0u;
            } while (__any_sync(0xffffffffu, miss) && ++it < SPIN / 16);
            float y0 = (__uint_as_float(v[0].x) + __uint_as_float(v[1].x)) + (__uint_as_float(v[2].x) + __uint_as_float(v[3].x));
            float y1 = (__uint_as_float(v[0].y) + __uint_as_float(v[1].y)) + (__uint_as_float(v[2].y) + __uint_as_float(v[3].y));
            y0 += __shfl_xor_sync(0xffffffffu, y0, 8); y1 += __shfl_xor_sync(0xffffffffu, y1, 8);
            y0 += __shfl_xor_sync(0xffffffffu, y0, 16); y1 += __shfl_xor_sync(0xffffffffu, y1, 16);
            if (lane < 8) reinterpret_cast<float2*>(rec)[cw * 8 + lane] = make_float2(y0, y1);
            bar_sync(3, 256);
            if (cw == 0) {
                const float4 t0_ = rec[(lane >> 3) * 4 + qd], t1_ = rec[16 + (lane >> 3) * 4 + qd];
                y0 = tok ? t0_.y + t1_.y : t0_.x + t1_.x; y1 = tok ? t0_.w + t1_.w : t0_.z + t1_.z;
                y0 += __shfl_xor_sync(0xffffffffu, y0, 8); y1 += __shfl_xor_sync(0xffffffffu, y1, 8);
                y0 += __shfl_xor_sync(0xffffffffu, y0, 16); y1 += __shfl_xor_sync(0xffffffffu, y1, 16);
                const uint32_t y2 = bmul2(pack_bf16(y0, y1), pack_bf16(sg, sg));
                if (lane < 8) *dst = badd2(xv, bmul2(gb, badd2(hv, y2)));
            }
        }
        }
        DBG_T(88);
        DBG_G(121);
    }
}

typedef CUresult (*EncodeFn)(CUtensorMap*, CUtensorMapDataType, cuuint32_t, void*, const cuuint64_t*, const cuuint64_t*,
                             const cuuint32_t*, const cuuint32_t*, CUtensorMapInterleave, CUtensorMapSwizzle,
                             CUtensorMapL2promotion, CUtensorMapFloatOOBfill);

static void make_map(EncodeFn enc, CUtensorMap* m, const void* ptr, int rank, const cuuint64_t* dims,
                     const cuuint64_t* strides, const cuuint32_t* box, CUtensorMapSwizzle sw = CU_TENSOR_MAP_SWIZZLE_128B,
                     CUtensorMapDataType dt = CU_TENSOR_MAP_DATA_TYPE_BFLOAT16) {
    const cuuint32_t es[3] = {1, 1, 1};
    enc(m, dt, rank, const_cast<void*>(ptr), dims, strides, box, es,
        CU_TENSOR_MAP_INTERLEAVE_NONE, sw, CU_TENSOR_MAP_L2_PROMOTION_L2_128B,
        CU_TENSOR_MAP_FLOAT_OOB_FILL_NONE);
}

extern "C" void kernel_launch(void* const* d_in, const int* in_sizes, int n_in, void* d_out, int out_size) {
    const bf16* x = (const bf16*)d_in[0];
    const bf16* kc = (const bf16*)d_in[1];
    const bf16* vc = (const bf16*)d_in[2];
    const bf16* wq = (const bf16*)d_in[3];
    const bf16* wo = (const bf16*)d_in[4];
    const bf16* w_r = (const bf16*)d_in[6];
    const bf16* w_gate = (const bf16*)d_in[7];
    const bf16* w_up = (const bf16*)d_in[8];
    const bf16* w_down = (const bf16*)d_in[9];
    const bf16* cvec = (const bf16*)d_in[10];
    const bf16* w_mod = (const bf16*)d_in[11];
    bf16* out = (bf16*)d_out;

    void* fn = nullptr;
    cudaDriverEntryPointQueryResult qr;
    cudaGetDriverEntryPoint("cuTensorMapEncodeTiled", &fn, cudaEnableDefault, &qr);
    EncodeFn enc = (EncodeFn)fn;
    void* p_s;
    cudaGetSymbolAddress(&p_s, g_s);

    CUtensorMap tm_wq, tm_k, tm_v, tm_wo, tm_p, tm_x, tm_d, tm_g, tm_u;
    { cuuint64_t d[2] = {QD, D_}, s[1] = {QD * 2}; cuuint32_t b[2] = {64, 128}; make_map(enc, &tm_wq, wq, 2, d, s, b); }
    { cuuint64_t d[2] = {DH, HKV * S_}, s[1] = {DH * 2}; cuuint32_t b[2] = {64, 128};
      make_map(enc, &tm_k, kc, 2, d, s, b); make_map(enc, &tm_v, vc, 2, d, s, b); }
    { cuuint64_t d[2] = {D_, QD}, s[1] = {D_ * 2}; cuuint32_t b[2] = {64, 128}; make_map(enc, &tm_wo, wo, 2, d, s, b); }
    { cuuint64_t d[3] = {256, 160, NCTA}, s[2] = {1024, 8 * WREG}; cuuint32_t b[3] = {256, 2, 8};
      make_map(enc, &tm_p, ((Scratch*)p_s)->frag, 3, d, s, b, CU_TENSOR_MAP_SWIZZLE_NONE, CU_TENSOR_MAP_DATA_TYPE_UINT32); }
    { cuuint64_t d[2] = {D_ / 4, S_}, s[1] = {D_ * 2}; cuuint32_t b[2] = {XP / 8, 16};
      make_map(enc, &tm_x, x, 2, d, s, b, CU_TENSOR_MAP_SWIZZLE_NONE, CU_TENSOR_MAP_DATA_TYPE_UINT64); }
    { cuuint64_t d[2] = {D_ / 4, F_}, s[1] = {D_ * 2}; cuuint32_t b[2] = {XP / 8, 18};
      make_map(enc, &tm_d, w_down, 2, d, s, b, CU_TENSOR_MAP_SWIZZLE_NONE, CU_TENSOR_MAP_DATA_TYPE_UINT64); }
    { cuuint64_t d[2] = {F_, D_}, s[1] = {F_ * 2}; cuuint32_t b[2] = {40, 24};
      make_map(enc, &tm_g, w_gate, 2, d, s, b, CU_TENSOR_MAP_SWIZZLE_NONE); make_map(enc, &tm_u, w_up, 2, d, s, b, CU_TENSOR_MAP_SWIZZLE_NONE); }

    cudaFuncSetAttribute(fused_kernel<true>, cudaFuncAttributeMaxDynamicSharedMemorySize, SM_TOTAL);
    cudaFuncSetAttribute(fused_kernel<false>, cudaFuncAttributeMaxDynamicSharedMemorySize, SM_TOTAL);
    cudaLaunchConfig_t cfg = {};
    cfg.gridDim = NCTA + 4; cfg.blockDim = 384; cfg.dynamicSmemBytes = SM_TOTAL;
    cudaLaunchAttribute at;
    at.id = cudaLaunchAttributeClusterDimension; at.val.clusterDim.x = 2; at.val.clusterDim.y = 1; at.val.clusterDim.z = 1;
    cfg.attrs = &at; cfg.numAttrs = 1;
    int ncl = 0;
    if (cudaOccupancyMaxActiveClusters(&ncl, fused_kernel<true>, &cfg) != cudaSuccess) { ncl = 0; cudaGetLastError(); }
    Args args{w_mod, cvec, (Scratch*)p_s, desc_lo(0, UNIT) | (0x40000040ull << 32), out, x, kc, vc, wq, wo, w_r, w_down};
    if (USE_SPARE && ncl >= NCTA / 2 + 2)
        fused_kernel<true><<<NCTA + 4, 384, SM_TOTAL>>>(args, tm_wq, tm_k, tm_v, tm_wo, tm_p, tm_x, tm_d, tm_g, tm_u);
    else
        fused_kernel<false><<<NCTA, 384, SM_TOTAL>>>(args, tm_wq, tm_k, tm_v, tm_wo, tm_p, tm_x, tm_d, tm_g, tm_u);
}
```

```cpp
#include <cuda_runtime.h>
#include <cuda_bf16.h>
#include <cuda.h>
#include <stdint.h>
#include <math.h>

typedef __nv_bfloat16 bf16;

constexpr int S_ = 2048;
constexpr int D_ = 576;
constexpr int HQ = 32, HKV = 16, DH = 128;
constexpr int F_ = 4608;
constexpr int QD = HQ * DH;

constexpr int NCTA = 128;
constexpr int WREG = 5 * 4096;
constexpr int CREP = 8;
constexpr int RSLOT = 192;
constexpr int MREP = 4;
struct Scratch {
    unsigned int epoch[128];
    unsigned int flag_mod[NCTA];
    unsigned int flag_part[16 * 32];
    unsigned int flag_q3[16 * 32];
    unsigned int flag_h[NCTA * 32];
    uint2 mod1[MREP * D_];
    uint32_t mod2[4 * D_];
    uint4 cand[CREP * NCTA * 2];
    uint2 ypart[72 * NCTA * 8];
    uint4 h[2][NCTA * 36 * 32];
    uint4 q3[NCTA * 8 * 128];
    uint4 rows[NCTA * 2 * RSLOT];
    uint8_t frag[NCTA * 8 * WREG];
    uint8_t keep[NCTA * 8 * 4096];
};
__device__ __align__(1024) Scratch g_s;
#define g_h gs->h[tag & 1]
#define g_q3 gs->q3
#define g_keep gs->keep
#define g_flag_h gs->flag_h
#define g_flag_part gs->flag_part
#define g_flag_mod gs->flag_mod
#define g_flag_q3 gs->flag_q3
#define g_frag gs->frag
#define g_cand gs->cand
#define g_ypart gs->ypart
#define g_rows gs->rows

#define DBG_INIT()
#define DBG_P(i)
#define DBG_PG(i)
#define DBG_T(i)
#define DBG_G(i)

__device__ __forceinline__ uint32_t pack_bf16(float lo, float hi) {
    uint32_t r;
    asm("cvt.rn.bf16x2.f32 %0, %1, %2;" : "=r"(r) : "f"(hi), "f"(lo));
    return r;
}
__device__ __forceinline__ float rbf(float x) { return __uint_as_float(pack_bf16(0.f, x)); }
__device__ __forceinline__ float bf_lo(uint32_t v) { return __uint_as_float(v << 16); }
__device__ __forceinline__ float bf_hi(uint32_t v) { return __uint_as_float(v & 0xffff0000u); }
__device__ __forceinline__ float ex2(float x) {
    float y;
    asm("ex2.approx.ftz.f32 %0, %1;" : "=f"(y) : "f"(x));
    return y;
}
template <class T>
__device__ __forceinline__ T* padd(T* p, uint32_t off) {
    unsigned long long r;
    asm("{\n.reg .b32 l, h;\nmov.b64 {l, h}, %1;\nadd.cc.u32 l, l, %2;\naddc.u32 h, h, 0;\nmov.b64 %0, {l, h};\n}" : "=l"(r) : "l"(p), "r"(off));
    return reinterpret_cast<T*>(r);
}
__device__ __forceinline__ uint32_t smem_u32(const void* p) { return (uint32_t)__cvta_generic_to_shared(p); }
__device__ __forceinline__ void mbar_init(uint32_t bar, uint32_t cnt) {
    asm volatile("mbarrier.init.shared::cta.b64 [%0], %1;" ::"r"(bar), "r"(cnt) : "memory");
}
__device__ __forceinline__ void mbar_expect_tx(uint32_t bar, uint32_t bytes) {
    asm volatile("mbarrier.arrive.expect_tx.shared::cta.b64 _, [%0], %1;" ::"r"(bar), "r"(bytes) : "memory");
}
__device__ __forceinline__ void mbar_arrive(uint32_t bar) {
    asm volatile("mbarrier.arrive.shared::cta.b64 _, [%0];" ::"r"(bar) : "memory");
}
__device__ __forceinline__ void mbar_arrive_cluster(uint32_t cluster_addr) {
    asm volatile("mbarrier.arrive.shared::cluster.b64 _, [%0];" ::"r"(cluster_addr) : "memory");
}
constexpr uint32_t SPIN = 1u << 20;
__device__ __forceinline__ void mbar_wait(uint32_t bar, uint32_t parity) {
    asm volatile("{\n.reg .pred p;\n.reg .b32 c;\nmov.b32 c, 0;\n"
                 "W_%=:\nmbarrier.try_wait.parity.shared::cta.b64 p, [%0], %1;\n"
                 "add.u32 c, c, 1;\nsetp.lt.and.u32 p, c, 0x100000, !p;\n@p bra W_%=;\n}"
                 ::"r"(bar), "r"(parity) : "memory");
}
__device__ __forceinline__ void anchor(uint32_t addr, float v) {
    asm volatile("{\n.reg .pred p;\nsetp.lt.f32 p, %1, 0f00000000;\n@p st.volatile.shared.f32 [%0], %1;\n}" ::"r"(addr), "f"(v) : "memory");
}
__device__ __forceinline__ void anchor(uint32_t addr, uint32_t v) {
    asm volatile("{\n.reg .pred p;\nsetp.eq.u32 p, %1, 0xffffffff;\n@p st.volatile.shared.u32 [%0], %1;\n}" ::"r"(addr), "r"(v) : "memory");
}
__device__ __forceinline__ void anchor(void* p, uint32_t v) {
    asm volatile("{\n.reg .pred p;\nsetp.eq.u32 p, %1, 0xffffffff;\n@p st.volatile.u32 [%0], %1;\n}" ::"l"(p), "r"(v) : "memory");
}
__device__ __forceinline__ void hold(float& a, float& b) {
    asm volatile("{\n.reg .pred p;\n.reg .b64 t;\n.reg .b32 l, h;\nmov.u64 t, %%clock64;\nmov.b64 {l, h}, t;\nsetp.eq.u32 p, h, 0xffffffff;\n"
                 "@p mov.f32 %0, 0f00000000;\n@p mov.f32 %1, 0f00000000;\n}" : "+f"(a), "+f"(b) :: "memory");
}
__device__ __forceinline__ void mbar_wait_sleep(uint32_t bar, uint32_t parity) {
    asm volatile("{\n.reg .pred p;\n.reg .b32 c;\nmov.b32 c, 0;\n"
                 "W_%=:\nmbarrier.try_wait.parity.shared::cta.b64 p, [%0], %1, 5000;\n"
                 "add.u32 c, c, 1;\nsetp.lt.and.u32 p, c, 0x20000, !p;\n@p bra W_%=;\n}"
                 ::"r"(bar), "r"(parity) : "memory");
}
__device__ __forceinline__ uint32_t load_tag(const Scratch* gs) {
    uint32_t tag;
    asm volatile("ld.global.ca.u32 %0, [%1];" : "=r"(tag) : "l"(gs->epoch) : "memory");
    return tag + 1;
}
__device__ __forceinline__ uint4 ld_relaxed(const uint4* p) {
    uint4 v;
    asm volatile("ld.relaxed.gpu.global.v4.u32 {%0,%1,%2,%3}, [%4];" : "=r"(v.x), "=r"(v.y), "=r"(v.z), "=r"(v.w) : "l"(p) : "memory");
    return v;
}
__device__ __forceinline__ void st_relaxed(uint4* p, uint32_t a, uint32_t b, uint32_t c, uint32_t d) {
    asm volatile("{\n.reg .b64 u, v;\nmov.b64 u, {%1, %2};\nmov.b64 v, {%3, %4};\nst.relaxed.gpu.global.v2.b64 [%0], {u, v};\n}"
                 ::"l"(p), "r"(a), "r"(b), "r"(c), "r"(d) : "memory");
}
__device__ __forceinline__ void st_relaxed4(void* p, uint32_t a, uint32_t b, uint32_t c, uint32_t d) {
    asm volatile("st.relaxed.gpu.global.v4.u32 [%0], {%1, %2, %3, %4};" ::"l"(p), "r"(a), "r"(b), "r"(c), "r"(d) : "memory");
}
__device__ __forceinline__ uint2 ld_relaxed8(const void* p) {
    uint2 v;
    asm volatile("ld.relaxed.gpu.global.v2.u32 {%0,%1}, [%2];" : "=r"(v.x), "=r"(v.y) : "l"(p) : "memory");
    return v;
}
__device__ __forceinline__ uint2 ld_relaxed64(const uint2* p) {
    uint2 v;
    asm volatile("{\n.reg .b64 u;\nld.relaxed.gpu.global.b64 u, [%2];\nmov.b64 {%0, %1}, u;\n}" : "=r"(v.x), "=r"(v.y) : "l"(p) : "memory");
    return v;
}
__device__ __forceinline__ void st_relaxed64(uint2* p, uint32_t a, uint32_t b) {
    asm volatile("{\n.reg .b64 u;\nmov.b64 u, {%1, %2};\nst.relaxed.gpu.global.b64 [%0], u;\n}" ::"l"(p), "r"(a), "r"(b) : "memory");
}
__device__ __forceinline__ uint4 ld_relaxed2(const uint4* p) {
    uint4 v;
    asm volatile("{\n.reg .b64 u, w;\nld.relaxed.gpu.global.v2.b64 {u, w}, [%4];\nmov.b64 {%0, %1}, u;\nmov.b64 {%2, %3}, w;\n}"
                 : "=r"(v.x), "=r"(v.y), "=r"(v.z), "=r"(v.w) : "l"(p) : "memory");
    return v;
}
__device__ __forceinline__ void reload16(uint4& v, const void* p, uint32_t& miss) {
    asm volatile("{\n.reg .pred p;\n.reg .b32 m;\n.reg .b64 u, w;\nmax.u32 m, %0, %2;\nsetp.eq.u32 p, m, 0xffffffff;\n"
                 "mov.b64 u, {%0, %1};\nmov.b64 w, {%2, %3};\n@p ld.relaxed.gpu.global.v2.b64 {u, w}, [%5];\n"
                 "mov.b64 {%0, %1}, u;\nmov.b64 {%2, %3}, w;\n@p mov.u32 %4, 1;\n}"
                 : "+r"(v.x), "+r"(v.y), "+r"(v.z), "+r"(v.w), "+r"(miss) : "l"(p) : "memory");
}
__device__ __forceinline__ void reload8(uint2& v, const void* p, uint32_t& miss) {
    asm volatile("{\n.reg .pred p;\n.reg .b64 u;\nsetp.eq.u32 p, %0, 0xffffffff;\nmov.b64 u, {%0, %1};\n"
                 "@p ld.relaxed.gpu.global.b64 u, [%3];\nmov.b64 {%0, %1}, u;\n@p mov.u32 %2, 1;\n}"
                 : "+r"(v.x), "+r"(v.y), "+r"(miss) : "l"(p) : "memory");
}
__device__ __forceinline__ uint32_t ld_relaxed32(const void* p) {
    uint32_t v;
    asm volatile("ld.relaxed.gpu.global.u32 %0, [%1];" : "=r"(v) : "l"(p) : "memory");
    return v;
}
__device__ __forceinline__ void flag_wait(const unsigned int* p, uint32_t tag) {
    uint32_t v, it = 0;
#pragma unroll 1
    do {
        asm volatile("ld.relaxed.gpu.global.u32 %0, [%1];" : "=r"(v) : "l"(p) : "memory");
    } while (__any_sync(0xffffffffu, v != tag) && ++it < SPIN / 16);
    asm volatile("fence.acquire.gpu;" ::: "memory");
    __syncwarp();
}
__device__ __forceinline__ bool elect() {
    uint32_t p;
    asm volatile("{\n.reg .pred p;\nelect.sync _|p, 0xffffffff;\nselp.u32 %0, 1, 0, p;\n}" : "=r"(p));
    return p;
}
__device__ __forceinline__ void flag_release(unsigned int* p, uint32_t tag) {
    asm volatile("st.release.gpu.global.u32 [%0], %1;" ::"l"(p), "r"(tag) : "memory");
}
__device__ __forceinline__ uint32_t touch(const void* p) {
    uint32_t v;
    asm volatile("ld.global.nc.L1::no_allocate.L2::128B.u32 %0, [%1];" : "=r"(v) : "l"(p));
    return v;
}
__device__ __forceinline__ void bar_sync(int id, int n) { asm volatile("bar.sync %0, %1;" ::"r"(id), "r"(n) : "memory"); }
__device__ __forceinline__ void bar_arrive(int id, int n) { asm volatile("bar.arrive %0, %1;" ::"r"(id), "r"(n) : "memory"); }

constexpr uint64_t EVICT_NORMAL = 0x1000000000000000ull, EVICT_FIRST = 0x12F0000000000000ull;
__device__ __forceinline__ void tma2d(uint32_t dst, const CUtensorMap* m, int c0, int c1, uint32_t bar) {
    asm volatile("cp.async.bulk.tensor.2d.shared::cluster.global.mbarrier::complete_tx::bytes.L2::cache_hint [%0], [%1, {%3, %4}], [%2], %5;"
                 ::"r"(dst), "l"(m), "r"(bar), "r"(c0), "r"(c1), "l"(EVICT_FIRST) : "memory");
}
__device__ __forceinline__ void tma2d_mc(uint32_t dst, const CUtensorMap* m, int c0, int c1, uint32_t bar, uint64_t pol) {
    asm volatile("cp.async.bulk.tensor.2d.shared::cluster.global.mbarrier::complete_tx::bytes.multicast::cluster.L2::cache_hint [%0], [%1, {%3, %4}], [%2], %5, %6;"
                 ::"r"(dst), "l"(m), "r"(bar), "r"(c0), "r"(c1), "h"((uint16_t)3), "l"(pol) : "memory");
}
__device__ __forceinline__ void tma3d(uint32_t dst, const CUtensorMap* m, int c0, int c1, int c2, uint32_t bar) {
    asm volatile("cp.async.bulk.tensor.3d.shared::cluster.global.mbarrier::complete_tx::bytes.L2::cache_hint [%0], [%1, {%3, %4, %5}], [%2], %6;"
                 ::"r"(dst), "l"(m), "r"(bar), "r"(c0), "r"(c1), "r"(c2), "l"(EVICT_FIRST) : "memory");
}
__device__ __forceinline__ void bulk_load(uint32_t dst, const void* src, uint32_t bytes, uint32_t bar) {
    asm volatile("cp.async.bulk.shared::cluster.global.mbarrier::complete_tx::bytes [%0], [%1], %2, [%3];"
                 ::"r"(dst), "l"(src), "r"(bytes), "r"(bar) : "memory");
}
__device__ __forceinline__ void l2_prefetch(const void* src, uint32_t bytes) {
    asm volatile("cp.async.bulk.prefetch.L2.global [%0], %1;" ::"l"(src), "r"(bytes) : "memory");
}
__device__ __forceinline__ uint32_t bmul2(uint32_t a, uint32_t b) { uint32_t r; asm("mul.rn.bf16x2 %0, %1, %2;" : "=r"(r) : "r"(a), "r"(b)); return r; }
__device__ __forceinline__ uint32_t badd2(uint32_t a, uint32_t b) { uint32_t r; asm("add.rn.bf16x2 %0, %1, %2;" : "=r"(r) : "r"(a), "r"(b)); return r; }
__device__ __forceinline__ uint32_t bsub2(uint32_t a, uint32_t b) { uint32_t r; asm("sub.rn.bf16x2 %0, %1, %2;" : "=r"(r) : "r"(a), "r"(b)); return r; }
__device__ __forceinline__ uint32_t bmax2(uint32_t a, uint32_t b) { uint32_t r; asm("max.bf16x2 %0, %1, %2;" : "=r"(r) : "r"(a), "r"(b)); return r; }
__device__ __forceinline__ uint32_t bfma2(uint32_t a, uint32_t b, uint32_t c) { uint32_t r; asm("fma.rn.bf16x2 %0, %1, %2, %3;" : "=r"(r) : "r"(a), "r"(b), "r"(c)); return r; }
__device__ __forceinline__ uint4 lds128(uint32_t a) { uint4 v; asm volatile("ld.shared.v4.u32 {%0,%1,%2,%3}, [%4];" : "=r"(v.x), "=r"(v.y), "=r"(v.z), "=r"(v.w) : "r"(a) : "memory"); return v; }
__device__ __forceinline__ uint2 lds64(uint32_t a) { uint2 v; asm volatile("ld.shared.v2.u32 {%0,%1}, [%2];" : "=r"(v.x), "=r"(v.y) : "r"(a) : "memory"); return v; }
__device__ __forceinline__ uint32_t lds32(uint32_t a) { uint32_t v; asm volatile("ld.shared.u32 %0, [%1];" : "=r"(v) : "r"(a) : "memory"); return v; }
__device__ __forceinline__ uint4 ldsm4(uint32_t a) {
    uint4 v;
    asm volatile("ldmatrix.sync.aligned.m8n8.x4.shared.b16 {%0,%1,%2,%3}, [%4];" : "=r"(v.x), "=r"(v.y), "=r"(v.z), "=r"(v.w) : "r"(a) : "memory");
    return v;
}
__device__ __forceinline__ uint4 ldsm4t(uint32_t a) {
    uint4 v;
    asm volatile("ldmatrix.sync.aligned.m8n8.x4.trans.shared.b16 {%0,%1,%2,%3}, [%4];" : "=r"(v.x), "=r"(v.y), "=r"(v.z), "=r"(v.w) : "r"(a) : "memory");
    return v;
}
__device__ __forceinline__ void mma1688(float* d, uint32_t a0, uint32_t a1, uint32_t b) {
    asm("mma.sync.aligned.m16n8k8.row.col.f32.bf16.bf16.f32 {%0,%1,%2,%3}, {%4,%5}, {%6}, {%0,%1,%2,%3};"
        : "+f"(d[0]), "+f"(d[1]), "+f"(d[2]), "+f"(d[3]) : "r"(a0), "r"(a1), "r"(b));
}
__device__ __forceinline__ void mma16816(float* d, uint32_t a0, uint32_t a1, uint32_t a2, uint32_t a3, uint32_t b0, uint32_t b1) {
    asm("mma.sync.aligned.m16n8k16.row.col.f32.bf16.bf16.f32 {%0,%1,%2,%3}, {%4,%5,%6,%7}, {%8,%9}, {%0,%1,%2,%3};"
                 : "+f"(d[0]), "+f"(d[1]), "+f"(d[2]), "+f"(d[3]) : "r"(a0), "r"(a1), "r"(a2), "r"(a3), "r"(b0), "r"(b1));
}
__device__ __forceinline__ void stsm_x4(uint32_t addr, uint32_t a, uint32_t b, uint32_t c, uint32_t d) {
    asm volatile("stmatrix.sync.aligned.m8n8.x4.shared.b16 [%0], {%1, %2, %3, %4};"
                 ::"r"(addr), "r"(a), "r"(b), "r"(c), "r"(d) : "memory");
}

__device__ __forceinline__ uint64_t mkdesc(uint32_t addr, uint32_t lbo, uint32_t sbo) {
    return (uint64_t)((addr & 0x3FFFF) >> 4) | ((uint64_t)(lbo >> 4) << 16) | ((uint64_t)(sbo >> 4) << 32) | (1ull << 62);
}
constexpr uint32_t SM0 = 1024;
__host__ __device__ constexpr uint32_t desc_lo(uint32_t off, uint32_t lbo) { return ((SM0 + off) >> 4) | ((lbo >> 4) << 16); }
#define WG_FENCE() asm volatile("wgmma.fence.sync.aligned;" ::: "memory")
#define WG_COMMIT() asm volatile("wgmma.commit_group.sync.aligned;" ::: "memory")
#define WG_WAIT(n) asm volatile("wgmma.wait_group.sync.aligned %0;" ::"n"(n) : "memory")

#define F8(a, i) "+f"(a[i]), "+f"(a[i + 1]), "+f"(a[i + 2]), "+f"(a[i + 3]), "+f"(a[i + 4]), "+f"(a[i + 5]), "+f"(a[i + 6]), "+f"(a[i + 7])
#define F16(a, i) F8(a, i), F8(a, i + 8)
#define F64(a) F16(a, 0), F16(a, 16), F16(a, 32), F16(a, 48)
#define F32(a) F16(a, 0), F16(a, 16)
#define L64 "%0,%1,%2,%3,%4,%5,%6,%7,%8,%9,%10,%11,%12,%13,%14,%15,%16,%17,%18,%19,%20,%21,%22,%23,%24,%25,%26,%27,%28,%29,%30,%31,%32,%33,%34,%35,%36,%37,%38,%39,%40,%41,%42,%43,%44,%45,%46,%47,%48,%49,%50,%51,%52,%53,%54,%55,%56,%57,%58,%59,%60,%61,%62,%63"
#define L32 "%0,%1,%2,%3,%4,%5,%6,%7,%8,%9,%10,%11,%12,%13,%14,%15,%16,%17,%18,%19,%20,%21,%22,%23,%24,%25,%26,%27,%28,%29,%30,%31"

template <int TB, int STEP = 128>
__device__ __forceinline__ void mma_rs128(float (&d)[64], uint32_t a0, uint32_t a1, uint32_t a2, uint32_t a3, uint64_t& b, int acc) {
    asm volatile("{\n.reg .pred p;\nsetp.ne.b32 p, %69, 0;\n"
                 "wgmma.mma_async.sync.aligned.m64n128k16.f32.bf16.bf16 {" L64 "}, {%65,%66,%67,%68}, %64, p, 1, 1, %70;\nadd.s64 %64, %64, %71;\n}"
                 : F64(d), "+l"(b) : "r"(a0), "r"(a1), "r"(a2), "r"(a3), "r"(acc), "n"(TB), "n"(STEP));
}
template <int TB>
__device__ __forceinline__ void mma_rs64(float (&d)[32], uint32_t a0, uint32_t a1, uint32_t a2, uint32_t a3, uint64_t& b, int acc) {
    asm volatile("{\n.reg .pred p;\nsetp.ne.b32 p, %37, 0;\n"
                 "wgmma.mma_async.sync.aligned.m64n64k16.f32.bf16.bf16 {" L32 "}, {%33,%34,%35,%36}, %32, p, 1, 1, %38;\nadd.s64 %32, %32, 128;\n}"
                 : F32(d), "+l"(b) : "r"(a0), "r"(a1), "r"(a2), "r"(a3), "r"(acc), "n"(TB));
}
template <int N>
__device__ __forceinline__ void fence_regs(float (&d)[N]) {
#pragma unroll
    for (int i = 0; i < N; i++) asm volatile("" : "+f"(d[i])::"memory");
}
template <int N>
__device__ __forceinline__ void fence_regs(uint32_t (&d)[N]) {
#pragma unroll
    for (int i = 0; i < N; i++) asm volatile("" : "+r"(d[i])::"memory");
}

template <int V> struct IC { static constexpr int value = V; };

constexpr int SLOT = 32768, UNIT = 16384;
constexpr int SM_Q = 4 * SLOT;
constexpr int SM_BAR = 7 * SLOT;
constexpr int SM_RED = SM_BAR + 512;
constexpr int SM_TOTAL = SM_BAR + 3072;
constexpr int XP = D_ * 2 + 16;
constexpr int M_MOD = 16 * XP;
constexpr int SM_T = SM_Q + 2 * D_ * 80, SM_TC = SM_T + D_ * 4, SM_TG = SM_TC + D_ * 4, SM_TS = SM_TG + D_ * 2;
constexpr float CS = 0.08838834764831845f * 1.4426950408889634f;
#define LMAX 0.5f
#define LMIN 0x1p-104f
#define USE_SPARE 1
#define MAXG 2
#define SPLIT 10
#define ESPLIT 3
#define PV1 8
#define RW 2
#define HW 2
#define HW2 1
#define XDELAY 200
#define QDELAY 300
#define TMPF 1
#define PFD0 2000
#define PFD1 400
#define HDELAY 300
#define RA 10
#define RB 2
#define RPE 2
#define OSPLIT 6
#define HOLD 1
#define DL 6
#define O2F 0
#define A2N 4
#define OPF 0
#define STAGE 11
#define POFF 102.f
#define WF0 3
#define WF1 13
#define C3D 0
#define C4D 300
#define DD 300
#define P2E 0
#define BO 0
#define MAP 2
#define CFULL 0
#define WFE 1
#define OUTD 0
#define OUTPOL EVICT_FIRST
#define WF2 19
constexpr int PF_KV = 8, PF_WO = 120;

__device__ __forceinline__ int cluster_role() {
    int k;
    asm volatile("mov.u32 %0, %%ctaid.x;" : "=r"(k));
    k >>= 1;
    if (MAP == 0) return k & 63;
    if (MAP == 1) return (k & 7) * 8 + ((k >> 3) & 7);
    if (MAP == 3) {
        asm("mov.u32 %0, %%smid;" : "=r"(k));
        k >>= 1;
        const int r = ((k - 32) * 37) >> 8;
        return k < 32 ? (k & 7) * 8 + (k >> 3) : k < 60 ? (k - 31 - r * 7) * 8 + 4 + r : (k - 58) & 7;
    }
    const int r = ((k - 36) * 37) >> 8, i = k - 36 - r * 7;
    if (MAP == 4) return k < 4 ? 4 + k : k < 36 ? ((k - 4) & 7) * 8 + ((k - 4) >> 3) : (i + 1) * 8 + ((4 + r) & 7);
    return k < 4 ? 12 + k : k < 36 ? ((k - 4) & 7) * 8 + ((k - 4) >> 3) : (i + (i > 0)) * 8 + ((4 + r) & 7);
}

struct Args {
    const bf16 *w_mod, *cvec;
    Scratch* gs;
    uint64_t d0;
    bf16* out;
    const bf16 *x, *kc, *vc, *wq, *wo, *w_r, *w_down;
};

__device__ __forceinline__ void frag_store(uint8_t* p, const uint32_t (&a)[32]) {
#pragma unroll
    for (int i = 0; i < 8; i++)
        __stcg(reinterpret_cast<uint4*>(p + i * 512), make_uint4(a[4 * i], a[4 * i + 1], a[4 * i + 2], a[4 * i + 3]));
}
template <int LO = 0, int HI = 8>
__device__ __forceinline__ void frag_load(uint32_t (&a)[32], const uint8_t* p) {
#pragma unroll
    for (int i = LO; i < HI; i++) {
        const uint4 v = ld_relaxed(reinterpret_cast<const uint4*>(p + i * 512));
        a[4 * i] = v.x; a[4 * i + 1] = v.y; a[4 * i + 2] = v.z; a[4 * i + 3] = v.w;
    }
}
__device__ __forceinline__ float quad_sum(float v) {
    v += __shfl_xor_sync(0xffffffffu, v, 1);
    return v + __shfl_xor_sync(0xffffffffu, v, 2);
}
__device__ __forceinline__ float quad_max(float v) {
    v = fmaxf(v, __shfl_xor_sync(0xffffffffu, v, 1));
    return fmaxf(v, __shfl_xor_sync(0xffffffffu, v, 2));
}
__device__ __forceinline__ float rcp_fast(float x) { float y; asm("rcp.approx.ftz.f32 %0, %1;" : "=f"(y) : "f"(x)); return y; }
__device__ __forceinline__ float sigmoidf_(float x) { return rcp_fast(1.f + ex2(-1.4426950408889634f * x)); }
__device__ __forceinline__ void top2(uint32_t k, uint32_t& k1, uint32_t& k2) {
    k1 = __reduce_max_sync(0xffffffffu, k);
    k2 = __reduce_max_sync(0xffffffffu, k == k1 ? 0 : k);
}

__device__ __forceinline__ void mod_fma(float (&a)[8], const uint4 w, float sc) {
    a[0] += sc * bf_lo(w.x); a[1] += sc * bf_hi(w.x); a[2] += sc * bf_lo(w.y); a[3] += sc * bf_hi(w.y);
    a[4] += sc * bf_lo(w.z); a[5] += sc * bf_hi(w.z); a[6] += sc * bf_lo(w.w); a[7] += sc * bf_hi(w.w);
}
__device__ __forceinline__ float mod_reduce(float (&a)[8], int lane) {
#pragma unroll
    for (int h = 4; h > 0; h >>= 1) {
        const bool up = lane & (8 / h);
#pragma unroll
        for (int i = 0; i < h; i++)
            a[i] = (up ? a[i + h] : a[i]) + __shfl_xor_sync(0xffffffffu, up ? a[i] : a[i + h], 8 / h);
    }
    return a[0] + __shfl_xor_sync(0xffffffffu, a[0], 16);
}

__device__ __forceinline__ float ln_stats(float sum, float sq, uint32_t& mean2) {
    const float mean = sum * (1.f / D_);
    const float var = fmaxf(fmaf(-mean, mean, sq * (1.f / D_)), 0.f);
    float sd;
    asm("sqrt.approx.ftz.f32 %0, %1;" : "=f"(sd) : "f"(rbf(rbf(var) + 1e-5f)));
    mean2 = pack_bf16(mean, mean);
    return rcp_fast(rbf(sd));
}
__device__ __forceinline__ uint32_t ln_pair(uint32_t x, uint32_t mean2, float rsd) {
    const uint32_t d = bsub2(x, mean2);
    return pack_bf16(bf_lo(d) * rsd, bf_hi(d) * rsd);
}
__device__ __forceinline__ void rows_load(uint32_t (&x)[20], uint32_t xs, int cw) {
#pragma unroll
    for (int ch = 0; ch < 5; ch++) {
        const uint4 v = ldsm4(ch < 4 ? xs + ch * 256 : xs + 1024 - cw * 16);
        x[4 * ch] = v.x; x[4 * ch + 1] = v.y; x[4 * ch + 2] = v.z; x[4 * ch + 3] = v.w;
    }
}
__device__ __forceinline__ void stats_add(float (&st)[12], uint32_t a, uint32_t b, uint32_t w) {
    mma1688(st, a, b, w);
    mma1688(st + 4, a, b, a);
    mma1688(st + 8, a, b, b);
}
__device__ __forceinline__ float rows_stats(const float (&st)[12], float4* rec, int cw, int lane, uint32_t& mean2, float& dot) {
    const int g8 = lane >> 2;
    if ((g8 >> 1) == (lane & 3)) {
        rec[cw * 16 + g8] = make_float4(st[0], (g8 & 1) ? st[5] : st[4], st[1], 0.f);
        rec[cw * 16 + 8 + g8] = make_float4(st[2], (g8 & 1) ? st[11] : st[10], st[3], 0.f);
    }
    bar_sync(3, 256);
    const float4* r = rec + (lane >> 4) * 64 + (lane & 15);
    const float4 s0 = r[0], s1 = r[16], s2 = r[32], s3 = r[48];
    const float sum = (s0.x + s1.x) + (s2.x + s3.x), sq = (s0.y + s1.y) + (s2.y + s3.y);
    dot = (s0.z + s1.z) + (s2.z + s3.z);
    dot += __shfl_xor_sync(0xffffffffu, dot, 16);
    return ln_stats(sum + __shfl_xor_sync(0xffffffffu, sum, 16), sq + __shfl_xor_sync(0xffffffffu, sq, 16), mean2);
}
template <class F>
__device__ __forceinline__ void rows_normalise(uint32_t* y, const uint32_t* x, uint32_t mean2, float rsd, int lane, F loads) {
    const int g8 = lane >> 2;
    const uint32_t ma2 = __shfl_sync(0xffffffffu, mean2, g8), mb2 = __shfl_sync(0xffffffffu, mean2, g8 + 8);
    const float ra = __shfl_sync(0xffffffffu, rsd, g8), rb = __shfl_sync(0xffffffffu, rsd, g8 + 8);
    loads();
#pragma unroll
    for (int k = 0; k < 9; k++) { y[2 * k] = ln_pair(x[2 * k], ma2, ra); y[2 * k + 1] = ln_pair(x[2 * k + 1], mb2, rb); }
}

__device__ __forceinline__ uint4 h_frag(const uint4* hf, int ks, int lane) {
    if (ks < 32) return ld_relaxed2(hf + ks * 32);
    const uint2* p = reinterpret_cast<const uint2*>(padd(hf, 256 - lane * 8) + ks * 32 - 16);
    const uint2 a = ld_relaxed64(p), b = ld_relaxed64(p + 32);
    return make_uint4(a.x, a.y, b.x, b.y);
}

__device__ __noinline__ void attn_fallback(uint32_t bad, uint32_t tag, const Scratch* gs, uint8_t* frag, uint8_t* keep, const bf16* wq, const bf16* kc, const bf16* vc) {
  const int lane = threadIdx.x & 31, g8 = lane >> 2, qd = lane & 3;
  const int role = cluster_role(), j = role & 7, qb = (role >> 3) * 2 + (blockIdx.x & 1);
  const uint4* hf = g_h + (size_t)(qb * 8 + (threadIdx.x >> 5) - 4) * (36 * 32) + lane;
#pragma unroll 1
  for (int t = 0; t < 4; t++) {
    if (!((bad >> t) & 1)) continue;
    const bf16 *wqp = wq + (4 * j + t) * DH, *kp = kc + (size_t)(2 * j + (t >> 1)) * S_ * DH, *vp = vc + (size_t)(2 * j + (t >> 1)) * S_ * DH;
    uint32_t q[32];
    float o[64];
#pragma unroll
    for (int i = 0; i < 64; i++) o[i] = 0.f;
#pragma unroll 1
    for (int ks = 0; ks < 36; ks++) {
        const uint4 a = h_frag(hf, ks, lane);
        const unsigned short* wr = reinterpret_cast<const unsigned short*>(wqp + (size_t)(ks * 16 + 2 * qd) * QD + g8);
#pragma unroll
        for (int dt = 0; dt < 16; dt++) {
            const uint32_t b0 = __ldg(wr + dt * 8) | ((uint32_t)__ldg(wr + dt * 8 + QD) << 16);
            const uint32_t b1 = __ldg(wr + dt * 8 + 8 * QD) | ((uint32_t)__ldg(wr + dt * 8 + 9 * QD) << 16);
            mma16816(o + 4 * dt, a.x, a.y, a.z, a.w, b0, b1);
        }
    }
#pragma unroll
    for (int i = 0; i < 32; i++) q[i] = pack_bf16(o[2 * i], o[2 * i + 1]);
#pragma unroll
    for (int i = 0; i < 64; i++) o[i] = 0.f;
    float m0 = -INFINITY, m1 = -INFINITY, l0 = 0.f, l1 = 0.f;
#pragma unroll 1
    for (int key = 0; key < S_; key += 16) {
        float sc[8];
#pragma unroll
        for (int i = 0; i < 8; i++) sc[i] = 0.f;
#pragma unroll
        for (int nt = 0; nt < 2; nt++) {
            const uint32_t* kr = reinterpret_cast<const uint32_t*>(kp + (size_t)(key + nt * 8 + g8) * DH) + qd;
#pragma unroll
            for (int ks = 0; ks < 8; ks++)
                mma16816(sc + 4 * nt, q[4 * ks], q[4 * ks + 1], q[4 * ks + 2], q[4 * ks + 3], __ldg(kr + ks * 8), __ldg(kr + ks * 8 + 4));
        }
        const float n0 = quad_max(fmaxf(fmaxf(m0, fmaxf(sc[0], sc[1])), fmaxf(sc[4], sc[5])));
        const float n1 = quad_max(fmaxf(fmaxf(m1, fmaxf(sc[2], sc[3])), fmaxf(sc[6], sc[7])));
        const float f0 = ex2((m0 - n0) * CS), f1 = ex2((m1 - n1) * CS);
        m0 = n0; m1 = n1;
#pragma unroll
        for (int i = 0; i < 8; i++) sc[i] = ex2((sc[i] - ((i & 2) ? n1 : n0)) * CS);
        l0 = l0 * f0 + (sc[0] + sc[1]) + (sc[4] + sc[5]);
        l1 = l1 * f1 + (sc[2] + sc[3]) + (sc[6] + sc[7]);
        const uint32_t e0 = pack_bf16(sc[0], sc[1]), e1 = pack_bf16(sc[2], sc[3]), e2 = pack_bf16(sc[4], sc[5]), e3 = pack_bf16(sc[6], sc[7]);
        const unsigned short* vr = reinterpret_cast<const unsigned short*>(vp + (size_t)(key + 2 * qd) * DH + g8);
#pragma unroll
        for (int dt = 0; dt < 16; dt++) {
            o[4 * dt] *= f0; o[4 * dt + 1] *= f0; o[4 * dt + 2] *= f1; o[4 * dt + 3] *= f1;
            const uint32_t b0 = __ldg(vr + dt * 8) | ((uint32_t)__ldg(vr + dt * 8 + DH) << 16);
            const uint32_t b1 = __ldg(vr + dt * 8 + 8 * DH) | ((uint32_t)__ldg(vr + dt * 8 + 9 * DH) << 16);
            mma16816(o + 4 * dt, e0, e1, e2, e3, b0, b1);
        }
    }
    const float i0 = 1.f / quad_sum(l0), i1 = 1.f / quad_sum(l1);
#pragma unroll
    for (int i = 0; i < 16; i++) {
        q[2 * i] = pack_bf16(o[4 * i] * i0, o[4 * i + 1] * i0);
        q[2 * i + 1] = pack_bf16(o[4 * i + 2] * i1, o[4 * i + 3] * i1);
    }
    frag_store(t < 3 ? frag + t * 4096 : keep, q);
  }
}

__device__ __forceinline__ void spare_q3(Scratch* gs, uint32_t sb, uint32_t bar_full, uint32_t bar_empty, int lane, int cw) {
    const uint32_t tag = load_tag(gs);
    uint32_t rel_base, e = 3;
    asm("mapa.shared::cluster.u32 %0, %1, %2;" : "=r"(rel_base) : "r"(bar_empty), "r"(lane & 1));
#pragma unroll 1
    for (int qb = blockIdx.x - NCTA; qb < 16; qb += 4) {
        uint32_t h[144];
        float o[64];
        flag_wait(&g_flag_h[(qb * 8 + cw) * 32], tag);
        const uint4* hf = g_h + (size_t)(qb * 8 + cw) * (36 * 32) + lane;
#pragma unroll
        for (int ks = 0; ks < 36; ks++) {
            const uint4 v = h_frag(hf, ks, lane);
            h[4 * ks] = v.x; h[4 * ks + 1] = v.y; h[4 * ks + 2] = v.z; h[4 * ks + 3] = v.w;
        }
#pragma unroll
        for (int i = 0; i < 64; i++) o[i] = 0.f;
#pragma unroll 1
        for (int v = 0; v < 4; v++) {
            fence_regs(o);
#pragma unroll
            for (int t = 0; t < 5; t++) {
                mbar_wait(bar_full + 8 * (e & 3), (e >> 2) & 1);
                uint64_t dv = mkdesc(sb + (e & 3) * SLOT, UNIT, 1024);
                WG_FENCE();
#pragma unroll
                for (int ks = 0; ks < (t < 4 ? 8 : 4); ks++)
                    mma_rs128<1>(o, h[32 * t + 4 * ks], h[32 * t + 4 * ks + 1], h[32 * t + 4 * ks + 2], h[32 * t + 4 * ks + 3], dv, ks | t);
                WG_COMMIT();
                if (t > 0) { WG_WAIT(1); if (lane < 2) mbar_arrive_cluster(rel_base + 8 * ((e - 1) & 3)); }
                e++;
            }
            WG_WAIT(0);
            fence_regs(o);
            if (lane < 2) mbar_arrive_cluster(rel_base + 8 * ((e - 1) & 3));
            uint4* dst = &g_q3[((qb * 8 + 2 * v) * 8 + cw) * 128 + lane];
#pragma unroll
            for (int i = 0; i < 8; i++)
                __stcg(dst + (i >> 2) * 1024 + (i & 3) * 32, make_uint4(pack_bf16(o[8 * i], o[8 * i + 1]), pack_bf16(o[8 * i + 2], o[8 * i + 3]),
                                                                        pack_bf16(o[8 * i + 4], o[8 * i + 5]), pack_bf16(o[8 * i + 6], o[8 * i + 7])));
        }
        bar_sync(3, 256);
        if (cw == 0 && lane == 0) flag_release(&g_flag_q3[qb * 32], tag);
        __syncwarp();
    }
}

template <bool SPARE>
__global__ void __cluster_dims__(2, 1, 1) __launch_bounds__(384, 1)
fused_kernel(const Args args, const __grid_constant__ CUtensorMap tm_wq,
             const __grid_constant__ CUtensorMap tm_k, const __grid_constant__ CUtensorMap tm_v,
             const __grid_constant__ CUtensorMap tm_wo, const __grid_constant__ CUtensorMap tm_p,
             const __grid_constant__ CUtensorMap tm_x, const __grid_constant__ CUtensorMap tm_d,
             const __grid_constant__ CUtensorMap tm_g, const __grid_constant__ CUtensorMap tm_u) {
    extern __shared__ __align__(1024) uint8_t smem_raw[];
    const uint32_t sb = smem_u32(smem_raw);
    Scratch* const gs = args.gs;
    const uint32_t bar_full = sb + SM_BAR;
    const uint32_t bar_g = bar_full + 8 * 4;
    const uint32_t bar_mod = bar_g + 8;
    const uint32_t bar_go = bar_mod + 8;
    const uint32_t bar_x = bar_go + 40;
    const uint32_t bar_empty = bar_x + 8;
    const uint32_t bar_pub = bar_empty + 8 * 4;
    const uint32_t bar_qfree = bar_pub + 32;
    const uint32_t bar_out = bar_qfree + 24;
    const uint32_t bar_q3 = bar_out + 8;
    const uint32_t bar_pre = bar_q3 + 16;
    const uint32_t bar_w0 = bar_q3 + 8;
    constexpr int E0 = SPARE ? 2 : 0;

    const int c = blockIdx.x & 1;
#define ROLES() const int role = cluster_role(), j = role & 7, qb = (role >> 3) * 2 + c, rg = qb * 8 + j
    const int warp = __shfl_sync(0xffffffffu, threadIdx.x >> 5, 0);

    if (SPARE && blockIdx.x >= NCTA && warp >= 4) {
        asm volatile("barrier.cluster.arrive.relaxed.aligned;" ::: "memory");
        asm volatile("setmaxnreg.inc.sync.aligned.u32 240;");
        asm volatile("barrier.cluster.wait.aligned;" ::: "memory");
        spare_q3(gs, sb, bar_full, bar_empty, threadIdx.x & 31, warp - 4);
        asm volatile("barrier.cluster.arrive.relaxed.aligned;\nbarrier.cluster.wait.aligned;" ::: "memory");
    } else if (warp < 4) {
        asm volatile("setmaxnreg.dec.sync.aligned.u32 24;");
        ROLES();
        int lane;
        asm volatile("mov.u32 %0, %%laneid;" : "=r"(lane));
        if (warp == 2 && elect()) {
            if (TMPF) asm volatile("prefetch.tensormap [%0];" ::"l"(&tm_x) : "memory");
#pragma unroll
            for (int i = 0; i < 27; i++) mbar_init(bar_full + 8 * i, i < 12 || i >= 23 ? 1 : i < 16 ? 16 : 8);
#pragma unroll
            for (int i = 0; i <= E0; i++) {
                mbar_arrive(bar_full + 8 * i);
                asm volatile("mbarrier.arrive.shared::cta.b64 _, [%0], 16;" ::"r"(bar_empty + 8 * i) : "memory");
            }
            asm volatile("fence.mbarrier_init.release.cluster;" ::: "memory");
        }
        __syncwarp();
        asm volatile("barrier.cluster.arrive.relaxed.aligned;" ::: "memory");
        if (warp == 2 && !(SPARE && blockIdx.x >= NCTA)) {
            if (XDELAY) __nanosleep(XDELAY);
            if (elect()) {
                mbar_expect_tx(bar_x, 16 * XP);
                tma2d(sb + SM_Q, &tm_x, 0, rg * 16, bar_x);
            }
            __syncwarp();
        }
        asm volatile("barrier.cluster.wait.aligned;" ::: "memory");
        const uint32_t tag = load_tag(gs);
        if (SPARE && blockIdx.x >= NCTA) {
            if (warp == 1) {
#pragma unroll 1
                for (int e = 3; e < 83; e++) {
                    const int v = (e - 3) / 5;
                    mbar_wait_sleep(bar_empty + 8 * (e & 3), ~(e >> 2) & 1);
                    if (elect()) {
                        mbar_expect_tx(bar_full + 8 * (e & 3), SLOT);
                        tma2d_mc(sb + (e & 3) * SLOT + c * UNIT, &tm_wq, (8 * (v & 3) + 4 * c + 3) * DH + 64, (e - 3 - v * 5) * 128,
                                 bar_full + 8 * (e & 3), EVICT_NORMAL);
                    }
                }
            }
            __syncwarp();
            asm volatile("barrier.cluster.arrive.relaxed.aligned;\nbarrier.cluster.wait.aligned;" ::: "memory");
            return;
        }
        if (warp == 3) {
#pragma unroll 1
            for (int e = 4; e < 20; e++) {
                __nanosleep(e == 4 ? PFD0 : PFD1);
                const int hd = (e * 52) >> 8, row = (e - hd * 5) * 128 + qb * 8 + (lane >> 1);
                if (lane < 16 && row < D_)
                    asm volatile("prefetch.global.L2 [%0];" ::"l"(padd(args.wq, (row * QD + (4 * j + ((0x1320 >> (4 * hd)) & 3)) * DH + (lane & 1) * 64) * 2)) : "memory");
            }
            __syncwarp();
            mbar_wait_sleep(bar_go, 0);
#pragma unroll 1
            for (int unit = 72 + blockIdx.x; unit < 216; unit += NCTA) {
                float a[8];
#pragma unroll
                for (int i = 0; i < 8; i++) a[i] = 0.f;
#pragma unroll 1
                for (int k = lane >> 1; k < D_; k += 16) {
                    const float cv = __bfloat162float(*padd(args.cvec, k * 2));
                    mod_fma(a, __ldg(reinterpret_cast<const uint4*>(padd(args.w_mod, (k * (6 * D_) + unit * 16 + (lane & 1) * 8) * 2))), rbf(cv * sigmoidf_(cv)));
                }
                const float v = mod_reduce(a, lane), v1 = __shfl_down_sync(0xffffffffu, v, 8);
                if (lane < 8) *padd(gs->mod2, ((unit - 72) * 8 + (lane & 1) * 4 + (lane & 2) + (lane >> 2)) * 4) = pack_bf16(v, v1);
            }
            __syncwarp();
            if (lane == 0) flag_release(padd(g_flag_mod, blockIdx.x * 4), tag);
#pragma unroll 1
            for (int k = 0; k < 36; k++) {
                __nanosleep(200);
                __stcg(padd(gs->h[0], (~tag & 1) * (NCTA * 36 * 512) + ((rg * 36 + k) * 32 + lane) * 16), make_uint4(0, 0, 0, 0));
            }
            __syncwarp();
            mbar_wait_sleep(bar_qfree + 16, 0);
            __nanosleep(2000);
            {
                uint4 v;
                uint32_t it = 0;
#pragma unroll 1
                do {
                    v = ld_relaxed(reinterpret_cast<const uint4*>(padd(g_flag_mod, lane * 16)));
                } while (((v.x ^ tag) | (v.y ^ tag) | (v.z ^ tag) | (v.w ^ tag)) && ++it < SPIN / 16);
                asm volatile("fence.acquire.gpu;" ::: "memory");
            }
            __syncwarp();
            {
                float w1 = 0.f, w2 = 0.f;
#pragma unroll 1
                for (int k = lane; k < D_ / 2; k += 32) {
                    const uint32_t* mp = padd(gs->mod2, k * 4);
                    const uint32_t sv = __ldcg(mp + D_ / 2), c1 = badd2(__ldcg(mp + D_), 0x3f803f80u);
                    const uint32_t wr = *reinterpret_cast<const uint32_t*>(padd(args.w_r, k * 4)), wp = bmul2(c1, wr);
                    reinterpret_cast<uint2*>(smem_raw + SM_T)[k] = make_uint2(__ldcg(mp), wp);
                    reinterpret_cast<uint2*>(smem_raw + SM_TC)[k] = make_uint2(c1, sv);
                    reinterpret_cast<uint32_t*>(smem_raw + SM_TG)[k] = __ldcg(mp + 3 * D_ / 2);
                    w1 += bf_lo(wp) + bf_hi(wp);
                    w2 += bf_lo(sv) * bf_lo(wr) + bf_hi(sv) * bf_hi(wr);
                }
#pragma unroll 1
                for (int i = 1; i < 32; i <<= 1) { w1 += __shfl_xor_sync(0xffffffffu, w1, i); w2 += __shfl_xor_sync(0xffffffffu, w2, i); }
                *reinterpret_cast<float2*>(smem_raw + SM_TS) = make_float2(w1, w2);
            }
#pragma unroll
            for (int i = 0; i < 4; i++) reinterpret_cast<uint4*>(smem_raw + SM_RED)[lane + 32 * i] = make_uint4(~0u, ~0u, ~0u, ~0u);
            asm volatile("fence.proxy.async.shared::cta;" ::: "memory");
            __syncwarp();
            if (elect()) {
                uint8_t* mb = g_frag + (size_t)rg * 8 * WREG + 3 * 4096;
#pragma unroll 1
                for (int k = 0; k < 8; k++, mb += WREG) {
#pragma unroll
                    for (int i = 0; i < 3; i++)
                        asm volatile("cp.async.bulk.global.shared::cta.bulk_group [%0], [%1], 2048;" ::"l"(mb + i * 2048), "r"(sb + SM_RED) : "memory");
                    __nanosleep(500);
                }
                asm volatile("cp.async.bulk.commit_group;\ncp.async.bulk.wait_group 0;\nfence.proxy.async.global;" ::: "memory");
            }
            __syncwarp();
            if (lane == 0) mbar_arrive(bar_mod);
            __syncwarp();
            mbar_wait_sleep(bar_go + 8, 0);
            if (elect()) asm volatile("prefetch.tensormap [%0];\nprefetch.tensormap [%1];\nprefetch.tensormap [%2];" ::"l"(&tm_x), "l"(&tm_p), "l"(&tm_d) : "memory");
            __syncwarp();
#pragma unroll 1
            for (int i = 1; i < 4; i++) {
                mbar_wait(bar_pub + 8 * i, 0);
                unsigned int* flags = padd(g_flag_part, (qb * 32 + i * 8 - 8) * 4);
                if (elect()) { flag_release(padd(flags, j * 4), tag); DBG_PG(93); }
                __syncwarp();
                const uint32_t slot = i < 3 ? i + 1 : 1;
                flag_wait(padd(flags, (lane & 7) * 4), tag);
                asm volatile("fence.proxy.async.global;" ::: "memory");
                if (lane == 0 && i == 3) DBG_PG(101);
                mbar_wait(bar_go + 8 + 8 * i, 0);
                mbar_wait(bar_empty + 8 * slot, i != 1);
                if (elect()) {
                    mbar_expect_tx(bar_full + 8 * slot, SLOT);
                    tma3d(sb + slot * SLOT, &tm_p, 0, j * 20 + (i - 1) * 4, qb * 8, bar_full + 8 * slot);
                    tma3d(sb + slot * SLOT + UNIT, &tm_p, 0, j * 20 + (i - 1) * 4 + 2, qb * 8, bar_full + 8 * slot);
                }
            }
        } else if (warp == 0) {
#pragma unroll 1
            for (int i = 0; i < 48; i++) {
                if (i == 0 || i == 17 || i == 34) mbar_wait_sleep(bar_qfree + (i >> 4) * 8, 0);
                if (SPARE && i == 17) {
                    flag_wait(&g_flag_q3[qb * 32], tag);
                    if (elect()) {
                        asm volatile("fence.proxy.async.global;" ::: "memory");
                        mbar_expect_tx(bar_q3, UNIT);
#pragma unroll 1
                        for (int k = 0; k < 8; k++) bulk_load(sb + SM_Q + 2 * SLOT + k * 4096 + 2048, &g_q3[(rg * 8 + k) * 128], 2048, bar_q3);
                    }
                }
                __nanosleep(700);
                if (elect()) {
                    asm volatile("mbarrier.expect_tx.shared::cta.b64 [%0], %1;" ::"r"(bar_g), "n"(1920) : "memory");
                    tma2d(sb + SM_Q + i * 1920, i < 24 ? &tm_g : &tm_u, (blockIdx.x * 36) & ~7, (i < 24 ? i : i - 24) * 24, bar_g);
                }
            }
            if (elect()) mbar_arrive(bar_g);
#pragma unroll 1
            for (int i = 0; i < 18; i++) {
                __nanosleep(400);
                if (OPF && i < 8 * OPF && elect()) l2_prefetch(g_frag + (size_t)(rg * 8 + (i & 7)) * WREG + (i >> 3) * 4096, 4096);
                if (elect()) l2_prefetch(args.w_down + (size_t)(blockIdx.x * 36 + i * 2) * D_, 4 * D_);
            }
            __syncwarp();
            mbar_wait_sleep(bar_go + 8 * 2, 0);
            uint32_t acc = 0;
#pragma unroll 1
            for (int k = lane; k < 16 * 9; k += 32) acc |= touch(padd(args.x, (rg * 16 * D_ + k * 64) * 2));
            if (acc == 0) reinterpret_cast<volatile uint32_t*>(smem_raw + SM_BAR)[127] = acc;
            __syncwarp();
            mbar_wait_sleep(bar_go + 8 * 4, 0);
            uint4* rp = padd(g_rows, (rg * 2 * RSLOT + lane) * 16);
#pragma unroll
            for (int k = 0; k < 12; k++) rp[k * 32] = make_uint4(~0u, ~0u, ~0u, ~0u);
            if (blockIdx.x < 72) {
                uint4* yp = reinterpret_cast<uint4*>(padd(g_ypart, blockIdx.x * NCTA * 64 + lane * 16));
#pragma unroll
                for (int k = 0; k < 16; k++) yp[k * 32] = make_uint4(~0u, ~0u, ~0u, ~0u);
            }
            asm volatile("fence.acq_rel.gpu;" ::: "memory");
            __syncwarp();
            if (lane == 0) mbar_arrive(bar_pre);
        } else if (warp == 1) {
            __nanosleep(QDELAY);
            uint32_t go = bar_go;
            uint64_t marks = 24 | 151 << 8 | 154 << 16 | 159ull << 24 | 165ull << 32;
#pragma unroll 1
            for (int e = E0; e < 168; e++) {
                const CUtensorMap* tm;
                int c0, c1;
                uint64_t pol = EVICT_FIRST;
                if (e == 158 || e == 163) continue;
                if (e < 21 && e != 19) {
                    const int i = SPARE && e < 12 ? e - 2 : e - (e == 20), hd = (i * 52) >> 8;
                    tm = &tm_wq; c0 = (4 * j + ((0x1320 >> (4 * hd)) & 3)) * DH + c * 64; c1 = (i - hd * 5) * 128 - 64;
                    if (SPARE && e >= 12 && e < 15) { c0 = (4 * j + 3) * DH; c1 = (2 * (e - 12) + c) * 128; }
                } else if (e < 148) {
                    const int i = max(e - 20, 0);
                    const bool isk = i == 0 || ((i & 1) && i < 127);
                    const int n = isk ? (i + 1) >> 1 : (i - 1) >> 1;
                    tm = isk ? &tm_k : &tm_v; c0 = c * 64; c1 = (2 * j + (n >> 5)) * S_ + (n & 15) * 128;
                    if (!(i & 32)) pol = EVICT_NORMAL;
                } else {
                    int i = e - 148 - (e > 158) - (e > 163);
                    tm = &tm_wo; c0 = (i >> 1) * 64; c1 = (4 * j + (O2F ? ((i & 1) ? c : 2 + c) : (i & 1) ? 1 + c : 3 * c)) * DH;
                }
                const uint32_t fb = e == E0 ? bar_w0 : bar_full + 8 * (e & 3), d = sb + (e == E0 ? 6 : e & 3) * SLOT;
                if (e >= 24 && e < 152) mbar_wait_sleep(bar_empty + 8 * (e & 3), ~(e >> 2) & 1);
                else if (e != E0) mbar_wait(bar_empty + 8 * (e & 3), ~(e >> 2) & 1);
                if (elect()) {
                    mbar_expect_tx(fb, SLOT);
                    tma2d_mc(d + c * UNIT, tm, c0, c1, fb, pol);
                    const int i = e - PF_KV;
                    if (i >= 0 && i < 128 && !(i & 32))
                        l2_prefetch(((i & 1) ? args.vc : args.kc) + (size_t)((2 * j + (i >> 6)) * S_ + (i & 30) * 64) * DH + qb * 1024, 2048);
                    if (e >= PF_WO && e < PF_WO + 18) l2_prefetch(args.wo + (size_t)blockIdx.x * (QD * D_ / NCTA) + (e - PF_WO) * 1024, 2048);
                    if (e == (marks & 255)) mbar_arrive(go);
                }
                if (e == (marks & 255)) { go += 8; marks >>= 8; }
            }
            asm volatile("fence.proxy.async.global;" ::: "memory");
            mbar_wait(bar_empty, 1);
            if (elect()) {
                mbar_expect_tx(bar_full, 16 * XP);
                tma2d(sb, &tm_x, 0, rg * 16, bar_full);
            }
            mbar_wait(bar_empty + 16, 1);
            if (C3D) __nanosleep(C3D);
            if (elect()) {
                mbar_expect_tx(bar_full + 16, SLOT);
                tma3d(sb + 2 * SLOT, &tm_p, 0, j * 20 + 12, qb * 8, bar_full + 16);
                tma3d(sb + 2 * SLOT + UNIT, &tm_p, 0, j * 20 + 14, qb * 8, bar_full + 16);
            }
            mbar_wait(bar_empty + 24, 1);
            if (C4D) __nanosleep(C4D);
            if (elect()) {
                mbar_expect_tx(bar_full + 24, UNIT);
                tma3d(sb + 3 * SLOT, &tm_p, 0, j * 20 + 16, qb * 8, bar_full + 24);
            }
            mbar_wait(bar_empty + 8, 0);
            mbar_wait(bar_empty + 16, 0);
            if (DD) __nanosleep(DD);
            if (elect()) {
#pragma unroll
                for (int i = 1; i < 3; i++) {
                    mbar_expect_tx(bar_full + 8 * i, 18 * XP);
                    tma2d(sb + i * SLOT, &tm_d, 0, blockIdx.x * 36 + (i - 1) * 18, bar_full + 8 * i);
                }
            }
        } else {
            if (elect()) asm volatile("prefetch.tensormap [%0];\nprefetch.tensormap [%1];\nprefetch.tensormap [%2];" ::"l"(&tm_k), "l"(&tm_v), "l"(&tm_wo) : "memory");
            if (SPARE) {
                mbar_wait_sleep(bar_pub, 0);
                if (lane == 0) flag_release(padd(g_flag_h, rg * 128), tag);
                __syncwarp();
            }
            bar_sync(1, 192);
#pragma unroll 1
            for (uint32_t e = 20; e < 148; e++) {
                mbar_wait_sleep(bar_full + 8 * (e & 3), (e >> 2) & 1);
                if (SPARE && e == 113) mbar_wait(bar_q3, 0);
                if (e & 1) bar_sync(1, 192);
                if (!(e & 1) || e == 147) bar_sync(4, 160);
            }
#pragma unroll 1
            for (uint32_t e = 148; e < 168; e++) {
                mbar_wait(bar_full + 8 * (e & 3), (e >> 2) & 1);
                if (e != 158 && e != 163) bar_sync(1, 192);
            }
        }
        __syncwarp();
        mbar_wait_sleep(bar_out, 0);
        if (OUTD) __nanosleep(OUTD);
        if (elect()) {
            asm volatile("fence.proxy.async.shared::cta;" ::: "memory");
            const int2 sel = reinterpret_cast<const int2*>(smem_raw + SM_RED)[8];
#pragma unroll 1
            for (int i = warp; i < 16; i += 4) {
                const int row = rg * 16 + i;
                if (row != sel.x && row != sel.y)
                    asm volatile("cp.async.bulk.global.shared::cta.bulk_group.L2::cache_hint [%0], [%1], %2, %3;"
                                 ::"l"(args.out + (size_t)row * D_), "r"(sb + i * XP), "n"(D_ * 2), "l"(OUTPOL) : "memory");
            }
            asm volatile("cp.async.bulk.commit_group;\ncp.async.bulk.wait_group.read 0;" ::: "memory");
        }
    } else {
        uint32_t cv[2] = {0, 0}, tag = load_tag(gs) - 1;
        if (blockIdx.x < 72) {
            uint32_t ws;
            int tid;
            asm volatile("mov.u32 %0, smem_raw;\nmov.u32 %1, %%tid.x;" : "=r"(ws), "=r"(tid));
            tid -= 128;
            ws += SM_Q + SLOT + tid * 16;
            const uint32_t* cp = padd(reinterpret_cast<const uint32_t*>(args.cvec), (tid & 0xe0) + (tid & 7) * 4);
            cv[0] = *padd(cp, (tid & 24) * 32);
            if (tid < 128) cv[1] = cp[256];
            const bf16* wrow = args.w_mod + (size_t)(tid >> 1) * (6 * D_) + (tid & 1) * 8 + blockIdx.x * 16;
#pragma unroll
            for (int i = 0; i < 5; i++)
                if (i < 4 || tid < 128)
                    asm volatile("cp.async.cg.shared.global [%0], [%1], 16;" ::"r"(ws + i * 4096), "l"(wrow + (size_t)i * 128 * (6 * D_)) : "memory");
        }
        asm volatile("barrier.cluster.arrive.relaxed.aligned;" ::: "memory");
        asm volatile("setmaxnreg.inc.sync.aligned.u32 240;");
        const int lane = threadIdx.x & 31;
        const int cw = warp - 4;
        const int w = cw >> 2;
        const int tid = threadIdx.x - 128;
        ROLES();
        float* red = reinterpret_cast<float*>(smem_raw + SM_RED);
        DBG_INIT();
        DBG_G(120);
        DBG_T(100);

        {
            if (blockIdx.x < 72) {
                uint32_t sa[10];
#pragma unroll
                for (int i = 0; i < 2; i++) {
                    const float lo = bf_lo(cv[i]), hi = bf_hi(cv[i]);
                    cv[i] = pack_bf16(lo * sigmoidf_(lo), hi * sigmoidf_(hi));
                }
#pragma unroll
                for (int i = 0; i < 10; i++) sa[i] = __shfl_sync(0xffffffffu, cv[i >> 3], (i & 7) * 4 + (lane & 3));
                uint2* mdst = &gs->mod1[(tid >> 3) * D_ + blockIdx.x * 8 + (tid & 7)];
                anchor(bar_full + 504, sa[0] & sa[1] & sa[2] & sa[3] & sa[4] & sa[5] & sa[6] & sa[7] & sa[8] & sa[9] & (uint32_t)(uintptr_t)mdst & (uint32_t)((uintptr_t)mdst >> 32));
                asm volatile("cp.async.wait_all;" ::: "memory");
                __syncwarp();
                const uint32_t ws = sb + SM_Q + SLOT + cw * 512 + (lane & 15) * 32 + (lane & 16);
                float d[16];
#pragma unroll
                for (int i = 0; i < 16; i++) d[i] = 0.f;
#pragma unroll
                for (int i = 0; i < 5; i++) {
                    const uint4 b = ldsm4t(ws + (i < 4 || cw < 4 ? i * 4096 : 0));
                    mma16816(d + 8 * (i & 1), sa[2 * i], sa[2 * i], sa[2 * i + 1], sa[2 * i + 1], b.x, b.y);
                    mma16816(d + 8 * (i & 1) + 4, sa[2 * i], sa[2 * i], sa[2 * i + 1], sa[2 * i + 1], b.z, b.w);
                }
                if (lane < 8) reinterpret_cast<float2*>(red)[lane * 8 + cw] = (lane & 4) ? make_float2(d[4] + d[12], d[5] + d[13]) : make_float2(d[0] + d[8], d[1] + d[9]);
                bar_sync(3, 256);
                if (tid < 8 * MREP) {
                    const float4* r = reinterpret_cast<const float4*>(red) + (tid & 7) * 4;
                    const float4 r0 = r[0], r1 = r[1], r2 = r[2], r3 = r[3];
                    st_relaxed64(mdst, pack_bf16(((r0.x + r0.z) + (r1.x + r1.z)) + ((r2.x + r2.z) + (r3.x + r3.z)),
                                                 ((r0.y + r0.w) + (r1.y + r1.w)) + ((r2.y + r2.w) + (r3.y + r3.w))), tag + 1);
                }
            }
            DBG_G(106);
            asm volatile("barrier.cluster.wait.aligned;" ::: "memory");
            mbar_wait(bar_x, 0);
            asm volatile("add.u32 %0, %0, 1;" : "+r"(tag));
            uint32_t x[20];
            float st[12], st2[12];
            rows_load(x, sb + SM_Q + (lane & 15) * XP + (lane >> 4) * 16 + cw * 32, cw);
#pragma unroll
            for (int i = 0; i < 12; i++) { st[i] = 0.f; st2[i] = 0.f; }
#pragma unroll
            for (int k = 0; k < 9; k++) stats_add((k & 1) ? st2 : st, x[2 * k], x[2 * k + 1], 0x3f803f80u);
#pragma unroll
            for (int i = 0; i < 12; i++) st[i] += st2[i];
            uint32_t mean2;
            float dot;
            const float rsd = rows_stats(st, reinterpret_cast<float4*>(red + 128), cw, lane, mean2, dot);
            const uint4* mp = reinterpret_cast<const uint4*>(gs->mod1 + ((blockIdx.x >> 1) & (MREP - 1)) * D_) + min(tid, D_ / 4 - 1);
            uint4 v0 = make_uint4(0, tag, 0, tag), v1 = v0;
            auto look = [&]() {
                asm volatile("{\n.reg .pred p;\n.reg .b64 a, b, c, d;\nsetp.lt.s32 p, %9, 5;\nmov.b64 a, {%0, %1};\nmov.b64 b, {%2, %3};\n"
                             "mov.b64 c, {%4, %5};\nmov.b64 d, {%6, %7};\n@p ld.relaxed.gpu.global.v2.b64 {a, b}, [%8];\n"
                             "@p ld.relaxed.gpu.global.v2.b64 {c, d}, [%8 + 2304];\n"
                             "mov.b64 {%0, %1}, a;\nmov.b64 {%2, %3}, b;\nmov.b64 {%4, %5}, c;\nmov.b64 {%6, %7}, d;\n}"
                             : "+r"(v0.x), "+r"(v0.y), "+r"(v0.z), "+r"(v0.w), "+r"(v1.x), "+r"(v1.y), "+r"(v1.z), "+r"(v1.w)
                             : "l"(mp), "r"(cw) : "memory");
            };
            rows_normalise(x, x, mean2, rsd, lane, look);
            fence_regs(x);
            uint32_t it = 0;
#pragma unroll 1
            while (((v0.y ^ tag) | (v0.w ^ tag) | (v1.y ^ tag) | (v1.w ^ tag)) && ++it < SPIN / 16) look();
            uint4* smod = reinterpret_cast<uint4*>(smem_raw + SM_Q + M_MOD);
            if (tid < D_ / 4) smod[tid] = make_uint4(badd2(v1.x, 0x3f803f80u), v0.x, badd2(v1.z, 0x3f803f80u), v0.z);
            uint4* hdst = g_h + (size_t)(rg * 36 + cw) * 32 + lane;
            uint2* hdst2 = reinterpret_cast<uint2*>(g_h + (size_t)(rg * 36 + 32) * 32) + tid;
            bar_sync(3, 256);
            DBG_G(107);
#pragma unroll
            for (int k = 0; k < 9; k++) {
                const uint2 cs = lds64(sb + SM_Q + M_MOD + (cw * 8 + (lane & 3) + (k < 8 ? (k >> 1) * 64 + (k & 1) * 4 : 256 - cw * 4)) * 8);
                const uint32_t c1 = cs.x, sa = cs.y;
                x[2 * k] = badd2(bmul2(x[2 * k], c1), sa);
                if (x[2 * k] == 0) x[2 * k] = 0x8000u;
                x[2 * k + 1] = badd2(bmul2(x[2 * k + 1], c1), sa);
            }
#pragma unroll
            for (int ch = 0; ch < 4; ch++) st_relaxed4(hdst + ch * 256, x[4 * ch], x[4 * ch + 1], x[4 * ch + 2], x[4 * ch + 3]);
            st_relaxed64(hdst2, x[16], x[17]);
            __syncwarp();
            if (SPARE && lane == 0) mbar_arrive(bar_pub);
            DBG_G(108);
        }

        uint32_t rel_base;
        asm("mapa.shared::cluster.u32 %0, %1, %2;" : "=r"(rel_base) : "r"(bar_empty), "r"(lane & 1));
        auto release = [&](uint32_t slot) { if (lane < 2) mbar_arrive_cluster(rel_base + 8 * slot); };
        uint32_t q[32], p[32];
        float s[64], o[64];

        uint4* qpark = reinterpret_cast<uint4*>(smem_raw + SM_Q - SLOT) + cw * 256 + lane;
        {
            uint32_t h[144];
            const uint4* hf = g_h + (size_t)(qb * 8 + cw) * (36 * 32) + lane;
            auto load_h = [&](auto lo, auto hi) {
#pragma unroll
                for (int ks = lo.value; ks < hi.value; ks++) {
                    const uint4 v = h_frag(hf, ks, lane);
                    h[4 * ks] = v.x; h[4 * ks + 1] = v.y; h[4 * ks + 2] = v.z; h[4 * ks + 3] = v.w;
                }
            };
            auto check_h = [&](auto lo, auto hi) {
                uint32_t it = 0;
                bool miss;
#pragma unroll 1
                do {
                    uint32_t mn = ~0u;
#pragma unroll
                    for (int ks = lo.value; ks < hi.value; ks++) mn = __vimin3_u32(mn, h[4 * ks], h[4 * ks + 2]);
                    miss = __any_sync(0xffffffffu, mn == 0);
                    if (miss) load_h(lo, hi);
                    asm volatile("add.u32 %0, %0, 1;" : "+r"(it));
                } while (miss && it < SPIN / 16);
            };
            __nanosleep(HDELAY);
            load_h(IC<0>{}, IC<4>{});
            DBG_T(104); DBG_G(109);
#pragma unroll
            for (int i = 0; i < 64; i++) o[i] = 0.f;
            uint32_t e = E0;
#pragma unroll 1
            for (int hd = 1;; hd++) {
                fence_regs(o);
                auto group = [&](auto tc) {
                    constexpr int t = tc.value, k0 = t ? 8 * t - 4 : 0;
                    const bool first = t == 0 && hd == 1;
                    mbar_wait(first ? bar_w0 : bar_full + 8 * (e & 3), (e >> 2) & 1);
                    uint64_t dv = args.d0 + ((t ? 0 : 512) + (first ? 6 : e & 3) * (SLOT / 16));
                    if (hd == 1) check_h(IC<k0>{}, IC<8 * t + 4>{});
                    WG_FENCE();
#pragma unroll
                    for (int ks = k0; ks < 8 * t + 4; ks++)
                        mma_rs128<1>(o, h[4 * ks], h[4 * ks + 1], h[4 * ks + 2], h[4 * ks + 3], dv, ks);
                    WG_COMMIT();
                    if (hd == 1) { if (t == 0) {   } if (t == 1) {   } if (t == 2) {   } if (t == 3) {   } if (t == 4) {   } }
                    if (t < 4 && hd == 1) load_h(IC<8 * t + 4>{}, IC<t < 4 ? 8 * t + 12 : 0>{});
                    if (t > 0) { WG_WAIT(1); if (t > 1 || hd > 1) release((e - 1) & 3); }
                    e++;
                };
                group(IC<0>{}); group(IC<1>{}); group(IC<2>{}); group(IC<3>{});
                if (e == 19) break;
                group(IC<4>{});
                WG_WAIT(0);
                if (hd == 1) {     }
                fence_regs(o);
                release((e - 1) & 3);
#pragma unroll
                for (int i = 0; i < 8; i++)
                    qpark[hd * 2048 + i * 32] = make_uint4(pack_bf16(o[8 * i], o[8 * i + 1]), pack_bf16(o[8 * i + 2], o[8 * i + 3]),
                                                           pack_bf16(o[8 * i + 4], o[8 * i + 5]), pack_bf16(o[8 * i + 6], o[8 * i + 7]));
                if (SPARE && hd == 2) {
                    float (&u)[32] = reinterpret_cast<float (&)[32]>(o);
                    fence_regs(u);
#pragma unroll
                    for (int t = 0; t < 3; t++) {
                        mbar_wait(bar_full + 8 * t, 1);
                        uint64_t dv = args.d0 + t * (SLOT / 16);
                        WG_FENCE();
#pragma unroll
                        for (int ks = 0; ks < (t < 2 ? 16 : 4); ks++)
                            mma_rs64<1>(u, h[64 * t + 4 * ks], h[64 * t + 4 * ks + 1], h[64 * t + 4 * ks + 2], h[64 * t + 4 * ks + 3],
                                        dv, ks | t);
                        WG_COMMIT();
                        if (t > 0) { WG_WAIT(1); release(t - 1); }
                    }
                    WG_WAIT(0);
                    fence_regs(u);
                    release(2);
                    e = 15;
#pragma unroll
                    for (int i = 0; i < 4; i++)
                        qpark[3 * 2048 + i * 32] = make_uint4(pack_bf16(u[8 * i], u[8 * i + 1]), pack_bf16(u[8 * i + 2], u[8 * i + 3]),
                                                              pack_bf16(u[8 * i + 4], u[8 * i + 5]), pack_bf16(u[8 * i + 6], u[8 * i + 7]));
                }
            }
#pragma unroll
            for (int i = 0; i < 8; i++) {
                const uint4 v = qpark[2048 + i * 32];
                q[4 * i] = v.x; q[4 * i + 1] = v.y; q[4 * i + 2] = v.z; q[4 * i + 3] = v.w;
            }
#pragma unroll
            for (int i = 0; i < 32; i++) p[i] = h[112 + i];
            mbar_wait(bar_full + 24, 0);
            WG_WAIT(0);
            fence_regs(o);
            release(2);
        }
        DBG_T(105);
        DBG_G(125);

        uint8_t* frag = reinterpret_cast<uint8_t*>(__shfl_sync(0xffffffffu, reinterpret_cast<unsigned long long>(g_frag + (size_t)(rg * 8 + cw) * WREG + lane * 16), lane));
        const uint4* qnext = reinterpret_cast<const uint4*>(__shfl_sync(0xffffffffu, reinterpret_cast<unsigned long long>(padd(smem_raw, SM_Q + tid * 16 + cw * 3584)), lane));
        uint8_t* odst = reinterpret_cast<uint8_t*>(const_cast<uint4*>(qnext));
        qnext -= 2048;
        float m0, m1, l0 = 0.25f, l1 = 0.25f, t0, t1;
        uint32_t bad = 0;
        const int lw = cw & 3;
        const uint32_t relw = lw == RW && lane < 8, handw = lw == HW || cw == HW2;
        auto release4 = [&](uint32_t off) {
            asm volatile("{\n.reg .pred p;\nsetp.ne.b32 p, %1, 0;\n@p mbarrier.arrive.shared::cluster.b64 _, [%0];\n}" ::"r"(rel_base + off), "r"(relw) : "memory"); };
        auto handoff = [&]() {
            asm volatile("{\n.reg .pred p;\nsetp.ne.b32 p, %1, 0;\n@p bar.arrive %0, 192;\n}" ::"r"(2 - w), "r"(handw) : "memory"); };
        if (cw == 4 + HW) bar_arrive(1, 192);
        auto finish = [&](auto lo, auto hi, uint32_t bit, auto sink) {
#pragma unroll
            for (int i = lo.value; i < hi.value; i++) {
                const uint32_t v0 = pack_bf16(o[8 * i] * t0, o[8 * i + 1] * t0), v1 = pack_bf16(o[8 * i + 2] * t1, o[8 * i + 3] * t1);
                const uint32_t v2 = pack_bf16(o[8 * i + 4] * t0, o[8 * i + 5] * t0), v3 = pack_bf16(o[8 * i + 6] * t1, o[8 * i + 7] * t1);
                if (i == 0 && fabsf(o[0] * t0) >= 0x1p-31f) bad |= bit << 8;
                sink(i, v0, v1, v2, v3);
            }
        };
        float lq[6];
        auto row_parts = [&]() {
#pragma unroll
            for (int i = 0; i < 3; i++) { lq[i] = __shfl_xor_sync(0xffffffffu, l0, i + 1); lq[3 + i] = __shfl_xor_sync(0xffffffffu, l1, i + 1); }
        };
        auto row_sums = [&](uint32_t bit) {
            t0 = (l0 + lq[0]) + (lq[1] + lq[2]); t1 = (l1 + lq[3]) + (lq[4] + lq[5]);
            if (!(t0 >= LMIN && t0 < LMAX && t1 >= LMIN && t1 < LMAX)) bad |= bit;
        };
        auto issue_pv = [&](uint64_t dv, int acc, auto lo, auto hi) {
            if (lo.value == 0) asm volatile("{\n.reg .pred p;\nsetp.eq.b32 p, %0, 0;\n@p bar.sync 4, 160;\n}" ::"r"(w) : "memory");
#pragma unroll
            for (int ks = lo.value; ks < hi.value; ks++)
                mma_rs128<1>(o, p[4 * ks], p[4 * ks + 1], p[4 * ks + 2], p[4 * ks + 3], dv, ks ? 1 : acc);
            WG_COMMIT();
        };
#pragma unroll
        for (int i = 0; i < 64; i++) s[i] = 0.f;
        uint64_t dv_lo = args.d0;
        uint32_t voff = 0;
        auto issue_qk = [&]() {
            uint64_t dk = dv_lo ^ (desc_lo(0, UNIT) ^ desc_lo(3 * SLOT, 16));
            bar_sync(1 + w, 192);
            fence_regs(s); fence_regs(q); fence_regs(o); fence_regs(p);
            WG_FENCE();
#pragma unroll
            for (int ks = 0; ks < 8; ks++)
                if (ks == 3) mma_rs128<0, 1018>(s, q[4 * ks], q[4 * ks + 1], q[4 * ks + 2], q[4 * ks + 3], dk, 1);
                else mma_rs128<0, 2>(s, q[4 * ks], q[4 * ks + 1], q[4 * ks + 2], q[4 * ks + 3], dk, ks != 0);
            WG_COMMIT();
        };
        auto to_frag = [&](int i, uint32_t v0, uint32_t v1, uint32_t v2, uint32_t v3) {
            *reinterpret_cast<uint4*>(odst + i * 512) = make_uint4(v0, v1, v2, v3); };
        int n = 0;
        auto scores_ready = [&]() {
            WG_WAIT(1);
            fence_regs(s); fence_regs(q);
        };
        auto pass_on = [&]() {
            release4(voff ^ 24);
            handoff();
        };
#pragma unroll 1
        for (;;) {
            {
                if (RPE) {
                    asm volatile("st.shared.v2.f32 [%0], {%1, %2};" ::"r"(sb + SM_RED + tid * 8), "f"(l0), "f"(l1) : "memory");
                    __syncwarp();
                    const uint4 a = lds128(sb + SM_RED + (tid & ~3) * 8), b = lds128(sb + SM_RED + (tid & ~3) * 8 + 16);
                    l0 = __uint_as_float(a.x); lq[0] = __uint_as_float(a.z); lq[1] = __uint_as_float(b.x); lq[2] = __uint_as_float(b.z);
                    l1 = __uint_as_float(a.y); lq[3] = __uint_as_float(a.w); lq[4] = __uint_as_float(b.y); lq[5] = __uint_as_float(b.w);
                } else {
                    row_parts();
                }
                issue_qk();
                if (RPE == 2) hold(l0, l1);
                row_sums(1u << (n >> 4));
                t0 = rcp_fast(t0); t1 = rcp_fast(t1);
                l0 = 0.f; l1 = 0.f;
                odst = n ? frag + ((n >> 4) - 1) * 4096 : odst;
                qnext = n == 48 ? reinterpret_cast<const uint4*>(frag + O2F * 8192) : qnext + 2048;
                if (RPE) anchor(bar_full + 504, (t0 + t1) * __uint_as_float((bad ^ (uint32_t)(uintptr_t)odst ^ (uint32_t)(uintptr_t)qnext) & 0x3fffffff));
                asm volatile("{\n.reg .pred p;\nsetp.ne.b32 p, %1, 0;\n@p mbarrier.arrive.shared::cta.b64 _, [%0];\n}"
                             ::"r"(bar_qfree + (n >> 1) - 8), "r"(lane ? 0 : n) : "memory");
                issue_pv(dv_lo, 1, IC<0>{}, IC<8>{});
                scores_ready();
                float a0 = fmaxf(s[0], s[1]), a1 = fmaxf(s[2], s[3]), a2 = fmaxf(s[4], s[5]), a3 = fmaxf(s[6], s[7]);
#pragma unroll
                for (int i = 1; i < MAXG; i++) {
                    a0 = fmaxf(a0, fmaxf(s[8 * i], s[8 * i + 1])); a1 = fmaxf(a1, fmaxf(s[8 * i + 2], s[8 * i + 3]));
                    a2 = fmaxf(a2, fmaxf(s[8 * i + 4], s[8 * i + 5])); a3 = fmaxf(a3, fmaxf(s[8 * i + 6], s[8 * i + 7]));
                }
                const uint32_t a = pack_bf16(fmaxf(a0, a2), fmaxf(a1, a3));
                const uint32_t b = bmax2(bmax2(a, __shfl_xor_sync(0xffffffffu, a, 1)), bmax2(__shfl_xor_sync(0xffffffffu, a, 2), __shfl_xor_sync(0xffffffffu, a, 3)));
                pass_on();
                m0 = fmaf(-CS, bf_lo(b), -POFF); m1 = fmaf(-CS, bf_hi(b), -POFF);
            }
#pragma unroll 1
            for (;;) {
                DBG_T(n);
#pragma unroll
                for (int i = 0; i < 4 * STAGE; i++) s[i] = fmaf(s[i], CS, (i & 2) ? m1 : m0);
#pragma unroll
                for (int i = 0; i < 4 * SPLIT; i++) s[i] = ex2(s[i]);
#pragma unroll
                for (int i = 0; i < SPLIT; i++) { l0 += s[4 * i] + s[4 * i + 1]; l1 += s[4 * i + 2] + s[4 * i + 3]; }
                if (STAGE < 16) {
                    m0 = fmaf(l0, 0.f, m0); m1 = fmaf(l1, 0.f, m1);
                }
                anchor(bar_full + 504, l0 + l1);
                WG_WAIT(0);
                fence_regs(o); fence_regs(p);
                release4(voff);
                dv_lo ^= 2 * SLOT / 16;
                voff ^= 16;
                n++;
#pragma unroll
                for (int i = 4 * STAGE; i < 64; i++) s[i] = fmaf(s[i], CS, (i & 2) ? m1 : m0);
#pragma unroll
                for (int i = 4 * SPLIT; i < 64; i++) s[i] = ex2(s[i]);
#pragma unroll
                for (int i = SPLIT; i < 16; i++) { l0 += s[4 * i] + s[4 * i + 1]; l1 += s[4 * i + 2] + s[4 * i + 3]; }
#pragma unroll
                for (int i = 0; i < 32; i++) p[i] = pack_bf16(s[2 * i], s[2 * i + 1]);
                const int jn = n & 15;
                if (jn > 1) {
                    issue_qk();
                    if ((n & RA) == RB) {
                        if (n & 1) {
#pragma unroll
                            for (int i = 0; i < 64; i++) o[i] *= (i & 2) ? t1 : t0;
                        } else {
                            row_parts();
                            row_sums(2u << (n >> 4));
                            const uint32_t e0 = __float_as_uint(t0) >> 23, e1 = __float_as_uint(t1) >> 23;
                            m0 -= __uint_as_float(0x4b000000u | e0) - (8388608.f + 127.f - POFF);
                            m1 -= __uint_as_float(0x4b000000u | e1) - (8388608.f + 127.f - POFF);
                            t0 = __uint_as_float((254 - (int)POFF - e0) << 23); t1 = __uint_as_float((254 - (int)POFF - e1) << 23);
                            l0 *= t0; l1 *= t1;
                        }
                    }
                    fence_regs(o);
                    WG_FENCE();
                    issue_pv(dv_lo, 1, IC<0>{}, IC<8>{});
                    scores_ready();
                    pass_on();
                    if (jn != 15) continue;
#pragma unroll
                    for (int i = 0; i < 8; i++) {
                        const uint4 v = qnext[i * 32];
                        q[4 * i] = v.x; q[4 * i + 1] = v.y; q[4 * i + 2] = v.z; q[4 * i + 3] = v.w;
                    }
                    continue;
                }
                if (jn == 0) break;
                finish(IC<0>{}, IC<ESPLIT>{}, 1u << (n >> 4), to_frag);
                issue_qk();
                if (HOLD) hold(t0, t1);
                finish(IC<ESPLIT>{}, IC<8>{}, 1u << (n >> 4), to_frag);
                WG_FENCE();
                issue_pv(dv_lo, 0, IC<0>{}, IC<8>{});
                scores_ready();
                pass_on();
            }
            if (n == 64) break;
        }
        DBG_T(64);
        uint32_t a1[32], a2[32];
        bar_sync(1 + w, 192);
        fence_regs(o); fence_regs(p);
        WG_FENCE();
        issue_pv(args.d0 + 3 * SLOT / 16, 1, IC<0>{}, IC<8>{});
        handoff();
        mbar_wait(bar_mod, 0);
        const int tid_ = __shfl_sync(0xffffffffu, tid, lane);
        row_parts();
        row_sums(16);
        t0 = rcp_fast(t0); t1 = rcp_fast(t1);
        anchor(frag, q[0] & q[4] & q[8] & q[12] & q[16] & q[20] & q[24] & q[28] & __float_as_uint(t0) & __float_as_uint(t1) & tid_);
        frag_load(a1, frag + (1 - O2F) * 4096);
        frag_load<0, A2N>(a2, frag + (2 - O2F) * 4096);
        anchor(frag, bad);
        WG_WAIT(0);
        fence_regs(o); fence_regs(p);
        release4(24);
        finish(IC<0>{}, IC<8>{}, 16, [&](int i, uint32_t v0, uint32_t v1, uint32_t v2, uint32_t v3) {
            p[4 * i] = v0; p[4 * i + 1] = v1; p[4 * i + 2] = v2; p[4 * i + 3] = v3; });
        if (A2N < 8) { anchor(frag, p[31] & p[15]); frag_load<A2N, 8>(a2, frag + (2 - O2F) * 4096); }
        bad = __reduce_or_sync(0xffffffffu, bad);
        bad = ((bad | ~(bad >> 8)) >> 1) & 15;
        if (__builtin_expect(bad != 0, 0)) {
            uint8_t* keep = g_keep + (size_t)(rg * 8 + cw) * 4096 + lane * 16;
            frag_store(keep, p);
            attn_fallback(bad, tag, gs, frag, keep, args.wq, args.kc, args.vc);
            frag_load(q, frag + O2F * 8192); frag_load(a1, frag + (1 - O2F) * 4096); frag_load(a2, frag + (2 - O2F) * 4096); frag_load(p, keep);
            anchor(frag, q[0] & q[4] & q[8] & q[12] & q[16] & q[20] & q[24] & q[28] & p[0] & p[4] & p[8] & p[12] & p[16] & p[20] & p[24] & p[28]);
        }
        DBG_T(80);
        DBG_G(124);

        const uint32_t eye = (lane >> 3) == (lane & 3) ? 0x3f80u << ((lane & 4) * 4) : 0;
        auto sum8 = [&](uint32_t* r, const uint4 (&v)[8]) {
            float d[16];
#pragma unroll
            for (int i = 0; i < 16; i++) d[i] = 0.f;
#pragma unroll
            for (int src = 0; src < 8; src++) {
                mma1688(d + 8 * (src & 1), v[src].x, v[src].y, eye);
                mma1688(d + 8 * (src & 1) + 4, v[src].z, v[src].w, eye);
            }
#pragma unroll
            for (int i = 0; i < 4; i++) r[i] = pack_bf16(d[2 * i] + d[8 + 2 * i], d[2 * i + 1] + d[9 + 2 * i]);
        };
        uint4 v2[8], v3[8], wf[23];
        uint2 u4[8], gw[9];
        uint32_t x1[20], xs, pa, ta;
        const uint8_t *mb, *mb4;
        auto load_wf = [&](auto lo, auto hi) {
            const uint32_t wa = sb + SM_Q + ((tid_ & 8) * (D_ / 8) + cw * 16 + (tid_ & 7) + (tid_ & 16) / 2) * 80;
            const uint32_t wb = wa + (512 - cw * 8) * 80 - (tid_ & 16) * 39;
#pragma unroll
            for (int i = lo.value; i < hi.value; i++) wf[i] = ldsm4t(i < 20 ? wa + (i / 5) * 10240 + (i % 5) * 16 : wb + (i - 20) * 32);
        };
        uint32_t at[18];
        {
            float (&u)[32] = reinterpret_cast<float (&)[32]>(o);
            uint32_t off = 0;
            auto turn = [&](const uint32_t (&a)[32], const uint32_t (&b)[32], int acc) {
                uint64_t dv = args.d0 + off * (SLOT / 128);
                bar_sync(1 + w, 192);
                fence_regs(u);
                WG_FENCE();
#pragma unroll
                for (int ks = 0; ks < 16; ks++) {
                    const uint32_t* f = ks < 8 ? &a[4 * ks] : &b[4 * ks - 32];
                    mma_rs64<1>(u, f[0], f[1], f[2], f[3], dv, ks | acc);
                    if (ks == OSPLIT - 1) WG_COMMIT();
                }
                WG_COMMIT();
                WG_WAIT(1);
            };
            auto done = [&]() {
                WG_WAIT(0);
                fence_regs(u);
                release4(off);
                off = (off + 8) & 24;
            };
            auto store = [&](uint8_t* dst) {
#pragma unroll
                for (int i = 0; i < 4; i++)
                    st_relaxed4(dst + i * 512, pack_bf16(u[8 * i], u[8 * i + 1]), pack_bf16(u[8 * i + 2], u[8 * i + 3]),
                                pack_bf16(u[8 * i + 4], u[8 * i + 5]), pack_bf16(u[8 * i + 6], u[8 * i + 7]));
            };
            pa = sb + w * (UNIT - 2048) + tid_ * 16;
#pragma unroll
            for (int i = 0; i < 8; i++) at[i] = 0;
            fence_regs(q); fence_regs(p);
            uint8_t* dst = frag;
#pragma unroll 1
            for (int k = 0; k < 8; k++, dst += 2048) {
                const uint32_t poff = off;
                const bool sum = (0xa0 >> k) & 1;
                if (sum) off = (off + 8) & 24;
                turn(q, p, 0);
                handoff();
                if (sum) {
                    uint4 v[8];
#pragma unroll
                    for (int src = 0; src < 8; src++) v[src] = lds128(pa + poff * (SLOT / 8) + src * 2048);
                    __syncwarp();
                    release(poff >> 3);
                    done();
                    float d[8];
#pragma unroll
                    for (int i = 0; i < 8; i++) {
                        float t[8];
#pragma unroll
                        for (int src = 0; src < 8; src++) {
                            const uint32_t x = i < 2 ? v[src].x : i < 4 ? v[src].y : i < 6 ? v[src].z : v[src].w;
                            t[src] = (i & 1) ? bf_hi(x) : bf_lo(x);
                        }
                        d[i] = ((t[0] + t[2]) + (t[4] + t[6])) + ((t[1] + t[3]) + (t[5] + t[7]));
                    }
#pragma unroll
                    for (int i = 0; i < 4; i++) { at[i] = at[4 + i]; at[4 + i] = pack_bf16(d[2 * i], d[2 * i + 1]); }
                } else {
                    done();
                }
                turn(a1, a2, 1);
                handoff();
                done();
                store(dst);
                __syncwarp();
                asm volatile("{\n.reg .pred p;\nsetp.ne.b32 p, %1, 0;\n@p mbarrier.arrive.shared::cta.b64 _, [%0];\n}"
                             ::"r"(bar_pub + 4 + 4 * k), "r"(lane ? 0 : (0x2a >> k) & 1) : "memory");
            }
            turn(q, p, 0);
            handoff();
            mb = padd(g_frag, (qb * 64 + j) * WREG + 3 * 4096 + tid_ * 16);
            mb4 = padd(mb, 4096 + ((cw >> 1) - cw) * 512 + (cw & 1) * 8);
            xs = sb + (tid_ & 15) * XP + (tid_ & 16) + cw * 32;
            ta = sb + (cw * 8 + (tid_ & 3)) * 8;
#pragma unroll
            for (int k = 0; k < 9; k++) {
                gw[k] = lds64(ta + SM_T + (k < 8 ? (k >> 1) * 64 + (k & 1) * 4 : 256 - cw * 4) * 8);
                if (!(tid_ & 4)) gw[k].y = 0x3f803f80u;
            }
            mbar_wait(bar_g, 0);
            done();
            load_wf(IC<0>{}, IC<WF0>{});
            turn(a1, a2, 1);
            if (w == 0) handoff();
            if (P2E) {
                mbar_wait(bar_full + 8, 0);
#pragma unroll
                for (int src = 0; src < 8; src++) v2[src] = lds128(pa + SLOT + src * 2048);
            }
            done();
            store(dst);
            mbar_wait(bar_full, 0);
            rows_load(x1, xs, cw);
            if (w == 0) bar_sync(5, 256); else bar_arrive(5, 256);
        }
        DBG_T(81);
        DBG_G(122);

        {
        const int tid = tid_, lane = tid & 31;
        const int g8 = lane >> 2, qd = lane & 3, l16 = lane & 15;
        uint32_t h2[18], gb[9], k1, k2;
        float4* rec = reinterpret_cast<float4*>(red + 128);
        const uint2* candp = reinterpret_cast<const uint2*>(padd(g_cand, ((blockIdx.x & (CREP - 1)) * NCTA + (tid >> 1)) * 32 + (tid & 1) * 8));
        uint2 cd;
        auto stage_out = [&]() {
#pragma unroll
            for (int k = 0; k < 9; k++) {
                x1[2 * k] = badd2(x1[2 * k], bmul2(gb[k], h2[2 * k]));
                x1[2 * k + 1] = badd2(x1[2 * k + 1], bmul2(gb[k], h2[2 * k + 1]));
            }
#pragma unroll
            for (int ch = 0; ch < 4; ch++) stsm_x4(xs + ch * 256, x1[4 * ch], x1[4 * ch + 1], x1[4 * ch + 2], x1[4 * ch + 3]);
            asm volatile("stmatrix.sync.aligned.m8n8.x2.shared.b16 [%0], {%1, %2};" ::"r"(xs + 1024 - cw * 16), "r"(x1[16]), "r"(x1[17]) : "memory");
        };
        {
            uint32_t it = 0, miss;
            if (!P2E) {
                mbar_wait(bar_full + 8, 0);
#pragma unroll
                for (int src = 0; src < 8; src++) v2[src] = lds128(pa + SLOT + src * 2048);
            }
            sum8(at + 8, v2);
            float st[12];
#pragma unroll
            for (int i = 0; i < 12; i++) st[i] = 0.f;
            auto add_pair = [&](int k) {
                x1[2 * k] = badd2(x1[2 * k], bmul2(gw[k].x, at[2 * k]));
                x1[2 * k + 1] = badd2(x1[2 * k + 1], bmul2(gw[k].x, at[2 * k + 1]));
                stats_add(st, x1[2 * k], x1[2 * k + 1], gw[k].y);
            };
#pragma unroll
            for (int k = 0; k < 6; k++) add_pair(k);
            mbar_wait(bar_full + 16, 0);
#pragma unroll
            for (int src = 0; src < 8; src++) v3[src] = lds128(pa + 2 * SLOT + src * 2048);
#pragma unroll 1
            do {
                if (BO && it) __nanosleep(BO);
                miss = 0;
#pragma unroll
                for (int src = 0; src < 8; src++) reload16(v3[src], mb + (size_t)src * 8 * WREG, miss);
            } while (__any_sync(0xffffffffu, miss) && ++it < SPIN / 16);
            if (lane < 4) mbar_arrive_cluster(rel_base + 8 * (1 + (lane >> 1)));
            sum8(at + 12, v3);
            add_pair(6); add_pair(7);
            load_wf(IC<WF0>{}, IC<WF1>{});
            uint2 cs[9];
#pragma unroll
            for (int k = 0; k < 9; k++) cs[k] = lds64(ta + SM_TC + (k < 8 ? (k >> 1) * 64 + (k & 1) * 4 : 256 - cw * 4) * 8);
            mbar_wait(bar_pre, 0);
            mbar_wait(bar_full + 24, 0);
#pragma unroll
            for (int src = 0; src < 8; src++) u4[src] = lds64(sb + 3 * SLOT + src * 2048 + (cw >> 1) * 512 + lane * 16 + (cw & 1) * 8);
#pragma unroll 1
            do {
                if (BO && miss) __nanosleep(BO);
                miss = 0;
#pragma unroll
                for (int src = 0; src < 8; src++) reload8(u4[src], mb4 + (size_t)src * 8 * WREG, miss);
            } while (__any_sync(0xffffffffu, miss) && ++it < SPIN / 16);
            float d[8] = {0.f, 0.f, 0.f, 0.f, 0.f, 0.f, 0.f, 0.f};
#pragma unroll
            for (int i = 0; i < 4; i++) mma16816(d + 4 * (i & 1), u4[2 * i].x, u4[2 * i].y, u4[2 * i + 1].x, u4[2 * i + 1].y, eye, eye);
            at[16] = pack_bf16(d[0] + d[4], d[1] + d[5]); at[17] = pack_bf16(d[2] + d[6], d[3] + d[7]);
            add_pair(8);
            DBG_G(123);
            const float2 ws = *reinterpret_cast<const float2*>(smem_raw + SM_TS);
            uint4* cdst = padd(g_cand, CFULL ? ((tid >> 1) * NCTA + rg) * 32 + (tid & 1) * 16 : (tid * NCTA + rg) * 32);
            uint32_t mean2;
            float dot;
            const float rsd = rows_stats(st, rec, cw, lane, mean2, dot);
            const uint32_t b = __float_as_uint(fmaf(fmaf(-bf_lo(mean2), ws.x, dot), rsd, ws.y));
            const uint32_t key = (((b & 0x80000000u) ? ~b : (b | 0x80000000u)) | 2047u) - (rg * 16 + l16);
            top2(key, k1, k2);
            if (tid < (CFULL + 1) * CREP) st_relaxed(cdst, k1, tag, k2, tag);
            cd = ld_relaxed64(candp);
            rows_normalise(h2, x1, mean2, rsd, lane, [&]() {
#pragma unroll
                for (int k = 0; k < 9; k++) gb[k] = lds32(sb + SM_TG + (cw * 8 + qd + (k < 8 ? (k >> 1) * 64 + (k & 1) * 4 : 256 - cw * 4)) * 4);
                if (WFE) load_wf(IC<WF1>{}, IC<WF2>{});
            });
#pragma unroll
            for (int k = 0; k < 18; k++) h2[k] = badd2(bmul2(h2[k], cs[k >> 1].x), cs[k >> 1].y);
            const uint32_t r1 = ~k1 & 15, r2 = ~k2 & 15;
            uint32_t todo = ((r1 & 7) == g8) | ((r2 & 7) == g8) << 1;
#pragma unroll 1
            while (todo) {
                const bool second = !(todo & 1), hi = (second ? r2 : r1) & 8;
                uint4* dst = padd(g_rows, ((rg * 2 + second) * RSLOT + cw * 24 + qd) * 16);
                uint32_t r[18];
#pragma unroll
                for (int k = 0; k < 9; k++) { r[k] = hi ? h2[2 * k + 1] : h2[2 * k]; r[9 + k] = hi ? x1[2 * k + 1] : x1[2 * k]; }
                fence_regs(r);
                st_relaxed(dst, r[0], r[1], r[2], r[3]);
                st_relaxed(dst + 8, r[4], r[5], r[6], r[7]);
                st_relaxed64(reinterpret_cast<uint2*>(padd(dst, 256 - qd * 8)), r[8], r[17]);
                st_relaxed(dst + 4, r[9], r[10], r[11], r[12]);
                st_relaxed(dst + 12, r[13], r[14], r[15], r[16]);
                todo &= todo - 1;
            }
            __syncwarp();

            stage_out();
            if (!WFE) load_wf(IC<WF1>{}, IC<WF2>{});
        }
        DBG_G(110);
        float4* part = reinterpret_cast<float4*>(smem_raw + 3 * SLOT + UNIT + 8192);
        bf16* act = reinterpret_cast<bf16*>(smem_raw + 3 * SLOT + UNIT + 4096);
        {
            uint32_t it = 0;
            const bool own = (tid >> 1) == rg;
            const uint32_t ks = sb + 3 * SLOT + UNIT + 5120;
#pragma unroll 1
            while (cd.y != tag && !own && ++it < SPIN / 16) cd = ld_relaxed64(candp);
            asm volatile("st.shared.u32 [%0], %1;" ::"r"(ks + tid * 4), "r"(own ? (tid & 1) ? k2 : k1 : cd.x) : "memory");
            bar_sync(3, 256);
            DBG_G(111);
            const uint4 a = lds128(ks + lane * 16), b = lds128(ks + 512 + lane * 16);
            const uint32_t a1 = max(a.x, a.z), a2 = __vimax3_u32(min(a.x, a.z), a.y, a.w);
            const uint32_t b1 = max(b.x, b.z), b2 = __vimax3_u32(min(b.x, b.z), b.y, b.w);
            const uint32_t c1 = max(a1, b1), c2 = __vimax3_u32(min(a1, b1), a2, b2);
            k1 = __reduce_max_sync(0xffffffffu, c1);
            k2 = __reduce_max_sync(0xffffffffu, c1 == k1 ? c2 : c1);
        }
        const int sel0 = ~k1 & 2047, sel1 = ~k2 & 2047;
        const uint32_t slot0 = (sel0 >> 4) * 2, slot1 = (sel1 >> 4) * 2 + ((sel0 ^ sel1) < 16);
        uint4 da[13];
        {
            const uint4* hp = padd(g_rows, (((g8 & 1) ? slot1 : slot0) * RSLOT + cw * 24 + qd) * 16);
            const uint2* hp2 = reinterpret_cast<const uint2*>(padd(hp, 256 - qd * 8));
            uint4 hv[2] = {ld_relaxed2(hp), ld_relaxed2(hp + 8)};
            uint2 hw = ld_relaxed64(hp2);
            if (tid == 255) {
                reinterpret_cast<int2*>(red)[8] = make_int2(sel0, sel1);
                mbar_arrive(bar_out);
            }
            load_wf(IC<WF2>{}, IC<23>{});
            mbar_wait(bar_full + 8, 1);
            mbar_wait(bar_full + 16, 1);
            auto load_d = [&](auto lo, auto hi) {
                const int r = (lane & 7) + (lane & 16) / 2;
                const uint32_t d0 = sb + SLOT + r * XP + cw * 144 + (lane & 8) * 2, d1 = d0 + (r < 2 ? 16 * XP : SLOT - 2 * XP);
                const uint32_t d2 = sb + 2 * SLOT + (14 + (lane & 3)) * XP + cw * 144 + (lane >> 3) * 16;
#pragma unroll
                for (int i = lo.value; i < hi.value; i++) da[i] = ldsm4t(i < 10 ? ((i & 1) ? d1 : d0) + (i >> 1) * 32 : d2 + (i - 10) * 64);
            };
            load_d(IC<0>{}, IC<DL>{});
            uint32_t it = 0, miss;
#pragma unroll 1
            do {
                miss = 0;
                reload16(hv[0], hp, miss);
                reload16(hv[1], hp + 8, miss);
                reload8(hw, hp2, miss);
            } while (__any_sync(0xffffffffu, miss) && ++it < SPIN / 16);
            DBG_G(112);
            load_d(IC<DL>{}, IC<13>{});
            float acc[20];
#pragma unroll
            for (int i = 0; i < 20; i++) acc[i] = 0.f;
#pragma unroll
            for (int i = 0; i < 5; i++) mma1688(acc + 4 * i, (i & 1) ? wf[20 + i / 2].z : wf[20 + i / 2].x, (i & 1) ? wf[20 + i / 2].w : wf[20 + i / 2].y, hw.x);
#pragma unroll
            for (int i = 0; i < 20; i++)
                mma16816(acc + 4 * (i % 5), wf[i].x, wf[i].y, wf[i].z, wf[i].w, (i / 5 & 1) ? hv[i / 10].z : hv[i / 10].x, (i / 5 & 1) ? hv[i / 10].w : hv[i / 10].y);
            if (qd == 0) {
#pragma unroll
                for (int i = 0; i < 5; i++) part[cw * 40 + i * 8 + g8] = make_float4(acc[4 * i], acc[4 * i + 1], acc[4 * i + 2], acc[4 * i + 3]);
            }
        }
        {
            uint2* dst = padd(g_ypart, ((cw * 9 * NCTA + blockIdx.x) * 8 + g8) * 8);
            bar_sync(3, 256);
            if (cw < 5) {
                const float* pp = reinterpret_cast<const float*>(part) + ((blockIdx.x & 1) << 4) + tid;
                const float g = rbf(((pp[0] + pp[160]) + (pp[320] + pp[480])) + ((pp[640] + pp[800]) + (pp[960] + pp[1120])));
                const float v = rbf(g * sigmoidf_(g)) * __shfl_down_sync(0xffffffffu, g, 2);
                if (!(tid & 2)) act[(tid & 1) * 56 + (tid >> 2)] = __float2bfloat16_rn(tid < 144 ? v : 0.f);
            }
            bar_sync(3, 256);
            DBG_G(113);
            const uint32_t ap = sb + 3 * SLOT + UNIT + 4096 + (lane & 1) * 112 + (lane >> 3) * 16;
            const uint4 b0 = ldsm4(ap);
            const uint32_t b1 = lds32(sb + 3 * SLOT + UNIT + 4096 + (g8 & 1) * 112 + 64 + qd * 4);
            float y[20];
#pragma unroll
            for (int i = 0; i < 20; i++) y[i] = 0.f;
#pragma unroll
            for (int i = 0; i < 5; i++) {
                mma16816(y + 4 * i, da[2 * i].x, da[2 * i].y, da[2 * i].z, da[2 * i].w, b0.x, b0.y);
                mma16816(y + 4 * i, da[2 * i + 1].x, da[2 * i + 1].y, da[2 * i + 1].z, da[2 * i + 1].w, b0.z, b0.w);
                mma1688(y + 4 * i, (i & 1) ? da[10 + i / 2].z : da[10 + i / 2].x, (i & 1) ? da[10 + i / 2].w : da[10 + i / 2].y, b1);
            }
#pragma unroll
            for (int i = 0; i < 9; i++)
                asm volatile("{\n.reg .pred p;\nsetp.eq.b32 p, %3, 0;\n@p st.relaxed.gpu.global.v2.f32 [%0], {%1, %2};\n}"
                             ::"l"(dst + i * (NCTA * 8)), "f"(y[2 * i]), "f"(y[2 * i + 1]), "r"(qd) : "memory");
        }
        DBG_G(114);
        if (blockIdx.x == 127 && tid == 0) gs->epoch[0] = tag;
        if (blockIdx.x < 72) {
            const int G = blockIdx.x, tok = g8 & 1, cp = G * 4 + qd;
            const uint2* src = padd(g_ypart, (blockIdx.x * NCTA * 8 + tid) * 8);
            const uint8_t* hsrc = reinterpret_cast<const uint8_t*>(padd(g_rows, (tok ? slot1 : slot0) * (RSLOT * 16) +
                (G < 64 ? (G >> 1 & 7) * 384 + (G >> 5) * 128 + qd * 16 + (G >> 1 & 8) + (G & 1) * 4 : (G - 64) * 384 + 256 + qd * 8)));
            const uint8_t* xsrc = hsrc + (G < 64 ? 64 : 4);
            uint32_t* dst = padd(reinterpret_cast<uint32_t*>(args.out), (tok ? sel1 : sel0) * (D_ * 2) + cp * 4);
            const uint32_t gb = reinterpret_cast<const uint32_t*>(smem_raw + SM_TG)[cp];
            const uint32_t ksel = ((tok ? k2 : k1) & ~2047u) | 1024u;
            const float sg = sigmoidf_(rbf(__uint_as_float((ksel & 0x80000000u) ? (ksel & 0x7fffffffu) : ~ksel)));
            uint2 v[4];
            uint32_t hv, xv, it = 0;
            bool miss;
#pragma unroll 1
            do {
#pragma unroll
                for (int i = 0; i < 4; i++) v[i] = ld_relaxed64(src + i * 256);
                hv = ld_relaxed32(hsrc);
                xv = ld_relaxed32(xsrc);
                miss = max(__vimax3_u32(v[0].x, v[1].x, v[2].x), __vimax3_u32(v[3].x, hv, xv)) == ~0u;
            } while (__any_sync(0xffffffffu, miss) && ++it < SPIN / 16);
            float y0 = (__uint_as_float(v[0].x) + __uint_as_float(v[1].x)) + (__uint_as_float(v[2].x) + __uint_as_float(v[3].x));
            float y1 = (__uint_as_float(v[0].y) + __uint_as_float(v[1].y)) + (__uint_as_float(v[2].y) + __uint_as_float(v[3].y));
            y0 += __shfl_xor_sync(0xffffffffu, y0, 8); y1 += __shfl_xor_sync(0xffffffffu, y1, 8);
            y0 += __shfl_xor_sync(0xffffffffu, y0, 16); y1 += __shfl_xor_sync(0xffffffffu, y1, 16);
            if (lane < 8) reinterpret_cast<float2*>(rec)[cw * 8 + lane] = make_float2(y0, y1);
            bar_sync(3, 256);
            if (cw == 0) {
                const float4 t0_ = rec[(lane >> 3) * 4 + qd], t1_ = rec[16 + (lane >> 3) * 4 + qd];
                y0 = tok ? t0_.y + t1_.y : t0_.x + t1_.x; y1 = tok ? t0_.w + t1_.w : t0_.z + t1_.z;
                y0 += __shfl_xor_sync(0xffffffffu, y0, 8); y1 += __shfl_xor_sync(0xffffffffu, y1, 8);
                y0 += __shfl_xor_sync(0xffffffffu, y0, 16); y1 += __shfl_xor_sync(0xffffffffu, y1, 16);
                const uint32_t y2 = bmul2(pack_bf16(y0, y1), pack_bf16(sg, sg));
                if (lane < 8) *dst = badd2(xv, bmul2(gb, badd2(hv, y2)));
            }
        }
        }
        DBG_T(88);
        DBG_G(121);
    }
}

typedef CUresult (*EncodeFn)(CUtensorMap*, CUtensorMapDataType, cuuint32_t, void*, const cuuint64_t*, const cuuint64_t*,
                             const cuuint32_t*, const cuuint32_t*, CUtensorMapInterleave, CUtensorMapSwizzle,
                             CUtensorMapL2promotion, CUtensorMapFloatOOBfill);

static void make_map(EncodeFn enc, CUtensorMap* m, const void* ptr, int rank, const cuuint64_t* dims,
                     const cuuint64_t* strides, const cuuint32_t* box, CUtensorMapSwizzle sw = CU_TENSOR_MAP_SWIZZLE_128B,
                     CUtensorMapDataType dt = CU_TENSOR_MAP_DATA_TYPE_BFLOAT16) {
    const cuuint32_t es[3] = {1, 1, 1};
    enc(m, dt, rank, const_cast<void*>(ptr), dims, strides, box, es,
        CU_TENSOR_MAP_INTERLEAVE_NONE, sw, CU_TENSOR_MAP_L2_PROMOTION_L2_128B,
        CU_TENSOR_MAP_FLOAT_OOB_FILL_NONE);
}

extern "C" void kernel_launch(void* const* d_in, const int* in_sizes, int n_in, void* d_out, int out_size) {
    const bf16* x = (const bf16*)d_in[0];
    const bf16* kc = (const bf16*)d_in[1];
    const bf16* vc = (const bf16*)d_in[2];
    const bf16* wq = (const bf16*)d_in[3];
    const bf16* wo = (const bf16*)d_in[4];
    const bf16* w_r = (const bf16*)d_in[6];
    const bf16* w_gate = (const bf16*)d_in[7];
    const bf16* w_up = (const bf16*)d_in[8];
    const bf16* w_down = (const bf16*)d_in[9];
    const bf16* cvec = (const bf16*)d_in[10];
    const bf16* w_mod = (const bf16*)d_in[11];
    bf16* out = (bf16*)d_out;

    void* fn = nullptr;
    cudaDriverEntryPointQueryResult qr;
    cudaGetDriverEntryPoint("cuTensorMapEncodeTiled", &fn, cudaEnableDefault, &qr);
    EncodeFn enc = (EncodeFn)fn;
    void* p_s;
    cudaGetSymbolAddress(&p_s, g_s);

    CUtensorMap tm_wq, tm_k, tm_v, tm_wo, tm_p, tm_x, tm_d, tm_g, tm_u;
    { cuuint64_t d[2] = {QD, D_}, s[1] = {QD * 2}; cuuint32_t b[2] = {64, 128}; make_map(enc, &tm_wq, wq, 2, d, s, b); }
    { cuuint64_t d[2] = {DH, HKV * S_}, s[1] = {DH * 2}; cuuint32_t b[2] = {64, 128};
      make_map(enc, &tm_k, kc, 2, d, s, b); make_map(enc, &tm_v, vc, 2, d, s, b); }
    { cuuint64_t d[2] = {D_, QD}, s[1] = {D_ * 2}; cuuint32_t b[2] = {64, 128}; make_map(enc, &tm_wo, wo, 2, d, s, b); }
    { cuuint64_t d[3] = {256, 160, NCTA}, s[2] = {1024, 8 * WREG}; cuuint32_t b[3] = {256, 2, 8};
      make_map(enc, &tm_p, ((Scratch*)p_s)->frag, 3, d, s, b, CU_TENSOR_MAP_SWIZZLE_NONE, CU_TENSOR_MAP_DATA_TYPE_UINT32); }
    { cuuint64_t d[2] = {D_ / 4, S_}, s[1] = {D_ * 2}; cuuint32_t b[2] = {XP / 8, 16};
      make_map(enc, &tm_x, x, 2, d, s, b, CU_TENSOR_MAP_SWIZZLE_NONE, CU_TENSOR_MAP_DATA_TYPE_UINT64); }
    { cuuint64_t d[2] = {D_ / 4, F_}, s[1] = {D_ * 2}; cuuint32_t b[2] = {XP / 8, 18};
      make_map(enc, &tm_d, w_down, 2, d, s, b, CU_TENSOR_MAP_SWIZZLE_NONE, CU_TENSOR_MAP_DATA_TYPE_UINT64); }
    { cuuint64_t d[2] = {F_, D_}, s[1] = {F_ * 2}; cuuint32_t b[2] = {40, 24};
      make_map(enc, &tm_g, w_gate, 2, d, s, b, CU_TENSOR_MAP_SWIZZLE_NONE); make_map(enc, &tm_u, w_up, 2, d, s, b, CU_TENSOR_MAP_SWIZZLE_NONE); }

    cudaFuncSetAttribute(fused_kernel<true>, cudaFuncAttributeMaxDynamicSharedMemorySize, SM_TOTAL);
    cudaFuncSetAttribute(fused_kernel<false>, cudaFuncAttributeMaxDynamicSharedMemorySize, SM_TOTAL);
    cudaLaunchConfig_t cfg = {};
    cfg.gridDim = NCTA + 4; cfg.blockDim = 384; cfg.dynamicSmemBytes = SM_TOTAL;
    cudaLaunchAttribute at;
    at.id = cudaLaunchAttributeClusterDimension; at.val.clusterDim.x = 2; at.val.clusterDim.y = 1; at.val.clusterDim.z = 1;
    cfg.attrs = &at; cfg.numAttrs = 1;
    int ncl = 0;
    if (cudaOccupancyMaxActiveClusters(&ncl, fused_kernel<true>, &cfg) != cudaSuccess) { ncl = 0; cudaGetLastError(); }
    Args args{w_mod, cvec, (Scratch*)p_s, desc_lo(0, UNIT) | (0x40000040ull << 32), out, x, kc, vc, wq, wo, w_r, w_down};
    if (USE_SPARE && ncl >= NCTA / 2 + 2)
        fused_kernel<true><<<NCTA + 4, 384, SM_TOTAL>>>(args, tm_wq, tm_k, tm_v, tm_wo, tm_p, tm_x, tm_d, tm_g, tm_u);
    else
        fused_kernel<false><<<NCTA, 384, SM_TOTAL>>>(args, tm_wq, tm_k, tm_v, tm_wo, tm_p, tm_x, tm_d, tm_g, tm_u);
}
```

```cpp
#include <cuda_runtime.h>
#include <cuda_bf16.h>
#include <cuda.h>
#include <stdint.h>
#include <math.h>

typedef __nv_bfloat16 bf16;

constexpr int S_ = 2048;
constexpr int D_ = 576;
constexpr int HQ = 32, HKV = 16, DH = 128;
constexpr int F_ = 4608;
constexpr int QD = HQ * DH;

constexpr int NCTA = 128;
constexpr int WREG = 5 * 4096;
constexpr int CREP = 8;
constexpr int RSLOT = 192;
constexpr int MREP = 4;
struct Scratch {
    unsigned int epoch[128];
    unsigned int flag_mod[NCTA];
    unsigned int flag_part[16 * 32];
    unsigned int flag_q3[16 * 32];
    unsigned int flag_h[NCTA * 32];
    uint2 mod1[MREP * D_];
    uint32_t mod2[4 * D_];
    uint4 cand[CREP * NCTA * 2];
    uint2 ypart[72 * NCTA * 8];
    uint4 h[2][NCTA * 36 * 32];
    uint4 q3[NCTA * 8 * 128];
    uint4 rows[NCTA * 2 * RSLOT];
    uint8_t frag[NCTA * 8 * WREG];
    uint8_t keep[NCTA * 8 * 4096];
};
__device__ __align__(1024) Scratch g_s;
#define g_h gs->h[tag & 1]
#define g_q3 gs->q3
#define g_keep gs->keep
#define g_flag_h gs->flag_h
#define g_flag_part gs->flag_part
#define g_flag_mod gs->flag_mod
#define g_flag_q3 gs->flag_q3
#define g_frag gs->frag
#define g_cand gs->cand
#define g_ypart gs->ypart
#define g_rows gs->rows

#define DBG_INIT()
#define DBG_P(i)
#define DBG_PG(i)
#define DBG_T(i)
#define DBG_G(i)

__device__ __forceinline__ uint32_t pack_bf16(float lo, float hi) {
    uint32_t r;
    asm("cvt.rn.bf16x2.f32 %0, %1, %2;" : "=r"(r) : "f"(hi), "f"(lo));
    return r;
}
__device__ __forceinline__ float rbf(float x) { return __uint_as_float(pack_bf16(0.f, x)); }
__device__ __forceinline__ float bf_lo(uint32_t v) { return __uint_as_float(v << 16); }
__device__ __forceinline__ float bf_hi(uint32_t v) { return __uint_as_float(v & 0xffff0000u); }
__device__ __forceinline__ float ex2(float x) {
    float y;
    asm("ex2.approx.ftz.f32 %0, %1;" : "=f"(y) : "f"(x));
    return y;
}
template <class T>
__device__ __forceinline__ T* padd(T* p, uint32_t off) {
    unsigned long long r;
    asm("{\n.reg .b32 l, h;\nmov.b64 {l, h}, %1;\nadd.cc.u32 l, l, %2;\naddc.u32 h, h, 0;\nmov.b64 %0, {l, h};\n}" : "=l"(r) : "l"(p), "r"(off));
    return reinterpret_cast<T*>(r);
}
__device__ __forceinline__ uint32_t smem_u32(const void* p) { return (uint32_t)__cvta_generic_to_shared(p); }
__device__ __forceinline__ void mbar_init(uint32_t bar, uint32_t cnt) {
    asm volatile("mbarrier.init.shared::cta.b64 [%0], %1;" ::"r"(bar), "r"(cnt) : "memory");
}
__device__ __forceinline__ void mbar_expect_tx(uint32_t bar, uint32_t bytes) {
    asm volatile("mbarrier.arrive.expect_tx.shared::cta.b64 _, [%0], %1;" ::"r"(bar), "r"(bytes) : "memory");
}
__device__ __forceinline__ void mbar_arrive(uint32_t bar) {
    asm volatile("mbarrier.arrive.shared::cta.b64 _, [%0];" ::"r"(bar) : "memory");
}
__device__ __forceinline__ void mbar_arrive_cluster(uint32_t cluster_addr) {
    asm volatile("mbarrier.arrive.shared::cluster.b64 _, [%0];" ::"r"(cluster_addr) : "memory");
}
constexpr uint32_t SPIN = 1u << 20;
__device__ __forceinline__ void mbar_wait(uint32_t bar, uint32_t parity) {
    asm volatile("{\n.reg .pred p;\n.reg .b32 c;\nmov.b32 c, 0;\n"
                 "W_%=:\nmbarrier.try_wait.parity.shared::cta.b64 p, [%0], %1;\n"
                 "add.u32 c, c, 1;\nsetp.lt.and.u32 p, c, 0x100000, !p;\n@p bra W_%=;\n}"
                 ::"r"(bar), "r"(parity) : "memory");
}
__device__ __forceinline__ void anchor(uint32_t addr, float v) {
    asm volatile("{\n.reg .pred p;\nsetp.lt.f32 p, %1, 0f00000000;\n@p st.volatile.shared.f32 [%0], %1;\n}" ::"r"(addr), "f"(v) : "memory");
}
__device__ __forceinline__ void anchor(uint32_t addr, uint32_t v) {
    asm volatile("{\n.reg .pred p;\nsetp.eq.u32 p, %1, 0xffffffff;\n@p st.volatile.shared.u32 [%0], %1;\n}" ::"r"(addr), "r"(v) : "memory");
}
__device__ __forceinline__ void anchor(void* p, uint32_t v) {
    asm volatile("{\n.reg .pred p;\nsetp.eq.u32 p, %1, 0xffffffff;\n@p st.volatile.u32 [%0], %1;\n}" ::"l"(p), "r"(v) : "memory");
}
__device__ __forceinline__ void hold(float& a, float& b) {
    asm volatile("{\n.reg .pred p;\n.reg .b64 t;\n.reg .b32 l, h;\nmov.u64 t, %%clock64;\nmov.b64 {l, h}, t;\nsetp.eq.u32 p, h, 0xffffffff;\n"
                 "@p mov.f32 %0, 0f00000000;\n@p mov.f32 %1, 0f00000000;\n}" : "+f"(a), "+f"(b) :: "memory");
}
__device__ __forceinline__ void mbar_wait_sleep(uint32_t bar, uint32_t parity) {
    asm volatile("{\n.reg .pred p;\n.reg .b32 c;\nmov.b32 c, 0;\n"
                 "W_%=:\nmbarrier.try_wait.parity.shared::cta.b64 p, [%0], %1, 5000;\n"
                 "add.u32 c, c, 1;\nsetp.lt.and.u32 p, c, 0x20000, !p;\n@p bra W_%=;\n}"
                 ::"r"(bar), "r"(parity) : "memory");
}
__device__ __forceinline__ uint32_t load_tag(const Scratch* gs) {
    uint32_t tag;
    asm volatile("ld.global.ca.u32 %0, [%1];" : "=r"(tag) : "l"(gs->epoch) : "memory");
    return tag + 1;
}
__device__ __forceinline__ uint4 ld_relaxed(const uint4* p) {
    uint4 v;
    asm volatile("ld.relaxed.gpu.global.v4.u32 {%0,%1,%2,%3}, [%4];" : "=r"(v.x), "=r"(v.y), "=r"(v.z), "=r"(v.w) : "l"(p) : "memory");
    return v;
}
__device__ __forceinline__ void st_relaxed(uint4* p, uint32_t a, uint32_t b, uint32_t c, uint32_t d) {
    asm volatile("{\n.reg .b64 u, v;\nmov.b64 u, {%1, %2};\nmov.b64 v, {%3, %4};\nst.relaxed.gpu.global.v2.b64 [%0], {u, v};\n}"
                 ::"l"(p), "r"(a), "r"(b), "r"(c), "r"(d) : "memory");
}
__device__ __forceinline__ void st_relaxed4(void* p, uint32_t a, uint32_t b, uint32_t c, uint32_t d) {
    asm volatile("st.relaxed.gpu.global.v4.u32 [%0], {%1, %2, %3, %4};" ::"l"(p), "r"(a), "r"(b), "r"(c), "r"(d) : "memory");
}
__device__ __forceinline__ uint2 ld_relaxed8(const void* p) {
    uint2 v;
    asm volatile("ld.relaxed.gpu.global.v2.u32 {%0,%1}, [%2];" : "=r"(v.x), "=r"(v.y) : "l"(p) : "memory");
    return v;
}
__device__ __forceinline__ uint2 ld_relaxed64(const uint2* p) {
    uint2 v;
    asm volatile("{\n.reg .b64 u;\nld.relaxed.gpu.global.b64 u, [%2];\nmov.b64 {%0, %1}, u;\n}" : "=r"(v.x), "=r"(v.y) : "l"(p) : "memory");
    return v;
}
__device__ __forceinline__ void st_relaxed64(uint2* p, uint32_t a, uint32_t b) {
    asm volatile("{\n.reg .b64 u;\nmov.b64 u, {%1, %2};\nst.relaxed.gpu.global.b64 [%0], u;\n}" ::"l"(p), "r"(a), "r"(b) : "memory");
}
__device__ __forceinline__ uint4 ld_relaxed2(const uint4* p) {
    uint4 v;
    asm volatile("{\n.reg .b64 u, w;\nld.relaxed.gpu.global.v2.b64 {u, w}, [%4];\nmov.b64 {%0, %1}, u;\nmov.b64 {%2, %3}, w;\n}"
                 : "=r"(v.x), "=r"(v.y), "=r"(v.z), "=r"(v.w) : "l"(p) : "memory");
    return v;
}
__device__ __forceinline__ void reload16(uint4& v, const void* p, uint32_t& miss) {
    asm volatile("{\n.reg .pred p;\n.reg .b32 m;\n.reg .b64 u, w;\nmax.u32 m, %0, %2;\nsetp.eq.u32 p, m, 0xffffffff;\n"
                 "mov.b64 u, {%0, %1};\nmov.b64 w, {%2, %3};\n@p ld.relaxed.gpu.global.v2.b64 {u, w}, [%5];\n"
                 "mov.b64 {%0, %1}, u;\nmov.b64 {%2, %3}, w;\n@p mov.u32 %4, 1;\n}"
                 : "+r"(v.x), "+r"(v.y), "+r"(v.z), "+r"(v.w), "+r"(miss) : "l"(p) : "memory");
}
__device__ __forceinline__ void reload8(uint2& v, const void* p, uint32_t& miss) {
    asm volatile("{\n.reg .pred p;\n.reg .b64 u;\nsetp.eq.u32 p, %0, 0xffffffff;\nmov.b64 u, {%0, %1};\n"
                 "@p ld.relaxed.gpu.global.b64 u, [%3];\nmov.b64 {%0, %1}, u;\n@p mov.u32 %2, 1;\n}"
                 : "+r"(v.x), "+r"(v.y), "+r"(miss) : "l"(p) : "memory");
}
__device__ __forceinline__ uint32_t ld_relaxed32(const void* p) {
    uint32_t v;
    asm volatile("ld.relaxed.gpu.global.u32 %0, [%1];" : "=r"(v) : "l"(p) : "memory");
    return v;
}
__device__ __forceinline__ void flag_wait(const unsigned int* p, uint32_t tag) {
    uint32_t v, it = 0;
#pragma unroll 1
    do {
        asm volatile("ld.relaxed.gpu.global.u32 %0, [%1];" : "=r"(v) : "l"(p) : "memory");
    } while (__any_sync(0xffffffffu, v != tag) && ++it < SPIN / 16);
    asm volatile("fence.acquire.gpu;" ::: "memory");
    __syncwarp();
}
__device__ __forceinline__ bool elect() {
    uint32_t p;
    asm volatile("{\n.reg .pred p;\nelect.sync _|p, 0xffffffff;\nselp.u32 %0, 1, 0, p;\n}" : "=r"(p));
    return p;
}
__device__ __forceinline__ void flag_release(unsigned int* p, uint32_t tag) {
    asm volatile("st.release.gpu.global.u32 [%0], %1;" ::"l"(p), "r"(tag) : "memory");
}
__device__ __forceinline__ uint32_t touch(const void* p) {
    uint32_t v;
    asm volatile("ld.global.nc.L1::no_allocate.L2::128B.u32 %0, [%1];" : "=r"(v) : "l"(p));
    return v;
}
__device__ __forceinline__ void bar_sync(int id, int n) { asm volatile("bar.sync %0, %1;" ::"r"(id), "r"(n) : "memory"); }
__device__ __forceinline__ void bar_arrive(int id, int n) { asm volatile("bar.arrive %0, %1;" ::"r"(id), "r"(n) : "memory"); }

constexpr uint64_t EVICT_NORMAL = 0x1000000000000000ull, EVICT_FIRST = 0x12F0000000000000ull;
__device__ __forceinline__ void tma2d(uint32_t dst, const CUtensorMap* m, int c0, int c1, uint32_t bar) {
    asm volatile("cp.async.bulk.tensor.2d.shared::cluster.global.mbarrier::complete_tx::bytes.L2::cache_hint [%0], [%1, {%3, %4}], [%2], %5;"
                 ::"r"(dst), "l"(m), "r"(bar), "r"(c0), "r"(c1), "l"(EVICT_FIRST) : "memory");
}
__device__ __forceinline__ void tma2d_mc(uint32_t dst, const CUtensorMap* m, int c0, int c1, uint32_t bar, uint64_t pol) {
    asm volatile("cp.async.bulk.tensor.2d.shared::cluster.global.mbarrier::complete_tx::bytes.multicast::cluster.L2::cache_hint [%0], [%1, {%3, %4}], [%2], %5, %6;"
                 ::"r"(dst), "l"(m), "r"(bar), "r"(c0), "r"(c1), "h"((uint16_t)3), "l"(pol) : "memory");
}
__device__ __forceinline__ void tma3d(uint32_t dst, const CUtensorMap* m, int c0, int c1, int c2, uint32_t bar) {
    asm volatile("cp.async.bulk.tensor.3d.shared::cluster.global.mbarrier::complete_tx::bytes.L2::cache_hint [%0], [%1, {%3, %4, %5}], [%2], %6;"
                 ::"r"(dst), "l"(m), "r"(bar), "r"(c0), "r"(c1), "r"(c2), "l"(EVICT_FIRST) : "memory");
}
__device__ __forceinline__ void bulk_load(uint32_t dst, const void* src, uint32_t bytes, uint32_t bar) {
    asm volatile("cp.async.bulk.shared::cluster.global.mbarrier::complete_tx::bytes [%0], [%1], %2, [%3];"
                 ::"r"(dst), "l"(src), "r"(bytes), "r"(bar) : "memory");
}
__device__ __forceinline__ void l2_prefetch(const void* src, uint32_t bytes) {
    asm volatile("cp.async.bulk.prefetch.L2.global [%0], %1;" ::"l"(src), "r"(bytes) : "memory");
}
__device__ __forceinline__ uint32_t bmul2(uint32_t a, uint32_t b) { uint32_t r; asm("mul.rn.bf16x2 %0, %1, %2;" : "=r"(r) : "r"(a), "r"(b)); return r; }
__device__ __forceinline__ uint32_t badd2(uint32_t a, uint32_t b) { uint32_t r; asm("add.rn.bf16x2 %0, %1, %2;" : "=r"(r) : "r"(a), "r"(b)); return r; }
__device__ __forceinline__ uint32_t bsub2(uint32_t a, uint32_t b) { uint32_t r; asm("sub.rn.bf16x2 %0, %1, %2;" : "=r"(r) : "r"(a), "r"(b)); return r; }
__device__ __forceinline__ uint32_t bmax2(uint32_t a, uint32_t b) { uint32_t r; asm("max.bf16x2 %0, %1, %2;" : "=r"(r) : "r"(a), "r"(b)); return r; }
__device__ __forceinline__ uint32_t bfma2(uint32_t a, uint32_t b, uint32_t c) { uint32_t r; asm("fma.rn.bf16x2 %0, %1, %2, %3;" : "=r"(r) : "r"(a), "r"(b), "r"(c)); return r; }
__device__ __forceinline__ uint4 lds128(uint32_t a) { uint4 v; asm volatile("ld.shared.v4.u32 {%0,%1,%2,%3}, [%4];" : "=r"(v.x), "=r"(v.y), "=r"(v.z), "=r"(v.w) : "r"(a) : "memory"); return v; }
__device__ __forceinline__ uint2 lds64(uint32_t a) { uint2 v; asm volatile("ld.shared.v2.u32 {%0,%1}, [%2];" : "=r"(v.x), "=r"(v.y) : "r"(a) : "memory"); return v; }
__device__ __forceinline__ uint32_t lds32(uint32_t a) { uint32_t v; asm volatile("ld.shared.u32 %0, [%1];" : "=r"(v) : "r"(a) : "memory"); return v; }
__device__ __forceinline__ uint4 ldsm4(uint32_t a) {
    uint4 v;
    asm volatile("ldmatrix.sync.aligned.m8n8.x4.shared.b16 {%0,%1,%2,%3}, [%4];" : "=r"(v.x), "=r"(v.y), "=r"(v.z), "=r"(v.w) : "r"(a) : "memory");
    return v;
}
__device__ __forceinline__ uint4 ldsm4t(uint32_t a) {
    uint4 v;
    asm volatile("ldmatrix.sync.aligned.m8n8.x4.trans.shared.b16 {%0,%1,%2,%3}, [%4];" : "=r"(v.x), "=r"(v.y), "=r"(v.z), "=r"(v.w) : "r"(a) : "memory");
    return v;
}
__device__ __forceinline__ void mma1688(float* d, uint32_t a0, uint32_t a1, uint32_t b) {
    asm("mma.sync.aligned.m16n8k8.row.col.f32.bf16.bf16.f32 {%0,%1,%2,%3}, {%4,%5}, {%6}, {%0,%1,%2,%3};"
        : "+f"(d[0]), "+f"(d[1]), "+f"(d[2]), "+f"(d[3]) : "r"(a0), "r"(a1), "r"(b));
}
__device__ __forceinline__ void mma16816(float* d, uint32_t a0, uint32_t a1, uint32_t a2, uint32_t a3, uint32_t b0, uint32_t b1) {
    asm("mma.sync.aligned.m16n8k16.row.col.f32.bf16.bf16.f32 {%0,%1,%2,%3}, {%4,%5,%6,%7}, {%8,%9}, {%0,%1,%2,%3};"
                 : "+f"(d[0]), "+f"(d[1]), "+f"(d[2]), "+f"(d[3]) : "r"(a0), "r"(a1), "r"(a2), "r"(a3), "r"(b0), "r"(b1));
}
__device__ __forceinline__ void stsm_x4(uint32_t addr, uint32_t a, uint32_t b, uint32_t c, uint32_t d) {
    asm volatile("stmatrix.sync.aligned.m8n8.x4.shared.b16 [%0], {%1, %2, %3, %4};"
                 ::"r"(addr), "r"(a), "r"(b), "r"(c), "r"(d) : "memory");
}

__device__ __forceinline__ uint64_t mkdesc(uint32_t addr, uint32_t lbo, uint32_t sbo) {
    return (uint64_t)((addr & 0x3FFFF) >> 4) | ((uint64_t)(lbo >> 4) << 16) | ((uint64_t)(sbo >> 4) << 32) | (1ull << 62);
}
constexpr uint32_t SM0 = 1024;
__host__ __device__ constexpr uint32_t desc_lo(uint32_t off, uint32_t lbo) { return ((SM0 + off) >> 4) | ((lbo >> 4) << 16); }
#define WG_FENCE() asm volatile("wgmma.fence.sync.aligned;" ::: "memory")
#define WG_COMMIT() asm volatile("wgmma.commit_group.sync.aligned;" ::: "memory")
#define WG_WAIT(n) asm volatile("wgmma.wait_group.sync.aligned %0;" ::"n"(n) : "memory")

#define F8(a, i) "+f"(a[i]), "+f"(a[i + 1]), "+f"(a[i + 2]), "+f"(a[i + 3]), "+f"(a[i + 4]), "+f"(a[i + 5]), "+f"(a[i + 6]), "+f"(a[i + 7])
#define F16(a, i) F8(a, i), F8(a, i + 8)
#define F64(a) F16(a, 0), F16(a, 16), F16(a, 32), F16(a, 48)
#define F32(a) F16(a, 0), F16(a, 16)
#define L64 "%0,%1,%2,%3,%4,%5,%6,%7,%8,%9,%10,%11,%12,%13,%14,%15,%16,%17,%18,%19,%20,%21,%22,%23,%24,%25,%26,%27,%28,%29,%30,%31,%32,%33,%34,%35,%36,%37,%38,%39,%40,%41,%42,%43,%44,%45,%46,%47,%48,%49,%50,%51,%52,%53,%54,%55,%56,%57,%58,%59,%60,%61,%62,%63"
#define L32 "%0,%1,%2,%3,%4,%5,%6,%7,%8,%9,%10,%11,%12,%13,%14,%15,%16,%17,%18,%19,%20,%21,%22,%23,%24,%25,%26,%27,%28,%29,%30,%31"

template <int TB, int STEP = 128>
__device__ __forceinline__ void mma_rs128(float (&d)[64], uint32_t a0, uint32_t a1, uint32_t a2, uint32_t a3, uint64_t& b, int acc) {
    asm volatile("{\n.reg .pred p;\nsetp.ne.b32 p, %69, 0;\n"
                 "wgmma.mma_async.sync.aligned.m64n128k16.f32.bf16.bf16 {" L64 "}, {%65,%66,%67,%68}, %64, p, 1, 1, %70;\nadd.s64 %64, %64, %71;\n}"
                 : F64(d), "+l"(b) : "r"(a0), "r"(a1), "r"(a2), "r"(a3), "r"(acc), "n"(TB), "n"(STEP));
}
template <int TB>
__device__ __forceinline__ void mma_rs64(float (&d)[32], uint32_t a0, uint32_t a1, uint32_t a2, uint32_t a3, uint64_t& b, int acc) {
    asm volatile("{\n.reg .pred p;\nsetp.ne.b32 p, %37, 0;\n"
                 "wgmma.mma_async.sync.aligned.m64n64k16.f32.bf16.bf16 {" L32 "}, {%33,%34,%35,%36}, %32, p, 1, 1, %38;\nadd.s64 %32, %32, 128;\n}"
                 : F32(d), "+l"(b) : "r"(a0), "r"(a1), "r"(a2), "r"(a3), "r"(acc), "n"(TB));
}
template <int N>
__device__ __forceinline__ void fence_regs(float (&d)[N]) {
#pragma unroll
    for (int i = 0; i < N; i++) asm volatile("" : "+f"(d[i])::"memory");
}
template <int N>
__device__ __forceinline__ void fence_regs(uint32_t (&d)[N]) {
#pragma unroll
    for (int i = 0; i < N; i++) asm volatile("" : "+r"(d[i])::"memory");
}

template <int V> struct IC { static constexpr int value = V; };

constexpr int SLOT = 32768, UNIT = 16384;
constexpr int SM_Q = 4 * SLOT;
constexpr int SM_BAR = 7 * SLOT;
constexpr int SM_RED = SM_BAR + 512;
constexpr int SM_TOTAL = SM_BAR + 3072;
constexpr int XP = D_ * 2 + 16;
constexpr int M_MOD = 16 * XP;
constexpr int SM_T = SM_Q + 2 * D_ * 80, SM_TC = SM_T + D_ * 4, SM_TG = SM_TC + D_ * 4, SM_TS = SM_TG + D_ * 2;
constexpr float CS = 0.08838834764831845f * 1.4426950408889634f;
#define LMAX 0.5f
#define LMIN 0x1p-104f
#define USE_SPARE 1
#define MAXG 1
#define SPLIT 10
#define ESPLIT 3
#define PV1 8
#define RW 2
#define HW 2
#define HW2 1
#define XDELAY 200
#define QDELAY 300
#define TMPF 1
#define PFD0 2000
#define PFD1 400
#define HDELAY 300
#define RA 10
#define RB 2
#define RPE 2
#define OSPLIT 6
#define HOLD 1
#define DL 6
#define O2F 0
#define A2N 4
#define OPF 0
#define PS 2
#define STAGE 11
#define POFF 102.f
#define WF0 3
#define WF1 13
#define C3D 0
#define C4D 300
#define DD 300
#define P2E 0
#define BO 0
#define MAP 2
#define CFULL 0
#define WFE 1
#define OUTD 0
#define OUTPOL EVICT_FIRST
#define WF2 19
constexpr int PF_KV = 8, PF_WO = 120;

__device__ __forceinline__ int cluster_role() {
    int k;
    asm volatile("mov.u32 %0, %%ctaid.x;" : "=r"(k));
    k >>= 1;
    if (MAP == 0) return k & 63;
    if (MAP == 1) return (k & 7) * 8 + ((k >> 3) & 7);
    if (MAP == 3) {
        asm("mov.u32 %0, %%smid;" : "=r"(k));
        k >>= 1;
        const int r = ((k - 32) * 37) >> 8;
        return k < 32 ? (k & 7) * 8 + (k >> 3) : k < 60 ? (k - 31 - r * 7) * 8 + 4 + r : (k - 58) & 7;
    }
    const int r = ((k - 36) * 37) >> 8, i = k - 36 - r * 7;
    if (MAP == 4) return k < 4 ? 4 + k : k < 36 ? ((k - 4) & 7) * 8 + ((k - 4) >> 3) : (i + 1) * 8 + ((4 + r) & 7);
    return k < 4 ? 12 + k : k < 36 ? ((k - 4) & 7) * 8 + ((k - 4) >> 3) : (i + (i > 0)) * 8 + ((4 + r) & 7);
}

struct Args {
    const bf16 *w_mod, *cvec;
    Scratch* gs;
    uint64_t d0;
    bf16* out;
    const bf16 *x, *kc, *vc, *wq, *wo, *w_r, *w_down;
};

__device__ __forceinline__ void frag_store(uint8_t* p, const uint32_t (&a)[32]) {
#pragma unroll
    for (int i = 0; i < 8; i++)
        __stcg(reinterpret_cast<uint4*>(p + i * 512), make_uint4(a[4 * i], a[4 * i + 1], a[4 * i + 2], a[4 * i + 3]));
}
template <int LO = 0, int HI = 8>
__device__ __forceinline__ void frag_load(uint32_t (&a)[32], const uint8_t* p) {
#pragma unroll
    for (int i = LO; i < HI; i++) {
        const uint4 v = ld_relaxed(reinterpret_cast<const uint4*>(p + i * 512));
        a[4 * i] = v.x; a[4 * i + 1] = v.y; a[4 * i + 2] = v.z; a[4 * i + 3] = v.w;
    }
}
__device__ __forceinline__ float quad_sum(float v) {
    v += __shfl_xor_sync(0xffffffffu, v, 1);
    return v + __shfl_xor_sync(0xffffffffu, v, 2);
}
__device__ __forceinline__ float quad_max(float v) {
    v = fmaxf(v, __shfl_xor_sync(0xffffffffu, v, 1));
    return fmaxf(v, __shfl_xor_sync(0xffffffffu, v, 2));
}
__device__ __forceinline__ float rcp_fast(float x) { float y; asm("rcp.approx.ftz.f32 %0, %1;" : "=f"(y) : "f"(x)); return y; }
__device__ __forceinline__ float sigmoidf_(float x) { return rcp_fast(1.f + ex2(-1.4426950408889634f * x)); }
__device__ __forceinline__ void top2(uint32_t k, uint32_t& k1, uint32_t& k2) {
    k1 = __reduce_max_sync(0xffffffffu, k);
    k2 = __reduce_max_sync(0xffffffffu, k == k1 ? 0 : k);
}

__device__ __forceinline__ void mod_fma(float (&a)[8], const uint4 w, float sc) {
    a[0] += sc * bf_lo(w.x); a[1] += sc * bf_hi(w.x); a[2] += sc * bf_lo(w.y); a[3] += sc * bf_hi(w.y);
    a[4] += sc * bf_lo(w.z); a[5] += sc * bf_hi(w.z); a[6] += sc * bf_lo(w.w); a[7] += sc * bf_hi(w.w);
}
__device__ __forceinline__ float mod_reduce(float (&a)[8], int lane) {
#pragma unroll
    for (int h = 4; h > 0; h >>= 1) {
        const bool up = lane & (8 / h);
#pragma unroll
        for (int i = 0; i < h; i++)
            a[i] = (up ? a[i + h] : a[i]) + __shfl_xor_sync(0xffffffffu, up ? a[i] : a[i + h], 8 / h);
    }
    return a[0] + __shfl_xor_sync(0xffffffffu, a[0], 16);
}

__device__ __forceinline__ float ln_stats(float sum, float sq, uint32_t& mean2) {
    const float mean = sum * (1.f / D_);
    const float var = fmaxf(fmaf(-mean, mean, sq * (1.f / D_)), 0.f);
    float sd;
    asm("sqrt.approx.ftz.f32 %0, %1;" : "=f"(sd) : "f"(rbf(rbf(var) + 1e-5f)));
    mean2 = pack_bf16(mean, mean);
    return rcp_fast(rbf(sd));
}
__device__ __forceinline__ uint32_t ln_pair(uint32_t x, uint32_t mean2, float rsd) {
    const uint32_t d = bsub2(x, mean2);
    return pack_bf16(bf_lo(d) * rsd, bf_hi(d) * rsd);
}
__device__ __forceinline__ void rows_load(uint32_t (&x)[20], uint32_t xs, int cw) {
#pragma unroll
    for (int ch = 0; ch < 5; ch++) {
        const uint4 v = ldsm4(ch < 4 ? xs + ch * 256 : xs + 1024 - cw * 16);
        x[4 * ch] = v.x; x[4 * ch + 1] = v.y; x[4 * ch + 2] = v.z; x[4 * ch + 3] = v.w;
    }
}
__device__ __forceinline__ void stats_add(float (&st)[12], uint32_t a, uint32_t b, uint32_t w) {
    mma1688(st, a, b, w);
    mma1688(st + 4, a, b, a);
    mma1688(st + 8, a, b, b);
}
__device__ __forceinline__ float rows_stats(const float (&st)[12], float4* rec, int cw, int lane, uint32_t& mean2, float& dot) {
    const int g8 = lane >> 2;
    if ((g8 >> 1) == (lane & 3)) {
        rec[cw * 16 + g8] = make_float4(st[0], (g8 & 1) ? st[5] : st[4], st[1], 0.f);
        rec[cw * 16 + 8 + g8] = make_float4(st[2], (g8 & 1) ? st[11] : st[10], st[3], 0.f);
    }
    bar_sync(3, 256);
    const float4* r = rec + (lane >> 4) * 64 + (lane & 15);
    const float4 s0 = r[0], s1 = r[16], s2 = r[32], s3 = r[48];
    const float sum = (s0.x + s1.x) + (s2.x + s3.x), sq = (s0.y + s1.y) + (s2.y + s3.y);
    dot = (s0.z + s1.z) + (s2.z + s3.z);
    dot += __shfl_xor_sync(0xffffffffu, dot, 16);
    return ln_stats(sum + __shfl_xor_sync(0xffffffffu, sum, 16), sq + __shfl_xor_sync(0xffffffffu, sq, 16), mean2);
}
template <class F>
__device__ __forceinline__ void rows_normalise(uint32_t* y, const uint32_t* x, uint32_t mean2, float rsd, int lane, F loads) {
    const int g8 = lane >> 2;
    const uint32_t ma2 = __shfl_sync(0xffffffffu, mean2, g8), mb2 = __shfl_sync(0xffffffffu, mean2, g8 + 8);
    const float ra = __shfl_sync(0xffffffffu, rsd, g8), rb = __shfl_sync(0xffffffffu, rsd, g8 + 8);
    loads();
#pragma unroll
    for (int k = 0; k < 9; k++) { y[2 * k] = ln_pair(x[2 * k], ma2, ra); y[2 * k + 1] = ln_pair(x[2 * k + 1], mb2, rb); }
}

__device__ __forceinline__ uint4 h_frag(const uint4* hf, int ks, int lane) {
    if (ks < 32) return ld_relaxed2(hf + ks * 32);
    const uint2* p = reinterpret_cast<const uint2*>(padd(hf, 256 - lane * 8) + ks * 32 - 16);
    const uint2 a = ld_relaxed64(p), b = ld_relaxed64(p + 32);
    return make_uint4(a.x, a.y, b.x, b.y);
}

__device__ __noinline__ void attn_fallback(uint32_t bad, uint32_t tag, const Scratch* gs, uint8_t* frag, uint8_t* keep, const bf16* wq, const bf16* kc, const bf16* vc) {
  const int lane = threadIdx.x & 31, g8 = lane >> 2, qd = lane & 3;
  const int role = cluster_role(), j = role & 7, qb = (role >> 3) * 2 + (blockIdx.x & 1);
  const uint4* hf = g_h + (size_t)(qb * 8 + (threadIdx.x >> 5) - 4) * (36 * 32) + lane;
#pragma unroll 1
  for (int t = 0; t < 4; t++) {
    if (!((bad >> t) & 1)) continue;
    const bf16 *wqp = wq + (4 * j + t) * DH, *kp = kc + (size_t)(2 * j + (t >> 1)) * S_ * DH, *vp = vc + (size_t)(2 * j + (t >> 1)) * S_ * DH;
    uint32_t q[32];
    float o[64];
#pragma unroll
    for (int i = 0; i < 64; i++) o[i] = 0.f;
#pragma unroll 1
    for (int ks = 0; ks < 36; ks++) {
        const uint4 a = h_frag(hf, ks, lane);
        const unsigned short* wr = reinterpret_cast<const unsigned short*>(wqp + (size_t)(ks * 16 + 2 * qd) * QD + g8);
#pragma unroll
        for (int dt = 0; dt < 16; dt++) {
            const uint32_t b0 = __ldg(wr + dt * 8) | ((uint32_t)__ldg(wr + dt * 8 + QD) << 16);
            const uint32_t b1 = __ldg(wr + dt * 8 + 8 * QD) | ((uint32_t)__ldg(wr + dt * 8 + 9 * QD) << 16);
            mma16816(o + 4 * dt, a.x, a.y, a.z, a.w, b0, b1);
        }
    }
#pragma unroll
    for (int i = 0; i < 32; i++) q[i] = pack_bf16(o[2 * i], o[2 * i + 1]);
#pragma unroll
    for (int i = 0; i < 64; i++) o[i] = 0.f;
    float m0 = -INFINITY, m1 = -INFINITY, l0 = 0.f, l1 = 0.f;
#pragma unroll 1
    for (int key = 0; key < S_; key += 16) {
        float sc[8];
#pragma unroll
        for (int i = 0; i < 8; i++) sc[i] = 0.f;
#pragma unroll
        for (int nt = 0; nt < 2; nt++) {
            const uint32_t* kr = reinterpret_cast<const uint32_t*>(kp + (size_t)(key + nt * 8 + g8) * DH) + qd;
#pragma unroll
            for (int ks = 0; ks < 8; ks++)
                mma16816(sc + 4 * nt, q[4 * ks], q[4 * ks + 1], q[4 * ks + 2], q[4 * ks + 3], __ldg(kr + ks * 8), __ldg(kr + ks * 8 + 4));
        }
        const float n0 = quad_max(fmaxf(fmaxf(m0, fmaxf(sc[0], sc[1])), fmaxf(sc[4], sc[5])));
        const float n1 = quad_max(fmaxf(fmaxf(m1, fmaxf(sc[2], sc[3])), fmaxf(sc[6], sc[7])));
        const float f0 = ex2((m0 - n0) * CS), f1 = ex2((m1 - n1) * CS);
        m0 = n0; m1 = n1;
#pragma unroll
        for (int i = 0; i < 8; i++) sc[i] = ex2((sc[i] - ((i & 2) ? n1 : n0)) * CS);
        l0 = l0 * f0 + (sc[0] + sc[1]) + (sc[4] + sc[5]);
        l1 = l1 * f1 + (sc[2] + sc[3]) + (sc[6] + sc[7]);
        const uint32_t e0 = pack_bf16(sc[0], sc[1]), e1 = pack_bf16(sc[2], sc[3]), e2 = pack_bf16(sc[4], sc[5]), e3 = pack_bf16(sc[6], sc[7]);
        const unsigned short* vr = reinterpret_cast<const unsigned short*>(vp + (size_t)(key + 2 * qd) * DH + g8);
#pragma unroll
        for (int dt = 0; dt < 16; dt++) {
            o[4 * dt] *= f0; o[4 * dt + 1] *= f0; o[4 * dt + 2] *= f1; o[4 * dt + 3] *= f1;
            const uint32_t b0 = __ldg(vr + dt * 8) | ((uint32_t)__ldg(vr + dt * 8 + DH) << 16);
            const uint32_t b1 = __ldg(vr + dt * 8 + 8 * DH) | ((uint32_t)__ldg(vr + dt * 8 + 9 * DH) << 16);
            mma16816(o + 4 * dt, e0, e1, e2, e3, b0, b1);
        }
    }
    const float i0 = 1.f / quad_sum(l0), i1 = 1.f / quad_sum(l1);
#pragma unroll
    for (int i = 0; i < 16; i++) {
        q[2 * i] = pack_bf16(o[4 * i] * i0, o[4 * i + 1] * i0);
        q[2 * i + 1] = pack_bf16(o[4 * i + 2] * i1, o[4 * i + 3] * i1);
    }
    frag_store(t < 3 ? frag + t * 4096 : keep, q);
  }
}

__device__ __forceinline__ void spare_q3(Scratch* gs, uint32_t sb, uint32_t bar_full, uint32_t bar_empty, int lane, int cw) {
    const uint32_t tag = load_tag(gs);
    uint32_t rel_base, e = 3;
    asm("mapa.shared::cluster.u32 %0, %1, %2;" : "=r"(rel_base) : "r"(bar_empty), "r"(lane & 1));
#pragma unroll 1
    for (int qb = blockIdx.x - NCTA; qb < 16; qb += 4) {
        uint32_t h[144];
        float o[64];
        flag_wait(&g_flag_h[(qb * 8 + cw) * 32], tag);
        const uint4* hf = g_h + (size_t)(qb * 8 + cw) * (36 * 32) + lane;
#pragma unroll
        for (int ks = 0; ks < 36; ks++) {
            const uint4 v = h_frag(hf, ks, lane);
            h[4 * ks] = v.x; h[4 * ks + 1] = v.y; h[4 * ks + 2] = v.z; h[4 * ks + 3] = v.w;
        }
#pragma unroll
        for (int i = 0; i < 64; i++) o[i] = 0.f;
#pragma unroll 1
        for (int v = 0; v < 4; v++) {
            fence_regs(o);
#pragma unroll
            for (int t = 0; t < 5; t++) {
                mbar_wait(bar_full + 8 * (e & 3), (e >> 2) & 1);
                uint64_t dv = mkdesc(sb + (e & 3) * SLOT, UNIT, 1024);
                WG_FENCE();
#pragma unroll
                for (int ks = 0; ks < (t < 4 ? 8 : 4); ks++)
                    mma_rs128<1>(o, h[32 * t + 4 * ks], h[32 * t + 4 * ks + 1], h[32 * t + 4 * ks + 2], h[32 * t + 4 * ks + 3], dv, ks | t);
                WG_COMMIT();
                if (t > 0) { WG_WAIT(1); if (lane < 2) mbar_arrive_cluster(rel_base + 8 * ((e - 1) & 3)); }
                e++;
            }
            WG_WAIT(0);
            fence_regs(o);
            if (lane < 2) mbar_arrive_cluster(rel_base + 8 * ((e - 1) & 3));
            uint4* dst = &g_q3[((qb * 8 + 2 * v) * 8 + cw) * 128 + lane];
#pragma unroll
            for (int i = 0; i < 8; i++)
                __stcg(dst + (i >> 2) * 1024 + (i & 3) * 32, make_uint4(pack_bf16(o[8 * i], o[8 * i + 1]), pack_bf16(o[8 * i + 2], o[8 * i + 3]),
                                                                        pack_bf16(o[8 * i + 4], o[8 * i + 5]), pack_bf16(o[8 * i + 6], o[8 * i + 7])));
        }
        bar_sync(3, 256);
        if (cw == 0 && lane == 0) flag_release(&g_flag_q3[qb * 32], tag);
        __syncwarp();
    }
}

template <bool SPARE>
__global__ void __cluster_dims__(2, 1, 1) __launch_bounds__(384, 1)
fused_kernel(const Args args, const __grid_constant__ CUtensorMap tm_wq,
             const __grid_constant__ CUtensorMap tm_k, const __grid_constant__ CUtensorMap tm_v,
             const __grid_constant__ CUtensorMap tm_wo, const __grid_constant__ CUtensorMap tm_p,
             const __grid_constant__ CUtensorMap tm_x, const __grid_constant__ CUtensorMap tm_d,
             const __grid_constant__ CUtensorMap tm_g, const __grid_constant__ CUtensorMap tm_u) {
    extern __shared__ __align__(1024) uint8_t smem_raw[];
    const uint32_t sb = smem_u32(smem_raw);
    Scratch* const gs = args.gs;
    const uint32_t bar_full = sb + SM_BAR;
    const uint32_t bar_g = bar_full + 8 * 4;
    const uint32_t bar_mod = bar_g + 8;
    const uint32_t bar_go = bar_mod + 8;
    const uint32_t bar_x = bar_go + 40;
    const uint32_t bar_empty = bar_x + 8;
    const uint32_t bar_pub = bar_empty + 8 * 4;
    const uint32_t bar_qfree = bar_pub + 32;
    const uint32_t bar_out = bar_qfree + 24;
    const uint32_t bar_q3 = bar_out + 8;
    const uint32_t bar_pre = bar_q3 + 16;
    const uint32_t bar_w0 = bar_q3 + 8;
    constexpr int E0 = SPARE ? 2 : 0;

    const int c = blockIdx.x & 1;
#define ROLES() const int role = cluster_role(), j = role & 7, qb = (role >> 3) * 2 + c, rg = qb * 8 + j
    const int warp = __shfl_sync(0xffffffffu, threadIdx.x >> 5, 0);

    if (SPARE && blockIdx.x >= NCTA && warp >= 4) {
        asm volatile("barrier.cluster.arrive.relaxed.aligned;" ::: "memory");
        asm volatile("setmaxnreg.inc.sync.aligned.u32 240;");
        asm volatile("barrier.cluster.wait.aligned;" ::: "memory");
        spare_q3(gs, sb, bar_full, bar_empty, threadIdx.x & 31, warp - 4);
        asm volatile("barrier.cluster.arrive.relaxed.aligned;\nbarrier.cluster.wait.aligned;" ::: "memory");
    } else if (warp < 4) {
        asm volatile("setmaxnreg.dec.sync.aligned.u32 24;");
        ROLES();
        int lane;
        asm volatile("mov.u32 %0, %%laneid;" : "=r"(lane));
        if (warp == 2 && elect()) {
            if (TMPF) asm volatile("prefetch.tensormap [%0];" ::"l"(&tm_x) : "memory");
#pragma unroll
            for (int i = 0; i < 27; i++) mbar_init(bar_full + 8 * i, i < 12 || i >= 23 ? 1 : i < 16 ? 16 : 8);
#pragma unroll
            for (int i = 0; i <= E0; i++) {
                mbar_arrive(bar_full + 8 * i);
                asm volatile("mbarrier.arrive.shared::cta.b64 _, [%0], 16;" ::"r"(bar_empty + 8 * i) : "memory");
            }
            asm volatile("fence.mbarrier_init.release.cluster;" ::: "memory");
        }
        __syncwarp();
        asm volatile("barrier.cluster.arrive.relaxed.aligned;" ::: "memory");
        if (warp == 2 && !(SPARE && blockIdx.x >= NCTA)) {
            if (XDELAY) __nanosleep(XDELAY);
            if (elect()) {
                mbar_expect_tx(bar_x, 16 * XP);
                tma2d(sb + SM_Q, &tm_x, 0, rg * 16, bar_x);
            }
            __syncwarp();
        }
        asm volatile("barrier.cluster.wait.aligned;" ::: "memory");
        const uint32_t tag = load_tag(gs);
        if (SPARE && blockIdx.x >= NCTA) {
            if (warp == 1) {
#pragma unroll 1
                for (int e = 3; e < 83; e++) {
                    const int v = (e - 3) / 5;
                    mbar_wait_sleep(bar_empty + 8 * (e & 3), ~(e >> 2) & 1);
                    if (elect()) {
                        mbar_expect_tx(bar_full + 8 * (e & 3), SLOT);
                        tma2d_mc(sb + (e & 3) * SLOT + c * UNIT, &tm_wq, (8 * (v & 3) + 4 * c + 3) * DH + 64, (e - 3 - v * 5) * 128,
                                 bar_full + 8 * (e & 3), EVICT_NORMAL);
                    }
                }
            }
            __syncwarp();
            asm volatile("barrier.cluster.arrive.relaxed.aligned;\nbarrier.cluster.wait.aligned;" ::: "memory");
            return;
        }
        if (warp == 3) {
#pragma unroll 1
            for (int e = 4; e < 20; e++) {
                __nanosleep(e == 4 ? PFD0 : PFD1);
                const int hd = (e * 52) >> 8, row = (e - hd * 5) * 128 + qb * 8 + (lane >> 1);
                if (lane < 16 && row < D_)
                    asm volatile("prefetch.global.L2 [%0];" ::"l"(padd(args.wq, (row * QD + (4 * j + ((0x1320 >> (4 * hd)) & 3)) * DH + (lane & 1) * 64) * 2)) : "memory");
            }
            __syncwarp();
            mbar_wait_sleep(bar_go, 0);
#pragma unroll 1
            for (int unit = 72 + blockIdx.x; unit < 216; unit += NCTA) {
                float a[8];
#pragma unroll
                for (int i = 0; i < 8; i++) a[i] = 0.f;
#pragma unroll 1
                for (int k = lane >> 1; k < D_; k += 16) {
                    const float cv = __bfloat162float(*padd(args.cvec, k * 2));
                    mod_fma(a, __ldg(reinterpret_cast<const uint4*>(padd(args.w_mod, (k * (6 * D_) + unit * 16 + (lane & 1) * 8) * 2))), rbf(cv * sigmoidf_(cv)));
                }
                const float v = mod_reduce(a, lane), v1 = __shfl_down_sync(0xffffffffu, v, 8);
                if (lane < 8) *padd(gs->mod2, ((unit - 72) * 8 + (lane & 1) * 4 + (lane & 2) + (lane >> 2)) * 4) = pack_bf16(v, v1);
            }
            __syncwarp();
            if (lane == 0) flag_release(padd(g_flag_mod, blockIdx.x * 4), tag);
#pragma unroll 1
            for (int k = 0; k < 36; k++) {
                __nanosleep(200);
                __stcg(padd(gs->h[0], (~tag & 1) * (NCTA * 36 * 512) + ((rg * 36 + k) * 32 + lane) * 16), make_uint4(0, 0, 0, 0));
            }
            __syncwarp();
            mbar_wait_sleep(bar_qfree + 16, 0);
            __nanosleep(2000);
            {
                uint4 v;
                uint32_t it = 0;
#pragma unroll 1
                do {
                    v = ld_relaxed(reinterpret_cast<const uint4*>(padd(g_flag_mod, lane * 16)));
                } while (((v.x ^ tag) | (v.y ^ tag) | (v.z ^ tag) | (v.w ^ tag)) && ++it < SPIN / 16);
                asm volatile("fence.acquire.gpu;" ::: "memory");
            }
            __syncwarp();
            {
                float w1 = 0.f, w2 = 0.f;
#pragma unroll 1
                for (int k = lane; k < D_ / 2; k += 32) {
                    const uint32_t* mp = padd(gs->mod2, k * 4);
                    const uint32_t sv = __ldcg(mp + D_ / 2), c1 = badd2(__ldcg(mp + D_), 0x3f803f80u);
                    const uint32_t wr = *reinterpret_cast<const uint32_t*>(padd(args.w_r, k * 4)), wp = bmul2(c1, wr);
                    reinterpret_cast<uint2*>(smem_raw + SM_T)[k] = make_uint2(__ldcg(mp), wp);
                    reinterpret_cast<uint2*>(smem_raw + SM_TC)[k] = make_uint2(c1, sv);
                    reinterpret_cast<uint32_t*>(smem_raw + SM_TG)[k] = __ldcg(mp + 3 * D_ / 2);
                    w1 += bf_lo(wp) + bf_hi(wp);
                    w2 += bf_lo(sv) * bf_lo(wr) + bf_hi(sv) * bf_hi(wr);
                }
#pragma unroll 1
                for (int i = 1; i < 32; i <<= 1) { w1 += __shfl_xor_sync(0xffffffffu, w1, i); w2 += __shfl_xor_sync(0xffffffffu, w2, i); }
                *reinterpret_cast<float2*>(smem_raw + SM_TS) = make_float2(w1, w2);
            }
#pragma unroll
            for (int i = 0; i < 4; i++) reinterpret_cast<uint4*>(smem_raw + SM_RED)[lane + 32 * i] = make_uint4(~0u, ~0u, ~0u, ~0u);
            asm volatile("fence.proxy.async.shared::cta;" ::: "memory");
            __syncwarp();
            if (elect()) {
                uint8_t* mb = g_frag + (size_t)rg * 8 * WREG + 3 * 4096;
#pragma unroll 1
                for (int k = 0; k < 8; k++, mb += WREG) {
#pragma unroll
                    for (int i = 0; i < 3; i++)
                        asm volatile("cp.async.bulk.global.shared::cta.bulk_group [%0], [%1], 2048;" ::"l"(mb + i * 2048), "r"(sb + SM_RED) : "memory");
                    __nanosleep(500);
                }
                asm volatile("cp.async.bulk.commit_group;\ncp.async.bulk.wait_group 0;\nfence.proxy.async.global;" ::: "memory");
            }
            __syncwarp();
            if (lane == 0) mbar_arrive(bar_mod);
            __syncwarp();
            mbar_wait_sleep(bar_go + 8, 0);
            if (elect()) asm volatile("prefetch.tensormap [%0];\nprefetch.tensormap [%1];\nprefetch.tensormap [%2];" ::"l"(&tm_x), "l"(&tm_p), "l"(&tm_d) : "memory");
            __syncwarp();
#pragma unroll 1
            for (int i = 1; i < 4; i++) {
                mbar_wait(bar_pub + 8 * i, 0);
                unsigned int* flags = padd(g_flag_part, (qb * 32 + i * 8 - 8) * 4);
                if (elect()) { flag_release(padd(flags, j * 4), tag); DBG_PG(93); }
                __syncwarp();
                const uint32_t slot = (i + 2) & 3;
                flag_wait(padd(flags, (lane & 7) * 4), tag);
                asm volatile("fence.proxy.async.global;" ::: "memory");
                if (lane == 0 && i == 3) DBG_PG(101);
                mbar_wait(bar_go + 8 + 8 * i, 0);
                mbar_wait(bar_empty + 8 * slot, i == 3);
                if (elect()) {
                    mbar_expect_tx(bar_full + 8 * slot, SLOT);
                    tma3d(sb + slot * SLOT, &tm_p, 0, j * 20 + (i - 1) * 4, qb * 8, bar_full + 8 * slot);
                    tma3d(sb + slot * SLOT + UNIT, &tm_p, 0, j * 20 + (i - 1) * 4 + 2, qb * 8, bar_full + 8 * slot);
                }
            }
        } else if (warp == 0) {
#pragma unroll 1
            for (int i = 0; i < 48; i++) {
                if (i == 0 || i == 17 || i == 34) mbar_wait_sleep(bar_qfree + (i >> 4) * 8, 0);
                if (SPARE && i == 17) {
                    flag_wait(&g_flag_q3[qb * 32], tag);
                    if (elect()) {
                        asm volatile("fence.proxy.async.global;" ::: "memory");
                        mbar_expect_tx(bar_q3, UNIT);
#pragma unroll 1
                        for (int k = 0; k < 8; k++) bulk_load(sb + SM_Q + 2 * SLOT + k * 4096 + 2048, &g_q3[(rg * 8 + k) * 128], 2048, bar_q3);
                    }
                }
                __nanosleep(700);
                if (elect()) {
                    asm volatile("mbarrier.expect_tx.shared::cta.b64 [%0], %1;" ::"r"(bar_g), "n"(1920) : "memory");
                    tma2d(sb + SM_Q + i * 1920, i < 24 ? &tm_g : &tm_u, (blockIdx.x * 36) & ~7, (i < 24 ? i : i - 24) * 24, bar_g);
                }
            }
            if (elect()) mbar_arrive(bar_g);
#pragma unroll 1
            for (int i = 0; i < 18; i++) {
                __nanosleep(400);
                if (OPF && i < 8 * OPF && elect()) l2_prefetch(g_frag + (size_t)(rg * 8 + (i & 7)) * WREG + (i >> 3) * 4096, 4096);
                if (elect()) l2_prefetch(args.w_down + (size_t)(blockIdx.x * 36 + i * 2) * D_, 4 * D_);
            }
            __syncwarp();
            mbar_wait_sleep(bar_go + 8 * 2, 0);
            uint32_t acc = 0;
#pragma unroll 1
            for (int k = lane; k < 16 * 9; k += 32) acc |= touch(padd(args.x, (rg * 16 * D_ + k * 64) * 2));
            if (acc == 0) reinterpret_cast<volatile uint32_t*>(smem_raw + SM_BAR)[127] = acc;
            __syncwarp();
            mbar_wait_sleep(bar_go + 8 * 4, 0);
            uint4* rp = padd(g_rows, (rg * 2 * RSLOT + lane) * 16);
#pragma unroll
            for (int k = 0; k < 12; k++) rp[k * 32] = make_uint4(~0u, ~0u, ~0u, ~0u);
            if (blockIdx.x < 72) {
                uint4* yp = reinterpret_cast<uint4*>(padd(g_ypart, blockIdx.x * NCTA * 64 + lane * 16));
#pragma unroll
                for (int k = 0; k < 16; k++) yp[k * 32] = make_uint4(~0u, ~0u, ~0u, ~0u);
            }
            asm volatile("fence.acq_rel.gpu;" ::: "memory");
            __syncwarp();
            if (lane == 0) mbar_arrive(bar_pre);
        } else if (warp == 1) {
            __nanosleep(QDELAY);
            uint32_t go = bar_go;
            uint64_t marks = 24 | 151 << 8 | 155 << 16 | 160ull << 24 | 165ull << 32;
#pragma unroll 1
            for (int e = E0; e < 168; e++) {
                const CUtensorMap* tm;
                int c0, c1;
                uint64_t pol = EVICT_FIRST;
                if (e == 159 || e == 164) continue;
                if (e < 21 && e != 19) {
                    const int i = SPARE && e < 12 ? e - 2 : e - (e == 20), hd = (i * 52) >> 8;
                    tm = &tm_wq; c0 = (4 * j + ((0x1320 >> (4 * hd)) & 3)) * DH + c * 64; c1 = (i - hd * 5) * 128 - 64;
                    if (SPARE && e >= 12 && e < 15) { c0 = (4 * j + 3) * DH; c1 = (2 * (e - 12) + c) * 128; }
                } else if (e < 148) {
                    const int i = max(e - 20, 0);
                    const bool isk = i == 0 || ((i & 1) && i < 127);
                    const int n = isk ? (i + 1) >> 1 : (i - 1) >> 1;
                    tm = isk ? &tm_k : &tm_v; c0 = c * 64; c1 = (2 * j + (n >> 5)) * S_ + (n & 15) * 128;
                    if (!(i & 32)) pol = EVICT_NORMAL;
                } else {
                    int i = e - 148 - (e > 159) - (e > 164);
                    tm = &tm_wo; c0 = (i >> 1) * 64; c1 = (4 * j + (O2F ? ((i & 1) ? c : 2 + c) : (i & 1) ? 1 + c : 3 * c)) * DH;
                }
                const uint32_t fb = e == E0 ? bar_w0 : bar_full + 8 * (e & 3), d = sb + (e == E0 ? 6 : e & 3) * SLOT;
                if (e >= 24 && e < 152) mbar_wait_sleep(bar_empty + 8 * (e & 3), ~(e >> 2) & 1);
                else if (e != E0) mbar_wait(bar_empty + 8 * (e & 3), ~(e >> 2) & 1);
                if (elect()) {
                    mbar_expect_tx(fb, SLOT);
                    tma2d_mc(d + c * UNIT, tm, c0, c1, fb, pol);
                    const int i = e - PF_KV;
                    if (i >= 0 && i < 128 && !(i & 32))
                        l2_prefetch(((i & 1) ? args.vc : args.kc) + (size_t)((2 * j + (i >> 6)) * S_ + (i & 30) * 64) * DH + qb * 1024, 2048);
                    if (e >= PF_WO && e < PF_WO + 18) l2_prefetch(args.wo + (size_t)blockIdx.x * (QD * D_ / NCTA) + (e - PF_WO) * 1024, 2048);
                    if (e == (marks & 255)) mbar_arrive(go);
                }
                if (e == (marks & 255)) { go += 8; marks >>= 8; }
            }
            asm volatile("fence.proxy.async.global;" ::: "memory");
            mbar_wait(bar_empty, 1);
            if (elect()) {
                mbar_expect_tx(bar_full, 16 * XP);
                tma2d(sb, &tm_x, 0, rg * 16, bar_full);
            }
            mbar_wait(bar_empty + 16, 1);
            if (C3D) __nanosleep(C3D);
            if (elect()) {
                mbar_expect_tx(bar_full + 16, SLOT);
                tma3d(sb + 2 * SLOT, &tm_p, 0, j * 20 + 12, qb * 8, bar_full + 16);
                tma3d(sb + 2 * SLOT + UNIT, &tm_p, 0, j * 20 + 14, qb * 8, bar_full + 16);
            }
            mbar_wait(bar_empty + 24, 1);
            if (C4D) __nanosleep(C4D);
            if (elect()) {
                mbar_expect_tx(bar_full + 24, UNIT);
                tma3d(sb + 3 * SLOT, &tm_p, 0, j * 20 + 16, qb * 8, bar_full + 24);
            }
            mbar_wait(bar_empty + 8, 0);
            mbar_wait(bar_empty + 16, 0);
            if (DD) __nanosleep(DD);
            if (elect()) {
#pragma unroll
                for (int i = 1; i < 3; i++) {
                    mbar_expect_tx(bar_full + 8 * i, 18 * XP);
                    tma2d(sb + i * SLOT, &tm_d, 0, blockIdx.x * 36 + (i - 1) * 18, bar_full + 8 * i);
                }
            }
        } else {
            if (elect()) asm volatile("prefetch.tensormap [%0];\nprefetch.tensormap [%1];\nprefetch.tensormap [%2];" ::"l"(&tm_k), "l"(&tm_v), "l"(&tm_wo) : "memory");
            if (SPARE) {
                mbar_wait_sleep(bar_pub, 0);
                if (lane == 0) flag_release(padd(g_flag_h, rg * 128), tag);
                __syncwarp();
            }
            bar_sync(1, 192);
#pragma unroll 1
            for (uint32_t e = 20; e < 148; e++) {
                mbar_wait_sleep(bar_full + 8 * (e & 3), (e >> 2) & 1);
                if (SPARE && e == 113) mbar_wait(bar_q3, 0);
                if (e & 1) bar_sync(1, 192);
                if (!(e & 1) || e == 147) bar_sync(4, 160);
            }
#pragma unroll 1
            for (uint32_t e = 148; e < 168; e++) {
                mbar_wait(bar_full + 8 * (e & 3), (e >> 2) & 1);
                if (e != 159 && e != 164) bar_sync(1, 192);
            }
        }
        __syncwarp();
        mbar_wait_sleep(bar_out, 0);
        if (OUTD) __nanosleep(OUTD);
        if (elect()) {
            asm volatile("fence.proxy.async.shared::cta;" ::: "memory");
            const int2 sel = reinterpret_cast<const int2*>(smem_raw + SM_RED)[8];
#pragma unroll 1
            for (int i = warp; i < 16; i += 4) {
                const int row = rg * 16 + i;
                if (row != sel.x && row != sel.y)
                    asm volatile("cp.async.bulk.global.shared::cta.bulk_group.L2::cache_hint [%0], [%1], %2, %3;"
                                 ::"l"(args.out + (size_t)row * D_), "r"(sb + i * XP), "n"(D_ * 2), "l"(OUTPOL) : "memory");
            }
            asm volatile("cp.async.bulk.commit_group;\ncp.async.bulk.wait_group.read 0;" ::: "memory");
        }
    } else {
        uint32_t cv[2] = {0, 0}, tag = load_tag(gs) - 1;
        if (blockIdx.x < 72) {
            uint32_t ws;
            int tid;
            asm volatile("mov.u32 %0, smem_raw;\nmov.u32 %1, %%tid.x;" : "=r"(ws), "=r"(tid));
            tid -= 128;
            ws += SM_Q + SLOT + tid * 16;
            const uint32_t* cp = padd(reinterpret_cast<const uint32_t*>(args.cvec), (tid & 0xe0) + (tid & 7) * 4);
            cv[0] = *padd(cp, (tid & 24) * 32);
            if (tid < 128) cv[1] = cp[256];
            const bf16* wrow = args.w_mod + (size_t)(tid >> 1) * (6 * D_) + (tid & 1) * 8 + blockIdx.x * 16;
#pragma unroll
            for (int i = 0; i < 5; i++)
                if (i < 4 || tid < 128)
                    asm volatile("cp.async.cg.shared.global [%0], [%1], 16;" ::"r"(ws + i * 4096), "l"(wrow + (size_t)i * 128 * (6 * D_)) : "memory");
        }
        asm volatile("barrier.cluster.arrive.relaxed.aligned;" ::: "memory");
        asm volatile("setmaxnreg.inc.sync.aligned.u32 240;");
        const int lane = threadIdx.x & 31;
        const int cw = warp - 4;
        const int w = cw >> 2;
        const int tid = threadIdx.x - 128;
        ROLES();
        float* red = reinterpret_cast<float*>(smem_raw + SM_RED);
        DBG_INIT();
        DBG_G(120);
        DBG_T(100);

        {
            if (blockIdx.x < 72) {
                uint32_t sa[10];
#pragma unroll
                for (int i = 0; i < 2; i++) {
                    const float lo = bf_lo(cv[i]), hi = bf_hi(cv[i]);
                    cv[i] = pack_bf16(lo * sigmoidf_(lo), hi * sigmoidf_(hi));
                }
#pragma unroll
                for (int i = 0; i < 10; i++) sa[i] = __shfl_sync(0xffffffffu, cv[i >> 3], (i & 7) * 4 + (lane & 3));
                uint2* mdst = &gs->mod1[(tid >> 3) * D_ + blockIdx.x * 8 + (tid & 7)];
                anchor(bar_full + 504, sa[0] & sa[1] & sa[2] & sa[3] & sa[4] & sa[5] & sa[6] & sa[7] & sa[8] & sa[9] & (uint32_t)(uintptr_t)mdst & (uint32_t)((uintptr_t)mdst >> 32));
                asm volatile("cp.async.wait_all;" ::: "memory");
                __syncwarp();
                const uint32_t ws = sb + SM_Q + SLOT + cw * 512 + (lane & 15) * 32 + (lane & 16);
                float d[16];
#pragma unroll
                for (int i = 0; i < 16; i++) d[i] = 0.f;
#pragma unroll
                for (int i = 0; i < 5; i++) {
                    const uint4 b = ldsm4t(ws + (i < 4 || cw < 4 ? i * 4096 : 0));
                    mma16816(d + 8 * (i & 1), sa[2 * i], sa[2 * i], sa[2 * i + 1], sa[2 * i + 1], b.x, b.y);
                    mma16816(d + 8 * (i & 1) + 4, sa[2 * i], sa[2 * i], sa[2 * i + 1], sa[2 * i + 1], b.z, b.w);
                }
                if (lane < 8) reinterpret_cast<float2*>(red)[lane * 8 + cw] = (lane & 4) ? make_float2(d[4] + d[12], d[5] + d[13]) : make_float2(d[0] + d[8], d[1] + d[9]);
                bar_sync(3, 256);
                if (tid < 8 * MREP) {
                    const float4* r = reinterpret_cast<const float4*>(red) + (tid & 7) * 4;
                    const float4 r0 = r[0], r1 = r[1], r2 = r[2], r3 = r[3];
                    st_relaxed64(mdst, pack_bf16(((r0.x + r0.z) + (r1.x + r1.z)) + ((r2.x + r2.z) + (r3.x + r3.z)),
                                                 ((r0.y + r0.w) + (r1.y + r1.w)) + ((r2.y + r2.w) + (r3.y + r3.w))), tag + 1);
                }
            }
            DBG_G(106);
            asm volatile("barrier.cluster.wait.aligned;" ::: "memory");
            mbar_wait(bar_x, 0);
            asm volatile("add.u32 %0, %0, 1;" : "+r"(tag));
            uint32_t x[20];
            float st[12], st2[12];
            rows_load(x, sb + SM_Q + (lane & 15) * XP + (lane >> 4) * 16 + cw * 32, cw);
#pragma unroll
            for (int i = 0; i < 12; i++) { st[i] = 0.f; st2[i] = 0.f; }
#pragma unroll
            for (int k = 0; k < 9; k++) stats_add((k & 1) ? st2 : st, x[2 * k], x[2 * k + 1], 0x3f803f80u);
#pragma unroll
            for (int i = 0; i < 12; i++) st[i] += st2[i];
            uint32_t mean2;
            float dot;
            const float rsd = rows_stats(st, reinterpret_cast<float4*>(red + 128), cw, lane, mean2, dot);
            const uint4* mp = reinterpret_cast<const uint4*>(gs->mod1 + ((blockIdx.x >> 1) & (MREP - 1)) * D_) + min(tid, D_ / 4 - 1);
            uint4 v0 = make_uint4(0, tag, 0, tag), v1 = v0;
            auto look = [&]() {
                asm volatile("{\n.reg .pred p;\n.reg .b64 a, b, c, d;\nsetp.lt.s32 p, %9, 5;\nmov.b64 a, {%0, %1};\nmov.b64 b, {%2, %3};\n"
                             "mov.b64 c, {%4, %5};\nmov.b64 d, {%6, %7};\n@p ld.relaxed.gpu.global.v2.b64 {a, b}, [%8];\n"
                             "@p ld.relaxed.gpu.global.v2.b64 {c, d}, [%8 + 2304];\n"
                             "mov.b64 {%0, %1}, a;\nmov.b64 {%2, %3}, b;\nmov.b64 {%4, %5}, c;\nmov.b64 {%6, %7}, d;\n}"
                             : "+r"(v0.x), "+r"(v0.y), "+r"(v0.z), "+r"(v0.w), "+r"(v1.x), "+r"(v1.y), "+r"(v1.z), "+r"(v1.w)
                             : "l"(mp), "r"(cw) : "memory");
            };
            rows_normalise(x, x, mean2, rsd, lane, look);
            fence_regs(x);
            uint32_t it = 0;
#pragma unroll 1
            while (((v0.y ^ tag) | (v0.w ^ tag) | (v1.y ^ tag) | (v1.w ^ tag)) && ++it < SPIN / 16) look();
            uint4* smod = reinterpret_cast<uint4*>(smem_raw + SM_Q + M_MOD);
            if (tid < D_ / 4) smod[tid] = make_uint4(badd2(v1.x, 0x3f803f80u), v0.x, badd2(v1.z, 0x3f803f80u), v0.z);
            uint4* hdst = g_h + (size_t)(rg * 36 + cw) * 32 + lane;
            uint2* hdst2 = reinterpret_cast<uint2*>(g_h + (size_t)(rg * 36 + 32) * 32) + tid;
            bar_sync(3, 256);
            DBG_G(107);
#pragma unroll
            for (int k = 0; k < 9; k++) {
                const uint2 cs = lds64(sb + SM_Q + M_MOD + (cw * 8 + (lane & 3) + (k < 8 ? (k >> 1) * 64 + (k & 1) * 4 : 256 - cw * 4)) * 8);
                const uint32_t c1 = cs.x, sa = cs.y;
                x[2 * k] = badd2(bmul2(x[2 * k], c1), sa);
                if (x[2 * k] == 0) x[2 * k] = 0x8000u;
                x[2 * k + 1] = badd2(bmul2(x[2 * k + 1], c1), sa);
            }
#pragma unroll
            for (int ch = 0; ch < 4; ch++) st_relaxed4(hdst + ch * 256, x[4 * ch], x[4 * ch + 1], x[4 * ch + 2], x[4 * ch + 3]);
            st_relaxed64(hdst2, x[16], x[17]);
            __syncwarp();
            if (SPARE && lane == 0) mbar_arrive(bar_pub);
            DBG_G(108);
        }

        uint32_t rel_base;
        asm("mapa.shared::cluster.u32 %0, %1, %2;" : "=r"(rel_base) : "r"(bar_empty), "r"(lane & 1));
        auto release = [&](uint32_t slot) { if (lane < 2) mbar_arrive_cluster(rel_base + 8 * slot); };
        uint32_t q[32], p[32];
        float s[64], o[64];

        uint4* qpark = reinterpret_cast<uint4*>(smem_raw + SM_Q - SLOT) + cw * 256 + lane;
        {
            uint32_t h[144];
            const uint4* hf = g_h + (size_t)(qb * 8 + cw) * (36 * 32) + lane;
            auto load_h = [&](auto lo, auto hi) {
#pragma unroll
                for (int ks = lo.value; ks < hi.value; ks++) {
                    const uint4 v = h_frag(hf, ks, lane);
                    h[4 * ks] = v.x; h[4 * ks + 1] = v.y; h[4 * ks + 2] = v.z; h[4 * ks + 3] = v.w;
                }
            };
            auto check_h = [&](auto lo, auto hi) {
                uint32_t it = 0;
                bool miss;
#pragma unroll 1
                do {
                    uint32_t mn = ~0u;
#pragma unroll
                    for (int ks = lo.value; ks < hi.value; ks++) mn = __vimin3_u32(mn, h[4 * ks], h[4 * ks + 2]);
                    miss = __any_sync(0xffffffffu, mn == 0);
                    if (miss) load_h(lo, hi);
                    asm volatile("add.u32 %0, %0, 1;" : "+r"(it));
                } while (miss && it < SPIN / 16);
            };
            __nanosleep(HDELAY);
            load_h(IC<0>{}, IC<4>{});
            DBG_T(104); DBG_G(109);
#pragma unroll
            for (int i = 0; i < 64; i++) o[i] = 0.f;
            uint32_t e = E0;
#pragma unroll 1
            for (int hd = 1;; hd++) {
                fence_regs(o);
                auto group = [&](auto tc) {
                    constexpr int t = tc.value, k0 = t ? 8 * t - 4 : 0;
                    const bool first = t == 0 && hd == 1;
                    mbar_wait(first ? bar_w0 : bar_full + 8 * (e & 3), (e >> 2) & 1);
                    uint64_t dv = args.d0 + ((t ? 0 : 512) + (first ? 6 : e & 3) * (SLOT / 16));
                    if (hd == 1) check_h(IC<k0>{}, IC<8 * t + 4>{});
                    WG_FENCE();
#pragma unroll
                    for (int ks = k0; ks < 8 * t + 4; ks++)
                        mma_rs128<1>(o, h[4 * ks], h[4 * ks + 1], h[4 * ks + 2], h[4 * ks + 3], dv, ks);
                    WG_COMMIT();
                    if (hd == 1) { if (t == 0) {   } if (t == 1) {   } if (t == 2) {   } if (t == 3) {   } if (t == 4) {   } }
                    if (t < 4 && hd == 1) load_h(IC<8 * t + 4>{}, IC<t < 4 ? 8 * t + 12 : 0>{});
                    if (t > 0) { WG_WAIT(1); if (t > 1 || hd > 1) release((e - 1) & 3); }
                    e++;
                };
                group(IC<0>{}); group(IC<1>{}); group(IC<2>{}); group(IC<3>{});
                if (e == 19) break;
                group(IC<4>{});
                WG_WAIT(0);
                if (hd == 1) {     }
                fence_regs(o);
                release((e - 1) & 3);
#pragma unroll
                for (int i = 0; i < 8; i++)
                    qpark[hd * 2048 + i * 32] = make_uint4(pack_bf16(o[8 * i], o[8 * i + 1]), pack_bf16(o[8 * i + 2], o[8 * i + 3]),
                                                           pack_bf16(o[8 * i + 4], o[8 * i + 5]), pack_bf16(o[8 * i + 6], o[8 * i + 7]));
                if (SPARE && hd == 2) {
                    float (&u)[32] = reinterpret_cast<float (&)[32]>(o);
                    fence_regs(u);
#pragma unroll
                    for (int t = 0; t < 3; t++) {
                        mbar_wait(bar_full + 8 * t, 1);
                        uint64_t dv = args.d0 + t * (SLOT / 16);
                        WG_FENCE();
#pragma unroll
                        for (int ks = 0; ks < (t < 2 ? 16 : 4); ks++)
                            mma_rs64<1>(u, h[64 * t + 4 * ks], h[64 * t + 4 * ks + 1], h[64 * t + 4 * ks + 2], h[64 * t + 4 * ks + 3],
                                        dv, ks | t);
                        WG_COMMIT();
                        if (t > 0) { WG_WAIT(1); release(t - 1); }
                    }
                    WG_WAIT(0);
                    fence_regs(u);
                    release(2);
                    e = 15;
#pragma unroll
                    for (int i = 0; i < 4; i++)
                        qpark[3 * 2048 + i * 32] = make_uint4(pack_bf16(u[8 * i], u[8 * i + 1]), pack_bf16(u[8 * i + 2], u[8 * i + 3]),
                                                              pack_bf16(u[8 * i + 4], u[8 * i + 5]), pack_bf16(u[8 * i + 6], u[8 * i + 7]));
                }
            }
#pragma unroll
            for (int i = 0; i < 8; i++) {
                const uint4 v = qpark[2048 + i * 32];
                q[4 * i] = v.x; q[4 * i + 1] = v.y; q[4 * i + 2] = v.z; q[4 * i + 3] = v.w;
            }
#pragma unroll
            for (int i = 0; i < 32; i++) p[i] = h[112 + i];
            mbar_wait(bar_full + 24, 0);
            WG_WAIT(0);
            fence_regs(o);
            release(2);
        }
        DBG_T(105);
        DBG_G(125);

        uint8_t* frag = reinterpret_cast<uint8_t*>(__shfl_sync(0xffffffffu, reinterpret_cast<unsigned long long>(g_frag + (size_t)(rg * 8 + cw) * WREG + lane * 16), lane));
        const uint4* qnext = reinterpret_cast<const uint4*>(__shfl_sync(0xffffffffu, reinterpret_cast<unsigned long long>(padd(smem_raw, SM_Q + tid * 16 + cw * 3584)), lane));
        uint8_t* odst = reinterpret_cast<uint8_t*>(const_cast<uint4*>(qnext));
        qnext -= 2048;
        float m0, m1, l0 = 0.25f, l1 = 0.25f, t0, t1;
        uint32_t bad = 0;
        const int lw = cw & 3;
        const uint32_t relw = lw == RW && lane < 8, handw = lw == HW || cw == HW2;
        auto release4 = [&](uint32_t off) {
            asm volatile("{\n.reg .pred p;\nsetp.ne.b32 p, %1, 0;\n@p mbarrier.arrive.shared::cluster.b64 _, [%0];\n}" ::"r"(rel_base + off), "r"(relw) : "memory"); };
        auto handoff = [&]() {
            asm volatile("{\n.reg .pred p;\nsetp.ne.b32 p, %1, 0;\n@p bar.arrive %0, 192;\n}" ::"r"(2 - w), "r"(handw) : "memory"); };
        if (cw == 4 + HW) bar_arrive(1, 192);
        auto finish = [&](auto lo, auto hi, uint32_t bit, auto sink) {
#pragma unroll
            for (int i = lo.value; i < hi.value; i++) {
                const uint32_t v0 = pack_bf16(o[8 * i] * t0, o[8 * i + 1] * t0), v1 = pack_bf16(o[8 * i + 2] * t1, o[8 * i + 3] * t1);
                const uint32_t v2 = pack_bf16(o[8 * i + 4] * t0, o[8 * i + 5] * t0), v3 = pack_bf16(o[8 * i + 6] * t1, o[8 * i + 7] * t1);
                if (i == 0 && fabsf(o[0] * t0) >= 0x1p-31f) bad |= bit << 8;
                sink(i, v0, v1, v2, v3);
            }
        };
        float lq[6];
        auto row_parts = [&]() {
#pragma unroll
            for (int i = 0; i < 3; i++) { lq[i] = __shfl_xor_sync(0xffffffffu, l0, i + 1); lq[3 + i] = __shfl_xor_sync(0xffffffffu, l1, i + 1); }
        };
        auto row_sums = [&](uint32_t bit) {
            t0 = (l0 + lq[0]) + (lq[1] + lq[2]); t1 = (l1 + lq[3]) + (lq[4] + lq[5]);
            if (!(t0 >= LMIN && t0 < LMAX && t1 >= LMIN && t1 < LMAX)) bad |= bit;
        };
        auto issue_pv = [&](uint64_t dv, int acc, auto lo, auto hi) {
            if (lo.value == 0) asm volatile("{\n.reg .pred p;\nsetp.eq.b32 p, %0, 0;\n@p bar.sync 4, 160;\n}" ::"r"(w) : "memory");
#pragma unroll
            for (int ks = lo.value; ks < hi.value; ks++)
                mma_rs128<1>(o, p[4 * ks], p[4 * ks + 1], p[4 * ks + 2], p[4 * ks + 3], dv, ks ? 1 : acc);
            WG_COMMIT();
        };
#pragma unroll
        for (int i = 0; i < 64; i++) s[i] = 0.f;
        uint64_t dv_lo = args.d0;
        uint32_t voff = 0;
        auto issue_qk = [&]() {
            uint64_t dk = dv_lo ^ (desc_lo(0, UNIT) ^ desc_lo(3 * SLOT, 16));
            bar_sync(1 + w, 192);
            fence_regs(s); fence_regs(q); fence_regs(o); fence_regs(p);
            WG_FENCE();
#pragma unroll
            for (int ks = 0; ks < 8; ks++)
                if (ks == 3) mma_rs128<0, 1018>(s, q[4 * ks], q[4 * ks + 1], q[4 * ks + 2], q[4 * ks + 3], dk, 1);
                else mma_rs128<0, 2>(s, q[4 * ks], q[4 * ks + 1], q[4 * ks + 2], q[4 * ks + 3], dk, ks != 0);
            WG_COMMIT();
        };
        auto to_frag = [&](int i, uint32_t v0, uint32_t v1, uint32_t v2, uint32_t v3) {
            *reinterpret_cast<uint4*>(odst + i * 512) = make_uint4(v0, v1, v2, v3); };
        int n = 0;
        auto scores_ready = [&]() {
            WG_WAIT(1);
            fence_regs(s); fence_regs(q);
        };
        auto pass_on = [&]() {
            release4(voff ^ 24);
            handoff();
        };
#pragma unroll 1
        for (;;) {
            {
                if (RPE) {
                    asm volatile("st.shared.v2.f32 [%0], {%1, %2};" ::"r"(sb + SM_RED + tid * 8), "f"(l0), "f"(l1) : "memory");
                    __syncwarp();
                    const uint4 a = lds128(sb + SM_RED + (tid & ~3) * 8), b = lds128(sb + SM_RED + (tid & ~3) * 8 + 16);
                    l0 = __uint_as_float(a.x); lq[0] = __uint_as_float(a.z); lq[1] = __uint_as_float(b.x); lq[2] = __uint_as_float(b.z);
                    l1 = __uint_as_float(a.y); lq[3] = __uint_as_float(a.w); lq[4] = __uint_as_float(b.y); lq[5] = __uint_as_float(b.w);
                } else {
                    row_parts();
                }
                issue_qk();
                if (RPE == 2) hold(l0, l1);
                row_sums(1u << (n >> 4));
                t0 = rcp_fast(t0); t1 = rcp_fast(t1);
                l0 = 0.f; l1 = 0.f;
                odst = n ? frag + ((n >> 4) - 1) * 4096 : odst;
                qnext = n == 48 ? reinterpret_cast<const uint4*>(frag + O2F * 8192) : qnext + 2048;
                if (RPE) anchor(bar_full + 504, (t0 + t1) * __uint_as_float((bad ^ (uint32_t)(uintptr_t)odst ^ (uint32_t)(uintptr_t)qnext) & 0x3fffffff));
                asm volatile("{\n.reg .pred p;\nsetp.ne.b32 p, %1, 0;\n@p mbarrier.arrive.shared::cta.b64 _, [%0];\n}"
                             ::"r"(bar_qfree + (n >> 1) - 8), "r"(lane ? 0 : n) : "memory");
                issue_pv(dv_lo, 1, IC<0>{}, IC<8>{});
                scores_ready();
                float a0 = fmaxf(s[0], s[1]), a1 = fmaxf(s[2], s[3]), a2 = fmaxf(s[4], s[5]), a3 = fmaxf(s[6], s[7]);
#pragma unroll
                for (int i = 1; i < MAXG; i++) {
                    a0 = fmaxf(a0, fmaxf(s[8 * i], s[8 * i + 1])); a1 = fmaxf(a1, fmaxf(s[8 * i + 2], s[8 * i + 3]));
                    a2 = fmaxf(a2, fmaxf(s[8 * i + 4], s[8 * i + 5])); a3 = fmaxf(a3, fmaxf(s[8 * i + 6], s[8 * i + 7]));
                }
                const uint32_t a = MAXG ? pack_bf16(fmaxf(a0, a2), fmaxf(a1, a3)) : pack_bf16(a0, a1);
                const uint32_t b = bmax2(bmax2(a, __shfl_xor_sync(0xffffffffu, a, 1)), bmax2(__shfl_xor_sync(0xffffffffu, a, 2), __shfl_xor_sync(0xffffffffu, a, 3)));
                pass_on();
                m0 = fmaf(-CS, bf_lo(b), -POFF); m1 = fmaf(-CS, bf_hi(b), -POFF);
            }
#pragma unroll 1
            for (;;) {
                DBG_T(n);
#pragma unroll
                for (int i = 0; i < 4 * STAGE; i++) s[i] = fmaf(s[i], CS, (i & 2) ? m1 : m0);
#pragma unroll
                for (int i = 0; i < 4 * SPLIT; i++) s[i] = ex2(s[i]);
#pragma unroll
                for (int i = 0; i < SPLIT; i++) { l0 += s[4 * i] + s[4 * i + 1]; l1 += s[4 * i + 2] + s[4 * i + 3]; }
                if (STAGE < 16) {
                    m0 = fmaf(l0, 0.f, m0); m1 = fmaf(l1, 0.f, m1);
                }
                anchor(bar_full + 504, l0 + l1);
                WG_WAIT(0);
                fence_regs(o); fence_regs(p);
                release4(voff);
                dv_lo ^= 2 * SLOT / 16;
                voff ^= 16;
                n++;
#pragma unroll
                for (int i = 4 * STAGE; i < 64; i++) s[i] = fmaf(s[i], CS, (i & 2) ? m1 : m0);
#pragma unroll
                for (int i = 4 * SPLIT; i < 64; i++) s[i] = ex2(s[i]);
#pragma unroll
                for (int i = SPLIT; i < 16; i++) { l0 += s[4 * i] + s[4 * i + 1]; l1 += s[4 * i + 2] + s[4 * i + 3]; }
#pragma unroll
                for (int i = 0; i < 32; i++) p[i] = pack_bf16(s[2 * i], s[2 * i + 1]);
                const int jn = n & 15;
                if (jn > 1) {
                    issue_qk();
                    if ((n & RA) == RB) {
                        if (n & 1) {
#pragma unroll
                            for (int i = 0; i < 64; i++) o[i] *= (i & 2) ? t1 : t0;
                        } else {
                            row_parts();
                            row_sums(2u << (n >> 4));
                            const uint32_t e0 = __float_as_uint(t0) >> 23, e1 = __float_as_uint(t1) >> 23;
                            m0 -= __uint_as_float(0x4b000000u | e0) - (8388608.f + 127.f - POFF);
                            m1 -= __uint_as_float(0x4b000000u | e1) - (8388608.f + 127.f - POFF);
                            t0 = __uint_as_float((254 - (int)POFF - e0) << 23); t1 = __uint_as_float((254 - (int)POFF - e1) << 23);
                            l0 *= t0; l1 *= t1;
                        }
                    }
                    fence_regs(o);
                    WG_FENCE();
                    issue_pv(dv_lo, 1, IC<0>{}, IC<8>{});
                    scores_ready();
                    pass_on();
                    if (jn != 15) continue;
#pragma unroll
                    for (int i = 0; i < 8; i++) {
                        const uint4 v = qnext[i * 32];
                        q[4 * i] = v.x; q[4 * i + 1] = v.y; q[4 * i + 2] = v.z; q[4 * i + 3] = v.w;
                    }
                    continue;
                }
                if (jn == 0) break;
                finish(IC<0>{}, IC<ESPLIT>{}, 1u << (n >> 4), to_frag);
                issue_qk();
                if (HOLD) hold(t0, t1);
                finish(IC<ESPLIT>{}, IC<8>{}, 1u << (n >> 4), to_frag);
                WG_FENCE();
                issue_pv(dv_lo, 0, IC<0>{}, IC<8>{});
                scores_ready();
                pass_on();
            }
            if (n == 64) break;
        }
        DBG_T(64);
        uint32_t a1[32], a2[32];
        bar_sync(1 + w, 192);
        fence_regs(o); fence_regs(p);
        WG_FENCE();
        issue_pv(args.d0 + 3 * SLOT / 16, 1, IC<0>{}, IC<8>{});
        handoff();
        mbar_wait(bar_mod, 0);
        const int tid_ = __shfl_sync(0xffffffffu, tid, lane);
        row_parts();
        row_sums(16);
        t0 = rcp_fast(t0); t1 = rcp_fast(t1);
        anchor(frag, q[0] & q[4] & q[8] & q[12] & q[16] & q[20] & q[24] & q[28] & __float_as_uint(t0) & __float_as_uint(t1) & tid_);
        frag_load(a1, frag + (1 - O2F) * 4096);
        frag_load<0, A2N>(a2, frag + (2 - O2F) * 4096);
        anchor(frag, bad);
        WG_WAIT(0);
        fence_regs(o); fence_regs(p);
        release4(24);
        finish(IC<0>{}, IC<8>{}, 16, [&](int i, uint32_t v0, uint32_t v1, uint32_t v2, uint32_t v3) {
            p[4 * i] = v0; p[4 * i + 1] = v1; p[4 * i + 2] = v2; p[4 * i + 3] = v3; });
        if (A2N < 8) { anchor(frag, p[31] & p[15]); frag_load<A2N, 8>(a2, frag + (2 - O2F) * 4096); }
        bad = __reduce_or_sync(0xffffffffu, bad);
        bad = ((bad | ~(bad >> 8)) >> 1) & 15;
        if (__builtin_expect(bad != 0, 0)) {
            uint8_t* keep = g_keep + (size_t)(rg * 8 + cw) * 4096 + lane * 16;
            frag_store(keep, p);
            attn_fallback(bad, tag, gs, frag, keep, args.wq, args.kc, args.vc);
            frag_load(q, frag + O2F * 8192); frag_load(a1, frag + (1 - O2F) * 4096); frag_load(a2, frag + (2 - O2F) * 4096); frag_load(p, keep);
            anchor(frag, q[0] & q[4] & q[8] & q[12] & q[16] & q[20] & q[24] & q[28] & p[0] & p[4] & p[8] & p[12] & p[16] & p[20] & p[24] & p[28]);
        }
        DBG_T(80);
        DBG_G(124);

        const uint32_t eye = (lane >> 3) == (lane & 3) ? 0x3f80u << ((lane & 4) * 4) : 0;
        auto sum8 = [&](uint32_t* r, const uint4 (&v)[8]) {
            float d[16];
#pragma unroll
            for (int i = 0; i < 16; i++) d[i] = 0.f;
#pragma unroll
            for (int src = 0; src < 8; src++) {
                mma1688(d + 8 * (src & 1), v[src].x, v[src].y, eye);
                mma1688(d + 8 * (src & 1) + 4, v[src].z, v[src].w, eye);
            }
#pragma unroll
            for (int i = 0; i < 4; i++) r[i] = pack_bf16(d[2 * i] + d[8 + 2 * i], d[2 * i + 1] + d[9 + 2 * i]);
        };
        uint4 v2[8], v3[8], wf[23];
        uint2 u4[8], gw[9];
        uint32_t x1[20], xs, pa, ta;
        const uint8_t *mb, *mb4;
        auto load_wf = [&](auto lo, auto hi) {
            const uint32_t wa = sb + SM_Q + ((tid_ & 8) * (D_ / 8) + cw * 16 + (tid_ & 7) + (tid_ & 16) / 2) * 80;
            const uint32_t wb = wa + (512 - cw * 8) * 80 - (tid_ & 16) * 39;
#pragma unroll
            for (int i = lo.value; i < hi.value; i++) wf[i] = ldsm4t(i < 20 ? wa + (i / 5) * 10240 + (i % 5) * 16 : wb + (i - 20) * 32);
        };
        uint32_t at[18];
        {
            float (&u)[32] = reinterpret_cast<float (&)[32]>(o);
            uint32_t off = 0;
            auto turn = [&](const uint32_t (&a)[32], const uint32_t (&b)[32], int acc) {
                uint64_t dv = args.d0 + off * (SLOT / 128);
                bar_sync(1 + w, 192);
                fence_regs(u);
                WG_FENCE();
#pragma unroll
                for (int ks = 0; ks < 16; ks++) {
                    const uint32_t* f = ks < 8 ? &a[4 * ks] : &b[4 * ks - 32];
                    mma_rs64<1>(u, f[0], f[1], f[2], f[3], dv, ks | acc);
                    if (ks == OSPLIT - 1) WG_COMMIT();
                }
                WG_COMMIT();
                WG_WAIT(1);
            };
            auto done = [&]() {
                WG_WAIT(0);
                fence_regs(u);
                release4(off);
                off = (off + 8) & 24;
            };
            auto store = [&](uint8_t* dst) {
#pragma unroll
                for (int i = 0; i < 4; i++)
                    st_relaxed4(dst + i * 512, pack_bf16(u[8 * i], u[8 * i + 1]), pack_bf16(u[8 * i + 2], u[8 * i + 3]),
                                pack_bf16(u[8 * i + 4], u[8 * i + 5]), pack_bf16(u[8 * i + 6], u[8 * i + 7]));
            };
            pa = sb + w * (UNIT - 2048) + tid_ * 16;
#pragma unroll
            for (int i = 0; i < 8; i++) at[i] = 0;
            fence_regs(q); fence_regs(p);
            uint8_t* dst = frag;
#pragma unroll
            for (int i = 0; i < 8; i++) asm volatile("" : "=r"(v2[i].x), "=r"(v2[i].y), "=r"(v2[i].z), "=r"(v2[i].w));
#pragma unroll 1
            for (int k = 0; k < 8; k++, dst += 2048) {
                const uint32_t poff = (off + 8) & 24;
                const bool sum = (0xa0 >> k) & 1;
                turn(q, p, 0);
                handoff();
                auto sum_p = [&](auto lo, auto hi) {
#pragma unroll
                    for (int i = lo.value; i < hi.value; i++) {
                        float a[8], b[8];
#pragma unroll
                        for (int src = 0; src < 8; src++) {
                            const uint32_t x = i == 0 ? v2[src].x : i == 1 ? v2[src].y : i == 2 ? v2[src].z : v2[src].w;
                            a[src] = bf_lo(x); b[src] = bf_hi(x);
                        }
                        at[i] = at[4 + i];
                        at[4 + i] = pack_bf16(((a[0] + a[2]) + (a[4] + a[6])) + ((a[1] + a[3]) + (a[5] + a[7])),
                                              ((b[0] + b[2]) + (b[4] + b[6])) + ((b[1] + b[3]) + (b[5] + b[7])));
                    }
                };
                if (sum) {
                    mbar_wait(bar_full + poff, 1);
#pragma unroll
                    for (int src = 0; src < 8; src++) v2[src] = lds128(pa + poff * (SLOT / 8) + src * 2048);
                    __syncwarp();
                    release(poff >> 3);
                    done();
                    off = (off + 8) & 24;
                    sum_p(IC<0>{}, IC<PS>{});
                } else {
                    done();
                }
                turn(a1, a2, 1);
                handoff();
                if (PS < 4 && sum) sum_p(IC<PS>{}, IC<4>{});
                done();
                store(dst);
                __syncwarp();
                asm volatile("{\n.reg .pred p;\nsetp.ne.b32 p, %1, 0;\n@p mbarrier.arrive.shared::cta.b64 _, [%0];\n}"
                             ::"r"(bar_pub + 4 + 4 * k), "r"(lane ? 0 : (0x2a >> k) & 1) : "memory");
            }
            turn(q, p, 0);
            handoff();
            mb = padd(g_frag, (qb * 64 + j) * WREG + 3 * 4096 + tid_ * 16);
            mb4 = padd(mb, 4096 + ((cw >> 1) - cw) * 512 + (cw & 1) * 8);
            xs = sb + (tid_ & 15) * XP + (tid_ & 16) + cw * 32;
            ta = sb + (cw * 8 + (tid_ & 3)) * 8;
#pragma unroll
            for (int k = 0; k < 9; k++) {
                gw[k] = lds64(ta + SM_T + (k < 8 ? (k >> 1) * 64 + (k & 1) * 4 : 256 - cw * 4) * 8);
                if (!(tid_ & 4)) gw[k].y = 0x3f803f80u;
            }
            mbar_wait(bar_g, 0);
            done();
            load_wf(IC<0>{}, IC<WF0>{});
            turn(a1, a2, 1);
            if (w == 0) handoff();
            if (P2E) {
                mbar_wait(bar_full + 8, 0);
#pragma unroll
                for (int src = 0; src < 8; src++) v2[src] = lds128(pa + SLOT + src * 2048);
            }
            done();
            store(dst);
            mbar_wait(bar_full, 0);
            rows_load(x1, xs, cw);
            if (w == 0) bar_sync(5, 256); else bar_arrive(5, 256);
        }
        DBG_T(81);
        DBG_G(122);

        {
        const int tid = tid_, lane = tid & 31;
        const int g8 = lane >> 2, qd = lane & 3, l16 = lane & 15;
        uint32_t h2[18], gb[9], k1, k2;
        float4* rec = reinterpret_cast<float4*>(red + 128);
        const uint2* candp = reinterpret_cast<const uint2*>(padd(g_cand, ((blockIdx.x & (CREP - 1)) * NCTA + (tid >> 1)) * 32 + (tid & 1) * 8));
        uint2 cd;
        auto stage_out = [&]() {
#pragma unroll
            for (int k = 0; k < 9; k++) {
                x1[2 * k] = badd2(x1[2 * k], bmul2(gb[k], h2[2 * k]));
                x1[2 * k + 1] = badd2(x1[2 * k + 1], bmul2(gb[k], h2[2 * k + 1]));
            }
#pragma unroll
            for (int ch = 0; ch < 4; ch++) stsm_x4(xs + ch * 256, x1[4 * ch], x1[4 * ch + 1], x1[4 * ch + 2], x1[4 * ch + 3]);
            asm volatile("stmatrix.sync.aligned.m8n8.x2.shared.b16 [%0], {%1, %2};" ::"r"(xs + 1024 - cw * 16), "r"(x1[16]), "r"(x1[17]) : "memory");
        };
        {
            uint32_t it = 0, miss;
            if (!P2E) {
                mbar_wait(bar_full + 8, 0);
#pragma unroll
                for (int src = 0; src < 8; src++) v2[src] = lds128(pa + SLOT + src * 2048);
            }
            sum8(at + 8, v2);
            float st[12];
#pragma unroll
            for (int i = 0; i < 12; i++) st[i] = 0.f;
            auto add_pair = [&](int k) {
                x1[2 * k] = badd2(x1[2 * k], bmul2(gw[k].x, at[2 * k]));
                x1[2 * k + 1] = badd2(x1[2 * k + 1], bmul2(gw[k].x, at[2 * k + 1]));
                stats_add(st, x1[2 * k], x1[2 * k + 1], gw[k].y);
            };
#pragma unroll
            for (int k = 0; k < 6; k++) add_pair(k);
            mbar_wait(bar_full + 16, 0);
#pragma unroll
            for (int src = 0; src < 8; src++) v3[src] = lds128(pa + 2 * SLOT + src * 2048);
#pragma unroll 1
            do {
                if (BO && it) __nanosleep(BO);
                miss = 0;
#pragma unroll
                for (int src = 0; src < 8; src++) reload16(v3[src], mb + (size_t)src * 8 * WREG, miss);
            } while (__any_sync(0xffffffffu, miss) && ++it < SPIN / 16);
            if (lane < 4) mbar_arrive_cluster(rel_base + 8 * (1 + (lane >> 1)));
            sum8(at + 12, v3);
            add_pair(6); add_pair(7);
            load_wf(IC<WF0>{}, IC<WF1>{});
            uint2 cs[9];
#pragma unroll
            for (int k = 0; k < 9; k++) cs[k] = lds64(ta + SM_TC + (k < 8 ? (k >> 1) * 64 + (k & 1) * 4 : 256 - cw * 4) * 8);
            mbar_wait(bar_pre, 0);
            mbar_wait(bar_full + 24, 0);
#pragma unroll
            for (int src = 0; src < 8; src++) u4[src] = lds64(sb + 3 * SLOT + src * 2048 + (cw >> 1) * 512 + lane * 16 + (cw & 1) * 8);
#pragma unroll 1
            do {
                if (BO && miss) __nanosleep(BO);
                miss = 0;
#pragma unroll
                for (int src = 0; src < 8; src++) reload8(u4[src], mb4 + (size_t)src * 8 * WREG, miss);
            } while (__any_sync(0xffffffffu, miss) && ++it < SPIN / 16);
            float d[8] = {0.f, 0.f, 0.f, 0.f, 0.f, 0.f, 0.f, 0.f};
#pragma unroll
            for (int i = 0; i < 4; i++) mma16816(d + 4 * (i & 1), u4[2 * i].x, u4[2 * i].y, u4[2 * i + 1].x, u4[2 * i + 1].y, eye, eye);
            at[16] = pack_bf16(d[0] + d[4], d[1] + d[5]); at[17] = pack_bf16(d[2] + d[6], d[3] + d[7]);
            add_pair(8);
            DBG_G(123);
            const float2 ws = *reinterpret_cast<const float2*>(smem_raw + SM_TS);
            uint4* cdst = padd(g_cand, CFULL ? ((tid >> 1) * NCTA + rg) * 32 + (tid & 1) * 16 : (tid * NCTA + rg) * 32);
            uint32_t mean2;
            float dot;
            const float rsd = rows_stats(st, rec, cw, lane, mean2, dot);
            const uint32_t b = __float_as_uint(fmaf(fmaf(-bf_lo(mean2), ws.x, dot), rsd, ws.y));
            const uint32_t key = (((b & 0x80000000u) ? ~b : (b | 0x80000000u)) | 2047u) - (rg * 16 + l16);
            top2(key, k1, k2);
            if (tid < (CFULL + 1) * CREP) st_relaxed(cdst, k1, tag, k2, tag);
            cd = ld_relaxed64(candp);
            rows_normalise(h2, x1, mean2, rsd, lane, [&]() {
#pragma unroll
                for (int k = 0; k < 9; k++) gb[k] = lds32(sb + SM_TG + (cw * 8 + qd + (k < 8 ? (k >> 1) * 64 + (k & 1) * 4 : 256 - cw * 4)) * 4);
                if (WFE) load_wf(IC<WF1>{}, IC<WF2>{});
            });
#pragma unroll
            for (int k = 0; k < 18; k++) h2[k] = badd2(bmul2(h2[k], cs[k >> 1].x), cs[k >> 1].y);
            const uint32_t r1 = ~k1 & 15, r2 = ~k2 & 15;
            uint32_t todo = ((r1 & 7) == g8) | ((r2 & 7) == g8) << 1;
#pragma unroll 1
            while (todo) {
                const bool second = !(todo & 1), hi = (second ? r2 : r1) & 8;
                uint4* dst = padd(g_rows, ((rg * 2 + second) * RSLOT + cw * 24 + qd) * 16);
                uint32_t r[18];
#pragma unroll
                for (int k = 0; k < 9; k++) { r[k] = hi ? h2[2 * k + 1] : h2[2 * k]; r[9 + k] = hi ? x1[2 * k + 1] : x1[2 * k]; }
                fence_regs(r);
                st_relaxed(dst, r[0], r[1], r[2], r[3]);
                st_relaxed(dst + 8, r[4], r[5], r[6], r[7]);
                st_relaxed64(reinterpret_cast<uint2*>(padd(dst, 256 - qd * 8)), r[8], r[17]);
                st_relaxed(dst + 4, r[9], r[10], r[11], r[12]);
                st_relaxed(dst + 12, r[13], r[14], r[15], r[16]);
                todo &= todo - 1;
            }
            __syncwarp();

            stage_out();
            if (!WFE) load_wf(IC<WF1>{}, IC<WF2>{});
        }
        DBG_G(110);
        float4* part = reinterpret_cast<float4*>(smem_raw + 3 * SLOT + UNIT + 8192);
        bf16* act = reinterpret_cast<bf16*>(smem_raw + 3 * SLOT + UNIT + 4096);
        {
            uint32_t it = 0;
            const bool own = (tid >> 1) == rg;
            const uint32_t ks = sb + 3 * SLOT + UNIT + 5120;
#pragma unroll 1
            while (cd.y != tag && !own && ++it < SPIN / 16) cd = ld_relaxed64(candp);
            asm volatile("st.shared.u32 [%0], %1;" ::"r"(ks + tid * 4), "r"(own ? (tid & 1) ? k2 : k1 : cd.x) : "memory");
            bar_sync(3, 256);
            DBG_G(111);
            const uint4 a = lds128(ks + lane * 16), b = lds128(ks + 512 + lane * 16);
            const uint32_t a1 = max(a.x, a.z), a2 = __vimax3_u32(min(a.x, a.z), a.y, a.w);
            const uint32_t b1 = max(b.x, b.z), b2 = __vimax3_u32(min(b.x, b.z), b.y, b.w);
            const uint32_t c1 = max(a1, b1), c2 = __vimax3_u32(min(a1, b1), a2, b2);
            k1 = __reduce_max_sync(0xffffffffu, c1);
            k2 = __reduce_max_sync(0xffffffffu, c1 == k1 ? c2 : c1);
        }
        const int sel0 = ~k1 & 2047, sel1 = ~k2 & 2047;
        const uint32_t slot0 = (sel0 >> 4) * 2, slot1 = (sel1 >> 4) * 2 + ((sel0 ^ sel1) < 16);
        uint4 da[13];
        {
            const uint4* hp = padd(g_rows, (((g8 & 1) ? slot1 : slot0) * RSLOT + cw * 24 + qd) * 16);
            const uint2* hp2 = reinterpret_cast<const uint2*>(padd(hp, 256 - qd * 8));
            uint4 hv[2] = {ld_relaxed2(hp), ld_relaxed2(hp + 8)};
            uint2 hw = ld_relaxed64(hp2);
            if (tid == 255) {
                reinterpret_cast<int2*>(red)[8] = make_int2(sel0, sel1);
                mbar_arrive(bar_out);
            }
            load_wf(IC<WF2>{}, IC<23>{});
            mbar_wait(bar_full + 8, 1);
            mbar_wait(bar_full + 16, 1);
            auto load_d = [&](auto lo, auto hi) {
                const int r = (lane & 7) + (lane & 16) / 2;
                const uint32_t d0 = sb + SLOT + r * XP + cw * 144 + (lane & 8) * 2, d1 = d0 + (r < 2 ? 16 * XP : SLOT - 2 * XP);
                const uint32_t d2 = sb + 2 * SLOT + (14 + (lane & 3)) * XP + cw * 144 + (lane >> 3) * 16;
#pragma unroll
                for (int i = lo.value; i < hi.value; i++) da[i] = ldsm4t(i < 10 ? ((i & 1) ? d1 : d0) + (i >> 1) * 32 : d2 + (i - 10) * 64);
            };
            load_d(IC<0>{}, IC<DL>{});
            uint32_t it = 0, miss;
#pragma unroll 1
            do {
                miss = 0;
                reload16(hv[0], hp, miss);
                reload16(hv[1], hp + 8, miss);
                reload8(hw, hp2, miss);
            } while (__any_sync(0xffffffffu, miss) && ++it < SPIN / 16);
            DBG_G(112);
            load_d(IC<DL>{}, IC<13>{});
            float acc[20];
#pragma unroll
            for (int i = 0; i < 20; i++) acc[i] = 0.f;
#pragma unroll
            for (int i = 0; i < 5; i++) mma1688(acc + 4 * i, (i & 1) ? wf[20 + i / 2].z : wf[20 + i / 2].x, (i & 1) ? wf[20 + i / 2].w : wf[20 + i / 2].y, hw.x);
#pragma unroll
            for (int i = 0; i < 20; i++)
                mma16816(acc + 4 * (i % 5), wf[i].x, wf[i].y, wf[i].z, wf[i].w, (i / 5 & 1) ? hv[i / 10].z : hv[i / 10].x, (i / 5 & 1) ? hv[i / 10].w : hv[i / 10].y);
            if (qd == 0) {
#pragma unroll
                for (int i = 0; i < 5; i++) part[cw * 40 + i * 8 + g8] = make_float4(acc[4 * i], acc[4 * i + 1], acc[4 * i + 2], acc[4 * i + 3]);
            }
        }
        {
            uint2* dst = padd(g_ypart, ((cw * 9 * NCTA + blockIdx.x) * 8 + g8) * 8);
            bar_sync(3, 256);
            if (cw < 5) {
                const float* pp = reinterpret_cast<const float*>(part) + ((blockIdx.x & 1) << 4) + tid;
                const float g = rbf(((pp[0] + pp[160]) + (pp[320] + pp[480])) + ((pp[640] + pp[800]) + (pp[960] + pp[1120])));
                const float v = rbf(g * sigmoidf_(g)) * __shfl_down_sync(0xffffffffu, g, 2);
                if (!(tid & 2)) act[(tid & 1) * 56 + (tid >> 2)] = __float2bfloat16_rn(tid < 144 ? v : 0.f);
            }
            bar_sync(3, 256);
            DBG_G(113);
            const uint32_t ap = sb + 3 * SLOT + UNIT + 4096 + (lane & 1) * 112 + (lane >> 3) * 16;
            const uint4 b0 = ldsm4(ap);
            const uint32_t b1 = lds32(sb + 3 * SLOT + UNIT + 4096 + (g8 & 1) * 112 + 64 + qd * 4);
            float y[20];
#pragma unroll
            for (int i = 0; i < 20; i++) y[i] = 0.f;
#pragma unroll
            for (int i = 0; i < 5; i++) {
                mma16816(y + 4 * i, da[2 * i].x, da[2 * i].y, da[2 * i].z, da[2 * i].w, b0.x, b0.y);
                mma16816(y + 4 * i, da[2 * i + 1].x, da[2 * i + 1].y, da[2 * i + 1].z, da[2 * i + 1].w, b0.z, b0.w);
                mma1688(y + 4 * i, (i & 1) ? da[10 + i / 2].z : da[10 + i / 2].x, (i & 1) ? da[10 + i / 2].w : da[10 + i / 2].y, b1);
            }
#pragma unroll
            for (int i = 0; i < 9; i++)
                asm volatile("{\n.reg .pred p;\nsetp.eq.b32 p, %3, 0;\n@p st.relaxed.gpu.global.v2.f32 [%0], {%1, %2};\n}"
                             ::"l"(dst + i * (NCTA * 8)), "f"(y[2 * i]), "f"(y[2 * i + 1]), "r"(qd) : "memory");
        }
        DBG_G(114);
        if (blockIdx.x == 127 && tid == 0) gs->epoch[0] = tag;
        if (blockIdx.x < 72) {
            const int G = blockIdx.x, tok = g8 & 1, cp = G * 4 + qd;
            const uint2* src = padd(g_ypart, (blockIdx.x * NCTA * 8 + tid) * 8);
            const uint8_t* hsrc = reinterpret_cast<const uint8_t*>(padd(g_rows, (tok ? slot1 : slot0) * (RSLOT * 16) +
                (G < 64 ? (G >> 1 & 7) * 384 + (G >> 5) * 128 + qd * 16 + (G >> 1 & 8) + (G & 1) * 4 : (G - 64) * 384 + 256 + qd * 8)));
            const uint8_t* xsrc = hsrc + (G < 64 ? 64 : 4);
            uint32_t* dst = padd(reinterpret_cast<uint32_t*>(args.out), (tok ? sel1 : sel0) * (D_ * 2) + cp * 4);
            const uint32_t gb = reinterpret_cast<const uint32_t*>(smem_raw + SM_TG)[cp];
            const uint32_t ksel = ((tok ? k2 : k1) & ~2047u) | 1024u;
            const float sg = sigmoidf_(rbf(__uint_as_float((ksel & 0x80000000u) ? (ksel & 0x7fffffffu) : ~ksel)));
            uint2 v[4];
            uint32_t hv, xv, it = 0;
            bool miss;
#pragma unroll 1
            do {
#pragma unroll
                for (int i = 0; i < 4; i++) v[i] = ld_relaxed64(src + i * 256);
                hv = ld_relaxed32(hsrc);
                xv = ld_relaxed32(xsrc);
                miss = max(__vimax3_u32(v[0].x, v[1].x, v[2].x), __vimax3_u32(v[3].x, hv, xv)) == ~0u;
            } while (__any_sync(0xffffffffu, miss) && ++it < SPIN / 16);
            float y0 = (__uint_as_float(v[0].x) + __uint_as_float(v[1].x)) + (__uint_as_float(v[2].x) + __uint_as_float(v[3].x));
            float y1 = (__uint_as_float(v[0].y) + __uint_as_float(v[1].y)) + (__uint_as_float(v[2].y) + __uint_as_float(v[3].y));
            y0 += __shfl_xor_sync(0xffffffffu, y0, 8); y1 += __shfl_xor_sync(0xffffffffu, y1, 8);
            y0 += __shfl_xor_sync(0xffffffffu, y0, 16); y1 += __shfl_xor_sync(0xffffffffu, y1, 16);
            if (lane < 8) reinterpret_cast<float2*>(rec)[cw * 8 + lane] = make_float2(y0, y1);
            bar_sync(3, 256);
            if (cw == 0) {
                const float4 t0_ = rec[(lane >> 3) * 4 + qd], t1_ = rec[16 + (lane >> 3) * 4 + qd];
                y0 = tok ? t0_.y + t1_.y : t0_.x + t1_.x; y1 = tok ? t0_.w + t1_.w : t0_.z + t1_.z;
                y0 += __shfl_xor_sync(0xffffffffu, y0, 8); y1 += __shfl_xor_sync(0xffffffffu, y1, 8);
                y0 += __shfl_xor_sync(0xffffffffu, y0, 16); y1 += __shfl_xor_sync(0xffffffffu, y1, 16);
                const uint32_t y2 = bmul2(pack_bf16(y0, y1), pack_bf16(sg, sg));
                if (lane < 8) *dst = badd2(xv, bmul2(gb, badd2(hv, y2)));
            }
        }
        }
        DBG_T(88);
        DBG_G(121);
    }
}

typedef CUresult (*EncodeFn)(CUtensorMap*, CUtensorMapDataType, cuuint32_t, void*, const cuuint64_t*, const cuuint64_t*,
                             const cuuint32_t*, const cuuint32_t*, CUtensorMapInterleave, CUtensorMapSwizzle,
                             CUtensorMapL2promotion, CUtensorMapFloatOOBfill);

static void make_map(EncodeFn enc, CUtensorMap* m, const void* ptr, int rank, const cuuint64_t* dims,
                     const cuuint64_t* strides, const cuuint32_t* box, CUtensorMapSwizzle sw = CU_TENSOR_MAP_SWIZZLE_128B,
                     CUtensorMapDataType dt = CU_TENSOR_MAP_DATA_TYPE_BFLOAT16) {
    const cuuint32_t es[3] = {1, 1, 1};
    enc(m, dt, rank, const_cast<void*>(ptr), dims, strides, box, es,
        CU_TENSOR_MAP_INTERLEAVE_NONE, sw, CU_TENSOR_MAP_L2_PROMOTION_L2_128B,
        CU_TENSOR_MAP_FLOAT_OOB_FILL_NONE);
}

extern "C" void kernel_launch(void* const* d_in, const int* in_sizes, int n_in, void* d_out, int out_size) {
    const bf16* x = (const bf16*)d_in[0];
    const bf16* kc = (const bf16*)d_in[1];
    const bf16* vc = (const bf16*)d_in[2];
    const bf16* wq = (const bf16*)d_in[3];
    const bf16* wo = (const bf16*)d_in[4];
    const bf16* w_r = (const bf16*)d_in[6];
    const bf16* w_gate = (const bf16*)d_in[7];
    const bf16* w_up = (const bf16*)d_in[8];
    const bf16* w_down = (const bf16*)d_in[9];
    const bf16* cvec = (const bf16*)d_in[10];
    const bf16* w_mod = (const bf16*)d_in[11];
    bf16* out = (bf16*)d_out;

    void* fn = nullptr;
    cudaDriverEntryPointQueryResult qr;
    cudaGetDriverEntryPoint("cuTensorMapEncodeTiled", &fn, cudaEnableDefault, &qr);
    EncodeFn enc = (EncodeFn)fn;
    void* p_s;
    cudaGetSymbolAddress(&p_s, g_s);

    CUtensorMap tm_wq, tm_k, tm_v, tm_wo, tm_p, tm_x, tm_d, tm_g, tm_u;
    { cuuint64_t d[2] = {QD, D_}, s[1] = {QD * 2}; cuuint32_t b[2] = {64, 128}; make_map(enc, &tm_wq, wq, 2, d, s, b); }
    { cuuint64_t d[2] = {DH, HKV * S_}, s[1] = {DH * 2}; cuuint32_t b[2] = {64, 128};
      make_map(enc, &tm_k, kc, 2, d, s, b); make_map(enc, &tm_v, vc, 2, d, s, b); }
    { cuuint64_t d[2] = {D_, QD}, s[1] = {D_ * 2}; cuuint32_t b[2] = {64, 128}; make_map(enc, &tm_wo, wo, 2, d, s, b); }
    { cuuint64_t d[3] = {256, 160, NCTA}, s[2] = {1024, 8 * WREG}; cuuint32_t b[3] = {256, 2, 8};
      make_map(enc, &tm_p, ((Scratch*)p_s)->frag, 3, d, s, b, CU_TENSOR_MAP_SWIZZLE_NONE, CU_TENSOR_MAP_DATA_TYPE_UINT32); }
    { cuuint64_t d[2] = {D_ / 4, S_}, s[1] = {D_ * 2}; cuuint32_t b[2] = {XP / 8, 16};
      make_map(enc, &tm_x, x, 2, d, s, b, CU_TENSOR_MAP_SWIZZLE_NONE, CU_TENSOR_MAP_DATA_TYPE_UINT64); }
    { cuuint64_t d[2] = {D_ / 4, F_}, s[1] = {D_ * 2}; cuuint32_t b[2] = {XP / 8, 18};
      make_map(enc, &tm_d, w_down, 2, d, s, b, CU_TENSOR_MAP_SWIZZLE_NONE, CU_TENSOR_MAP_DATA_TYPE_UINT64); }
    { cuuint64_t d[2] = {F_, D_}, s[1] = {F_ * 2}; cuuint32_t b[2] = {40, 24};
      make_map(enc, &tm_g, w_gate, 2, d, s, b, CU_TENSOR_MAP_SWIZZLE_NONE); make_map(enc, &tm_u, w_up, 2, d, s, b, CU_TENSOR_MAP_SWIZZLE_NONE); }

    cudaFuncSetAttribute(fused_kernel<true>, cudaFuncAttributeMaxDynamicSharedMemorySize, SM_TOTAL);
    cudaFuncSetAttribute(fused_kernel<false>, cudaFuncAttributeMaxDynamicSharedMemorySize, SM_TOTAL);
    cudaLaunchConfig_t cfg = {};
    cfg.gridDim = NCTA + 4; cfg.blockDim = 384; cfg.dynamicSmemBytes = SM_TOTAL;
    cudaLaunchAttribute at;
    at.id = cudaLaunchAttributeClusterDimension; at.val.clusterDim.x = 2; at.val.clusterDim.y = 1; at.val.clusterDim.z = 1;
    cfg.attrs = &at; cfg.numAttrs = 1;
    int ncl = 0;
    if (cudaOccupancyMaxActiveClusters(&ncl, fused_kernel<true>, &cfg) != cudaSuccess) { ncl = 0; cudaGetLastError(); }
    Args args{w_mod, cvec, (Scratch*)p_s, desc_lo(0, UNIT) | (0x40000040ull << 32), out, x, kc, vc, wq, wo, w_r, w_down};
    if (USE_SPARE && ncl >= NCTA / 2 + 2)
        fused_kernel<true><<<NCTA + 4, 384, SM_TOTAL>>>(args, tm_wq, tm_k, tm_v, tm_wo, tm_p, tm_x, tm_d, tm_g, tm_u);
    else
        fused_kernel<false><<<NCTA, 384, SM_TOTAL>>>(args, tm_wq, tm_k, tm_v, tm_wo, tm_p, tm_x, tm_d, tm_g, tm_u);
}
```

```cpp
#include <cuda_runtime.h>
#include <cuda_bf16.h>
#include <cuda.h>
#include <stdint.h>
#include <math.h>

typedef __nv_bfloat16 bf16;

constexpr int S_ = 2048;
constexpr int D_ = 576;
constexpr int HQ = 32, HKV = 16, DH = 128;
constexpr int F_ = 4608;
constexpr int QD = HQ * DH;

constexpr int NCTA = 128;
constexpr int WREG = 5 * 4096;
constexpr int CREP = 8;
constexpr int RSLOT = 192;
constexpr int MREP = 4;
struct Scratch {
    unsigned int epoch[128];
    unsigned int flag_mod[NCTA];
    unsigned int flag_part[16 * 32];
    unsigned int flag_q3[16 * 32];
    unsigned int flag_h[NCTA * 32];
    uint2 mod1[MREP * D_];
    uint32_t mod2[4 * D_];
    uint4 cand[CREP * NCTA * 2];
    uint2 ypart[72 * NCTA * 8];
    uint4 h[2][NCTA * 36 * 32];
    uint4 q3[NCTA * 8 * 128];
    uint4 rows[NCTA * 2 * RSLOT];
    uint8_t frag[NCTA * 8 * WREG];
    uint8_t keep[NCTA * 8 * 4096];
};
__device__ __align__(1024) Scratch g_s;
#define g_h gs->h[tag & 1]
#define g_q3 gs->q3
#define g_keep gs->keep
#define g_flag_h gs->flag_h
#define g_flag_part gs->flag_part
#define g_flag_mod gs->flag_mod
#define g_flag_q3 gs->flag_q3
#define g_frag gs->frag
#define g_cand gs->cand
#define g_ypart gs->ypart
#define g_rows gs->rows

#define DBG_INIT()
#define DBG_P(i)
#define DBG_PG(i)
#define DBG_T(i)
#define DBG_G(i)

__device__ __forceinline__ uint32_t pack_bf16(float lo, float hi) {
    uint32_t r;
    asm("cvt.rn.bf16x2.f32 %0, %1, %2;" : "=r"(r) : "f"(hi), "f"(lo));
    return r;
}
__device__ __forceinline__ float rbf(float x) { return __uint_as_float(pack_bf16(0.f, x)); }
__device__ __forceinline__ float bf_lo(uint32_t v) { return __uint_as_float(v << 16); }
__device__ __forceinline__ float bf_hi(uint32_t v) { return __uint_as_float(v & 0xffff0000u); }
__device__ __forceinline__ float ex2(float x) {
    float y;
    asm("ex2.approx.ftz.f32 %0, %1;" : "=f"(y) : "f"(x));
    return y;
}
template <class T>
__device__ __forceinline__ T* padd(T* p, uint32_t off) {
    unsigned long long r;
    asm("{\n.reg .b32 l, h;\nmov.b64 {l, h}, %1;\nadd.cc.u32 l, l, %2;\naddc.u32 h, h, 0;\nmov.b64 %0, {l, h};\n}" : "=l"(r) : "l"(p), "r"(off));
    return reinterpret_cast<T*>(r);
}
__device__ __forceinline__ uint32_t smem_u32(const void* p) { return (uint32_t)__cvta_generic_to_shared(p); }
__device__ __forceinline__ void mbar_init(uint32_t bar, uint32_t cnt) {
    asm volatile("mbarrier.init.shared::cta.b64 [%0], %1;" ::"r"(bar), "r"(cnt) : "memory");
}
__device__ __forceinline__ void mbar_expect_tx(uint32_t bar, uint32_t bytes) {
    asm volatile("mbarrier.arrive.expect_tx.shared::cta.b64 _, [%0], %1;" ::"r"(bar), "r"(bytes) : "memory");
}
__device__ __forceinline__ void mbar_arrive(uint32_t bar) {
    asm volatile("mbarrier.arrive.shared::cta.b64 _, [%0];" ::"r"(bar) : "memory");
}
__device__ __forceinline__ void mbar_arrive_cluster(uint32_t cluster_addr) {
    asm volatile("mbarrier.arrive.shared::cluster.b64 _, [%0];" ::"r"(cluster_addr) : "memory");
}
constexpr uint32_t SPIN = 1u << 20;
__device__ __forceinline__ void mbar_wait(uint32_t bar, uint32_t parity) {
    asm volatile("{\n.reg .pred p;\n.reg .b32 c;\nmov.b32 c, 0;\n"
                 "W_%=:\nmbarrier.try_wait.parity.shared::cta.b64 p, [%0], %1;\n"
                 "add.u32 c, c, 1;\nsetp.lt.and.u32 p, c, 0x100000, !p;\n@p bra W_%=;\n}"
                 ::"r"(bar), "r"(parity) : "memory");
}
__device__ __forceinline__ void anchor(uint32_t addr, float v) {
    asm volatile("{\n.reg .pred p;\nsetp.lt.f32 p, %1, 0f00000000;\n@p st.volatile.shared.f32 [%0], %1;\n}" ::"r"(addr), "f"(v) : "memory");
}
__device__ __forceinline__ void anchor(uint32_t addr, uint32_t v) {
    asm volatile("{\n.reg .pred p;\nsetp.eq.u32 p, %1, 0xffffffff;\n@p st.volatile.shared.u32 [%0], %1;\n}" ::"r"(addr), "r"(v) : "memory");
}
__device__ __forceinline__ void anchor(void* p, uint32_t v) {
    asm volatile("{\n.reg .pred p;\nsetp.eq.u32 p, %1, 0xffffffff;\n@p st.volatile.u32 [%0], %1;\n}" ::"l"(p), "r"(v) : "memory");
}
__device__ __forceinline__ void hold(float& a, float& b) {
    asm volatile("{\n.reg .pred p;\n.reg .b64 t;\n.reg .b32 l, h;\nmov.u64 t, %%clock64;\nmov.b64 {l, h}, t;\nsetp.eq.u32 p, h, 0xffffffff;\n"
                 "@p mov.f32 %0, 0f00000000;\n@p mov.f32 %1, 0f00000000;\n}" : "+f"(a), "+f"(b) :: "memory");
}
__device__ __forceinline__ void mbar_wait_sleep(uint32_t bar, uint32_t parity) {
    asm volatile("{\n.reg .pred p;\n.reg .b32 c;\nmov.b32 c, 0;\n"
                 "W_%=:\nmbarrier.try_wait.parity.shared::cta.b64 p, [%0], %1, 5000;\n"
                 "add.u32 c, c, 1;\nsetp.lt.and.u32 p, c, 0x20000, !p;\n@p bra W_%=;\n}"
                 ::"r"(bar), "r"(parity) : "memory");
}
__device__ __forceinline__ uint32_t load_tag(const Scratch* gs) {
    uint32_t tag;
    asm volatile("ld.global.ca.u32 %0, [%1];" : "=r"(tag) : "l"(gs->epoch) : "memory");
    return tag + 1;
}
__device__ __forceinline__ uint4 ld_relaxed(const uint4* p) {
    uint4 v;
    asm volatile("ld.relaxed.gpu.global.v4.u32 {%0,%1,%2,%3}, [%4];" : "=r"(v.x), "=r"(v.y), "=r"(v.z), "=r"(v.w) : "l"(p) : "memory");
    return v;
}
__device__ __forceinline__ void st_relaxed(uint4* p, uint32_t a, uint32_t b, uint32_t c, uint32_t d) {
    asm volatile("{\n.reg .b64 u, v;\nmov.b64 u, {%1, %2};\nmov.b64 v, {%3, %4};\nst.relaxed.gpu.global.v2.b64 [%0], {u, v};\n}"
                 ::"l"(p), "r"(a), "r"(b), "r"(c), "r"(d) : "memory");
}
__device__ __forceinline__ void st_relaxed4(void* p, uint32_t a, uint32_t b, uint32_t c, uint32_t d) {
    asm volatile("st.relaxed.gpu.global.v4.u32 [%0], {%1, %2, %3, %4};" ::"l"(p), "r"(a), "r"(b), "r"(c), "r"(d) : "memory");
}
__device__ __forceinline__ uint2 ld_relaxed8(const void* p) {
    uint2 v;
    asm volatile("ld.relaxed.gpu.global.v2.u32 {%0,%1}, [%2];" : "=r"(v.x), "=r"(v.y) : "l"(p) : "memory");
    return v;
}
__device__ __forceinline__ uint2 ld_relaxed64(const uint2* p) {
    uint2 v;
    asm volatile("{\n.reg .b64 u;\nld.relaxed.gpu.global.b64 u, [%2];\nmov.b64 {%0, %1}, u;\n}" : "=r"(v.x), "=r"(v.y) : "l"(p) : "memory");
    return v;
}
__device__ __forceinline__ void st_relaxed64(uint2* p, uint32_t a, uint32_t b) {
    asm volatile("{\n.reg .b64 u;\nmov.b64 u, {%1, %2};\nst.relaxed.gpu.global.b64 [%0], u;\n}" ::"l"(p), "r"(a), "r"(b) : "memory");
}
__device__ __forceinline__ uint4 ld_relaxed2(const uint4* p) {
    uint4 v;
    asm volatile("{\n.reg .b64 u, w;\nld.relaxed.gpu.global.v2.b64 {u, w}, [%4];\nmov.b64 {%0, %1}, u;\nmov.b64 {%2, %3}, w;\n}"
                 : "=r"(v.x), "=r"(v.y), "=r"(v.z), "=r"(v.w) : "l"(p) : "memory");
    return v;
}
__device__ __forceinline__ void reload16(uint4& v, const void* p, uint32_t& miss) {
    asm volatile("{\n.reg .pred p;\n.reg .b32 m;\n.reg .b64 u, w;\nmax.u32 m, %0, %2;\nsetp.eq.u32 p, m, 0xffffffff;\n"
                 "mov.b64 u, {%0, %1};\nmov.b64 w, {%2, %3};\n@p ld.relaxed.gpu.global.v2.b64 {u, w}, [%5];\n"
                 "mov.b64 {%0, %1}, u;\nmov.b64 {%2, %3}, w;\n@p mov.u32 %4, 1;\n}"
                 : "+r"(v.x), "+r"(v.y), "+r"(v.z), "+r"(v.w), "+r"(miss) : "l"(p) : "memory");
}
__device__ __forceinline__ void reload8(uint2& v, const void* p, uint32_t& miss) {
    asm volatile("{\n.reg .pred p;\n.reg .b64 u;\nsetp.eq.u32 p, %0, 0xffffffff;\nmov.b64 u, {%0, %1};\n"
                 "@p ld.relaxed.gpu.global.b64 u, [%3];\nmov.b64 {%0, %1}, u;\n@p mov.u32 %2, 1;\n}"
                 : "+r"(v.x), "+r"(v.y), "+r"(miss) : "l"(p) : "memory");
}
__device__ __forceinline__ uint32_t ld_relaxed32(const void* p) {
    uint32_t v;
    asm volatile("ld.relaxed.gpu.global.u32 %0, [%1];" : "=r"(v) : "l"(p) : "memory");
    return v;
}
__device__ __forceinline__ void flag_wait(const unsigned int* p, uint32_t tag) {
    uint32_t v, it = 0;
#pragma unroll 1
    do {
        asm volatile("ld.relaxed.gpu.global.u32 %0, [%1];" : "=r"(v) : "l"(p) : "memory");
    } while (__any_sync(0xffffffffu, v != tag) && ++it < SPIN / 16);
    asm volatile("fence.acquire.gpu;" ::: "memory");
    __syncwarp();
}
__device__ __forceinline__ bool elect() {
    uint32_t p;
    asm volatile("{\n.reg .pred p;\nelect.sync _|p, 0xffffffff;\nselp.u32 %0, 1, 0, p;\n}" : "=r"(p));
    return p;
}
__device__ __forceinline__ void flag_release(unsigned int* p, uint32_t tag) {
    asm volatile("st.release.gpu.global.u32 [%0], %1;" ::"l"(p), "r"(tag) : "memory");
}
__device__ __forceinline__ uint32_t touch(const void* p) {
    uint32_t v;
    asm volatile("ld.global.nc.L1::no_allocate.L2::128B.u32 %0, [%1];" : "=r"(v) : "l"(p));
    return v;
}
__device__ __forceinline__ void bar_sync(int id, int n) { asm volatile("bar.sync %0, %1;" ::"r"(id), "r"(n) : "memory"); }
__device__ __forceinline__ void bar_arrive(int id, int n) { asm volatile("bar.arrive %0, %1;" ::"r"(id), "r"(n) : "memory"); }

constexpr uint64_t EVICT_NORMAL = 0x1000000000000000ull, EVICT_FIRST = 0x12F0000000000000ull;
__device__ __forceinline__ void tma2d(uint32_t dst, const CUtensorMap* m, int c0, int c1, uint32_t bar) {
    asm volatile("cp.async.bulk.tensor.2d.shared::cluster.global.mbarrier::complete_tx::bytes.L2::cache_hint [%0], [%1, {%3, %4}], [%2], %5;"
                 ::"r"(dst), "l"(m), "r"(bar), "r"(c0), "r"(c1), "l"(EVICT_FIRST) : "memory");
}
__device__ __forceinline__ void tma2d_mc(uint32_t dst, const CUtensorMap* m, int c0, int c1, uint32_t bar, uint64_t pol) {
    asm volatile("cp.async.bulk.tensor.2d.shared::cluster.global.mbarrier::complete_tx::bytes.multicast::cluster.L2::cache_hint [%0], [%1, {%3, %4}], [%2], %5, %6;"
                 ::"r"(dst), "l"(m), "r"(bar), "r"(c0), "r"(c1), "h"((uint16_t)3), "l"(pol) : "memory");
}
__device__ __forceinline__ void tma3d(uint32_t dst, const CUtensorMap* m, int c0, int c1, int c2, uint32_t bar) {
    asm volatile("cp.async.bulk.tensor.3d.shared::cluster.global.mbarrier::complete_tx::bytes.L2::cache_hint [%0], [%1, {%3, %4, %5}], [%2], %6;"
                 ::"r"(dst), "l"(m), "r"(bar), "r"(c0), "r"(c1), "r"(c2), "l"(EVICT_FIRST) : "memory");
}
__device__ __forceinline__ void bulk_load(uint32_t dst, const void* src, uint32_t bytes, uint32_t bar) {
    asm volatile("cp.async.bulk.shared::cluster.global.mbarrier::complete_tx::bytes [%0], [%1], %2, [%3];"
                 ::"r"(dst), "l"(src), "r"(bytes), "r"(bar) : "memory");
}
__device__ __forceinline__ void l2_prefetch(const void* src, uint32_t bytes) {
    asm volatile("cp.async.bulk.prefetch.L2.global [%0], %1;" ::"l"(src), "r"(bytes) : "memory");
}
__device__ __forceinline__ uint32_t bmul2(uint32_t a, uint32_t b) { uint32_t r; asm("mul.rn.bf16x2 %0, %1, %2;" : "=r"(r) : "r"(a), "r"(b)); return r; }
__device__ __forceinline__ uint32_t badd2(uint32_t a, uint32_t b) { uint32_t r; asm("add.rn.bf16x2 %0, %1, %2;" : "=r"(r) : "r"(a), "r"(b)); return r; }
__device__ __forceinline__ uint32_t bsub2(uint32_t a, uint32_t b) { uint32_t r; asm("sub.rn.bf16x2 %0, %1, %2;" : "=r"(r) : "r"(a), "r"(b)); return r; }
__device__ __forceinline__ uint32_t bmax2(uint32_t a, uint32_t b) { uint32_t r; asm("max.bf16x2 %0, %1, %2;" : "=r"(r) : "r"(a), "r"(b)); return r; }
__device__ __forceinline__ uint32_t bfma2(uint32_t a, uint32_t b, uint32_t c) { uint32_t r; asm("fma.rn.bf16x2 %0, %1, %2, %3;" : "=r"(r) : "r"(a), "r"(b), "r"(c)); return r; }
__device__ __forceinline__ uint4 lds128(uint32_t a) { uint4 v; asm volatile("ld.shared.v4.u32 {%0,%1,%2,%3}, [%4];" : "=r"(v.x), "=r"(v.y), "=r"(v.z), "=r"(v.w) : "r"(a) : "memory"); return v; }
__device__ __forceinline__ uint2 lds64(uint32_t a) { uint2 v; asm volatile("ld.shared.v2.u32 {%0,%1}, [%2];" : "=r"(v.x), "=r"(v.y) : "r"(a) : "memory"); return v; }
__device__ __forceinline__ uint32_t lds32(uint32_t a) { uint32_t v; asm volatile("ld.shared.u32 %0, [%1];" : "=r"(v) : "r"(a) : "memory"); return v; }
__device__ __forceinline__ uint4 ldsm4(uint32_t a) {
    uint4 v;
    asm volatile("ldmatrix.sync.aligned.m8n8.x4.shared.b16 {%0,%1,%2,%3}, [%4];" : "=r"(v.x), "=r"(v.y), "=r"(v.z), "=r"(v.w) : "r"(a) : "memory");
    return v;
}
__device__ __forceinline__ uint4 ldsm4t(uint32_t a) {
    uint4 v;
    asm volatile("ldmatrix.sync.aligned.m8n8.x4.trans.shared.b16 {%0,%1,%2,%3}, [%4];" : "=r"(v.x), "=r"(v.y), "=r"(v.z), "=r"(v.w) : "r"(a) : "memory");
    return v;
}
__device__ __forceinline__ void mma1688(float* d, uint32_t a0, uint32_t a1, uint32_t b) {
    asm("mma.sync.aligned.m16n8k8.row.col.f32.bf16.bf16.f32 {%0,%1,%2,%3}, {%4,%5}, {%6}, {%0,%1,%2,%3};"
        : "+f"(d[0]), "+f"(d[1]), "+f"(d[2]), "+f"(d[3]) : "r"(a0), "r"(a1), "r"(b));
}
__device__ __forceinline__ void mma16816(float* d, uint32_t a0, uint32_t a1, uint32_t a2, uint32_t a3, uint32_t b0, uint32_t b1) {
    asm("mma.sync.aligned.m16n8k16.row.col.f32.bf16.bf16.f32 {%0,%1,%2,%3}, {%4,%5,%6,%7}, {%8,%9}, {%0,%1,%2,%3};"
                 : "+f"(d[0]), "+f"(d[1]), "+f"(d[2]), "+f"(d[3]) : "r"(a0), "r"(a1), "r"(a2), "r"(a3), "r"(b0), "r"(b1));
}
__device__ __forceinline__ void stsm_x4(uint32_t addr, uint32_t a, uint32_t b, uint32_t c, uint32_t d) {
    asm volatile("stmatrix.sync.aligned.m8n8.x4.shared.b16 [%0], {%1, %2, %3, %4};"
                 ::"r"(addr), "r"(a), "r"(b), "r"(c), "r"(d) : "memory");
}

__device__ __forceinline__ uint64_t mkdesc(uint32_t addr, uint32_t lbo, uint32_t sbo) {
    return (uint64_t)((addr & 0x3FFFF) >> 4) | ((uint64_t)(lbo >> 4) << 16) | ((uint64_t)(sbo >> 4) << 32) | (1ull << 62);
}
constexpr uint32_t SM0 = 1024;
__host__ __device__ constexpr uint32_t desc_lo(uint32_t off, uint32_t lbo) { return ((SM0 + off) >> 4) | ((lbo >> 4) << 16); }
#define WG_FENCE() asm volatile("wgmma.fence.sync.aligned;" ::: "memory")
#define WG_COMMIT() asm volatile("wgmma.commit_group.sync.aligned;" ::: "memory")
#define WG_WAIT(n) asm volatile("wgmma.wait_group.sync.aligned %0;" ::"n"(n) : "memory")

#define F8(a, i) "+f"(a[i]), "+f"(a[i + 1]), "+f"(a[i + 2]), "+f"(a[i + 3]), "+f"(a[i + 4]), "+f"(a[i + 5]), "+f"(a[i + 6]), "+f"(a[i + 7])
#define F16(a, i) F8(a, i), F8(a, i + 8)
#define F64(a) F16(a, 0), F16(a, 16), F16(a, 32), F16(a, 48)
#define F32(a) F16(a, 0), F16(a, 16)
#define L64 "%0,%1,%2,%3,%4,%5,%6,%7,%8,%9,%10,%11,%12,%13,%14,%15,%16,%17,%18,%19,%20,%21,%22,%23,%24,%25,%26,%27,%28,%29,%30,%31,%32,%33,%34,%35,%36,%37,%38,%39,%40,%41,%42,%43,%44,%45,%46,%47,%48,%49,%50,%51,%52,%53,%54,%55,%56,%57,%58,%59,%60,%61,%62,%63"
#define L32 "%0,%1,%2,%3,%4,%5,%6,%7,%8,%9,%10,%11,%12,%13,%14,%15,%16,%17,%18,%19,%20,%21,%22,%23,%24,%25,%26,%27,%28,%29,%30,%31"

template <int TB, int STEP = 128>
__device__ __forceinline__ void mma_rs128(float (&d)[64], uint32_t a0, uint32_t a1, uint32_t a2, uint32_t a3, uint64_t& b, int acc) {
    asm volatile("{\n.reg .pred p;\nsetp.ne.b32 p, %69, 0;\n"
                 "wgmma.mma_async.sync.aligned.m64n128k16.f32.bf16.bf16 {" L64 "}, {%65,%66,%67,%68}, %64, p, 1, 1, %70;\nadd.s64 %64, %64, %71;\n}"
                 : F64(d), "+l"(b) : "r"(a0), "r"(a1), "r"(a2), "r"(a3), "r"(acc), "n"(TB), "n"(STEP));
}
template <int TB>
__device__ __forceinline__ void mma_rs64(float (&d)[32], uint32_t a0, uint32_t a1, uint32_t a2, uint32_t a3, uint64_t& b, int acc) {
    asm volatile("{\n.reg .pred p;\nsetp.ne.b32 p, %37, 0;\n"
                 "wgmma.mma_async.sync.aligned.m64n64k16.f32.bf16.bf16 {" L32 "}, {%33,%34,%35,%36}, %32, p, 1, 1, %38;\nadd.s64 %32, %32, 128;\n}"
                 : F32(d), "+l"(b) : "r"(a0), "r"(a1), "r"(a2), "r"(a3), "r"(acc), "n"(TB));
}
template <int N>
__device__ __forceinline__ void fence_regs(float (&d)[N]) {
#pragma unroll
    for (int i = 0; i < N; i++) asm volatile("" : "+f"(d[i])::"memory");
}
template <int N>
__device__ __forceinline__ void fence_regs(uint32_t (&d)[N]) {
#pragma unroll
    for (int i = 0; i < N; i++) asm volatile("" : "+r"(d[i])::"memory");
}

template <int V> struct IC { static constexpr int value = V; };

constexpr int SLOT = 32768, UNIT = 16384;
constexpr int SM_Q = 4 * SLOT;
constexpr int SM_BAR = 7 * SLOT;
constexpr int SM_RED = SM_BAR + 512;
constexpr int SM_TOTAL = SM_BAR + 3072;
constexpr int XP = D_ * 2 + 16;
constexpr int M_MOD = 16 * XP;
constexpr int SM_T = SM_Q + 2 * D_ * 80, SM_TC = SM_T + D_ * 4, SM_TG = SM_TC + D_ * 4, SM_TS = SM_TG + D_ * 2;
constexpr float CS = 0.08838834764831845f * 1.4426950408889634f;
#define LMAX 0.5f
#define LMIN 0x1p-104f
#define USE_SPARE 1
#define MAXG 1
#define SPLIT 10
#define ESPLIT 3
#define PV1 8
#define RW 2
#define HW 2
#define HW2 1
#define XDELAY 200
#define QDELAY 300
#define TMPF 1
#define PFD0 2000
#define PFD1 400
#define HDELAY 300
#define RA 10
#define RB 2
#define RPE 2
#define OSPLIT 6
#define HOLD 1
#define DL 6
#define O2F 0
#define A2N 4
#define OPF 0
#define PS 2
#define QSPLIT 4
#define QT0 4
#define STAGE 11
#define POFF 102.f
#define WF0 3
#define WF1 13
#define C3D 0
#define C4D 300
#define DD 300
#define P2E 0
#define BO 0
#define MAP 2
#define CFULL 0
#define WFE 1
#define OUTD 0
#define OUTPOL EVICT_FIRST
#define WF2 19
constexpr int PF_KV = 8, PF_WO = 120;

__device__ __forceinline__ int cluster_role() {
    int k;
    asm volatile("mov.u32 %0, %%ctaid.x;" : "=r"(k));
    k >>= 1;
    if (MAP == 0) return k & 63;
    if (MAP == 1) return (k & 7) * 8 + ((k >> 3) & 7);
    if (MAP == 3) {
        asm("mov.u32 %0, %%smid;" : "=r"(k));
        k >>= 1;
        const int r = ((k - 32) * 37) >> 8;
        return k < 32 ? (k & 7) * 8 + (k >> 3) : k < 60 ? (k - 31 - r * 7) * 8 + 4 + r : (k - 58) & 7;
    }
    const int r = ((k - 36) * 37) >> 8, i = k - 36 - r * 7;
    if (MAP == 4) return k < 4 ? 4 + k : k < 36 ? ((k - 4) & 7) * 8 + ((k - 4) >> 3) : (i + 1) * 8 + ((4 + r) & 7);
    return k < 4 ? 12 + k : k < 36 ? ((k - 4) & 7) * 8 + ((k - 4) >> 3) : (i + (i > 0)) * 8 + ((4 + r) & 7);
}

struct Args {
    const bf16 *w_mod, *cvec;
    Scratch* gs;
    uint64_t d0;
    bf16* out;
    const bf16 *x, *kc, *vc, *wq, *wo, *w_r, *w_down;
};

__device__ __forceinline__ void frag_store(uint8_t* p, const uint32_t (&a)[32]) {
#pragma unroll
    for (int i = 0; i < 8; i++)
        __stcg(reinterpret_cast<uint4*>(p + i * 512), make_uint4(a[4 * i], a[4 * i + 1], a[4 * i + 2], a[4 * i + 3]));
}
template <int LO = 0, int HI = 8>
__device__ __forceinline__ void frag_load(uint32_t (&a)[32], const uint8_t* p) {
#pragma unroll
    for (int i = LO; i < HI; i++) {
        const uint4 v = ld_relaxed(reinterpret_cast<const uint4*>(p + i * 512));
        a[4 * i] = v.x; a[4 * i + 1] = v.y; a[4 * i + 2] = v.z; a[4 * i + 3] = v.w;
    }
}
__device__ __forceinline__ float quad_sum(float v) {
    v += __shfl_xor_sync(0xffffffffu, v, 1);
    return v + __shfl_xor_sync(0xffffffffu, v, 2);
}
__device__ __forceinline__ float quad_max(float v) {
    v = fmaxf(v, __shfl_xor_sync(0xffffffffu, v, 1));
    return fmaxf(v, __shfl_xor_sync(0xffffffffu, v, 2));
}
__device__ __forceinline__ float rcp_fast(float x) { float y; asm("rcp.approx.ftz.f32 %0, %1;" : "=f"(y) : "f"(x)); return y; }
__device__ __forceinline__ float sigmoidf_(float x) { return rcp_fast(1.f + ex2(-1.4426950408889634f * x)); }
__device__ __forceinline__ void top2(uint32_t k, uint32_t& k1, uint32_t& k2) {
    k1 = __reduce_max_sync(0xffffffffu, k);
    k2 = __reduce_max_sync(0xffffffffu, k == k1 ? 0 : k);
}

__device__ __forceinline__ void mod_fma(float (&a)[8], const uint4 w, float sc) {
    a[0] += sc * bf_lo(w.x); a[1] += sc * bf_hi(w.x); a[2] += sc * bf_lo(w.y); a[3] += sc * bf_hi(w.y);
    a[4] += sc * bf_lo(w.z); a[5] += sc * bf_hi(w.z); a[6] += sc * bf_lo(w.w); a[7] += sc * bf_hi(w.w);
}
__device__ __forceinline__ float mod_reduce(float (&a)[8], int lane) {
#pragma unroll
    for (int h = 4; h > 0; h >>= 1) {
        const bool up = lane & (8 / h);
#pragma unroll
        for (int i = 0; i < h; i++)
            a[i] = (up ? a[i + h] : a[i]) + __shfl_xor_sync(0xffffffffu, up ? a[i] : a[i + h], 8 / h);
    }
    return a[0] + __shfl_xor_sync(0xffffffffu, a[0], 16);
}

__device__ __forceinline__ float ln_stats(float sum, float sq, uint32_t& mean2) {
    const float mean = sum * (1.f / D_);
    const float var = fmaxf(fmaf(-mean, mean, sq * (1.f / D_)), 0.f);
    float sd;
    asm("sqrt.approx.ftz.f32 %0, %1;" : "=f"(sd) : "f"(rbf(rbf(var) + 1e-5f)));
    mean2 = pack_bf16(mean, mean);
    return rcp_fast(rbf(sd));
}
__device__ __forceinline__ uint32_t ln_pair(uint32_t x, uint32_t mean2, float rsd) {
    const uint32_t d = bsub2(x, mean2);
    return pack_bf16(bf_lo(d) * rsd, bf_hi(d) * rsd);
}
__device__ __forceinline__ void rows_load(uint32_t (&x)[20], uint32_t xs, int cw) {
#pragma unroll
    for (int ch = 0; ch < 5; ch++) {
        const uint4 v = ldsm4(ch < 4 ? xs + ch * 256 : xs + 1024 - cw * 16);
        x[4 * ch] = v.x; x[4 * ch + 1] = v.y; x[4 * ch + 2] = v.z; x[4 * ch + 3] = v.w;
    }
}
__device__ __forceinline__ void stats_add(float (&st)[12], uint32_t a, uint32_t b, uint32_t w) {
    mma1688(st, a, b, w);
    mma1688(st + 4, a, b, a);
    mma1688(st + 8, a, b, b);
}
__device__ __forceinline__ float rows_stats(const float (&st)[12], float4* rec, int cw, int lane, uint32_t& mean2, float& dot) {
    const int g8 = lane >> 2;
    if ((g8 >> 1) == (lane & 3)) {
        rec[cw * 16 + g8] = make_float4(st[0], (g8 & 1) ? st[5] : st[4], st[1], 0.f);
        rec[cw * 16 + 8 + g8] = make_float4(st[2], (g8 & 1) ? st[11] : st[10], st[3], 0.f);
    }
    bar_sync(3, 256);
    const float4* r = rec + (lane >> 4) * 64 + (lane & 15);
    const float4 s0 = r[0], s1 = r[16], s2 = r[32], s3 = r[48];
    const float sum = (s0.x + s1.x) + (s2.x + s3.x), sq = (s0.y + s1.y) + (s2.y + s3.y);
    dot = (s0.z + s1.z) + (s2.z + s3.z);
    dot += __shfl_xor_sync(0xffffffffu, dot, 16);
    return ln_stats(sum + __shfl_xor_sync(0xffffffffu, sum, 16), sq + __shfl_xor_sync(0xffffffffu, sq, 16), mean2);
}
template <class F>
__device__ __forceinline__ void rows_normalise(uint32_t* y, const uint32_t* x, uint32_t mean2, float rsd, int lane, F loads) {
    const int g8 = lane >> 2;
    const uint32_t ma2 = __shfl_sync(0xffffffffu, mean2, g8), mb2 = __shfl_sync(0xffffffffu, mean2, g8 + 8);
    const float ra = __shfl_sync(0xffffffffu, rsd, g8), rb = __shfl_sync(0xffffffffu, rsd, g8 + 8);
    loads();
#pragma unroll
    for (int k = 0; k < 9; k++) { y[2 * k] = ln_pair(x[2 * k], ma2, ra); y[2 * k + 1] = ln_pair(x[2 * k + 1], mb2, rb); }
}

__device__ __forceinline__ uint4 h_frag(const uint4* hf, int ks, int lane) {
    if (ks < 32) return ld_relaxed2(hf + ks * 32);
    const uint2* p = reinterpret_cast<const uint2*>(padd(hf, 256 - lane * 8) + ks * 32 - 16);
    const uint2 a = ld_relaxed64(p), b = ld_relaxed64(p + 32);
    return make_uint4(a.x, a.y, b.x, b.y);
}

__device__ __noinline__ void attn_fallback(uint32_t bad, uint32_t tag, const Scratch* gs, uint8_t* frag, uint8_t* keep, const bf16* wq, const bf16* kc, const bf16* vc) {
  const int lane = threadIdx.x & 31, g8 = lane >> 2, qd = lane & 3;
  const int role = cluster_role(), j = role & 7, qb = (role >> 3) * 2 + (blockIdx.x & 1);
  const uint4* hf = g_h + (size_t)(qb * 8 + (threadIdx.x >> 5) - 4) * (36 * 32) + lane;
#pragma unroll 1
  for (int t = 0; t < 4; t++) {
    if (!((bad >> t) & 1)) continue;
    const bf16 *wqp = wq + (4 * j + t) * DH, *kp = kc + (size_t)(2 * j + (t >> 1)) * S_ * DH, *vp = vc + (size_t)(2 * j + (t >> 1)) * S_ * DH;
    uint32_t q[32];
    float o[64];
#pragma unroll
    for (int i = 0; i < 64; i++) o[i] = 0.f;
#pragma unroll 1
    for (int ks = 0; ks < 36; ks++) {
        const uint4 a = h_frag(hf, ks, lane);
        const unsigned short* wr = reinterpret_cast<const unsigned short*>(wqp + (size_t)(ks * 16 + 2 * qd) * QD + g8);
#pragma unroll
        for (int dt = 0; dt < 16; dt++) {
            const uint32_t b0 = __ldg(wr + dt * 8) | ((uint32_t)__ldg(wr + dt * 8 + QD) << 16);
            const uint32_t b1 = __ldg(wr + dt * 8 + 8 * QD) | ((uint32_t)__ldg(wr + dt * 8 + 9 * QD) << 16);
            mma16816(o + 4 * dt, a.x, a.y, a.z, a.w, b0, b1);
        }
    }
#pragma unroll
    for (int i = 0; i < 32; i++) q[i] = pack_bf16(o[2 * i], o[2 * i + 1]);
#pragma unroll
    for (int i = 0; i < 64; i++) o[i] = 0.f;
    float m0 = -INFINITY, m1 = -INFINITY, l0 = 0.f, l1 = 0.f;
#pragma unroll 1
    for (int key = 0; key < S_; key += 16) {
        float sc[8];
#pragma unroll
        for (int i = 0; i < 8; i++) sc[i] = 0.f;
#pragma unroll
        for (int nt = 0; nt < 2; nt++) {
            const uint32_t* kr = reinterpret_cast<const uint32_t*>(kp + (size_t)(key + nt * 8 + g8) * DH) + qd;
#pragma unroll
            for (int ks = 0; ks < 8; ks++)
                mma16816(sc + 4 * nt, q[4 * ks], q[4 * ks + 1], q[4 * ks + 2], q[4 * ks + 3], __ldg(kr + ks * 8), __ldg(kr + ks * 8 + 4));
        }
        const float n0 = quad_max(fmaxf(fmaxf(m0, fmaxf(sc[0], sc[1])), fmaxf(sc[4], sc[5])));
        const float n1 = quad_max(fmaxf(fmaxf(m1, fmaxf(sc[2], sc[3])), fmaxf(sc[6], sc[7])));
        const float f0 = ex2((m0 - n0) * CS), f1 = ex2((m1 - n1) * CS);
        m0 = n0; m1 = n1;
#pragma unroll
        for (int i = 0; i < 8; i++) sc[i] = ex2((sc[i] - ((i & 2) ? n1 : n0)) * CS);
        l0 = l0 * f0 + (sc[0] + sc[1]) + (sc[4] + sc[5]);
        l1 = l1 * f1 + (sc[2] + sc[3]) + (sc[6] + sc[7]);
        const uint32_t e0 = pack_bf16(sc[0], sc[1]), e1 = pack_bf16(sc[2], sc[3]), e2 = pack_bf16(sc[4], sc[5]), e3 = pack_bf16(sc[6], sc[7]);
        const unsigned short* vr = reinterpret_cast<const unsigned short*>(vp + (size_t)(key + 2 * qd) * DH + g8);
#pragma unroll
        for (int dt = 0; dt < 16; dt++) {
            o[4 * dt] *= f0; o[4 * dt + 1] *= f0; o[4 * dt + 2] *= f1; o[4 * dt + 3] *= f1;
            const uint32_t b0 = __ldg(vr + dt * 8) | ((uint32_t)__ldg(vr + dt * 8 + DH) << 16);
            const uint32_t b1 = __ldg(vr + dt * 8 + 8 * DH) | ((uint32_t)__ldg(vr + dt * 8 + 9 * DH) << 16);
            mma16816(o + 4 * dt, e0, e1, e2, e3, b0, b1);
        }
    }
    const float i0 = 1.f / quad_sum(l0), i1 = 1.f / quad_sum(l1);
#pragma unroll
    for (int i = 0; i < 16; i++) {
        q[2 * i] = pack_bf16(o[4 * i] * i0, o[4 * i + 1] * i0);
        q[2 * i + 1] = pack_bf16(o[4 * i + 2] * i1, o[4 * i + 3] * i1);
    }
    frag_store(t < 3 ? frag + t * 4096 : keep, q);
  }
}

__device__ __forceinline__ void spare_q3(Scratch* gs, uint32_t sb, uint32_t bar_full, uint32_t bar_empty, int lane, int cw) {
    const uint32_t tag = load_tag(gs);
    uint32_t rel_base, e = 3;
    asm("mapa.shared::cluster.u32 %0, %1, %2;" : "=r"(rel_base) : "r"(bar_empty), "r"(lane & 1));
#pragma unroll 1
    for (int qb = blockIdx.x - NCTA; qb < 16; qb += 4) {
        uint32_t h[144];
        float o[64];
        flag_wait(&g_flag_h[(qb * 8 + cw) * 32], tag);
        const uint4* hf = g_h + (size_t)(qb * 8 + cw) * (36 * 32) + lane;
#pragma unroll
        for (int ks = 0; ks < 36; ks++) {
            const uint4 v = h_frag(hf, ks, lane);
            h[4 * ks] = v.x; h[4 * ks + 1] = v.y; h[4 * ks + 2] = v.z; h[4 * ks + 3] = v.w;
        }
#pragma unroll
        for (int i = 0; i < 64; i++) o[i] = 0.f;
#pragma unroll 1
        for (int v = 0; v < 4; v++) {
            fence_regs(o);
#pragma unroll
            for (int t = 0; t < 5; t++) {
                mbar_wait(bar_full + 8 * (e & 3), (e >> 2) & 1);
                uint64_t dv = mkdesc(sb + (e & 3) * SLOT, UNIT, 1024);
                WG_FENCE();
#pragma unroll
                for (int ks = 0; ks < (t < 4 ? 8 : 4); ks++)
                    mma_rs128<1>(o, h[32 * t + 4 * ks], h[32 * t + 4 * ks + 1], h[32 * t + 4 * ks + 2], h[32 * t + 4 * ks + 3], dv, ks | t);
                WG_COMMIT();
                if (t > 0) { WG_WAIT(1); if (lane < 2) mbar_arrive_cluster(rel_base + 8 * ((e - 1) & 3)); }
                e++;
            }
            WG_WAIT(0);
            fence_regs(o);
            if (lane < 2) mbar_arrive_cluster(rel_base + 8 * ((e - 1) & 3));
            uint4* dst = &g_q3[((qb * 8 + 2 * v) * 8 + cw) * 128 + lane];
#pragma unroll
            for (int i = 0; i < 8; i++)
                __stcg(dst + (i >> 2) * 1024 + (i & 3) * 32, make_uint4(pack_bf16(o[8 * i], o[8 * i + 1]), pack_bf16(o[8 * i + 2], o[8 * i + 3]),
                                                                        pack_bf16(o[8 * i + 4], o[8 * i + 5]), pack_bf16(o[8 * i + 6], o[8 * i + 7])));
        }
        bar_sync(3, 256);
        if (cw == 0 && lane == 0) flag_release(&g_flag_q3[qb * 32], tag);
        __syncwarp();
    }
}

template <bool SPARE>
__global__ void __cluster_dims__(2, 1, 1) __launch_bounds__(384, 1)
fused_kernel(const Args args, const __grid_constant__ CUtensorMap tm_wq,
             const __grid_constant__ CUtensorMap tm_k, const __grid_constant__ CUtensorMap tm_v,
             const __grid_constant__ CUtensorMap tm_wo, const __grid_constant__ CUtensorMap tm_p,
             const __grid_constant__ CUtensorMap tm_x, const __grid_constant__ CUtensorMap tm_d,
             const __grid_constant__ CUtensorMap tm_g, const __grid_constant__ CUtensorMap tm_u) {
    extern __shared__ __align__(1024) uint8_t smem_raw[];
    const uint32_t sb = smem_u32(smem_raw);
    Scratch* const gs = args.gs;
    const uint32_t bar_full = sb + SM_BAR;
    const uint32_t bar_g = bar_full + 8 * 4;
    const uint32_t bar_mod = bar_g + 8;
    const uint32_t bar_go = bar_mod + 8;
    const uint32_t bar_x = bar_go + 40;
    const uint32_t bar_empty = bar_x + 8;
    const uint32_t bar_pub = bar_empty + 8 * 4;
    const uint32_t bar_qfree = bar_pub + 32;
    const uint32_t bar_out = bar_qfree + 24;
    const uint32_t bar_q3 = bar_out + 8;
    const uint32_t bar_pre = bar_q3 + 16;
    const uint32_t bar_w0 = bar_q3 + 8;
    constexpr int E0 = SPARE ? 2 : 0;

    const int c = blockIdx.x & 1;
#define ROLES() const int role = cluster_role(), j = role & 7, qb = (role >> 3) * 2 + c, rg = qb * 8 + j
    const int warp = __shfl_sync(0xffffffffu, threadIdx.x >> 5, 0);

    if (SPARE && blockIdx.x >= NCTA && warp >= 4) {
        asm volatile("barrier.cluster.arrive.relaxed.aligned;" ::: "memory");
        asm volatile("setmaxnreg.inc.sync.aligned.u32 240;");
        asm volatile("barrier.cluster.wait.aligned;" ::: "memory");
        spare_q3(gs, sb, bar_full, bar_empty, threadIdx.x & 31, warp - 4);
        asm volatile("barrier.cluster.arrive.relaxed.aligned;\nbarrier.cluster.wait.aligned;" ::: "memory");
    } else if (warp < 4) {
        asm volatile("setmaxnreg.dec.sync.aligned.u32 24;");
        ROLES();
        int lane;
        asm volatile("mov.u32 %0, %%laneid;" : "=r"(lane));
        if (warp == 2 && elect()) {
            if (TMPF) asm volatile("prefetch.tensormap [%0];" ::"l"(&tm_x) : "memory");
#pragma unroll
            for (int i = 0; i < 27; i++) mbar_init(bar_full + 8 * i, i < 12 || i >= 23 ? 1 : i < 16 ? 16 : 8);
#pragma unroll
            for (int i = 0; i <= E0; i++) {
                mbar_arrive(bar_full + 8 * i);
                asm volatile("mbarrier.arrive.shared::cta.b64 _, [%0], 16;" ::"r"(bar_empty + 8 * i) : "memory");
            }
            asm volatile("fence.mbarrier_init.release.cluster;" ::: "memory");
        }
        __syncwarp();
        asm volatile("barrier.cluster.arrive.relaxed.aligned;" ::: "memory");
        if (warp == 2 && !(SPARE && blockIdx.x >= NCTA)) {
            if (XDELAY) __nanosleep(XDELAY);
            if (elect()) {
                mbar_expect_tx(bar_x, 16 * XP);
                tma2d(sb + SM_Q, &tm_x, 0, rg * 16, bar_x);
            }
            __syncwarp();
        }
        asm volatile("barrier.cluster.wait.aligned;" ::: "memory");
        const uint32_t tag = load_tag(gs);
        if (SPARE && blockIdx.x >= NCTA) {
            if (warp == 1) {
#pragma unroll 1
                for (int e = 3; e < 83; e++) {
                    const int v = (e - 3) / 5;
                    mbar_wait_sleep(bar_empty + 8 * (e & 3), ~(e >> 2) & 1);
                    if (elect()) {
                        mbar_expect_tx(bar_full + 8 * (e & 3), SLOT);
                        tma2d_mc(sb + (e & 3) * SLOT + c * UNIT, &tm_wq, (8 * (v & 3) + 4 * c + 3) * DH + 64, (e - 3 - v * 5) * 128,
                                 bar_full + 8 * (e & 3), EVICT_NORMAL);
                    }
                }
            }
            __syncwarp();
            asm volatile("barrier.cluster.arrive.relaxed.aligned;\nbarrier.cluster.wait.aligned;" ::: "memory");
            return;
        }
        if (warp == 3) {
#pragma unroll 1
            for (int e = 4; e < 20; e++) {
                __nanosleep(e == 4 ? PFD0 : PFD1);
                const int hd = (e * 52) >> 8, row = (e - hd * 5) * 128 + qb * 8 + (lane >> 1);
                if (lane < 16 && row < D_)
                    asm volatile("prefetch.global.L2 [%0];" ::"l"(padd(args.wq, (row * QD + (4 * j + ((0x1320 >> (4 * hd)) & 3)) * DH + (lane & 1) * 64) * 2)) : "memory");
            }
            __syncwarp();
            mbar_wait_sleep(bar_go, 0);
#pragma unroll 1
            for (int unit = 72 + blockIdx.x; unit < 216; unit += NCTA) {
                float a[8];
#pragma unroll
                for (int i = 0; i < 8; i++) a[i] = 0.f;
#pragma unroll 1
                for (int k = lane >> 1; k < D_; k += 16) {
                    const float cv = __bfloat162float(*padd(args.cvec, k * 2));
                    mod_fma(a, __ldg(reinterpret_cast<const uint4*>(padd(args.w_mod, (k * (6 * D_) + unit * 16 + (lane & 1) * 8) * 2))), rbf(cv * sigmoidf_(cv)));
                }
                const float v = mod_reduce(a, lane), v1 = __shfl_down_sync(0xffffffffu, v, 8);
                if (lane < 8) *padd(gs->mod2, ((unit - 72) * 8 + (lane & 1) * 4 + (lane & 2) + (lane >> 2)) * 4) = pack_bf16(v, v1);
            }
            __syncwarp();
            if (lane == 0) flag_release(padd(g_flag_mod, blockIdx.x * 4), tag);
#pragma unroll 1
            for (int k = 0; k < 36; k++) {
                __nanosleep(200);
                __stcg(padd(gs->h[0], (~tag & 1) * (NCTA * 36 * 512) + ((rg * 36 + k) * 32 + lane) * 16), make_uint4(0, 0, 0, 0));
            }
            __syncwarp();
            mbar_wait_sleep(bar_qfree + 16, 0);
            __nanosleep(2000);
            {
                uint4 v;
                uint32_t it = 0;
#pragma unroll 1
                do {
                    v = ld_relaxed(reinterpret_cast<const uint4*>(padd(g_flag_mod, lane * 16)));
                } while (((v.x ^ tag) | (v.y ^ tag) | (v.z ^ tag) | (v.w ^ tag)) && ++it < SPIN / 16);
                asm volatile("fence.acquire.gpu;" ::: "memory");
            }
            __syncwarp();
            {
                float w1 = 0.f, w2 = 0.f;
#pragma unroll 1
                for (int k = lane; k < D_ / 2; k += 32) {
                    const uint32_t* mp = padd(gs->mod2, k * 4);
                    const uint32_t sv = __ldcg(mp + D_ / 2), c1 = badd2(__ldcg(mp + D_), 0x3f803f80u);
                    const uint32_t wr = *reinterpret_cast<const uint32_t*>(padd(args.w_r, k * 4)), wp = bmul2(c1, wr);
                    reinterpret_cast<uint2*>(smem_raw + SM_T)[k] = make_uint2(__ldcg(mp), wp);
                    reinterpret_cast<uint2*>(smem_raw + SM_TC)[k] = make_uint2(c1, sv);
                    reinterpret_cast<uint32_t*>(smem_raw + SM_TG)[k] = __ldcg(mp + 3 * D_ / 2);
                    w1 += bf_lo(wp) + bf_hi(wp);
                    w2 += bf_lo(sv) * bf_lo(wr) + bf_hi(sv) * bf_hi(wr);
                }
#pragma unroll 1
                for (int i = 1; i < 32; i <<= 1) { w1 += __shfl_xor_sync(0xffffffffu, w1, i); w2 += __shfl_xor_sync(0xffffffffu, w2, i); }
                *reinterpret_cast<float2*>(smem_raw + SM_TS) = make_float2(w1, w2);
            }
#pragma unroll
            for (int i = 0; i < 4; i++) reinterpret_cast<uint4*>(smem_raw + SM_RED)[lane + 32 * i] = make_uint4(~0u, ~0u, ~0u, ~0u);
            asm volatile("fence.proxy.async.shared::cta;" ::: "memory");
            __syncwarp();
            if (elect()) {
                uint8_t* mb = g_frag + (size_t)rg * 8 * WREG + 3 * 4096;
#pragma unroll 1
                for (int k = 0; k < 8; k++, mb += WREG) {
#pragma unroll
                    for (int i = 0; i < 3; i++)
                        asm volatile("cp.async.bulk.global.shared::cta.bulk_group [%0], [%1], 2048;" ::"l"(mb + i * 2048), "r"(sb + SM_RED) : "memory");
                    __nanosleep(500);
                }
                asm volatile("cp.async.bulk.commit_group;\ncp.async.bulk.wait_group 0;\nfence.proxy.async.global;" ::: "memory");
            }
            __syncwarp();
            if (lane == 0) mbar_arrive(bar_mod);
            __syncwarp();
            mbar_wait_sleep(bar_go + 8, 0);
            if (elect()) asm volatile("prefetch.tensormap [%0];\nprefetch.tensormap [%1];\nprefetch.tensormap [%2];" ::"l"(&tm_x), "l"(&tm_p), "l"(&tm_d) : "memory");
            __syncwarp();
#pragma unroll 1
            for (int i = 1; i < 4; i++) {
                mbar_wait(bar_pub + 8 * i, 0);
                unsigned int* flags = padd(g_flag_part, (qb * 32 + i * 8 - 8) * 4);
                if (elect()) { flag_release(padd(flags, j * 4), tag); DBG_PG(93); }
                __syncwarp();
                const uint32_t slot = (i + 2) & 3;
                flag_wait(padd(flags, (lane & 7) * 4), tag);
                asm volatile("fence.proxy.async.global;" ::: "memory");
                if (lane == 0 && i == 3) DBG_PG(101);
                mbar_wait(bar_go + 8 + 8 * i, 0);
                mbar_wait(bar_empty + 8 * slot, i == 3);
                if (elect()) {
                    mbar_expect_tx(bar_full + 8 * slot, SLOT);
                    tma3d(sb + slot * SLOT, &tm_p, 0, j * 20 + (i - 1) * 4, qb * 8, bar_full + 8 * slot);
                    tma3d(sb + slot * SLOT + UNIT, &tm_p, 0, j * 20 + (i - 1) * 4 + 2, qb * 8, bar_full + 8 * slot);
                }
            }
        } else if (warp == 0) {
#pragma unroll 1
            for (int i = 0; i < 48; i++) {
                if (i == 0 || i == 17 || i == 34) mbar_wait_sleep(bar_qfree + (i >> 4) * 8, 0);
                if (SPARE && i == 17) {
                    flag_wait(&g_flag_q3[qb * 32], tag);
                    if (elect()) {
                        asm volatile("fence.proxy.async.global;" ::: "memory");
                        mbar_expect_tx(bar_q3, UNIT);
#pragma unroll 1
                        for (int k = 0; k < 8; k++) bulk_load(sb + SM_Q + 2 * SLOT + k * 4096 + 2048, &g_q3[(rg * 8 + k) * 128], 2048, bar_q3);
                    }
                }
                __nanosleep(700);
                if (elect()) {
                    asm volatile("mbarrier.expect_tx.shared::cta.b64 [%0], %1;" ::"r"(bar_g), "n"(1920) : "memory");
                    tma2d(sb + SM_Q + i * 1920, i < 24 ? &tm_g : &tm_u, (blockIdx.x * 36) & ~7, (i < 24 ? i : i - 24) * 24, bar_g);
                }
            }
            if (elect()) mbar_arrive(bar_g);
#pragma unroll 1
            for (int i = 0; i < 18; i++) {
                __nanosleep(400);
                if (OPF && i < 8 * OPF && elect()) l2_prefetch(g_frag + (size_t)(rg * 8 + (i & 7)) * WREG + (i >> 3) * 4096, 4096);
                if (elect()) l2_prefetch(args.w_down + (size_t)(blockIdx.x * 36 + i * 2) * D_, 4 * D_);
            }
            __syncwarp();
            mbar_wait_sleep(bar_go + 8 * 2, 0);
            uint32_t acc = 0;
#pragma unroll 1
            for (int k = lane; k < 16 * 9; k += 32) acc |= touch(padd(args.x, (rg * 16 * D_ + k * 64) * 2));
            if (acc == 0) reinterpret_cast<volatile uint32_t*>(smem_raw + SM_BAR)[127] = acc;
            __syncwarp();
            mbar_wait_sleep(bar_go + 8 * 4, 0);
            uint4* rp = padd(g_rows, (rg * 2 * RSLOT + lane) * 16);
#pragma unroll
            for (int k = 0; k < 12; k++) rp[k * 32] = make_uint4(~0u, ~0u, ~0u, ~0u);
            if (blockIdx.x < 72) {
                uint4* yp = reinterpret_cast<uint4*>(padd(g_ypart, blockIdx.x * NCTA * 64 + lane * 16));
#pragma unroll
                for (int k = 0; k < 16; k++) yp[k * 32] = make_uint4(~0u, ~0u, ~0u, ~0u);
            }
            asm volatile("fence.acq_rel.gpu;" ::: "memory");
            __syncwarp();
            if (lane == 0) mbar_arrive(bar_pre);
        } else if (warp == 1) {
            __nanosleep(QDELAY);
            uint32_t go = bar_go;
            uint64_t marks = 24 | 151 << 8 | 155 << 16 | 160ull << 24 | 165ull << 32;
#pragma unroll 1
            for (int e = E0; e < 168; e++) {
                const CUtensorMap* tm;
                int c0, c1;
                uint64_t pol = EVICT_FIRST;
                if (e == 159 || e == 164) continue;
                if (e < 21 && e != 19) {
                    const int i = SPARE && e < 12 ? e - 2 : e - (e == 20), hd = (i * 52) >> 8;
                    tm = &tm_wq; c0 = (4 * j + ((0x1320 >> (4 * hd)) & 3)) * DH + c * 64; c1 = (i - hd * 5) * 128 - 64;
                    if (SPARE && e >= 12 && e < 15) { c0 = (4 * j + 3) * DH; c1 = (2 * (e - 12) + c) * 128; }
                } else if (e < 148) {
                    const int i = max(e - 20, 0);
                    const bool isk = i == 0 || ((i & 1) && i < 127);
                    const int n = isk ? (i + 1) >> 1 : (i - 1) >> 1;
                    tm = isk ? &tm_k : &tm_v; c0 = c * 64; c1 = (2 * j + (n >> 5)) * S_ + (n & 15) * 128;
                    if (!(i & 32)) pol = EVICT_NORMAL;
                } else {
                    int i = e - 148 - (e > 159) - (e > 164);
                    tm = &tm_wo; c0 = (i >> 1) * 64; c1 = (4 * j + (O2F ? ((i & 1) ? c : 2 + c) : (i & 1) ? 1 + c : 3 * c)) * DH;
                }
                const uint32_t fb = e == E0 ? bar_w0 : bar_full + 8 * (e & 3), d = sb + (e == E0 ? 6 : e & 3) * SLOT;
                if (e >= 24 && e < 152) mbar_wait_sleep(bar_empty + 8 * (e & 3), ~(e >> 2) & 1);
                else if (e != E0) mbar_wait(bar_empty + 8 * (e & 3), ~(e >> 2) & 1);
                if (elect()) {
                    mbar_expect_tx(fb, SLOT);
                    tma2d_mc(d + c * UNIT, tm, c0, c1, fb, pol);
                    const int i = e - PF_KV;
                    if (i >= 0 && i < 128 && !(i & 32))
                        l2_prefetch(((i & 1) ? args.vc : args.kc) + (size_t)((2 * j + (i >> 6)) * S_ + (i & 30) * 64) * DH + qb * 1024, 2048);
                    if (e >= PF_WO && e < PF_WO + 18) l2_prefetch(args.wo + (size_t)blockIdx.x * (QD * D_ / NCTA) + (e - PF_WO) * 1024, 2048);
                    if (e == (marks & 255)) mbar_arrive(go);
                }
                if (e == (marks & 255)) { go += 8; marks >>= 8; }
            }
            asm volatile("fence.proxy.async.global;" ::: "memory");
            mbar_wait(bar_empty, 1);
            if (elect()) {
                mbar_expect_tx(bar_full, 16 * XP);
                tma2d(sb, &tm_x, 0, rg * 16, bar_full);
            }
            mbar_wait(bar_empty + 16, 1);
            if (C3D) __nanosleep(C3D);
            if (elect()) {
                mbar_expect_tx(bar_full + 16, SLOT);
                tma3d(sb + 2 * SLOT, &tm_p, 0, j * 20 + 12, qb * 8, bar_full + 16);
                tma3d(sb + 2 * SLOT + UNIT, &tm_p, 0, j * 20 + 14, qb * 8, bar_full + 16);
            }
            mbar_wait(bar_empty + 24, 1);
            if (C4D) __nanosleep(C4D);
            if (elect()) {
                mbar_expect_tx(bar_full + 24, UNIT);
                tma3d(sb + 3 * SLOT, &tm_p, 0, j * 20 + 16, qb * 8, bar_full + 24);
            }
            mbar_wait(bar_empty + 8, 0);
            mbar_wait(bar_empty + 16, 0);
            if (DD) __nanosleep(DD);
            if (elect()) {
#pragma unroll
                for (int i = 1; i < 3; i++) {
                    mbar_expect_tx(bar_full + 8 * i, 18 * XP);
                    tma2d(sb + i * SLOT, &tm_d, 0, blockIdx.x * 36 + (i - 1) * 18, bar_full + 8 * i);
                }
            }
        } else {
            if (elect()) asm volatile("prefetch.tensormap [%0];\nprefetch.tensormap [%1];\nprefetch.tensormap [%2];" ::"l"(&tm_k), "l"(&tm_v), "l"(&tm_wo) : "memory");
            if (SPARE) {
                mbar_wait_sleep(bar_pub, 0);
                if (lane == 0) flag_release(padd(g_flag_h, rg * 128), tag);
                __syncwarp();
            }
            bar_sync(1, 192);
            for (int i = QT0; i < 4; i++) bar_sync(1, 192);
#pragma unroll 1
            for (uint32_t e = E0 + 5; e < 20; e++) {
                mbar_wait(bar_full + 8 * (e & 3), (e >> 2) & 1);
                if (!(((SPARE ? 0xa080 : 0x8420) >> e) & 1)) bar_sync(1, 192);
            }
#pragma unroll 1
            for (uint32_t e = 20; e < 148; e++) {
                mbar_wait_sleep(bar_full + 8 * (e & 3), (e >> 2) & 1);
                if (SPARE && e == 113) mbar_wait(bar_q3, 0);
                if (e & 1) bar_sync(1, 192);
                if (!(e & 1) || e == 147) bar_sync(4, 160);
            }
#pragma unroll 1
            for (uint32_t e = 148; e < 168; e++) {
                mbar_wait(bar_full + 8 * (e & 3), (e >> 2) & 1);
                if (e != 159 && e != 164) bar_sync(1, 192);
            }
        }
        __syncwarp();
        mbar_wait_sleep(bar_out, 0);
        if (OUTD) __nanosleep(OUTD);
        if (elect()) {
            asm volatile("fence.proxy.async.shared::cta;" ::: "memory");
            const int2 sel = reinterpret_cast<const int2*>(smem_raw + SM_RED)[8];
#pragma unroll 1
            for (int i = warp; i < 16; i += 4) {
                const int row = rg * 16 + i;
                if (row != sel.x && row != sel.y)
                    asm volatile("cp.async.bulk.global.shared::cta.bulk_group.L2::cache_hint [%0], [%1], %2, %3;"
                                 ::"l"(args.out + (size_t)row * D_), "r"(sb + i * XP), "n"(D_ * 2), "l"(OUTPOL) : "memory");
            }
            asm volatile("cp.async.bulk.commit_group;\ncp.async.bulk.wait_group.read 0;" ::: "memory");
        }
    } else {
        uint32_t cv[2] = {0, 0}, tag = load_tag(gs) - 1;
        if (blockIdx.x < 72) {
            uint32_t ws;
            int tid;
            asm volatile("mov.u32 %0, smem_raw;\nmov.u32 %1, %%tid.x;" : "=r"(ws), "=r"(tid));
            tid -= 128;
            ws += SM_Q + SLOT + tid * 16;
            const uint32_t* cp = padd(reinterpret_cast<const uint32_t*>(args.cvec), (tid & 0xe0) + (tid & 7) * 4);
            cv[0] = *padd(cp, (tid & 24) * 32);
            if (tid < 128) cv[1] = cp[256];
            const bf16* wrow = args.w_mod + (size_t)(tid >> 1) * (6 * D_) + (tid & 1) * 8 + blockIdx.x * 16;
#pragma unroll
            for (int i = 0; i < 5; i++)
                if (i < 4 || tid < 128)
                    asm volatile("cp.async.cg.shared.global [%0], [%1], 16;" ::"r"(ws + i * 4096), "l"(wrow + (size_t)i * 128 * (6 * D_)) : "memory");
        }
        asm volatile("barrier.cluster.arrive.relaxed.aligned;" ::: "memory");
        asm volatile("setmaxnreg.inc.sync.aligned.u32 240;");
        const int lane = threadIdx.x & 31;
        const int cw = warp - 4;
        const int w = cw >> 2;
        const int tid = threadIdx.x - 128;
        ROLES();
        float* red = reinterpret_cast<float*>(smem_raw + SM_RED);
        DBG_INIT();
        DBG_G(120);
        DBG_T(100);

        {
            if (blockIdx.x < 72) {
                uint32_t sa[10];
#pragma unroll
                for (int i = 0; i < 2; i++) {
                    const float lo = bf_lo(cv[i]), hi = bf_hi(cv[i]);
                    cv[i] = pack_bf16(lo * sigmoidf_(lo), hi * sigmoidf_(hi));
                }
#pragma unroll
                for (int i = 0; i < 10; i++) sa[i] = __shfl_sync(0xffffffffu, cv[i >> 3], (i & 7) * 4 + (lane & 3));
                uint2* mdst = &gs->mod1[(tid >> 3) * D_ + blockIdx.x * 8 + (tid & 7)];
                anchor(bar_full + 504, sa[0] & sa[1] & sa[2] & sa[3] & sa[4] & sa[5] & sa[6] & sa[7] & sa[8] & sa[9] & (uint32_t)(uintptr_t)mdst & (uint32_t)((uintptr_t)mdst >> 32));
                asm volatile("cp.async.wait_all;" ::: "memory");
                __syncwarp();
                const uint32_t ws = sb + SM_Q + SLOT + cw * 512 + (lane & 15) * 32 + (lane & 16);
                float d[16];
#pragma unroll
                for (int i = 0; i < 16; i++) d[i] = 0.f;
#pragma unroll
                for (int i = 0; i < 5; i++) {
                    const uint4 b = ldsm4t(ws + (i < 4 || cw < 4 ? i * 4096 : 0));
                    mma16816(d + 8 * (i & 1), sa[2 * i], sa[2 * i], sa[2 * i + 1], sa[2 * i + 1], b.x, b.y);
                    mma16816(d + 8 * (i & 1) + 4, sa[2 * i], sa[2 * i], sa[2 * i + 1], sa[2 * i + 1], b.z, b.w);
                }
                if (lane < 8) reinterpret_cast<float2*>(red)[lane * 8 + cw] = (lane & 4) ? make_float2(d[4] + d[12], d[5] + d[13]) : make_float2(d[0] + d[8], d[1] + d[9]);
                bar_sync(3, 256);
                if (tid < 8 * MREP) {
                    const float4* r = reinterpret_cast<const float4*>(red) + (tid & 7) * 4;
                    const float4 r0 = r[0], r1 = r[1], r2 = r[2], r3 = r[3];
                    st_relaxed64(mdst, pack_bf16(((r0.x + r0.z) + (r1.x + r1.z)) + ((r2.x + r2.z) + (r3.x + r3.z)),
                                                 ((r0.y + r0.w) + (r1.y + r1.w)) + ((r2.y + r2.w) + (r3.y + r3.w))), tag + 1);
                }
            }
            DBG_G(106);
            asm volatile("barrier.cluster.wait.aligned;" ::: "memory");
            mbar_wait(bar_x, 0);
            asm volatile("add.u32 %0, %0, 1;" : "+r"(tag));
            uint32_t x[20];
            float st[12], st2[12];
            rows_load(x, sb + SM_Q + (lane & 15) * XP + (lane >> 4) * 16 + cw * 32, cw);
#pragma unroll
            for (int i = 0; i < 12; i++) { st[i] = 0.f; st2[i] = 0.f; }
#pragma unroll
            for (int k = 0; k < 9; k++) stats_add((k & 1) ? st2 : st, x[2 * k], x[2 * k + 1], 0x3f803f80u);
#pragma unroll
            for (int i = 0; i < 12; i++) st[i] += st2[i];
            uint32_t mean2;
            float dot;
            const float rsd = rows_stats(st, reinterpret_cast<float4*>(red + 128), cw, lane, mean2, dot);
            const uint4* mp = reinterpret_cast<const uint4*>(gs->mod1 + ((blockIdx.x >> 1) & (MREP - 1)) * D_) + min(tid, D_ / 4 - 1);
            uint4 v0 = make_uint4(0, tag, 0, tag), v1 = v0;
            auto look = [&]() {
                asm volatile("{\n.reg .pred p;\n.reg .b64 a, b, c, d;\nsetp.lt.s32 p, %9, 5;\nmov.b64 a, {%0, %1};\nmov.b64 b, {%2, %3};\n"
                             "mov.b64 c, {%4, %5};\nmov.b64 d, {%6, %7};\n@p ld.relaxed.gpu.global.v2.b64 {a, b}, [%8];\n"
                             "@p ld.relaxed.gpu.global.v2.b64 {c, d}, [%8 + 2304];\n"
                             "mov.b64 {%0, %1}, a;\nmov.b64 {%2, %3}, b;\nmov.b64 {%4, %5}, c;\nmov.b64 {%6, %7}, d;\n}"
                             : "+r"(v0.x), "+r"(v0.y), "+r"(v0.z), "+r"(v0.w), "+r"(v1.x), "+r"(v1.y), "+r"(v1.z), "+r"(v1.w)
                             : "l"(mp), "r"(cw) : "memory");
            };
            rows_normalise(x, x, mean2, rsd, lane, look);
            fence_regs(x);
            uint32_t it = 0;
#pragma unroll 1
            while (((v0.y ^ tag) | (v0.w ^ tag) | (v1.y ^ tag) | (v1.w ^ tag)) && ++it < SPIN / 16) look();
            uint4* smod = reinterpret_cast<uint4*>(smem_raw + SM_Q + M_MOD);
            if (tid < D_ / 4) smod[tid] = make_uint4(badd2(v1.x, 0x3f803f80u), v0.x, badd2(v1.z, 0x3f803f80u), v0.z);
            uint4* hdst = g_h + (size_t)(rg * 36 + cw) * 32 + lane;
            uint2* hdst2 = reinterpret_cast<uint2*>(g_h + (size_t)(rg * 36 + 32) * 32) + tid;
            bar_sync(3, 256);
            DBG_G(107);
#pragma unroll
            for (int k = 0; k < 9; k++) {
                const uint2 cs = lds64(sb + SM_Q + M_MOD + (cw * 8 + (lane & 3) + (k < 8 ? (k >> 1) * 64 + (k & 1) * 4 : 256 - cw * 4)) * 8);
                const uint32_t c1 = cs.x, sa = cs.y;
                x[2 * k] = badd2(bmul2(x[2 * k], c1), sa);
                if (x[2 * k] == 0) x[2 * k] = 0x8000u;
                x[2 * k + 1] = badd2(bmul2(x[2 * k + 1], c1), sa);
            }
#pragma unroll
            for (int ch = 0; ch < 4; ch++) st_relaxed4(hdst + ch * 256, x[4 * ch], x[4 * ch + 1], x[4 * ch + 2], x[4 * ch + 3]);
            st_relaxed64(hdst2, x[16], x[17]);
            __syncwarp();
            if (SPARE && lane == 0) mbar_arrive(bar_pub);
            DBG_G(108);
        }

        uint32_t rel_base;
        asm("mapa.shared::cluster.u32 %0, %1, %2;" : "=r"(rel_base) : "r"(bar_empty), "r"(lane & 1));
        auto release = [&](uint32_t slot) { if (lane < 2) mbar_arrive_cluster(rel_base + 8 * slot); };
        uint32_t q[32], p[32];
        float s[64], o[64];

        const int lw = cw & 3;
        const uint32_t relw = lw == RW && lane < 8, handw = lw == HW || cw == HW2;
        auto release4 = [&](uint32_t off, uint32_t on = 1) {
            asm volatile("{\n.reg .pred p;\nsetp.ne.b32 p, %1, 0;\n@p mbarrier.arrive.shared::cluster.b64 _, [%0];\n}" ::"r"(rel_base + off), "r"(relw & on) : "memory"); };
        auto handoff = [&](uint32_t on = 1) {
            asm volatile("{\n.reg .pred p;\nsetp.ne.b32 p, %1, 0;\n@p bar.arrive %0, 192;\n}" ::"r"(2 - w), "r"(handw & on) : "memory"); };
        if (cw == 4 + HW) bar_arrive(1, 192);

        uint4* qpark = reinterpret_cast<uint4*>(smem_raw + SM_Q - SLOT) + cw * 256 + lane;
        {
            uint32_t h[144];
            const uint4* hf = g_h + (size_t)(qb * 8 + cw) * (36 * 32) + lane;
            auto load_h = [&](auto lo, auto hi) {
#pragma unroll
                for (int ks = lo.value; ks < hi.value; ks++) {
                    const uint4 v = h_frag(hf, ks, lane);
                    h[4 * ks] = v.x; h[4 * ks + 1] = v.y; h[4 * ks + 2] = v.z; h[4 * ks + 3] = v.w;
                }
            };
            auto check_h = [&](auto lo, auto hi) {
                uint32_t it = 0;
                bool miss;
#pragma unroll 1
                do {
                    uint32_t mn = ~0u;
#pragma unroll
                    for (int ks = lo.value; ks < hi.value; ks++) mn = __vimin3_u32(mn, h[4 * ks], h[4 * ks + 2]);
                    miss = __any_sync(0xffffffffu, mn == 0);
                    if (miss) load_h(lo, hi);
                    asm volatile("add.u32 %0, %0, 1;" : "+r"(it));
                } while (miss && it < SPIN / 16);
            };
            __nanosleep(HDELAY);
            load_h(IC<0>{}, IC<4>{});
            DBG_T(104); DBG_G(109);
            mbar_wait(bar_w0, 0);
#pragma unroll
            for (int e = E0 + 1; e < E0 + 5; e++) mbar_wait(bar_full + 8 * (e & 3), e >> 2);
#pragma unroll
            for (int i = 0; i < 64; i++) o[i] = 0.f;
            auto group = [&](auto tc, auto ec) {
                constexpr int t = tc.value, e = ec.value, k0 = t ? 8 * t - 4 : 0;
                constexpr bool first = e < E0 + 5, turns = e >= E0 + QT0;
                uint64_t dv = (first ? args.d0 : desc_lo(0, UNIT) | (0x40000040ull << 32)) + ((t ? 0 : 512) + (e == E0 ? 6 : e & 3) * (SLOT / 16));
                if (first) check_h(IC<k0>{}, IC<8 * t + 4>{});
                if (t != 1 && turns) bar_sync(1 + w, 192);
                if (t != 1 || first) WG_FENCE();
#pragma unroll
                for (int ks = k0; ks < 8 * t + 4; ks++) {
                    mma_rs128<1>(o, h[4 * ks], h[4 * ks + 1], h[4 * ks + 2], h[4 * ks + 3], dv, ks);
                    if (t && turns && ks == k0 + QSPLIT - 1) WG_COMMIT();
                }
                if (t || first) WG_COMMIT();
                if (t < 4 && first) load_h(IC<8 * t + 4>{}, IC<t < 4 ? 8 * t + 12 : 0>{});
                if (t > 0) {
                    WG_WAIT(1);
                    if (turns) handoff();
                    if ((t == 1 && !first) || (t > 1 && e <= E0 + QT0)) release4(8 * ((e - 1) & 3));
                    if (turns && e != 18) { WG_WAIT(0); release4(8 * (e & 3)); }
                }
            };
            auto head = [&](auto ec, int slot) {
                constexpr int e = ec.value;
                fence_regs(o);
                group(IC<0>{}, IC<e>{}); group(IC<1>{}, IC<e + 1>{}); group(IC<2>{}, IC<e + 2>{}); group(IC<3>{}, IC<e + 3>{});
                if (e == 15) return;
                group(IC<4>{}, IC<e + 4>{});
                fence_regs(o);
#pragma unroll
                for (int i = 0; i < 8; i++)
                    qpark[slot * 2048 + i * 32] = make_uint4(pack_bf16(o[8 * i], o[8 * i + 1]), pack_bf16(o[8 * i + 2], o[8 * i + 3]),
                                                             pack_bf16(o[8 * i + 4], o[8 * i + 5]), pack_bf16(o[8 * i + 6], o[8 * i + 7]));
            };
            head(IC<E0>{}, 1);
            head(IC<E0 + 5>{}, 2);
            if (SPARE) {
                float (&u)[32] = reinterpret_cast<float (&)[32]>(o);
                fence_regs(u);
#pragma unroll
                for (int t = 0; t < 2; t++) {
                    uint64_t dv = args.d0 + t * (SLOT / 16);
                    bar_sync(1 + w, 192);
                    WG_FENCE();
#pragma unroll
                    for (int ks = 0; ks < 16 + 4 * t; ks++) {
                        mma_rs64<1>(u, h[64 * t + 4 * ks], h[64 * t + 4 * ks + 1], h[64 * t + 4 * ks + 2], h[64 * t + 4 * ks + 3], dv, ks | t);
                        if (ks == 2 * QSPLIT + 4 * t - 1) WG_COMMIT();
                    }
                    WG_COMMIT();
                    WG_WAIT(1);
                    handoff();
                    WG_WAIT(0);
                    release4(8 * t);
                }
                fence_regs(u);
                release4(16);
#pragma unroll
                for (int i = 0; i < 4; i++)
                    qpark[3 * 2048 + i * 32] = make_uint4(pack_bf16(u[8 * i], u[8 * i + 1]), pack_bf16(u[8 * i + 2], u[8 * i + 3]),
                                                          pack_bf16(u[8 * i + 4], u[8 * i + 5]), pack_bf16(u[8 * i + 6], u[8 * i + 7]));
            } else {
                head(IC<10>{}, 3);
            }
            head(IC<15>{}, 0);
#pragma unroll
            for (int i = 0; i < 8; i++) {
                const uint4 v = lds128(smem_u32(qpark + 2048 + i * 32));
                q[4 * i] = v.x; q[4 * i + 1] = v.y; q[4 * i + 2] = v.z; q[4 * i + 3] = v.w;
            }
#pragma unroll
            for (int i = 0; i < 32; i++) p[i] = h[112 + i];
            WG_WAIT(0);
            fence_regs(o);
            release4(16);
        }
        DBG_T(105);
        DBG_G(125);

        uint8_t* frag = reinterpret_cast<uint8_t*>(__shfl_sync(0xffffffffu, reinterpret_cast<unsigned long long>(g_frag + (size_t)(rg * 8 + cw) * WREG + lane * 16), lane));
        const uint4* qnext = reinterpret_cast<const uint4*>(__shfl_sync(0xffffffffu, reinterpret_cast<unsigned long long>(padd(smem_raw, SM_Q + tid * 16 + cw * 3584)), lane));
        uint8_t* odst = reinterpret_cast<uint8_t*>(const_cast<uint4*>(qnext));
        qnext -= 2048;
        float m0, m1, l0 = 0.25f, l1 = 0.25f, t0, t1;
        uint32_t bad = 0;
        auto finish = [&](auto lo, auto hi, uint32_t bit, auto sink) {
#pragma unroll
            for (int i = lo.value; i < hi.value; i++) {
                const uint32_t v0 = pack_bf16(o[8 * i] * t0, o[8 * i + 1] * t0), v1 = pack_bf16(o[8 * i + 2] * t1, o[8 * i + 3] * t1);
                const uint32_t v2 = pack_bf16(o[8 * i + 4] * t0, o[8 * i + 5] * t0), v3 = pack_bf16(o[8 * i + 6] * t1, o[8 * i + 7] * t1);
                if (i == 0 && fabsf(o[0] * t0) >= 0x1p-31f) bad |= bit << 8;
                sink(i, v0, v1, v2, v3);
            }
        };
        float lq[6];
        auto row_parts = [&]() {
#pragma unroll
            for (int i = 0; i < 3; i++) { lq[i] = __shfl_xor_sync(0xffffffffu, l0, i + 1); lq[3 + i] = __shfl_xor_sync(0xffffffffu, l1, i + 1); }
        };
        auto row_sums = [&](uint32_t bit) {
            t0 = (l0 + lq[0]) + (lq[1] + lq[2]); t1 = (l1 + lq[3]) + (lq[4] + lq[5]);
            if (!(t0 >= LMIN && t0 < LMAX && t1 >= LMIN && t1 < LMAX)) bad |= bit;
        };
        auto issue_pv = [&](uint64_t dv, int acc, auto lo, auto hi) {
            if (lo.value == 0) asm volatile("{\n.reg .pred p;\nsetp.eq.b32 p, %0, 0;\n@p bar.sync 4, 160;\n}" ::"r"(w) : "memory");
#pragma unroll
            for (int ks = lo.value; ks < hi.value; ks++)
                mma_rs128<1>(o, p[4 * ks], p[4 * ks + 1], p[4 * ks + 2], p[4 * ks + 3], dv, ks ? 1 : acc);
            WG_COMMIT();
        };
#pragma unroll
        for (int i = 0; i < 64; i++) s[i] = 0.f;
        uint64_t dv_lo = args.d0;
        uint32_t voff = 0;
        auto issue_qk = [&]() {
            uint64_t dk = dv_lo ^ (desc_lo(0, UNIT) ^ desc_lo(3 * SLOT, 16));
            bar_sync(1 + w, 192);
            fence_regs(s); fence_regs(q); fence_regs(o); fence_regs(p);
            WG_FENCE();
#pragma unroll
            for (int ks = 0; ks < 8; ks++)
                if (ks == 3) mma_rs128<0, 1018>(s, q[4 * ks], q[4 * ks + 1], q[4 * ks + 2], q[4 * ks + 3], dk, 1);
                else mma_rs128<0, 2>(s, q[4 * ks], q[4 * ks + 1], q[4 * ks + 2], q[4 * ks + 3], dk, ks != 0);
            WG_COMMIT();
        };
        auto to_frag = [&](int i, uint32_t v0, uint32_t v1, uint32_t v2, uint32_t v3) {
            *reinterpret_cast<uint4*>(odst + i * 512) = make_uint4(v0, v1, v2, v3); };
        int n = 0;
        auto scores_ready = [&]() {
            WG_WAIT(1);
            fence_regs(s); fence_regs(q);
        };
        auto pass_on = [&]() {
            release4(voff ^ 24);
            handoff();
        };
#pragma unroll 1
        for (;;) {
            {
                if (RPE) {
                    asm volatile("st.shared.v2.f32 [%0], {%1, %2};" ::"r"(sb + SM_RED + tid * 8), "f"(l0), "f"(l1) : "memory");
                    __syncwarp();
                    const uint4 a = lds128(sb + SM_RED + (tid & ~3) * 8), b = lds128(sb + SM_RED + (tid & ~3) * 8 + 16);
                    l0 = __uint_as_float(a.x); lq[0] = __uint_as_float(a.z); lq[1] = __uint_as_float(b.x); lq[2] = __uint_as_float(b.z);
                    l1 = __uint_as_float(a.y); lq[3] = __uint_as_float(a.w); lq[4] = __uint_as_float(b.y); lq[5] = __uint_as_float(b.w);
                } else {
                    row_parts();
                }
                issue_qk();
                if (RPE == 2) hold(l0, l1);
                row_sums(1u << (n >> 4));
                t0 = rcp_fast(t0); t1 = rcp_fast(t1);
                l0 = 0.f; l1 = 0.f;
                odst = n ? frag + ((n >> 4) - 1) * 4096 : odst;
                qnext = n == 48 ? reinterpret_cast<const uint4*>(frag + O2F * 8192) : qnext + 2048;
                if (RPE) anchor(bar_full + 504, (t0 + t1) * __uint_as_float((bad ^ (uint32_t)(uintptr_t)odst ^ (uint32_t)(uintptr_t)qnext) & 0x3fffffff));
                asm volatile("{\n.reg .pred p;\nsetp.ne.b32 p, %1, 0;\n@p mbarrier.arrive.shared::cta.b64 _, [%0];\n}"
                             ::"r"(bar_qfree + (n >> 1) - 8), "r"(lane ? 0 : n) : "memory");
                issue_pv(dv_lo, 1, IC<0>{}, IC<8>{});
                scores_ready();
                float a0 = fmaxf(s[0], s[1]), a1 = fmaxf(s[2], s[3]), a2 = fmaxf(s[4], s[5]), a3 = fmaxf(s[6], s[7]);
#pragma unroll
                for (int i = 1; i < MAXG; i++) {
                    a0 = fmaxf(a0, fmaxf(s[8 * i], s[8 * i + 1])); a1 = fmaxf(a1, fmaxf(s[8 * i + 2], s[8 * i + 3]));
                    a2 = fmaxf(a2, fmaxf(s[8 * i + 4], s[8 * i + 5])); a3 = fmaxf(a3, fmaxf(s[8 * i + 6], s[8 * i + 7]));
                }
                const uint32_t a = MAXG ? pack_bf16(fmaxf(a0, a2), fmaxf(a1, a3)) : pack_bf16(a0, a1);
                const uint32_t b = bmax2(bmax2(a, __shfl_xor_sync(0xffffffffu, a, 1)), bmax2(__shfl_xor_sync(0xffffffffu, a, 2), __shfl_xor_sync(0xffffffffu, a, 3)));
                pass_on();
                m0 = fmaf(-CS, bf_lo(b), -POFF); m1 = fmaf(-CS, bf_hi(b), -POFF);
            }
#pragma unroll 1
            for (;;) {
                DBG_T(n);
#pragma unroll
                for (int i = 0; i < 4 * STAGE; i++) s[i] = fmaf(s[i], CS, (i & 2) ? m1 : m0);
#pragma unroll
                for (int i = 0; i < 4 * SPLIT; i++) s[i] = ex2(s[i]);
#pragma unroll
                for (int i = 0; i < SPLIT; i++) { l0 += s[4 * i] + s[4 * i + 1]; l1 += s[4 * i + 2] + s[4 * i + 3]; }
                if (STAGE < 16) {
                    m0 = fmaf(l0, 0.f, m0); m1 = fmaf(l1, 0.f, m1);
                }
                anchor(bar_full + 504, l0 + l1);
                WG_WAIT(0);
                fence_regs(o); fence_regs(p);
                release4(voff);
                dv_lo ^= 2 * SLOT / 16;
                voff ^= 16;
                n++;
#pragma unroll
                for (int i = 4 * STAGE; i < 64; i++) s[i] = fmaf(s[i], CS, (i & 2) ? m1 : m0);
#pragma unroll
                for (int i = 4 * SPLIT; i < 64; i++) s[i] = ex2(s[i]);
#pragma unroll
                for (int i = SPLIT; i < 16; i++) { l0 += s[4 * i] + s[4 * i + 1]; l1 += s[4 * i + 2] + s[4 * i + 3]; }
#pragma unroll
                for (int i = 0; i < 32; i++) p[i] = pack_bf16(s[2 * i], s[2 * i + 1]);
                const int jn = n & 15;
                if (jn > 1) {
                    issue_qk();
                    if ((n & RA) == RB) {
                        if (n & 1) {
#pragma unroll
                            for (int i = 0; i < 64; i++) o[i] *= (i & 2) ? t1 : t0;
                        } else {
                            row_parts();
                            row_sums(2u << (n >> 4));
                            const uint32_t e0 = __float_as_uint(t0) >> 23, e1 = __float_as_uint(t1) >> 23;
                            m0 -= __uint_as_float(0x4b000000u | e0) - (8388608.f + 127.f - POFF);
                            m1 -= __uint_as_float(0x4b000000u | e1) - (8388608.f + 127.f - POFF);
                            t0 = __uint_as_float((254 - (int)POFF - e0) << 23); t1 = __uint_as_float((254 - (int)POFF - e1) << 23);
                            l0 *= t0; l1 *= t1;
                        }
                    }
                    fence_regs(o);
                    WG_FENCE();
                    issue_pv(dv_lo, 1, IC<0>{}, IC<8>{});
                    scores_ready();
                    pass_on();
                    if (jn != 15) continue;
#pragma unroll
                    for (int i = 0; i < 8; i++) {
                        const uint4 v = qnext[i * 32];
                        q[4 * i] = v.x; q[4 * i + 1] = v.y; q[4 * i + 2] = v.z; q[4 * i + 3] = v.w;
                    }
                    continue;
                }
                if (jn == 0) break;
                finish(IC<0>{}, IC<ESPLIT>{}, 1u << (n >> 4), to_frag);
                issue_qk();
                if (HOLD) hold(t0, t1);
                finish(IC<ESPLIT>{}, IC<8>{}, 1u << (n >> 4), to_frag);
                WG_FENCE();
                issue_pv(dv_lo, 0, IC<0>{}, IC<8>{});
                scores_ready();
                pass_on();
            }
            if (n == 64) break;
        }
        DBG_T(64);
        uint32_t a1[32], a2[32];
        bar_sync(1 + w, 192);
        fence_regs(o); fence_regs(p);
        WG_FENCE();
        issue_pv(args.d0 + 3 * SLOT / 16, 1, IC<0>{}, IC<8>{});
        handoff();
        mbar_wait(bar_mod, 0);
        const int tid_ = __shfl_sync(0xffffffffu, tid, lane);
        row_parts();
        row_sums(16);
        t0 = rcp_fast(t0); t1 = rcp_fast(t1);
        anchor(frag, q[0] & q[4] & q[8] & q[12] & q[16] & q[20] & q[24] & q[28] & __float_as_uint(t0) & __float_as_uint(t1) & tid_);
        frag_load(a1, frag + (1 - O2F) * 4096);
        frag_load<0, A2N>(a2, frag + (2 - O2F) * 4096);
        anchor(frag, bad);
        WG_WAIT(0);
        fence_regs(o); fence_regs(p);
        release4(24);
        finish(IC<0>{}, IC<8>{}, 16, [&](int i, uint32_t v0, uint32_t v1, uint32_t v2, uint32_t v3) {
            p[4 * i] = v0; p[4 * i + 1] = v1; p[4 * i + 2] = v2; p[4 * i + 3] = v3; });
        if (A2N < 8) { anchor(frag, p[31] & p[15]); frag_load<A2N, 8>(a2, frag + (2 - O2F) * 4096); }
        bad = __reduce_or_sync(0xffffffffu, bad);
        bad = ((bad | ~(bad >> 8)) >> 1) & 15;
        if (__builtin_expect(bad != 0, 0)) {
            uint8_t* keep = g_keep + (size_t)(rg * 8 + cw) * 4096 + lane * 16;
            frag_store(keep, p);
            attn_fallback(bad, tag, gs, frag, keep, args.wq, args.kc, args.vc);
            frag_load(q, frag + O2F * 8192); frag_load(a1, frag + (1 - O2F) * 4096); frag_load(a2, frag + (2 - O2F) * 4096); frag_load(p, keep);
            anchor(frag, q[0] & q[4] & q[8] & q[12] & q[16] & q[20] & q[24] & q[28] & p[0] & p[4] & p[8] & p[12] & p[16] & p[20] & p[24] & p[28]);
        }
        DBG_T(80);
        DBG_G(124);

        const uint32_t eye = (lane >> 3) == (lane & 3) ? 0x3f80u << ((lane & 4) * 4) : 0;
        auto sum8 = [&](uint32_t* r, const uint4 (&v)[8]) {
            float d[16];
#pragma unroll
            for (int i = 0; i < 16; i++) d[i] = 0.f;
#pragma unroll
            for (int src = 0; src < 8; src++) {
                mma1688(d + 8 * (src & 1), v[src].x, v[src].y, eye);
                mma1688(d + 8 * (src & 1) + 4, v[src].z, v[src].w, eye);
            }
#pragma unroll
            for (int i = 0; i < 4; i++) r[i] = pack_bf16(d[2 * i] + d[8 + 2 * i], d[2 * i + 1] + d[9 + 2 * i]);
        };
        uint4 v2[8], v3[8], wf[23];
        uint2 u4[8], gw[9];
        uint32_t x1[20], xs, pa, ta;
        const uint8_t *mb, *mb4;
        auto load_wf = [&](auto lo, auto hi) {
            const uint32_t wa = sb + SM_Q + ((tid_ & 8) * (D_ / 8) + cw * 16 + (tid_ & 7) + (tid_ & 16) / 2) * 80;
            const uint32_t wb = wa + (512 - cw * 8) * 80 - (tid_ & 16) * 39;
#pragma unroll
            for (int i = lo.value; i < hi.value; i++) wf[i] = ldsm4t(i < 20 ? wa + (i / 5) * 10240 + (i % 5) * 16 : wb + (i - 20) * 32);
        };
        uint32_t at[18];
        {
            float (&u)[32] = reinterpret_cast<float (&)[32]>(o);
            uint32_t off = 0;
            auto turn = [&](const uint32_t (&a)[32], const uint32_t (&b)[32], int acc) {
                uint64_t dv = args.d0 + off * (SLOT / 128);
                bar_sync(1 + w, 192);
                fence_regs(u);
                WG_FENCE();
#pragma unroll
                for (int ks = 0; ks < 16; ks++) {
                    const uint32_t* f = ks < 8 ? &a[4 * ks] : &b[4 * ks - 32];
                    mma_rs64<1>(u, f[0], f[1], f[2], f[3], dv, ks | acc);
                    if (ks == OSPLIT - 1) WG_COMMIT();
                }
                WG_COMMIT();
                WG_WAIT(1);
            };
            auto done = [&]() {
                WG_WAIT(0);
                fence_regs(u);
                release4(off);
                off = (off + 8) & 24;
            };
            auto store = [&](uint8_t* dst) {
#pragma unroll
                for (int i = 0; i < 4; i++)
                    st_relaxed4(dst + i * 512, pack_bf16(u[8 * i], u[8 * i + 1]), pack_bf16(u[8 * i + 2], u[8 * i + 3]),
                                pack_bf16(u[8 * i + 4], u[8 * i + 5]), pack_bf16(u[8 * i + 6], u[8 * i + 7]));
            };
            pa = sb + w * (UNIT - 2048) + tid_ * 16;
#pragma unroll
            for (int i = 0; i < 8; i++) at[i] = 0;
            fence_regs(q); fence_regs(p);
            uint8_t* dst = frag;
#pragma unroll
            for (int i = 0; i < 8; i++) asm volatile("" : "=r"(v2[i].x), "=r"(v2[i].y), "=r"(v2[i].z), "=r"(v2[i].w));
#pragma unroll 1
            for (int k = 0; k < 8; k++, dst += 2048) {
                const uint32_t poff = (off + 8) & 24;
                const bool sum = (0xa0 >> k) & 1;
                turn(q, p, 0);
                handoff();
                auto sum_p = [&](auto lo, auto hi) {
#pragma unroll
                    for (int i = lo.value; i < hi.value; i++) {
                        float a[8], b[8];
#pragma unroll
                        for (int src = 0; src < 8; src++) {
                            const uint32_t x = i == 0 ? v2[src].x : i == 1 ? v2[src].y : i == 2 ? v2[src].z : v2[src].w;
                            a[src] = bf_lo(x); b[src] = bf_hi(x);
                        }
                        at[i] = at[4 + i];
                        at[4 + i] = pack_bf16(((a[0] + a[2]) + (a[4] + a[6])) + ((a[1] + a[3]) + (a[5] + a[7])),
                                              ((b[0] + b[2]) + (b[4] + b[6])) + ((b[1] + b[3]) + (b[5] + b[7])));
                    }
                };
                if (sum) {
                    mbar_wait(bar_full + poff, 1);
#pragma unroll
                    for (int src = 0; src < 8; src++) v2[src] = lds128(pa + poff * (SLOT / 8) + src * 2048);
                    __syncwarp();
                    release(poff >> 3);
                    done();
                    off = (off + 8) & 24;
                    sum_p(IC<0>{}, IC<PS>{});
                } else {
                    done();
                }
                turn(a1, a2, 1);
                handoff();
                if (PS < 4 && sum) sum_p(IC<PS>{}, IC<4>{});
                done();
                store(dst);
                __syncwarp();
                asm volatile("{\n.reg .pred p;\nsetp.ne.b32 p, %1, 0;\n@p mbarrier.arrive.shared::cta.b64 _, [%0];\n}"
                             ::"r"(bar_pub + 4 + 4 * k), "r"(lane ? 0 : (0x2a >> k) & 1) : "memory");
            }
            turn(q, p, 0);
            handoff();
            mb = padd(g_frag, (qb * 64 + j) * WREG + 3 * 4096 + tid_ * 16);
            mb4 = padd(mb, 4096 + ((cw >> 1) - cw) * 512 + (cw & 1) * 8);
            xs = sb + (tid_ & 15) * XP + (tid_ & 16) + cw * 32;
            ta = sb + (cw * 8 + (tid_ & 3)) * 8;
#pragma unroll
            for (int k = 0; k < 9; k++) {
                gw[k] = lds64(ta + SM_T + (k < 8 ? (k >> 1) * 64 + (k & 1) * 4 : 256 - cw * 4) * 8);
                if (!(tid_ & 4)) gw[k].y = 0x3f803f80u;
            }
            mbar_wait(bar_g, 0);
            done();
            load_wf(IC<0>{}, IC<WF0>{});
            turn(a1, a2, 1);
            if (w == 0) handoff();
            if (P2E) {
                mbar_wait(bar_full + 8, 0);
#pragma unroll
                for (int src = 0; src < 8; src++) v2[src] = lds128(pa + SLOT + src * 2048);
            }
            done();
            store(dst);
            mbar_wait(bar_full, 0);
            rows_load(x1, xs, cw);
            if (w == 0) bar_sync(5, 256); else bar_arrive(5, 256);
        }
        DBG_T(81);
        DBG_G(122);

        {
        const int tid = tid_, lane = tid & 31;
        const int g8 = lane >> 2, qd = lane & 3, l16 = lane & 15;
        uint32_t h2[18], gb[9], k1, k2;
        float4* rec = reinterpret_cast<float4*>(red + 128);
        const uint2* candp = reinterpret_cast<const uint2*>(padd(g_cand, ((blockIdx.x & (CREP - 1)) * NCTA + (tid >> 1)) * 32 + (tid & 1) * 8));
        uint2 cd;
        auto stage_out = [&]() {
#pragma unroll
            for (int k = 0; k < 9; k++) {
                x1[2 * k] = badd2(x1[2 * k], bmul2(gb[k], h2[2 * k]));
                x1[2 * k + 1] = badd2(x1[2 * k + 1], bmul2(gb[k], h2[2 * k + 1]));
            }
#pragma unroll
            for (int ch = 0; ch < 4; ch++) stsm_x4(xs + ch * 256, x1[4 * ch], x1[4 * ch + 1], x1[4 * ch + 2], x1[4 * ch + 3]);
            asm volatile("stmatrix.sync.aligned.m8n8.x2.shared.b16 [%0], {%1, %2};" ::"r"(xs + 1024 - cw * 16), "r"(x1[16]), "r"(x1[17]) : "memory");
        };
        {
            uint32_t it = 0, miss;
            if (!P2E) {
                mbar_wait(bar_full + 8, 0);
#pragma unroll
                for (int src = 0; src < 8; src++) v2[src] = lds128(pa + SLOT + src * 2048);
            }
            sum8(at + 8, v2);
            float st[12];
#pragma unroll
            for (int i = 0; i < 12; i++) st[i] = 0.f;
            auto add_pair = [&](int k) {
                x1[2 * k] = badd2(x1[2 * k], bmul2(gw[k].x, at[2 * k]));
                x1[2 * k + 1] = badd2(x1[2 * k + 1], bmul2(gw[k].x, at[2 * k + 1]));
                stats_add(st, x1[2 * k], x1[2 * k + 1], gw[k].y);
            };
#pragma unroll
            for (int k = 0; k < 6; k++) add_pair(k);
            mbar_wait(bar_full + 16, 0);
#pragma unroll
            for (int src = 0; src < 8; src++) v3[src] = lds128(pa + 2 * SLOT + src * 2048);
#pragma unroll 1
            do {
                if (BO && it) __nanosleep(BO);
                miss = 0;
#pragma unroll
                for (int src = 0; src < 8; src++) reload16(v3[src], mb + (size_t)src * 8 * WREG, miss);
            } while (__any_sync(0xffffffffu, miss) && ++it < SPIN / 16);
            if (lane < 4) mbar_arrive_cluster(rel_base + 8 * (1 + (lane >> 1)));
            sum8(at + 12, v3);
            add_pair(6); add_pair(7);
            load_wf(IC<WF0>{}, IC<WF1>{});
            uint2 cs[9];
#pragma unroll
            for (int k = 0; k < 9; k++) cs[k] = lds64(ta + SM_TC + (k < 8 ? (k >> 1) * 64 + (k & 1) * 4 : 256 - cw * 4) * 8);
            mbar_wait(bar_pre, 0);
            mbar_wait(bar_full + 24, 0);
#pragma unroll
            for (int src = 0; src < 8; src++) u4[src] = lds64(sb + 3 * SLOT + src * 2048 + (cw >> 1) * 512 + lane * 16 + (cw & 1) * 8);
#pragma unroll 1
            do {
                if (BO && miss) __nanosleep(BO);
                miss = 0;
#pragma unroll
                for (int src = 0; src < 8; src++) reload8(u4[src], mb4 + (size_t)src * 8 * WREG, miss);
            } while (__any_sync(0xffffffffu, miss) && ++it < SPIN / 16);
            float d[8] = {0.f, 0.f, 0.f, 0.f, 0.f, 0.f, 0.f, 0.f};
#pragma unroll
            for (int i = 0; i < 4; i++) mma16816(d + 4 * (i & 1), u4[2 * i].x, u4[2 * i].y, u4[2 * i + 1].x, u4[2 * i + 1].y, eye, eye);
            at[16] = pack_bf16(d[0] + d[4], d[1] + d[5]); at[17] = pack_bf16(d[2] + d[6], d[3] + d[7]);
            add_pair(8);
            DBG_G(123);
            const float2 ws = *reinterpret_cast<const float2*>(smem_raw + SM_TS);
            uint4* cdst = padd(g_cand, CFULL ? ((tid >> 1) * NCTA + rg) * 32 + (tid & 1) * 16 : (tid * NCTA + rg) * 32);
            uint32_t mean2;
            float dot;
            const float rsd = rows_stats(st, rec, cw, lane, mean2, dot);
            const uint32_t b = __float_as_uint(fmaf(fmaf(-bf_lo(mean2), ws.x, dot), rsd, ws.y));
            const uint32_t key = (((b & 0x80000000u) ? ~b : (b | 0x80000000u)) | 2047u) - (rg * 16 + l16);
            top2(key, k1, k2);
            if (tid < (CFULL + 1) * CREP) st_relaxed(cdst, k1, tag, k2, tag);
            cd = ld_relaxed64(candp);
            rows_normalise(h2, x1, mean2, rsd, lane, [&]() {
#pragma unroll
                for (int k = 0; k < 9; k++) gb[k] = lds32(sb + SM_TG + (cw * 8 + qd + (k < 8 ? (k >> 1) * 64 + (k & 1) * 4 : 256 - cw * 4)) * 4);
                if (WFE) load_wf(IC<WF1>{}, IC<WF2>{});
            });
#pragma unroll
            for (int k = 0; k < 18; k++) h2[k] = badd2(bmul2(h2[k], cs[k >> 1].x), cs[k >> 1].y);
            const uint32_t r1 = ~k1 & 15, r2 = ~k2 & 15;
            uint32_t todo = ((r1 & 7) == g8) | ((r2 & 7) == g8) << 1;
#pragma unroll 1
            while (todo) {
                const bool second = !(todo & 1), hi = (second ? r2 : r1) & 8;
                uint4* dst = padd(g_rows, ((rg * 2 + second) * RSLOT + cw * 24 + qd) * 16);
                uint32_t r[18];
#pragma unroll
                for (int k = 0; k < 9; k++) { r[k] = hi ? h2[2 * k + 1] : h2[2 * k]; r[9 + k] = hi ? x1[2 * k + 1] : x1[2 * k]; }
                fence_regs(r);
                st_relaxed(dst, r[0], r[1], r[2], r[3]);
                st_relaxed(dst + 8, r[4], r[5], r[6], r[7]);
                st_relaxed64(reinterpret_cast<uint2*>(padd(dst, 256 - qd * 8)), r[8], r[17]);
                st_relaxed(dst + 4, r[9], r[10], r[11], r[12]);
                st_relaxed(dst + 12, r[13], r[14], r[15], r[16]);
                todo &= todo - 1;
            }
            __syncwarp();

            stage_out();
            if (!WFE) load_wf(IC<WF1>{}, IC<WF2>{});
        }
        DBG_G(110);
        float4* part = reinterpret_cast<float4*>(smem_raw + 3 * SLOT + UNIT + 8192);
        bf16* act = reinterpret_cast<bf16*>(smem_raw + 3 * SLOT + UNIT + 4096);
        {
            uint32_t it = 0;
            const bool own = (tid >> 1) == rg;
            const uint32_t ks = sb + 3 * SLOT + UNIT + 5120;
#pragma unroll 1
            while (cd.y != tag && !own && ++it < SPIN / 16) cd = ld_relaxed64(candp);
            asm volatile("st.shared.u32 [%0], %1;" ::"r"(ks + tid * 4), "r"(own ? (tid & 1) ? k2 : k1 : cd.x) : "memory");
            bar_sync(3, 256);
            DBG_G(111);
            const uint4 a = lds128(ks + lane * 16), b = lds128(ks + 512 + lane * 16);
            const uint32_t a1 = max(a.x, a.z), a2 = __vimax3_u32(min(a.x, a.z), a.y, a.w);
            const uint32_t b1 = max(b.x, b.z), b2 = __vimax3_u32(min(b.x, b.z), b.y, b.w);
            const uint32_t c1 = max(a1, b1), c2 = __vimax3_u32(min(a1, b1), a2, b2);
            k1 = __reduce_max_sync(0xffffffffu, c1);
            k2 = __reduce_max_sync(0xffffffffu, c1 == k1 ? c2 : c1);
        }
        const int sel0 = ~k1 & 2047, sel1 = ~k2 & 2047;
        const uint32_t slot0 = (sel0 >> 4) * 2, slot1 = (sel1 >> 4) * 2 + ((sel0 ^ sel1) < 16);
        uint4 da[13];
        {
            const uint4* hp = padd(g_rows, (((g8 & 1) ? slot1 : slot0) * RSLOT + cw * 24 + qd) * 16);
            const uint2* hp2 = reinterpret_cast<const uint2*>(padd(hp, 256 - qd * 8));
            uint4 hv[2] = {ld_relaxed2(hp), ld_relaxed2(hp + 8)};
            uint2 hw = ld_relaxed64(hp2);
            if (tid == 255) {
                reinterpret_cast<int2*>(red)[8] = make_int2(sel0, sel1);
                mbar_arrive(bar_out);
            }
            load_wf(IC<WF2>{}, IC<23>{});
            mbar_wait(bar_full + 8, 1);
            mbar_wait(bar_full + 16, 1);
            auto load_d = [&](auto lo, auto hi) {
                const int r = (lane & 7) + (lane & 16) / 2;
                const uint32_t d0 = sb + SLOT + r * XP + cw * 144 + (lane & 8) * 2, d1 = d0 + (r < 2 ? 16 * XP : SLOT - 2 * XP);
                const uint32_t d2 = sb + 2 * SLOT + (14 + (lane & 3)) * XP + cw * 144 + (lane >> 3) * 16;
#pragma unroll
                for (int i = lo.value; i < hi.value; i++) da[i] = ldsm4t(i < 10 ? ((i & 1) ? d1 : d0) + (i >> 1) * 32 : d2 + (i - 10) * 64);
            };
            load_d(IC<0>{}, IC<DL>{});
            uint32_t it = 0, miss;
#pragma unroll 1
            do {
                miss = 0;
                reload16(hv[0], hp, miss);
                reload16(hv[1], hp + 8, miss);
                reload8(hw, hp2, miss);
            } while (__any_sync(0xffffffffu, miss) && ++it < SPIN / 16);
            DBG_G(112);
            load_d(IC<DL>{}, IC<13>{});
            float acc[20];
#pragma unroll
            for (int i = 0; i < 20; i++) acc[i] = 0.f;
#pragma unroll
            for (int i = 0; i < 5; i++) mma1688(acc + 4 * i, (i & 1) ? wf[20 + i / 2].z : wf[20 + i / 2].x, (i & 1) ? wf[20 + i / 2].w : wf[20 + i / 2].y, hw.x);
#pragma unroll
            for (int i = 0; i < 20; i++)
                mma16816(acc + 4 * (i % 5), wf[i].x, wf[i].y, wf[i].z, wf[i].w, (i / 5 & 1) ? hv[i / 10].z : hv[i / 10].x, (i / 5 & 1) ? hv[i / 10].w : hv[i / 10].y);
            if (qd == 0) {
#pragma unroll
                for (int i = 0; i < 5; i++) part[cw * 40 + i * 8 + g8] = make_float4(acc[4 * i], acc[4 * i + 1], acc[4 * i + 2], acc[4 * i + 3]);
            }
        }
        {
            uint2* dst = padd(g_ypart, ((cw * 9 * NCTA + blockIdx.x) * 8 + g8) * 8);
            bar_sync(3, 256);
            if (cw < 5) {
                const float* pp = reinterpret_cast<const float*>(part) + ((blockIdx.x & 1) << 4) + tid;
                const float g = rbf(((pp[0] + pp[160]) + (pp[320] + pp[480])) + ((pp[640] + pp[800]) + (pp[960] + pp[1120])));
                const float v = rbf(g * sigmoidf_(g)) * __shfl_down_sync(0xffffffffu, g, 2);
                if (!(tid & 2)) act[(tid & 1) * 56 + (tid >> 2)] = __float2bfloat16_rn(tid < 144 ? v : 0.f);
            }
            bar_sync(3, 256);
            DBG_G(113);
            const uint32_t ap = sb + 3 * SLOT + UNIT + 4096 + (lane & 1) * 112 + (lane >> 3) * 16;
            const uint4 b0 = ldsm4(ap);
            const uint32_t b1 = lds32(sb + 3 * SLOT + UNIT + 4096 + (g8 & 1) * 112 + 64 + qd * 4);
            float y[20];
#pragma unroll
            for (int i = 0; i < 20; i++) y[i] = 0.f;
#pragma unroll
            for (int i = 0; i < 5; i++) {
                mma16816(y + 4 * i, da[2 * i].x, da[2 * i].y, da[2 * i].z, da[2 * i].w, b0.x, b0.y);
                mma16816(y + 4 * i, da[2 * i + 1].x, da[2 * i + 1].y, da[2 * i + 1].z, da[2 * i + 1].w, b0.z, b0.w);
                mma1688(y + 4 * i, (i & 1) ? da[10 + i / 2].z : da[10 + i / 2].x, (i & 1) ? da[10 + i / 2].w : da[10 + i / 2].y, b1);
            }
#pragma unroll
            for (int i = 0; i < 9; i++)
                asm volatile("{\n.reg .pred p;\nsetp.eq.b32 p, %3, 0;\n@p st.relaxed.gpu.global.v2.f32 [%0], {%1, %2};\n}"
                             ::"l"(dst + i * (NCTA * 8)), "f"(y[2 * i]), "f"(y[2 * i + 1]), "r"(qd) : "memory");
        }
        DBG_G(114);
        if (blockIdx.x == 127 && tid == 0) gs->epoch[0] = tag;
        if (blockIdx.x < 72) {
            const int G = blockIdx.x, tok = g8 & 1, cp = G * 4 + qd;
            const uint2* src = padd(g_ypart, (blockIdx.x * NCTA * 8 + tid) * 8);
            const uint8_t* hsrc = reinterpret_cast<const uint8_t*>(padd(g_rows, (tok ? slot1 : slot0) * (RSLOT * 16) +
                (G < 64 ? (G >> 1 & 7) * 384 + (G >> 5) * 128 + qd * 16 + (G >> 1 & 8) + (G & 1) * 4 : (G - 64) * 384 + 256 + qd * 8)));
            const uint8_t* xsrc = hsrc + (G < 64 ? 64 : 4);
            uint32_t* dst = padd(reinterpret_cast<uint32_t*>(args.out), (tok ? sel1 : sel0) * (D_ * 2) + cp * 4);
            const uint32_t gb = reinterpret_cast<const uint32_t*>(smem_raw + SM_TG)[cp];
            const uint32_t ksel = ((tok ? k2 : k1) & ~2047u) | 1024u;
            const float sg = sigmoidf_(rbf(__uint_as_float((ksel & 0x80000000u) ? (ksel & 0x7fffffffu) : ~ksel)));
            uint2 v[4];
            uint32_t hv, xv, it = 0;
            bool miss;
#pragma unroll 1
            do {
#pragma unroll
                for (int i = 0; i < 4; i++) v[i] = ld_relaxed64(src + i * 256);
                hv = ld_relaxed32(hsrc);
                xv = ld_relaxed32(xsrc);
                miss = max(__vimax3_u32(v[0].x, v[1].x, v[2].x), __vimax3_u32(v[3].x, hv, xv)) == ~0u;
            } while (__any_sync(0xffffffffu, miss) && ++it < SPIN / 16);
            float y0 = (__uint_as_float(v[0].x) + __uint_as_float(v[1].x)) + (__uint_as_float(v[2].x) + __uint_as_float(v[3].x));
            float y1 = (__uint_as_float(v[0].y) + __uint_as_float(v[1].y)) + (__uint_as_float(v[2].y) + __uint_as_float(v[3].y));
            y0 += __shfl_xor_sync(0xffffffffu, y0, 8); y1 += __shfl_xor_sync(0xffffffffu, y1, 8);
            y0 += __shfl_xor_sync(0xffffffffu, y0, 16); y1 += __shfl_xor_sync(0xffffffffu, y1, 16);
            if (lane < 8) reinterpret_cast<float2*>(rec)[cw * 8 + lane] = make_float2(y0, y1);
            bar_sync(3, 256);
            if (cw == 0) {
                const float4 t0_ = rec[(lane >> 3) * 4 + qd], t1_ = rec[16 + (lane >> 3) * 4 + qd];
                y0 = tok ? t0_.y + t1_.y : t0_.x + t1_.x; y1 = tok ? t0_.w + t1_.w : t0_.z + t1_.z;
                y0 += __shfl_xor_sync(0xffffffffu, y0, 8); y1 += __shfl_xor_sync(0xffffffffu, y1, 8);
                y0 += __shfl_xor_sync(0xffffffffu, y0, 16); y1 += __shfl_xor_sync(0xffffffffu, y1, 16);
                const uint32_t y2 = bmul2(pack_bf16(y0, y1), pack_bf16(sg, sg));
                if (lane < 8) *dst = badd2(xv, bmul2(gb, badd2(hv, y2)));
            }
        }
        }
        DBG_T(88);
        DBG_G(121);
    }
}

typedef CUresult (*EncodeFn)(CUtensorMap*, CUtensorMapDataType, cuuint32_t, void*, const cuuint64_t*, const cuuint64_t*,
                             const cuuint32_t*, const cuuint32_t*, CUtensorMapInterleave, CUtensorMapSwizzle,
                             CUtensorMapL2promotion, CUtensorMapFloatOOBfill);

static void make_map(EncodeFn enc, CUtensorMap* m, const void* ptr, int rank, const cuuint64_t* dims,
                     const cuuint64_t* strides, const cuuint32_t* box, CUtensorMapSwizzle sw = CU_TENSOR_MAP_SWIZZLE_128B,
                     CUtensorMapDataType dt = CU_TENSOR_MAP_DATA_TYPE_BFLOAT16) {
    const cuuint32_t es[3] = {1, 1, 1};
    enc(m, dt, rank, const_cast<void*>(ptr), dims, strides, box, es,
        CU_TENSOR_MAP_INTERLEAVE_NONE, sw, CU_TENSOR_MAP_L2_PROMOTION_L2_128B,
        CU_TENSOR_MAP_FLOAT_OOB_FILL_NONE);
}

extern "C" void kernel_launch(void* const* d_in, const int* in_sizes, int n_in, void* d_out, int out_size) {
    const bf16* x = (const bf16*)d_in[0];
    const bf16* kc = (const bf16*)d_in[1];
    const bf16* vc = (const bf16*)d_in[2];
    const bf16* wq = (const bf16*)d_in[3];
    const bf16* wo = (const bf16*)d_in[4];
    const bf16* w_r = (const bf16*)d_in[6];
    const bf16* w_gate = (const bf16*)d_in[7];
    const bf16* w_up = (const bf16*)d_in[8];
    const bf16* w_down = (const bf16*)d_in[9];
    const bf16* cvec = (const bf16*)d_in[10];
    const bf16* w_mod = (const bf16*)d_in[11];
    bf16* out = (bf16*)d_out;

    void* fn = nullptr;
    cudaDriverEntryPointQueryResult qr;
    cudaGetDriverEntryPoint("cuTensorMapEncodeTiled", &fn, cudaEnableDefault, &qr);
    EncodeFn enc = (EncodeFn)fn;
    void* p_s;
    cudaGetSymbolAddress(&p_s, g_s);

    CUtensorMap tm_wq, tm_k, tm_v, tm_wo, tm_p, tm_x, tm_d, tm_g, tm_u;
    { cuuint64_t d[2] = {QD, D_}, s[1] = {QD * 2}; cuuint32_t b[2] = {64, 128}; make_map(enc, &tm_wq, wq, 2, d, s, b); }
    { cuuint64_t d[2] = {DH, HKV * S_}, s[1] = {DH * 2}; cuuint32_t b[2] = {64, 128};
      make_map(enc, &tm_k, kc, 2, d, s, b); make_map(enc, &tm_v, vc, 2, d, s, b); }
    { cuuint64_t d[2] = {D_, QD}, s[1] = {D_ * 2}; cuuint32_t b[2] = {64, 128}; make_map(enc, &tm_wo, wo, 2, d, s, b); }
    { cuuint64_t d[3] = {256, 160, NCTA}, s[2] = {1024, 8 * WREG}; cuuint32_t b[3] = {256, 2, 8};
      make_map(enc, &tm_p, ((Scratch*)p_s)->frag, 3, d, s, b, CU_TENSOR_MAP_SWIZZLE_NONE, CU_TENSOR_MAP_DATA_TYPE_UINT32); }
    { cuuint64_t d[2] = {D_ / 4, S_}, s[1] = {D_ * 2}; cuuint32_t b[2] = {XP / 8, 16};
      make_map(enc, &tm_x, x, 2, d, s, b, CU_TENSOR_MAP_SWIZZLE_NONE, CU_TENSOR_MAP_DATA_TYPE_UINT64); }
    { cuuint64_t d[2] = {D_ / 4, F_}, s[1] = {D_ * 2}; cuuint32_t b[2] = {XP / 8, 18};
      make_map(enc, &tm_d, w_down, 2, d, s, b, CU_TENSOR_MAP_SWIZZLE_NONE, CU_TENSOR_MAP_DATA_TYPE_UINT64); }
    { cuuint64_t d[2] = {F_, D_}, s[1] = {F_ * 2}; cuuint32_t b[2] = {40, 24};
      make_map(enc, &tm_g, w_gate, 2, d, s, b, CU_TENSOR_MAP_SWIZZLE_NONE); make_map(enc, &tm_u, w_up, 2, d, s, b, CU_TENSOR_MAP_SWIZZLE_NONE); }

    cudaFuncSetAttribute(fused_kernel<true>, cudaFuncAttributeMaxDynamicSharedMemorySize, SM_TOTAL);
    cudaFuncSetAttribute(fused_kernel<false>, cudaFuncAttributeMaxDynamicSharedMemorySize, SM_TOTAL);
    cudaLaunchConfig_t cfg = {};
    cfg.gridDim = NCTA + 4; cfg.blockDim = 384; cfg.dynamicSmemBytes = SM_TOTAL;
    cudaLaunchAttribute at;
    at.id = cudaLaunchAttributeClusterDimension; at.val.clusterDim.x = 2; at.val.clusterDim.y = 1; at.val.clusterDim.z = 1;
    cfg.attrs = &at; cfg.numAttrs = 1;
    int ncl = 0;
    if (cudaOccupancyMaxActiveClusters(&ncl, fused_kernel<true>, &cfg) != cudaSuccess) { ncl = 0; cudaGetLastError(); }
    Args args{w_mod, cvec, (Scratch*)p_s, desc_lo(0, UNIT) | (0x40000040ull << 32), out, x, kc, vc, wq, wo, w_r, w_down};
    if (USE_SPARE && ncl >= NCTA / 2 + 2)
        fused_kernel<true><<<NCTA + 4, 384, SM_TOTAL>>>(args, tm_wq, tm_k, tm_v, tm_wo, tm_p, tm_x, tm_d, tm_g, tm_u);
    else
        fused_kernel<false><<<NCTA, 384, SM_TOTAL>>>(args, tm_wq, tm_k, tm_v, tm_wo, tm_p, tm_x, tm_d, tm_g, tm_u);
}
```

```cpp
#include <cuda_runtime.h>
#include <cuda_bf16.h>
#include <cuda.h>
#include <stdint.h>
#include <math.h>

typedef __nv_bfloat16 bf16;

constexpr int S_ = 2048;
constexpr int D_ = 576;
constexpr int HQ = 32, HKV = 16, DH = 128;
constexpr int F_ = 4608;
constexpr int QD = HQ * DH;

constexpr int NCTA = 128;
constexpr int WREG = 5 * 4096;
constexpr int CREP = 8;
constexpr int RSLOT = 192;
constexpr int MREP = 4;
struct Scratch {
    unsigned int epoch[128];
    unsigned int flag_mod[NCTA];
    unsigned int flag_part[16 * 32];
    unsigned int flag_q3[16 * 32];
    unsigned int flag_h[NCTA * 32];
    uint2 mod1[MREP * D_];
    uint32_t mod2[4 * D_];
    uint4 cand[CREP * NCTA * 2];
    uint2 ypart[72 * NCTA * 8];
    uint4 h[2][NCTA * 36 * 32];
    uint4 q3[NCTA * 8 * 128];
    uint4 rows[NCTA * 2 * RSLOT];
    uint8_t frag[NCTA * 8 * WREG];
    uint8_t keep[NCTA * 8 * 4096];
};
__device__ __align__(1024) Scratch g_s;
#define g_h gs->h[tag & 1]
#define g_q3 gs->q3
#define g_keep gs->keep
#define g_flag_h gs->flag_h
#define g_flag_part gs->flag_part
#define g_flag_mod gs->flag_mod
#define g_flag_q3 gs->flag_q3
#define g_frag gs->frag
#define g_cand gs->cand
#define g_ypart gs->ypart
#define g_rows gs->rows

#define DBG_INIT()
#define DBG_P(i)
#define DBG_PG(i)
#define DBG_T(i)
#define DBG_G(i)

__device__ __forceinline__ uint32_t pack_bf16(float lo, float hi) {
    uint32_t r;
    asm("cvt.rn.bf16x2.f32 %0, %1, %2;" : "=r"(r) : "f"(hi), "f"(lo));
    return r;
}
__device__ __forceinline__ float rbf(float x) { return __uint_as_float(pack_bf16(0.f, x)); }
__device__ __forceinline__ float bf_lo(uint32_t v) { return __uint_as_float(v << 16); }
__device__ __forceinline__ float bf_hi(uint32_t v) { return __uint_as_float(v & 0xffff0000u); }
__device__ __forceinline__ float ex2(float x) {
    float y;
    asm("ex2.approx.ftz.f32 %0, %1;" : "=f"(y) : "f"(x));
    return y;
}
template <class T>
__device__ __forceinline__ T* padd(T* p, uint32_t off) {
    unsigned long long r;
    asm("{\n.reg .b32 l, h;\nmov.b64 {l, h}, %1;\nadd.cc.u32 l, l, %2;\naddc.u32 h, h, 0;\nmov.b64 %0, {l, h};\n}" : "=l"(r) : "l"(p), "r"(off));
    return reinterpret_cast<T*>(r);
}
__device__ __forceinline__ uint32_t smem_u32(const void* p) { return (uint32_t)__cvta_generic_to_shared(p); }
__device__ __forceinline__ void mbar_init(uint32_t bar, uint32_t cnt) {
    asm volatile("mbarrier.init.shared::cta.b64 [%0], %1;" ::"r"(bar), "r"(cnt) : "memory");
}
__device__ __forceinline__ void mbar_expect_tx(uint32_t bar, uint32_t bytes) {
    asm volatile("mbarrier.arrive.expect_tx.shared::cta.b64 _, [%0], %1;" ::"r"(bar), "r"(bytes) : "memory");
}
__device__ __forceinline__ void mbar_arrive(uint32_t bar) {
    asm volatile("mbarrier.arrive.shared::cta.b64 _, [%0];" ::"r"(bar) : "memory");
}
__device__ __forceinline__ void mbar_arrive_cluster(uint32_t cluster_addr) {
    asm volatile("mbarrier.arrive.shared::cluster.b64 _, [%0];" ::"r"(cluster_addr) : "memory");
}
constexpr uint32_t SPIN = 1u << 20;
__device__ __forceinline__ void mbar_wait(uint32_t bar, uint32_t parity) {
    asm volatile("{\n.reg .pred p;\n.reg .b32 c;\nmov.b32 c, 0;\n"
                 "W_%=:\nmbarrier.try_wait.parity.shared::cta.b64 p, [%0], %1;\n"
                 "add.u32 c, c, 1;\nsetp.lt.and.u32 p, c, 0x100000, !p;\n@p bra W_%=;\n}"
                 ::"r"(bar), "r"(parity) : "memory");
}
__device__ __forceinline__ void anchor(uint32_t addr, float v) {
    asm volatile("{\n.reg .pred p;\nsetp.lt.f32 p, %1, 0f00000000;\n@p st.volatile.shared.f32 [%0], %1;\n}" ::"r"(addr), "f"(v) : "memory");
}
__device__ __forceinline__ void anchor(uint32_t addr, uint32_t v) {
    asm volatile("{\n.reg .pred p;\nsetp.eq.u32 p, %1, 0xffffffff;\n@p st.volatile.shared.u32 [%0], %1;\n}" ::"r"(addr), "r"(v) : "memory");
}
__device__ __forceinline__ void anchor(void* p, uint32_t v) {
    asm volatile("{\n.reg .pred p;\nsetp.eq.u32 p, %1, 0xffffffff;\n@p st.volatile.u32 [%0], %1;\n}" ::"l"(p), "r"(v) : "memory");
}
__device__ __forceinline__ void hold(float& a, float& b) {
    asm volatile("{\n.reg .pred p;\n.reg .b64 t;\n.reg .b32 l, h;\nmov.u64 t, %%clock64;\nmov.b64 {l, h}, t;\nsetp.eq.u32 p, h, 0xffffffff;\n"
                 "@p mov.f32 %0, 0f00000000;\n@p mov.f32 %1, 0f00000000;\n}" : "+f"(a), "+f"(b) :: "memory");
}
__device__ __forceinline__ void mbar_wait_sleep(uint32_t bar, uint32_t parity) {
    asm volatile("{\n.reg .pred p;\n.reg .b32 c;\nmov.b32 c, 0;\n"
                 "W_%=:\nmbarrier.try_wait.parity.shared::cta.b64 p, [%0], %1, 5000;\n"
                 "add.u32 c, c, 1;\nsetp.lt.and.u32 p, c, 0x20000, !p;\n@p bra W_%=;\n}"
                 ::"r"(bar), "r"(parity) : "memory");
}
__device__ __forceinline__ uint32_t load_tag(const Scratch* gs) {
    uint32_t tag;
    asm volatile("ld.global.ca.u32 %0, [%1];" : "=r"(tag) : "l"(gs->epoch) : "memory");
    return tag + 1;
}
__device__ __forceinline__ uint4 ld_relaxed(const uint4* p) {
    uint4 v;
    asm volatile("ld.relaxed.gpu.global.v4.u32 {%0,%1,%2,%3}, [%4];" : "=r"(v.x), "=r"(v.y), "=r"(v.z), "=r"(v.w) : "l"(p) : "memory");
    return v;
}
__device__ __forceinline__ void st_relaxed(uint4* p, uint32_t a, uint32_t b, uint32_t c, uint32_t d) {
    asm volatile("{\n.reg .b64 u, v;\nmov.b64 u, {%1, %2};\nmov.b64 v, {%3, %4};\nst.relaxed.gpu.global.v2.b64 [%0], {u, v};\n}"
                 ::"l"(p), "r"(a), "r"(b), "r"(c), "r"(d) : "memory");
}
__device__ __forceinline__ void st_relaxed4(void* p, uint32_t a, uint32_t b, uint32_t c, uint32_t d) {
    asm volatile("st.relaxed.gpu.global.v4.u32 [%0], {%1, %2, %3, %4};" ::"l"(p), "r"(a), "r"(b), "r"(c), "r"(d) : "memory");
}
__device__ __forceinline__ uint2 ld_relaxed8(const void* p) {
    uint2 v;
    asm volatile("ld.relaxed.gpu.global.v2.u32 {%0,%1}, [%2];" : "=r"(v.x), "=r"(v.y) : "l"(p) : "memory");
    return v;
}
__device__ __forceinline__ uint2 ld_relaxed64(const uint2* p) {
    uint2 v;
    asm volatile("{\n.reg .b64 u;\nld.relaxed.gpu.global.b64 u, [%2];\nmov.b64 {%0, %1}, u;\n}" : "=r"(v.x), "=r"(v.y) : "l"(p) : "memory");
    return v;
}
__device__ __forceinline__ void st_relaxed64(uint2* p, uint32_t a, uint32_t b) {
    asm volatile("{\n.reg .b64 u;\nmov.b64 u, {%1, %2};\nst.relaxed.gpu.global.b64 [%0], u;\n}" ::"l"(p), "r"(a), "r"(b) : "memory");
}
__device__ __forceinline__ uint4 ld_relaxed2(const uint4* p) {
    uint4 v;
    asm volatile("{\n.reg .b64 u, w;\nld.relaxed.gpu.global.v2.b64 {u, w}, [%4];\nmov.b64 {%0, %1}, u;\nmov.b64 {%2, %3}, w;\n}"
                 : "=r"(v.x), "=r"(v.y), "=r"(v.z), "=r"(v.w) : "l"(p) : "memory");
    return v;
}
__device__ __forceinline__ void reload16(uint4& v, const void* p, uint32_t& miss) {
    asm volatile("{\n.reg .pred p;\n.reg .b32 m;\n.reg .b64 u, w;\nmax.u32 m, %0, %2;\nsetp.eq.u32 p, m, 0xffffffff;\n"
                 "mov.b64 u, {%0, %1};\nmov.b64 w, {%2, %3};\n@p ld.relaxed.gpu.global.v2.b64 {u, w}, [%5];\n"
                 "mov.b64 {%0, %1}, u;\nmov.b64 {%2, %3}, w;\n@p mov.u32 %4, 1;\n}"
                 : "+r"(v.x), "+r"(v.y), "+r"(v.z), "+r"(v.w), "+r"(miss) : "l"(p) : "memory");
}
__device__ __forceinline__ void reload8(uint2& v, const void* p, uint32_t& miss) {
    asm volatile("{\n.reg .pred p;\n.reg .b64 u;\nsetp.eq.u32 p, %0, 0xffffffff;\nmov.b64 u, {%0, %1};\n"
                 "@p ld.relaxed.gpu.global.b64 u, [%3];\nmov.b64 {%0, %1}, u;\n@p mov.u32 %2, 1;\n}"
                 : "+r"(v.x), "+r"(v.y), "+r"(miss) : "l"(p) : "memory");
}
__device__ __forceinline__ uint32_t ld_relaxed32(const void* p) {
    uint32_t v;
    asm volatile("ld.relaxed.gpu.global.u32 %0, [%1];" : "=r"(v) : "l"(p) : "memory");
    return v;
}
__device__ __forceinline__ void flag_wait(const unsigned int* p, uint32_t tag) {
    uint32_t v, it = 0;
#pragma unroll 1
    do {
        asm volatile("ld.relaxed.gpu.global.u32 %0, [%1];" : "=r"(v) : "l"(p) : "memory");
    } while (__any_sync(0xffffffffu, v != tag) && ++it < SPIN / 16);
    asm volatile("fence.acquire.gpu;" ::: "memory");
    __syncwarp();
}
__device__ __forceinline__ bool elect() {
    uint32_t p;
    asm volatile("{\n.reg .pred p;\nelect.sync _|p, 0xffffffff;\nselp.u32 %0, 1, 0, p;\n}" : "=r"(p));
    return p;
}
__device__ __forceinline__ void flag_release(unsigned int* p, uint32_t tag) {
    asm volatile("st.release.gpu.global.u32 [%0], %1;" ::"l"(p), "r"(tag) : "memory");
}
__device__ __forceinline__ uint32_t touch(const void* p) {
    uint32_t v;
    asm volatile("ld.global.nc.L1::no_allocate.L2::128B.u32 %0, [%1];" : "=r"(v) : "l"(p));
    return v;
}
__device__ __forceinline__ void bar_sync(int id, int n) { asm volatile("bar.sync %0, %1;" ::"r"(id), "r"(n) : "memory"); }
__device__ __forceinline__ void bar_arrive(int id, int n) { asm volatile("bar.arrive %0, %1;" ::"r"(id), "r"(n) : "memory"); }

constexpr uint64_t EVICT_NORMAL = 0x1000000000000000ull, EVICT_FIRST = 0x12F0000000000000ull;
__device__ __forceinline__ void tma2d(uint32_t dst, const CUtensorMap* m, int c0, int c1, uint32_t bar) {
    asm volatile("cp.async.bulk.tensor.2d.shared::cluster.global.mbarrier::complete_tx::bytes.L2::cache_hint [%0], [%1, {%3, %4}], [%2], %5;"
                 ::"r"(dst), "l"(m), "r"(bar), "r"(c0), "r"(c1), "l"(EVICT_FIRST) : "memory");
}
__device__ __forceinline__ void tma2d_mc(uint32_t dst, const CUtensorMap* m, int c0, int c1, uint32_t bar, uint64_t pol) {
    asm volatile("cp.async.bulk.tensor.2d.shared::cluster.global.mbarrier::complete_tx::bytes.multicast::cluster.L2::cache_hint [%0], [%1, {%3, %4}], [%2], %5, %6;"
                 ::"r"(dst), "l"(m), "r"(bar), "r"(c0), "r"(c1), "h"((uint16_t)3), "l"(pol) : "memory");
}
__device__ __forceinline__ void tma3d(uint32_t dst, const CUtensorMap* m, int c0, int c1, int c2, uint32_t bar) {
    asm volatile("cp.async.bulk.tensor.3d.shared::cluster.global.mbarrier::complete_tx::bytes.L2::cache_hint [%0], [%1, {%3, %4, %5}], [%2], %6;"
                 ::"r"(dst), "l"(m), "r"(bar), "r"(c0), "r"(c1), "r"(c2), "l"(EVICT_FIRST) : "memory");
}
__device__ __forceinline__ void bulk_load(uint32_t dst, const void* src, uint32_t bytes, uint32_t bar) {
    asm volatile("cp.async.bulk.shared::cluster.global.mbarrier::complete_tx::bytes [%0], [%1], %2, [%3];"
                 ::"r"(dst), "l"(src), "r"(bytes), "r"(bar) : "memory");
}
__device__ __forceinline__ void l2_prefetch(const void* src, uint32_t bytes) {
    asm volatile("cp.async.bulk.prefetch.L2.global [%0], %1;" ::"l"(src), "r"(bytes) : "memory");
}
__device__ __forceinline__ uint32_t bmul2(uint32_t a, uint32_t b) { uint32_t r; asm("mul.rn.bf16x2 %0, %1, %2;" : "=r"(r) : "r"(a), "r"(b)); return r; }
__device__ __forceinline__ uint32_t badd2(uint32_t a, uint32_t b) { uint32_t r; asm("add.rn.bf16x2 %0, %1, %2;" : "=r"(r) : "r"(a), "r"(b)); return r; }
__device__ __forceinline__ uint32_t bsub2(uint32_t a, uint32_t b) { uint32_t r; asm("sub.rn.bf16x2 %0, %1, %2;" : "=r"(r) : "r"(a), "r"(b)); return r; }
__device__ __forceinline__ uint32_t bmax2(uint32_t a, uint32_t b) { uint32_t r; asm("max.bf16x2 %0, %1, %2;" : "=r"(r) : "r"(a), "r"(b)); return r; }
__device__ __forceinline__ uint32_t bfma2(uint32_t a, uint32_t b, uint32_t c) { uint32_t r; asm("fma.rn.bf16x2 %0, %1, %2, %3;" : "=r"(r) : "r"(a), "r"(b), "r"(c)); return r; }
__device__ __forceinline__ uint4 lds128(uint32_t a) { uint4 v; asm volatile("ld.shared.v4.u32 {%0,%1,%2,%3}, [%4];" : "=r"(v.x), "=r"(v.y), "=r"(v.z), "=r"(v.w) : "r"(a) : "memory"); return v; }
__device__ __forceinline__ uint2 lds64(uint32_t a) { uint2 v; asm volatile("ld.shared.v2.u32 {%0,%1}, [%2];" : "=r"(v.x), "=r"(v.y) : "r"(a) : "memory"); return v; }
__device__ __forceinline__ uint32_t lds32(uint32_t a) { uint32_t v; asm volatile("ld.shared.u32 %0, [%1];" : "=r"(v) : "r"(a) : "memory"); return v; }
__device__ __forceinline__ uint4 ldsm4(uint32_t a) {
    uint4 v;
    asm volatile("ldmatrix.sync.aligned.m8n8.x4.shared.b16 {%0,%1,%2,%3}, [%4];" : "=r"(v.x), "=r"(v.y), "=r"(v.z), "=r"(v.w) : "r"(a) : "memory");
    return v;
}
__device__ __forceinline__ uint4 ldsm4t(uint32_t a) {
    uint4 v;
    asm volatile("ldmatrix.sync.aligned.m8n8.x4.trans.shared.b16 {%0,%1,%2,%3}, [%4];" : "=r"(v.x), "=r"(v.y), "=r"(v.z), "=r"(v.w) : "r"(a) : "memory");
    return v;
}
__device__ __forceinline__ void mma1688(float* d, uint32_t a0, uint32_t a1, uint32_t b) {
    asm("mma.sync.aligned.m16n8k8.row.col.f32.bf16.bf16.f32 {%0,%1,%2,%3}, {%4,%5}, {%6}, {%0,%1,%2,%3};"
        : "+f"(d[0]), "+f"(d[1]), "+f"(d[2]), "+f"(d[3]) : "r"(a0), "r"(a1), "r"(b));
}
__device__ __forceinline__ void mma16816(float* d, uint32_t a0, uint32_t a1, uint32_t a2, uint32_t a3, uint32_t b0, uint32_t b1) {
    asm("mma.sync.aligned.m16n8k16.row.col.f32.bf16.bf16.f32 {%0,%1,%2,%3}, {%4,%5,%6,%7}, {%8,%9}, {%0,%1,%2,%3};"
                 : "+f"(d[0]), "+f"(d[1]), "+f"(d[2]), "+f"(d[3]) : "r"(a0), "r"(a1), "r"(a2), "r"(a3), "r"(b0), "r"(b1));
}
__device__ __forceinline__ void stsm_x4(uint32_t addr, uint32_t a, uint32_t b, uint32_t c, uint32_t d) {
    asm volatile("stmatrix.sync.aligned.m8n8.x4.shared.b16 [%0], {%1, %2, %3, %4};"
                 ::"r"(addr), "r"(a), "r"(b), "r"(c), "r"(d) : "memory");
}

__device__ __forceinline__ uint64_t mkdesc(uint32_t addr, uint32_t lbo, uint32_t sbo) {
    return (uint64_t)((addr & 0x3FFFF) >> 4) | ((uint64_t)(lbo >> 4) << 16) | ((uint64_t)(sbo >> 4) << 32) | (1ull << 62);
}
constexpr uint32_t SM0 = 1024;
__host__ __device__ constexpr uint32_t desc_lo(uint32_t off, uint32_t lbo) { return ((SM0 + off) >> 4) | ((lbo >> 4) << 16); }
#define WG_FENCE() asm volatile("wgmma.fence.sync.aligned;" ::: "memory")
#define WG_COMMIT() asm volatile("wgmma.commit_group.sync.aligned;" ::: "memory")
#define WG_WAIT(n) asm volatile("wgmma.wait_group.sync.aligned %0;" ::"n"(n) : "memory")

#define F8(a, i) "+f"(a[i]), "+f"(a[i + 1]), "+f"(a[i + 2]), "+f"(a[i + 3]), "+f"(a[i + 4]), "+f"(a[i + 5]), "+f"(a[i + 6]), "+f"(a[i + 7])
#define F16(a, i) F8(a, i), F8(a, i + 8)
#define F64(a) F16(a, 0), F16(a, 16), F16(a, 32), F16(a, 48)
#define F32(a) F16(a, 0), F16(a, 16)
#define L64 "%0,%1,%2,%3,%4,%5,%6,%7,%8,%9,%10,%11,%12,%13,%14,%15,%16,%17,%18,%19,%20,%21,%22,%23,%24,%25,%26,%27,%28,%29,%30,%31,%32,%33,%34,%35,%36,%37,%38,%39,%40,%41,%42,%43,%44,%45,%46,%47,%48,%49,%50,%51,%52,%53,%54,%55,%56,%57,%58,%59,%60,%61,%62,%63"
#define L32 "%0,%1,%2,%3,%4,%5,%6,%7,%8,%9,%10,%11,%12,%13,%14,%15,%16,%17,%18,%19,%20,%21,%22,%23,%24,%25,%26,%27,%28,%29,%30,%31"

template <int TB, int STEP = 128>
__device__ __forceinline__ void mma_rs128(float (&d)[64], uint32_t a0, uint32_t a1, uint32_t a2, uint32_t a3, uint64_t& b, int acc) {
    asm volatile("{\n.reg .pred p;\nsetp.ne.b32 p, %69, 0;\n"
                 "wgmma.mma_async.sync.aligned.m64n128k16.f32.bf16.bf16 {" L64 "}, {%65,%66,%67,%68}, %64, p, 1, 1, %70;\nadd.s64 %64, %64, %71;\n}"
                 : F64(d), "+l"(b) : "r"(a0), "r"(a1), "r"(a2), "r"(a3), "r"(acc), "n"(TB), "n"(STEP));
}
template <int TB>
__device__ __forceinline__ void mma_rs64(float (&d)[32], uint32_t a0, uint32_t a1, uint32_t a2, uint32_t a3, uint64_t& b, int acc) {
    asm volatile("{\n.reg .pred p;\nsetp.ne.b32 p, %37, 0;\n"
                 "wgmma.mma_async.sync.aligned.m64n64k16.f32.bf16.bf16 {" L32 "}, {%33,%34,%35,%36}, %32, p, 1, 1, %38;\nadd.s64 %32, %32, 128;\n}"
                 : F32(d), "+l"(b) : "r"(a0), "r"(a1), "r"(a2), "r"(a3), "r"(acc), "n"(TB));
}
template <int N>
__device__ __forceinline__ void fence_regs(float (&d)[N]) {
#pragma unroll
    for (int i = 0; i < N; i++) asm volatile("" : "+f"(d[i])::"memory");
}
template <int N>
__device__ __forceinline__ void fence_regs(uint32_t (&d)[N]) {
#pragma unroll
    for (int i = 0; i < N; i++) asm volatile("" : "+r"(d[i])::"memory");
}

template <int V> struct IC { static constexpr int value = V; };

constexpr int SLOT = 32768, UNIT = 16384;
constexpr int SM_Q = 4 * SLOT;
constexpr int SM_BAR = 7 * SLOT;
constexpr int SM_RED = SM_BAR + 512;
constexpr int SM_TOTAL = SM_BAR + 3072;
constexpr int XP = D_ * 2 + 16;
constexpr int M_MOD = 16 * XP;
constexpr int SM_T = SM_Q + 2 * D_ * 80, SM_TC = SM_T + D_ * 4, SM_TG = SM_TC + D_ * 4, SM_TS = SM_TG + D_ * 2;
constexpr float CS = 0.08838834764831845f * 1.4426950408889634f;
#define LMAX 0.5f
#define LMIN 0x1p-104f
#define USE_SPARE 1
#define MAXG 1
#define SPLIT 10
#define ESPLIT 3
#define PV1 8
#define RW 2
#define HW 2
#define HW2 1
#define XDELAY 200
#define QDELAY 300
#define TMPF 1
#define PFD0 2000
#define PFD1 400
#define HDELAY 300
#define RA 10
#define RB 2
#define RPE 2
#define OSPLIT 6
#define HOLD 1
#define DL 6
#define O2F 0
#define A2N 4
#define OPF 0
#define PS 2
#define QSPLIT 4
#define QT0 4
#define HE 1
#define STAGE 11
#define POFF 102.f
#define WF0 3
#define WF1 13
#define C3D 0
#define C4D 300
#define DD 300
#define P2E 0
#define BO 0
#define MAP 2
#define CFULL 0
#define WFE 1
#define OUTD 0
#define OUTPOL EVICT_FIRST
#define WF2 19
constexpr int PF_KV = 8, PF_WO = 120;

__device__ __forceinline__ int cluster_role() {
    int k;
    asm volatile("mov.u32 %0, %%ctaid.x;" : "=r"(k));
    k >>= 1;
    if (MAP == 0) return k & 63;
    if (MAP == 1) return (k & 7) * 8 + ((k >> 3) & 7);
    if (MAP == 3) {
        asm("mov.u32 %0, %%smid;" : "=r"(k));
        k >>= 1;
        const int r = ((k - 32) * 37) >> 8;
        return k < 32 ? (k & 7) * 8 + (k >> 3) : k < 60 ? (k - 31 - r * 7) * 8 + 4 + r : (k - 58) & 7;
    }
    const int r = ((k - 36) * 37) >> 8, i = k - 36 - r * 7;
    if (MAP == 4) return k < 4 ? 4 + k : k < 36 ? ((k - 4) & 7) * 8 + ((k - 4) >> 3) : (i + 1) * 8 + ((4 + r) & 7);
    return k < 4 ? 12 + k : k < 36 ? ((k - 4) & 7) * 8 + ((k - 4) >> 3) : (i + (i > 0)) * 8 + ((4 + r) & 7);
}

struct Args {
    const bf16 *w_mod, *cvec;
    Scratch* gs;
    uint64_t d0;
    bf16* out;
    const bf16 *x, *kc, *vc, *wq, *wo, *w_r, *w_down;
};

__device__ __forceinline__ void frag_store(uint8_t* p, const uint32_t (&a)[32]) {
#pragma unroll
    for (int i = 0; i < 8; i++)
        __stcg(reinterpret_cast<uint4*>(p + i * 512), make_uint4(a[4 * i], a[4 * i + 1], a[4 * i + 2], a[4 * i + 3]));
}
template <int LO = 0, int HI = 8>
__device__ __forceinline__ void frag_load(uint32_t (&a)[32], const uint8_t* p) {
#pragma unroll
    for (int i = LO; i < HI; i++) {
        const uint4 v = ld_relaxed(reinterpret_cast<const uint4*>(p + i * 512));
        a[4 * i] = v.x; a[4 * i + 1] = v.y; a[4 * i + 2] = v.z; a[4 * i + 3] = v.w;
    }
}
__device__ __forceinline__ float quad_sum(float v) {
    v += __shfl_xor_sync(0xffffffffu, v, 1);
    return v + __shfl_xor_sync(0xffffffffu, v, 2);
}
__device__ __forceinline__ float quad_max(float v) {
    v = fmaxf(v, __shfl_xor_sync(0xffffffffu, v, 1));
    return fmaxf(v, __shfl_xor_sync(0xffffffffu, v, 2));
}
__device__ __forceinline__ float rcp_fast(float x) { float y; asm("rcp.approx.ftz.f32 %0, %1;" : "=f"(y) : "f"(x)); return y; }
__device__ __forceinline__ float sigmoidf_(float x) { return rcp_fast(1.f + ex2(-1.4426950408889634f * x)); }
__device__ __forceinline__ void top2(uint32_t k, uint32_t& k1, uint32_t& k2) {
    k1 = __reduce_max_sync(0xffffffffu, k);
    k2 = __reduce_max_sync(0xffffffffu, k == k1 ? 0 : k);
}

__device__ __forceinline__ void mod_fma(float (&a)[8], const uint4 w, float sc) {
    a[0] += sc * bf_lo(w.x); a[1] += sc * bf_hi(w.x); a[2] += sc * bf_lo(w.y); a[3] += sc * bf_hi(w.y);
    a[4] += sc * bf_lo(w.z); a[5] += sc * bf_hi(w.z); a[6] += sc * bf_lo(w.w); a[7] += sc * bf_hi(w.w);
}
__device__ __forceinline__ float mod_reduce(float (&a)[8], int lane) {
#pragma unroll
    for (int h = 4; h > 0; h >>= 1) {
        const bool up = lane & (8 / h);
#pragma unroll
        for (int i = 0; i < h; i++)
            a[i] = (up ? a[i + h] : a[i]) + __shfl_xor_sync(0xffffffffu, up ? a[i] : a[i + h], 8 / h);
    }
    return a[0] + __shfl_xor_sync(0xffffffffu, a[0], 16);
}

__device__ __forceinline__ float ln_stats(float sum, float sq, uint32_t& mean2) {
    const float mean = sum * (1.f / D_);
    const float var = fmaxf(fmaf(-mean, mean, sq * (1.f / D_)), 0.f);
    float sd;
    asm("sqrt.approx.ftz.f32 %0, %1;" : "=f"(sd) : "f"(rbf(rbf(var) + 1e-5f)));
    mean2 = pack_bf16(mean, mean);
    return rcp_fast(rbf(sd));
}
__device__ __forceinline__ uint32_t ln_pair(uint32_t x, uint32_t mean2, float rsd) {
    const uint32_t d = bsub2(x, mean2);
    return pack_bf16(bf_lo(d) * rsd, bf_hi(d) * rsd);
}
__device__ __forceinline__ void rows_load(uint32_t (&x)[20], uint32_t xs, int cw) {
#pragma unroll
    for (int ch = 0; ch < 5; ch++) {
        const uint4 v = ldsm4(ch < 4 ? xs + ch * 256 : xs + 1024 - cw * 16);
        x[4 * ch] = v.x; x[4 * ch + 1] = v.y; x[4 * ch + 2] = v.z; x[4 * ch + 3] = v.w;
    }
}
__device__ __forceinline__ void stats_add(float (&st)[12], uint32_t a, uint32_t b, uint32_t w) {
    mma1688(st, a, b, w);
    mma1688(st + 4, a, b, a);
    mma1688(st + 8, a, b, b);
}
__device__ __forceinline__ float rows_stats(const float (&st)[12], float4* rec, int cw, int lane, uint32_t& mean2, float& dot) {
    const int g8 = lane >> 2;
    if ((g8 >> 1) == (lane & 3)) {
        rec[cw * 16 + g8] = make_float4(st[0], (g8 & 1) ? st[5] : st[4], st[1], 0.f);
        rec[cw * 16 + 8 + g8] = make_float4(st[2], (g8 & 1) ? st[11] : st[10], st[3], 0.f);
    }
    bar_sync(3, 256);
    const float4* r = rec + (lane >> 4) * 64 + (lane & 15);
    const float4 s0 = r[0], s1 = r[16], s2 = r[32], s3 = r[48];
    const float sum = (s0.x + s1.x) + (s2.x + s3.x), sq = (s0.y + s1.y) + (s2.y + s3.y);
    dot = (s0.z + s1.z) + (s2.z + s3.z);
    dot += __shfl_xor_sync(0xffffffffu, dot, 16);
    return ln_stats(sum + __shfl_xor_sync(0xffffffffu, sum, 16), sq + __shfl_xor_sync(0xffffffffu, sq, 16), mean2);
}
template <class F>
__device__ __forceinline__ void rows_normalise(uint32_t* y, const uint32_t* x, uint32_t mean2, float rsd, int lane, F loads) {
    const int g8 = lane >> 2;
    const uint32_t ma2 = __shfl_sync(0xffffffffu, mean2, g8), mb2 = __shfl_sync(0xffffffffu, mean2, g8 + 8);
    const float ra = __shfl_sync(0xffffffffu, rsd, g8), rb = __shfl_sync(0xffffffffu, rsd, g8 + 8);
    loads();
#pragma unroll
    for (int k = 0; k < 9; k++) { y[2 * k] = ln_pair(x[2 * k], ma2, ra); y[2 * k + 1] = ln_pair(x[2 * k + 1], mb2, rb); }
}

__device__ __forceinline__ uint4 h_frag(const uint4* hf, int ks, int lane) {
    if (ks < 32) return ld_relaxed2(hf + ks * 32);
    const uint2* p = reinterpret_cast<const uint2*>(padd(hf, 256 - lane * 8) + ks * 32 - 16);
    const uint2 a = ld_relaxed64(p), b = ld_relaxed64(p + 32);
    return make_uint4(a.x, a.y, b.x, b.y);
}

__device__ __noinline__ void attn_fallback(uint32_t bad, uint32_t tag, const Scratch* gs, uint8_t* frag, uint8_t* keep, const bf16* wq, const bf16* kc, const bf16* vc) {
  const int lane = threadIdx.x & 31, g8 = lane >> 2, qd = lane & 3;
  const int role = cluster_role(), j = role & 7, qb = (role >> 3) * 2 + (blockIdx.x & 1);
  const uint4* hf = g_h + (size_t)(qb * 8 + (threadIdx.x >> 5) - 4) * (36 * 32) + lane;
#pragma unroll 1
  for (int t = 0; t < 4; t++) {
    if (!((bad >> t) & 1)) continue;
    const bf16 *wqp = wq + (4 * j + t) * DH, *kp = kc + (size_t)(2 * j + (t >> 1)) * S_ * DH, *vp = vc + (size_t)(2 * j + (t >> 1)) * S_ * DH;
    uint32_t q[32];
    float o[64];
#pragma unroll
    for (int i = 0; i < 64; i++) o[i] = 0.f;
#pragma unroll 1
    for (int ks = 0; ks < 36; ks++) {
        const uint4 a = h_frag(hf, ks, lane);
        const unsigned short* wr = reinterpret_cast<const unsigned short*>(wqp + (size_t)(ks * 16 + 2 * qd) * QD + g8);
#pragma unroll
        for (int dt = 0; dt < 16; dt++) {
            const uint32_t b0 = __ldg(wr + dt * 8) | ((uint32_t)__ldg(wr + dt * 8 + QD) << 16);
            const uint32_t b1 = __ldg(wr + dt * 8 + 8 * QD) | ((uint32_t)__ldg(wr + dt * 8 + 9 * QD) << 16);
            mma16816(o + 4 * dt, a.x, a.y, a.z, a.w, b0, b1);
        }
    }
#pragma unroll
    for (int i = 0; i < 32; i++) q[i] = pack_bf16(o[2 * i], o[2 * i + 1]);
#pragma unroll
    for (int i = 0; i < 64; i++) o[i] = 0.f;
    float m0 = -INFINITY, m1 = -INFINITY, l0 = 0.f, l1 = 0.f;
#pragma unroll 1
    for (int key = 0; key < S_; key += 16) {
        float sc[8];
#pragma unroll
        for (int i = 0; i < 8; i++) sc[i] = 0.f;
#pragma unroll
        for (int nt = 0; nt < 2; nt++) {
            const uint32_t* kr = reinterpret_cast<const uint32_t*>(kp + (size_t)(key + nt * 8 + g8) * DH) + qd;
#pragma unroll
            for (int ks = 0; ks < 8; ks++)
                mma16816(sc + 4 * nt, q[4 * ks], q[4 * ks + 1], q[4 * ks + 2], q[4 * ks + 3], __ldg(kr + ks * 8), __ldg(kr + ks * 8 + 4));
        }
        const float n0 = quad_max(fmaxf(fmaxf(m0, fmaxf(sc[0], sc[1])), fmaxf(sc[4], sc[5])));
        const float n1 = quad_max(fmaxf(fmaxf(m1, fmaxf(sc[2], sc[3])), fmaxf(sc[6], sc[7])));
        const float f0 = ex2((m0 - n0) * CS), f1 = ex2((m1 - n1) * CS);
        m0 = n0; m1 = n1;
#pragma unroll
        for (int i = 0; i < 8; i++) sc[i] = ex2((sc[i] - ((i & 2) ? n1 : n0)) * CS);
        l0 = l0 * f0 + (sc[0] + sc[1]) + (sc[4] + sc[5]);
        l1 = l1 * f1 + (sc[2] + sc[3]) + (sc[6] + sc[7]);
        const uint32_t e0 = pack_bf16(sc[0], sc[1]), e1 = pack_bf16(sc[2], sc[3]), e2 = pack_bf16(sc[4], sc[5]), e3 = pack_bf16(sc[6], sc[7]);
        const unsigned short* vr = reinterpret_cast<const unsigned short*>(vp + (size_t)(key + 2 * qd) * DH + g8);
#pragma unroll
        for (int dt = 0; dt < 16; dt++) {
            o[4 * dt] *= f0; o[4 * dt + 1] *= f0; o[4 * dt + 2] *= f1; o[4 * dt + 3] *= f1;
            const uint32_t b0 = __ldg(vr + dt * 8) | ((uint32_t)__ldg(vr + dt * 8 + DH) << 16);
            const uint32_t b1 = __ldg(vr + dt * 8 + 8 * DH) | ((uint32_t)__ldg(vr + dt * 8 + 9 * DH) << 16);
            mma16816(o + 4 * dt, e0, e1, e2, e3, b0, b1);
        }
    }
    const float i0 = 1.f / quad_sum(l0), i1 = 1.f / quad_sum(l1);
#pragma unroll
    for (int i = 0; i < 16; i++) {
        q[2 * i] = pack_bf16(o[4 * i] * i0, o[4 * i + 1] * i0);
        q[2 * i + 1] = pack_bf16(o[4 * i + 2] * i1, o[4 * i + 3] * i1);
    }
    frag_store(t < 3 ? frag + t * 4096 : keep, q);
  }
}

__device__ __forceinline__ void spare_q3(Scratch* gs, uint32_t sb, uint32_t bar_full, uint32_t bar_empty, int lane, int cw) {
    const uint32_t tag = load_tag(gs);
    uint32_t rel_base, e = 3;
    asm("mapa.shared::cluster.u32 %0, %1, %2;" : "=r"(rel_base) : "r"(bar_empty), "r"(lane & 1));
#pragma unroll 1
    for (int qb = blockIdx.x - NCTA; qb < 16; qb += 4) {
        uint32_t h[144];
        float o[64];
        flag_wait(&g_flag_h[(qb * 8 + cw) * 32], tag);
        const uint4* hf = g_h + (size_t)(qb * 8 + cw) * (36 * 32) + lane;
#pragma unroll
        for (int ks = 0; ks < 36; ks++) {
            const uint4 v = h_frag(hf, ks, lane);
            h[4 * ks] = v.x; h[4 * ks + 1] = v.y; h[4 * ks + 2] = v.z; h[4 * ks + 3] = v.w;
        }
#pragma unroll
        for (int i = 0; i < 64; i++) o[i] = 0.f;
#pragma unroll 1
        for (int v = 0; v < 4; v++) {
            fence_regs(o);
#pragma unroll
            for (int t = 0; t < 5; t++) {
                mbar_wait(bar_full + 8 * (e & 3), (e >> 2) & 1);
                uint64_t dv = mkdesc(sb + (e & 3) * SLOT, UNIT, 1024);
                WG_FENCE();
#pragma unroll
                for (int ks = 0; ks < (t < 4 ? 8 : 4); ks++)
                    mma_rs128<1>(o, h[32 * t + 4 * ks], h[32 * t + 4 * ks + 1], h[32 * t + 4 * ks + 2], h[32 * t + 4 * ks + 3], dv, ks | t);
                WG_COMMIT();
                if (t > 0) { WG_WAIT(1); if (lane < 2) mbar_arrive_cluster(rel_base + 8 * ((e - 1) & 3)); }
                e++;
            }
            WG_WAIT(0);
            fence_regs(o);
            if (lane < 2) mbar_arrive_cluster(rel_base + 8 * ((e - 1) & 3));
            uint4* dst = &g_q3[((qb * 8 + 2 * v) * 8 + cw) * 128 + lane];
#pragma unroll
            for (int i = 0; i < 8; i++)
                __stcg(dst + (i >> 2) * 1024 + (i & 3) * 32, make_uint4(pack_bf16(o[8 * i], o[8 * i + 1]), pack_bf16(o[8 * i + 2], o[8 * i + 3]),
                                                                        pack_bf16(o[8 * i + 4], o[8 * i + 5]), pack_bf16(o[8 * i + 6], o[8 * i + 7])));
        }
        bar_sync(3, 256);
        if (cw == 0 && lane == 0) flag_release(&g_flag_q3[qb * 32], tag);
        __syncwarp();
    }
}

template <bool SPARE>
__global__ void __cluster_dims__(2, 1, 1) __launch_bounds__(384, 1)
fused_kernel(const Args args, const __grid_constant__ CUtensorMap tm_wq,
             const __grid_constant__ CUtensorMap tm_k, const __grid_constant__ CUtensorMap tm_v,
             const __grid_constant__ CUtensorMap tm_wo, const __grid_constant__ CUtensorMap tm_p,
             const __grid_constant__ CUtensorMap tm_x, const __grid_constant__ CUtensorMap tm_d,
             const __grid_constant__ CUtensorMap tm_g, const __grid_constant__ CUtensorMap tm_u) {
    extern __shared__ __align__(1024) uint8_t smem_raw[];
    const uint32_t sb = smem_u32(smem_raw);
    Scratch* const gs = args.gs;
    const uint32_t bar_full = sb + SM_BAR;
    const uint32_t bar_g = bar_full + 8 * 4;
    const uint32_t bar_mod = bar_g + 8;
    const uint32_t bar_go = bar_mod + 8;
    const uint32_t bar_x = bar_go + 40;
    const uint32_t bar_empty = bar_x + 8;
    const uint32_t bar_pub = bar_empty + 8 * 4;
    const uint32_t bar_qfree = bar_pub + 32;
    const uint32_t bar_out = bar_qfree + 24;
    const uint32_t bar_q3 = bar_out + 8;
    const uint32_t bar_pre = bar_q3 + 16;
    const uint32_t bar_w0 = bar_q3 + 8;
    constexpr int E0 = SPARE ? 2 : 0;

    const int c = blockIdx.x & 1;
#define ROLES() const int role = cluster_role(), j = role & 7, qb = (role >> 3) * 2 + c, rg = qb * 8 + j
    const int warp = __shfl_sync(0xffffffffu, threadIdx.x >> 5, 0);

    if (SPARE && blockIdx.x >= NCTA && warp >= 4) {
        asm volatile("barrier.cluster.arrive.relaxed.aligned;" ::: "memory");
        asm volatile("setmaxnreg.inc.sync.aligned.u32 240;");
        asm volatile("barrier.cluster.wait.aligned;" ::: "memory");
        spare_q3(gs, sb, bar_full, bar_empty, threadIdx.x & 31, warp - 4);
        asm volatile("barrier.cluster.arrive.relaxed.aligned;\nbarrier.cluster.wait.aligned;" ::: "memory");
    } else if (warp < 4) {
        asm volatile("setmaxnreg.dec.sync.aligned.u32 24;");
        ROLES();
        int lane;
        asm volatile("mov.u32 %0, %%laneid;" : "=r"(lane));
        if (warp == 2 && elect()) {
            if (TMPF) asm volatile("prefetch.tensormap [%0];" ::"l"(&tm_x) : "memory");
#pragma unroll
            for (int i = 0; i < 27; i++) mbar_init(bar_full + 8 * i, i < 12 || i >= 23 ? 1 : i < 16 ? 16 : 8);
#pragma unroll
            for (int i = 0; i <= E0; i++) {
                mbar_arrive(bar_full + 8 * i);
                asm volatile("mbarrier.arrive.shared::cta.b64 _, [%0], 16;" ::"r"(bar_empty + 8 * i) : "memory");
            }
            asm volatile("fence.mbarrier_init.release.cluster;" ::: "memory");
        }
        __syncwarp();
        asm volatile("barrier.cluster.arrive.relaxed.aligned;" ::: "memory");
        if (warp == 2 && !(SPARE && blockIdx.x >= NCTA)) {
            if (XDELAY) __nanosleep(XDELAY);
            if (elect()) {
                mbar_expect_tx(bar_x, 16 * XP);
                tma2d(sb + SM_Q, &tm_x, 0, rg * 16, bar_x);
            }
            __syncwarp();
        }
        asm volatile("barrier.cluster.wait.aligned;" ::: "memory");
        const uint32_t tag = load_tag(gs);
        if (SPARE && blockIdx.x >= NCTA) {
            if (warp == 1) {
#pragma unroll 1
                for (int e = 3; e < 83; e++) {
                    const int v = (e - 3) / 5;
                    mbar_wait_sleep(bar_empty + 8 * (e & 3), ~(e >> 2) & 1);
                    if (elect()) {
                        mbar_expect_tx(bar_full + 8 * (e & 3), SLOT);
                        tma2d_mc(sb + (e & 3) * SLOT + c * UNIT, &tm_wq, (8 * (v & 3) + 4 * c + 3) * DH + 64, (e - 3 - v * 5) * 128,
                                 bar_full + 8 * (e & 3), EVICT_NORMAL);
                    }
                }
            }
            __syncwarp();
            asm volatile("barrier.cluster.arrive.relaxed.aligned;\nbarrier.cluster.wait.aligned;" ::: "memory");
            return;
        }
        if (warp == 3) {
#pragma unroll 1
            for (int e = 4; e < 20; e++) {
                __nanosleep(e == 4 ? PFD0 : PFD1);
                const int hd = (e * 52) >> 8, row = (e - hd * 5) * 128 + qb * 8 + (lane >> 1);
                if (lane < 16 && row < D_)
                    asm volatile("prefetch.global.L2 [%0];" ::"l"(padd(args.wq, (row * QD + (4 * j + ((0x1320 >> (4 * hd)) & 3)) * DH + (lane & 1) * 64) * 2)) : "memory");
            }
            __syncwarp();
            mbar_wait_sleep(bar_go, 0);
#pragma unroll 1
            for (int unit = 72 + blockIdx.x; unit < 216; unit += NCTA) {
                float a[8];
#pragma unroll
                for (int i = 0; i < 8; i++) a[i] = 0.f;
#pragma unroll 1
                for (int k = lane >> 1; k < D_; k += 16) {
                    const float cv = __bfloat162float(*padd(args.cvec, k * 2));
                    mod_fma(a, __ldg(reinterpret_cast<const uint4*>(padd(args.w_mod, (k * (6 * D_) + unit * 16 + (lane & 1) * 8) * 2))), rbf(cv * sigmoidf_(cv)));
                }
                const float v = mod_reduce(a, lane), v1 = __shfl_down_sync(0xffffffffu, v, 8);
                if (lane < 8) *padd(gs->mod2, ((unit - 72) * 8 + (lane & 1) * 4 + (lane & 2) + (lane >> 2)) * 4) = pack_bf16(v, v1);
            }
            __syncwarp();
            if (lane == 0) flag_release(padd(g_flag_mod, blockIdx.x * 4), tag);
#pragma unroll 1
            for (int k = 0; k < 36; k++) {
                __nanosleep(200);
                __stcg(padd(gs->h[0], (~tag & 1) * (NCTA * 36 * 512) + ((rg * 36 + k) * 32 + lane) * 16), make_uint4(0, 0, 0, 0));
            }
            __syncwarp();
            mbar_wait_sleep(bar_qfree + 16, 0);
            __nanosleep(2000);
            {
                uint4 v;
                uint32_t it = 0;
#pragma unroll 1
                do {
                    v = ld_relaxed(reinterpret_cast<const uint4*>(padd(g_flag_mod, lane * 16)));
                } while (((v.x ^ tag) | (v.y ^ tag) | (v.z ^ tag) | (v.w ^ tag)) && ++it < SPIN / 16);
                asm volatile("fence.acquire.gpu;" ::: "memory");
            }
            __syncwarp();
            {
                float w1 = 0.f, w2 = 0.f;
#pragma unroll 1
                for (int k = lane; k < D_ / 2; k += 32) {
                    const uint32_t* mp = padd(gs->mod2, k * 4);
                    const uint32_t sv = __ldcg(mp + D_ / 2), c1 = badd2(__ldcg(mp + D_), 0x3f803f80u);
                    const uint32_t wr = *reinterpret_cast<const uint32_t*>(padd(args.w_r, k * 4)), wp = bmul2(c1, wr);
                    reinterpret_cast<uint2*>(smem_raw + SM_T)[k] = make_uint2(__ldcg(mp), wp);
                    reinterpret_cast<uint2*>(smem_raw + SM_TC)[k] = make_uint2(c1, sv);
                    reinterpret_cast<uint32_t*>(smem_raw + SM_TG)[k] = __ldcg(mp + 3 * D_ / 2);
                    w1 += bf_lo(wp) + bf_hi(wp);
                    w2 += bf_lo(sv) * bf_lo(wr) + bf_hi(sv) * bf_hi(wr);
                }
#pragma unroll 1
                for (int i = 1; i < 32; i <<= 1) { w1 += __shfl_xor_sync(0xffffffffu, w1, i); w2 += __shfl_xor_sync(0xffffffffu, w2, i); }
                *reinterpret_cast<float2*>(smem_raw + SM_TS) = make_float2(w1, w2);
            }
#pragma unroll
            for (int i = 0; i < 4; i++) reinterpret_cast<uint4*>(smem_raw + SM_RED)[lane + 32 * i] = make_uint4(~0u, ~0u, ~0u, ~0u);
            asm volatile("fence.proxy.async.shared::cta;" ::: "memory");
            __syncwarp();
            if (elect()) {
                uint8_t* mb = g_frag + (size_t)rg * 8 * WREG + 3 * 4096;
#pragma unroll 1
                for (int k = 0; k < 8; k++, mb += WREG) {
#pragma unroll
                    for (int i = 0; i < 3; i++)
                        asm volatile("cp.async.bulk.global.shared::cta.bulk_group [%0], [%1], 2048;" ::"l"(mb + i * 2048), "r"(sb + SM_RED) : "memory");
                    __nanosleep(500);
                }
                asm volatile("cp.async.bulk.commit_group;\ncp.async.bulk.wait_group 0;\nfence.proxy.async.global;" ::: "memory");
            }
            __syncwarp();
            if (lane == 0) mbar_arrive(bar_mod);
            __syncwarp();
            mbar_wait_sleep(bar_go + 8, 0);
            if (elect()) asm volatile("prefetch.tensormap [%0];\nprefetch.tensormap [%1];\nprefetch.tensormap [%2];" ::"l"(&tm_x), "l"(&tm_p), "l"(&tm_d) : "memory");
            __syncwarp();
#pragma unroll 1
            for (int i = 1; i < 4; i++) {
                mbar_wait(bar_pub + 8 * i, 0);
                unsigned int* flags = padd(g_flag_part, (qb * 32 + i * 8 - 8) * 4);
                if (elect()) { flag_release(padd(flags, j * 4), tag); DBG_PG(93); }
                __syncwarp();
                const uint32_t slot = (i + 2) & 3;
                flag_wait(padd(flags, (lane & 7) * 4), tag);
                asm volatile("fence.proxy.async.global;" ::: "memory");
                if (lane == 0 && i == 3) DBG_PG(101);
                mbar_wait(bar_go + 8 + 8 * i, 0);
                mbar_wait(bar_empty + 8 * slot, i == 3);
                if (elect()) {
                    mbar_expect_tx(bar_full + 8 * slot, SLOT);
                    tma3d(sb + slot * SLOT, &tm_p, 0, j * 20 + (i - 1) * 4, qb * 8, bar_full + 8 * slot);
                    tma3d(sb + slot * SLOT + UNIT, &tm_p, 0, j * 20 + (i - 1) * 4 + 2, qb * 8, bar_full + 8 * slot);
                }
            }
        } else if (warp == 0) {
#pragma unroll 1
            for (int i = 0; i < 48; i++) {
                if (i == 0 || i == 17 || i == 34) mbar_wait_sleep(bar_qfree + (i >> 4) * 8, 0);
                if (SPARE && i == 17) {
                    flag_wait(&g_flag_q3[qb * 32], tag);
                    if (elect()) {
                        asm volatile("fence.proxy.async.global;" ::: "memory");
                        mbar_expect_tx(bar_q3, UNIT);
#pragma unroll 1
                        for (int k = 0; k < 8; k++) bulk_load(sb + SM_Q + 2 * SLOT + k * 4096 + 2048, &g_q3[(rg * 8 + k) * 128], 2048, bar_q3);
                    }
                }
                __nanosleep(700);
                if (elect()) {
                    asm volatile("mbarrier.expect_tx.shared::cta.b64 [%0], %1;" ::"r"(bar_g), "n"(1920) : "memory");
                    tma2d(sb + SM_Q + i * 1920, i < 24 ? &tm_g : &tm_u, (blockIdx.x * 36) & ~7, (i < 24 ? i : i - 24) * 24, bar_g);
                }
            }
            if (elect()) mbar_arrive(bar_g);
#pragma unroll 1
            for (int i = 0; i < 18; i++) {
                __nanosleep(400);
                if (OPF && i < 8 * OPF && elect()) l2_prefetch(g_frag + (size_t)(rg * 8 + (i & 7)) * WREG + (i >> 3) * 4096, 4096);
                if (elect()) l2_prefetch(args.w_down + (size_t)(blockIdx.x * 36 + i * 2) * D_, 4 * D_);
            }
            __syncwarp();
            mbar_wait_sleep(bar_go + 8 * 2, 0);
            uint32_t acc = 0;
#pragma unroll 1
            for (int k = lane; k < 16 * 9; k += 32) acc |= touch(padd(args.x, (rg * 16 * D_ + k * 64) * 2));
            if (acc == 0) reinterpret_cast<volatile uint32_t*>(smem_raw + SM_BAR)[127] = acc;
            __syncwarp();
            mbar_wait_sleep(bar_go + 8 * 4, 0);
            uint4* rp = padd(g_rows, (rg * 2 * RSLOT + lane) * 16);
#pragma unroll
            for (int k = 0; k < 12; k++) rp[k * 32] = make_uint4(~0u, ~0u, ~0u, ~0u);
            if (blockIdx.x < 72) {
                uint4* yp = reinterpret_cast<uint4*>(padd(g_ypart, blockIdx.x * NCTA * 64 + lane * 16));
#pragma unroll
                for (int k = 0; k < 16; k++) yp[k * 32] = make_uint4(~0u, ~0u, ~0u, ~0u);
            }
            asm volatile("fence.acq_rel.gpu;" ::: "memory");
            __syncwarp();
            if (lane == 0) mbar_arrive(bar_pre);
        } else if (warp == 1) {
            __nanosleep(QDELAY);
            uint32_t go = bar_go;
            uint64_t marks = 24 | 151 << 8 | 155 << 16 | 160ull << 24 | 165ull << 32;
#pragma unroll 1
            for (int e = E0; e < 168; e++) {
                const CUtensorMap* tm;
                int c0, c1;
                uint64_t pol = EVICT_FIRST;
                if (e == 159 || e == 164) continue;
                if (e < 21 && e != 19) {
                    const int i = SPARE && e < 12 ? e - 2 : e - (e == 20), hd = (i * 52) >> 8;
                    tm = &tm_wq; c0 = (4 * j + ((0x1320 >> (4 * hd)) & 3)) * DH + c * 64; c1 = (i - hd * 5) * 128 - 64;
                    if (SPARE && e >= 12 && e < 15) { c0 = (4 * j + 3) * DH; c1 = (2 * (e - 12) + c) * 128; }
                } else if (e < 148) {
                    const int i = max(e - 20, 0);
                    const bool isk = i == 0 || ((i & 1) && i < 127);
                    const int n = isk ? (i + 1) >> 1 : (i - 1) >> 1;
                    tm = isk ? &tm_k : &tm_v; c0 = c * 64; c1 = (2 * j + (n >> 5)) * S_ + (n & 15) * 128;
                    if (!(i & 32)) pol = EVICT_NORMAL;
                } else {
                    int i = e - 148 - (e > 159) - (e > 164);
                    tm = &tm_wo; c0 = (i >> 1) * 64; c1 = (4 * j + (O2F ? ((i & 1) ? c : 2 + c) : (i & 1) ? 1 + c : 3 * c)) * DH;
                }
                const uint32_t fb = e == E0 ? bar_w0 : bar_full + 8 * (e & 3), d = sb + (e == E0 ? 6 : e & 3) * SLOT;
                if (e >= 24 && e < 152) mbar_wait_sleep(bar_empty + 8 * (e & 3), ~(e >> 2) & 1);
                else if (e != E0) mbar_wait(bar_empty + 8 * (e & 3), ~(e >> 2) & 1);
                if (elect()) {
                    mbar_expect_tx(fb, SLOT);
                    tma2d_mc(d + c * UNIT, tm, c0, c1, fb, pol);
                    const int i = e - PF_KV;
                    if (i >= 0 && i < 128 && !(i & 32))
                        l2_prefetch(((i & 1) ? args.vc : args.kc) + (size_t)((2 * j + (i >> 6)) * S_ + (i & 30) * 64) * DH + qb * 1024, 2048);
                    if (e >= PF_WO && e < PF_WO + 18) l2_prefetch(args.wo + (size_t)blockIdx.x * (QD * D_ / NCTA) + (e - PF_WO) * 1024, 2048);
                    if (e == (marks & 255)) mbar_arrive(go);
                }
                if (e == (marks & 255)) { go += 8; marks >>= 8; }
            }
            asm volatile("fence.proxy.async.global;" ::: "memory");
            mbar_wait(bar_empty, 1);
            if (elect()) {
                mbar_expect_tx(bar_full, 16 * XP);
                tma2d(sb, &tm_x, 0, rg * 16, bar_full);
            }
            mbar_wait(bar_empty + 16, 1);
            if (C3D) __nanosleep(C3D);
            if (elect()) {
                mbar_expect_tx(bar_full + 16, SLOT);
                tma3d(sb + 2 * SLOT, &tm_p, 0, j * 20 + 12, qb * 8, bar_full + 16);
                tma3d(sb + 2 * SLOT + UNIT, &tm_p, 0, j * 20 + 14, qb * 8, bar_full + 16);
            }
            mbar_wait(bar_empty + 24, 1);
            if (C4D) __nanosleep(C4D);
            if (elect()) {
                mbar_expect_tx(bar_full + 24, UNIT);
                tma3d(sb + 3 * SLOT, &tm_p, 0, j * 20 + 16, qb * 8, bar_full + 24);
            }
            mbar_wait(bar_empty + 8, 0);
            mbar_wait(bar_empty + 16, 0);
            if (DD) __nanosleep(DD);
            if (elect()) {
#pragma unroll
                for (int i = 1; i < 3; i++) {
                    mbar_expect_tx(bar_full + 8 * i, 18 * XP);
                    tma2d(sb + i * SLOT, &tm_d, 0, blockIdx.x * 36 + (i - 1) * 18, bar_full + 8 * i);
                }
            }
        } else {
            if (elect()) asm volatile("prefetch.tensormap [%0];\nprefetch.tensormap [%1];\nprefetch.tensormap [%2];" ::"l"(&tm_k), "l"(&tm_v), "l"(&tm_wo) : "memory");
            if (SPARE) {
                mbar_wait_sleep(bar_pub, 0);
                if (lane == 0) flag_release(padd(g_flag_h, rg * 128), tag);
                __syncwarp();
            }
            bar_sync(1, 192);
            for (int i = QT0; i < 4; i++) bar_sync(1, 192);
#pragma unroll 1
            for (uint32_t e = E0 + 5; e < 20; e++) {
                mbar_wait(bar_full + 8 * (e & 3), (e >> 2) & 1);
                if (!(((SPARE ? 0xa080 : 0x8420) >> e) & 1)) bar_sync(1, 192);
            }
#pragma unroll 1
            for (uint32_t e = 20; e < 148; e++) {
                mbar_wait_sleep(bar_full + 8 * (e & 3), (e >> 2) & 1);
                if (SPARE && e == 113) mbar_wait(bar_q3, 0);
                if (e & 1) bar_sync(1, 192);
                if (!(e & 1) || e == 147) bar_sync(4, 160);
            }
#pragma unroll 1
            for (uint32_t e = 148; e < 168; e++) {
                mbar_wait(bar_full + 8 * (e & 3), (e >> 2) & 1);
                if (e != 159 && e != 164) bar_sync(1, 192);
            }
        }
        __syncwarp();
        mbar_wait_sleep(bar_out, 0);
        if (OUTD) __nanosleep(OUTD);
        if (elect()) {
            asm volatile("fence.proxy.async.shared::cta;" ::: "memory");
            const int2 sel = reinterpret_cast<const int2*>(smem_raw + SM_RED)[8];
#pragma unroll 1
            for (int i = warp; i < 16; i += 4) {
                const int row = rg * 16 + i;
                if (row != sel.x && row != sel.y)
                    asm volatile("cp.async.bulk.global.shared::cta.bulk_group.L2::cache_hint [%0], [%1], %2, %3;"
                                 ::"l"(args.out + (size_t)row * D_), "r"(sb + i * XP), "n"(D_ * 2), "l"(OUTPOL) : "memory");
            }
            asm volatile("cp.async.bulk.commit_group;\ncp.async.bulk.wait_group.read 0;" ::: "memory");
        }
    } else {
        uint32_t cv[2] = {0, 0}, tag = load_tag(gs) - 1;
        if (blockIdx.x < 72) {
            uint32_t ws;
            int tid;
            asm volatile("mov.u32 %0, smem_raw;\nmov.u32 %1, %%tid.x;" : "=r"(ws), "=r"(tid));
            tid -= 128;
            ws += SM_Q + SLOT + tid * 16;
            const uint32_t* cp = padd(reinterpret_cast<const uint32_t*>(args.cvec), (tid & 0xe0) + (tid & 7) * 4);
            cv[0] = *padd(cp, (tid & 24) * 32);
            if (tid < 128) cv[1] = cp[256];
            const bf16* wrow = args.w_mod + (size_t)(tid >> 1) * (6 * D_) + (tid & 1) * 8 + blockIdx.x * 16;
#pragma unroll
            for (int i = 0; i < 5; i++)
                if (i < 4 || tid < 128)
                    asm volatile("cp.async.cg.shared.global [%0], [%1], 16;" ::"r"(ws + i * 4096), "l"(wrow + (size_t)i * 128 * (6 * D_)) : "memory");
        }
        asm volatile("barrier.cluster.arrive.relaxed.aligned;" ::: "memory");
        asm volatile("setmaxnreg.inc.sync.aligned.u32 240;");
        const int lane = threadIdx.x & 31;
        const int cw = warp - 4;
        const int w = cw >> 2;
        const int tid = threadIdx.x - 128;
        ROLES();
        float* red = reinterpret_cast<float*>(smem_raw + SM_RED);
        DBG_INIT();
        DBG_G(120);
        DBG_T(100);

        {
            if (blockIdx.x < 72) {
                uint32_t sa[10];
#pragma unroll
                for (int i = 0; i < 2; i++) {
                    const float lo = bf_lo(cv[i]), hi = bf_hi(cv[i]);
                    cv[i] = pack_bf16(lo * sigmoidf_(lo), hi * sigmoidf_(hi));
                }
#pragma unroll
                for (int i = 0; i < 10; i++) sa[i] = __shfl_sync(0xffffffffu, cv[i >> 3], (i & 7) * 4 + (lane & 3));
                uint2* mdst = &gs->mod1[(tid >> 3) * D_ + blockIdx.x * 8 + (tid & 7)];
                anchor(bar_full + 504, sa[0] & sa[1] & sa[2] & sa[3] & sa[4] & sa[5] & sa[6] & sa[7] & sa[8] & sa[9] & (uint32_t)(uintptr_t)mdst & (uint32_t)((uintptr_t)mdst >> 32));
                asm volatile("cp.async.wait_all;" ::: "memory");
                __syncwarp();
                const uint32_t ws = sb + SM_Q + SLOT + cw * 512 + (lane & 15) * 32 + (lane & 16);
                float d[16];
#pragma unroll
                for (int i = 0; i < 16; i++) d[i] = 0.f;
#pragma unroll
                for (int i = 0; i < 5; i++) {
                    const uint4 b = ldsm4t(ws + (i < 4 || cw < 4 ? i * 4096 : 0));
                    mma16816(d + 8 * (i & 1), sa[2 * i], sa[2 * i], sa[2 * i + 1], sa[2 * i + 1], b.x, b.y);
                    mma16816(d + 8 * (i & 1) + 4, sa[2 * i], sa[2 * i], sa[2 * i + 1], sa[2 * i + 1], b.z, b.w);
                }
                if (lane < 8) reinterpret_cast<float2*>(red)[lane * 8 + cw] = (lane & 4) ? make_float2(d[4] + d[12], d[5] + d[13]) : make_float2(d[0] + d[8], d[1] + d[9]);
                bar_sync(3, 256);
                if (tid < 8 * MREP) {
                    const float4* r = reinterpret_cast<const float4*>(red) + (tid & 7) * 4;
                    const float4 r0 = r[0], r1 = r[1], r2 = r[2], r3 = r[3];
                    st_relaxed64(mdst, pack_bf16(((r0.x + r0.z) + (r1.x + r1.z)) + ((r2.x + r2.z) + (r3.x + r3.z)),
                                                 ((r0.y + r0.w) + (r1.y + r1.w)) + ((r2.y + r2.w) + (r3.y + r3.w))), tag + 1);
                }
            }
            DBG_G(106);
            asm volatile("barrier.cluster.wait.aligned;" ::: "memory");
            mbar_wait(bar_x, 0);
            asm volatile("add.u32 %0, %0, 1;" : "+r"(tag));
            uint32_t x[20];
            float st[12], st2[12];
            rows_load(x, sb + SM_Q + (lane & 15) * XP + (lane >> 4) * 16 + cw * 32, cw);
#pragma unroll
            for (int i = 0; i < 12; i++) { st[i] = 0.f; st2[i] = 0.f; }
#pragma unroll
            for (int k = 0; k < 9; k++) stats_add((k & 1) ? st2 : st, x[2 * k], x[2 * k + 1], 0x3f803f80u);
#pragma unroll
            for (int i = 0; i < 12; i++) st[i] += st2[i];
            uint32_t mean2;
            float dot;
            const float rsd = rows_stats(st, reinterpret_cast<float4*>(red + 128), cw, lane, mean2, dot);
            const uint4* mp = reinterpret_cast<const uint4*>(gs->mod1 + ((blockIdx.x >> 1) & (MREP - 1)) * D_) + min(tid, D_ / 4 - 1);
            uint4 v0 = make_uint4(0, tag, 0, tag), v1 = v0;
            auto look = [&]() {
                asm volatile("{\n.reg .pred p;\n.reg .b64 a, b, c, d;\nsetp.lt.s32 p, %9, 5;\nmov.b64 a, {%0, %1};\nmov.b64 b, {%2, %3};\n"
                             "mov.b64 c, {%4, %5};\nmov.b64 d, {%6, %7};\n@p ld.relaxed.gpu.global.v2.b64 {a, b}, [%8];\n"
                             "@p ld.relaxed.gpu.global.v2.b64 {c, d}, [%8 + 2304];\n"
                             "mov.b64 {%0, %1}, a;\nmov.b64 {%2, %3}, b;\nmov.b64 {%4, %5}, c;\nmov.b64 {%6, %7}, d;\n}"
                             : "+r"(v0.x), "+r"(v0.y), "+r"(v0.z), "+r"(v0.w), "+r"(v1.x), "+r"(v1.y), "+r"(v1.z), "+r"(v1.w)
                             : "l"(mp), "r"(cw) : "memory");
            };
            rows_normalise(x, x, mean2, rsd, lane, look);
            fence_regs(x);
            uint32_t it = 0;
#pragma unroll 1
            while (((v0.y ^ tag) | (v0.w ^ tag) | (v1.y ^ tag) | (v1.w ^ tag)) && ++it < SPIN / 16) look();
            uint4* smod = reinterpret_cast<uint4*>(smem_raw + SM_Q + M_MOD);
            if (tid < D_ / 4) smod[tid] = make_uint4(badd2(v1.x, 0x3f803f80u), v0.x, badd2(v1.z, 0x3f803f80u), v0.z);
            uint4* hdst = g_h + (size_t)(rg * 36 + cw) * 32 + lane;
            uint2* hdst2 = reinterpret_cast<uint2*>(g_h + (size_t)(rg * 36 + 32) * 32) + tid;
            bar_sync(3, 256);
            DBG_G(107);
#pragma unroll
            for (int k = 0; k < 9; k++) {
                const uint2 cs = lds64(sb + SM_Q + M_MOD + (cw * 8 + (lane & 3) + (k < 8 ? (k >> 1) * 64 + (k & 1) * 4 : 256 - cw * 4)) * 8);
                const uint32_t c1 = cs.x, sa = cs.y;
                x[2 * k] = badd2(bmul2(x[2 * k], c1), sa);
                if (x[2 * k] == 0) x[2 * k] = 0x8000u;
                x[2 * k + 1] = badd2(bmul2(x[2 * k + 1], c1), sa);
            }
#pragma unroll
            for (int ch = 0; ch < 4; ch++) st_relaxed4(hdst + ch * 256, x[4 * ch], x[4 * ch + 1], x[4 * ch + 2], x[4 * ch + 3]);
            st_relaxed64(hdst2, x[16], x[17]);
            __syncwarp();
            if (SPARE && lane == 0) mbar_arrive(bar_pub);
            DBG_G(108);
        }

        uint32_t rel_base;
        asm("mapa.shared::cluster.u32 %0, %1, %2;" : "=r"(rel_base) : "r"(bar_empty), "r"(lane & 1));
        auto release = [&](uint32_t slot) { if (lane < 2) mbar_arrive_cluster(rel_base + 8 * slot); };
        uint32_t q[32], p[32];
        float s[64], o[64];

        const int lw = cw & 3;
        const uint32_t relw = lw == RW && lane < 8, handw = lw == HW || cw == HW2;
        auto release4 = [&](uint32_t off, uint32_t on = 1) {
            asm volatile("{\n.reg .pred p;\nsetp.ne.b32 p, %1, 0;\n@p mbarrier.arrive.shared::cluster.b64 _, [%0];\n}" ::"r"(rel_base + off), "r"(relw & on) : "memory"); };
        auto handoff = [&](uint32_t on = 1) {
            asm volatile("{\n.reg .pred p;\nsetp.ne.b32 p, %1, 0;\n@p bar.arrive %0, 192;\n}" ::"r"(2 - w), "r"(handw & on) : "memory"); };
        if (cw == 4 + HW) bar_arrive(1, 192);

        uint4* qpark = reinterpret_cast<uint4*>(smem_raw + SM_Q - SLOT) + cw * 256 + lane;
        {
            uint32_t h[144];
            const uint4* hf = g_h + (size_t)(qb * 8 + cw) * (36 * 32) + lane;
            auto load_h = [&](auto lo, auto hi) {
#pragma unroll
                for (int ks = lo.value; ks < hi.value; ks++) {
                    const uint4 v = h_frag(hf, ks, lane);
                    h[4 * ks] = v.x; h[4 * ks + 1] = v.y; h[4 * ks + 2] = v.z; h[4 * ks + 3] = v.w;
                }
            };
            auto check_h = [&](auto lo, auto hi) {
                uint32_t it = 0;
                bool miss;
#pragma unroll 1
                do {
                    uint32_t mn = ~0u;
#pragma unroll
                    for (int ks = lo.value; ks < hi.value; ks++) mn = __vimin3_u32(mn, h[4 * ks], h[4 * ks + 2]);
                    miss = __any_sync(0xffffffffu, mn == 0);
                    if (miss) load_h(lo, hi);
                    asm volatile("add.u32 %0, %0, 1;" : "+r"(it));
                } while (miss && it < SPIN / 16);
            };
            auto check_h2 = [&](auto lo, auto hi, auto nx) {
                float f0 = __uint_as_float(~0u), f1 = f0;
                hold(f0, f1);
                auto low = [&]() {
                    uint32_t m0 = __float_as_uint(f0), m1 = m0;
#pragma unroll
                    for (int ks = lo.value; ks < hi.value; ks += 2) { m0 = __vimin3_u32(m0, h[4 * ks], h[4 * ks + 2]); m1 = __vimin3_u32(m1, h[4 * ks + 4], h[4 * ks + 6]); }
                    return min(m0, m1);
                };
                anchor(const_cast<uint4*>(hf), h[4 * hi.value - 1] & __float_as_uint(f0));
                load_h(hi, nx);
                if (__any_sync(0xffffffffu, low() == 0)) {
                    uint32_t it = 0;
#pragma unroll 1
                    do load_h(lo, hi); while (__any_sync(0xffffffffu, low() == 0) && ++it < SPIN / 16);
                }
            };
            __nanosleep(HDELAY);
            load_h(IC<0>{}, IC<4>{});
            DBG_T(104); DBG_G(109);
            mbar_wait(bar_w0, 0);
#pragma unroll
            for (int e = E0 + 1; e < E0 + 5; e++) mbar_wait(bar_full + 8 * (e & 3), e >> 2);
#pragma unroll
            for (int i = 0; i < 64; i++) o[i] = 0.f;
            auto group = [&](auto tc, auto ec) {
                constexpr int t = tc.value, e = ec.value, k0 = t ? 8 * t - 4 : 0;
                constexpr bool first = e < E0 + 5, turns = e >= E0 + QT0;
                uint64_t dv = (first ? args.d0 : desc_lo(0, UNIT) | (0x40000040ull << 32)) + ((t ? 0 : 512) + (e == E0 ? 6 : e & 3) * (SLOT / 16));
                if (first) { if (t < HE) check_h(IC<k0>{}, IC<8 * t + 4>{}); else check_h2(IC<k0>{}, IC<8 * t + 4>{}, IC<t < 4 ? 8 * t + 12 : 0>{}); }
                if (t != 1 && turns) bar_sync(1 + w, 192);
                if (t != 1 || first) WG_FENCE();
#pragma unroll
                for (int ks = k0; ks < 8 * t + 4; ks++) {
                    mma_rs128<1>(o, h[4 * ks], h[4 * ks + 1], h[4 * ks + 2], h[4 * ks + 3], dv, ks);
                    if (t && turns && ks == k0 + QSPLIT - 1) WG_COMMIT();
                }
                if (t || first) WG_COMMIT();
                if (t < 4 && first && t < HE) load_h(IC<8 * t + 4>{}, IC<t < 4 ? 8 * t + 12 : 0>{});
                if (t > 0) {
                    WG_WAIT(1);
                    if (turns) handoff();
                    if ((t == 1 && !first) || (t > 1 && e <= E0 + QT0)) release4(8 * ((e - 1) & 3));
                    if (turns && e != 18) { WG_WAIT(0); release4(8 * (e & 3)); }
                }
            };
            auto head = [&](auto ec, int slot) {
                constexpr int e = ec.value;
                fence_regs(o);
                group(IC<0>{}, IC<e>{}); group(IC<1>{}, IC<e + 1>{}); group(IC<2>{}, IC<e + 2>{}); group(IC<3>{}, IC<e + 3>{});
                if (e == 15) return;
                group(IC<4>{}, IC<e + 4>{});
                fence_regs(o);
#pragma unroll
                for (int i = 0; i < 8; i++)
                    qpark[slot * 2048 + i * 32] = make_uint4(pack_bf16(o[8 * i], o[8 * i + 1]), pack_bf16(o[8 * i + 2], o[8 * i + 3]),
                                                             pack_bf16(o[8 * i + 4], o[8 * i + 5]), pack_bf16(o[8 * i + 6], o[8 * i + 7]));
            };
            head(IC<E0>{}, 1);
            head(IC<E0 + 5>{}, 2);
            if (SPARE) {
                float (&u)[32] = reinterpret_cast<float (&)[32]>(o);
                fence_regs(u);
#pragma unroll
                for (int t = 0; t < 2; t++) {
                    uint64_t dv = args.d0 + t * (SLOT / 16);
                    bar_sync(1 + w, 192);
                    WG_FENCE();
#pragma unroll
                    for (int ks = 0; ks < 16 + 4 * t; ks++) {
                        mma_rs64<1>(u, h[64 * t + 4 * ks], h[64 * t + 4 * ks + 1], h[64 * t + 4 * ks + 2], h[64 * t + 4 * ks + 3], dv, ks | t);
                        if (ks == 2 * QSPLIT + 4 * t - 1) WG_COMMIT();
                    }
                    WG_COMMIT();
                    WG_WAIT(1);
                    handoff();
                    WG_WAIT(0);
                    release4(8 * t);
                }
                fence_regs(u);
                release4(16);
#pragma unroll
                for (int i = 0; i < 4; i++)
                    qpark[3 * 2048 + i * 32] = make_uint4(pack_bf16(u[8 * i], u[8 * i + 1]), pack_bf16(u[8 * i + 2], u[8 * i + 3]),
                                                          pack_bf16(u[8 * i + 4], u[8 * i + 5]), pack_bf16(u[8 * i + 6], u[8 * i + 7]));
            } else {
                head(IC<10>{}, 3);
            }
            head(IC<15>{}, 0);
#pragma unroll
            for (int i = 0; i < 8; i++) {
                const uint4 v = lds128(smem_u32(qpark + 2048 + i * 32));
                q[4 * i] = v.x; q[4 * i + 1] = v.y; q[4 * i + 2] = v.z; q[4 * i + 3] = v.w;
            }
#pragma unroll
            for (int i = 0; i < 32; i++) p[i] = h[112 + i];
            WG_WAIT(0);
            fence_regs(o);
            release4(16);
        }
        DBG_T(105);
        DBG_G(125);

        uint8_t* frag = reinterpret_cast<uint8_t*>(__shfl_sync(0xffffffffu, reinterpret_cast<unsigned long long>(g_frag + (size_t)(rg * 8 + cw) * WREG + lane * 16), lane));
        const uint4* qnext = reinterpret_cast<const uint4*>(__shfl_sync(0xffffffffu, reinterpret_cast<unsigned long long>(padd(smem_raw, SM_Q + tid * 16 + cw * 3584)), lane));
        uint8_t* odst = reinterpret_cast<uint8_t*>(const_cast<uint4*>(qnext));
        qnext -= 2048;
        float m0, m1, l0 = 0.25f, l1 = 0.25f, t0, t1;
        uint32_t bad = 0;
        auto finish = [&](auto lo, auto hi, uint32_t bit, auto sink) {
#pragma unroll
            for (int i = lo.value; i < hi.value; i++) {
                const uint32_t v0 = pack_bf16(o[8 * i] * t0, o[8 * i + 1] * t0), v1 = pack_bf16(o[8 * i + 2] * t1, o[8 * i + 3] * t1);
                const uint32_t v2 = pack_bf16(o[8 * i + 4] * t0, o[8 * i + 5] * t0), v3 = pack_bf16(o[8 * i + 6] * t1, o[8 * i + 7] * t1);
                if (i == 0 && fabsf(o[0] * t0) >= 0x1p-31f) bad |= bit << 8;
                sink(i, v0, v1, v2, v3);
            }
        };
        float lq[6];
        auto row_parts = [&]() {
#pragma unroll
            for (int i = 0; i < 3; i++) { lq[i] = __shfl_xor_sync(0xffffffffu, l0, i + 1); lq[3 + i] = __shfl_xor_sync(0xffffffffu, l1, i + 1); }
        };
        auto row_sums = [&](uint32_t bit) {
            t0 = (l0 + lq[0]) + (lq[1] + lq[2]); t1 = (l1 + lq[3]) + (lq[4] + lq[5]);
            if (!(t0 >= LMIN && t0 < LMAX && t1 >= LMIN && t1 < LMAX)) bad |= bit;
        };
        auto issue_pv = [&](uint64_t dv, int acc, auto lo, auto hi) {
            if (lo.value == 0) asm volatile("{\n.reg .pred p;\nsetp.eq.b32 p, %0, 0;\n@p bar.sync 4, 160;\n}" ::"r"(w) : "memory");
#pragma unroll
            for (int ks = lo.value; ks < hi.value; ks++)
                mma_rs128<1>(o, p[4 * ks], p[4 * ks + 1], p[4 * ks + 2], p[4 * ks + 3], dv, ks ? 1 : acc);
            WG_COMMIT();
        };
#pragma unroll
        for (int i = 0; i < 64; i++) s[i] = 0.f;
        uint64_t dv_lo = args.d0;
        uint32_t voff = 0;
        auto issue_qk = [&]() {
            uint64_t dk = dv_lo ^ (desc_lo(0, UNIT) ^ desc_lo(3 * SLOT, 16));
            bar_sync(1 + w, 192);
            fence_regs(s); fence_regs(q); fence_regs(o); fence_regs(p);
            WG_FENCE();
#pragma unroll
            for (int ks = 0; ks < 8; ks++)
                if (ks == 3) mma_rs128<0, 1018>(s, q[4 * ks], q[4 * ks + 1], q[4 * ks + 2], q[4 * ks + 3], dk, 1);
                else mma_rs128<0, 2>(s, q[4 * ks], q[4 * ks + 1], q[4 * ks + 2], q[4 * ks + 3], dk, ks != 0);
            WG_COMMIT();
        };
        auto to_frag = [&](int i, uint32_t v0, uint32_t v1, uint32_t v2, uint32_t v3) {
            *reinterpret_cast<uint4*>(odst + i * 512) = make_uint4(v0, v1, v2, v3); };
        int n = 0;
        auto scores_ready = [&]() {
            WG_WAIT(1);
            fence_regs(s); fence_regs(q);
        };
        auto pass_on = [&]() {
            release4(voff ^ 24);
            handoff();
        };
#pragma unroll 1
        for (;;) {
            {
                if (RPE) {
                    asm volatile("st.shared.v2.f32 [%0], {%1, %2};" ::"r"(sb + SM_RED + tid * 8), "f"(l0), "f"(l1) : "memory");
                    __syncwarp();
                    const uint4 a = lds128(sb + SM_RED + (tid & ~3) * 8), b = lds128(sb + SM_RED + (tid & ~3) * 8 + 16);
                    l0 = __uint_as_float(a.x); lq[0] = __uint_as_float(a.z); lq[1] = __uint_as_float(b.x); lq[2] = __uint_as_float(b.z);
                    l1 = __uint_as_float(a.y); lq[3] = __uint_as_float(a.w); lq[4] = __uint_as_float(b.y); lq[5] = __uint_as_float(b.w);
                } else {
                    row_parts();
                }
                issue_qk();
                if (RPE == 2) hold(l0, l1);
                row_sums(1u << (n >> 4));
                t0 = rcp_fast(t0); t1 = rcp_fast(t1);
                l0 = 0.f; l1 = 0.f;
                odst = n ? frag + ((n >> 4) - 1) * 4096 : odst;
                qnext = n == 48 ? reinterpret_cast<const uint4*>(frag + O2F * 8192) : qnext + 2048;
                if (RPE) anchor(bar_full + 504, (t0 + t1) * __uint_as_float((bad ^ (uint32_t)(uintptr_t)odst ^ (uint32_t)(uintptr_t)qnext) & 0x3fffffff));
                asm volatile("{\n.reg .pred p;\nsetp.ne.b32 p, %1, 0;\n@p mbarrier.arrive.shared::cta.b64 _, [%0];\n}"
                             ::"r"(bar_qfree + (n >> 1) - 8), "r"(lane ? 0 : n) : "memory");
                issue_pv(dv_lo, 1, IC<0>{}, IC<8>{});
                scores_ready();
                float a0 = fmaxf(s[0], s[1]), a1 = fmaxf(s[2], s[3]), a2 = fmaxf(s[4], s[5]), a3 = fmaxf(s[6], s[7]);
#pragma unroll
                for (int i = 1; i < MAXG; i++) {
                    a0 = fmaxf(a0, fmaxf(s[8 * i], s[8 * i + 1])); a1 = fmaxf(a1, fmaxf(s[8 * i + 2], s[8 * i + 3]));
                    a2 = fmaxf(a2, fmaxf(s[8 * i + 4], s[8 * i + 5])); a3 = fmaxf(a3, fmaxf(s[8 * i + 6], s[8 * i + 7]));
                }
                const uint32_t a = MAXG ? pack_bf16(fmaxf(a0, a2), fmaxf(a1, a3)) : pack_bf16(a0, a1);
                const uint32_t b = bmax2(bmax2(a, __shfl_xor_sync(0xffffffffu, a, 1)), bmax2(__shfl_xor_sync(0xffffffffu, a, 2), __shfl_xor_sync(0xffffffffu, a, 3)));
                pass_on();
                m0 = fmaf(-CS, bf_lo(b), -POFF); m1 = fmaf(-CS, bf_hi(b), -POFF);
            }
#pragma unroll 1
            for (;;) {
                DBG_T(n);
#pragma unroll
                for (int i = 0; i < 4 * STAGE; i++) s[i] = fmaf(s[i], CS, (i & 2) ? m1 : m0);
#pragma unroll
                for (int i = 0; i < 4 * SPLIT; i++) s[i] = ex2(s[i]);
#pragma unroll
                for (int i = 0; i < SPLIT; i++) { l0 += s[4 * i] + s[4 * i + 1]; l1 += s[4 * i + 2] + s[4 * i + 3]; }
                if (STAGE < 16) {
                    m0 = fmaf(l0, 0.f, m0); m1 = fmaf(l1, 0.f, m1);
                }
                anchor(bar_full + 504, l0 + l1);
                WG_WAIT(0);
                fence_regs(o); fence_regs(p);
                release4(voff);
                dv_lo ^= 2 * SLOT / 16;
                voff ^= 16;
                n++;
#pragma unroll
                for (int i = 4 * STAGE; i < 64; i++) s[i] = fmaf(s[i], CS, (i & 2) ? m1 : m0);
#pragma unroll
                for (int i = 4 * SPLIT; i < 64; i++) s[i] = ex2(s[i]);
#pragma unroll
                for (int i = SPLIT; i < 16; i++) { l0 += s[4 * i] + s[4 * i + 1]; l1 += s[4 * i + 2] + s[4 * i + 3]; }
#pragma unroll
                for (int i = 0; i < 32; i++) p[i] = pack_bf16(s[2 * i], s[2 * i + 1]);
                const int jn = n & 15;
                if (jn > 1) {
                    issue_qk();
                    if ((n & RA) == RB) {
                        if (n & 1) {
#pragma unroll
                            for (int i = 0; i < 64; i++) o[i] *= (i & 2) ? t1 : t0;
                        } else {
                            row_parts();
                            row_sums(2u << (n >> 4));
                            const uint32_t e0 = __float_as_uint(t0) >> 23, e1 = __float_as_uint(t1) >> 23;
                            m0 -= __uint_as_float(0x4b000000u | e0) - (8388608.f + 127.f - POFF);
                            m1 -= __uint_as_float(0x4b000000u | e1) - (8388608.f + 127.f - POFF);
                            t0 = __uint_as_float((254 - (int)POFF - e0) << 23); t1 = __uint_as_float((254 - (int)POFF - e1) << 23);
                            l0 *= t0; l1 *= t1;
                        }
                    }
                    fence_regs(o);
                    WG_FENCE();
                    issue_pv(dv_lo, 1, IC<0>{}, IC<8>{});
                    scores_ready();
                    pass_on();
                    if (jn != 15) continue;
#pragma unroll
                    for (int i = 0; i < 8; i++) {
                        const uint4 v = qnext[i * 32];
                        q[4 * i] = v.x; q[4 * i + 1] = v.y; q[4 * i + 2] = v.z; q[4 * i + 3] = v.w;
                    }
                    continue;
                }
                if (jn == 0) break;
                finish(IC<0>{}, IC<ESPLIT>{}, 1u << (n >> 4), to_frag);
                issue_qk();
                if (HOLD) hold(t0, t1);
                finish(IC<ESPLIT>{}, IC<8>{}, 1u << (n >> 4), to_frag);
                WG_FENCE();
                issue_pv(dv_lo, 0, IC<0>{}, IC<8>{});
                scores_ready();
                pass_on();
            }
            if (n == 64) break;
        }
        DBG_T(64);
        uint32_t a1[32], a2[32];
        bar_sync(1 + w, 192);
        fence_regs(o); fence_regs(p);
        WG_FENCE();
        issue_pv(args.d0 + 3 * SLOT / 16, 1, IC<0>{}, IC<8>{});
        handoff();
        mbar_wait(bar_mod, 0);
        const int tid_ = __shfl_sync(0xffffffffu, tid, lane);
        row_parts();
        row_sums(16);
        t0 = rcp_fast(t0); t1 = rcp_fast(t1);
        anchor(frag, q[0] & q[4] & q[8] & q[12] & q[16] & q[20] & q[24] & q[28] & __float_as_uint(t0) & __float_as_uint(t1) & tid_);
        frag_load(a1, frag + (1 - O2F) * 4096);
        frag_load<0, A2N>(a2, frag + (2 - O2F) * 4096);
        anchor(frag, bad);
        WG_WAIT(0);
        fence_regs(o); fence_regs(p);
        release4(24);
        finish(IC<0>{}, IC<8>{}, 16, [&](int i, uint32_t v0, uint32_t v1, uint32_t v2, uint32_t v3) {
            p[4 * i] = v0; p[4 * i + 1] = v1; p[4 * i + 2] = v2; p[4 * i + 3] = v3; });
        if (A2N < 8) { anchor(frag, p[31] & p[15]); frag_load<A2N, 8>(a2, frag + (2 - O2F) * 4096); }
        bad = __reduce_or_sync(0xffffffffu, bad);
        bad = ((bad | ~(bad >> 8)) >> 1) & 15;
        if (__builtin_expect(bad != 0, 0)) {
            uint8_t* keep = g_keep + (size_t)(rg * 8 + cw) * 4096 + lane * 16;
            frag_store(keep, p);
            attn_fallback(bad, tag, gs, frag, keep, args.wq, args.kc, args.vc);
            frag_load(q, frag + O2F * 8192); frag_load(a1, frag + (1 - O2F) * 4096); frag_load(a2, frag + (2 - O2F) * 4096); frag_load(p, keep);
            anchor(frag, q[0] & q[4] & q[8] & q[12] & q[16] & q[20] & q[24] & q[28] & p[0] & p[4] & p[8] & p[12] & p[16] & p[20] & p[24] & p[28]);
        }
        DBG_T(80);
        DBG_G(124);

        const uint32_t eye = (lane >> 3) == (lane & 3) ? 0x3f80u << ((lane & 4) * 4) : 0;
        auto sum8 = [&](uint32_t* r, const uint4 (&v)[8]) {
            float d[16];
#pragma unroll
            for (int i = 0; i < 16; i++) d[i] = 0.f;
#pragma unroll
            for (int src = 0; src < 8; src++) {
                mma1688(d + 8 * (src & 1), v[src].x, v[src].y, eye);
                mma1688(d + 8 * (src & 1) + 4, v[src].z, v[src].w, eye);
            }
#pragma unroll
            for (int i = 0; i < 4; i++) r[i] = pack_bf16(d[2 * i] + d[8 + 2 * i], d[2 * i + 1] + d[9 + 2 * i]);
        };
        uint4 v2[8], v3[8], wf[23];
        uint2 u4[8], gw[9];
        uint32_t x1[20], xs, pa, ta;
        const uint8_t *mb, *mb4;
        auto load_wf = [&](auto lo, auto hi) {
            const uint32_t wa = sb + SM_Q + ((tid_ & 8) * (D_ / 8) + cw * 16 + (tid_ & 7) + (tid_ & 16) / 2) * 80;
            const uint32_t wb = wa + (512 - cw * 8) * 80 - (tid_ & 16) * 39;
#pragma unroll
            for (int i = lo.value; i < hi.value; i++) wf[i] = ldsm4t(i < 20 ? wa + (i / 5) * 10240 + (i % 5) * 16 : wb + (i - 20) * 32);
        };
        uint32_t at[18];
        {
            float (&u)[32] = reinterpret_cast<float (&)[32]>(o);
            uint32_t off = 0;
            auto turn = [&](const uint32_t (&a)[32], const uint32_t (&b)[32], int acc) {
                uint64_t dv = args.d0 + off * (SLOT / 128);
                bar_sync(1 + w, 192);
                fence_regs(u);
                WG_FENCE();
#pragma unroll
                for (int ks = 0; ks < 16; ks++) {
                    const uint32_t* f = ks < 8 ? &a[4 * ks] : &b[4 * ks - 32];
                    mma_rs64<1>(u, f[0], f[1], f[2], f[3], dv, ks | acc);
                    if (ks == OSPLIT - 1) WG_COMMIT();
                }
                WG_COMMIT();
                WG_WAIT(1);
            };
            auto done = [&]() {
                WG_WAIT(0);
                fence_regs(u);
                release4(off);
                off = (off + 8) & 24;
            };
            auto store = [&](uint8_t* dst) {
#pragma unroll
                for (int i = 0; i < 4; i++)
                    st_relaxed4(dst + i * 512, pack_bf16(u[8 * i], u[8 * i + 1]), pack_bf16(u[8 * i + 2], u[8 * i + 3]),
                                pack_bf16(u[8 * i + 4], u[8 * i + 5]), pack_bf16(u[8 * i + 6], u[8 * i + 7]));
            };
            pa = sb + w * (UNIT - 2048) + tid_ * 16;
#pragma unroll
            for (int i = 0; i < 8; i++) at[i] = 0;
            fence_regs(q); fence_regs(p);
            uint8_t* dst = frag;
#pragma unroll
            for (int i = 0; i < 8; i++) asm volatile("" : "=r"(v2[i].x), "=r"(v2[i].y), "=r"(v2[i].z), "=r"(v2[i].w));
#pragma unroll 1
            for (int k = 0; k < 8; k++, dst += 2048) {
                const uint32_t poff = (off + 8) & 24;
                const bool sum = (0xa0 >> k) & 1;
                turn(q, p, 0);
                handoff();
                auto sum_p = [&](auto lo, auto hi) {
#pragma unroll
                    for (int i = lo.value; i < hi.value; i++) {
                        float a[8], b[8];
#pragma unroll
                        for (int src = 0; src < 8; src++) {
                            const uint32_t x = i == 0 ? v2[src].x : i == 1 ? v2[src].y : i == 2 ? v2[src].z : v2[src].w;
                            a[src] = bf_lo(x); b[src] = bf_hi(x);
                        }
                        at[i] = at[4 + i];
                        at[4 + i] = pack_bf16(((a[0] + a[2]) + (a[4] + a[6])) + ((a[1] + a[3]) + (a[5] + a[7])),
                                              ((b[0] + b[2]) + (b[4] + b[6])) + ((b[1] + b[3]) + (b[5] + b[7])));
                    }
                };
                if (sum) {
                    mbar_wait(bar_full + poff, 1);
#pragma unroll
                    for (int src = 0; src < 8; src++) v2[src] = lds128(pa + poff * (SLOT / 8) + src * 2048);
                    __syncwarp();
                    release(poff >> 3);
                    done();
                    off = (off + 8) & 24;
                    sum_p(IC<0>{}, IC<PS>{});
                } else {
                    done();
                }
                turn(a1, a2, 1);
                handoff();
                if (PS < 4 && sum) sum_p(IC<PS>{}, IC<4>{});
                done();
                store(dst);
                __syncwarp();
                asm volatile("{\n.reg .pred p;\nsetp.ne.b32 p, %1, 0;\n@p mbarrier.arrive.shared::cta.b64 _, [%0];\n}"
                             ::"r"(bar_pub + 4 + 4 * k), "r"(lane ? 0 : (0x2a >> k) & 1) : "memory");
            }
            turn(q, p, 0);
            handoff();
            mb = padd(g_frag, (qb * 64 + j) * WREG + 3 * 4096 + tid_ * 16);
            mb4 = padd(mb, 4096 + ((cw >> 1) - cw) * 512 + (cw & 1) * 8);
            xs = sb + (tid_ & 15) * XP + (tid_ & 16) + cw * 32;
            ta = sb + (cw * 8 + (tid_ & 3)) * 8;
#pragma unroll
            for (int k = 0; k < 9; k++) {
                gw[k] = lds64(ta + SM_T + (k < 8 ? (k >> 1) * 64 + (k & 1) * 4 : 256 - cw * 4) * 8);
                if (!(tid_ & 4)) gw[k].y = 0x3f803f80u;
            }
            mbar_wait(bar_g, 0);
            done();
            load_wf(IC<0>{}, IC<WF0>{});
            turn(a1, a2, 1);
            if (w == 0) handoff();
            if (P2E) {
                mbar_wait(bar_full + 8, 0);
#pragma unroll
                for (int src = 0; src < 8; src++) v2[src] = lds128(pa + SLOT + src * 2048);
            }
            done();
            store(dst);
            mbar_wait(bar_full, 0);
            rows_load(x1, xs, cw);
            if (w == 0) bar_sync(5, 256); else bar_arrive(5, 256);
        }
        DBG_T(81);
        DBG_G(122);

        {
        const int tid = tid_, lane = tid & 31;
        const int g8 = lane >> 2, qd = lane & 3, l16 = lane & 15;
        uint32_t h2[18], gb[9], k1, k2;
        float4* rec = reinterpret_cast<float4*>(red + 128);
        const uint2* candp = reinterpret_cast<const uint2*>(padd(g_cand, ((blockIdx.x & (CREP - 1)) * NCTA + (tid >> 1)) * 32 + (tid & 1) * 8));
        uint2 cd;
        auto stage_out = [&]() {
#pragma unroll
            for (int k = 0; k < 9; k++) {
                x1[2 * k] = badd2(x1[2 * k], bmul2(gb[k], h2[2 * k]));
                x1[2 * k + 1] = badd2(x1[2 * k + 1], bmul2(gb[k], h2[2 * k + 1]));
            }
#pragma unroll
            for (int ch = 0; ch < 4; ch++) stsm_x4(xs + ch * 256, x1[4 * ch], x1[4 * ch + 1], x1[4 * ch + 2], x1[4 * ch + 3]);
            asm volatile("stmatrix.sync.aligned.m8n8.x2.shared.b16 [%0], {%1, %2};" ::"r"(xs + 1024 - cw * 16), "r"(x1[16]), "r"(x1[17]) : "memory");
        };
        {
            uint32_t it = 0, miss;
            if (!P2E) {
                mbar_wait(bar_full + 8, 0);
#pragma unroll
                for (int src = 0; src < 8; src++) v2[src] = lds128(pa + SLOT + src * 2048);
            }
            sum8(at + 8, v2);
            float st[12];
#pragma unroll
            for (int i = 0; i < 12; i++) st[i] = 0.f;
            auto add_pair = [&](int k) {
                x1[2 * k] = badd2(x1[2 * k], bmul2(gw[k].x, at[2 * k]));
                x1[2 * k + 1] = badd2(x1[2 * k + 1], bmul2(gw[k].x, at[2 * k + 1]));
                stats_add(st, x1[2 * k], x1[2 * k + 1], gw[k].y);
            };
#pragma unroll
            for (int k = 0; k < 6; k++) add_pair(k);
            mbar_wait(bar_full + 16, 0);
#pragma unroll
            for (int src = 0; src < 8; src++) v3[src] = lds128(pa + 2 * SLOT + src * 2048);
#pragma unroll 1
            do {
                if (BO && it) __nanosleep(BO);
                miss = 0;
#pragma unroll
                for (int src = 0; src < 8; src++) reload16(v3[src], mb + (size_t)src * 8 * WREG, miss);
            } while (__any_sync(0xffffffffu, miss) && ++it < SPIN / 16);
            if (lane < 4) mbar_arrive_cluster(rel_base + 8 * (1 + (lane >> 1)));
            sum8(at + 12, v3);
            add_pair(6); add_pair(7);
            load_wf(IC<WF0>{}, IC<WF1>{});
            uint2 cs[9];
#pragma unroll
            for (int k = 0; k < 9; k++) cs[k] = lds64(ta + SM_TC + (k < 8 ? (k >> 1) * 64 + (k & 1) * 4 : 256 - cw * 4) * 8);
            mbar_wait(bar_pre, 0);
            mbar_wait(bar_full + 24, 0);
#pragma unroll
            for (int src = 0; src < 8; src++) u4[src] = lds64(sb + 3 * SLOT + src * 2048 + (cw >> 1) * 512 + lane * 16 + (cw & 1) * 8);
#pragma unroll 1
            do {
                if (BO && miss) __nanosleep(BO);
                miss = 0;
#pragma unroll
                for (int src = 0; src < 8; src++) reload8(u4[src], mb4 + (size_t)src * 8 * WREG, miss);
            } while (__any_sync(0xffffffffu, miss) && ++it < SPIN / 16);
            float d[8] = {0.f, 0.f, 0.f, 0.f, 0.f, 0.f, 0.f, 0.f};
#pragma unroll
            for (int i = 0; i < 4; i++) mma16816(d + 4 * (i & 1), u4[2 * i].x, u4[2 * i].y, u4[2 * i + 1].x, u4[2 * i + 1].y, eye, eye);
            at[16] = pack_bf16(d[0] + d[4], d[1] + d[5]); at[17] = pack_bf16(d[2] + d[6], d[3] + d[7]);
            add_pair(8);
            DBG_G(123);
            const float2 ws = *reinterpret_cast<const float2*>(smem_raw + SM_TS);
            uint4* cdst = padd(g_cand, CFULL ? ((tid >> 1) * NCTA + rg) * 32 + (tid & 1) * 16 : (tid * NCTA + rg) * 32);
            uint32_t mean2;
            float dot;
            const float rsd = rows_stats(st, rec, cw, lane, mean2, dot);
            const uint32_t b = __float_as_uint(fmaf(fmaf(-bf_lo(mean2), ws.x, dot), rsd, ws.y));
            const uint32_t key = (((b & 0x80000000u) ? ~b : (b | 0x80000000u)) | 2047u) - (rg * 16 + l16);
            top2(key, k1, k2);
            if (tid < (CFULL + 1) * CREP) st_relaxed(cdst, k1, tag, k2, tag);
            cd = ld_relaxed64(candp);
            rows_normalise(h2, x1, mean2, rsd, lane, [&]() {
#pragma unroll
                for (int k = 0; k < 9; k++) gb[k] = lds32(sb + SM_TG + (cw * 8 + qd + (k < 8 ? (k >> 1) * 64 + (k & 1) * 4 : 256 - cw * 4)) * 4);
                if (WFE) load_wf(IC<WF1>{}, IC<WF2>{});
            });
#pragma unroll
            for (int k = 0; k < 18; k++) h2[k] = badd2(bmul2(h2[k], cs[k >> 1].x), cs[k >> 1].y);
            const uint32_t r1 = ~k1 & 15, r2 = ~k2 & 15;
            uint32_t todo = ((r1 & 7) == g8) | ((r2 & 7) == g8) << 1;
#pragma unroll 1
            while (todo) {
                const bool second = !(todo & 1), hi = (second ? r2 : r1) & 8;
                uint4* dst = padd(g_rows, ((rg * 2 + second) * RSLOT + cw * 24 + qd) * 16);
                uint32_t r[18];
#pragma unroll
                for (int k = 0; k < 9; k++) { r[k] = hi ? h2[2 * k + 1] : h2[2 * k]; r[9 + k] = hi ? x1[2 * k + 1] : x1[2 * k]; }
                fence_regs(r);
                st_relaxed(dst, r[0], r[1], r[2], r[3]);
                st_relaxed(dst + 8, r[4], r[5], r[6], r[7]);
                st_relaxed64(reinterpret_cast<uint2*>(padd(dst, 256 - qd * 8)), r[8], r[17]);
                st_relaxed(dst + 4, r[9], r[10], r[11], r[12]);
                st_relaxed(dst + 12, r[13], r[14], r[15], r[16]);
                todo &= todo - 1;
            }
            __syncwarp();

            stage_out();
            if (!WFE) load_wf(IC<WF1>{}, IC<WF2>{});
        }
        DBG_G(110);
        float4* part = reinterpret_cast<float4*>(smem_raw + 3 * SLOT + UNIT + 8192);
        bf16* act = reinterpret_cast<bf16*>(smem_raw + 3 * SLOT + UNIT + 4096);
        {
            uint32_t it = 0;
            const bool own = (tid >> 1) == rg;
            const uint32_t ks = sb + 3 * SLOT + UNIT + 5120;
#pragma unroll 1
            while (cd.y != tag && !own && ++it < SPIN / 16) cd = ld_relaxed64(candp);
            asm volatile("st.shared.u32 [%0], %1;" ::"r"(ks + tid * 4), "r"(own ? (tid & 1) ? k2 : k1 : cd.x) : "memory");
            bar_sync(3, 256);
            DBG_G(111);
            const uint4 a = lds128(ks + lane * 16), b = lds128(ks + 512 + lane * 16);
            const uint32_t a1 = max(a.x, a.z), a2 = __vimax3_u32(min(a.x, a.z), a.y, a.w);
            const uint32_t b1 = max(b.x, b.z), b2 = __vimax3_u32(min(b.x, b.z), b.y, b.w);
            const uint32_t c1 = max(a1, b1), c2 = __vimax3_u32(min(a1, b1), a2, b2);
            k1 = __reduce_max_sync(0xffffffffu, c1);
            k2 = __reduce_max_sync(0xffffffffu, c1 == k1 ? c2 : c1);
        }
        const int sel0 = ~k1 & 2047, sel1 = ~k2 & 2047;
        const uint32_t slot0 = (sel0 >> 4) * 2, slot1 = (sel1 >> 4) * 2 + ((sel0 ^ sel1) < 16);
        uint4 da[13];
        {
            const uint4* hp = padd(g_rows, (((g8 & 1) ? slot1 : slot0) * RSLOT + cw * 24 + qd) * 16);
            const uint2* hp2 = reinterpret_cast<const uint2*>(padd(hp, 256 - qd * 8));
            uint4 hv[2] = {ld_relaxed2(hp), ld_relaxed2(hp + 8)};
            uint2 hw = ld_relaxed64(hp2);
            if (tid == 255) {
                reinterpret_cast<int2*>(red)[8] = make_int2(sel0, sel1);
                mbar_arrive(bar_out);
            }
            load_wf(IC<WF2>{}, IC<23>{});
            mbar_wait(bar_full + 8, 1);
            mbar_wait(bar_full + 16, 1);
            auto load_d = [&](auto lo, auto hi) {
                const int r = (lane & 7) + (lane & 16) / 2;
                const uint32_t d0 = sb + SLOT + r * XP + cw * 144 + (lane & 8) * 2, d1 = d0 + (r < 2 ? 16 * XP : SLOT - 2 * XP);
                const uint32_t d2 = sb + 2 * SLOT + (14 + (lane & 3)) * XP + cw * 144 + (lane >> 3) * 16;
#pragma unroll
                for (int i = lo.value; i < hi.value; i++) da[i] = ldsm4t(i < 10 ? ((i & 1) ? d1 : d0) + (i >> 1) * 32 : d2 + (i - 10) * 64);
            };
            load_d(IC<0>{}, IC<DL>{});
            uint32_t it = 0, miss;
#pragma unroll 1
            do {
                miss = 0;
                reload16(hv[0], hp, miss);
                reload16(hv[1], hp + 8, miss);
                reload8(hw, hp2, miss);
            } while (__any_sync(0xffffffffu, miss) && ++it < SPIN / 16);
            DBG_G(112);
            load_d(IC<DL>{}, IC<13>{});
            float acc[20];
#pragma unroll
            for (int i = 0; i < 20; i++) acc[i] = 0.f;
#pragma unroll
            for (int i = 0; i < 5; i++) mma1688(acc + 4 * i, (i & 1) ? wf[20 + i / 2].z : wf[20 + i / 2].x, (i & 1) ? wf[20 + i / 2].w : wf[20 + i / 2].y, hw.x);
#pragma unroll
            for (int i = 0; i < 20; i++)
                mma16816(acc + 4 * (i % 5), wf[i].x, wf[i].y, wf[i].z, wf[i].w, (i / 5 & 1) ? hv[i / 10].z : hv[i / 10].x, (i / 5 & 1) ? hv[i / 10].w : hv[i / 10].y);
            if (qd == 0) {
#pragma unroll
                for (int i = 0; i < 5; i++) part[cw * 40 + i * 8 + g8] = make_float4(acc[4 * i], acc[4 * i + 1], acc[4 * i + 2], acc[4 * i + 3]);
            }
        }
        {
            uint2* dst = padd(g_ypart, ((cw * 9 * NCTA + blockIdx.x) * 8 + g8) * 8);
            bar_sync(3, 256);
            if (cw < 5) {
                const float* pp = reinterpret_cast<const float*>(part) + ((blockIdx.x & 1) << 4) + tid;
                const float g = rbf(((pp[0] + pp[160]) + (pp[320] + pp[480])) + ((pp[640] + pp[800]) + (pp[960] + pp[1120])));
                const float v = rbf(g * sigmoidf_(g)) * __shfl_down_sync(0xffffffffu, g, 2);
                if (!(tid & 2)) act[(tid & 1) * 56 + (tid >> 2)] = __float2bfloat16_rn(tid < 144 ? v : 0.f);
            }
            bar_sync(3, 256);
            DBG_G(113);
            const uint32_t ap = sb + 3 * SLOT + UNIT + 4096 + (lane & 1) * 112 + (lane >> 3) * 16;
            const uint4 b0 = ldsm4(ap);
            const uint32_t b1 = lds32(sb + 3 * SLOT + UNIT + 4096 + (g8 & 1) * 112 + 64 + qd * 4);
            float y[20];
#pragma unroll
            for (int i = 0; i < 20; i++) y[i] = 0.f;
#pragma unroll
            for (int i = 0; i < 5; i++) {
                mma16816(y + 4 * i, da[2 * i].x, da[2 * i].y, da[2 * i].z, da[2 * i].w, b0.x, b0.y);
                mma16816(y + 4 * i, da[2 * i + 1].x, da[2 * i + 1].y, da[2 * i + 1].z, da[2 * i + 1].w, b0.z, b0.w);
                mma1688(y + 4 * i, (i & 1) ? da[10 + i / 2].z : da[10 + i / 2].x, (i & 1) ? da[10 + i / 2].w : da[10 + i / 2].y, b1);
            }
#pragma unroll
            for (int i = 0; i < 9; i++)
                asm volatile("{\n.reg .pred p;\nsetp.eq.b32 p, %3, 0;\n@p st.relaxed.gpu.global.v2.f32 [%0], {%1, %2};\n}"
                             ::"l"(dst + i * (NCTA * 8)), "f"(y[2 * i]), "f"(y[2 * i + 1]), "r"(qd) : "memory");
        }
        DBG_G(114);
        if (blockIdx.x == 127 && tid == 0) gs->epoch[0] = tag;
        if (blockIdx.x < 72) {
            const int G = blockIdx.x, tok = g8 & 1, cp = G * 4 + qd;
            const uint2* src = padd(g_ypart, (blockIdx.x * NCTA * 8 + tid) * 8);
            const uint8_t* hsrc = reinterpret_cast<const uint8_t*>(padd(g_rows, (tok ? slot1 : slot0) * (RSLOT * 16) +
                (G < 64 ? (G >> 1 & 7) * 384 + (G >> 5) * 128 + qd * 16 + (G >> 1 & 8) + (G & 1) * 4 : (G - 64) * 384 + 256 + qd * 8)));
            const uint8_t* xsrc = hsrc + (G < 64 ? 64 : 4);
            uint32_t* dst = padd(reinterpret_cast<uint32_t*>(args.out), (tok ? sel1 : sel0) * (D_ * 2) + cp * 4);
            const uint32_t gb = reinterpret_cast<const uint32_t*>(smem_raw + SM_TG)[cp];
            const uint32_t ksel = ((tok ? k2 : k1) & ~2047u) | 1024u;
            const float sg = sigmoidf_(rbf(__uint_as_float((ksel & 0x80000000u) ? (ksel & 0x7fffffffu) : ~ksel)));
            uint2 v[4];
            uint32_t hv, xv, it = 0;
            bool miss;
#pragma unroll 1
            do {
#pragma unroll
                for (int i = 0; i < 4; i++) v[i] = ld_relaxed64(src + i * 256);
                hv = ld_relaxed32(hsrc);
                xv = ld_relaxed32(xsrc);
                miss = max(__vimax3_u32(v[0].x, v[1].x, v[2].x), __vimax3_u32(v[3].x, hv, xv)) == ~0u;
            } while (__any_sync(0xffffffffu, miss) && ++it < SPIN / 16);
            float y0 = (__uint_as_float(v[0].x) + __uint_as_float(v[1].x)) + (__uint_as_float(v[2].x) + __uint_as_float(v[3].x));
            float y1 = (__uint_as_float(v[0].y) + __uint_as_float(v[1].y)) + (__uint_as_float(v[2].y) + __uint_as_float(v[3].y));
            y0 += __shfl_xor_sync(0xffffffffu, y0, 8); y1 += __shfl_xor_sync(0xffffffffu, y1, 8);
            y0 += __shfl_xor_sync(0xffffffffu, y0, 16); y1 += __shfl_xor_sync(0xffffffffu, y1, 16);
            if (lane < 8) reinterpret_cast<float2*>(rec)[cw * 8 + lane] = make_float2(y0, y1);
            bar_sync(3, 256);
            if (cw == 0) {
                const float4 t0_ = rec[(lane >> 3) * 4 + qd], t1_ = rec[16 + (lane >> 3) * 4 + qd];
                y0 = tok ? t0_.y + t1_.y : t0_.x + t1_.x; y1 = tok ? t0_.w + t1_.w : t0_.z + t1_.z;
                y0 += __shfl_xor_sync(0xffffffffu, y0, 8); y1 += __shfl_xor_sync(0xffffffffu, y1, 8);
                y0 += __shfl_xor_sync(0xffffffffu, y0, 16); y1 += __shfl_xor_sync(0xffffffffu, y1, 16);
                const uint32_t y2 = bmul2(pack_bf16(y0, y1), pack_bf16(sg, sg));
                if (lane < 8) *dst = badd2(xv, bmul2(gb, badd2(hv, y2)));
            }
        }
        }
        DBG_T(88);
        DBG_G(121);
    }
}

typedef CUresult (*EncodeFn)(CUtensorMap*, CUtensorMapDataType, cuuint32_t, void*, const cuuint64_t*, const cuuint64_t*,
                             const cuuint32_t*, const cuuint32_t*, CUtensorMapInterleave, CUtensorMapSwizzle,
                             CUtensorMapL2promotion, CUtensorMapFloatOOBfill);

static void make_map(EncodeFn enc, CUtensorMap* m, const void* ptr, int rank, const cuuint64_t* dims,
                     const cuuint64_t* strides, const cuuint32_t* box, CUtensorMapSwizzle sw = CU_TENSOR_MAP_SWIZZLE_128B,
                     CUtensorMapDataType dt = CU_TENSOR_MAP_DATA_TYPE_BFLOAT16) {
    const cuuint32_t es[3] = {1, 1, 1};
    enc(m, dt, rank, const_cast<void*>(ptr), dims, strides, box, es,
        CU_TENSOR_MAP_INTERLEAVE_NONE, sw, CU_TENSOR_MAP_L2_PROMOTION_L2_128B,
        CU_TENSOR_MAP_FLOAT_OOB_FILL_NONE);
}

extern "C" void kernel_launch(void* const* d_in, const int* in_sizes, int n_in, void* d_out, int out_size) {
    const bf16* x = (const bf16*)d_in[0];
    const bf16* kc = (const bf16*)d_in[1];
    const bf16* vc = (const bf16*)d_in[2];
    const bf16* wq = (const bf16*)d_in[3];
    const bf16* wo = (const bf16*)d_in[4];
    const bf16* w_r = (const bf16*)d_in[6];
    const bf16* w_gate = (const bf16*)d_in[7];
    const bf16* w_up = (const bf16*)d_in[8];
    const bf16* w_down = (const bf16*)d_in[9];
    const bf16* cvec = (const bf16*)d_in[10];
    const bf16* w_mod = (const bf16*)d_in[11];
    bf16* out = (bf16*)d_out;

    void* fn = nullptr;
    cudaDriverEntryPointQueryResult qr;
    cudaGetDriverEntryPoint("cuTensorMapEncodeTiled", &fn, cudaEnableDefault, &qr);
    EncodeFn enc = (EncodeFn)fn;
    void* p_s;
    cudaGetSymbolAddress(&p_s, g_s);

    CUtensorMap tm_wq, tm_k, tm_v, tm_wo, tm_p, tm_x, tm_d, tm_g, tm_u;
    { cuuint64_t d[2] = {QD, D_}, s[1] = {QD * 2}; cuuint32_t b[2] = {64, 128}; make_map(enc, &tm_wq, wq, 2, d, s, b); }
    { cuuint64_t d[2] = {DH, HKV * S_}, s[1] = {DH * 2}; cuuint32_t b[2] = {64, 128};
      make_map(enc, &tm_k, kc, 2, d, s, b); make_map(enc, &tm_v, vc, 2, d, s, b); }
    { cuuint64_t d[2] = {D_, QD}, s[1] = {D_ * 2}; cuuint32_t b[2] = {64, 128}; make_map(enc, &tm_wo, wo, 2, d, s, b); }
    { cuuint64_t d[3] = {256, 160, NCTA}, s[2] = {1024, 8 * WREG}; cuuint32_t b[3] = {256, 2, 8};
      make_map(enc, &tm_p, ((Scratch*)p_s)->frag, 3, d, s, b, CU_TENSOR_MAP_SWIZZLE_NONE, CU_TENSOR_MAP_DATA_TYPE_UINT32); }
    { cuuint64_t d[2] = {D_ / 4, S_}, s[1] = {D_ * 2}; cuuint32_t b[2] = {XP / 8, 16};
      make_map(enc, &tm_x, x, 2, d, s, b, CU_TENSOR_MAP_SWIZZLE_NONE, CU_TENSOR_MAP_DATA_TYPE_UINT64); }
    { cuuint64_t d[2] = {D_ / 4, F_}, s[1] = {D_ * 2}; cuuint32_t b[2] = {XP / 8, 18};
      make_map(enc, &tm_d, w_down, 2, d, s, b, CU_TENSOR_MAP_SWIZZLE_NONE, CU_TENSOR_MAP_DATA_TYPE_UINT64); }
    { cuuint64_t d[2] = {F_, D_}, s[1] = {F_ * 2}; cuuint32_t b[2] = {40, 24};
      make_map(enc, &tm_g, w_gate, 2, d, s, b, CU_TENSOR_MAP_SWIZZLE_NONE); make_map(enc, &tm_u, w_up, 2, d, s, b, CU_TENSOR_MAP_SWIZZLE_NONE); }

    cudaFuncSetAttribute(fused_kernel<true>, cudaFuncAttributeMaxDynamicSharedMemorySize, SM_TOTAL);
    cudaFuncSetAttribute(fused_kernel<false>, cudaFuncAttributeMaxDynamicSharedMemorySize, SM_TOTAL);
    cudaLaunchConfig_t cfg = {};
    cfg.gridDim = NCTA + 4; cfg.blockDim = 384; cfg.dynamicSmemBytes = SM_TOTAL;
    cudaLaunchAttribute at;
    at.id = cudaLaunchAttributeClusterDimension; at.val.clusterDim.x = 2; at.val.clusterDim.y = 1; at.val.clusterDim.z = 1;
    cfg.attrs = &at; cfg.numAttrs = 1;
    int ncl = 0;
    if (cudaOccupancyMaxActiveClusters(&ncl, fused_kernel<true>, &cfg) != cudaSuccess) { ncl = 0; cudaGetLastError(); }
    Args args{w_mod, cvec, (Scratch*)p_s, desc_lo(0, UNIT) | (0x40000040ull << 32), out, x, kc, vc, wq, wo, w_r, w_down};
    if (USE_SPARE && ncl >= NCTA / 2 + 2)
        fused_kernel<true><<<NCTA + 4, 384, SM_TOTAL>>>(args, tm_wq, tm_k, tm_v, tm_wo, tm_p, tm_x, tm_d, tm_g, tm_u);
    else
        fused_kernel<false><<<NCTA, 384, SM_TOTAL>>>(args, tm_wq, tm_k, tm_v, tm_wo, tm_p, tm_x, tm_d, tm_g, tm_u);
}
```

```cpp
#include <cuda_runtime.h>
#include <cuda_bf16.h>
#include <cuda.h>
#include <stdint.h>
#include <math.h>

typedef __nv_bfloat16 bf16;

constexpr int S_ = 2048;
constexpr int D_ = 576;
constexpr int HQ = 32, HKV = 16, DH = 128;
constexpr int F_ = 4608;
constexpr int QD = HQ * DH;

constexpr int NCTA = 128;
constexpr int WREG = 5 * 4096;
constexpr int CREP = 8;
constexpr int RSLOT = 192;
constexpr int MREP = 4;
struct Scratch {
    unsigned int epoch[128];
    unsigned int flag_mod[NCTA];
    unsigned int flag_part[16 * 32];
    unsigned int flag_q3[16 * 32];
    unsigned int flag_h[NCTA * 32];
    uint2 mod1[MREP * D_];
    uint32_t mod2[4 * D_];
    uint4 cand[CREP * NCTA * 2];
    uint2 ypart[72 * NCTA * 8];
    uint4 h[2][NCTA * 36 * 32];
    uint4 q3[NCTA * 8 * 128];
    uint4 rows[NCTA * 2 * RSLOT];
    uint8_t frag[NCTA * 8 * WREG];
    uint8_t keep[NCTA * 8 * 4096];
};
__device__ __align__(1024) Scratch g_s;
#define g_h gs->h[tag & 1]
#define g_q3 gs->q3
#define g_keep gs->keep
#define g_flag_h gs->flag_h
#define g_flag_part gs->flag_part
#define g_flag_mod gs->flag_mod
#define g_flag_q3 gs->flag_q3
#define g_frag gs->frag
#define g_cand gs->cand
#define g_ypart gs->ypart
#define g_rows gs->rows

#define DBG_INIT()
#define DBG_P(i)
#define DBG_PG(i)
#define DBG_T(i)
#define DBG_G(i)

__device__ __forceinline__ uint32_t pack_bf16(float lo, float hi) {
    uint32_t r;
    asm("cvt.rn.bf16x2.f32 %0, %1, %2;" : "=r"(r) : "f"(hi), "f"(lo));
    return r;
}
__device__ __forceinline__ float rbf(float x) { return __uint_as_float(pack_bf16(0.f, x)); }
__device__ __forceinline__ float bf_lo(uint32_t v) { return __uint_as_float(v << 16); }
__device__ __forceinline__ float bf_hi(uint32_t v) { return __uint_as_float(v & 0xffff0000u); }
__device__ __forceinline__ float ex2(float x) {
    float y;
    asm("ex2.approx.ftz.f32 %0, %1;" : "=f"(y) : "f"(x));
    return y;
}
template <class T>
__device__ __forceinline__ T* padd(T* p, uint32_t off) {
    unsigned long long r;
    asm("{\n.reg .b32 l, h;\nmov.b64 {l, h}, %1;\nadd.cc.u32 l, l, %2;\naddc.u32 h, h, 0;\nmov.b64 %0, {l, h};\n}" : "=l"(r) : "l"(p), "r"(off));
    return reinterpret_cast<T*>(r);
}
__device__ __forceinline__ uint32_t smem_u32(const void* p) { return (uint32_t)__cvta_generic_to_shared(p); }
__device__ __forceinline__ void mbar_init(uint32_t bar, uint32_t cnt) {
    asm volatile("mbarrier.init.shared::cta.b64 [%0], %1;" ::"r"(bar), "r"(cnt) : "memory");
}
__device__ __forceinline__ void mbar_expect_tx(uint32_t bar, uint32_t bytes) {
    asm volatile("mbarrier.arrive.expect_tx.shared::cta.b64 _, [%0], %1;" ::"r"(bar), "r"(bytes) : "memory");
}
__device__ __forceinline__ void mbar_arrive(uint32_t bar) {
    asm volatile("mbarrier.arrive.shared::cta.b64 _, [%0];" ::"r"(bar) : "memory");
}
__device__ __forceinline__ void mbar_arrive_cluster(uint32_t cluster_addr) {
    asm volatile("mbarrier.arrive.shared::cluster.b64 _, [%0];" ::"r"(cluster_addr) : "memory");
}
constexpr uint32_t SPIN = 1u << 20;
__device__ __forceinline__ void mbar_wait(uint32_t bar, uint32_t parity) {
    asm volatile("{\n.reg .pred p;\n.reg .b32 c;\nmov.b32 c, 0;\n"
                 "W_%=:\nmbarrier.try_wait.parity.shared::cta.b64 p, [%0], %1;\n"
                 "add.u32 c, c, 1;\nsetp.lt.and.u32 p, c, 0x100000, !p;\n@p bra W_%=;\n}"
                 ::"r"(bar), "r"(parity) : "memory");
}
__device__ __forceinline__ void anchor(uint32_t addr, float v) {
    asm volatile("{\n.reg .pred p;\nsetp.lt.f32 p, %1, 0f00000000;\n@p st.volatile.shared.f32 [%0], %1;\n}" ::"r"(addr), "f"(v) : "memory");
}
__device__ __forceinline__ void anchor(uint32_t addr, uint32_t v) {
    asm volatile("{\n.reg .pred p;\nsetp.eq.u32 p, %1, 0xffffffff;\n@p st.volatile.shared.u32 [%0], %1;\n}" ::"r"(addr), "r"(v) : "memory");
}
__device__ __forceinline__ void anchor(void* p, uint32_t v) {
    asm volatile("{\n.reg .pred p;\nsetp.eq.u32 p, %1, 0xffffffff;\n@p st.volatile.u32 [%0], %1;\n}" ::"l"(p), "r"(v) : "memory");
}
__device__ __forceinline__ void hold(float& a, float& b) {
    asm volatile("{\n.reg .pred p;\n.reg .b64 t;\n.reg .b32 l, h;\nmov.u64 t, %%clock64;\nmov.b64 {l, h}, t;\nsetp.eq.u32 p, h, 0xffffffff;\n"
                 "@p mov.f32 %0, 0f00000000;\n@p mov.f32 %1, 0f00000000;\n}" : "+f"(a), "+f"(b) :: "memory");
}
__device__ __forceinline__ void mbar_wait_sleep(uint32_t bar, uint32_t parity) {
    asm volatile("{\n.reg .pred p;\n.reg .b32 c;\nmov.b32 c, 0;\n"
                 "W_%=:\nmbarrier.try_wait.parity.shared::cta.b64 p, [%0], %1, 5000;\n"
                 "add.u32 c, c, 1;\nsetp.lt.and.u32 p, c, 0x20000, !p;\n@p bra W_%=;\n}"
                 ::"r"(bar), "r"(parity) : "memory");
}
__device__ __forceinline__ uint32_t load_tag(const Scratch* gs) {
    uint32_t tag;
    asm volatile("ld.global.ca.u32 %0, [%1];" : "=r"(tag) : "l"(gs->epoch) : "memory");
    return tag + 1;
}
__device__ __forceinline__ uint4 ld_relaxed(const uint4* p) {
    uint4 v;
    asm volatile("ld.relaxed.gpu.global.v4.u32 {%0,%1,%2,%3}, [%4];" : "=r"(v.x), "=r"(v.y), "=r"(v.z), "=r"(v.w) : "l"(p) : "memory");
    return v;
}
__device__ __forceinline__ void st_relaxed(uint4* p, uint32_t a, uint32_t b, uint32_t c, uint32_t d) {
    asm volatile("{\n.reg .b64 u, v;\nmov.b64 u, {%1, %2};\nmov.b64 v, {%3, %4};\nst.relaxed.gpu.global.v2.b64 [%0], {u, v};\n}"
                 ::"l"(p), "r"(a), "r"(b), "r"(c), "r"(d) : "memory");
}
__device__ __forceinline__ void st_relaxed4(void* p, uint32_t a, uint32_t b, uint32_t c, uint32_t d) {
    asm volatile("st.relaxed.gpu.global.v4.u32 [%0], {%1, %2, %3, %4};" ::"l"(p), "r"(a), "r"(b), "r"(c), "r"(d) : "memory");
}
__device__ __forceinline__ uint2 ld_relaxed64(const uint2* p) {
    uint2 v;
    asm volatile("{\n.reg .b64 u;\nld.relaxed.gpu.global.b64 u, [%2];\nmov.b64 {%0, %1}, u;\n}" : "=r"(v.x), "=r"(v.y) : "l"(p) : "memory");
    return v;
}
__device__ __forceinline__ void st_relaxed64(uint2* p, uint32_t a, uint32_t b) {
    asm volatile("{\n.reg .b64 u;\nmov.b64 u, {%1, %2};\nst.relaxed.gpu.global.b64 [%0], u;\n}" ::"l"(p), "r"(a), "r"(b) : "memory");
}
__device__ __forceinline__ uint4 ld_relaxed2(const uint4* p) {
    uint4 v;
    asm volatile("{\n.reg .b64 u, w;\nld.relaxed.gpu.global.v2.b64 {u, w}, [%4];\nmov.b64 {%0, %1}, u;\nmov.b64 {%2, %3}, w;\n}"
                 : "=r"(v.x), "=r"(v.y), "=r"(v.z), "=r"(v.w) : "l"(p) : "memory");
    return v;
}
__device__ __forceinline__ void reload16(uint4& v, const void* p, uint32_t& miss) {
    asm volatile("{\n.reg .pred p;\n.reg .b32 m;\n.reg .b64 u, w;\nmax.u32 m, %0, %2;\nsetp.eq.u32 p, m, 0xffffffff;\n"
                 "mov.b64 u, {%0, %1};\nmov.b64 w, {%2, %3};\n@p ld.relaxed.gpu.global.v2.b64 {u, w}, [%5];\n"
                 "mov.b64 {%0, %1}, u;\nmov.b64 {%2, %3}, w;\n@p mov.u32 %4, 1;\n}"
                 : "+r"(v.x), "+r"(v.y), "+r"(v.z), "+r"(v.w), "+r"(miss) : "l"(p) : "memory");
}
__device__ __forceinline__ void reload8(uint2& v, const void* p, uint32_t& miss) {
    asm volatile("{\n.reg .pred p;\n.reg .b64 u;\nsetp.eq.u32 p, %0, 0xffffffff;\nmov.b64 u, {%0, %1};\n"
                 "@p ld.relaxed.gpu.global.b64 u, [%3];\nmov.b64 {%0, %1}, u;\n@p mov.u32 %2, 1;\n}"
                 : "+r"(v.x), "+r"(v.y), "+r"(miss) : "l"(p) : "memory");
}
__device__ __forceinline__ uint32_t ld_relaxed32(const void* p) {
    uint32_t v;
    asm volatile("ld.relaxed.gpu.global.u32 %0, [%1];" : "=r"(v) : "l"(p) : "memory");
    return v;
}
__device__ __forceinline__ void flag_wait(const unsigned int* p, uint32_t tag) {
    uint32_t v, it = 0;
#pragma unroll 1
    do {
        asm volatile("ld.relaxed.gpu.global.u32 %0, [%1];" : "=r"(v) : "l"(p) : "memory");
    } while (__any_sync(0xffffffffu, v != tag) && ++it < SPIN / 16);
    asm volatile("fence.acquire.gpu;" ::: "memory");
    __syncwarp();
}
__device__ __forceinline__ bool elect() {
    uint32_t p;
    asm volatile("{\n.reg .pred p;\nelect.sync _|p, 0xffffffff;\nselp.u32 %0, 1, 0, p;\n}" : "=r"(p));
    return p;
}
__device__ __forceinline__ void flag_release(unsigned int* p, uint32_t tag) {
    asm volatile("st.release.gpu.global.u32 [%0], %1;" ::"l"(p), "r"(tag) : "memory");
}
__device__ __forceinline__ uint32_t touch(const void* p) {
    uint32_t v;
    asm volatile("ld.global.nc.L1::no_allocate.L2::128B.u32 %0, [%1];" : "=r"(v) : "l"(p));
    return v;
}
__device__ __forceinline__ void bar_sync(int id, int n) { asm volatile("bar.sync %0, %1;" ::"r"(id), "r"(n) : "memory"); }
__device__ __forceinline__ void bar_arrive(int id, int n) { asm volatile("bar.arrive %0, %1;" ::"r"(id), "r"(n) : "memory"); }

constexpr uint64_t EVICT_NORMAL = 0x1000000000000000ull, EVICT_FIRST = 0x12F0000000000000ull;
__device__ __forceinline__ void tma2d(uint32_t dst, const CUtensorMap* m, int c0, int c1, uint32_t bar) {
    asm volatile("cp.async.bulk.tensor.2d.shared::cluster.global.mbarrier::complete_tx::bytes.L2::cache_hint [%0], [%1, {%3, %4}], [%2], %5;"
                 ::"r"(dst), "l"(m), "r"(bar), "r"(c0), "r"(c1), "l"(EVICT_FIRST) : "memory");
}
__device__ __forceinline__ void tma2d_mc(uint32_t dst, const CUtensorMap* m, int c0, int c1, uint32_t bar, uint64_t pol) {
    asm volatile("cp.async.bulk.tensor.2d.shared::cluster.global.mbarrier::complete_tx::bytes.multicast::cluster.L2::cache_hint [%0], [%1, {%3, %4}], [%2], %5, %6;"
                 ::"r"(dst), "l"(m), "r"(bar), "r"(c0), "r"(c1), "h"((uint16_t)3), "l"(pol) : "memory");
}
__device__ __forceinline__ void tma3d(uint32_t dst, const CUtensorMap* m, int c0, int c1, int c2, uint32_t bar) {
    asm volatile("cp.async.bulk.tensor.3d.shared::cluster.global.mbarrier::complete_tx::bytes.L2::cache_hint [%0], [%1, {%3, %4, %5}], [%2], %6;"
                 ::"r"(dst), "l"(m), "r"(bar), "r"(c0), "r"(c1), "r"(c2), "l"(EVICT_FIRST) : "memory");
}
__device__ __forceinline__ void bulk_load(uint32_t dst, const void* src, uint32_t bytes, uint32_t bar) {
    asm volatile("cp.async.bulk.shared::cluster.global.mbarrier::complete_tx::bytes [%0], [%1], %2, [%3];"
                 ::"r"(dst), "l"(src), "r"(bytes), "r"(bar) : "memory");
}
__device__ __forceinline__ void l2_prefetch(const void* src, uint32_t bytes) {
    asm volatile("cp.async.bulk.prefetch.L2.global [%0], %1;" ::"l"(src), "r"(bytes) : "memory");
}
__device__ __forceinline__ uint32_t bmul2(uint32_t a, uint32_t b) { uint32_t r; asm("mul.rn.bf16x2 %0, %1, %2;" : "=r"(r) : "r"(a), "r"(b)); return r; }
__device__ __forceinline__ uint32_t badd2(uint32_t a, uint32_t b) { uint32_t r; asm("add.rn.bf16x2 %0, %1, %2;" : "=r"(r) : "r"(a), "r"(b)); return r; }
__device__ __forceinline__ uint32_t bsub2(uint32_t a, uint32_t b) { uint32_t r; asm("sub.rn.bf16x2 %0, %1, %2;" : "=r"(r) : "r"(a), "r"(b)); return r; }
__device__ __forceinline__ uint32_t bmax2(uint32_t a, uint32_t b) { uint32_t r; asm("max.bf16x2 %0, %1, %2;" : "=r"(r) : "r"(a), "r"(b)); return r; }
__device__ __forceinline__ uint4 lds128(uint32_t a) { uint4 v; asm volatile("ld.shared.v4.u32 {%0,%1,%2,%3}, [%4];" : "=r"(v.x), "=r"(v.y), "=r"(v.z), "=r"(v.w) : "r"(a) : "memory"); return v; }
__device__ __forceinline__ uint2 lds64(uint32_t a) { uint2 v; asm volatile("ld.shared.v2.u32 {%0,%1}, [%2];" : "=r"(v.x), "=r"(v.y) : "r"(a) : "memory"); return v; }
__device__ __forceinline__ uint32_t lds32(uint32_t a) { uint32_t v; asm volatile("ld.shared.u32 %0, [%1];" : "=r"(v) : "r"(a) : "memory"); return v; }
__device__ __forceinline__ uint4 ldsm4(uint32_t a) {
    uint4 v;
    asm volatile("ldmatrix.sync.aligned.m8n8.x4.shared.b16 {%0,%1,%2,%3}, [%4];" : "=r"(v.x), "=r"(v.y), "=r"(v.z), "=r"(v.w) : "r"(a) : "memory");
    return v;
}
__device__ __forceinline__ uint4 ldsm4t(uint32_t a) {
    uint4 v;
    asm volatile("ldmatrix.sync.aligned.m8n8.x4.trans.shared.b16 {%0,%1,%2,%3}, [%4];" : "=r"(v.x), "=r"(v.y), "=r"(v.z), "=r"(v.w) : "r"(a) : "memory");
    return v;
}
__device__ __forceinline__ void mma1688(float* d, uint32_t a0, uint32_t a1, uint32_t b) {
    asm("mma.sync.aligned.m16n8k8.row.col.f32.bf16.bf16.f32 {%0,%1,%2,%3}, {%4,%5}, {%6}, {%0,%1,%2,%3};"
        : "+f"(d[0]), "+f"(d[1]), "+f"(d[2]), "+f"(d[3]) : "r"(a0), "r"(a1), "r"(b));
}
__device__ __forceinline__ void mma16816(float* d, uint32_t a0, uint32_t a1, uint32_t a2, uint32_t a3, uint32_t b0, uint32_t b1) {
    asm("mma.sync.aligned.m16n8k16.row.col.f32.bf16.bf16.f32 {%0,%1,%2,%3}, {%4,%5,%6,%7}, {%8,%9}, {%0,%1,%2,%3};"
                 : "+f"(d[0]), "+f"(d[1]), "+f"(d[2]), "+f"(d[3]) : "r"(a0), "r"(a1), "r"(a2), "r"(a3), "r"(b0), "r"(b1));
}
__device__ __forceinline__ void stsm_x4(uint32_t addr, uint32_t a, uint32_t b, uint32_t c, uint32_t d) {
    asm volatile("stmatrix.sync.aligned.m8n8.x4.shared.b16 [%0], {%1, %2, %3, %4};"
                 ::"r"(addr), "r"(a), "r"(b), "r"(c), "r"(d) : "memory");
}

__device__ __forceinline__ uint64_t mkdesc(uint32_t addr, uint32_t lbo, uint32_t sbo) {
    return (uint64_t)((addr & 0x3FFFF) >> 4) | ((uint64_t)(lbo >> 4) << 16) | ((uint64_t)(sbo >> 4) << 32) | (1ull << 62);
}
constexpr uint32_t SM0 = 1024;
__host__ __device__ constexpr uint32_t desc_lo(uint32_t off, uint32_t lbo) { return ((SM0 + off) >> 4) | ((lbo >> 4) << 16); }
#define WG_FENCE() asm volatile("wgmma.fence.sync.aligned;" ::: "memory")
#define WG_COMMIT() asm volatile("wgmma.commit_group.sync.aligned;" ::: "memory")
#define WG_WAIT(n) asm volatile("wgmma.wait_group.sync.aligned %0;" ::"n"(n) : "memory")

#define F8(a, i) "+f"(a[i]), "+f"(a[i + 1]), "+f"(a[i + 2]), "+f"(a[i + 3]), "+f"(a[i + 4]), "+f"(a[i + 5]), "+f"(a[i + 6]), "+f"(a[i + 7])
#define F16(a, i) F8(a, i), F8(a, i + 8)
#define F64(a) F16(a, 0), F16(a, 16), F16(a, 32), F16(a, 48)
#define F32(a) F16(a, 0), F16(a, 16)
#define L64 "%0,%1,%2,%3,%4,%5,%6,%7,%8,%9,%10,%11,%12,%13,%14,%15,%16,%17,%18,%19,%20,%21,%22,%23,%24,%25,%26,%27,%28,%29,%30,%31,%32,%33,%34,%35,%36,%37,%38,%39,%40,%41,%42,%43,%44,%45,%46,%47,%48,%49,%50,%51,%52,%53,%54,%55,%56,%57,%58,%59,%60,%61,%62,%63"
#define L32 "%0,%1,%2,%3,%4,%5,%6,%7,%8,%9,%10,%11,%12,%13,%14,%15,%16,%17,%18,%19,%20,%21,%22,%23,%24,%25,%26,%27,%28,%29,%30,%31"

template <int TB, int STEP = 128>
__device__ __forceinline__ void mma_rs128(float (&d)[64], uint32_t a0, uint32_t a1, uint32_t a2, uint32_t a3, uint64_t& b, int acc) {
    asm volatile("{\n.reg .pred p;\nsetp.ne.b32 p, %69, 0;\n"
                 "wgmma.mma_async.sync.aligned.m64n128k16.f32.bf16.bf16 {" L64 "}, {%65,%66,%67,%68}, %64, p, 1, 1, %70;\nadd.s64 %64, %64, %71;\n}"
                 : F64(d), "+l"(b) : "r"(a0), "r"(a1), "r"(a2), "r"(a3), "r"(acc), "n"(TB), "n"(STEP));
}
template <int TB>
__device__ __forceinline__ void mma_rs64(float (&d)[32], uint32_t a0, uint32_t a1, uint32_t a2, uint32_t a3, uint64_t& b, int acc) {
    asm volatile("{\n.reg .pred p;\nsetp.ne.b32 p, %37, 0;\n"
                 "wgmma.mma_async.sync.aligned.m64n64k16.f32.bf16.bf16 {" L32 "}, {%33,%34,%35,%36}, %32, p, 1, 1, %38;\nadd.s64 %32, %32, 128;\n}"
                 : F32(d), "+l"(b) : "r"(a0), "r"(a1), "r"(a2), "r"(a3), "r"(acc), "n"(TB));
}
template <int N>
__device__ __forceinline__ void fence_regs(float (&d)[N]) {
#pragma unroll
    for (int i = 0; i < N; i++) asm volatile("" : "+f"(d[i])::"memory");
}
template <int N>
__device__ __forceinline__ void fence_regs(uint32_t (&d)[N]) {
#pragma unroll
    for (int i = 0; i < N; i++) asm volatile("" : "+r"(d[i])::"memory");
}

template <int V> struct IC { static constexpr int value = V; };

constexpr int SLOT = 32768, UNIT = 16384;
constexpr int SM_Q = 4 * SLOT;
constexpr int SM_BAR = 7 * SLOT;
constexpr int SM_RED = SM_BAR + 512;
constexpr int SM_TOTAL = SM_BAR + 3072;
constexpr int XP = D_ * 2 + 16;
constexpr int M_MOD = 16 * XP;
constexpr int SM_T = SM_Q + 2 * D_ * 80, SM_TC = SM_T + D_ * 4, SM_TG = SM_TC + D_ * 4, SM_TS = SM_TG + D_ * 2;
constexpr float CS = 0.08838834764831845f * 1.4426950408889634f;
#define USE_SPARE 1
constexpr float POFF = 102.f, LMIN = 0x1p-104f;
#define LMAX 0.5f
constexpr int SPLIT = 10;
constexpr int STAGE = 11;
constexpr int ESPLIT = 3;
constexpr int QSPLIT = 4, OSPLIT = 6;
constexpr int WF0 = 3, WF1 = 13, WF2 = 19, DL = 6;
constexpr int PF_KV = 4, PF_WO = 120;

__device__ __forceinline__ int cluster_role() {
    int k;
    asm volatile("mov.u32 %0, %%ctaid.x;" : "=r"(k));
    k >>= 1;
    const int r = ((k - 36) * 37) >> 8, i = k - 36 - r * 7;
    return k < 4 ? 12 + k : k < 36 ? ((k - 4) & 7) * 8 + ((k - 4) >> 3) : (i + (i > 0)) * 8 + ((4 + r) & 7);
}

struct Args {
    const bf16 *w_mod, *cvec;
    Scratch* gs;
    uint64_t d0;
    bf16* out;
    const bf16 *x, *kc, *vc, *wq, *wo, *w_r, *w_down;
};

__device__ __forceinline__ void frag_store(uint8_t* p, const uint32_t (&a)[32]) {
#pragma unroll
    for (int i = 0; i < 8; i++)
        __stcg(reinterpret_cast<uint4*>(p + i * 512), make_uint4(a[4 * i], a[4 * i + 1], a[4 * i + 2], a[4 * i + 3]));
}
template <int LO = 0, int HI = 8>
__device__ __forceinline__ void frag_load(uint32_t (&a)[32], const uint8_t* p) {
#pragma unroll
    for (int i = LO; i < HI; i++) {
        const uint4 v = ld_relaxed(reinterpret_cast<const uint4*>(p + i * 512));
        a[4 * i] = v.x; a[4 * i + 1] = v.y; a[4 * i + 2] = v.z; a[4 * i + 3] = v.w;
    }
}
__device__ __forceinline__ float quad_sum(float v) {
    v += __shfl_xor_sync(0xffffffffu, v, 1);
    return v + __shfl_xor_sync(0xffffffffu, v, 2);
}
__device__ __forceinline__ float quad_max(float v) {
    v = fmaxf(v, __shfl_xor_sync(0xffffffffu, v, 1));
    return fmaxf(v, __shfl_xor_sync(0xffffffffu, v, 2));
}
__device__ __forceinline__ float rcp_fast(float x) { float y; asm("rcp.approx.ftz.f32 %0, %1;" : "=f"(y) : "f"(x)); return y; }
__device__ __forceinline__ float sigmoidf_(float x) { return rcp_fast(1.f + ex2(-1.4426950408889634f * x)); }
__device__ __forceinline__ void top2(uint32_t k, uint32_t& k1, uint32_t& k2) {
    k1 = __reduce_max_sync(0xffffffffu, k);
    k2 = __reduce_max_sync(0xffffffffu, k == k1 ? 0 : k);
}

__device__ __forceinline__ void mod_fma(float (&a)[8], const uint4 w, float sc) {
    a[0] += sc * bf_lo(w.x); a[1] += sc * bf_hi(w.x); a[2] += sc * bf_lo(w.y); a[3] += sc * bf_hi(w.y);
    a[4] += sc * bf_lo(w.z); a[5] += sc * bf_hi(w.z); a[6] += sc * bf_lo(w.w); a[7] += sc * bf_hi(w.w);
}
__device__ __forceinline__ float mod_reduce(float (&a)[8], int lane) {
#pragma unroll
    for (int h = 4; h > 0; h >>= 1) {
        const bool up = lane & (8 / h);
#pragma unroll
        for (int i = 0; i < h; i++)
            a[i] = (up ? a[i + h] : a[i]) + __shfl_xor_sync(0xffffffffu, up ? a[i] : a[i + h], 8 / h);
    }
    return a[0] + __shfl_xor_sync(0xffffffffu, a[0], 16);
}

__device__ __forceinline__ float ln_stats(float sum, float sq, uint32_t& mean2) {
    const float mean = sum * (1.f / D_);
    const float var = fmaxf(fmaf(-mean, mean, sq * (1.f / D_)), 0.f);
    float sd;
    asm("sqrt.approx.ftz.f32 %0, %1;" : "=f"(sd) : "f"(rbf(rbf(var) + 1e-5f)));
    mean2 = pack_bf16(mean, mean);
    return rcp_fast(rbf(sd));
}
__device__ __forceinline__ uint32_t ln_pair(uint32_t x, uint32_t mean2, float rsd) {
    const uint32_t d = bsub2(x, mean2);
    return pack_bf16(bf_lo(d) * rsd, bf_hi(d) * rsd);
}
__device__ __forceinline__ void rows_load(uint32_t (&x)[20], uint32_t xs, int cw) {
#pragma unroll
    for (int ch = 0; ch < 5; ch++) {
        const uint4 v = ldsm4(ch < 4 ? xs + ch * 256 : xs + 1024 - cw * 16);
        x[4 * ch] = v.x; x[4 * ch + 1] = v.y; x[4 * ch + 2] = v.z; x[4 * ch + 3] = v.w;
    }
}
__device__ __forceinline__ void stats_add(float (&st)[12], uint32_t a, uint32_t b, uint32_t w) {
    mma1688(st, a, b, w);
    mma1688(st + 4, a, b, a);
    mma1688(st + 8, a, b, b);
}
__device__ __forceinline__ float rows_stats(const float (&st)[12], float4* rec, int cw, int lane, uint32_t& mean2, float& dot) {
    const int g8 = lane >> 2;
    if ((g8 >> 1) == (lane & 3)) {
        rec[cw * 16 + g8] = make_float4(st[0], (g8 & 1) ? st[5] : st[4], st[1], 0.f);
        rec[cw * 16 + 8 + g8] = make_float4(st[2], (g8 & 1) ? st[11] : st[10], st[3], 0.f);
    }
    bar_sync(3, 256);
    const float4* r = rec + (lane >> 4) * 64 + (lane & 15);
    const float4 s0 = r[0], s1 = r[16], s2 = r[32], s3 = r[48];
    const float sum = (s0.x + s1.x) + (s2.x + s3.x), sq = (s0.y + s1.y) + (s2.y + s3.y);
    dot = (s0.z + s1.z) + (s2.z + s3.z);
    dot += __shfl_xor_sync(0xffffffffu, dot, 16);
    return ln_stats(sum + __shfl_xor_sync(0xffffffffu, sum, 16), sq + __shfl_xor_sync(0xffffffffu, sq, 16), mean2);
}
template <class F>
__device__ __forceinline__ void rows_normalise(uint32_t* y, const uint32_t* x, uint32_t mean2, float rsd, int lane, F loads) {
    const int g8 = lane >> 2;
    const uint32_t ma2 = __shfl_sync(0xffffffffu, mean2, g8), mb2 = __shfl_sync(0xffffffffu, mean2, g8 + 8);
    const float ra = __shfl_sync(0xffffffffu, rsd, g8), rb = __shfl_sync(0xffffffffu, rsd, g8 + 8);
    loads();
#pragma unroll
    for (int k = 0; k < 9; k++) { y[2 * k] = ln_pair(x[2 * k], ma2, ra); y[2 * k + 1] = ln_pair(x[2 * k + 1], mb2, rb); }
}

__device__ __forceinline__ uint4 h_frag(const uint4* hf, int ks, int lane) {
    if (ks < 32) return ld_relaxed2(hf + ks * 32);
    const uint2* p = reinterpret_cast<const uint2*>(padd(hf, 256 - lane * 8) + ks * 32 - 16);
    const uint2 a = ld_relaxed64(p), b = ld_relaxed64(p + 32);
    return make_uint4(a.x, a.y, b.x, b.y);
}

__device__ __noinline__ void attn_fallback(uint32_t bad, uint32_t tag, const Scratch* gs, uint8_t* frag, uint8_t* keep, const bf16* wq, const bf16* kc, const bf16* vc) {
  const int lane = threadIdx.x & 31, g8 = lane >> 2, qd = lane & 3;
  const int role = cluster_role(), j = role & 7, qb = (role >> 3) * 2 + (blockIdx.x & 1);
  const uint4* hf = g_h + (size_t)(qb * 8 + (threadIdx.x >> 5) - 4) * (36 * 32) + lane;
#pragma unroll 1
  for (int t = 0; t < 4; t++) {
    if (!((bad >> t) & 1)) continue;
    const bf16 *wqp = wq + (4 * j + t) * DH, *kp = kc + (size_t)(2 * j + (t >> 1)) * S_ * DH, *vp = vc + (size_t)(2 * j + (t >> 1)) * S_ * DH;
    uint32_t q[32];
    float o[64];
#pragma unroll
    for (int i = 0; i < 64; i++) o[i] = 0.f;
#pragma unroll 1
    for (int ks = 0; ks < 36; ks++) {
        const uint4 a = h_frag(hf, ks, lane);
        const unsigned short* wr = reinterpret_cast<const unsigned short*>(wqp + (size_t)(ks * 16 + 2 * qd) * QD + g8);
#pragma unroll
        for (int dt = 0; dt < 16; dt++) {
            const uint32_t b0 = __ldg(wr + dt * 8) | ((uint32_t)__ldg(wr + dt * 8 + QD) << 16);
            const uint32_t b1 = __ldg(wr + dt * 8 + 8 * QD) | ((uint32_t)__ldg(wr + dt * 8 + 9 * QD) << 16);
            mma16816(o + 4 * dt, a.x, a.y, a.z, a.w, b0, b1);
        }
    }
#pragma unroll
    for (int i = 0; i < 32; i++) q[i] = pack_bf16(o[2 * i], o[2 * i + 1]);
#pragma unroll
    for (int i = 0; i < 64; i++) o[i] = 0.f;
    float m0 = -INFINITY, m1 = -INFINITY, l0 = 0.f, l1 = 0.f;
#pragma unroll 1
    for (int key = 0; key < S_; key += 16) {
        float sc[8];
#pragma unroll
        for (int i = 0; i < 8; i++) sc[i] = 0.f;
#pragma unroll
        for (int nt = 0; nt < 2; nt++) {
            const uint32_t* kr = reinterpret_cast<const uint32_t*>(kp + (size_t)(key + nt * 8 + g8) * DH) + qd;
#pragma unroll
            for (int ks = 0; ks < 8; ks++)
                mma16816(sc + 4 * nt, q[4 * ks], q[4 * ks + 1], q[4 * ks + 2], q[4 * ks + 3], __ldg(kr + ks * 8), __ldg(kr + ks * 8 + 4));
        }
        const float n0 = quad_max(fmaxf(fmaxf(m0, fmaxf(sc[0], sc[1])), fmaxf(sc[4], sc[5])));
        const float n1 = quad_max(fmaxf(fmaxf(m1, fmaxf(sc[2], sc[3])), fmaxf(sc[6], sc[7])));
        const float f0 = ex2((m0 - n0) * CS), f1 = ex2((m1 - n1) * CS);
        m0 = n0; m1 = n1;
#pragma unroll
        for (int i = 0; i < 8; i++) sc[i] = ex2((sc[i] - ((i & 2) ? n1 : n0)) * CS);
        l0 = l0 * f0 + (sc[0] + sc[1]) + (sc[4] + sc[5]);
        l1 = l1 * f1 + (sc[2] + sc[3]) + (sc[6] + sc[7]);
        const uint32_t e0 = pack_bf16(sc[0], sc[1]), e1 = pack_bf16(sc[2], sc[3]), e2 = pack_bf16(sc[4], sc[5]), e3 = pack_bf16(sc[6], sc[7]);
        const unsigned short* vr = reinterpret_cast<const unsigned short*>(vp + (size_t)(key + 2 * qd) * DH + g8);
#pragma unroll
        for (int dt = 0; dt < 16; dt++) {
            o[4 * dt] *= f0; o[4 * dt + 1] *= f0; o[4 * dt + 2] *= f1; o[4 * dt + 3] *= f1;
            const uint32_t b0 = __ldg(vr + dt * 8) | ((uint32_t)__ldg(vr + dt * 8 + DH) << 16);
            const uint32_t b1 = __ldg(vr + dt * 8 + 8 * DH) | ((uint32_t)__ldg(vr + dt * 8 + 9 * DH) << 16);
            mma16816(o + 4 * dt, e0, e1, e2, e3, b0, b1);
        }
    }
    const float i0 = 1.f / quad_sum(l0), i1 = 1.f / quad_sum(l1);
#pragma unroll
    for (int i = 0; i < 16; i++) {
        q[2 * i] = pack_bf16(o[4 * i] * i0, o[4 * i + 1] * i0);
        q[2 * i + 1] = pack_bf16(o[4 * i + 2] * i1, o[4 * i + 3] * i1);
    }
    frag_store(t < 3 ? frag + t * 4096 : keep, q);
  }
}

__device__ __forceinline__ void spare_q3(Scratch* gs, uint32_t sb, uint32_t bar_full, uint32_t bar_empty, int lane, int cw) {
    const uint32_t tag = load_tag(gs);
    uint32_t rel_base, e = 3;
    asm("mapa.shared::cluster.u32 %0, %1, %2;" : "=r"(rel_base) : "r"(bar_empty), "r"(lane & 1));
#pragma unroll 1
    for (int qb = blockIdx.x - NCTA; qb < 16; qb += 4) {
        uint32_t h[144];
        float o[64];
        flag_wait(&g_flag_h[(qb * 8 + cw) * 32], tag);
        const uint4* hf = g_h + (size_t)(qb * 8 + cw) * (36 * 32) + lane;
#pragma unroll
        for (int ks = 0; ks < 36; ks++) {
            const uint4 v = h_frag(hf, ks, lane);
            h[4 * ks] = v.x; h[4 * ks + 1] = v.y; h[4 * ks + 2] = v.z; h[4 * ks + 3] = v.w;
        }
#pragma unroll
        for (int i = 0; i < 64; i++) o[i] = 0.f;
#pragma unroll 1
        for (int v = 0; v < 4; v++) {
            fence_regs(o);
#pragma unroll
            for (int t = 0; t < 5; t++) {
                mbar_wait(bar_full + 8 * (e & 3), (e >> 2) & 1);
                uint64_t dv = mkdesc(sb + (e & 3) * SLOT, UNIT, 1024);
                WG_FENCE();
#pragma unroll
                for (int ks = 0; ks < (t < 4 ? 8 : 4); ks++)
                    mma_rs128<1>(o, h[32 * t + 4 * ks], h[32 * t + 4 * ks + 1], h[32 * t + 4 * ks + 2], h[32 * t + 4 * ks + 3], dv, ks | t);
                WG_COMMIT();
                if (t > 0) { WG_WAIT(1); if (lane < 2) mbar_arrive_cluster(rel_base + 8 * ((e - 1) & 3)); }
                e++;
            }
            WG_WAIT(0);
            fence_regs(o);
            if (lane < 2) mbar_arrive_cluster(rel_base + 8 * ((e - 1) & 3));
            uint4* dst = &g_q3[((qb * 8 + 2 * v) * 8 + cw) * 128 + lane];
#pragma unroll
            for (int i = 0; i < 8; i++)
                __stcg(dst + (i >> 2) * 1024 + (i & 3) * 32, make_uint4(pack_bf16(o[8 * i], o[8 * i + 1]), pack_bf16(o[8 * i + 2], o[8 * i + 3]),
                                                                        pack_bf16(o[8 * i + 4], o[8 * i + 5]), pack_bf16(o[8 * i + 6], o[8 * i + 7])));
        }
        bar_sync(3, 256);
        if (cw == 0 && lane == 0) flag_release(&g_flag_q3[qb * 32], tag);
        __syncwarp();
    }
}

template <bool SPARE>
__global__ void __cluster_dims__(2, 1, 1) __launch_bounds__(384, 1)
fused_kernel(const Args args, const __grid_constant__ CUtensorMap tm_wq,
             const __grid_constant__ CUtensorMap tm_k, const __grid_constant__ CUtensorMap tm_v,
             const __grid_constant__ CUtensorMap tm_wo, const __grid_constant__ CUtensorMap tm_p,
             const __grid_constant__ CUtensorMap tm_x, const __grid_constant__ CUtensorMap tm_d,
             const __grid_constant__ CUtensorMap tm_g, const __grid_constant__ CUtensorMap tm_u) {
    extern __shared__ __align__(1024) uint8_t smem_raw[];
    const uint32_t sb = smem_u32(smem_raw);
    Scratch* const gs = args.gs;
    const uint32_t bar_full = sb + SM_BAR;
    const uint32_t bar_g = bar_full + 8 * 4;
    const uint32_t bar_mod = bar_g + 8;
    const uint32_t bar_go = bar_mod + 8;
    const uint32_t bar_x = bar_go + 40;
    const uint32_t bar_empty = bar_x + 8;
    const uint32_t bar_pub = bar_empty + 8 * 4;
    const uint32_t bar_qfree = bar_pub + 32;
    const uint32_t bar_out = bar_qfree + 24;
    const uint32_t bar_q3 = bar_out + 8;
    const uint32_t bar_pre = bar_q3 + 16;
    const uint32_t bar_w0 = bar_q3 + 8;
    constexpr int E0 = SPARE ? 2 : 0;

    const int c = blockIdx.x & 1;
#define ROLES() const int role = cluster_role(), j = role & 7, qb = (role >> 3) * 2 + c, rg = qb * 8 + j
    const int warp = __shfl_sync(0xffffffffu, threadIdx.x >> 5, 0);

    if (SPARE && blockIdx.x >= NCTA && warp >= 4) {
        asm volatile("barrier.cluster.arrive.relaxed.aligned;" ::: "memory");
        asm volatile("setmaxnreg.inc.sync.aligned.u32 240;");
        asm volatile("barrier.cluster.wait.aligned;" ::: "memory");
        spare_q3(gs, sb, bar_full, bar_empty, threadIdx.x & 31, warp - 4);
        asm volatile("barrier.cluster.arrive.relaxed.aligned;\nbarrier.cluster.wait.aligned;" ::: "memory");
    } else if (warp < 4) {
        asm volatile("setmaxnreg.dec.sync.aligned.u32 24;");
        ROLES();
        int lane;
        asm volatile("mov.u32 %0, %%laneid;" : "=r"(lane));
        if (warp == 2 && elect()) {
            asm volatile("prefetch.tensormap [%0];" ::"l"(&tm_x) : "memory");
#pragma unroll
            for (int i = 0; i < 27; i++) mbar_init(bar_full + 8 * i, i < 12 || i >= 23 ? 1 : i < 16 ? 16 : 8);
#pragma unroll
            for (int i = 0; i <= E0; i++) {
                mbar_arrive(bar_full + 8 * i);
                asm volatile("mbarrier.arrive.shared::cta.b64 _, [%0], 16;" ::"r"(bar_empty + 8 * i) : "memory");
            }
            asm volatile("fence.mbarrier_init.release.cluster;" ::: "memory");
        }
        __syncwarp();
        asm volatile("barrier.cluster.arrive.relaxed.aligned;" ::: "memory");
        if (warp == 2 && !(SPARE && blockIdx.x >= NCTA)) {
            __nanosleep(200);
            if (elect()) {
                mbar_expect_tx(bar_x, 16 * XP);
                tma2d(sb + SM_Q, &tm_x, 0, rg * 16, bar_x);
            }
            __syncwarp();
        }
        asm volatile("barrier.cluster.wait.aligned;" ::: "memory");
        const uint32_t tag = load_tag(gs);
        if (SPARE && blockIdx.x >= NCTA) {
            if (warp == 1) {
#pragma unroll 1
                for (int e = 3; e < 83; e++) {
                    const int v = (e - 3) / 5;
                    mbar_wait_sleep(bar_empty + 8 * (e & 3), ~(e >> 2) & 1);
                    if (elect()) {
                        mbar_expect_tx(bar_full + 8 * (e & 3), SLOT);
                        tma2d_mc(sb + (e & 3) * SLOT + c * UNIT, &tm_wq, (8 * (v & 3) + 4 * c + 3) * DH + 64, (e - 3 - v * 5) * 128,
                                 bar_full + 8 * (e & 3), EVICT_NORMAL);
                    }
                }
            }
            __syncwarp();
            asm volatile("barrier.cluster.arrive.relaxed.aligned;\nbarrier.cluster.wait.aligned;" ::: "memory");
            return;
        }
        if (warp == 3) {
#pragma unroll 1
            for (int e = 4; e < 20; e++) {
                __nanosleep(e == 4 ? 2000 : 400);
                const int hd = (e * 52) >> 8, row = (e - hd * 5) * 128 + qb * 8 + (lane >> 1);
                if (lane < 16 && row < D_)
                    asm volatile("prefetch.global.L2 [%0];" ::"l"(padd(args.wq, (row * QD + (4 * j + ((0x1320 >> (4 * hd)) & 3)) * DH + (lane & 1) * 64) * 2)) : "memory");
            }
            __syncwarp();
            mbar_wait_sleep(bar_go, 0);
#pragma unroll 1
            for (int unit = 72 + blockIdx.x; unit < 216; unit += NCTA) {
                float a[8];
#pragma unroll
                for (int i = 0; i < 8; i++) a[i] = 0.f;
#pragma unroll 1
                for (int k = lane >> 1; k < D_; k += 16) {
                    const float cv = __bfloat162float(*padd(args.cvec, k * 2));
                    mod_fma(a, __ldg(reinterpret_cast<const uint4*>(padd(args.w_mod, (k * (6 * D_) + unit * 16 + (lane & 1) * 8) * 2))), rbf(cv * sigmoidf_(cv)));
                }
                const float v = mod_reduce(a, lane), v1 = __shfl_down_sync(0xffffffffu, v, 8);
                if (lane < 8) *padd(gs->mod2, ((unit - 72) * 8 + (lane & 1) * 4 + (lane & 2) + (lane >> 2)) * 4) = pack_bf16(v, v1);
            }
            __syncwarp();
            if (lane == 0) flag_release(padd(g_flag_mod, blockIdx.x * 4), tag);
#pragma unroll 1
            for (int k = 0; k < 36; k++) {
                __nanosleep(200);
                __stcg(padd(gs->h[0], (~tag & 1) * (NCTA * 36 * 512) + ((rg * 36 + k) * 32 + lane) * 16), make_uint4(0, 0, 0, 0));
            }
            __syncwarp();
            mbar_wait_sleep(bar_qfree + 16, 0);
            __nanosleep(2000);
            {
                uint4 v;
                uint32_t it = 0;
#pragma unroll 1
                do {
                    v = ld_relaxed(reinterpret_cast<const uint4*>(padd(g_flag_mod, lane * 16)));
                } while (((v.x ^ tag) | (v.y ^ tag) | (v.z ^ tag) | (v.w ^ tag)) && ++it < SPIN / 16);
                asm volatile("fence.acquire.gpu;" ::: "memory");
            }
            __syncwarp();
            {
                float w1 = 0.f, w2 = 0.f;
#pragma unroll 1
                for (int k = lane; k < D_ / 2; k += 32) {
                    const uint32_t* mp = padd(gs->mod2, k * 4);
                    const uint32_t sv = __ldcg(mp + D_ / 2), c1 = badd2(__ldcg(mp + D_), 0x3f803f80u);
                    const uint32_t wr = *reinterpret_cast<const uint32_t*>(padd(args.w_r, k * 4)), wp = bmul2(c1, wr);
                    reinterpret_cast<uint2*>(smem_raw + SM_T)[k] = make_uint2(__ldcg(mp), wp);
                    reinterpret_cast<uint2*>(smem_raw + SM_TC)[k] = make_uint2(c1, sv);
                    reinterpret_cast<uint32_t*>(smem_raw + SM_TG)[k] = __ldcg(mp + 3 * D_ / 2);
                    w1 += bf_lo(wp) + bf_hi(wp);
                    w2 += bf_lo(sv) * bf_lo(wr) + bf_hi(sv) * bf_hi(wr);
                }
#pragma unroll 1
                for (int i = 1; i < 32; i <<= 1) { w1 += __shfl_xor_sync(0xffffffffu, w1, i); w2 += __shfl_xor_sync(0xffffffffu, w2, i); }
                *reinterpret_cast<float2*>(smem_raw + SM_TS) = make_float2(w1, w2);
            }
#pragma unroll
            for (int i = 0; i < 4; i++) reinterpret_cast<uint4*>(smem_raw + SM_RED)[lane + 32 * i] = make_uint4(~0u, ~0u, ~0u, ~0u);
            asm volatile("fence.proxy.async.shared::cta;" ::: "memory");
            __syncwarp();
            if (elect()) {
                uint8_t* mb = g_frag + (size_t)rg * 8 * WREG + 3 * 4096;
#pragma unroll 1
                for (int k = 0; k < 8; k++, mb += WREG) {
#pragma unroll
                    for (int i = 0; i < 3; i++)
                        asm volatile("cp.async.bulk.global.shared::cta.bulk_group [%0], [%1], 2048;" ::"l"(mb + i * 2048), "r"(sb + SM_RED) : "memory");
                    __nanosleep(500);
                }
                asm volatile("cp.async.bulk.commit_group;\ncp.async.bulk.wait_group 0;\nfence.proxy.async.global;" ::: "memory");
            }
            __syncwarp();
            if (lane == 0) mbar_arrive(bar_mod);
            __syncwarp();
            mbar_wait_sleep(bar_go + 8, 0);
            if (elect()) asm volatile("prefetch.tensormap [%0];\nprefetch.tensormap [%1];\nprefetch.tensormap [%2];" ::"l"(&tm_x), "l"(&tm_p), "l"(&tm_d) : "memory");
            __syncwarp();
#pragma unroll 1
            for (int i = 1; i < 4; i++) {
                mbar_wait(bar_pub + 8 * i, 0);
                unsigned int* flags = padd(g_flag_part, (qb * 32 + i * 8 - 8) * 4);
                if (elect()) { flag_release(padd(flags, j * 4), tag); DBG_PG(93); }
                __syncwarp();
                const uint32_t slot = (i + 2) & 3;
                flag_wait(padd(flags, (lane & 7) * 4), tag);
                asm volatile("fence.proxy.async.global;" ::: "memory");
                if (lane == 0 && i == 3) DBG_PG(101);
                mbar_wait(bar_go + 8 + 8 * i, 0);
                mbar_wait(bar_empty + 8 * slot, i == 3);
                if (elect()) {
                    mbar_expect_tx(bar_full + 8 * slot, SLOT);
                    tma3d(sb + slot * SLOT, &tm_p, 0, j * 20 + (i - 1) * 4, qb * 8, bar_full + 8 * slot);
                    tma3d(sb + slot * SLOT + UNIT, &tm_p, 0, j * 20 + (i - 1) * 4 + 2, qb * 8, bar_full + 8 * slot);
                }
            }
        } else if (warp == 0) {
#pragma unroll 1
            for (int i = 0; i < 48; i++) {
                if (SPARE && i == 34) {
                    flag_wait(&g_flag_q3[qb * 32], tag);
                    if (elect()) {
                        asm volatile("fence.proxy.async.global;" ::: "memory");
                        mbar_expect_tx(bar_q3, UNIT);
#pragma unroll 1
                        for (int k = 0; k < 8; k++) bulk_load(sb + SM_Q + 2 * SLOT + k * 4096 + 2048, &g_q3[(rg * 8 + k) * 128], 2048, bar_q3);
                    }
                }
                if (i == 0 || i == 17 || i == 34) { mbar_wait_sleep(bar_qfree + (i >> 4) * 8, 0); __nanosleep(2000); }
                __nanosleep(500);
                if (elect()) {
                    asm volatile("mbarrier.expect_tx.shared::cta.b64 [%0], %1;" ::"r"(bar_g), "n"(1920) : "memory");
                    tma2d(sb + SM_Q + i * 1920, i < 24 ? &tm_g : &tm_u, (blockIdx.x * 36) & ~7, (i < 24 ? i : i - 24) * 24, bar_g);
                }
            }
            if (elect()) mbar_arrive(bar_g);
#pragma unroll 1
            for (int i = 0; i < 18; i++) {
                __nanosleep(400);
                if (elect()) l2_prefetch(args.w_down + (size_t)(blockIdx.x * 36 + i * 2) * D_, 4 * D_);
            }
            __syncwarp();
            mbar_wait_sleep(bar_go + 8 * 2, 0);
            uint32_t acc = 0;
#pragma unroll 1
            for (int k = lane; k < 16 * 9; k += 32) acc |= touch(padd(args.x, (rg * 16 * D_ + k * 64) * 2));
            if (acc == 0) reinterpret_cast<volatile uint32_t*>(smem_raw + SM_BAR)[127] = acc;
            __syncwarp();
            mbar_wait_sleep(bar_go + 8 * 4, 0);
            uint4* rp = padd(g_rows, (rg * 2 * RSLOT + lane) * 16);
#pragma unroll
            for (int k = 0; k < 12; k++) rp[k * 32] = make_uint4(~0u, ~0u, ~0u, ~0u);
            if (blockIdx.x < 72) {
                uint4* yp = reinterpret_cast<uint4*>(padd(g_ypart, blockIdx.x * NCTA * 64 + lane * 16));
#pragma unroll
                for (int k = 0; k < 16; k++) yp[k * 32] = make_uint4(~0u, ~0u, ~0u, ~0u);
            }
            asm volatile("fence.acq_rel.gpu;" ::: "memory");
            __syncwarp();
            if (lane == 0) mbar_arrive(bar_pre);
        } else if (warp == 1) {
            __nanosleep(300);
            uint32_t go = bar_go;
            uint64_t marks = 24 | 151 << 8 | 155 << 16 | 160ull << 24 | 165ull << 32;
#pragma unroll 1
            for (int e = E0; e < 168; e++) {
                const CUtensorMap* tm;
                int c0, c1;
                uint64_t pol = EVICT_FIRST;
                if (e == 159 || e == 164) continue;
                if (e < 21 && e != 19) {
                    const int i = SPARE && e < 12 ? e - 2 : e - (e == 20), hd = (i * 52) >> 8;
                    tm = &tm_wq; c0 = (4 * j + ((0x1320 >> (4 * hd)) & 3)) * DH + c * 64; c1 = (i - hd * 5) * 128 - 64;
                    if (SPARE && e >= 12 && e < 15) { c0 = (4 * j + 3) * DH; c1 = (2 * (e - 12) + c) * 128; }
                } else if (e < 148) {
                    const int i = max(e - 20, 0);
                    const bool isk = i == 0 || ((i & 1) && i < 127);
                    const int n = isk ? (i + 1) >> 1 : (i - 1) >> 1;
                    tm = isk ? &tm_k : &tm_v; c0 = c * 64; c1 = (2 * j + (n >> 5)) * S_ + (n & 15) * 128;
                    if (!(i & 32)) pol = EVICT_NORMAL;
                } else {
                    int i = e - 148 - (e > 159) - (e > 164);
                    tm = &tm_wo; c0 = (i >> 1) * 64; c1 = (4 * j + ((i & 1) ? 1 + c : 3 * c)) * DH;
                }
                const uint32_t fb = e == E0 ? bar_w0 : bar_full + 8 * (e & 3), d = sb + (e == E0 ? 6 : e & 3) * SLOT;
                if (e >= 24 && e < 152) mbar_wait_sleep(bar_empty + 8 * (e & 3), ~(e >> 2) & 1);
                else if (e != E0) mbar_wait(bar_empty + 8 * (e & 3), ~(e >> 2) & 1);
                if (elect()) {
                    mbar_expect_tx(fb, SLOT);
                    tma2d_mc(d + c * UNIT, tm, c0, c1, fb, pol);
                    const int i = e - PF_KV;
                    if (i >= 0 && i < 128 && !(i & 32))
                        l2_prefetch(((i & 1) ? args.vc : args.kc) + (size_t)((2 * j + (i >> 6)) * S_ + (i & 30) * 64) * DH + qb * 1024, 2048);
                    if (e >= PF_WO && e < PF_WO + 18) l2_prefetch(args.wo + (size_t)blockIdx.x * (QD * D_ / NCTA) + (e - PF_WO) * 1024, 2048);
                    if (e == (marks & 255)) mbar_arrive(go);
                }
                if (e == (marks & 255)) { go += 8; marks >>= 8; }
            }
            asm volatile("fence.proxy.async.global;" ::: "memory");
            mbar_wait(bar_empty, 1);
            if (elect()) {
                mbar_expect_tx(bar_full, 16 * XP);
                tma2d(sb, &tm_x, 0, rg * 16, bar_full);
            }
            mbar_wait(bar_empty + 16, 1);
            if (elect()) {
                mbar_expect_tx(bar_full + 16, SLOT);
                tma3d(sb + 2 * SLOT, &tm_p, 0, j * 20 + 12, qb * 8, bar_full + 16);
                tma3d(sb + 2 * SLOT + UNIT, &tm_p, 0, j * 20 + 14, qb * 8, bar_full + 16);
            }
            mbar_wait(bar_empty + 24, 1);
            __nanosleep(300);
            if (elect()) {
                mbar_expect_tx(bar_full + 24, UNIT);
                tma3d(sb + 3 * SLOT, &tm_p, 0, j * 20 + 16, qb * 8, bar_full + 24);
            }
            mbar_wait(bar_empty + 8, 0);
            mbar_wait(bar_empty + 16, 0);
            __nanosleep(300);
            if (elect()) {
#pragma unroll
                for (int i = 1; i < 3; i++) {
                    mbar_expect_tx(bar_full + 8 * i, 18 * XP);
                    tma2d(sb + i * SLOT, &tm_d, 0, blockIdx.x * 36 + (i - 1) * 18, bar_full + 8 * i);
                }
            }
        } else {
            if (elect()) asm volatile("prefetch.tensormap [%0];\nprefetch.tensormap [%1];\nprefetch.tensormap [%2];" ::"l"(&tm_k), "l"(&tm_v), "l"(&tm_wo) : "memory");
            if (SPARE) {
                mbar_wait_sleep(bar_pub, 0);
                if (lane == 0) flag_release(padd(g_flag_h, rg * 128), tag);
                __syncwarp();
            }
            bar_sync(1, 192);
#pragma unroll 1
            for (uint32_t e = E0 + 5; e < 20; e++) {
                mbar_wait(bar_full + 8 * (e & 3), (e >> 2) & 1);
                if (!(((SPARE ? 0xa080 : 0x8420) >> e) & 1)) bar_sync(1, 192);
            }
#pragma unroll 1
            for (uint32_t e = 20; e < 148; e++) {
                mbar_wait_sleep(bar_full + 8 * (e & 3), (e >> 2) & 1);
                if (SPARE && e == 113) mbar_wait(bar_q3, 0);
                if (e & 1) bar_sync(1, 192);
                if (!(e & 1) || e == 147) bar_sync(4, 160);
            }
#pragma unroll 1
            for (uint32_t e = 148; e < 168; e++) {
                mbar_wait(bar_full + 8 * (e & 3), (e >> 2) & 1);
                if (e != 159 && e != 164) bar_sync(1, 192);
            }
        }
        __syncwarp();
        mbar_wait_sleep(bar_out, 0);
        if (elect()) {
            asm volatile("fence.proxy.async.shared::cta;" ::: "memory");
            const int2 sel = reinterpret_cast<const int2*>(smem_raw + SM_RED)[8];
#pragma unroll 1
            for (int i = warp; i < 16; i += 4) {
                const int row = rg * 16 + i;
                if (row != sel.x && row != sel.y)
                    asm volatile("cp.async.bulk.global.shared::cta.bulk_group.L2::cache_hint [%0], [%1], %2, %3;"
                                 ::"l"(args.out + (size_t)row * D_), "r"(sb + i * XP), "n"(D_ * 2), "l"(EVICT_FIRST) : "memory");
            }
            asm volatile("cp.async.bulk.commit_group;\ncp.async.bulk.wait_group.read 0;" ::: "memory");
        }
    } else {
        uint32_t cv[2] = {0, 0}, tag = load_tag(gs) - 1;
        if (blockIdx.x < 72) {
            uint32_t ws;
            int tid;
            asm volatile("mov.u32 %0, smem_raw;\nmov.u32 %1, %%tid.x;" : "=r"(ws), "=r"(tid));
            tid -= 128;
            ws += SM_Q + SLOT + tid * 16;
            const uint32_t* cp = padd(reinterpret_cast<const uint32_t*>(args.cvec), (tid & 0xe0) + (tid & 7) * 4);
            cv[0] = *padd(cp, (tid & 24) * 32);
            if (tid < 128) cv[1] = cp[256];
            const bf16* wrow = args.w_mod + (size_t)(tid >> 1) * (6 * D_) + (tid & 1) * 8 + blockIdx.x * 16;
#pragma unroll
            for (int i = 0; i < 5; i++)
                if (i < 4 || tid < 128)
                    asm volatile("cp.async.cg.shared.global [%0], [%1], 16;" ::"r"(ws + i * 4096), "l"(wrow + (size_t)i * 128 * (6 * D_)) : "memory");
        }
        asm volatile("barrier.cluster.arrive.relaxed.aligned;" ::: "memory");
        asm volatile("setmaxnreg.inc.sync.aligned.u32 240;");
        const int lane = threadIdx.x & 31;
        const int cw = warp - 4;
        const int w = cw >> 2;
        const int tid = threadIdx.x - 128;
        ROLES();
        float* red = reinterpret_cast<float*>(smem_raw + SM_RED);
        DBG_INIT();
        DBG_G(120);
        DBG_T(100);

        {
            if (blockIdx.x < 72) {
                uint32_t sa[10];
#pragma unroll
                for (int i = 0; i < 2; i++) {
                    const float lo = bf_lo(cv[i]), hi = bf_hi(cv[i]);
                    cv[i] = pack_bf16(lo * sigmoidf_(lo), hi * sigmoidf_(hi));
                }
#pragma unroll
                for (int i = 0; i < 10; i++) sa[i] = __shfl_sync(0xffffffffu, cv[i >> 3], (i & 7) * 4 + (lane & 3));
                uint2* mdst = &gs->mod1[(tid >> 3) * D_ + blockIdx.x * 8 + (tid & 7)];
                anchor(bar_full + 504, sa[0] & sa[1] & sa[2] & sa[3] & sa[4] & sa[5] & sa[6] & sa[7] & sa[8] & sa[9] & (uint32_t)(uintptr_t)mdst & (uint32_t)((uintptr_t)mdst >> 32));
                asm volatile("cp.async.wait_all;" ::: "memory");
                __syncwarp();
                const uint32_t ws = sb + SM_Q + SLOT + cw * 512 + (lane & 15) * 32 + (lane & 16);
                float d[16];
#pragma unroll
                for (int i = 0; i < 16; i++) d[i] = 0.f;
#pragma unroll
                for (int i = 0; i < 5; i++) {
                    const uint4 b = ldsm4t(ws + (i < 4 || cw < 4 ? i * 4096 : 0));
                    mma16816(d + 8 * (i & 1), sa[2 * i], sa[2 * i], sa[2 * i + 1], sa[2 * i + 1], b.x, b.y);
                    mma16816(d + 8 * (i & 1) + 4, sa[2 * i], sa[2 * i], sa[2 * i + 1], sa[2 * i + 1], b.z, b.w);
                }
                if (lane < 8) reinterpret_cast<float2*>(red)[lane * 8 + cw] = (lane & 4) ? make_float2(d[4] + d[12], d[5] + d[13]) : make_float2(d[0] + d[8], d[1] + d[9]);
                bar_sync(3, 256);
                if (tid < 8 * MREP) {
                    const float4* r = reinterpret_cast<const float4*>(red) + (tid & 7) * 4;
                    const float4 r0 = r[0], r1 = r[1], r2 = r[2], r3 = r[3];
                    st_relaxed64(mdst, pack_bf16(((r0.x + r0.z) + (r1.x + r1.z)) + ((r2.x + r2.z) + (r3.x + r3.z)),
                                                 ((r0.y + r0.w) + (r1.y + r1.w)) + ((r2.y + r2.w) + (r3.y + r3.w))), tag + 1);
                }
            }
            DBG_G(106);
            asm volatile("barrier.cluster.wait.aligned;" ::: "memory");
            mbar_wait(bar_x, 0);
            asm volatile("add.u32 %0, %0, 1;" : "+r"(tag));
            uint32_t x[20];
            float st[12], st2[12];
            rows_load(x, sb + SM_Q + (lane & 15) * XP + (lane >> 4) * 16 + cw * 32, cw);
#pragma unroll
            for (int i = 0; i < 12; i++) { st[i] = 0.f; st2[i] = 0.f; }
#pragma unroll
            for (int k = 0; k < 9; k++) stats_add((k & 1) ? st2 : st, x[2 * k], x[2 * k + 1], 0x3f803f80u);
#pragma unroll
            for (int i = 0; i < 12; i++) st[i] += st2[i];
            uint32_t mean2;
            float dot;
            const float rsd = rows_stats(st, reinterpret_cast<float4*>(red + 128), cw, lane, mean2, dot);
            const uint4* mp = reinterpret_cast<const uint4*>(gs->mod1 + ((blockIdx.x >> 1) & (MREP - 1)) * D_) + min(tid, D_ / 4 - 1);
            uint4 v0 = make_uint4(0, tag, 0, tag), v1 = v0;
            auto look = [&]() {
                asm volatile("{\n.reg .pred p;\n.reg .b64 a, b, c, d;\nsetp.lt.s32 p, %9, 5;\nmov.b64 a, {%0, %1};\nmov.b64 b, {%2, %3};\n"
                             "mov.b64 c, {%4, %5};\nmov.b64 d, {%6, %7};\n@p ld.relaxed.gpu.global.v2.b64 {a, b}, [%8];\n"
                             "@p ld.relaxed.gpu.global.v2.b64 {c, d}, [%8 + 2304];\n"
                             "mov.b64 {%0, %1}, a;\nmov.b64 {%2, %3}, b;\nmov.b64 {%4, %5}, c;\nmov.b64 {%6, %7}, d;\n}"
                             : "+r"(v0.x), "+r"(v0.y), "+r"(v0.z), "+r"(v0.w), "+r"(v1.x), "+r"(v1.y), "+r"(v1.z), "+r"(v1.w)
                             : "l"(mp), "r"(cw) : "memory");
            };
            rows_normalise(x, x, mean2, rsd, lane, look);
            fence_regs(x);
            uint32_t it = 0;
#pragma unroll 1
            while (((v0.y ^ tag) | (v0.w ^ tag) | (v1.y ^ tag) | (v1.w ^ tag)) && ++it < SPIN / 16) look();
            uint4* smod = reinterpret_cast<uint4*>(smem_raw + SM_Q + M_MOD);
            if (tid < D_ / 4) smod[tid] = make_uint4(badd2(v1.x, 0x3f803f80u), v0.x, badd2(v1.z, 0x3f803f80u), v0.z);
            uint4* hdst = g_h + (size_t)(rg * 36 + cw) * 32 + lane;
            uint2* hdst2 = reinterpret_cast<uint2*>(g_h + (size_t)(rg * 36 + 32) * 32) + tid;
            bar_sync(3, 256);
            DBG_G(107);
#pragma unroll
            for (int k = 0; k < 9; k++) {
                const uint2 cs = lds64(sb + SM_Q + M_MOD + (cw * 8 + (lane & 3) + (k < 8 ? (k >> 1) * 64 + (k & 1) * 4 : 256 - cw * 4)) * 8);
                const uint32_t c1 = cs.x, sa = cs.y;
                x[2 * k] = badd2(bmul2(x[2 * k], c1), sa);
                if (x[2 * k] == 0) x[2 * k] = 0x8000u;
                x[2 * k + 1] = badd2(bmul2(x[2 * k + 1], c1), sa);
            }
#pragma unroll
            for (int ch = 0; ch < 4; ch++) st_relaxed4(hdst + ch * 256, x[4 * ch], x[4 * ch + 1], x[4 * ch + 2], x[4 * ch + 3]);
            st_relaxed64(hdst2, x[16], x[17]);
            __syncwarp();
            if (SPARE && lane == 0) mbar_arrive(bar_pub);
            DBG_G(108);
        }

        uint32_t rel_base;
        asm("mapa.shared::cluster.u32 %0, %1, %2;" : "=r"(rel_base) : "r"(bar_empty), "r"(lane & 1));
        auto release = [&](uint32_t slot) { if (lane < 2) mbar_arrive_cluster(rel_base + 8 * slot); };
        uint32_t q[32], p[32];
        float s[64], o[64];

        const int lw = cw & 3;
        const uint32_t relw = lw == 2 && lane < 8, handw = lw == 2 || cw == 1;
        auto release4 = [&](uint32_t off, uint32_t on = 1) {
            asm volatile("{\n.reg .pred p;\nsetp.ne.b32 p, %1, 0;\n@p mbarrier.arrive.shared::cluster.b64 _, [%0];\n}" ::"r"(rel_base + off), "r"(relw & on) : "memory"); };
        auto handoff = [&](uint32_t on = 1) {
            asm volatile("{\n.reg .pred p;\nsetp.ne.b32 p, %1, 0;\n@p bar.arrive %0, 192;\n}" ::"r"(2 - w), "r"(handw & on) : "memory"); };
        if (cw == 6) bar_arrive(1, 192);

        uint4* qpark = reinterpret_cast<uint4*>(smem_raw + SM_Q - SLOT) + cw * 256 + lane;
        {
            uint32_t h[144];
            const uint4* hf = g_h + (size_t)(qb * 8 + cw) * (36 * 32) + lane;
            auto load_h = [&](auto lo, auto hi) {
#pragma unroll
                for (int ks = lo.value; ks < hi.value; ks++) {
                    const uint4 v = h_frag(hf, ks, lane);
                    h[4 * ks] = v.x; h[4 * ks + 1] = v.y; h[4 * ks + 2] = v.z; h[4 * ks + 3] = v.w;
                }
            };
            auto check_h = [&](auto lo, auto hi) {
                uint32_t it = 0;
                bool miss;
#pragma unroll 1
                do {
                    uint32_t mn = ~0u;
#pragma unroll
                    for (int ks = lo.value; ks < hi.value; ks++) mn = __vimin3_u32(mn, h[4 * ks], h[4 * ks + 2]);
                    miss = __any_sync(0xffffffffu, mn == 0);
                    if (miss) load_h(lo, hi);
                    asm volatile("add.u32 %0, %0, 1;" : "+r"(it));
                } while (miss && it < SPIN / 16);
            };
            auto check_h2 = [&](auto lo, auto hi, auto nx) {
                float f0 = __uint_as_float(~0u), f1 = f0;
                hold(f0, f1);
                auto low = [&]() {
                    uint32_t m0 = __float_as_uint(f0), m1 = m0;
#pragma unroll
                    for (int ks = lo.value; ks < hi.value; ks += 2) { m0 = __vimin3_u32(m0, h[4 * ks], h[4 * ks + 2]); m1 = __vimin3_u32(m1, h[4 * ks + 4], h[4 * ks + 6]); }
                    return min(m0, m1);
                };
                anchor(const_cast<uint4*>(hf), h[4 * hi.value - 1] & __float_as_uint(f0));
                load_h(hi, nx);
                if (__any_sync(0xffffffffu, low() == 0)) {
                    uint32_t it = 0;
#pragma unroll 1
                    do load_h(lo, hi); while (__any_sync(0xffffffffu, low() == 0) && ++it < SPIN / 16);
                }
            };
            __nanosleep(300);
            load_h(IC<0>{}, IC<4>{});
            DBG_T(104); DBG_G(109);
            mbar_wait(bar_w0, 0);
#pragma unroll
            for (int e = E0 + 1; e < E0 + 3; e++) mbar_wait(bar_full + 8 * (e & 3), e >> 2);
#pragma unroll
            for (int i = 0; i < 64; i++) o[i] = 0.f;
            auto group = [&](auto tc, auto ec) {
                constexpr int t = tc.value, e = ec.value, k0 = t ? 8 * t - 4 : 0;
                constexpr bool first = e < E0 + 5, turns = e >= E0 + 4;
                uint64_t dv = (first ? args.d0 : desc_lo(0, UNIT) | (0x40000040ull << 32)) + ((t ? 0 : 512) + (e == E0 ? 6 : e & 3) * (SLOT / 16));
                if (first && t == 0) check_h(IC<0>{}, IC<4>{});
                if (first && t >= 3) mbar_wait(bar_full + 8 * (e & 3), e >> 2);
                if (first && t > 0) check_h2(IC<k0>{}, IC<8 * t + 4>{}, IC<t < 4 ? 8 * t + 12 : 0>{});
                if (t != 1 && turns) bar_sync(1 + w, 192);
                if (t != 1 || first) WG_FENCE();
#pragma unroll
                for (int ks = k0; ks < 8 * t + 4; ks++) {
                    mma_rs128<1>(o, h[4 * ks], h[4 * ks + 1], h[4 * ks + 2], h[4 * ks + 3], dv, ks);
                    if (t && turns && ks == k0 + QSPLIT - 1) WG_COMMIT();
                }
                if (t || first) WG_COMMIT();
                if (first && t == 0) load_h(IC<4>{}, IC<12>{});
                if (t > 0) {
                    WG_WAIT(1);
                    if (turns) handoff();
                    if ((t == 1 && !first) || (t > 1 && e <= E0 + 4)) release4(8 * ((e - 1) & 3));
                    if (turns && e != 18) { WG_WAIT(0); release4(8 * (e & 3)); }
                }
            };
            auto head = [&](auto ec, int slot) {
                constexpr int e = ec.value;
                fence_regs(o);
                group(IC<0>{}, IC<e>{}); group(IC<1>{}, IC<e + 1>{}); group(IC<2>{}, IC<e + 2>{}); group(IC<3>{}, IC<e + 3>{});
                if (e == 15) return;
                group(IC<4>{}, IC<e + 4>{});
                fence_regs(o);
#pragma unroll
                for (int i = 0; i < 8; i++)
                    qpark[slot * 2048 + i * 32] = make_uint4(pack_bf16(o[8 * i], o[8 * i + 1]), pack_bf16(o[8 * i + 2], o[8 * i + 3]),
                                                             pack_bf16(o[8 * i + 4], o[8 * i + 5]), pack_bf16(o[8 * i + 6], o[8 * i + 7]));
            };
            head(IC<E0>{}, 1);
            head(IC<E0 + 5>{}, 2);
            if (SPARE) {
                float (&u)[32] = reinterpret_cast<float (&)[32]>(o);
                fence_regs(u);
#pragma unroll
                for (int t = 0; t < 2; t++) {
                    uint64_t dv = args.d0 + t * (SLOT / 16);
                    bar_sync(1 + w, 192);
                    WG_FENCE();
#pragma unroll
                    for (int ks = 0; ks < 16 + 4 * t; ks++) {
                        mma_rs64<1>(u, h[64 * t + 4 * ks], h[64 * t + 4 * ks + 1], h[64 * t + 4 * ks + 2], h[64 * t + 4 * ks + 3], dv, ks | t);
                        if (ks == 2 * QSPLIT + 4 * t - 1) WG_COMMIT();
                    }
                    WG_COMMIT();
                    WG_WAIT(1);
                    handoff();
                    WG_WAIT(0);
                    release4(8 * t);
                }
                fence_regs(u);
                release4(16);
#pragma unroll
                for (int i = 0; i < 4; i++)
                    qpark[3 * 2048 + i * 32] = make_uint4(pack_bf16(u[8 * i], u[8 * i + 1]), pack_bf16(u[8 * i + 2], u[8 * i + 3]),
                                                          pack_bf16(u[8 * i + 4], u[8 * i + 5]), pack_bf16(u[8 * i + 6], u[8 * i + 7]));
            } else {
                head(IC<10>{}, 3);
            }
            head(IC<15>{}, 0);
#pragma unroll
            for (int i = 0; i < 8; i++) {
                const uint4 v = lds128(smem_u32(qpark + 2048 + i * 32));
                q[4 * i] = v.x; q[4 * i + 1] = v.y; q[4 * i + 2] = v.z; q[4 * i + 3] = v.w;
            }
#pragma unroll
            for (int i = 0; i < 32; i++) p[i] = h[112 + i];
            WG_WAIT(0);
            fence_regs(o);
            release4(16);
        }
        DBG_T(105);
        DBG_G(125);

        uint8_t* frag = reinterpret_cast<uint8_t*>(__shfl_sync(0xffffffffu, reinterpret_cast<unsigned long long>(g_frag + (size_t)(rg * 8 + cw) * WREG + lane * 16), lane));
        const uint4* qnext = reinterpret_cast<const uint4*>(__shfl_sync(0xffffffffu, reinterpret_cast<unsigned long long>(padd(smem_raw, SM_Q + tid * 16 + cw * 3584)), lane));
        uint8_t* odst = reinterpret_cast<uint8_t*>(const_cast<uint4*>(qnext));
        qnext -= 2048;
        float m0, m1, l0 = 0.25f, l1 = 0.25f, t0, t1;
        uint32_t bad = 0;
        auto finish = [&](auto lo, auto hi, uint32_t bit, auto sink) {
#pragma unroll
            for (int i = lo.value; i < hi.value; i++) {
                const uint32_t v0 = pack_bf16(o[8 * i] * t0, o[8 * i + 1] * t0), v1 = pack_bf16(o[8 * i + 2] * t1, o[8 * i + 3] * t1);
                const uint32_t v2 = pack_bf16(o[8 * i + 4] * t0, o[8 * i + 5] * t0), v3 = pack_bf16(o[8 * i + 6] * t1, o[8 * i + 7] * t1);
                if (i == 0 && fabsf(o[0] * t0) >= 0x1p-31f) bad |= bit << 8;
                sink(i, v0, v1, v2, v3);
            }
        };
        float lq[6];
        auto row_parts = [&]() {
#pragma unroll
            for (int i = 0; i < 3; i++) { lq[i] = __shfl_xor_sync(0xffffffffu, l0, i + 1); lq[3 + i] = __shfl_xor_sync(0xffffffffu, l1, i + 1); }
        };
        auto row_sums = [&](uint32_t bit) {
            t0 = (l0 + lq[0]) + (lq[1] + lq[2]); t1 = (l1 + lq[3]) + (lq[4] + lq[5]);
            if (!(t0 >= LMIN && t0 < LMAX && t1 >= LMIN && t1 < LMAX)) bad |= bit;
        };
        auto issue_pv = [&](uint64_t dv, int acc) {
            asm volatile("{\n.reg .pred p;\nsetp.eq.b32 p, %0, 0;\n@p bar.sync 4, 160;\n}" ::"r"(w) : "memory");
#pragma unroll
            for (int ks = 0; ks < 8; ks++)
                mma_rs128<1>(o, p[4 * ks], p[4 * ks + 1], p[4 * ks + 2], p[4 * ks + 3], dv, ks ? 1 : acc);
            WG_COMMIT();
        };
#pragma unroll
        for (int i = 0; i < 64; i++) s[i] = 0.f;
        uint64_t dv_lo = args.d0;
        uint32_t voff = 0;
        auto issue_qk = [&]() {
            uint64_t dk = dv_lo ^ (desc_lo(0, UNIT) ^ desc_lo(3 * SLOT, 16));
            bar_sync(1 + w, 192);
            fence_regs(s); fence_regs(q); fence_regs(o); fence_regs(p);
            WG_FENCE();
#pragma unroll
            for (int ks = 0; ks < 8; ks++)
                if (ks == 3) mma_rs128<0, 1018>(s, q[4 * ks], q[4 * ks + 1], q[4 * ks + 2], q[4 * ks + 3], dk, 1);
                else mma_rs128<0, 2>(s, q[4 * ks], q[4 * ks + 1], q[4 * ks + 2], q[4 * ks + 3], dk, ks != 0);
            WG_COMMIT();
        };
        auto to_frag = [&](int i, uint32_t v0, uint32_t v1, uint32_t v2, uint32_t v3) {
            *reinterpret_cast<uint4*>(odst + i * 512) = make_uint4(v0, v1, v2, v3); };
        int n = 0;
        auto scores_ready = [&]() {
            WG_WAIT(1);
            fence_regs(s); fence_regs(q);
        };
        auto pass_on = [&]() {
            release4(voff ^ 24);
            handoff();
        };
#pragma unroll 1
        for (;;) {
            {
                {
                    asm volatile("st.shared.v2.f32 [%0], {%1, %2};" ::"r"(sb + SM_RED + tid * 8), "f"(l0), "f"(l1) : "memory");
                    __syncwarp();
                    const uint4 a = lds128(sb + SM_RED + (tid & ~3) * 8), b = lds128(sb + SM_RED + (tid & ~3) * 8 + 16);
                    l0 = __uint_as_float(a.x); lq[0] = __uint_as_float(a.z); lq[1] = __uint_as_float(b.x); lq[2] = __uint_as_float(b.z);
                    l1 = __uint_as_float(a.y); lq[3] = __uint_as_float(a.w); lq[4] = __uint_as_float(b.y); lq[5] = __uint_as_float(b.w);
                }
                issue_qk();
                hold(l0, l1);
                row_sums(1u << (n >> 4));
                t0 = rcp_fast(t0); t1 = rcp_fast(t1);
                l0 = 0.f; l1 = 0.f;
                odst = n ? frag + ((n >> 4) - 1) * 4096 : odst;
                qnext = n == 48 ? reinterpret_cast<const uint4*>(frag) : qnext + 2048;
                anchor(bar_full + 504, (t0 + t1) * __uint_as_float((bad ^ (uint32_t)(uintptr_t)odst ^ (uint32_t)(uintptr_t)qnext) & 0x3fffffff));
                asm volatile("{\n.reg .pred p;\nsetp.ne.b32 p, %1, 0;\n@p mbarrier.arrive.shared::cta.b64 _, [%0];\n}"
                             ::"r"(bar_qfree + (n >> 1) - 8), "r"(lane ? 0 : n) : "memory");
                issue_pv(dv_lo, 1);
                scores_ready();
                const uint32_t a = pack_bf16(fmaxf(fmaxf(s[0], s[1]), fmaxf(s[4], s[5])), fmaxf(fmaxf(s[2], s[3]), fmaxf(s[6], s[7])));
                const uint32_t b = bmax2(bmax2(a, __shfl_xor_sync(0xffffffffu, a, 1)), bmax2(__shfl_xor_sync(0xffffffffu, a, 2), __shfl_xor_sync(0xffffffffu, a, 3)));
                pass_on();
                m0 = fmaf(-CS, bf_lo(b), -POFF); m1 = fmaf(-CS, bf_hi(b), -POFF);
            }
#pragma unroll 1
            for (;;) {
                DBG_T(n);
#pragma unroll
                for (int i = 0; i < 4 * STAGE; i++) s[i] = fmaf(s[i], CS, (i & 2) ? m1 : m0);
#pragma unroll
                for (int i = 0; i < 4 * SPLIT; i++) s[i] = ex2(s[i]);
#pragma unroll
                for (int i = 0; i < SPLIT; i++) { l0 += s[4 * i] + s[4 * i + 1]; l1 += s[4 * i + 2] + s[4 * i + 3]; }
                m0 = fmaf(l0, 0.f, m0); m1 = fmaf(l1, 0.f, m1);
                anchor(bar_full + 504, l0 + l1);
                WG_WAIT(0);
                fence_regs(o); fence_regs(p);
                release4(voff);
                dv_lo ^= 2 * SLOT / 16;
                voff ^= 16;
                n++;
#pragma unroll
                for (int i = 4 * STAGE; i < 64; i++) s[i] = fmaf(s[i], CS, (i & 2) ? m1 : m0);
#pragma unroll
                for (int i = 4 * SPLIT; i < 64; i++) s[i] = ex2(s[i]);
#pragma unroll
                for (int i = SPLIT; i < 16; i++) { l0 += s[4 * i] + s[4 * i + 1]; l1 += s[4 * i + 2] + s[4 * i + 3]; }
#pragma unroll
                for (int i = 0; i < 32; i++) p[i] = pack_bf16(s[2 * i], s[2 * i + 1]);
                const int jn = n & 15;
                if (jn > 1) {
                    issue_qk();
                    if ((n & 10) == 2) {
                        if (n & 1) {
#pragma unroll
                            for (int i = 0; i < 64; i++) o[i] *= (i & 2) ? t1 : t0;
                        } else {
                            row_parts();
                            row_sums(2u << (n >> 4));
                            const uint32_t e0 = __float_as_uint(t0) >> 23, e1 = __float_as_uint(t1) >> 23;
                            m0 -= __uint_as_float(0x4b000000u | e0) - (8388608.f + 127.f - POFF);
                            m1 -= __uint_as_float(0x4b000000u | e1) - (8388608.f + 127.f - POFF);
                            t0 = __uint_as_float((254 - (int)POFF - e0) << 23); t1 = __uint_as_float((254 - (int)POFF - e1) << 23);
                            l0 *= t0; l1 *= t1;
                        }
                    }
                    fence_regs(o);
                    WG_FENCE();
                    issue_pv(dv_lo, 1);
                    scores_ready();
                    pass_on();
                    if (jn != 15) continue;
#pragma unroll
                    for (int i = 0; i < 8; i++) {
                        const uint4 v = qnext[i * 32];
                        q[4 * i] = v.x; q[4 * i + 1] = v.y; q[4 * i + 2] = v.z; q[4 * i + 3] = v.w;
                    }
                    continue;
                }
                if (jn == 0) break;
                finish(IC<0>{}, IC<ESPLIT>{}, 1u << (n >> 4), to_frag);
                issue_qk();
                hold(t0, t1);
                finish(IC<ESPLIT>{}, IC<8>{}, 1u << (n >> 4), to_frag);
                WG_FENCE();
                issue_pv(dv_lo, 0);
                scores_ready();
                pass_on();
            }
            if (n == 64) break;
        }
        DBG_T(64);
        uint32_t a1[32], a2[32];
        bar_sync(1 + w, 192);
        fence_regs(o); fence_regs(p);
        WG_FENCE();
        issue_pv(args.d0 + 3 * SLOT / 16, 1);
        handoff();
        mbar_wait(bar_mod, 0);
        const int tid_ = __shfl_sync(0xffffffffu, tid, lane);
        row_parts();
        row_sums(16);
        t0 = rcp_fast(t0); t1 = rcp_fast(t1);
        anchor(frag, q[0] & q[4] & q[8] & q[12] & q[16] & q[20] & q[24] & q[28] & __float_as_uint(t0) & __float_as_uint(t1) & tid_);
        frag_load(a1, frag + 4096);
        frag_load<0, 4>(a2, frag + 8192);
        anchor(frag, bad);
        WG_WAIT(0);
        fence_regs(o); fence_regs(p);
        release4(24);
        finish(IC<0>{}, IC<8>{}, 16, [&](int i, uint32_t v0, uint32_t v1, uint32_t v2, uint32_t v3) {
            p[4 * i] = v0; p[4 * i + 1] = v1; p[4 * i + 2] = v2; p[4 * i + 3] = v3; });
        anchor(frag, p[31] & p[15]);
        frag_load<4, 8>(a2, frag + 8192);
        bad = __reduce_or_sync(0xffffffffu, bad);
        bad = ((bad | ~(bad >> 8)) >> 1) & 15;
        if (__builtin_expect(bad != 0, 0)) {
            uint8_t* keep = g_keep + (size_t)(rg * 8 + cw) * 4096 + lane * 16;
            frag_store(keep, p);
            attn_fallback(bad, tag, gs, frag, keep, args.wq, args.kc, args.vc);
            frag_load(q, frag); frag_load(a1, frag + 4096); frag_load(a2, frag + 8192); frag_load(p, keep);
            anchor(frag, q[0] & q[4] & q[8] & q[12] & q[16] & q[20] & q[24] & q[28] & p[0] & p[4] & p[8] & p[12] & p[16] & p[20] & p[24] & p[28]);
        }
        DBG_T(80);
        DBG_G(124);

        const uint32_t eye = (tid_ >> 3 & 3) == (tid_ & 3) ? 0x3f80u << ((tid_ & 4) * 4) : 0;
        auto sum8 = [&](uint32_t* r, const uint4 (&v)[8]) {
            float d[16];
#pragma unroll
            for (int i = 0; i < 16; i++) d[i] = 0.f;
#pragma unroll
            for (int src = 0; src < 8; src++) {
                mma1688(d + 8 * (src & 1), v[src].x, v[src].y, eye);
                mma1688(d + 8 * (src & 1) + 4, v[src].z, v[src].w, eye);
            }
#pragma unroll
            for (int i = 0; i < 4; i++) r[i] = pack_bf16(d[2 * i] + d[8 + 2 * i], d[2 * i + 1] + d[9 + 2 * i]);
        };
        uint4 v2[8], v3[8], wf[23];
        uint2 u4[8], gw[9];
        uint32_t x1[20], xs, pa, ta;
        const uint8_t *mb, *mb4;
        auto load_wf = [&](auto lo, auto hi) {
            const uint32_t wa = sb + SM_Q + ((tid_ & 8) * (D_ / 8) + cw * 16 + (tid_ & 7) + (tid_ & 16) / 2) * 80;
            const uint32_t wb = wa + (512 - cw * 8) * 80 - (tid_ & 16) * 39;
#pragma unroll
            for (int i = lo.value; i < hi.value; i++) wf[i] = ldsm4t(i < 20 ? wa + (i / 5) * 10240 + (i % 5) * 16 : wb + (i - 20) * 32);
        };
        uint32_t at[18];
        {
            float (&u)[32] = reinterpret_cast<float (&)[32]>(o);
            uint32_t off = 0;
            auto turn = [&](const uint32_t (&a)[32], const uint32_t (&b)[32], int acc) {
                uint64_t dv = args.d0 + off * (SLOT / 128);
                bar_sync(1 + w, 192);
                fence_regs(u);
                WG_FENCE();
#pragma unroll
                for (int ks = 0; ks < 16; ks++) {
                    const uint32_t* f = ks < 8 ? &a[4 * ks] : &b[4 * ks - 32];
                    mma_rs64<1>(u, f[0], f[1], f[2], f[3], dv, ks | acc);
                    if (ks == OSPLIT - 1) WG_COMMIT();
                }
                WG_COMMIT();
                WG_WAIT(1);
            };
            auto done = [&]() {
                WG_WAIT(0);
                fence_regs(u);
                release4(off);
                off = (off + 8) & 24;
            };
            auto store = [&](uint8_t* dst) {
#pragma unroll
                for (int i = 0; i < 4; i++)
                    st_relaxed4(dst + i * 512, pack_bf16(u[8 * i], u[8 * i + 1]), pack_bf16(u[8 * i + 2], u[8 * i + 3]),
                                pack_bf16(u[8 * i + 4], u[8 * i + 5]), pack_bf16(u[8 * i + 6], u[8 * i + 7]));
            };
            pa = sb + w * (UNIT - 2048) + tid_ * 16;
#pragma unroll
            for (int i = 0; i < 8; i++) at[i] = 0;
            fence_regs(q); fence_regs(p);
            uint8_t* dst = frag;
#pragma unroll
            for (int i = 0; i < 8; i++) asm volatile("" : "=r"(v2[i].x), "=r"(v2[i].y), "=r"(v2[i].z), "=r"(v2[i].w));
#pragma unroll 1
            for (int k = 0; k < 8; k++, dst += 2048) {
                const uint32_t poff = (off + 8) & 24;
                const bool sum = (0xa0 >> k) & 1;
                turn(q, p, 0);
                handoff();
                auto sum_p = [&](auto lo, auto hi) {
#pragma unroll
                    for (int i = lo.value; i < hi.value; i++) {
                        float a[8], b[8];
#pragma unroll
                        for (int src = 0; src < 8; src++) {
                            const uint32_t x = i == 0 ? v2[src].x : i == 1 ? v2[src].y : i == 2 ? v2[src].z : v2[src].w;
                            a[src] = bf_lo(x); b[src] = bf_hi(x);
                        }
                        at[i] = at[4 + i];
                        at[4 + i] = pack_bf16(((a[0] + a[2]) + (a[4] + a[6])) + ((a[1] + a[3]) + (a[5] + a[7])),
                                              ((b[0] + b[2]) + (b[4] + b[6])) + ((b[1] + b[3]) + (b[5] + b[7])));
                    }
                };
                if (sum) {
                    mbar_wait(bar_full + poff, 1);
#pragma unroll
                    for (int src = 0; src < 8; src++) v2[src] = lds128(pa + poff * (SLOT / 8) + src * 2048);
                    __syncwarp();
                    release(poff >> 3);
                    done();
                    off = (off + 8) & 24;
                    sum_p(IC<0>{}, IC<2>{});
                } else {
                    done();
                }
                turn(a1, a2, 1);
                handoff();
                if (sum) sum_p(IC<2>{}, IC<4>{});
                done();
                store(dst);
                __syncwarp();
                asm volatile("{\n.reg .pred p;\nsetp.ne.b32 p, %1, 0;\n@p mbarrier.arrive.shared::cta.b64 _, [%0];\n}"
                             ::"r"(bar_pub + 4 + 4 * k), "r"(lane ? 0 : (0x2a >> k) & 1) : "memory");
            }
            turn(q, p, 0);
            handoff();
            mb = padd(g_frag, (qb * 64 + j) * WREG + 3 * 4096 + tid_ * 16);
            mb4 = padd(mb, 4096 + ((cw >> 1) - cw) * 512 + (cw & 1) * 8);
            xs = sb + (tid_ & 15) * XP + (tid_ & 16) + cw * 32;
            ta = sb + (cw * 8 + (tid_ & 3)) * 8;
#pragma unroll
            for (int k = 0; k < 9; k++) {
                gw[k] = lds64(ta + SM_T + (k < 8 ? (k >> 1) * 64 + (k & 1) * 4 : 256 - cw * 4) * 8);
                if (!(tid_ & 4)) gw[k].y = 0x3f803f80u;
            }
            mbar_wait(bar_g, 0);
            done();
            load_wf(IC<0>{}, IC<WF0>{});
            turn(a1, a2, 1);
            if (w == 0) handoff();
            done();
            store(dst);
            mbar_wait(bar_full, 0);
            rows_load(x1, xs, cw);
            if (w == 0) bar_sync(5, 256); else bar_arrive(5, 256);
        }
        DBG_T(81);
        DBG_G(122);

        {
        const int tid = tid_, lane = tid & 31;
        const int g8 = lane >> 2, qd = lane & 3, l16 = lane & 15;
        uint32_t h2[18], gb[9], k1, k2;
        float4* rec = reinterpret_cast<float4*>(red + 128);
        const uint2* candp = reinterpret_cast<const uint2*>(padd(g_cand, ((blockIdx.x & (CREP - 1)) * NCTA + (tid >> 1)) * 32 + (tid & 1) * 8));
        uint2 cd;
        auto stage_out = [&]() {
#pragma unroll
            for (int k = 0; k < 9; k++) {
                x1[2 * k] = badd2(x1[2 * k], bmul2(gb[k], h2[2 * k]));
                x1[2 * k + 1] = badd2(x1[2 * k + 1], bmul2(gb[k], h2[2 * k + 1]));
            }
#pragma unroll
            for (int ch = 0; ch < 4; ch++) stsm_x4(xs + ch * 256, x1[4 * ch], x1[4 * ch + 1], x1[4 * ch + 2], x1[4 * ch + 3]);
            asm volatile("stmatrix.sync.aligned.m8n8.x2.shared.b16 [%0], {%1, %2};" ::"r"(xs + 1024 - cw * 16), "r"(x1[16]), "r"(x1[17]) : "memory");
        };
        {
            uint32_t it = 0, miss;
            mbar_wait(bar_full + 8, 0);
#pragma unroll
            for (int src = 0; src < 8; src++) v2[src] = lds128(pa + SLOT + src * 2048);
            sum8(at + 8, v2);
            float st[12];
#pragma unroll
            for (int i = 0; i < 12; i++) st[i] = 0.f;
            auto add_pair = [&](int k) {
                x1[2 * k] = badd2(x1[2 * k], bmul2(gw[k].x, at[2 * k]));
                x1[2 * k + 1] = badd2(x1[2 * k + 1], bmul2(gw[k].x, at[2 * k + 1]));
                stats_add(st, x1[2 * k], x1[2 * k + 1], gw[k].y);
            };
#pragma unroll
            for (int k = 0; k < 6; k++) add_pair(k);
            mbar_wait(bar_full + 16, 0);
#pragma unroll
            for (int src = 0; src < 8; src++) v3[src] = lds128(pa + 2 * SLOT + src * 2048);
#pragma unroll 1
            do {
                miss = 0;
#pragma unroll
                for (int src = 0; src < 8; src++) reload16(v3[src], mb + (size_t)src * 8 * WREG, miss);
            } while (__any_sync(0xffffffffu, miss) && ++it < SPIN / 16);
            if (lane < 4) mbar_arrive_cluster(rel_base + 8 * (1 + (lane >> 1)));
            sum8(at + 12, v3);
            add_pair(6); add_pair(7);
            load_wf(IC<WF0>{}, IC<WF1>{});
            uint2 cs[9];
#pragma unroll
            for (int k = 0; k < 9; k++) cs[k] = lds64(ta + SM_TC + (k < 8 ? (k >> 1) * 64 + (k & 1) * 4 : 256 - cw * 4) * 8);
            mbar_wait(bar_pre, 0);
            mbar_wait(bar_full + 24, 0);
#pragma unroll
            for (int src = 0; src < 8; src++) u4[src] = lds64(sb + 3 * SLOT + src * 2048 + (cw >> 1) * 512 + lane * 16 + (cw & 1) * 8);
#pragma unroll 1
            do {
                miss = 0;
#pragma unroll
                for (int src = 0; src < 8; src++) reload8(u4[src], mb4 + (size_t)src * 8 * WREG, miss);
            } while (__any_sync(0xffffffffu, miss) && ++it < SPIN / 16);
            float d[8] = {0.f, 0.f, 0.f, 0.f, 0.f, 0.f, 0.f, 0.f};
#pragma unroll
            for (int i = 0; i < 4; i++) mma16816(d + 4 * (i & 1), u4[2 * i].x, u4[2 * i].y, u4[2 * i + 1].x, u4[2 * i + 1].y, eye, eye);
            at[16] = pack_bf16(d[0] + d[4], d[1] + d[5]); at[17] = pack_bf16(d[2] + d[6], d[3] + d[7]);
            add_pair(8);
            DBG_G(123);
            const float2 ws = *reinterpret_cast<const float2*>(smem_raw + SM_TS);
            uint4* cdst = padd(g_cand, (tid * NCTA + rg) * 32);
            uint32_t mean2;
            float dot;
            const float rsd = rows_stats(st, rec, cw, lane, mean2, dot);
            const uint32_t b = __float_as_uint(fmaf(fmaf(-bf_lo(mean2), ws.x, dot), rsd, ws.y));
            const uint32_t key = (((b & 0x80000000u) ? ~b : (b | 0x80000000u)) | 2047u) - (rg * 16 + l16);
            top2(key, k1, k2);
            if (tid < CREP) st_relaxed(cdst, k1, tag, k2, tag);
            cd = ld_relaxed64(candp);
            rows_normalise(h2, x1, mean2, rsd, lane, [&]() {
#pragma unroll
                for (int k = 0; k < 9; k++) gb[k] = lds32(sb + SM_TG + (cw * 8 + qd + (k < 8 ? (k >> 1) * 64 + (k & 1) * 4 : 256 - cw * 4)) * 4);
                load_wf(IC<WF1>{}, IC<WF2>{});
            });
#pragma unroll
            for (int k = 0; k < 18; k++) h2[k] = badd2(bmul2(h2[k], cs[k >> 1].x), cs[k >> 1].y);
            const uint32_t r1 = ~k1 & 15, r2 = ~k2 & 15;
            uint32_t todo = ((r1 & 7) == g8) | ((r2 & 7) == g8) << 1;
#pragma unroll 1
            while (todo) {
                const bool second = !(todo & 1), hi = (second ? r2 : r1) & 8;
                uint4* dst = padd(g_rows, ((rg * 2 + second) * RSLOT + cw * 24 + qd) * 16);
                uint32_t r[18];
#pragma unroll
                for (int k = 0; k < 9; k++) { r[k] = hi ? h2[2 * k + 1] : h2[2 * k]; r[9 + k] = hi ? x1[2 * k + 1] : x1[2 * k]; }
                fence_regs(r);
                st_relaxed(dst, r[0], r[1], r[2], r[3]);
                st_relaxed(dst + 8, r[4], r[5], r[6], r[7]);
                st_relaxed64(reinterpret_cast<uint2*>(padd(dst, 256 - qd * 8)), r[8], r[17]);
                st_relaxed(dst + 4, r[9], r[10], r[11], r[12]);
                st_relaxed(dst + 12, r[13], r[14], r[15], r[16]);
                todo &= todo - 1;
            }
            __syncwarp();

            stage_out();
        }
        DBG_G(110);
        float4* part = reinterpret_cast<float4*>(smem_raw + 3 * SLOT + UNIT + 8192);
        bf16* act = reinterpret_cast<bf16*>(smem_raw + 3 * SLOT + UNIT + 4096);
        {
            uint32_t it = 0;
            const bool own = (tid >> 1) == rg;
            const uint32_t ks = sb + 3 * SLOT + UNIT + 5120;
#pragma unroll 1
            while (cd.y != tag && !own && ++it < SPIN / 16) cd = ld_relaxed64(candp);
            asm volatile("st.shared.u32 [%0], %1;" ::"r"(ks + tid * 4), "r"(own ? (tid & 1) ? k2 : k1 : cd.x) : "memory");
            bar_sync(3, 256);
            DBG_G(111);
            const uint4 a = lds128(ks + lane * 16), b = lds128(ks + 512 + lane * 16);
            const uint32_t a1 = max(a.x, a.z), a2 = __vimax3_u32(min(a.x, a.z), a.y, a.w);
            const uint32_t b1 = max(b.x, b.z), b2 = __vimax3_u32(min(b.x, b.z), b.y, b.w);
            const uint32_t c1 = max(a1, b1), c2 = __vimax3_u32(min(a1, b1), a2, b2);
            k1 = __reduce_max_sync(0xffffffffu, c1);
            k2 = __reduce_max_sync(0xffffffffu, c1 == k1 ? c2 : c1);
        }
        const int sel0 = ~k1 & 2047, sel1 = ~k2 & 2047;
        const uint32_t slot0 = (sel0 >> 4) * 2, slot1 = (sel1 >> 4) * 2 + ((sel0 ^ sel1) < 16);
        uint4 da[13];
        {
            const uint4* hp = padd(g_rows, (((g8 & 1) ? slot1 : slot0) * RSLOT + cw * 24 + qd) * 16);
            const uint2* hp2 = reinterpret_cast<const uint2*>(padd(hp, 256 - qd * 8));
            uint4 hv[2] = {ld_relaxed2(hp), ld_relaxed2(hp + 8)};
            uint2 hw = ld_relaxed64(hp2);
            if (tid == 255) {
                reinterpret_cast<int2*>(red)[8] = make_int2(sel0, sel1);
                mbar_arrive(bar_out);
            }
            load_wf(IC<WF2>{}, IC<23>{});
            mbar_wait(bar_full + 8, 1);
            mbar_wait(bar_full + 16, 1);
            auto load_d = [&](auto lo, auto hi) {
                const int r = (lane & 7) + (lane & 16) / 2;
                const uint32_t d0 = sb + SLOT + r * XP + cw * 144 + (lane & 8) * 2, d1 = d0 + (r < 2 ? 16 * XP : SLOT - 2 * XP);
                const uint32_t d2 = sb + 2 * SLOT + (14 + (lane & 3)) * XP + cw * 144 + (lane >> 3) * 16;
#pragma unroll
                for (int i = lo.value; i < hi.value; i++) da[i] = ldsm4t(i < 10 ? ((i & 1) ? d1 : d0) + (i >> 1) * 32 : d2 + (i - 10) * 64);
            };
            load_d(IC<0>{}, IC<DL>{});
            uint32_t it = 0, miss;
#pragma unroll 1
            do {
                miss = 0;
                reload16(hv[0], hp, miss);
                reload16(hv[1], hp + 8, miss);
                reload8(hw, hp2, miss);
            } while (__any_sync(0xffffffffu, miss) && ++it < SPIN / 16);
            DBG_G(112);
            load_d(IC<DL>{}, IC<13>{});
            float acc[20];
#pragma unroll
            for (int i = 0; i < 20; i++) acc[i] = 0.f;
#pragma unroll
            for (int i = 0; i < 5; i++) mma1688(acc + 4 * i, (i & 1) ? wf[20 + i / 2].z : wf[20 + i / 2].x, (i & 1) ? wf[20 + i / 2].w : wf[20 + i / 2].y, hw.x);
#pragma unroll
            for (int i = 0; i < 20; i++)
                mma16816(acc + 4 * (i % 5), wf[i].x, wf[i].y, wf[i].z, wf[i].w, (i / 5 & 1) ? hv[i / 10].z : hv[i / 10].x, (i / 5 & 1) ? hv[i / 10].w : hv[i / 10].y);
            if (qd == 0) {
#pragma unroll
                for (int i = 0; i < 5; i++) part[cw * 40 + i * 8 + g8] = make_float4(acc[4 * i], acc[4 * i + 1], acc[4 * i + 2], acc[4 * i + 3]);
            }
        }
        {
            uint2* dst = padd(g_ypart, ((cw * 9 * NCTA + blockIdx.x) * 8 + g8) * 8);
            bar_sync(3, 256);
            if (cw < 5) {
                const float* pp = reinterpret_cast<const float*>(part) + ((blockIdx.x & 1) << 4) + tid;
                const float g = rbf(((pp[0] + pp[160]) + (pp[320] + pp[480])) + ((pp[640] + pp[800]) + (pp[960] + pp[1120])));
                const float v = rbf(g * sigmoidf_(g)) * __shfl_down_sync(0xffffffffu, g, 2);
                if (!(tid & 2)) act[(tid & 1) * 56 + (tid >> 2)] = __float2bfloat16_rn(tid < 144 ? v : 0.f);
            }
            bar_sync(3, 256);
            DBG_G(113);
            const uint32_t ap = sb + 3 * SLOT + UNIT + 4096 + (lane & 1) * 112 + (lane >> 3) * 16;
            const uint4 b0 = ldsm4(ap);
            const uint32_t b1 = lds32(sb + 3 * SLOT + UNIT + 4096 + (g8 & 1) * 112 + 64 + qd * 4);
            float y[20];
#pragma unroll
            for (int i = 0; i < 20; i++) y[i] = 0.f;
#pragma unroll
            for (int i = 0; i < 5; i++) {
                mma16816(y + 4 * i, da[2 * i].x, da[2 * i].y, da[2 * i].z, da[2 * i].w, b0.x, b0.y);
                mma16816(y + 4 * i, da[2 * i + 1].x, da[2 * i + 1].y, da[2 * i + 1].z, da[2 * i + 1].w, b0.z, b0.w);
                mma1688(y + 4 * i, (i & 1) ? da[10 + i / 2].z : da[10 + i / 2].x, (i & 1) ? da[10 + i / 2].w : da[10 + i / 2].y, b1);
            }
#pragma unroll
            for (int i = 0; i < 9; i++)
                asm volatile("{\n.reg .pred p;\nsetp.eq.b32 p, %3, 0;\n@p st.relaxed.gpu.global.v2.f32 [%0], {%1, %2};\n}"
                             ::"l"(dst + i * (NCTA * 8)), "f"(y[2 * i]), "f"(y[2 * i + 1]), "r"(qd) : "memory");
        }
        DBG_G(114);
        if (blockIdx.x == 127 && tid == 0) gs->epoch[0] = tag;
        if (blockIdx.x < 72) {
            const int G = blockIdx.x, tok = g8 & 1, cp = G * 4 + qd;
            const uint2* src = padd(g_ypart, (blockIdx.x * NCTA * 8 + tid) * 8);
            const uint8_t* hsrc = reinterpret_cast<const uint8_t*>(padd(g_rows, (tok ? slot1 : slot0) * (RSLOT * 16) +
                (G < 64 ? (G >> 1 & 7) * 384 + (G >> 5) * 128 + qd * 16 + (G >> 1 & 8) + (G & 1) * 4 : (G - 64) * 384 + 256 + qd * 8)));
            const uint8_t* xsrc = hsrc + (G < 64 ? 64 : 4);
            uint32_t* dst = padd(reinterpret_cast<uint32_t*>(args.out), (tok ? sel1 : sel0) * (D_ * 2) + cp * 4);
            const uint32_t gb = reinterpret_cast<const uint32_t*>(smem_raw + SM_TG)[cp];
            const uint32_t ksel = ((tok ? k2 : k1) & ~2047u) | 1024u;
            const float sg = sigmoidf_(rbf(__uint_as_float((ksel & 0x80000000u) ? (ksel & 0x7fffffffu) : ~ksel)));
            uint2 v[4];
            uint32_t hv, xv, it = 0;
            bool miss;
#pragma unroll 1
            do {
#pragma unroll
                for (int i = 0; i < 4; i++) v[i] = ld_relaxed64(src + i * 256);
                hv = ld_relaxed32(hsrc);
                xv = ld_relaxed32(xsrc);
                miss = max(__vimax3_u32(v[0].x, v[1].x, v[2].x), __vimax3_u32(v[3].x, hv, xv)) == ~0u;
            } while (__any_sync(0xffffffffu, miss) && ++it < SPIN / 16);
            float y0 = (__uint_as_float(v[0].x) + __uint_as_float(v[1].x)) + (__uint_as_float(v[2].x) + __uint_as_float(v[3].x));
            float y1 = (__uint_as_float(v[0].y) + __uint_as_float(v[1].y)) + (__uint_as_float(v[2].y) + __uint_as_float(v[3].y));
            y0 += __shfl_xor_sync(0xffffffffu, y0, 8); y1 += __shfl_xor_sync(0xffffffffu, y1, 8);
            y0 += __shfl_xor_sync(0xffffffffu, y0, 16); y1 += __shfl_xor_sync(0xffffffffu, y1, 16);
            if (lane < 8) reinterpret_cast<float2*>(rec)[cw * 8 + lane] = make_float2(y0, y1);
            bar_sync(3, 256);
            if (cw == 0) {
                const float4 t0_ = rec[(lane >> 3) * 4 + qd], t1_ = rec[16 + (lane >> 3) * 4 + qd];
                y0 = tok ? t0_.y + t1_.y : t0_.x + t1_.x; y1 = tok ? t0_.w + t1_.w : t0_.z + t1_.z;
                y0 += __shfl_xor_sync(0xffffffffu, y0, 8); y1 += __shfl_xor_sync(0xffffffffu, y1, 8);
                y0 += __shfl_xor_sync(0xffffffffu, y0, 16); y1 += __shfl_xor_sync(0xffffffffu, y1, 16);
                const uint32_t y2 = bmul2(pack_bf16(y0, y1), pack_bf16(sg, sg));
                if (lane < 8) *dst = badd2(xv, bmul2(gb, badd2(hv, y2)));
            }
        }
        }
        DBG_T(88);
        DBG_G(121);
    }
}

typedef CUresult (*EncodeFn)(CUtensorMap*, CUtensorMapDataType, cuuint32_t, void*, const cuuint64_t*, const cuuint64_t*,
                             const cuuint32_t*, const cuuint32_t*, CUtensorMapInterleave, CUtensorMapSwizzle,
                             CUtensorMapL2promotion, CUtensorMapFloatOOBfill);

static void make_map(EncodeFn enc, CUtensorMap* m, const void* ptr, int rank, const cuuint64_t* dims,
                     const cuuint64_t* strides, const cuuint32_t* box, CUtensorMapSwizzle sw = CU_TENSOR_MAP_SWIZZLE_128B,
                     CUtensorMapDataType dt = CU_TENSOR_MAP_DATA_TYPE_BFLOAT16) {
    const cuuint32_t es[3] = {1, 1, 1};
    enc(m, dt, rank, const_cast<void*>(ptr), dims, strides, box, es,
        CU_TENSOR_MAP_INTERLEAVE_NONE, sw, CU_TENSOR_MAP_L2_PROMOTION_L2_128B,
        CU_TENSOR_MAP_FLOAT_OOB_FILL_NONE);
}

extern "C" void kernel_launch(void* const* d_in, const int* in_sizes, int n_in, void* d_out, int out_size) {
    const bf16* x = (const bf16*)d_in[0];
    const bf16* kc = (const bf16*)d_in[1];
    const bf16* vc = (const bf16*)d_in[2];
    const bf16* wq = (const bf16*)d_in[3];
    const bf16* wo = (const bf16*)d_in[4];
    const bf16* w_r = (const bf16*)d_in[6];
    const bf16* w_gate = (const bf16*)d_in[7];
    const bf16* w_up = (const bf16*)d_in[8];
    const bf16* w_down = (const bf16*)d_in[9];
    const bf16* cvec = (const bf16*)d_in[10];
    const bf16* w_mod = (const bf16*)d_in[11];
    bf16* out = (bf16*)d_out;

    void* fn = nullptr;
    cudaDriverEntryPointQueryResult qr;
    cudaGetDriverEntryPoint("cuTensorMapEncodeTiled", &fn, cudaEnableDefault, &qr);
    EncodeFn enc = (EncodeFn)fn;
    void* p_s;
    cudaGetSymbolAddress(&p_s, g_s);

    CUtensorMap tm_wq, tm_k, tm_v, tm_wo, tm_p, tm_x, tm_d, tm_g, tm_u;
    { cuuint64_t d[2] = {QD, D_}, s[1] = {QD * 2}; cuuint32_t b[2] = {64, 128}; make_map(enc, &tm_wq, wq, 2, d, s, b); }
    { cuuint64_t d[2] = {DH, HKV * S_}, s[1] = {DH * 2}; cuuint32_t b[2] = {64, 128};
      make_map(enc, &tm_k, kc, 2, d, s, b); make_map(enc, &tm_v, vc, 2, d, s, b); }
    { cuuint64_t d[2] = {D_, QD}, s[1] = {D_ * 2}; cuuint32_t b[2] = {64, 128}; make_map(enc, &tm_wo, wo, 2, d, s, b); }
    { cuuint64_t d[3] = {256, 160, NCTA}, s[2] = {1024, 8 * WREG}; cuuint32_t b[3] = {256, 2, 8};
      make_map(enc, &tm_p, ((Scratch*)p_s)->frag, 3, d, s, b, CU_TENSOR_MAP_SWIZZLE_NONE, CU_TENSOR_MAP_DATA_TYPE_UINT32); }
    { cuuint64_t d[2] = {D_ / 4, S_}, s[1] = {D_ * 2}; cuuint32_t b[2] = {XP / 8, 16};
      make_map(enc, &tm_x, x, 2, d, s, b, CU_TENSOR_MAP_SWIZZLE_NONE, CU_TENSOR_MAP_DATA_TYPE_UINT64); }
    { cuuint64_t d[2] = {D_ / 4, F_}, s[1] = {D_ * 2}; cuuint32_t b[2] = {XP / 8, 18};
      make_map(enc, &tm_d, w_down, 2, d, s, b, CU_TENSOR_MAP_SWIZZLE_NONE, CU_TENSOR_MAP_DATA_TYPE_UINT64); }
    { cuuint64_t d[2] = {F_, D_}, s[1] = {F_ * 2}; cuuint32_t b[2] = {40, 24};
      make_map(enc, &tm_g, w_gate, 2, d, s, b, CU_TENSOR_MAP_SWIZZLE_NONE); make_map(enc, &tm_u, w_up, 2, d, s, b, CU_TENSOR_MAP_SWIZZLE_NONE); }

    cudaFuncSetAttribute(fused_kernel<true>, cudaFuncAttributeMaxDynamicSharedMemorySize, SM_TOTAL);
    cudaFuncSetAttribute(fused_kernel<false>, cudaFuncAttributeMaxDynamicSharedMemorySize, SM_TOTAL);
    cudaLaunchConfig_t cfg = {};
    cfg.gridDim = NCTA + 4; cfg.blockDim = 384; cfg.dynamicSmemBytes = SM_TOTAL;
    cudaLaunchAttribute at;
    at.id = cudaLaunchAttributeClusterDimension; at.val.clusterDim.x = 2; at.val.clusterDim.y = 1; at.val.clusterDim.z = 1;
    cfg.attrs = &at; cfg.numAttrs = 1;
    int ncl = 0;
    if (cudaOccupancyMaxActiveClusters(&ncl, fused_kernel<true>, &cfg) != cudaSuccess) { ncl = 0; cudaGetLastError(); }
    Args args{w_mod, cvec, (Scratch*)p_s, desc_lo(0, UNIT) | (0x40000040ull << 32), out, x, kc, vc, wq, wo, w_r, w_down};
    if (USE_SPARE && ncl >= NCTA / 2 + 2)
        fused_kernel<true><<<NCTA + 4, 384, SM_TOTAL>>>(args, tm_wq, tm_k, tm_v, tm_wo, tm_p, tm_x, tm_d, tm_g, tm_u);
    else
        fused_kernel<false><<<NCTA, 384, SM_TOTAL>>>(args, tm_wq, tm_k, tm_v, tm_wo, tm_p, tm_x, tm_d, tm_g, tm_u);
}
```

```cpp
#include <cuda_runtime.h>
#include <cuda_bf16.h>
#include <cuda.h>
#include <stdint.h>
#include <math.h>

typedef __nv_bfloat16 bf16;

constexpr int S_ = 2048;
constexpr int D_ = 576;
constexpr int HQ = 32, HKV = 16, DH = 128;
constexpr int F_ = 4608;
constexpr int QD = HQ * DH;

constexpr int NCTA = 128;
constexpr int WREG = 5 * 4096;
constexpr int CREP = 8;
constexpr int RSLOT = 192;
constexpr int MREP = 4;
struct Scratch {
    unsigned int epoch[128];
    unsigned int flag_mod[NCTA];
    unsigned int flag_part[16 * 32];
    unsigned int flag_q3[16 * 32];
    unsigned int flag_h[NCTA * 32];
    uint2 mod1[MREP * D_];
    uint32_t mod2[4 * D_];
    uint4 cand[CREP * NCTA * 2];
    uint2 ypart[72 * NCTA * 8];
    uint4 h[2][NCTA * 36 * 32];
    uint4 q3[NCTA * 8 * 128];
    uint4 rows[NCTA * 2 * RSLOT];
    uint8_t frag[NCTA * 8 * WREG];
    uint8_t keep[NCTA * 8 * 4096];
};
__device__ __align__(1024) Scratch g_s;
#define g_h gs->h[tag & 1]
#define g_q3 gs->q3
#define g_keep gs->keep
#define g_flag_h gs->flag_h
#define g_flag_part gs->flag_part
#define g_flag_mod gs->flag_mod
#define g_flag_q3 gs->flag_q3
#define g_frag gs->frag
#define g_cand gs->cand
#define g_ypart gs->ypart
#define g_rows gs->rows

#define DBG_INIT()
#define DBG_P(i)
#define DBG_PG(i)
#define DBG_T(i)
#define DBG_G(i)

__device__ __forceinline__ uint32_t pack_bf16(float lo, float hi) {
    uint32_t r;
    asm("cvt.rn.bf16x2.f32 %0, %1, %2;" : "=r"(r) : "f"(hi), "f"(lo));
    return r;
}
__device__ __forceinline__ float rbf(float x) { return __uint_as_float(pack_bf16(0.f, x)); }
__device__ __forceinline__ float bf_lo(uint32_t v) { return __uint_as_float(v << 16); }
__device__ __forceinline__ float bf_hi(uint32_t v) { return __uint_as_float(v & 0xffff0000u); }
__device__ __forceinline__ float ex2(float x) {
    float y;
    asm("ex2.approx.ftz.f32 %0, %1;" : "=f"(y) : "f"(x));
    return y;
}
template <class T>
__device__ __forceinline__ T* padd(T* p, uint32_t off) {
    unsigned long long r;
    asm("{\n.reg .b32 l, h;\nmov.b64 {l, h}, %1;\nadd.cc.u32 l, l, %2;\naddc.u32 h, h, 0;\nmov.b64 %0, {l, h};\n}" : "=l"(r) : "l"(p), "r"(off));
    return reinterpret_cast<T*>(r);
}
__device__ __forceinline__ uint32_t smem_u32(const void* p) { return (uint32_t)__cvta_generic_to_shared(p); }
__device__ __forceinline__ void mbar_init(uint32_t bar, uint32_t cnt) {
    asm volatile("mbarrier.init.shared::cta.b64 [%0], %1;" ::"r"(bar), "r"(cnt) : "memory");
}
__device__ __forceinline__ void mbar_expect_tx(uint32_t bar, uint32_t bytes) {
    asm volatile("mbarrier.arrive.expect_tx.shared::cta.b64 _, [%0], %1;" ::"r"(bar), "r"(bytes) : "memory");
}
__device__ __forceinline__ void mbar_arrive(uint32_t bar) {
    asm volatile("mbarrier.arrive.shared::cta.b64 _, [%0];" ::"r"(bar) : "memory");
}
__device__ __forceinline__ void mbar_arrive_cluster(uint32_t cluster_addr) {
    asm volatile("mbarrier.arrive.shared::cluster.b64 _, [%0];" ::"r"(cluster_addr) : "memory");
}
constexpr uint32_t SPIN = 1u << 20;
__device__ __forceinline__ void mbar_wait(uint32_t bar, uint32_t parity) {
    asm volatile("{\n.reg .pred p;\n.reg .b32 c;\nmov.b32 c, 0;\n"
                 "W_%=:\nmbarrier.try_wait.parity.shared::cta.b64 p, [%0], %1;\n"
                 "add.u32 c, c, 1;\nsetp.lt.and.u32 p, c, 0x100000, !p;\n@p bra W_%=;\n}"
                 ::"r"(bar), "r"(parity) : "memory");
}
__device__ __forceinline__ void anchor(uint32_t addr, float v) {
    asm volatile("{\n.reg .pred p;\nsetp.lt.f32 p, %1, 0f00000000;\n@p st.volatile.shared.f32 [%0], %1;\n}" ::"r"(addr), "f"(v) : "memory");
}
__device__ __forceinline__ void anchor(uint32_t addr, uint32_t v) {
    asm volatile("{\n.reg .pred p;\nsetp.eq.u32 p, %1, 0xffffffff;\n@p st.volatile.shared.u32 [%0], %1;\n}" ::"r"(addr), "r"(v) : "memory");
}
__device__ __forceinline__ void anchor(void* p, uint32_t v) {
    asm volatile("{\n.reg .pred p;\nsetp.eq.u32 p, %1, 0xffffffff;\n@p st.volatile.u32 [%0], %1;\n}" ::"l"(p), "r"(v) : "memory");
}
__device__ __forceinline__ void hold(float& a, float& b) {
    asm volatile("{\n.reg .pred p;\n.reg .b64 t;\n.reg .b32 l, h;\nmov.u64 t, %%clock64;\nmov.b64 {l, h}, t;\nsetp.eq.u32 p, h, 0xffffffff;\n"
                 "@p mov.f32 %0, 0f00000000;\n@p mov.f32 %1, 0f00000000;\n}" : "+f"(a), "+f"(b) :: "memory");
}
__device__ __forceinline__ void mbar_wait_sleep(uint32_t bar, uint32_t parity) {
    asm volatile("{\n.reg .pred p;\n.reg .b32 c;\nmov.b32 c, 0;\n"
                 "W_%=:\nmbarrier.try_wait.parity.shared::cta.b64 p, [%0], %1, 5000;\n"
                 "add.u32 c, c, 1;\nsetp.lt.and.u32 p, c, 0x20000, !p;\n@p bra W_%=;\n}"
                 ::"r"(bar), "r"(parity) : "memory");
}
__device__ __forceinline__ uint32_t load_tag(const Scratch* gs) {
    uint32_t tag;
    asm volatile("ld.global.ca.u32 %0, [%1];" : "=r"(tag) : "l"(gs->epoch) : "memory");
    return tag + 1;
}
__device__ __forceinline__ uint4 ld_relaxed(const uint4* p) {
    uint4 v;
    asm volatile("ld.relaxed.gpu.global.v4.u32 {%0,%1,%2,%3}, [%4];" : "=r"(v.x), "=r"(v.y), "=r"(v.z), "=r"(v.w) : "l"(p) : "memory");
    return v;
}
__device__ __forceinline__ void st_relaxed(uint4* p, uint32_t a, uint32_t b, uint32_t c, uint32_t d) {
    asm volatile("{\n.reg .b64 u, v;\nmov.b64 u, {%1, %2};\nmov.b64 v, {%3, %4};\nst.relaxed.gpu.global.v2.b64 [%0], {u, v};\n}"
                 ::"l"(p), "r"(a), "r"(b), "r"(c), "r"(d) : "memory");
}
__device__ __forceinline__ void st_relaxed4(void* p, uint32_t a, uint32_t b, uint32_t c, uint32_t d) {
    asm volatile("st.relaxed.gpu.global.v4.u32 [%0], {%1, %2, %3, %4};" ::"l"(p), "r"(a), "r"(b), "r"(c), "r"(d) : "memory");
}
__device__ __forceinline__ uint2 ld_relaxed64(const uint2* p) {
    uint2 v;
    asm volatile("{\n.reg .b64 u;\nld.relaxed.gpu.global.b64 u, [%2];\nmov.b64 {%0, %1}, u;\n}" : "=r"(v.x), "=r"(v.y) : "l"(p) : "memory");
    return v;
}
__device__ __forceinline__ void st_relaxed64(uint2* p, uint32_t a, uint32_t b) {
    asm volatile("{\n.reg .b64 u;\nmov.b64 u, {%1, %2};\nst.relaxed.gpu.global.b64 [%0], u;\n}" ::"l"(p), "r"(a), "r"(b) : "memory");
}
__device__ __forceinline__ uint4 ld_relaxed2(const uint4* p) {
    uint4 v;
    asm volatile("{\n.reg .b64 u, w;\nld.relaxed.gpu.global.v2.b64 {u, w}, [%4];\nmov.b64 {%0, %1}, u;\nmov.b64 {%2, %3}, w;\n}"
                 : "=r"(v.x), "=r"(v.y), "=r"(v.z), "=r"(v.w) : "l"(p) : "memory");
    return v;
}
__device__ __forceinline__ void reload16(uint4& v, const void* p, uint32_t& miss) {
    asm volatile("{\n.reg .pred p;\n.reg .b32 m;\n.reg .b64 u, w;\nmax.u32 m, %0, %2;\nsetp.eq.u32 p, m, 0xffffffff;\n"
                 "mov.b64 u, {%0, %1};\nmov.b64 w, {%2, %3};\n@p ld.relaxed.gpu.global.v2.b64 {u, w}, [%5];\n"
                 "mov.b64 {%0, %1}, u;\nmov.b64 {%2, %3}, w;\n@p mov.u32 %4, 1;\n}"
                 : "+r"(v.x), "+r"(v.y), "+r"(v.z), "+r"(v.w), "+r"(miss) : "l"(p) : "memory");
}
__device__ __forceinline__ void reload8(uint2& v, const void* p, uint32_t& miss) {
    asm volatile("{\n.reg .pred p;\n.reg .b64 u;\nsetp.eq.u32 p, %0, 0xffffffff;\nmov.b64 u, {%0, %1};\n"
                 "@p ld.relaxed.gpu.global.b64 u, [%3];\nmov.b64 {%0, %1}, u;\n@p mov.u32 %2, 1;\n}"
                 : "+r"(v.x), "+r"(v.y), "+r"(miss) : "l"(p) : "memory");
}
__device__ __forceinline__ uint32_t ld_relaxed32(const void* p) {
    uint32_t v;
    asm volatile("ld.relaxed.gpu.global.u32 %0, [%1];" : "=r"(v) : "l"(p) : "memory");
    return v;
}
__device__ __forceinline__ void flag_wait(const unsigned int* p, uint32_t tag) {
    uint32_t v, it = 0;
#pragma unroll 1
    do {
        asm volatile("ld.relaxed.gpu.global.u32 %0, [%1];" : "=r"(v) : "l"(p) : "memory");
    } while (__any_sync(0xffffffffu, v != tag) && ++it < SPIN / 16);
    asm volatile("fence.acquire.gpu;" ::: "memory");
    __syncwarp();
}
__device__ __forceinline__ bool elect() {
    uint32_t p;
    asm volatile("{\n.reg .pred p;\nelect.sync _|p, 0xffffffff;\nselp.u32 %0, 1, 0, p;\n}" : "=r"(p));
    return p;
}
__device__ __forceinline__ void flag_release(unsigned int* p, uint32_t tag) {
    asm volatile("st.release.gpu.global.u32 [%0], %1;" ::"l"(p), "r"(tag) : "memory");
}
__device__ __forceinline__ uint32_t touch(const void* p) {
    uint32_t v;
    asm volatile("ld.global.nc.L1::no_allocate.L2::128B.u32 %0, [%1];" : "=r"(v) : "l"(p));
    return v;
}
__device__ __forceinline__ void bar_sync(int id, int n) { asm volatile("bar.sync %0, %1;" ::"r"(id), "r"(n) : "memory"); }
__device__ __forceinline__ void bar_arrive(int id, int n) { asm volatile("bar.arrive %0, %1;" ::"r"(id), "r"(n) : "memory"); }

constexpr uint64_t EVICT_NORMAL = 0x1000000000000000ull, EVICT_FIRST = 0x12F0000000000000ull;
__device__ __forceinline__ void tma2d(uint32_t dst, const CUtensorMap* m, int c0, int c1, uint32_t bar) {
    asm volatile("cp.async.bulk.tensor.2d.shared::cluster.global.mbarrier::complete_tx::bytes.L2::cache_hint [%0], [%1, {%3, %4}], [%2], %5;"
                 ::"r"(dst), "l"(m), "r"(bar), "r"(c0), "r"(c1), "l"(EVICT_FIRST) : "memory");
}
__device__ __forceinline__ void tma2d_mc(uint32_t dst, const CUtensorMap* m, int c0, int c1, uint32_t bar, uint64_t pol) {
    asm volatile("cp.async.bulk.tensor.2d.shared::cluster.global.mbarrier::complete_tx::bytes.multicast::cluster.L2::cache_hint [%0], [%1, {%3, %4}], [%2], %5, %6;"
                 ::"r"(dst), "l"(m), "r"(bar), "r"(c0), "r"(c1), "h"((uint16_t)3), "l"(pol) : "memory");
}
__device__ __forceinline__ void tma3d(uint32_t dst, const CUtensorMap* m, int c0, int c1, int c2, uint32_t bar) {
    asm volatile("cp.async.bulk.tensor.3d.shared::cluster.global.mbarrier::complete_tx::bytes.L2::cache_hint [%0], [%1, {%3, %4, %5}], [%2], %6;"
                 ::"r"(dst), "l"(m), "r"(bar), "r"(c0), "r"(c1), "r"(c2), "l"(EVICT_FIRST) : "memory");
}
__device__ __forceinline__ void bulk_load(uint32_t dst, const void* src, uint32_t bytes, uint32_t bar) {
    asm volatile("cp.async.bulk.shared::cluster.global.mbarrier::complete_tx::bytes [%0], [%1], %2, [%3];"
                 ::"r"(dst), "l"(src), "r"(bytes), "r"(bar) : "memory");
}
__device__ __forceinline__ void l2_prefetch(const void* src, uint32_t bytes) {
    asm volatile("cp.async.bulk.prefetch.L2.global [%0], %1;" ::"l"(src), "r"(bytes) : "memory");
}
__device__ __forceinline__ uint32_t bmul2(uint32_t a, uint32_t b) { uint32_t r; asm("mul.rn.bf16x2 %0, %1, %2;" : "=r"(r) : "r"(a), "r"(b)); return r; }
__device__ __forceinline__ uint32_t badd2(uint32_t a, uint32_t b) { uint32_t r; asm("add.rn.bf16x2 %0, %1, %2;" : "=r"(r) : "r"(a), "r"(b)); return r; }
__device__ __forceinline__ uint32_t bsub2(uint32_t a, uint32_t b) { uint32_t r; asm("sub.rn.bf16x2 %0, %1, %2;" : "=r"(r) : "r"(a), "r"(b)); return r; }
__device__ __forceinline__ uint32_t bmax2(uint32_t a, uint32_t b) { uint32_t r; asm("max.bf16x2 %0, %1, %2;" : "=r"(r) : "r"(a), "r"(b)); return r; }
__device__ __forceinline__ uint4 lds128(uint32_t a) { uint4 v; asm volatile("ld.shared.v4.u32 {%0,%1,%2,%3}, [%4];" : "=r"(v.x), "=r"(v.y), "=r"(v.z), "=r"(v.w) : "r"(a) : "memory"); return v; }
__device__ __forceinline__ uint2 lds64(uint32_t a) { uint2 v; asm volatile("ld.shared.v2.u32 {%0,%1}, [%2];" : "=r"(v.x), "=r"(v.y) : "r"(a) : "memory"); return v; }
__device__ __forceinline__ uint32_t lds32(uint32_t a) { uint32_t v; asm volatile("ld.shared.u32 %0, [%1];" : "=r"(v) : "r"(a) : "memory"); return v; }
__device__ __forceinline__ uint4 ldsm4(uint32_t a) {
    uint4 v;
    asm volatile("ldmatrix.sync.aligned.m8n8.x4.shared.b16 {%0,%1,%2,%3}, [%4];" : "=r"(v.x), "=r"(v.y), "=r"(v.z), "=r"(v.w) : "r"(a) : "memory");
    return v;
}
__device__ __forceinline__ uint4 ldsm4t(uint32_t a) {
    uint4 v;
    asm volatile("ldmatrix.sync.aligned.m8n8.x4.trans.shared.b16 {%0,%1,%2,%3}, [%4];" : "=r"(v.x), "=r"(v.y), "=r"(v.z), "=r"(v.w) : "r"(a) : "memory");
    return v;
}
__device__ __forceinline__ void mma1688(float* d, uint32_t a0, uint32_t a1, uint32_t b) {
    asm("mma.sync.aligned.m16n8k8.row.col.f32.bf16.bf16.f32 {%0,%1,%2,%3}, {%4,%5}, {%6}, {%0,%1,%2,%3};"
        : "+f"(d[0]), "+f"(d[1]), "+f"(d[2]), "+f"(d[3]) : "r"(a0), "r"(a1), "r"(b));
}
__device__ __forceinline__ void mma16816(float* d, uint32_t a0, uint32_t a1, uint32_t a2, uint32_t a3, uint32_t b0, uint32_t b1) {
    asm("mma.sync.aligned.m16n8k16.row.col.f32.bf16.bf16.f32 {%0,%1,%2,%3}, {%4,%5,%6,%7}, {%8,%9}, {%0,%1,%2,%3};"
                 : "+f"(d[0]), "+f"(d[1]), "+f"(d[2]), "+f"(d[3]) : "r"(a0), "r"(a1), "r"(a2), "r"(a3), "r"(b0), "r"(b1));
}
__device__ __forceinline__ void stsm_x4(uint32_t addr, uint32_t a, uint32_t b, uint32_t c, uint32_t d) {
    asm volatile("stmatrix.sync.aligned.m8n8.x4.shared.b16 [%0], {%1, %2, %3, %4};"
                 ::"r"(addr), "r"(a), "r"(b), "r"(c), "r"(d) : "memory");
}

__device__ __forceinline__ uint64_t mkdesc(uint32_t addr, uint32_t lbo, uint32_t sbo) {
    return (uint64_t)((addr & 0x3FFFF) >> 4) | ((uint64_t)(lbo >> 4) << 16) | ((uint64_t)(sbo >> 4) << 32) | (1ull << 62);
}
constexpr uint32_t SM0 = 1024;
__host__ __device__ constexpr uint32_t desc_lo(uint32_t off, uint32_t lbo) { return ((SM0 + off) >> 4) | ((lbo >> 4) << 16); }
#define WG_FENCE() asm volatile("wgmma.fence.sync.aligned;" ::: "memory")
#define WG_COMMIT() asm volatile("wgmma.commit_group.sync.aligned;" ::: "memory")
#define WG_WAIT(n) asm volatile("wgmma.wait_group.sync.aligned %0;" ::"n"(n) : "memory")

#define F8(a, i) "+f"(a[i]), "+f"(a[i + 1]), "+f"(a[i + 2]), "+f"(a[i + 3]), "+f"(a[i + 4]), "+f"(a[i + 5]), "+f"(a[i + 6]), "+f"(a[i + 7])
#define F16(a, i) F8(a, i), F8(a, i + 8)
#define F64(a) F16(a, 0), F16(a, 16), F16(a, 32), F16(a, 48)
#define F32(a) F16(a, 0), F16(a, 16)
#define L64 "%0,%1,%2,%3,%4,%5,%6,%7,%8,%9,%10,%11,%12,%13,%14,%15,%16,%17,%18,%19,%20,%21,%22,%23,%24,%25,%26,%27,%28,%29,%30,%31,%32,%33,%34,%35,%36,%37,%38,%39,%40,%41,%42,%43,%44,%45,%46,%47,%48,%49,%50,%51,%52,%53,%54,%55,%56,%57,%58,%59,%60,%61,%62,%63"
#define L32 "%0,%1,%2,%3,%4,%5,%6,%7,%8,%9,%10,%11,%12,%13,%14,%15,%16,%17,%18,%19,%20,%21,%22,%23,%24,%25,%26,%27,%28,%29,%30,%31"

template <int TB, int STEP = 128>
__device__ __forceinline__ void mma_rs128(float (&d)[64], uint32_t a0, uint32_t a1, uint32_t a2, uint32_t a3, uint64_t& b, int acc) {
    asm volatile("{\n.reg .pred p;\nsetp.ne.b32 p, %69, 0;\n"
                 "wgmma.mma_async.sync.aligned.m64n128k16.f32.bf16.bf16 {" L64 "}, {%65,%66,%67,%68}, %64, p, 1, 1, %70;\nadd.s64 %64, %64, %71;\n}"
                 : F64(d), "+l"(b) : "r"(a0), "r"(a1), "r"(a2), "r"(a3), "r"(acc), "n"(TB), "n"(STEP));
}
template <int TB>
__device__ __forceinline__ void mma_rs64(float (&d)[32], uint32_t a0, uint32_t a1, uint32_t a2, uint32_t a3, uint64_t& b, int acc) {
    asm volatile("{\n.reg .pred p;\nsetp.ne.b32 p, %37, 0;\n"
                 "wgmma.mma_async.sync.aligned.m64n64k16.f32.bf16.bf16 {" L32 "}, {%33,%34,%35,%36}, %32, p, 1, 1, %38;\nadd.s64 %32, %32, 128;\n}"
                 : F32(d), "+l"(b) : "r"(a0), "r"(a1), "r"(a2), "r"(a3), "r"(acc), "n"(TB));
}
template <int N>
__device__ __forceinline__ void fence_regs(float (&d)[N]) {
#pragma unroll
    for (int i = 0; i < N; i++) asm volatile("" : "+f"(d[i])::"memory");
}
template <int N>
__device__ __forceinline__ void fence_regs(uint32_t (&d)[N]) {
#pragma unroll
    for (int i = 0; i < N; i++) asm volatile("" : "+r"(d[i])::"memory");
}

template <int V> struct IC { static constexpr int value = V; };

constexpr int SLOT = 32768, UNIT = 16384;
constexpr int SM_Q = 4 * SLOT;
constexpr int SM_BAR = 7 * SLOT;
constexpr int SM_RED = SM_BAR + 512;
constexpr int SM_TOTAL = SM_BAR + 3072;
constexpr int XP = D_ * 2 + 16;
constexpr int M_MOD = 16 * XP;
constexpr int SM_T = SM_Q + 2 * D_ * 80, SM_TC = SM_T + D_ * 4, SM_TG = SM_TC + D_ * 4, SM_TS = SM_TG + D_ * 2;
constexpr float CS = 0.08838834764831845f * 1.4426950408889634f;
#define USE_SPARE 1
constexpr float POFF = 102.f, LMIN = 0x1p-104f;
#define LMAX 0.5f
constexpr int SPLIT = 10;
constexpr int STAGE = 11;
constexpr int ESPLIT = 3;
constexpr int QSPLIT = 4, OSPLIT = 6;
#define OE 0
#define OED 0
#define NOOUT 0
#define RD 0
#define RP 1
#define T_X 0
#define T_B 0
#define T_C 1
#define T_U 1
#define T_D 1
#define W0_ 3
#define W1_ 13
#define W2_ 19
#define DL_ 9
constexpr int WF0 = W0_, WF1 = W1_, WF2 = W2_, DL = DL_;
constexpr int PF_KV = 4, PF_WO = 120;

__device__ __forceinline__ int cluster_role() {
    int k;
    asm volatile("mov.u32 %0, %%ctaid.x;" : "=r"(k));
    k >>= 1;
    const int r = ((k - 36) * 37) >> 8, i = k - 36 - r * 7;
    return k < 4 ? 12 + k : k < 36 ? ((k - 4) & 7) * 8 + ((k - 4) >> 3) : (i + (i > 0)) * 8 + ((4 + r) & 7);
}

struct Args {
    const bf16 *w_mod, *cvec;
    Scratch* gs;
    uint64_t d0;
    bf16* out;
    const bf16 *x, *kc, *vc, *wq, *wo, *w_r, *w_down;
};

__device__ __forceinline__ void frag_store(uint8_t* p, const uint32_t (&a)[32]) {
#pragma unroll
    for (int i = 0; i < 8; i++)
        __stcg(reinterpret_cast<uint4*>(p + i * 512), make_uint4(a[4 * i], a[4 * i + 1], a[4 * i + 2], a[4 * i + 3]));
}
template <int LO = 0, int HI = 8>
__device__ __forceinline__ void frag_load(uint32_t (&a)[32], const uint8_t* p) {
#pragma unroll
    for (int i = LO; i < HI; i++) {
        const uint4 v = ld_relaxed(reinterpret_cast<const uint4*>(p + i * 512));
        a[4 * i] = v.x; a[4 * i + 1] = v.y; a[4 * i + 2] = v.z; a[4 * i + 3] = v.w;
    }
}
__device__ __forceinline__ float quad_sum(float v) {
    v += __shfl_xor_sync(0xffffffffu, v, 1);
    return v + __shfl_xor_sync(0xffffffffu, v, 2);
}
__device__ __forceinline__ float quad_max(float v) {
    v = fmaxf(v, __shfl_xor_sync(0xffffffffu, v, 1));
    return fmaxf(v, __shfl_xor_sync(0xffffffffu, v, 2));
}
__device__ __forceinline__ float rcp_fast(float x) { float y; asm("rcp.approx.ftz.f32 %0, %1;" : "=f"(y) : "f"(x)); return y; }
__device__ __forceinline__ float sigmoidf_(float x) { return rcp_fast(1.f + ex2(-1.4426950408889634f * x)); }
__device__ __forceinline__ void top2(uint32_t k, uint32_t& k1, uint32_t& k2) {
    k1 = __reduce_max_sync(0xffffffffu, k);
    k2 = __reduce_max_sync(0xffffffffu, k == k1 ? 0 : k);
}

__device__ __forceinline__ void mod_fma(float (&a)[8], const uint4 w, float sc) {
    a[0] += sc * bf_lo(w.x); a[1] += sc * bf_hi(w.x); a[2] += sc * bf_lo(w.y); a[3] += sc * bf_hi(w.y);
    a[4] += sc * bf_lo(w.z); a[5] += sc * bf_hi(w.z); a[6] += sc * bf_lo(w.w); a[7] += sc * bf_hi(w.w);
}
__device__ __forceinline__ float mod_reduce(float (&a)[8], int lane) {
#pragma unroll
    for (int h = 4; h > 0; h >>= 1) {
        const bool up = lane & (8 / h);
#pragma unroll
        for (int i = 0; i < h; i++)
            a[i] = (up ? a[i + h] : a[i]) + __shfl_xor_sync(0xffffffffu, up ? a[i] : a[i + h], 8 / h);
    }
    return a[0] + __shfl_xor_sync(0xffffffffu, a[0], 16);
}

__device__ __forceinline__ float ln_stats(float sum, float sq, uint32_t& mean2) {
    const float mean = sum * (1.f / D_);
    const float var = fmaxf(fmaf(-mean, mean, sq * (1.f / D_)), 0.f);
    float sd;
    asm("sqrt.approx.ftz.f32 %0, %1;" : "=f"(sd) : "f"(rbf(rbf(var) + 1e-5f)));
    mean2 = pack_bf16(mean, mean);
    return rcp_fast(rbf(sd));
}
__device__ __forceinline__ uint32_t ln_pair(uint32_t x, uint32_t mean2, float rsd) {
    const uint32_t d = bsub2(x, mean2);
    return pack_bf16(bf_lo(d) * rsd, bf_hi(d) * rsd);
}
__device__ __forceinline__ void rows_load(uint32_t (&x)[20], uint32_t xs, int cw) {
#pragma unroll
    for (int ch = 0; ch < 5; ch++) {
        const uint4 v = ldsm4(ch < 4 ? xs + ch * 256 : xs + 1024 - cw * 16);
        x[4 * ch] = v.x; x[4 * ch + 1] = v.y; x[4 * ch + 2] = v.z; x[4 * ch + 3] = v.w;
    }
}
__device__ __forceinline__ void stats_add(float (&st)[12], uint32_t a, uint32_t b, uint32_t w) {
    mma1688(st, a, b, w);
    mma1688(st + 4, a, b, a);
    mma1688(st + 8, a, b, b);
}
__device__ __forceinline__ float rows_stats(const float (&st)[12], float4* rec, int cw, int lane, uint32_t& mean2, float& dot) {
    const int g8 = lane >> 2;
    if ((g8 >> 1) == (lane & 3)) {
        rec[cw * 16 + g8] = make_float4(st[0], (g8 & 1) ? st[5] : st[4], st[1], 0.f);
        rec[cw * 16 + 8 + g8] = make_float4(st[2], (g8 & 1) ? st[11] : st[10], st[3], 0.f);
    }
    bar_sync(3, 256);
    const float4* r = rec + (lane >> 4) * 64 + (lane & 15);
    const float4 s0 = r[0], s1 = r[16], s2 = r[32], s3 = r[48];
    const float sum = (s0.x + s1.x) + (s2.x + s3.x), sq = (s0.y + s1.y) + (s2.y + s3.y);
    dot = (s0.z + s1.z) + (s2.z + s3.z);
    dot += __shfl_xor_sync(0xffffffffu, dot, 16);
    return ln_stats(sum + __shfl_xor_sync(0xffffffffu, sum, 16), sq + __shfl_xor_sync(0xffffffffu, sq, 16), mean2);
}
template <class F>
__device__ __forceinline__ void rows_normalise(uint32_t* y, const uint32_t* x, uint32_t mean2, float rsd, int lane, F loads) {
    const int g8 = lane >> 2;
    const uint32_t ma2 = __shfl_sync(0xffffffffu, mean2, g8), mb2 = __shfl_sync(0xffffffffu, mean2, g8 + 8);
    const float ra = __shfl_sync(0xffffffffu, rsd, g8), rb = __shfl_sync(0xffffffffu, rsd, g8 + 8);
    loads();
#pragma unroll
    for (int k = 0; k < 9; k++) { y[2 * k] = ln_pair(x[2 * k], ma2, ra); y[2 * k + 1] = ln_pair(x[2 * k + 1], mb2, rb); }
}

__device__ __forceinline__ uint4 h_frag(const uint4* hf, int ks, int lane) {
    if (ks < 32) return ld_relaxed2(hf + ks * 32);
    const uint2* p = reinterpret_cast<const uint2*>(padd(hf, 256 - lane * 8) + ks * 32 - 16);
    const uint2 a = ld_relaxed64(p), b = ld_relaxed64(p + 32);
    return make_uint4(a.x, a.y, b.x, b.y);
}

__device__ __noinline__ void attn_fallback(uint32_t bad, uint32_t tag, const Scratch* gs, uint8_t* frag, uint8_t* keep, const bf16* wq, const bf16* kc, const bf16* vc) {
  const int lane = threadIdx.x & 31, g8 = lane >> 2, qd = lane & 3;
  const int role = cluster_role(), j = role & 7, qb = (role >> 3) * 2 + (blockIdx.x & 1);
  const uint4* hf = g_h + (size_t)(qb * 8 + (threadIdx.x >> 5) - 4) * (36 * 32) + lane;
#pragma unroll 1
  for (int t = 0; t < 4; t++) {
    if (!((bad >> t) & 1)) continue;
    const bf16 *wqp = wq + (4 * j + t) * DH, *kp = kc + (size_t)(2 * j + (t >> 1)) * S_ * DH, *vp = vc + (size_t)(2 * j + (t >> 1)) * S_ * DH;
    uint32_t q[32];
    float o[64];
#pragma unroll
    for (int i = 0; i < 64; i++) o[i] = 0.f;
#pragma unroll 1
    for (int ks = 0; ks < 36; ks++) {
        const uint4 a = h_frag(hf, ks, lane);
        const unsigned short* wr = reinterpret_cast<const unsigned short*>(wqp + (size_t)(ks * 16 + 2 * qd) * QD + g8);
#pragma unroll
        for (int dt = 0; dt < 16; dt++) {
            const uint32_t b0 = __ldg(wr + dt * 8) | ((uint32_t)__ldg(wr + dt * 8 + QD) << 16);
            const uint32_t b1 = __ldg(wr + dt * 8 + 8 * QD) | ((uint32_t)__ldg(wr + dt * 8 + 9 * QD) << 16);
            mma16816(o + 4 * dt, a.x, a.y, a.z, a.w, b0, b1);
        }
    }
#pragma unroll
    for (int i = 0; i < 32; i++) q[i] = pack_bf16(o[2 * i], o[2 * i + 1]);
#pragma unroll
    for (int i = 0; i < 64; i++) o[i] = 0.f;
    float m0 = -INFINITY, m1 = -INFINITY, l0 = 0.f, l1 = 0.f;
#pragma unroll 1
    for (int key = 0; key < S_; key += 16) {
        float sc[8];
#pragma unroll
        for (int i = 0; i < 8; i++) sc[i] = 0.f;
#pragma unroll
        for (int nt = 0; nt < 2; nt++) {
            const uint32_t* kr = reinterpret_cast<const uint32_t*>(kp + (size_t)(key + nt * 8 + g8) * DH) + qd;
#pragma unroll
            for (int ks = 0; ks < 8; ks++)
                mma16816(sc + 4 * nt, q[4 * ks], q[4 * ks + 1], q[4 * ks + 2], q[4 * ks + 3], __ldg(kr + ks * 8), __ldg(kr + ks * 8 + 4));
        }
        const float n0 = quad_max(fmaxf(fmaxf(m0, fmaxf(sc[0], sc[1])), fmaxf(sc[4], sc[5])));
        const float n1 = quad_max(fmaxf(fmaxf(m1, fmaxf(sc[2], sc[3])), fmaxf(sc[6], sc[7])));
        const float f0 = ex2((m0 - n0) * CS), f1 = ex2((m1 - n1) * CS);
        m0 = n0; m1 = n1;
#pragma unroll
        for (int i = 0; i < 8; i++) sc[i] = ex2((sc[i] - ((i & 2) ? n1 : n0)) * CS);
        l0 = l0 * f0 + (sc[0] + sc[1]) + (sc[4] + sc[5]);
        l1 = l1 * f1 + (sc[2] + sc[3]) + (sc[6] + sc[7]);
        const uint32_t e0 = pack_bf16(sc[0], sc[1]), e1 = pack_bf16(sc[2], sc[3]), e2 = pack_bf16(sc[4], sc[5]), e3 = pack_bf16(sc[6], sc[7]);
        const unsigned short* vr = reinterpret_cast<const unsigned short*>(vp + (size_t)(key + 2 * qd) * DH + g8);
#pragma unroll
        for (int dt = 0; dt < 16; dt++) {
            o[4 * dt] *= f0; o[4 * dt + 1] *= f0; o[4 * dt + 2] *= f1; o[4 * dt + 3] *= f1;
            const uint32_t b0 = __ldg(vr + dt * 8) | ((uint32_t)__ldg(vr + dt * 8 + DH) << 16);
            const uint32_t b1 = __ldg(vr + dt * 8 + 8 * DH) | ((uint32_t)__ldg(vr + dt * 8 + 9 * DH) << 16);
            mma16816(o + 4 * dt, e0, e1, e2, e3, b0, b1);
        }
    }
    const float i0 = 1.f / quad_sum(l0), i1 = 1.f / quad_sum(l1);
#pragma unroll
    for (int i = 0; i < 16; i++) {
        q[2 * i] = pack_bf16(o[4 * i] * i0, o[4 * i + 1] * i0);
        q[2 * i + 1] = pack_bf16(o[4 * i + 2] * i1, o[4 * i + 3] * i1);
    }
    frag_store(t < 3 ? frag + t * 4096 : keep, q);
  }
}

__device__ __forceinline__ void spare_q3(Scratch* gs, uint32_t sb, uint32_t bar_full, uint32_t bar_empty, int lane, int cw) {
    const uint32_t tag = load_tag(gs);
    uint32_t rel_base, e = 3;
    asm("mapa.shared::cluster.u32 %0, %1, %2;" : "=r"(rel_base) : "r"(bar_empty), "r"(lane & 1));
#pragma unroll 1
    for (int qb = blockIdx.x - NCTA; qb < 16; qb += 4) {
        uint32_t h[144];
        float o[64];
        flag_wait(&g_flag_h[(qb * 8 + cw) * 32], tag);
        const uint4* hf = g_h + (size_t)(qb * 8 + cw) * (36 * 32) + lane;
#pragma unroll
        for (int ks = 0; ks < 36; ks++) {
            const uint4 v = h_frag(hf, ks, lane);
            h[4 * ks] = v.x; h[4 * ks + 1] = v.y; h[4 * ks + 2] = v.z; h[4 * ks + 3] = v.w;
        }
#pragma unroll
        for (int i = 0; i < 64; i++) o[i] = 0.f;
#pragma unroll 1
        for (int v = 0; v < 4; v++) {
            fence_regs(o);
#pragma unroll
            for (int t = 0; t < 5; t++) {
                mbar_wait(bar_full + 8 * (e & 3), (e >> 2) & 1);
                uint64_t dv = mkdesc(sb + (e & 3) * SLOT, UNIT, 1024);
                WG_FENCE();
#pragma unroll
                for (int ks = 0; ks < (t < 4 ? 8 : 4); ks++)
                    mma_rs128<1>(o, h[32 * t + 4 * ks], h[32 * t + 4 * ks + 1], h[32 * t + 4 * ks + 2], h[32 * t + 4 * ks + 3], dv, ks | t);
                WG_COMMIT();
                if (t > 0) { WG_WAIT(1); if (lane < 2) mbar_arrive_cluster(rel_base + 8 * ((e - 1) & 3)); }
                e++;
            }
            WG_WAIT(0);
            fence_regs(o);
            if (lane < 2) mbar_arrive_cluster(rel_base + 8 * ((e - 1) & 3));
            uint4* dst = &g_q3[((qb * 8 + 2 * v) * 8 + cw) * 128 + lane];
#pragma unroll
            for (int i = 0; i < 8; i++)
                __stcg(dst + (i >> 2) * 1024 + (i & 3) * 32, make_uint4(pack_bf16(o[8 * i], o[8 * i + 1]), pack_bf16(o[8 * i + 2], o[8 * i + 3]),
                                                                        pack_bf16(o[8 * i + 4], o[8 * i + 5]), pack_bf16(o[8 * i + 6], o[8 * i + 7])));
        }
        bar_sync(3, 256);
        if (cw == 0 && lane == 0) flag_release(&g_flag_q3[qb * 32], tag);
        __syncwarp();
    }
}

template <bool SPARE>
__global__ void __cluster_dims__(2, 1, 1) __launch_bounds__(384, 1)
fused_kernel(const Args args, const __grid_constant__ CUtensorMap tm_wq,
             const __grid_constant__ CUtensorMap tm_k, const __grid_constant__ CUtensorMap tm_v,
             const __grid_constant__ CUtensorMap tm_wo, const __grid_constant__ CUtensorMap tm_p,
             const __grid_constant__ CUtensorMap tm_x, const __grid_constant__ CUtensorMap tm_d,
             const __grid_constant__ CUtensorMap tm_g, const __grid_constant__ CUtensorMap tm_u) {
    extern __shared__ __align__(1024) uint8_t smem_raw[];
    const uint32_t sb = smem_u32(smem_raw);
    Scratch* const gs = args.gs;
    const uint32_t bar_full = sb + SM_BAR;
    const uint32_t bar_g = bar_full + 8 * 4;
    const uint32_t bar_mod = bar_g + 8;
    const uint32_t bar_go = bar_mod + 8;
    const uint32_t bar_x = bar_go + 40;
    const uint32_t bar_empty = bar_x + 8;
    const uint32_t bar_pub = bar_empty + 8 * 4;
    const uint32_t bar_qfree = bar_pub + 32;
    const uint32_t bar_out = bar_qfree + 24;
    const uint32_t bar_q3 = bar_out + 8;
    const uint32_t bar_stg = bar_q3 + 24;
    const uint32_t bar_pre = bar_q3 + 16;
    const uint32_t bar_w0 = bar_q3 + 8;
    constexpr int E0 = SPARE ? 2 : 0;

    const int c = blockIdx.x & 1;
#define ROLES() const int role = cluster_role(), j = role & 7, qb = (role >> 3) * 2 + c, rg = qb * 8 + j
    const int warp = __shfl_sync(0xffffffffu, threadIdx.x >> 5, 0);

    if (SPARE && blockIdx.x >= NCTA && warp >= 4) {
        asm volatile("barrier.cluster.arrive.relaxed.aligned;" ::: "memory");
        asm volatile("setmaxnreg.inc.sync.aligned.u32 240;");
        asm volatile("barrier.cluster.wait.aligned;" ::: "memory");
        spare_q3(gs, sb, bar_full, bar_empty, threadIdx.x & 31, warp - 4);
        asm volatile("barrier.cluster.arrive.relaxed.aligned;\nbarrier.cluster.wait.aligned;" ::: "memory");
    } else if (warp < 4) {
        asm volatile("setmaxnreg.dec.sync.aligned.u32 24;");
        ROLES();
        int lane;
        asm volatile("mov.u32 %0, %%laneid;" : "=r"(lane));
        if (warp == 2 && elect()) {
            asm volatile("prefetch.tensormap [%0];" ::"l"(&tm_x) : "memory");
#pragma unroll
            for (int i = 0; i < 28; i++) mbar_init(bar_full + 8 * i, i < 12 || (i >= 23 && i < 27) ? 1 : i < 16 ? 16 : 8);
#pragma unroll
            for (int i = 0; i <= E0; i++) {
                mbar_arrive(bar_full + 8 * i);
                asm volatile("mbarrier.arrive.shared::cta.b64 _, [%0], 16;" ::"r"(bar_empty + 8 * i) : "memory");
            }
            asm volatile("fence.mbarrier_init.release.cluster;" ::: "memory");
        }
        __syncwarp();
        asm volatile("barrier.cluster.arrive.relaxed.aligned;" ::: "memory");
        if (warp == 2 && !(SPARE && blockIdx.x >= NCTA)) {
            __nanosleep(200);
            if (elect()) {
                mbar_expect_tx(bar_x, 16 * XP);
                tma2d(sb + SM_Q, &tm_x, 0, rg * 16, bar_x);
            }
            __syncwarp();
        }
        asm volatile("barrier.cluster.wait.aligned;" ::: "memory");
        const uint32_t tag = load_tag(gs);
        if (SPARE && blockIdx.x >= NCTA) {
            if (warp == 1) {
#pragma unroll 1
                for (int e = 3; e < 83; e++) {
                    const int v = (e - 3) / 5;
                    mbar_wait_sleep(bar_empty + 8 * (e & 3), ~(e >> 2) & 1);
                    if (elect()) {
                        mbar_expect_tx(bar_full + 8 * (e & 3), SLOT);
                        tma2d_mc(sb + (e & 3) * SLOT + c * UNIT, &tm_wq, (8 * (v & 3) + 4 * c + 3) * DH + 64, (e - 3 - v * 5) * 128,
                                 bar_full + 8 * (e & 3), EVICT_NORMAL);
                    }
                }
            }
            __syncwarp();
            asm volatile("barrier.cluster.arrive.relaxed.aligned;\nbarrier.cluster.wait.aligned;" ::: "memory");
            return;
        }
        if (warp == 3) {
#pragma unroll 1
            for (int e = 4; e < 20; e++) {
                __nanosleep(e == 4 ? 2000 : 400);
                const int hd = (e * 52) >> 8, row = (e - hd * 5) * 128 + qb * 8 + (lane >> 1);
                if (lane < 16 && row < D_)
                    asm volatile("prefetch.global.L2 [%0];" ::"l"(padd(args.wq, (row * QD + (4 * j + ((0x1320 >> (4 * hd)) & 3)) * DH + (lane & 1) * 64) * 2)) : "memory");
            }
            __syncwarp();
            mbar_wait_sleep(bar_go, 0);
#pragma unroll 1
            for (int unit = 72 + blockIdx.x; unit < 216; unit += NCTA) {
                float a[8];
#pragma unroll
                for (int i = 0; i < 8; i++) a[i] = 0.f;
#pragma unroll 1
                for (int k = lane >> 1; k < D_; k += 16) {
                    const float cv = __bfloat162float(*padd(args.cvec, k * 2));
                    mod_fma(a, __ldg(reinterpret_cast<const uint4*>(padd(args.w_mod, (k * (6 * D_) + unit * 16 + (lane & 1) * 8) * 2))), rbf(cv * sigmoidf_(cv)));
                }
                const float v = mod_reduce(a, lane), v1 = __shfl_down_sync(0xffffffffu, v, 8);
                if (lane < 8) *padd(gs->mod2, ((unit - 72) * 8 + (lane & 1) * 4 + (lane & 2) + (lane >> 2)) * 4) = pack_bf16(v, v1);
            }
            __syncwarp();
            if (lane == 0) flag_release(padd(g_flag_mod, blockIdx.x * 4), tag);
#pragma unroll 1
            for (int k = 0; k < 36; k++) {
                __nanosleep(200);
                __stcg(padd(gs->h[0], (~tag & 1) * (NCTA * 36 * 512) + ((rg * 36 + k) * 32 + lane) * 16), make_uint4(0, 0, 0, 0));
            }
            __syncwarp();
            mbar_wait_sleep(bar_qfree + 16, 0);
            __nanosleep(2000);
            {
                uint4 v;
                uint32_t it = 0;
#pragma unroll 1
                do {
                    v = ld_relaxed(reinterpret_cast<const uint4*>(padd(g_flag_mod, lane * 16)));
                } while (((v.x ^ tag) | (v.y ^ tag) | (v.z ^ tag) | (v.w ^ tag)) && ++it < SPIN / 16);
                asm volatile("fence.acquire.gpu;" ::: "memory");
            }
            __syncwarp();
            {
                float w1 = 0.f, w2 = 0.f;
#pragma unroll 1
                for (int k = lane; k < D_ / 2; k += 32) {
                    const uint32_t* mp = padd(gs->mod2, k * 4);
                    const uint32_t sv = __ldcg(mp + D_ / 2), c1 = badd2(__ldcg(mp + D_), 0x3f803f80u);
                    const uint32_t wr = *reinterpret_cast<const uint32_t*>(padd(args.w_r, k * 4)), wp = bmul2(c1, wr);
                    reinterpret_cast<uint2*>(smem_raw + SM_T)[k] = make_uint2(__ldcg(mp), wp);
                    reinterpret_cast<uint2*>(smem_raw + SM_TC)[k] = make_uint2(c1, sv);
                    reinterpret_cast<uint32_t*>(smem_raw + SM_TG)[k] = __ldcg(mp + 3 * D_ / 2);
                    w1 += bf_lo(wp) + bf_hi(wp);
                    w2 += bf_lo(sv) * bf_lo(wr) + bf_hi(sv) * bf_hi(wr);
                }
#pragma unroll 1
                for (int i = 1; i < 32; i <<= 1) { w1 += __shfl_xor_sync(0xffffffffu, w1, i); w2 += __shfl_xor_sync(0xffffffffu, w2, i); }
                *reinterpret_cast<float2*>(smem_raw + SM_TS) = make_float2(w1, w2);
            }
#pragma unroll
            for (int i = 0; i < 4; i++) reinterpret_cast<uint4*>(smem_raw + SM_RED)[lane + 32 * i] = make_uint4(~0u, ~0u, ~0u, ~0u);
            asm volatile("fence.proxy.async.shared::cta;" ::: "memory");
            __syncwarp();
            if (elect()) {
                uint8_t* mb = g_frag + (size_t)rg * 8 * WREG + 3 * 4096;
#pragma unroll 1
                for (int k = 0; k < 8; k++, mb += WREG) {
#pragma unroll
                    for (int i = 0; i < 3; i++)
                        asm volatile("cp.async.bulk.global.shared::cta.bulk_group [%0], [%1], 2048;" ::"l"(mb + i * 2048), "r"(sb + SM_RED) : "memory");
                    __nanosleep(500);
                }
                asm volatile("cp.async.bulk.commit_group;\ncp.async.bulk.wait_group 0;\nfence.proxy.async.global;" ::: "memory");
            }
            __syncwarp();
            if (lane == 0) mbar_arrive(bar_mod);
            __syncwarp();
            mbar_wait_sleep(bar_go + 8, 0);
            if (elect()) asm volatile("prefetch.tensormap [%0];\nprefetch.tensormap [%1];\nprefetch.tensormap [%2];" ::"l"(&tm_x), "l"(&tm_p), "l"(&tm_d) : "memory");
            __syncwarp();
#pragma unroll 1
            for (int i = 1; i < 4; i++) {
                mbar_wait(bar_pub + 8 * i, 0);
                unsigned int* flags = padd(g_flag_part, (qb * 32 + i * 8 - 8) * 4);
                if (elect()) { flag_release(padd(flags, j * 4), tag); DBG_PG(93); }
                __syncwarp();
                const uint32_t slot = (i + 2) & 3;
                flag_wait(padd(flags, (lane & 7) * 4), tag);
                asm volatile("fence.proxy.async.global;" ::: "memory");
                if (lane == 0 && i == 3) DBG_PG(101);
                mbar_wait(bar_go + 8 + 8 * i, 0);
                mbar_wait(bar_empty + 8 * slot, i == 3);
                if (elect()) {
                    mbar_expect_tx(bar_full + 8 * slot, SLOT);
                    tma3d(sb + slot * SLOT, &tm_p, 0, j * 20 + (i - 1) * 4, qb * 8, bar_full + 8 * slot);
                    tma3d(sb + slot * SLOT + UNIT, &tm_p, 0, j * 20 + (i - 1) * 4 + 2, qb * 8, bar_full + 8 * slot);
                }
            }
        } else if (warp == 0) {
#pragma unroll 1
            for (int i = 0; i < 48; i++) {
                if (SPARE && i == 34) {
                    flag_wait(&g_flag_q3[qb * 32], tag);
                    if (elect()) {
                        asm volatile("fence.proxy.async.global;" ::: "memory");
                        mbar_expect_tx(bar_q3, UNIT);
#pragma unroll 1
                        for (int k = 0; k < 8; k++) bulk_load(sb + SM_Q + 2 * SLOT + k * 4096 + 2048, &g_q3[(rg * 8 + k) * 128], 2048, bar_q3);
                    }
                }
                if (i == 0 || i == 17 || i == 34) { mbar_wait_sleep(bar_qfree + (i >> 4) * 8, 0); __nanosleep(2000); }
                __nanosleep(500);
                if (elect()) {
                    asm volatile("mbarrier.expect_tx.shared::cta.b64 [%0], %1;" ::"r"(bar_g), "n"(1920) : "memory");
                    tma2d(sb + SM_Q + i * 1920, i < 24 ? &tm_g : &tm_u, (blockIdx.x * 36) & ~7, (i < 24 ? i : i - 24) * 24, bar_g);
                }
            }
            if (elect()) mbar_arrive(bar_g);
#pragma unroll 1
            for (int i = 0; i < 18; i++) {
                __nanosleep(400);
                if (elect()) l2_prefetch(args.w_down + (size_t)(blockIdx.x * 36 + i * 2) * D_, 4 * D_);
            }
            __syncwarp();
            mbar_wait_sleep(bar_go + 8 * 2, 0);
            uint32_t acc = 0;
#pragma unroll 1
            for (int k = lane; k < 16 * 9; k += 32) acc |= touch(padd(args.x, (rg * 16 * D_ + k * 64) * 2));
            if (acc == 0) reinterpret_cast<volatile uint32_t*>(smem_raw + SM_BAR)[127] = acc;
            __syncwarp();
            mbar_wait_sleep(bar_go + 8 * 4, 0);
            uint4* rp = padd(g_rows, (rg * 2 * RSLOT + lane) * 16);
#pragma unroll
            for (int k = 0; k < 12; k++) rp[k * 32] = make_uint4(~0u, ~0u, ~0u, ~0u);
            if (blockIdx.x < 72) {
                uint4* yp = reinterpret_cast<uint4*>(padd(g_ypart, blockIdx.x * NCTA * 64 + lane * 16));
#pragma unroll
                for (int k = 0; k < 16; k++) yp[k * 32] = make_uint4(~0u, ~0u, ~0u, ~0u);
            }
            asm volatile("fence.acq_rel.gpu;" ::: "memory");
            __syncwarp();
            if (lane == 0) mbar_arrive(bar_pre);
        } else if (warp == 1) {
            __nanosleep(300);
            uint32_t go = bar_go;
            uint64_t marks = 24 | 151 << 8 | 155 << 16 | 160ull << 24 | 165ull << 32;
#pragma unroll 1
            for (int e = E0; e < 168; e++) {
                const CUtensorMap* tm;
                int c0, c1;
                uint64_t pol = EVICT_FIRST;
                if (e == 159 || e == 164) continue;
                if (e < 21 && e != 19) {
                    const int i = SPARE && e < 12 ? e - 2 : e - (e == 20), hd = (i * 52) >> 8;
                    tm = &tm_wq; c0 = (4 * j + ((0x1320 >> (4 * hd)) & 3)) * DH + c * 64; c1 = (i - hd * 5) * 128 - 64;
                    if (SPARE && e >= 12 && e < 15) { c0 = (4 * j + 3) * DH; c1 = (2 * (e - 12) + c) * 128; }
                } else if (e < 148) {
                    const int i = max(e - 20, 0);
                    const bool isk = i == 0 || ((i & 1) && i < 127);
                    const int n = isk ? (i + 1) >> 1 : (i - 1) >> 1;
                    tm = isk ? &tm_k : &tm_v; c0 = c * 64; c1 = (2 * j + (n >> 5)) * S_ + (n & 15) * 128;
                    if (!(i & 32)) pol = EVICT_NORMAL;
                } else {
                    int i = e - 148 - (e > 159) - (e > 164);
                    tm = &tm_wo; c0 = (i >> 1) * 64; c1 = (4 * j + ((i & 1) ? 1 + c : 3 * c)) * DH;
                }
                const uint32_t fb = e == E0 ? bar_w0 : bar_full + 8 * (e & 3), d = sb + (e == E0 ? 6 : e & 3) * SLOT;
                if (e >= 24 && e < 152) mbar_wait_sleep(bar_empty + 8 * (e & 3), ~(e >> 2) & 1);
                else if (e != E0) mbar_wait(bar_empty + 8 * (e & 3), ~(e >> 2) & 1);
                if (elect()) {
                    mbar_expect_tx(fb, SLOT);
                    tma2d_mc(d + c * UNIT, tm, c0, c1, fb, pol);
                    const int i = e - PF_KV;
                    if (i >= 0 && i < 128 && !(i & 32))
                        l2_prefetch(((i & 1) ? args.vc : args.kc) + (size_t)((2 * j + (i >> 6)) * S_ + (i & 30) * 64) * DH + qb * 1024, 2048);
                    if (e >= PF_WO && e < PF_WO + 18) l2_prefetch(args.wo + (size_t)blockIdx.x * (QD * D_ / NCTA) + (e - PF_WO) * 1024, 2048);
                    if (e == (marks & 255)) mbar_arrive(go);
                }
                if (e == (marks & 255)) { go += 8; marks >>= 8; }
            }
            asm volatile("fence.proxy.async.global;" ::: "memory");
            mbar_wait(bar_empty, 1);
            if (elect()) {
                mbar_expect_tx(bar_full, 16 * XP);
                tma2d(sb, &tm_x, 0, rg * 16, bar_full);
            }
            mbar_wait(bar_empty + 16, 1);
            if (elect()) {
                mbar_expect_tx(bar_full + 16, SLOT);
                tma3d(sb + 2 * SLOT, &tm_p, 0, j * 20 + 12, qb * 8, bar_full + 16);
                tma3d(sb + 2 * SLOT + UNIT, &tm_p, 0, j * 20 + 14, qb * 8, bar_full + 16);
            }
            mbar_wait(bar_empty + 24, 1);
            __nanosleep(300);
            if (elect()) {
                mbar_expect_tx(bar_full + 24, UNIT);
                tma3d(sb + 3 * SLOT, &tm_p, 0, j * 20 + 16, qb * 8, bar_full + 24);
            }
            mbar_wait(bar_empty + 8, 0);
            mbar_wait(bar_empty + 16, 0);
            __nanosleep(300);
            if (elect()) {
#pragma unroll
                for (int i = 1; i < 3; i++) {
                    mbar_expect_tx(bar_full + 8 * i, 18 * XP);
                    tma2d(sb + i * SLOT, &tm_d, 0, blockIdx.x * 36 + (i - 1) * 18, bar_full + 8 * i);
                }
            }
        } else {
            if (elect()) asm volatile("prefetch.tensormap [%0];\nprefetch.tensormap [%1];\nprefetch.tensormap [%2];" ::"l"(&tm_k), "l"(&tm_v), "l"(&tm_wo) : "memory");
            if (SPARE) {
                mbar_wait_sleep(bar_pub, 0);
                if (lane == 0) flag_release(padd(g_flag_h, rg * 128), tag);
                __syncwarp();
            }
            bar_sync(1, 192);
#pragma unroll 1
            for (uint32_t e = E0 + 5; e < 20; e++) {
                mbar_wait(bar_full + 8 * (e & 3), (e >> 2) & 1);
                if (!(((SPARE ? 0xa080 : 0x8420) >> e) & 1)) bar_sync(1, 192);
            }
#pragma unroll 1
            for (uint32_t e = 20; e < 148; e++) {
                mbar_wait_sleep(bar_full + 8 * (e & 3), (e >> 2) & 1);
                if (SPARE && e == 113) mbar_wait(bar_q3, 0);
                if (e & 1) bar_sync(1, 192);
                if (!(e & 1) || e == 147) bar_sync(4, 160);
            }
#pragma unroll 1
            for (uint32_t e = 148; e < 168; e++) {
                mbar_wait(bar_full + 8 * (e & 3), (e >> 2) & 1);
                if (e != 159 && e != 164) bar_sync(1, 192);
            }
        }
        __syncwarp();
        uint32_t rows = 0x1111u << warp;
        auto store_rows = [&](uint32_t m) {
#pragma unroll 1
            for (; m; m &= m - 1) {
                const int i = __ffs(m) - 1;
                asm volatile("cp.async.bulk.global.shared::cta.bulk_group.L2::cache_hint [%0], [%1], %2, %3;"
                             ::"l"(padd(args.out, (rg * 16 + i) * (D_ * 2))), "r"(sb + i * XP), "n"(NOOUT ? 16 : D_ * 2), "l"(EVICT_FIRST) : "memory");
            }
        };
        if (OE) {
            mbar_wait_sleep(bar_stg, 0);
            if (OED) __nanosleep(OED);
            const uint32_t early = rows & ((1u << (4 * OE)) - 1) & ~lds32(sb + SM_RED + 72);
            rows &= ~early;
            if (elect()) {
                asm volatile("fence.proxy.async.shared::cta;" ::: "memory");
                store_rows(early);
            }
        }
        mbar_wait_sleep(bar_out, 0);
        if (blockIdx.x == 127 && warp == 0 && lane == 0) gs->epoch[0] = tag;
        if (elect()) {
            asm volatile("fence.proxy.async.shared::cta;" ::: "memory");
            const uint2 sel = lds64(sb + SM_RED + 64);
            if ((sel.x >> 4) == rg) rows &= ~(1u << (sel.x & 15));
            if ((sel.y >> 4) == rg) rows &= ~(1u << (sel.y & 15));
            store_rows(rows);
            asm volatile("cp.async.bulk.commit_group;\ncp.async.bulk.wait_group.read 0;" ::: "memory");
        }
    } else {
        uint32_t cv[2] = {0, 0}, tag = load_tag(gs) - 1;
        if (blockIdx.x < 72) {
            uint32_t ws;
            int tid;
            asm volatile("mov.u32 %0, smem_raw;\nmov.u32 %1, %%tid.x;" : "=r"(ws), "=r"(tid));
            tid -= 128;
            ws += SM_Q + SLOT + tid * 16;
            const uint32_t* cp = padd(reinterpret_cast<const uint32_t*>(args.cvec), (tid & 0xe0) + (tid & 7) * 4);
            cv[0] = *padd(cp, (tid & 24) * 32);
            if (tid < 128) cv[1] = cp[256];
            const bf16* wrow = args.w_mod + (size_t)(tid >> 1) * (6 * D_) + (tid & 1) * 8 + blockIdx.x * 16;
#pragma unroll
            for (int i = 0; i < 5; i++)
                if (i < 4 || tid < 128)
                    asm volatile("cp.async.cg.shared.global [%0], [%1], 16;" ::"r"(ws + i * 4096), "l"(wrow + (size_t)i * 128 * (6 * D_)) : "memory");
        }
        asm volatile("barrier.cluster.arrive.relaxed.aligned;" ::: "memory");
        asm volatile("setmaxnreg.inc.sync.aligned.u32 240;");
        const int lane = threadIdx.x & 31;
        const int cw = warp - 4;
        const int w = cw >> 2;
        const int tid = threadIdx.x - 128;
        ROLES();
        float* red = reinterpret_cast<float*>(smem_raw + SM_RED);
        DBG_INIT();
        DBG_G(120);
        DBG_T(100);

        {
            if (blockIdx.x < 72) {
                uint32_t sa[10];
#pragma unroll
                for (int i = 0; i < 2; i++) {
                    const float lo = bf_lo(cv[i]), hi = bf_hi(cv[i]);
                    cv[i] = pack_bf16(lo * sigmoidf_(lo), hi * sigmoidf_(hi));
                }
#pragma unroll
                for (int i = 0; i < 10; i++) sa[i] = __shfl_sync(0xffffffffu, cv[i >> 3], (i & 7) * 4 + (lane & 3));
                uint2* mdst = &gs->mod1[(tid >> 3) * D_ + blockIdx.x * 8 + (tid & 7)];
                anchor(bar_full + 504, sa[0] & sa[1] & sa[2] & sa[3] & sa[4] & sa[5] & sa[6] & sa[7] & sa[8] & sa[9] & (uint32_t)(uintptr_t)mdst & (uint32_t)((uintptr_t)mdst >> 32));
                asm volatile("cp.async.wait_all;" ::: "memory");
                __syncwarp();
                const uint32_t ws = sb + SM_Q + SLOT + cw * 512 + (lane & 15) * 32 + (lane & 16);
                float d[16];
#pragma unroll
                for (int i = 0; i < 16; i++) d[i] = 0.f;
#pragma unroll
                for (int i = 0; i < 5; i++) {
                    const uint4 b = ldsm4t(ws + (i < 4 || cw < 4 ? i * 4096 : 0));
                    mma16816(d + 8 * (i & 1), sa[2 * i], sa[2 * i], sa[2 * i + 1], sa[2 * i + 1], b.x, b.y);
                    mma16816(d + 8 * (i & 1) + 4, sa[2 * i], sa[2 * i], sa[2 * i + 1], sa[2 * i + 1], b.z, b.w);
                }
                if (lane < 8) reinterpret_cast<float2*>(red)[lane * 8 + cw] = (lane & 4) ? make_float2(d[4] + d[12], d[5] + d[13]) : make_float2(d[0] + d[8], d[1] + d[9]);
                bar_sync(3, 256);
                if (tid < 8 * MREP) {
                    const float4* r = reinterpret_cast<const float4*>(red) + (tid & 7) * 4;
                    const float4 r0 = r[0], r1 = r[1], r2 = r[2], r3 = r[3];
                    st_relaxed64(mdst, pack_bf16(((r0.x + r0.z) + (r1.x + r1.z)) + ((r2.x + r2.z) + (r3.x + r3.z)),
                                                 ((r0.y + r0.w) + (r1.y + r1.w)) + ((r2.y + r2.w) + (r3.y + r3.w))), tag + 1);
                }
            }
            DBG_G(106);
            asm volatile("barrier.cluster.wait.aligned;" ::: "memory");
            mbar_wait(bar_x, 0);
            asm volatile("add.u32 %0, %0, 1;" : "+r"(tag));
            uint32_t x[20];
            float st[12], st2[12];
            rows_load(x, sb + SM_Q + (lane & 15) * XP + (lane >> 4) * 16 + cw * 32, cw);
#pragma unroll
            for (int i = 0; i < 12; i++) { st[i] = 0.f; st2[i] = 0.f; }
#pragma unroll
            for (int k = 0; k < 9; k++) stats_add((k & 1) ? st2 : st, x[2 * k], x[2 * k + 1], 0x3f803f80u);
#pragma unroll
            for (int i = 0; i < 12; i++) st[i] += st2[i];
            uint32_t mean2;
            float dot;
            const float rsd = rows_stats(st, reinterpret_cast<float4*>(red + 128), cw, lane, mean2, dot);
            const uint4* mp = reinterpret_cast<const uint4*>(gs->mod1 + ((blockIdx.x >> 1) & (MREP - 1)) * D_) + min(tid, D_ / 4 - 1);
            uint4 v0 = make_uint4(0, tag, 0, tag), v1 = v0;
            auto look = [&]() {
                asm volatile("{\n.reg .pred p;\n.reg .b64 a, b, c, d;\nsetp.lt.s32 p, %9, 5;\nmov.b64 a, {%0, %1};\nmov.b64 b, {%2, %3};\n"
                             "mov.b64 c, {%4, %5};\nmov.b64 d, {%6, %7};\n@p ld.relaxed.gpu.global.v2.b64 {a, b}, [%8];\n"
                             "@p ld.relaxed.gpu.global.v2.b64 {c, d}, [%8 + 2304];\n"
                             "mov.b64 {%0, %1}, a;\nmov.b64 {%2, %3}, b;\nmov.b64 {%4, %5}, c;\nmov.b64 {%6, %7}, d;\n}"
                             : "+r"(v0.x), "+r"(v0.y), "+r"(v0.z), "+r"(v0.w), "+r"(v1.x), "+r"(v1.y), "+r"(v1.z), "+r"(v1.w)
                             : "l"(mp), "r"(cw) : "memory");
            };
            rows_normalise(x, x, mean2, rsd, lane, look);
            fence_regs(x);
            uint32_t it = 0;
#pragma unroll 1
            while (((v0.y ^ tag) | (v0.w ^ tag) | (v1.y ^ tag) | (v1.w ^ tag)) && ++it < SPIN / 16) look();
            uint4* smod = reinterpret_cast<uint4*>(smem_raw + SM_Q + M_MOD);
            if (tid < D_ / 4) smod[tid] = make_uint4(badd2(v1.x, 0x3f803f80u), v0.x, badd2(v1.z, 0x3f803f80u), v0.z);
            uint4* hdst = g_h + (size_t)(rg * 36 + cw) * 32 + lane;
            uint2* hdst2 = reinterpret_cast<uint2*>(g_h + (size_t)(rg * 36 + 32) * 32) + tid;
            bar_sync(3, 256);
            DBG_G(107);
#pragma unroll
            for (int k = 0; k < 9; k++) {
                const uint2 cs = lds64(sb + SM_Q + M_MOD + (cw * 8 + (lane & 3) + (k < 8 ? (k >> 1) * 64 + (k & 1) * 4 : 256 - cw * 4)) * 8);
                const uint32_t c1 = cs.x, sa = cs.y;
                x[2 * k] = badd2(bmul2(x[2 * k], c1), sa);
                if (x[2 * k] == 0) x[2 * k] = 0x8000u;
                x[2 * k + 1] = badd2(bmul2(x[2 * k + 1], c1), sa);
            }
#pragma unroll
            for (int ch = 0; ch < 4; ch++) st_relaxed4(hdst + ch * 256, x[4 * ch], x[4 * ch + 1], x[4 * ch + 2], x[4 * ch + 3]);
            st_relaxed64(hdst2, x[16], x[17]);
            __syncwarp();
            if (SPARE && lane == 0) mbar_arrive(bar_pub);
            DBG_G(108);
        }

        uint32_t rel_base;
        asm("mapa.shared::cluster.u32 %0, %1, %2;" : "=r"(rel_base) : "r"(bar_empty), "r"(lane & 1));
        auto release = [&](uint32_t slot) { if (lane < 2) mbar_arrive_cluster(rel_base + 8 * slot); };
        uint32_t q[32], p[32];
        float s[64], o[64];

        const int lw = cw & 3;
        const uint32_t relw = lw == 2 && lane < 8, handw = lw == 2 || cw == 1;
        auto release4 = [&](uint32_t off, uint32_t on = 1) {
            asm volatile("{\n.reg .pred p;\nsetp.ne.b32 p, %1, 0;\n@p mbarrier.arrive.shared::cluster.b64 _, [%0];\n}" ::"r"(rel_base + off), "r"(relw & on) : "memory"); };
        auto handoff = [&](uint32_t on = 1) {
            asm volatile("{\n.reg .pred p;\nsetp.ne.b32 p, %1, 0;\n@p bar.arrive %0, 192;\n}" ::"r"(2 - w), "r"(handw & on) : "memory"); };
        if (cw == 6) bar_arrive(1, 192);

        uint4* qpark = reinterpret_cast<uint4*>(smem_raw + SM_Q - SLOT) + cw * 256 + lane;
        {
            uint32_t h[144];
            const uint4* hf = g_h + (size_t)(qb * 8 + cw) * (36 * 32) + lane;
            auto load_h = [&](auto lo, auto hi) {
#pragma unroll
                for (int ks = lo.value; ks < hi.value; ks++) {
                    const uint4 v = h_frag(hf, ks, lane);
                    h[4 * ks] = v.x; h[4 * ks + 1] = v.y; h[4 * ks + 2] = v.z; h[4 * ks + 3] = v.w;
                }
            };
            auto check_h = [&](auto lo, auto hi) {
                uint32_t it = 0;
                bool miss;
#pragma unroll 1
                do {
                    uint32_t mn = ~0u;
#pragma unroll
                    for (int ks = lo.value; ks < hi.value; ks++) mn = __vimin3_u32(mn, h[4 * ks], h[4 * ks + 2]);
                    miss = __any_sync(0xffffffffu, mn == 0);
                    if (miss) load_h(lo, hi);
                    asm volatile("add.u32 %0, %0, 1;" : "+r"(it));
                } while (miss && it < SPIN / 16);
            };
            auto check_h2 = [&](auto lo, auto hi, auto nx) {
                float f0 = __uint_as_float(~0u), f1 = f0;
                hold(f0, f1);
                auto low = [&]() {
                    uint32_t m0 = __float_as_uint(f0), m1 = m0;
#pragma unroll
                    for (int ks = lo.value; ks < hi.value; ks += 2) { m0 = __vimin3_u32(m0, h[4 * ks], h[4 * ks + 2]); m1 = __vimin3_u32(m1, h[4 * ks + 4], h[4 * ks + 6]); }
                    return min(m0, m1);
                };
                anchor(const_cast<uint4*>(hf), h[4 * hi.value - 1] & __float_as_uint(f0));
                load_h(hi, nx);
                if (__any_sync(0xffffffffu, low() == 0)) {
                    uint32_t it = 0;
#pragma unroll 1
                    do load_h(lo, hi); while (__any_sync(0xffffffffu, low() == 0) && ++it < SPIN / 16);
                }
            };
            __nanosleep(300);
            load_h(IC<0>{}, IC<4>{});
            DBG_T(104); DBG_G(109);
            mbar_wait(bar_w0, 0);
#pragma unroll
            for (int e = E0 + 1; e < E0 + 3; e++) mbar_wait(bar_full + 8 * (e & 3), e >> 2);
#pragma unroll
            for (int i = 0; i < 64; i++) o[i] = 0.f;
            auto group = [&](auto tc, auto ec) {
                constexpr int t = tc.value, e = ec.value, k0 = t ? 8 * t - 4 : 0;
                constexpr bool first = e < E0 + 5, turns = e >= E0 + 4;
                uint64_t dv = (first ? args.d0 : desc_lo(0, UNIT) | (0x40000040ull << 32)) + ((t ? 0 : 512) + (e == E0 ? 6 : e & 3) * (SLOT / 16));
                if (first && t == 0) check_h(IC<0>{}, IC<4>{});
                if (first && t >= 3) mbar_wait(bar_full + 8 * (e & 3), e >> 2);
                if (first && t > 0) check_h2(IC<k0>{}, IC<8 * t + 4>{}, IC<t < 4 ? 8 * t + 12 : 0>{});
                if (t != 1 && turns) bar_sync(1 + w, 192);
                if (t != 1 || first) WG_FENCE();
#pragma unroll
                for (int ks = k0; ks < 8 * t + 4; ks++) {
                    mma_rs128<1>(o, h[4 * ks], h[4 * ks + 1], h[4 * ks + 2], h[4 * ks + 3], dv, ks);
                    if (t && turns && ks == k0 + QSPLIT - 1) WG_COMMIT();
                }
                if (t || first) WG_COMMIT();
                if (first && t == 0) load_h(IC<4>{}, IC<12>{});
                if (t > 0) {
                    WG_WAIT(1);
                    if (turns) handoff();
                    if ((t == 1 && !first) || (t > 1 && e <= E0 + 4)) release4(8 * ((e - 1) & 3));
                    if (turns && e != 18) { WG_WAIT(0); release4(8 * (e & 3)); }
                }
            };
            auto head = [&](auto ec, int slot) {
                constexpr int e = ec.value;
                fence_regs(o);
                group(IC<0>{}, IC<e>{}); group(IC<1>{}, IC<e + 1>{}); group(IC<2>{}, IC<e + 2>{}); group(IC<3>{}, IC<e + 3>{});
                if (e == 15) return;
                group(IC<4>{}, IC<e + 4>{});
                fence_regs(o);
#pragma unroll
                for (int i = 0; i < 8; i++)
                    qpark[slot * 2048 + i * 32] = make_uint4(pack_bf16(o[8 * i], o[8 * i + 1]), pack_bf16(o[8 * i + 2], o[8 * i + 3]),
                                                             pack_bf16(o[8 * i + 4], o[8 * i + 5]), pack_bf16(o[8 * i + 6], o[8 * i + 7]));
            };
            head(IC<E0>{}, 1);
            head(IC<E0 + 5>{}, 2);
            if (SPARE) {
                float (&u)[32] = reinterpret_cast<float (&)[32]>(o);
                fence_regs(u);
#pragma unroll
                for (int t = 0; t < 2; t++) {
                    uint64_t dv = args.d0 + t * (SLOT / 16);
                    bar_sync(1 + w, 192);
                    WG_FENCE();
#pragma unroll
                    for (int ks = 0; ks < 16 + 4 * t; ks++) {
                        mma_rs64<1>(u, h[64 * t + 4 * ks], h[64 * t + 4 * ks + 1], h[64 * t + 4 * ks + 2], h[64 * t + 4 * ks + 3], dv, ks | t);
                        if (ks == 2 * QSPLIT + 4 * t - 1) WG_COMMIT();
                    }
                    WG_COMMIT();
                    WG_WAIT(1);
                    handoff();
                    WG_WAIT(0);
                    release4(8 * t);
                }
                fence_regs(u);
                release4(16);
#pragma unroll
                for (int i = 0; i < 4; i++)
                    qpark[3 * 2048 + i * 32] = make_uint4(pack_bf16(u[8 * i], u[8 * i + 1]), pack_bf16(u[8 * i + 2], u[8 * i + 3]),
                                                          pack_bf16(u[8 * i + 4], u[8 * i + 5]), pack_bf16(u[8 * i + 6], u[8 * i + 7]));
            } else {
                head(IC<10>{}, 3);
            }
            head(IC<15>{}, 0);
#pragma unroll
            for (int i = 0; i < 8; i++) {
                const uint4 v = lds128(smem_u32(qpark + 2048 + i * 32));
                q[4 * i] = v.x; q[4 * i + 1] = v.y; q[4 * i + 2] = v.z; q[4 * i + 3] = v.w;
            }
#pragma unroll
            for (int i = 0; i < 32; i++) p[i] = h[112 + i];
            WG_WAIT(0);
            fence_regs(o);
            release4(16);
        }
        DBG_T(105);
        DBG_G(125);

        uint8_t* frag = reinterpret_cast<uint8_t*>(__shfl_sync(0xffffffffu, reinterpret_cast<unsigned long long>(g_frag + (size_t)(rg * 8 + cw) * WREG + lane * 16), lane));
        const uint4* qnext = reinterpret_cast<const uint4*>(__shfl_sync(0xffffffffu, reinterpret_cast<unsigned long long>(padd(smem_raw, SM_Q + tid * 16 + cw * 3584)), lane));
        uint8_t* odst = reinterpret_cast<uint8_t*>(const_cast<uint4*>(qnext));
        qnext -= 2048;
        float m0, m1, l0 = 0.25f, l1 = 0.25f, t0, t1;
        uint32_t bad = 0;
        auto finish = [&](auto lo, auto hi, uint32_t bit, auto sink) {
#pragma unroll
            for (int i = lo.value; i < hi.value; i++) {
                const uint32_t v0 = pack_bf16(o[8 * i] * t0, o[8 * i + 1] * t0), v1 = pack_bf16(o[8 * i + 2] * t1, o[8 * i + 3] * t1);
                const uint32_t v2 = pack_bf16(o[8 * i + 4] * t0, o[8 * i + 5] * t0), v3 = pack_bf16(o[8 * i + 6] * t1, o[8 * i + 7] * t1);
                if (i == 0 && fabsf(o[0] * t0) >= 0x1p-31f) bad |= bit << 8;
                sink(i, v0, v1, v2, v3);
            }
        };
        float lq[6];
        auto row_parts = [&]() {
#pragma unroll
            for (int i = 0; i < 3; i++) { lq[i] = __shfl_xor_sync(0xffffffffu, l0, i + 1); lq[3 + i] = __shfl_xor_sync(0xffffffffu, l1, i + 1); }
        };
        auto row_sums = [&](uint32_t bit) {
            t0 = (l0 + lq[0]) + (lq[1] + lq[2]); t1 = (l1 + lq[3]) + (lq[4] + lq[5]);
            if (!(t0 >= LMIN && t0 < LMAX && t1 >= LMIN && t1 < LMAX)) bad |= bit;
        };
        auto issue_pv = [&](uint64_t dv, int acc) {
            asm volatile("{\n.reg .pred p;\nsetp.eq.b32 p, %0, 0;\n@p bar.sync 4, 160;\n}" ::"r"(w) : "memory");
#pragma unroll
            for (int ks = 0; ks < 8; ks++)
                mma_rs128<1>(o, p[4 * ks], p[4 * ks + 1], p[4 * ks + 2], p[4 * ks + 3], dv, ks ? 1 : acc);
            WG_COMMIT();
        };
#pragma unroll
        for (int i = 0; i < 64; i++) s[i] = 0.f;
        uint64_t dv_lo = args.d0;
        uint32_t voff = 0;
        auto issue_qk = [&]() {
            uint64_t dk = dv_lo ^ (desc_lo(0, UNIT) ^ desc_lo(3 * SLOT, 16));
            bar_sync(1 + w, 192);
            fence_regs(s); fence_regs(q); fence_regs(o); fence_regs(p);
            WG_FENCE();
#pragma unroll
            for (int ks = 0; ks < 8; ks++)
                if (ks == 3) mma_rs128<0, 1018>(s, q[4 * ks], q[4 * ks + 1], q[4 * ks + 2], q[4 * ks + 3], dk, 1);
                else mma_rs128<0, 2>(s, q[4 * ks], q[4 * ks + 1], q[4 * ks + 2], q[4 * ks + 3], dk, ks != 0);
            WG_COMMIT();
        };
        auto to_frag = [&](int i, uint32_t v0, uint32_t v1, uint32_t v2, uint32_t v3) {
            *reinterpret_cast<uint4*>(odst + i * 512) = make_uint4(v0, v1, v2, v3); };
        int n = 0;
        auto scores_ready = [&]() {
            WG_WAIT(1);
            fence_regs(s); fence_regs(q);
        };
        auto pass_on = [&]() {
            release4(voff ^ 24);
            handoff();
        };
#pragma unroll 1
        for (;;) {
            {
                {
                    asm volatile("st.shared.v2.f32 [%0], {%1, %2};" ::"r"(sb + SM_RED + tid * 8), "f"(l0), "f"(l1) : "memory");
                    __syncwarp();
                    const uint4 a = lds128(sb + SM_RED + (tid & ~3) * 8), b = lds128(sb + SM_RED + (tid & ~3) * 8 + 16);
                    l0 = __uint_as_float(a.x); lq[0] = __uint_as_float(a.z); lq[1] = __uint_as_float(b.x); lq[2] = __uint_as_float(b.z);
                    l1 = __uint_as_float(a.y); lq[3] = __uint_as_float(a.w); lq[4] = __uint_as_float(b.y); lq[5] = __uint_as_float(b.w);
                }
                issue_qk();
                hold(l0, l1);
                row_sums(1u << (n >> 4));
                t0 = rcp_fast(t0); t1 = rcp_fast(t1);
                l0 = 0.f; l1 = 0.f;
                odst = n ? frag + ((n >> 4) - 1) * 4096 : odst;
                qnext = n == 48 ? reinterpret_cast<const uint4*>(frag) : qnext + 2048;
                anchor(bar_full + 504, (t0 + t1) * __uint_as_float((bad ^ (uint32_t)(uintptr_t)odst ^ (uint32_t)(uintptr_t)qnext) & 0x3fffffff));
                asm volatile("{\n.reg .pred p;\nsetp.ne.b32 p, %1, 0;\n@p mbarrier.arrive.shared::cta.b64 _, [%0];\n}"
                             ::"r"(bar_qfree + (n >> 1) - 8), "r"(lane ? 0 : n) : "memory");
                issue_pv(dv_lo, 1);
                scores_ready();
                const uint32_t a = pack_bf16(fmaxf(fmaxf(s[0], s[1]), fmaxf(s[4], s[5])), fmaxf(fmaxf(s[2], s[3]), fmaxf(s[6], s[7])));
                const uint32_t b = bmax2(bmax2(a, __shfl_xor_sync(0xffffffffu, a, 1)), bmax2(__shfl_xor_sync(0xffffffffu, a, 2), __shfl_xor_sync(0xffffffffu, a, 3)));
                pass_on();
                m0 = fmaf(-CS, bf_lo(b), -POFF); m1 = fmaf(-CS, bf_hi(b), -POFF);
            }
#pragma unroll 1
            for (;;) {
                DBG_T(n);
#pragma unroll
                for (int i = 0; i < 4 * STAGE; i++) s[i] = fmaf(s[i], CS, (i & 2) ? m1 : m0);
#pragma unroll
                for (int i = 0; i < 4 * SPLIT; i++) s[i] = ex2(s[i]);
#pragma unroll
                for (int i = 0; i < SPLIT; i++) { l0 += s[4 * i] + s[4 * i + 1]; l1 += s[4 * i + 2] + s[4 * i + 3]; }
                m0 = fmaf(l0, 0.f, m0); m1 = fmaf(l1, 0.f, m1);
                anchor(bar_full + 504, l0 + l1);
                WG_WAIT(0);
                fence_regs(o); fence_regs(p);
                release4(voff);
                dv_lo ^= 2 * SLOT / 16;
                voff ^= 16;
                n++;
#pragma unroll
                for (int i = 4 * STAGE; i < 64; i++) s[i] = fmaf(s[i], CS, (i & 2) ? m1 : m0);
#pragma unroll
                for (int i = 4 * SPLIT; i < 64; i++) s[i] = ex2(s[i]);
#pragma unroll
                for (int i = SPLIT; i < 16; i++) { l0 += s[4 * i] + s[4 * i + 1]; l1 += s[4 * i + 2] + s[4 * i + 3]; }
#pragma unroll
                for (int i = 0; i < 32; i++) p[i] = pack_bf16(s[2 * i], s[2 * i + 1]);
                const int jn = n & 15;
                if (jn > 1) {
                    issue_qk();
                    if ((n & 10) == 2) {
                        if (n & 1) {
#pragma unroll
                            for (int i = 0; i < 64; i++) o[i] *= (i & 2) ? t1 : t0;
                        } else {
                            row_parts();
                            row_sums(2u << (n >> 4));
                            const uint32_t e0 = __float_as_uint(t0) >> 23, e1 = __float_as_uint(t1) >> 23;
                            m0 -= __uint_as_float(0x4b000000u | e0) - (8388608.f + 127.f - POFF);
                            m1 -= __uint_as_float(0x4b000000u | e1) - (8388608.f + 127.f - POFF);
                            t0 = __uint_as_float((254 - (int)POFF - e0) << 23); t1 = __uint_as_float((254 - (int)POFF - e1) << 23);
                            l0 *= t0; l1 *= t1;
                        }
                    }
                    fence_regs(o);
                    WG_FENCE();
                    issue_pv(dv_lo, 1);
                    scores_ready();
                    pass_on();
                    if (jn != 15) continue;
#pragma unroll
                    for (int i = 0; i < 8; i++) {
                        const uint4 v = qnext[i * 32];
                        q[4 * i] = v.x; q[4 * i + 1] = v.y; q[4 * i + 2] = v.z; q[4 * i + 3] = v.w;
                    }
                    continue;
                }
                if (jn == 0) break;
                finish(IC<0>{}, IC<ESPLIT>{}, 1u << (n >> 4), to_frag);
                issue_qk();
                hold(t0, t1);
                finish(IC<ESPLIT>{}, IC<8>{}, 1u << (n >> 4), to_frag);
                WG_FENCE();
                issue_pv(dv_lo, 0);
                scores_ready();
                pass_on();
            }
            if (n == 64) break;
        }
        DBG_T(64);
        uint32_t a1[32], a2[32];
        bar_sync(1 + w, 192);
        fence_regs(o); fence_regs(p);
        WG_FENCE();
        issue_pv(args.d0 + 3 * SLOT / 16, 1);
        handoff();
        mbar_wait(bar_mod, 0);
        const int tid_ = __shfl_sync(0xffffffffu, tid, lane);
        row_parts();
        row_sums(16);
        t0 = rcp_fast(t0); t1 = rcp_fast(t1);
        anchor(frag, q[0] & q[4] & q[8] & q[12] & q[16] & q[20] & q[24] & q[28] & __float_as_uint(t0) & __float_as_uint(t1) & tid_);
        frag_load(a1, frag + 4096);
        frag_load<0, 4>(a2, frag + 8192);
        anchor(frag, bad);
        WG_WAIT(0);
        fence_regs(o); fence_regs(p);
        release4(24);
        finish(IC<0>{}, IC<8>{}, 16, [&](int i, uint32_t v0, uint32_t v1, uint32_t v2, uint32_t v3) {
            p[4 * i] = v0; p[4 * i + 1] = v1; p[4 * i + 2] = v2; p[4 * i + 3] = v3; });
        anchor(frag, p[31] & p[15]);
        frag_load<4, 8>(a2, frag + 8192);
        bad = __reduce_or_sync(0xffffffffu, bad);
        bad = ((bad | ~(bad >> 8)) >> 1) & 15;
        if (__builtin_expect(bad != 0, 0)) {
            uint8_t* keep = g_keep + (size_t)(rg * 8 + cw) * 4096 + lane * 16;
            frag_store(keep, p);
            attn_fallback(bad, tag, gs, frag, keep, args.wq, args.kc, args.vc);
            frag_load(q, frag); frag_load(a1, frag + 4096); frag_load(a2, frag + 8192); frag_load(p, keep);
            anchor(frag, q[0] & q[4] & q[8] & q[12] & q[16] & q[20] & q[24] & q[28] & p[0] & p[4] & p[8] & p[12] & p[16] & p[20] & p[24] & p[28]);
        }
        DBG_T(80);
        DBG_G(124);

        const uint32_t eye = (tid_ >> 3 & 3) == (tid_ & 3) ? 0x3f80u << ((tid_ & 4) * 4) : 0;
        auto sum8 = [&](uint32_t* r, const uint4 (&v)[8]) {
            float d[16];
#pragma unroll
            for (int i = 0; i < 16; i++) d[i] = 0.f;
#pragma unroll
            for (int src = 0; src < 8; src++) {
                mma1688(d + 8 * (src & 1), v[src].x, v[src].y, eye);
                mma1688(d + 8 * (src & 1) + 4, v[src].z, v[src].w, eye);
            }
#pragma unroll
            for (int i = 0; i < 4; i++) r[i] = pack_bf16(d[2 * i] + d[8 + 2 * i], d[2 * i + 1] + d[9 + 2 * i]);
        };
        uint4 v2[8], v3[8], wf[23];
        uint2 u4[8], gw[9];
        uint32_t x1[20], xs, pa, ta;
        const uint8_t *mb, *mb4;
        auto load_wf = [&](auto lo, auto hi) {
            const uint32_t wa = sb + SM_Q + ((tid_ & 8) * (D_ / 8) + cw * 16 + (tid_ & 7) + (tid_ & 16) / 2) * 80;
            const uint32_t wb = wa + (512 - cw * 8) * 80 - (tid_ & 16) * 39;
#pragma unroll
            for (int i = lo.value; i < hi.value; i++) wf[i] = ldsm4t(i < 20 ? wa + (i / 5) * 10240 + (i % 5) * 16 : wb + (i - 20) * 32);
        };
        uint32_t at[18];
        {
            float (&u)[32] = reinterpret_cast<float (&)[32]>(o);
            uint32_t off = 0;
            auto turn = [&](const uint32_t (&a)[32], const uint32_t (&b)[32], int acc) {
                uint64_t dv = args.d0 + off * (SLOT / 128);
                bar_sync(1 + w, 192);
                fence_regs(u);
                WG_FENCE();
#pragma unroll
                for (int ks = 0; ks < 16; ks++) {
                    const uint32_t* f = ks < 8 ? &a[4 * ks] : &b[4 * ks - 32];
                    mma_rs64<1>(u, f[0], f[1], f[2], f[3], dv, ks | acc);
                    if (ks == OSPLIT - 1) WG_COMMIT();
                }
                WG_COMMIT();
                WG_WAIT(1);
            };
            auto done = [&]() {
                WG_WAIT(0);
                fence_regs(u);
                release4(off);
                off = (off + 8) & 24;
            };
            auto store = [&](uint8_t* dst) {
#pragma unroll
                for (int i = 0; i < 4; i++)
                    st_relaxed4(dst + i * 512, pack_bf16(u[8 * i], u[8 * i + 1]), pack_bf16(u[8 * i + 2], u[8 * i + 3]),
                                pack_bf16(u[8 * i + 4], u[8 * i + 5]), pack_bf16(u[8 * i + 6], u[8 * i + 7]));
            };
            pa = sb + w * (UNIT - 2048) + tid_ * 16;
#pragma unroll
            for (int i = 0; i < 8; i++) at[i] = 0;
            fence_regs(q); fence_regs(p);
            uint8_t* dst = frag;
#pragma unroll
            for (int i = 0; i < 8; i++) asm volatile("" : "=r"(v2[i].x), "=r"(v2[i].y), "=r"(v2[i].z), "=r"(v2[i].w));
#pragma unroll 1
            for (int k = 0; k < 8; k++, dst += 2048) {
                const uint32_t poff = (off + 8) & 24;
                const bool sum = (0xa0 >> k) & 1;
                turn(q, p, 0);
                handoff();
                auto sum_p = [&](auto lo, auto hi) {
#pragma unroll
                    for (int i = lo.value; i < hi.value; i++) {
                        float a[8], b[8];
#pragma unroll
                        for (int src = 0; src < 8; src++) {
                            const uint32_t x = i == 0 ? v2[src].x : i == 1 ? v2[src].y : i == 2 ? v2[src].z : v2[src].w;
                            a[src] = bf_lo(x); b[src] = bf_hi(x);
                        }
                        at[i] = at[4 + i];
                        at[4 + i] = pack_bf16(((a[0] + a[2]) + (a[4] + a[6])) + ((a[1] + a[3]) + (a[5] + a[7])),
                                              ((b[0] + b[2]) + (b[4] + b[6])) + ((b[1] + b[3]) + (b[5] + b[7])));
                    }
                };
                if (sum) {
                    mbar_wait(bar_full + poff, 1);
#pragma unroll
                    for (int src = 0; src < 8; src++) v2[src] = lds128(pa + poff * (SLOT / 8) + src * 2048);
                    __syncwarp();
                    release(poff >> 3);
                    done();
                    off = (off + 8) & 24;
                    sum_p(IC<0>{}, IC<2>{});
                } else {
                    done();
                }
                turn(a1, a2, 1);
                handoff();
                if (sum) sum_p(IC<2>{}, IC<4>{});
                done();
                store(dst);
                __syncwarp();
                asm volatile("{\n.reg .pred p;\nsetp.ne.b32 p, %1, 0;\n@p mbarrier.arrive.shared::cta.b64 _, [%0];\n}"
                             ::"r"(bar_pub + 4 + 4 * k), "r"(lane ? 0 : (0x2a >> k) & 1) : "memory");
            }
            turn(q, p, 0);
            handoff();
            mb = padd(g_frag, (qb * 64 + j) * WREG + 3 * 4096 + tid_ * 16);
            mb4 = padd(mb, 4096 + ((cw >> 1) - cw) * 512 + (cw & 1) * 8);
            xs = sb + (tid_ & 15) * XP + (tid_ & 16) + cw * 32;
            ta = sb + (cw * 8 + (tid_ & 3)) * 8;
#pragma unroll
            for (int k = 0; k < 9; k++) {
                gw[k] = lds64(ta + SM_T + (k < 8 ? (k >> 1) * 64 + (k & 1) * 4 : 256 - cw * 4) * 8);
                if (!(tid_ & 4)) gw[k].y = 0x3f803f80u;
            }
            mbar_wait(bar_g, 0);
            if (T_X) mbar_wait(bar_full, 0);
            done();
            if (T_X) rows_load(x1, xs, cw);
            load_wf(IC<0>{}, IC<WF0>{});
            turn(a1, a2, 1);
            if (w == 0) handoff();
            done();
            store(dst);
            if (!T_X) { mbar_wait(bar_full, 0); rows_load(x1, xs, cw); }
            if (w == 0) bar_sync(5, 256); else bar_arrive(5, 256);
        }
        DBG_T(81);
        DBG_G(122);

        {
        const int tid = tid_, lane = tid & 31;
        const int g8 = lane >> 2, qd = lane & 3, l16 = lane & 15;
        uint32_t h2[18], gb[9], k1, k2;
        float4* rec = reinterpret_cast<float4*>(red + 128);
        const uint2* candp = reinterpret_cast<const uint2*>(padd(g_cand, ((blockIdx.x & (CREP - 1)) * NCTA + (tid >> 1)) * 32 + (tid & 1) * 8));
        uint2 cd;
        auto stage_out = [&]() {
#pragma unroll
            for (int k = 0; k < 9; k++) {
                x1[2 * k] = badd2(x1[2 * k], bmul2(gb[k], h2[2 * k]));
                x1[2 * k + 1] = badd2(x1[2 * k + 1], bmul2(gb[k], h2[2 * k + 1]));
            }
#pragma unroll
            for (int ch = 0; ch < 4; ch++) stsm_x4(xs + ch * 256, x1[4 * ch], x1[4 * ch + 1], x1[4 * ch + 2], x1[4 * ch + 3]);
            asm volatile("stmatrix.sync.aligned.m8n8.x2.shared.b16 [%0], {%1, %2};" ::"r"(xs + 1024 - cw * 16), "r"(x1[16]), "r"(x1[17]) : "memory");
        };
        {
            uint32_t it = 0, miss;
            mbar_wait(bar_full + 8, 0);
            if (T_B) mbar_wait(bar_full + 16, 0);
#pragma unroll
            for (int src = 0; src < 8; src++) v2[src] = lds128(pa + SLOT + src * 2048);
#pragma unroll
            for (int src = 0; src < 8 * T_B; src++) v3[src] = lds128(pa + 2 * SLOT + src * 2048);
            sum8(at + 8, v2);
            float st[12];
#pragma unroll
            for (int i = 0; i < 12; i++) st[i] = 0.f;
            auto add_pair = [&](int k) {
                x1[2 * k] = badd2(x1[2 * k], bmul2(gw[k].x, at[2 * k]));
                x1[2 * k + 1] = badd2(x1[2 * k + 1], bmul2(gw[k].x, at[2 * k + 1]));
                stats_add(st, x1[2 * k], x1[2 * k + 1], gw[k].y);
            };
#pragma unroll
            for (int k = 0; k < 6; k++) add_pair(k);
            if (!T_B) mbar_wait(bar_full + 16, 0);
#pragma unroll
            for (int src = 0; src < 8 * !T_B; src++) v3[src] = lds128(pa + 2 * SLOT + src * 2048);
            miss = __vimax3_u32(__vimax3_u32(v3[0].x, v3[0].z, v3[1].x), __vimax3_u32(v3[1].z, v3[2].x, v3[2].z), __vimax3_u32(v3[3].x, v3[3].z, v3[4].x));
            miss = __vimax3_u32(miss, __vimax3_u32(v3[4].z, v3[5].x, v3[5].z), max(__vimax3_u32(v3[6].x, v3[6].z, v3[7].x), v3[7].z));
            if (!T_C || __any_sync(0xffffffffu, miss == ~0u))
#pragma unroll 1
            do {
                miss = 0;
#pragma unroll
                for (int src = 0; src < 8; src++) reload16(v3[src], mb + (size_t)src * 8 * WREG, miss);
            } while (__any_sync(0xffffffffu, miss) && ++it < SPIN / 16);
            if (lane < 4) mbar_arrive_cluster(rel_base + 8 * (1 + (lane >> 1)));
            sum8(at + 12, v3);
            add_pair(6); add_pair(7);
            load_wf(IC<WF0>{}, IC<WF1>{});
            uint2 cs[9];
#pragma unroll
            for (int k = 0; k < 9; k++) cs[k] = lds64(ta + SM_TC + (k < 8 ? (k >> 1) * 64 + (k & 1) * 4 : 256 - cw * 4) * 8);
            mbar_wait(bar_pre, 0);
            mbar_wait(bar_full + 24, 0);
#pragma unroll
            for (int src = 0; src < 8; src++) u4[src] = lds64(sb + 3 * SLOT + src * 2048 + (cw >> 1) * 512 + lane * 16 + (cw & 1) * 8);
            miss = __vimax3_u32(__vimax3_u32(u4[0].x, u4[1].x, u4[2].x), __vimax3_u32(u4[3].x, u4[4].x, u4[5].x), max(u4[6].x, u4[7].x));
            if (!T_C || __any_sync(0xffffffffu, miss == ~0u))
#pragma unroll 1
            do {
                miss = 0;
#pragma unroll
                for (int src = 0; src < 8; src++) reload8(u4[src], mb4 + (size_t)src * 8 * WREG, miss);
            } while (__any_sync(0xffffffffu, miss) && ++it < SPIN / 16);
            float d[8] = {0.f, 0.f, 0.f, 0.f, 0.f, 0.f, 0.f, 0.f};
#pragma unroll
            for (int i = 0; i < 4; i++) mma16816(d + 4 * (i & 1), u4[2 * i].x, u4[2 * i].y, u4[2 * i + 1].x, u4[2 * i + 1].y, eye, eye);
            at[16] = pack_bf16(d[0] + d[4], d[1] + d[5]); at[17] = pack_bf16(d[2] + d[6], d[3] + d[7]);
            add_pair(8);
            DBG_G(123);
            const float2 ws = *reinterpret_cast<const float2*>(smem_raw + SM_TS);
            uint4* cdst = padd(g_cand, (tid * NCTA + rg) * 32);
            uint32_t mean2;
            float dot;
            const float rsd = rows_stats(st, rec, cw, lane, mean2, dot);
            const uint32_t b = __float_as_uint(fmaf(fmaf(-bf_lo(mean2), ws.x, dot), rsd, ws.y));
            const uint32_t key = (((b & 0x80000000u) ? ~b : (b | 0x80000000u)) | 2047u) - (rg * 16 + l16);
            top2(key, k1, k2);
            if (tid < CREP) st_relaxed(cdst, k1, tag, k2, tag);
            cd = ld_relaxed64(candp);
            rows_normalise(h2, x1, mean2, rsd, lane, [&]() {
#pragma unroll
                for (int k = 0; k < 9; k++) gb[k] = lds32(sb + SM_TG + (cw * 8 + qd + (k < 8 ? (k >> 1) * 64 + (k & 1) * 4 : 256 - cw * 4)) * 4);
                load_wf(IC<WF1>{}, IC<WF2>{});
            });
#pragma unroll
            for (int k = 0; k < 18; k++) h2[k] = badd2(bmul2(h2[k], cs[k >> 1].x), cs[k >> 1].y);
            const uint32_t r1 = ~k1 & 15, r2 = ~k2 & 15;
            uint32_t todo = ((r1 & 7) == g8) | ((r2 & 7) == g8) << 1;
#pragma unroll 1
            while (todo) {
                const bool second = !(todo & 1), hi = (second ? r2 : r1) & 8;
                uint4* dst = padd(g_rows, ((rg * 2 + second) * RSLOT + cw * 24 + qd) * 16);
                uint32_t r[18];
#pragma unroll
                for (int k = 0; k < 9; k++) { r[k] = hi ? h2[2 * k + 1] : h2[2 * k]; r[9 + k] = hi ? x1[2 * k + 1] : x1[2 * k]; }
                fence_regs(r);
                st_relaxed(dst, r[0], r[1], r[2], r[3]);
                st_relaxed(dst + 8, r[4], r[5], r[6], r[7]);
                st_relaxed64(reinterpret_cast<uint2*>(padd(dst, 256 - qd * 8)), r[8], r[17]);
                st_relaxed(dst + 4, r[9], r[10], r[11], r[12]);
                st_relaxed(dst + 12, r[13], r[14], r[15], r[16]);
                todo &= todo - 1;
            }
            __syncwarp();

            stage_out();
            if (OE) {
                __syncwarp();
                if (lane == 0) { reinterpret_cast<uint32_t*>(red)[18] = (1u << r1) | (1u << r2); mbar_arrive(bar_stg); }
            }
        }
        DBG_G(110);
        float4* part = reinterpret_cast<float4*>(smem_raw + 3 * SLOT + UNIT + 8192);
        bf16* act = reinterpret_cast<bf16*>(smem_raw + 3 * SLOT + UNIT + 4096);
        {
            uint32_t it = 0;
            const bool own = (tid >> 1) == rg;
            const uint32_t ks = sb + 3 * SLOT + UNIT + 5120;
#pragma unroll 1
            while (T_U ? __any_sync(0xffffffffu, cd.y != tag && !own) && ++it < SPIN / 16 : cd.y != tag && !own && ++it < SPIN / 16) {
                if (T_U) asm volatile("{\n.reg .pred p;\n.reg .b64 u;\nsetp.ne.u32 p, %1, %3;\nmov.b64 u, {%0, %1};\n"
                             "@p ld.relaxed.gpu.global.b64 u, [%2];\nmov.b64 {%0, %1}, u;\n}" : "+r"(cd.x), "+r"(cd.y) : "l"(candp), "r"(tag) : "memory");
                else cd = ld_relaxed64(candp);
            }
            asm volatile("st.shared.u32 [%0], %1;" ::"r"(ks + tid * 4), "r"(own ? (tid & 1) ? k2 : k1 : cd.x) : "memory");
            bar_sync(3, 256);
            DBG_G(111);
            const uint4 a = lds128(ks + lane * 16), b = lds128(ks + 512 + lane * 16);
            const uint32_t a1 = max(a.x, a.z), a2 = __vimax3_u32(min(a.x, a.z), a.y, a.w);
            const uint32_t b1 = max(b.x, b.z), b2 = __vimax3_u32(min(b.x, b.z), b.y, b.w);
            const uint32_t c1 = max(a1, b1), c2 = __vimax3_u32(min(a1, b1), a2, b2);
            k1 = __reduce_max_sync(0xffffffffu, c1);
            k2 = __reduce_max_sync(0xffffffffu, c1 == k1 ? c2 : c1);
        }
        const int sel0 = ~k1 & 2047, sel1 = ~k2 & 2047;
        const uint32_t slot0 = (sel0 >> 4) * 2, slot1 = (sel1 >> 4) * 2 + ((sel0 ^ sel1) < 16);
        uint4 da[13];
        {
            const uint4* hp = padd(g_rows, (((g8 & 1) ? slot1 : slot0) * RSLOT + cw * 24 + qd) * 16);
            const uint2* hp2 = reinterpret_cast<const uint2*>(padd(hp, 256 - qd * 8));
            uint4 hv[2] = {ld_relaxed2(hp), ld_relaxed2(hp + 8)};
            uint2 hw = ld_relaxed64(hp2);
            if (tid == 255) {
                reinterpret_cast<int2*>(red)[8] = make_int2(sel0, sel1);
                mbar_arrive(bar_out);
            }
            load_wf(IC<WF2>{}, IC<23>{});
            mbar_wait(bar_full + 8, 1);
            mbar_wait(bar_full + 16, 1);
            auto load_d = [&](auto lo, auto hi) {
                const int r = (lane & 7) + (lane & 16) / 2;
                const uint32_t d0 = sb + SLOT + r * XP + cw * 144 + (lane & 8) * 2, d1 = d0 + (r < 2 ? 16 * XP : SLOT - 2 * XP);
                const uint32_t d2 = sb + 2 * SLOT + (14 + (lane & 3)) * XP + cw * 144 + (lane >> 3) * 16;
#pragma unroll
                for (int i = lo.value; i < hi.value; i++) da[i] = ldsm4t(i < 10 ? ((i & 1) ? d1 : d0) + (i >> 1) * 32 : d2 + (i - 10) * 64);
            };
            load_d(IC<0>{}, IC<DL>{});
            uint32_t it = 0, miss;
            float f0 = 1.f, f1 = 1.f;
            hold(f0, f1);
            if (!T_C || __any_sync(0xffffffffu, max(__vimax3_u32(__vimax3_u32(__float_as_uint(f0), hv[0].x, hv[0].z), hv[1].x, hv[1].z), hw.x) == ~0u))
#pragma unroll 1
            do {
                miss = 0;
                reload16(hv[0], hp, miss);
                reload16(hv[1], hp + 8, miss);
                reload8(hw, hp2, miss);
            } while (__any_sync(0xffffffffu, miss) && ++it < SPIN / 16);
            DBG_G(112);
            if (!T_D) load_d(IC<DL>{}, IC<13>{});
            float acc[20];
#pragma unroll
            for (int i = 0; i < 20; i++) acc[i] = 0.f;
#pragma unroll
            for (int i = 0; i < 5; i++) mma1688(acc + 4 * i, (i & 1) ? wf[20 + i / 2].z : wf[20 + i / 2].x, (i & 1) ? wf[20 + i / 2].w : wf[20 + i / 2].y, hw.x);
#pragma unroll
            for (int i = 0; i < 20; i++)
                mma16816(acc + 4 * (i % 5), wf[i].x, wf[i].y, wf[i].z, wf[i].w, (i / 5 & 1) ? hv[i / 10].z : hv[i / 10].x, (i / 5 & 1) ? hv[i / 10].w : hv[i / 10].y);
            if (qd == 0) {
#pragma unroll
                for (int i = 0; i < 5; i++) part[cw * 40 + i * 8 + g8] = make_float4(acc[4 * i], acc[4 * i + 1], acc[4 * i + 2], acc[4 * i + 3]);
            }
            if (T_D) load_d(IC<DL>{}, IC<13>{});
        }
        {
            uint2* dst = padd(g_ypart, ((cw * 9 * NCTA + blockIdx.x) * 8 + g8) * 8);
            bar_sync(3, 256);
            if (cw < 5) {
                const float* pp = reinterpret_cast<const float*>(part) + ((blockIdx.x & 1) << 4) + tid;
                const float g = rbf(((pp[0] + pp[160]) + (pp[320] + pp[480])) + ((pp[640] + pp[800]) + (pp[960] + pp[1120])));
                const float v = rbf(g * sigmoidf_(g)) * __shfl_down_sync(0xffffffffu, g, 2);
                if (!(tid & 2)) act[(tid & 1) * 56 + (tid >> 2)] = __float2bfloat16_rn(tid < 144 ? v : 0.f);
            }
            bar_sync(3, 256);
            DBG_G(113);
            const uint32_t ap = sb + 3 * SLOT + UNIT + 4096 + (lane & 1) * 112 + (lane >> 3) * 16;
            const uint4 b0 = ldsm4(ap);
            const uint32_t b1 = lds32(sb + 3 * SLOT + UNIT + 4096 + (g8 & 1) * 112 + 64 + qd * 4);
            float y[20];
#pragma unroll
            for (int i = 0; i < 20; i++) y[i] = 0.f;
#pragma unroll
            for (int i = 0; i < 5; i++) {
                mma16816(y + 4 * i, da[2 * i].x, da[2 * i].y, da[2 * i].z, da[2 * i].w, b0.x, b0.y);
                mma16816(y + 4 * i, da[2 * i + 1].x, da[2 * i + 1].y, da[2 * i + 1].z, da[2 * i + 1].w, b0.z, b0.w);
                mma1688(y + 4 * i, (i & 1) ? da[10 + i / 2].z : da[10 + i / 2].x, (i & 1) ? da[10 + i / 2].w : da[10 + i / 2].y, b1);
            }
            if (qd == 0) {
#pragma unroll
                for (int i = 0; i < 9; i++)
                    asm volatile("st.relaxed.gpu.global.v2.f32 [%0], {%1, %2};" ::"l"(dst + i * (NCTA * 8)), "f"(y[2 * i]), "f"(y[2 * i + 1]) : "memory");
            }
        }
        DBG_G(114);
        if (blockIdx.x < 72) {
            const int G = blockIdx.x, tok = g8 & 1, cp = G * 4 + qd;
            const uint2* src = padd(g_ypart, (blockIdx.x * NCTA * 8 + tid) * 8);
            if (RD) __nanosleep(RD);
            const uint8_t* hsrc = reinterpret_cast<const uint8_t*>(padd(g_rows, (tok ? slot1 : slot0) * (RSLOT * 16) +
                (G < 64 ? (G >> 1 & 7) * 384 + (G >> 5) * 128 + qd * 16 + (G >> 1 & 8) + (G & 1) * 4 : (G - 64) * 384 + 256 + qd * 8)));
            const uint8_t* xsrc = hsrc + (G < 64 ? 64 : 4);
            uint32_t* dst = padd(reinterpret_cast<uint32_t*>(args.out), (tok ? sel1 : sel0) * (D_ * 2) + cp * 4);
            const uint32_t gb = reinterpret_cast<const uint32_t*>(smem_raw + SM_TG)[cp];
            const uint32_t ksel = ((tok ? k2 : k1) & ~2047u) | 1024u;
            const float sg = sigmoidf_(rbf(__uint_as_float((ksel & 0x80000000u) ? (ksel & 0x7fffffffu) : ~ksel)));
            uint2 v[4];
            uint32_t hv = 0, xv = 0, it = 0, miss;
            if (cw == 0) { hv = ld_relaxed32(hsrc); xv = ld_relaxed32(xsrc); }
#pragma unroll
            for (int i = 0; i < 4; i++) v[i] = make_uint2(~0u, 0);
#pragma unroll 1
            do {
#pragma unroll
                for (int i = 0; i < 4; i++) reload8(v[i], src + i * 256, miss);
                if (RP > 1) __nanosleep(RP);
            } while (__any_sync(0xffffffffu, max(__vimax3_u32(v[0].x, v[1].x, v[2].x), v[3].x) == ~0u) && ++it < SPIN / 16);
#pragma unroll 1
            while (max(hv, xv) == ~0u && ++it < SPIN / 16) { hv = ld_relaxed32(hsrc); xv = ld_relaxed32(xsrc); }
            __syncwarp();
            float y0 = (__uint_as_float(v[0].x) + __uint_as_float(v[1].x)) + (__uint_as_float(v[2].x) + __uint_as_float(v[3].x));
            float y1 = (__uint_as_float(v[0].y) + __uint_as_float(v[1].y)) + (__uint_as_float(v[2].y) + __uint_as_float(v[3].y));
            y0 += __shfl_xor_sync(0xffffffffu, y0, 8); y1 += __shfl_xor_sync(0xffffffffu, y1, 8);
            y0 += __shfl_xor_sync(0xffffffffu, y0, 16); y1 += __shfl_xor_sync(0xffffffffu, y1, 16);
            if (lane < 8) reinterpret_cast<float2*>(rec)[cw * 8 + lane] = make_float2(y0, y1);
            bar_sync(3, 256);
            if (cw == 0) {
                const float4 t0_ = rec[(lane >> 3) * 4 + qd], t1_ = rec[16 + (lane >> 3) * 4 + qd];
                y0 = tok ? t0_.y + t1_.y : t0_.x + t1_.x; y1 = tok ? t0_.w + t1_.w : t0_.z + t1_.z;
                y0 += __shfl_xor_sync(0xffffffffu, y0, 8); y1 += __shfl_xor_sync(0xffffffffu, y1, 8);
                y0 += __shfl_xor_sync(0xffffffffu, y0, 16); y1 += __shfl_xor_sync(0xffffffffu, y1, 16);
                const uint32_t y2 = bmul2(pack_bf16(y0, y1), pack_bf16(sg, sg));
                if (lane < 8) *dst = badd2(xv, bmul2(gb, badd2(hv, y2)));
            }
        }
        }
        DBG_T(88);
        DBG_G(121);
    }
}

typedef CUresult (*EncodeFn)(CUtensorMap*, CUtensorMapDataType, cuuint32_t, void*, const cuuint64_t*, const cuuint64_t*,
                             const cuuint32_t*, const cuuint32_t*, CUtensorMapInterleave, CUtensorMapSwizzle,
                             CUtensorMapL2promotion, CUtensorMapFloatOOBfill);

static void make_map(EncodeFn enc, CUtensorMap* m, const void* ptr, int rank, const cuuint64_t* dims,
                     const cuuint64_t* strides, const cuuint32_t* box, CUtensorMapSwizzle sw = CU_TENSOR_MAP_SWIZZLE_128B,
                     CUtensorMapDataType dt = CU_TENSOR_MAP_DATA_TYPE_BFLOAT16) {
    const cuuint32_t es[3] = {1, 1, 1};
    enc(m, dt, rank, const_cast<void*>(ptr), dims, strides, box, es,
        CU_TENSOR_MAP_INTERLEAVE_NONE, sw, CU_TENSOR_MAP_L2_PROMOTION_L2_128B,
        CU_TENSOR_MAP_FLOAT_OOB_FILL_NONE);
}

extern "C" void kernel_launch(void* const* d_in, const int* in_sizes, int n_in, void* d_out, int out_size) {
    const bf16* x = (const bf16*)d_in[0];
    const bf16* kc = (const bf16*)d_in[1];
    const bf16* vc = (const bf16*)d_in[2];
    const bf16* wq = (const bf16*)d_in[3];
    const bf16* wo = (const bf16*)d_in[4];
    const bf16* w_r = (const bf16*)d_in[6];
    const bf16* w_gate = (const bf16*)d_in[7];
    const bf16* w_up = (const bf16*)d_in[8];
    const bf16* w_down = (const bf16*)d_in[9];
    const bf16* cvec = (const bf16*)d_in[10];
    const bf16* w_mod = (const bf16*)d_in[11];
    bf16* out = (bf16*)d_out;

    void* fn = nullptr;
    cudaDriverEntryPointQueryResult qr;
    cudaGetDriverEntryPoint("cuTensorMapEncodeTiled", &fn, cudaEnableDefault, &qr);
    EncodeFn enc = (EncodeFn)fn;
    void* p_s;
    cudaGetSymbolAddress(&p_s, g_s);

    CUtensorMap tm_wq, tm_k, tm_v, tm_wo, tm_p, tm_x, tm_d, tm_g, tm_u;
    { cuuint64_t d[2] = {QD, D_}, s[1] = {QD * 2}; cuuint32_t b[2] = {64, 128}; make_map(enc, &tm_wq, wq, 2, d, s, b); }
    { cuuint64_t d[2] = {DH, HKV * S_}, s[1] = {DH * 2}; cuuint32_t b[2] = {64, 128};
      make_map(enc, &tm_k, kc, 2, d, s, b); make_map(enc, &tm_v, vc, 2, d, s, b); }
    { cuuint64_t d[2] = {D_, QD}, s[1] = {D_ * 2}; cuuint32_t b[2] = {64, 128}; make_map(enc, &tm_wo, wo, 2, d, s, b); }
    { cuuint64_t d[3] = {256, 160, NCTA}, s[2] = {1024, 8 * WREG}; cuuint32_t b[3] = {256, 2, 8};
      make_map(enc, &tm_p, ((Scratch*)p_s)->frag, 3, d, s, b, CU_TENSOR_MAP_SWIZZLE_NONE, CU_TENSOR_MAP_DATA_TYPE_UINT32); }
    { cuuint64_t d[2] = {D_ / 4, S_}, s[1] = {D_ * 2}; cuuint32_t b[2] = {XP / 8, 16};
      make_map(enc, &tm_x, x, 2, d, s, b, CU_TENSOR_MAP_SWIZZLE_NONE, CU_TENSOR_MAP_DATA_TYPE_UINT64); }
    { cuuint64_t d[2] = {D_ / 4, F_}, s[1] = {D_ * 2}; cuuint32_t b[2] = {XP / 8, 18};
      make_map(enc, &tm_d, w_down, 2, d, s, b, CU_TENSOR_MAP_SWIZZLE_NONE, CU_TENSOR_MAP_DATA_TYPE_UINT64); }
    { cuuint64_t d[2] = {F_, D_}, s[1] = {F_ * 2}; cuuint32_t b[2] = {40, 24};
      make_map(enc, &tm_g, w_gate, 2, d, s, b, CU_TENSOR_MAP_SWIZZLE_NONE); make_map(enc, &tm_u, w_up, 2, d, s, b, CU_TENSOR_MAP_SWIZZLE_NONE); }

    cudaFuncSetAttribute(fused_kernel<true>, cudaFuncAttributeMaxDynamicSharedMemorySize, SM_TOTAL);
    cudaFuncSetAttribute(fused_kernel<false>, cudaFuncAttributeMaxDynamicSharedMemorySize, SM_TOTAL);
    cudaLaunchConfig_t cfg = {};
    cfg.gridDim = NCTA + 4; cfg.blockDim = 384; cfg.dynamicSmemBytes = SM_TOTAL;
    cudaLaunchAttribute at;
    at.id = cudaLaunchAttributeClusterDimension; at.val.clusterDim.x = 2; at.val.clusterDim.y = 1; at.val.clusterDim.z = 1;
    cfg.attrs = &at; cfg.numAttrs = 1;
    int ncl = 0;
    if (cudaOccupancyMaxActiveClusters(&ncl, fused_kernel<true>, &cfg) != cudaSuccess) { ncl = 0; cudaGetLastError(); }
    Args args{w_mod, cvec, (Scratch*)p_s, desc_lo(0, UNIT) | (0x40000040ull << 32), out, x, kc, vc, wq, wo, w_r, w_down};
    if (USE_SPARE && ncl >= NCTA / 2 + 2)
        fused_kernel<true><<<NCTA + 4, 384, SM_TOTAL>>>(args, tm_wq, tm_k, tm_v, tm_wo, tm_p, tm_x, tm_d, tm_g, tm_u);
    else
        fused_kernel<false><<<NCTA, 384, SM_TOTAL>>>(args, tm_wq, tm_k, tm_v, tm_wo, tm_p, tm_x, tm_d, tm_g, tm_u);
}
```

```cpp
#include <cuda_runtime.h>
#include <cuda_bf16.h>
#include <cuda.h>
#include <stdint.h>
#include <math.h>

typedef __nv_bfloat16 bf16;

constexpr int S_ = 2048;
constexpr int D_ = 576;
constexpr int HQ = 32, HKV = 16, DH = 128;
constexpr int F_ = 4608;
constexpr int QD = HQ * DH;

constexpr int NCTA = 128;
constexpr int WREG = 5 * 4096;
constexpr int CREP = 8;
constexpr int RSLOT = 192;
constexpr int MREP = 4;
struct Scratch {
    unsigned int epoch[128];
    unsigned int flag_mod[NCTA];
    unsigned int flag_part[16 * 32];
    unsigned int flag_q3[16 * 32];
    unsigned int flag_h[NCTA * 32];
    uint2 mod1[MREP * D_];
    uint32_t mod2[4 * D_];
    uint4 cand[CREP * NCTA * 2];
    uint2 ypart[72 * NCTA * 8];
    uint4 h[2][NCTA * 36 * 32];
    uint4 q3[NCTA * 8 * 128];
    uint4 rows[NCTA * 2 * RSLOT];
    uint8_t frag[NCTA * 8 * WREG];
    uint8_t keep[NCTA * 8 * 4096];
};
__device__ __align__(1024) Scratch g_s;
#define g_h gs->h[tag & 1]
#define g_q3 gs->q3
#define g_keep gs->keep
#define g_flag_h gs->flag_h
#define g_flag_part gs->flag_part
#define g_flag_mod gs->flag_mod
#define g_flag_q3 gs->flag_q3
#define g_frag gs->frag
#define g_cand gs->cand
#define g_ypart gs->ypart
#define g_rows gs->rows

#define DBG_INIT()
#define DBG_P(i)
#define DBG_PG(i)
#define DBG_T(i)
#define DBG_G(i)

__device__ __forceinline__ uint32_t pack_bf16(float lo, float hi) {
    uint32_t r;
    asm("cvt.rn.bf16x2.f32 %0, %1, %2;" : "=r"(r) : "f"(hi), "f"(lo));
    return r;
}
__device__ __forceinline__ float rbf(float x) { return __uint_as_float(pack_bf16(0.f, x)); }
__device__ __forceinline__ float bf_lo(uint32_t v) { return __uint_as_float(v << 16); }
__device__ __forceinline__ float bf_hi(uint32_t v) { return __uint_as_float(v & 0xffff0000u); }
__device__ __forceinline__ float ex2(float x) {
    float y;
    asm("ex2.approx.ftz.f32 %0, %1;" : "=f"(y) : "f"(x));
    return y;
}
template <class T>
__device__ __forceinline__ T* padd(T* p, uint32_t off) {
    unsigned long long r;
    asm("{\n.reg .b32 l, h;\nmov.b64 {l, h}, %1;\nadd.cc.u32 l, l, %2;\naddc.u32 h, h, 0;\nmov.b64 %0, {l, h};\n}" : "=l"(r) : "l"(p), "r"(off));
    return reinterpret_cast<T*>(r);
}
__device__ __forceinline__ uint32_t smem_u32(const void* p) { return (uint32_t)__cvta_generic_to_shared(p); }
__device__ __forceinline__ void mbar_init(uint32_t bar, uint32_t cnt) {
    asm volatile("mbarrier.init.shared::cta.b64 [%0], %1;" ::"r"(bar), "r"(cnt) : "memory");
}
__device__ __forceinline__ void mbar_expect_tx(uint32_t bar, uint32_t bytes) {
    asm volatile("mbarrier.arrive.expect_tx.shared::cta.b64 _, [%0], %1;" ::"r"(bar), "r"(bytes) : "memory");
}
__device__ __forceinline__ void mbar_arrive(uint32_t bar) {
    asm volatile("mbarrier.arrive.shared::cta.b64 _, [%0];" ::"r"(bar) : "memory");
}
__device__ __forceinline__ void mbar_arrive_cluster(uint32_t cluster_addr) {
    asm volatile("mbarrier.arrive.shared::cluster.b64 _, [%0];" ::"r"(cluster_addr) : "memory");
}
constexpr uint32_t SPIN = 1u << 20;
__device__ __forceinline__ void mbar_wait(uint32_t bar, uint32_t parity) {
    asm volatile("{\n.reg .pred p;\n.reg .b32 c;\nmov.b32 c, 0;\n"
                 "W_%=:\nmbarrier.try_wait.parity.shared::cta.b64 p, [%0], %1;\n"
                 "add.u32 c, c, 1;\nsetp.lt.and.u32 p, c, 0x100000, !p;\n@p bra W_%=;\n}"
                 ::"r"(bar), "r"(parity) : "memory");
}
__device__ __forceinline__ void anchor(uint32_t addr, float v) {
    asm volatile("{\n.reg .pred p;\nsetp.lt.f32 p, %1, 0f00000000;\n@p st.volatile.shared.f32 [%0], %1;\n}" ::"r"(addr), "f"(v) : "memory");
}
__device__ __forceinline__ void anchor(uint32_t addr, uint32_t v) {
    asm volatile("{\n.reg .pred p;\nsetp.eq.u32 p, %1, 0xffffffff;\n@p st.volatile.shared.u32 [%0], %1;\n}" ::"r"(addr), "r"(v) : "memory");
}
__device__ __forceinline__ void anchor(void* p, uint32_t v) {
    asm volatile("{\n.reg .pred p;\nsetp.eq.u32 p, %1, 0xffffffff;\n@p st.volatile.u32 [%0], %1;\n}" ::"l"(p), "r"(v) : "memory");
}
__device__ __forceinline__ void hold(float& a, float& b) {
    asm volatile("{\n.reg .pred p;\n.reg .b64 t;\n.reg .b32 l, h;\nmov.u64 t, %%clock64;\nmov.b64 {l, h}, t;\nsetp.eq.u32 p, h, 0xffffffff;\n"
                 "@p mov.f32 %0, 0f00000000;\n@p mov.f32 %1, 0f00000000;\n}" : "+f"(a), "+f"(b) :: "memory");
}
__device__ __forceinline__ void mbar_wait_sleep(uint32_t bar, uint32_t parity) {
    asm volatile("{\n.reg .pred p;\n.reg .b32 c;\nmov.b32 c, 0;\n"
                 "W_%=:\nmbarrier.try_wait.parity.shared::cta.b64 p, [%0], %1, 5000;\n"
                 "add.u32 c, c, 1;\nsetp.lt.and.u32 p, c, 0x20000, !p;\n@p bra W_%=;\n}"
                 ::"r"(bar), "r"(parity) : "memory");
}
__device__ __forceinline__ uint32_t load_tag(const Scratch* gs) {
    uint32_t tag;
    asm volatile("ld.global.ca.u32 %0, [%1];" : "=r"(tag) : "l"(gs->epoch) : "memory");
    return tag + 1;
}
__device__ __forceinline__ uint4 ld_relaxed(const uint4* p) {
    uint4 v;
    asm volatile("ld.relaxed.gpu.global.v4.u32 {%0,%1,%2,%3}, [%4];" : "=r"(v.x), "=r"(v.y), "=r"(v.z), "=r"(v.w) : "l"(p) : "memory");
    return v;
}
__device__ __forceinline__ void st_relaxed(uint4* p, uint32_t a, uint32_t b, uint32_t c, uint32_t d) {
    asm volatile("{\n.reg .b64 u, v;\nmov.b64 u, {%1, %2};\nmov.b64 v, {%3, %4};\nst.relaxed.gpu.global.v2.b64 [%0], {u, v};\n}"
                 ::"l"(p), "r"(a), "r"(b), "r"(c), "r"(d) : "memory");
}
__device__ __forceinline__ void st_relaxed4(void* p, uint32_t a, uint32_t b, uint32_t c, uint32_t d) {
    asm volatile("st.relaxed.gpu.global.v4.u32 [%0], {%1, %2, %3, %4};" ::"l"(p), "r"(a), "r"(b), "r"(c), "r"(d) : "memory");
}
__device__ __forceinline__ uint2 ld_relaxed64(const uint2* p) {
    uint2 v;
    asm volatile("{\n.reg .b64 u;\nld.relaxed.gpu.global.b64 u, [%2];\nmov.b64 {%0, %1}, u;\n}" : "=r"(v.x), "=r"(v.y) : "l"(p) : "memory");
    return v;
}
__device__ __forceinline__ void st_relaxed64(uint2* p, uint32_t a, uint32_t b) {
    asm volatile("{\n.reg .b64 u;\nmov.b64 u, {%1, %2};\nst.relaxed.gpu.global.b64 [%0], u;\n}" ::"l"(p), "r"(a), "r"(b) : "memory");
}
__device__ __forceinline__ uint4 ld_relaxed2(const uint4* p) {
    uint4 v;
    asm volatile("{\n.reg .b64 u, w;\nld.relaxed.gpu.global.v2.b64 {u, w}, [%4];\nmov.b64 {%0, %1}, u;\nmov.b64 {%2, %3}, w;\n}"
                 : "=r"(v.x), "=r"(v.y), "=r"(v.z), "=r"(v.w) : "l"(p) : "memory");
    return v;
}
__device__ __forceinline__ void reload16(uint4& v, const void* p, uint32_t& miss) {
    asm volatile("{\n.reg .pred p;\n.reg .b32 m;\n.reg .b64 u, w;\nmax.u32 m, %0, %2;\nsetp.eq.u32 p, m, 0xffffffff;\n"
                 "mov.b64 u, {%0, %1};\nmov.b64 w, {%2, %3};\n@p ld.relaxed.gpu.global.v2.b64 {u, w}, [%5];\n"
                 "mov.b64 {%0, %1}, u;\nmov.b64 {%2, %3}, w;\n@p mov.u32 %4, 1;\n}"
                 : "+r"(v.x), "+r"(v.y), "+r"(v.z), "+r"(v.w), "+r"(miss) : "l"(p) : "memory");
}
__device__ __forceinline__ void reload8(uint2& v, const void* p, uint32_t& miss) {
    asm volatile("{\n.reg .pred p;\n.reg .b64 u;\nsetp.eq.u32 p, %0, 0xffffffff;\nmov.b64 u, {%0, %1};\n"
                 "@p ld.relaxed.gpu.global.b64 u, [%3];\nmov.b64 {%0, %1}, u;\n@p mov.u32 %2, 1;\n}"
                 : "+r"(v.x), "+r"(v.y), "+r"(miss) : "l"(p) : "memory");
}
__device__ __forceinline__ uint32_t ld_relaxed32(const void* p) {
    uint32_t v;
    asm volatile("ld.relaxed.gpu.global.u32 %0, [%1];" : "=r"(v) : "l"(p) : "memory");
    return v;
}
__device__ __forceinline__ void flag_wait(const unsigned int* p, uint32_t tag) {
    uint32_t v, it = 0;
#pragma unroll 1
    do {
        asm volatile("ld.relaxed.gpu.global.u32 %0, [%1];" : "=r"(v) : "l"(p) : "memory");
    } while (__any_sync(0xffffffffu, v != tag) && ++it < SPIN / 16);
    asm volatile("fence.acquire.gpu;" ::: "memory");
    __syncwarp();
}
__device__ __forceinline__ bool elect() {
    uint32_t p;
    asm volatile("{\n.reg .pred p;\nelect.sync _|p, 0xffffffff;\nselp.u32 %0, 1, 0, p;\n}" : "=r"(p));
    return p;
}
__device__ __forceinline__ void flag_release(unsigned int* p, uint32_t tag) {
    asm volatile("st.release.gpu.global.u32 [%0], %1;" ::"l"(p), "r"(tag) : "memory");
}
__device__ __forceinline__ uint32_t touch(const void* p) {
    uint32_t v;
    asm volatile("ld.global.nc.L1::no_allocate.L2::128B.u32 %0, [%1];" : "=r"(v) : "l"(p));
    return v;
}
__device__ __forceinline__ void bar_sync(int id, int n) { asm volatile("bar.sync %0, %1;" ::"r"(id), "r"(n) : "memory"); }
__device__ __forceinline__ void bar_arrive(int id, int n) { asm volatile("bar.arrive %0, %1;" ::"r"(id), "r"(n) : "memory"); }

constexpr uint64_t EVICT_NORMAL = 0x1000000000000000ull, EVICT_FIRST = 0x12F0000000000000ull;
__device__ __forceinline__ void tma2d(uint32_t dst, const CUtensorMap* m, int c0, int c1, uint32_t bar) {
    asm volatile("cp.async.bulk.tensor.2d.shared::cluster.global.mbarrier::complete_tx::bytes.L2::cache_hint [%0], [%1, {%3, %4}], [%2], %5;"
                 ::"r"(dst), "l"(m), "r"(bar), "r"(c0), "r"(c1), "l"(EVICT_FIRST) : "memory");
}
__device__ __forceinline__ void tma2d_mc(uint32_t dst, const CUtensorMap* m, int c0, int c1, uint32_t bar, uint64_t pol) {
    asm volatile("cp.async.bulk.tensor.2d.shared::cluster.global.mbarrier::complete_tx::bytes.multicast::cluster.L2::cache_hint [%0], [%1, {%3, %4}], [%2], %5, %6;"
                 ::"r"(dst), "l"(m), "r"(bar), "r"(c0), "r"(c1), "h"((uint16_t)3), "l"(pol) : "memory");
}
__device__ __forceinline__ void tma3d(uint32_t dst, const CUtensorMap* m, int c0, int c1, int c2, uint32_t bar) {
    asm volatile("cp.async.bulk.tensor.3d.shared::cluster.global.mbarrier::complete_tx::bytes.L2::cache_hint [%0], [%1, {%3, %4, %5}], [%2], %6;"
                 ::"r"(dst), "l"(m), "r"(bar), "r"(c0), "r"(c1), "r"(c2), "l"(EVICT_FIRST) : "memory");
}
__device__ __forceinline__ void bulk_load(uint32_t dst, const void* src, uint32_t bytes, uint32_t bar) {
    asm volatile("cp.async.bulk.shared::cluster.global.mbarrier::complete_tx::bytes [%0], [%1], %2, [%3];"
                 ::"r"(dst), "l"(src), "r"(bytes), "r"(bar) : "memory");
}
__device__ __forceinline__ void l2_prefetch(const void* src, uint32_t bytes) {
    asm volatile("cp.async.bulk.prefetch.L2.global [%0], %1;" ::"l"(src), "r"(bytes) : "memory");
}
__device__ __forceinline__ uint32_t bmul2(uint32_t a, uint32_t b) { uint32_t r; asm("mul.rn.bf16x2 %0, %1, %2;" : "=r"(r) : "r"(a), "r"(b)); return r; }
__device__ __forceinline__ uint32_t badd2(uint32_t a, uint32_t b) { uint32_t r; asm("add.rn.bf16x2 %0, %1, %2;" : "=r"(r) : "r"(a), "r"(b)); return r; }
__device__ __forceinline__ uint32_t bsub2(uint32_t a, uint32_t b) { uint32_t r; asm("sub.rn.bf16x2 %0, %1, %2;" : "=r"(r) : "r"(a), "r"(b)); return r; }
__device__ __forceinline__ uint32_t bmax2(uint32_t a, uint32_t b) { uint32_t r; asm("max.bf16x2 %0, %1, %2;" : "=r"(r) : "r"(a), "r"(b)); return r; }
__device__ __forceinline__ uint4 lds128(uint32_t a) { uint4 v; asm volatile("ld.shared.v4.u32 {%0,%1,%2,%3}, [%4];" : "=r"(v.x), "=r"(v.y), "=r"(v.z), "=r"(v.w) : "r"(a) : "memory"); return v; }
__device__ __forceinline__ uint2 lds64(uint32_t a) { uint2 v; asm volatile("ld.shared.v2.u32 {%0,%1}, [%2];" : "=r"(v.x), "=r"(v.y) : "r"(a) : "memory"); return v; }
__device__ __forceinline__ uint32_t lds32(uint32_t a) { uint32_t v; asm volatile("ld.shared.u32 %0, [%1];" : "=r"(v) : "r"(a) : "memory"); return v; }
__device__ __forceinline__ uint4 ldsm4(uint32_t a) {
    uint4 v;
    asm volatile("ldmatrix.sync.aligned.m8n8.x4.shared.b16 {%0,%1,%2,%3}, [%4];" : "=r"(v.x), "=r"(v.y), "=r"(v.z), "=r"(v.w) : "r"(a) : "memory");
    return v;
}
__device__ __forceinline__ uint4 ldsm4t(uint32_t a) {
    uint4 v;
    asm volatile("ldmatrix.sync.aligned.m8n8.x4.trans.shared.b16 {%0,%1,%2,%3}, [%4];" : "=r"(v.x), "=r"(v.y), "=r"(v.z), "=r"(v.w) : "r"(a) : "memory");
    return v;
}
__device__ __forceinline__ void mma1688(float* d, uint32_t a0, uint32_t a1, uint32_t b) {
    asm("mma.sync.aligned.m16n8k8.row.col.f32.bf16.bf16.f32 {%0,%1,%2,%3}, {%4,%5}, {%6}, {%0,%1,%2,%3};"
        : "+f"(d[0]), "+f"(d[1]), "+f"(d[2]), "+f"(d[3]) : "r"(a0), "r"(a1), "r"(b));
}
__device__ __forceinline__ void mma16816(float* d, uint32_t a0, uint32_t a1, uint32_t a2, uint32_t a3, uint32_t b0, uint32_t b1) {
    asm("mma.sync.aligned.m16n8k16.row.col.f32.bf16.bf16.f32 {%0,%1,%2,%3}, {%4,%5,%6,%7}, {%8,%9}, {%0,%1,%2,%3};"
                 : "+f"(d[0]), "+f"(d[1]), "+f"(d[2]), "+f"(d[3]) : "r"(a0), "r"(a1), "r"(a2), "r"(a3), "r"(b0), "r"(b1));
}
__device__ __forceinline__ void stsm_x4(uint32_t addr, uint32_t a, uint32_t b, uint32_t c, uint32_t d) {
    asm volatile("stmatrix.sync.aligned.m8n8.x4.shared.b16 [%0], {%1, %2, %3, %4};"
                 ::"r"(addr), "r"(a), "r"(b), "r"(c), "r"(d) : "memory");
}

__device__ __forceinline__ uint64_t mkdesc(uint32_t addr, uint32_t lbo, uint32_t sbo) {
    return (uint64_t)((addr & 0x3FFFF) >> 4) | ((uint64_t)(lbo >> 4) << 16) | ((uint64_t)(sbo >> 4) << 32) | (1ull << 62);
}
constexpr uint32_t SM0 = 1024;
__host__ __device__ constexpr uint32_t desc_lo(uint32_t off, uint32_t lbo) { return ((SM0 + off) >> 4) | ((lbo >> 4) << 16); }
#define WG_FENCE() asm volatile("wgmma.fence.sync.aligned;" ::: "memory")
#define WG_COMMIT() asm volatile("wgmma.commit_group.sync.aligned;" ::: "memory")
#define WG_WAIT(n) asm volatile("wgmma.wait_group.sync.aligned %0;" ::"n"(n) : "memory")

#define F8(a, i) "+f"(a[i]), "+f"(a[i + 1]), "+f"(a[i + 2]), "+f"(a[i + 3]), "+f"(a[i + 4]), "+f"(a[i + 5]), "+f"(a[i + 6]), "+f"(a[i + 7])
#define F16(a, i) F8(a, i), F8(a, i + 8)
#define F64(a) F16(a, 0), F16(a, 16), F16(a, 32), F16(a, 48)
#define F32(a) F16(a, 0), F16(a, 16)
#define L64 "%0,%1,%2,%3,%4,%5,%6,%7,%8,%9,%10,%11,%12,%13,%14,%15,%16,%17,%18,%19,%20,%21,%22,%23,%24,%25,%26,%27,%28,%29,%30,%31,%32,%33,%34,%35,%36,%37,%38,%39,%40,%41,%42,%43,%44,%45,%46,%47,%48,%49,%50,%51,%52,%53,%54,%55,%56,%57,%58,%59,%60,%61,%62,%63"
#define L32 "%0,%1,%2,%3,%4,%5,%6,%7,%8,%9,%10,%11,%12,%13,%14,%15,%16,%17,%18,%19,%20,%21,%22,%23,%24,%25,%26,%27,%28,%29,%30,%31"

template <int TB, int STEP = 128>
__device__ __forceinline__ void mma_rs128(float (&d)[64], uint32_t a0, uint32_t a1, uint32_t a2, uint32_t a3, uint64_t& b, int acc) {
    asm volatile("{\n.reg .pred p;\nsetp.ne.b32 p, %69, 0;\n"
                 "wgmma.mma_async.sync.aligned.m64n128k16.f32.bf16.bf16 {" L64 "}, {%65,%66,%67,%68}, %64, p, 1, 1, %70;\nadd.s64 %64, %64, %71;\n}"
                 : F64(d), "+l"(b) : "r"(a0), "r"(a1), "r"(a2), "r"(a3), "r"(acc), "n"(TB), "n"(STEP));
}
template <int TB>
__device__ __forceinline__ void mma_rs64(float (&d)[32], uint32_t a0, uint32_t a1, uint32_t a2, uint32_t a3, uint64_t& b, int acc) {
    asm volatile("{\n.reg .pred p;\nsetp.ne.b32 p, %37, 0;\n"
                 "wgmma.mma_async.sync.aligned.m64n64k16.f32.bf16.bf16 {" L32 "}, {%33,%34,%35,%36}, %32, p, 1, 1, %38;\nadd.s64 %32, %32, 128;\n}"
                 : F32(d), "+l"(b) : "r"(a0), "r"(a1), "r"(a2), "r"(a3), "r"(acc), "n"(TB));
}
template <int N>
__device__ __forceinline__ void fence_regs(float (&d)[N]) {
#pragma unroll
    for (int i = 0; i < N; i++) asm volatile("" : "+f"(d[i])::"memory");
}
template <int N>
__device__ __forceinline__ void fence_regs(uint32_t (&d)[N]) {
#pragma unroll
    for (int i = 0; i < N; i++) asm volatile("" : "+r"(d[i])::"memory");
}

template <int V> struct IC { static constexpr int value = V; };

constexpr int SLOT = 32768, UNIT = 16384;
constexpr int SM_Q = 4 * SLOT;
constexpr int SM_BAR = 7 * SLOT;
constexpr int SM_RED = SM_BAR + 512;
constexpr int SM_TOTAL = SM_BAR + 3072;
constexpr int XP = D_ * 2 + 16;
constexpr int M_MOD = 16 * XP;
constexpr int SM_T = SM_Q + 2 * D_ * 80, SM_TC = SM_T + D_ * 4, SM_TG = SM_TC + D_ * 4, SM_TS = SM_TG + D_ * 2;
constexpr float CS = 0.08838834764831845f * 1.4426950408889634f;
#define USE_SPARE 1
constexpr float POFF = 102.f, LMIN = 0x1p-104f;
#define LMAX 0.5f
constexpr int SPLIT = 10;
constexpr int STAGE = 11;
constexpr int ESPLIT = 3;
constexpr int QSPLIT = 4, OSPLIT = 6;
#define OE 0
#define OED 0
#define NOOUT 0
#define RD 0
#define RP 1
#define T_X 0
#define T_B 0
#define T_C 1
#define T_U 1
#define T_D 1
#define W0_ 3
#define W1_ 13
#define W2_ 19
#define DL_ 9
constexpr int WF0 = W0_, WF1 = W1_, WF2 = W2_, DL = DL_;
constexpr int PF_KV = 4, PF_WO = 120;

__device__ __forceinline__ int cluster_role() {
    int k;
    asm volatile("mov.u32 %0, %%ctaid.x;" : "=r"(k));
    k >>= 1;
    const int r = ((k - 36) * 37) >> 8, i = k - 36 - r * 7;
    return k < 4 ? 12 + k : k < 36 ? ((k - 4) & 7) * 8 + ((k - 4) >> 3) : (i + (i > 0)) * 8 + ((4 + r) & 7);
}

struct Args {
    const bf16 *w_mod, *cvec;
    Scratch* gs;
    uint64_t d0;
    bf16* out;
    const bf16 *x, *kc, *vc, *wq, *wo, *w_r, *w_down;
};

__device__ __forceinline__ void frag_store(uint8_t* p, const uint32_t (&a)[32]) {
#pragma unroll
    for (int i = 0; i < 8; i++)
        __stcg(reinterpret_cast<uint4*>(p + i * 512), make_uint4(a[4 * i], a[4 * i + 1], a[4 * i + 2], a[4 * i + 3]));
}
template <int LO = 0, int HI = 8>
__device__ __forceinline__ void frag_load(uint32_t (&a)[32], const uint8_t* p) {
#pragma unroll
    for (int i = LO; i < HI; i++) {
        const uint4 v = ld_relaxed(reinterpret_cast<const uint4*>(p + i * 512));
        a[4 * i] = v.x; a[4 * i + 1] = v.y; a[4 * i + 2] = v.z; a[4 * i + 3] = v.w;
    }
}
__device__ __forceinline__ float quad_sum(float v) {
    v += __shfl_xor_sync(0xffffffffu, v, 1);
    return v + __shfl_xor_sync(0xffffffffu, v, 2);
}
__device__ __forceinline__ float quad_max(float v) {
    v = fmaxf(v, __shfl_xor_sync(0xffffffffu, v, 1));
    return fmaxf(v, __shfl_xor_sync(0xffffffffu, v, 2));
}
__device__ __forceinline__ float rcp_fast(float x) { float y; asm("rcp.approx.ftz.f32 %0, %1;" : "=f"(y) : "f"(x)); return y; }
__device__ __forceinline__ float sigmoidf_(float x) { return rcp_fast(1.f + ex2(-1.4426950408889634f * x)); }
__device__ __forceinline__ void top2(uint32_t k, uint32_t& k1, uint32_t& k2) {
    k1 = __reduce_max_sync(0xffffffffu, k);
    k2 = __reduce_max_sync(0xffffffffu, k == k1 ? 0 : k);
}

__device__ __forceinline__ void mod_fma(float (&a)[8], const uint4 w, float sc) {
    a[0] += sc * bf_lo(w.x); a[1] += sc * bf_hi(w.x); a[2] += sc * bf_lo(w.y); a[3] += sc * bf_hi(w.y);
    a[4] += sc * bf_lo(w.z); a[5] += sc * bf_hi(w.z); a[6] += sc * bf_lo(w.w); a[7] += sc * bf_hi(w.w);
}
__device__ __forceinline__ float mod_reduce(float (&a)[8], int lane) {
#pragma unroll
    for (int h = 4; h > 0; h >>= 1) {
        const bool up = lane & (8 / h);
#pragma unroll
        for (int i = 0; i < h; i++)
            a[i] = (up ? a[i + h] : a[i]) + __shfl_xor_sync(0xffffffffu, up ? a[i] : a[i + h], 8 / h);
    }
    return a[0] + __shfl_xor_sync(0xffffffffu, a[0], 16);
}

__device__ __forceinline__ float ln_stats(float sum, float sq, uint32_t& mean2) {
    const float mean = sum * (1.f / D_);
    const float var = fmaxf(fmaf(-mean, mean, sq * (1.f / D_)), 0.f);
    float sd;
    asm("sqrt.approx.ftz.f32 %0, %1;" : "=f"(sd) : "f"(rbf(rbf(var) + 1e-5f)));
    mean2 = pack_bf16(mean, mean);
    return rcp_fast(rbf(sd));
}
__device__ __forceinline__ uint32_t ln_pair(uint32_t x, uint32_t mean2, float rsd) {
    const uint32_t d = bsub2(x, mean2);
    return pack_bf16(bf_lo(d) * rsd, bf_hi(d) * rsd);
}
__device__ __forceinline__ void rows_load(uint32_t (&x)[20], uint32_t xs, int cw) {
#pragma unroll
    for (int ch = 0; ch < 5; ch++) {
        const uint4 v = ldsm4(ch < 4 ? xs + ch * 256 : xs + 1024 - cw * 16);
        x[4 * ch] = v.x; x[4 * ch + 1] = v.y; x[4 * ch + 2] = v.z; x[4 * ch + 3] = v.w;
    }
}
__device__ __forceinline__ void stats_add(float (&st)[12], uint32_t a, uint32_t b, uint32_t w) {
    mma1688(st, a, b, w);
    mma1688(st + 4, a, b, a);
    mma1688(st + 8, a, b, b);
}
__device__ __forceinline__ float rows_stats(const float (&st)[12], float4* rec, int cw, int lane, uint32_t& mean2, float& dot) {
    const int g8 = lane >> 2;
    if ((g8 >> 1) == (lane & 3)) {
        rec[cw * 16 + g8] = make_float4(st[0], (g8 & 1) ? st[5] : st[4], st[1], 0.f);
        rec[cw * 16 + 8 + g8] = make_float4(st[2], (g8 & 1) ? st[11] : st[10], st[3], 0.f);
    }
    bar_sync(3, 256);
    const float4* r = rec + (lane >> 4) * 64 + (lane & 15);
    const float4 s0 = r[0], s1 = r[16], s2 = r[32], s3 = r[48];
    const float sum = (s0.x + s1.x) + (s2.x + s3.x), sq = (s0.y + s1.y) + (s2.y + s3.y);
    dot = (s0.z + s1.z) + (s2.z + s3.z);
    dot += __shfl_xor_sync(0xffffffffu, dot, 16);
    return ln_stats(sum + __shfl_xor_sync(0xffffffffu, sum, 16), sq + __shfl_xor_sync(0xffffffffu, sq, 16), mean2);
}
template <class F>
__device__ __forceinline__ void rows_normalise(uint32_t* y, const uint32_t* x, uint32_t mean2, float rsd, int lane, F loads) {
    const int g8 = lane >> 2;
    const uint32_t ma2 = __shfl_sync(0xffffffffu, mean2, g8), mb2 = __shfl_sync(0xffffffffu, mean2, g8 + 8);
    const float ra = __shfl_sync(0xffffffffu, rsd, g8), rb = __shfl_sync(0xffffffffu, rsd, g8 + 8);
    loads();
#pragma unroll
    for (int k = 0; k < 9; k++) { y[2 * k] = ln_pair(x[2 * k], ma2, ra); y[2 * k + 1] = ln_pair(x[2 * k + 1], mb2, rb); }
}

__device__ __forceinline__ uint4 h_frag(const uint4* hf, int ks, int lane) {
    if (ks < 32) return ld_relaxed2(hf + ks * 32);
    const uint2* p = reinterpret_cast<const uint2*>(padd(hf, 256 - lane * 8) + ks * 32 - 16);
    const uint2 a = ld_relaxed64(p), b = ld_relaxed64(p + 32);
    return make_uint4(a.x, a.y, b.x, b.y);
}

__device__ __noinline__ void attn_fallback(uint32_t bad, uint32_t tag, const Scratch* gs, uint8_t* frag, uint8_t* keep, const bf16* wq, const bf16* kc, const bf16* vc) {
  const int lane = threadIdx.x & 31, g8 = lane >> 2, qd = lane & 3;
  const int role = cluster_role(), j = role & 7, qb = (role >> 3) * 2 + (blockIdx.x & 1);
  const uint4* hf = g_h + (size_t)(qb * 8 + (threadIdx.x >> 5) - 4) * (36 * 32) + lane;
#pragma unroll 1
  for (int t = 0; t < 4; t++) {
    if (!((bad >> t) & 1)) continue;
    const bf16 *wqp = wq + (4 * j + t) * DH, *kp = kc + (size_t)(2 * j + (t >> 1)) * S_ * DH, *vp = vc + (size_t)(2 * j + (t >> 1)) * S_ * DH;
    uint32_t q[32];
    float o[64];
#pragma unroll
    for (int i = 0; i < 64; i++) o[i] = 0.f;
#pragma unroll 1
    for (int ks = 0; ks < 36; ks++) {
        const uint4 a = h_frag(hf, ks, lane);
        const unsigned short* wr = reinterpret_cast<const unsigned short*>(wqp + (size_t)(ks * 16 + 2 * qd) * QD + g8);
#pragma unroll
        for (int dt = 0; dt < 16; dt++) {
            const uint32_t b0 = __ldg(wr + dt * 8) | ((uint32_t)__ldg(wr + dt * 8 + QD) << 16);
            const uint32_t b1 = __ldg(wr + dt * 8 + 8 * QD) | ((uint32_t)__ldg(wr + dt * 8 + 9 * QD) << 16);
            mma16816(o + 4 * dt, a.x, a.y, a.z, a.w, b0, b1);
        }
    }
#pragma unroll
    for (int i = 0; i < 32; i++) q[i] = pack_bf16(o[2 * i], o[2 * i + 1]);
#pragma unroll
    for (int i = 0; i < 64; i++) o[i] = 0.f;
    float m0 = -INFINITY, m1 = -INFINITY, l0 = 0.f, l1 = 0.f;
#pragma unroll 1
    for (int key = 0; key < S_; key += 16) {
        float sc[8];
#pragma unroll
        for (int i = 0; i < 8; i++) sc[i] = 0.f;
#pragma unroll
        for (int nt = 0; nt < 2; nt++) {
            const uint32_t* kr = reinterpret_cast<const uint32_t*>(kp + (size_t)(key + nt * 8 + g8) * DH) + qd;
#pragma unroll
            for (int ks = 0; ks < 8; ks++)
                mma16816(sc + 4 * nt, q[4 * ks], q[4 * ks + 1], q[4 * ks + 2], q[4 * ks + 3], __ldg(kr + ks * 8), __ldg(kr + ks * 8 + 4));
        }
        const float n0 = quad_max(fmaxf(fmaxf(m0, fmaxf(sc[0], sc[1])), fmaxf(sc[4], sc[5])));
        const float n1 = quad_max(fmaxf(fmaxf(m1, fmaxf(sc[2], sc[3])), fmaxf(sc[6], sc[7])));
        const float f0 = ex2((m0 - n0) * CS), f1 = ex2((m1 - n1) * CS);
        m0 = n0; m1 = n1;
#pragma unroll
        for (int i = 0; i < 8; i++) sc[i] = ex2((sc[i] - ((i & 2) ? n1 : n0)) * CS);
        l0 = l0 * f0 + (sc[0] + sc[1]) + (sc[4] + sc[5]);
        l1 = l1 * f1 + (sc[2] + sc[3]) + (sc[6] + sc[7]);
        const uint32_t e0 = pack_bf16(sc[0], sc[1]), e1 = pack_bf16(sc[2], sc[3]), e2 = pack_bf16(sc[4], sc[5]), e3 = pack_bf16(sc[6], sc[7]);
        const unsigned short* vr = reinterpret_cast<const unsigned short*>(vp + (size_t)(key + 2 * qd) * DH + g8);
#pragma unroll
        for (int dt = 0; dt < 16; dt++) {
            o[4 * dt] *= f0; o[4 * dt + 1] *= f0; o[4 * dt + 2] *= f1; o[4 * dt + 3] *= f1;
            const uint32_t b0 = __ldg(vr + dt * 8) | ((uint32_t)__ldg(vr + dt * 8 + DH) << 16);
            const uint32_t b1 = __ldg(vr + dt * 8 + 8 * DH) | ((uint32_t)__ldg(vr + dt * 8 + 9 * DH) << 16);
            mma16816(o + 4 * dt, e0, e1, e2, e3, b0, b1);
        }
    }
    const float i0 = 1.f / quad_sum(l0), i1 = 1.f / quad_sum(l1);
#pragma unroll
    for (int i = 0; i < 16; i++) {
        q[2 * i] = pack_bf16(o[4 * i] * i0, o[4 * i + 1] * i0);
        q[2 * i + 1] = pack_bf16(o[4 * i + 2] * i1, o[4 * i + 3] * i1);
    }
    frag_store(t < 3 ? frag + t * 4096 : keep, q);
  }
}

__device__ __forceinline__ void spare_q3(Scratch* gs, uint32_t sb, uint32_t bar_full, uint32_t bar_empty, int lane, int cw) {
    const uint32_t tag = load_tag(gs);
    uint32_t rel_base, e = 3;
    asm("mapa.shared::cluster.u32 %0, %1, %2;" : "=r"(rel_base) : "r"(bar_empty), "r"(lane & 1));
#pragma unroll 1
    for (int qb = blockIdx.x - NCTA; qb < 16; qb += 4) {
        uint32_t h[144];
        float o[64];
        flag_wait(&g_flag_h[(qb * 8 + cw) * 32], tag);
        const uint4* hf = g_h + (size_t)(qb * 8 + cw) * (36 * 32) + lane;
#pragma unroll
        for (int ks = 0; ks < 36; ks++) {
            const uint4 v = h_frag(hf, ks, lane);
            h[4 * ks] = v.x; h[4 * ks + 1] = v.y; h[4 * ks + 2] = v.z; h[4 * ks + 3] = v.w;
        }
#pragma unroll
        for (int i = 0; i < 64; i++) o[i] = 0.f;
#pragma unroll 1
        for (int v = 0; v < 4; v++) {
            fence_regs(o);
#pragma unroll
            for (int t = 0; t < 5; t++) {
                mbar_wait(bar_full + 8 * (e & 3), (e >> 2) & 1);
                uint64_t dv = mkdesc(sb + (e & 3) * SLOT, UNIT, 1024);
                WG_FENCE();
#pragma unroll
                for (int ks = 0; ks < (t < 4 ? 8 : 4); ks++)
                    mma_rs128<1>(o, h[32 * t + 4 * ks], h[32 * t + 4 * ks + 1], h[32 * t + 4 * ks + 2], h[32 * t + 4 * ks + 3], dv, ks | t);
                WG_COMMIT();
                if (t > 0) { WG_WAIT(1); if (lane < 2) mbar_arrive_cluster(rel_base + 8 * ((e - 1) & 3)); }
                e++;
            }
            WG_WAIT(0);
            fence_regs(o);
            if (lane < 2) mbar_arrive_cluster(rel_base + 8 * ((e - 1) & 3));
            uint4* dst = &g_q3[((qb * 8 + 2 * v) * 8 + cw) * 128 + lane];
#pragma unroll
            for (int i = 0; i < 8; i++)
                __stcg(dst + (i >> 2) * 1024 + (i & 3) * 32, make_uint4(pack_bf16(o[8 * i], o[8 * i + 1]), pack_bf16(o[8 * i + 2], o[8 * i + 3]),
                                                                        pack_bf16(o[8 * i + 4], o[8 * i + 5]), pack_bf16(o[8 * i + 6], o[8 * i + 7])));
        }
        bar_sync(3, 256);
        if (cw == 0 && lane == 0) flag_release(&g_flag_q3[qb * 32], tag);
        __syncwarp();
    }
}

template <bool SPARE>
__global__ void __cluster_dims__(2, 1, 1) __launch_bounds__(384, 1)
fused_kernel(const Args args, const __grid_constant__ CUtensorMap tm_wq,
             const __grid_constant__ CUtensorMap tm_k, const __grid_constant__ CUtensorMap tm_v,
             const __grid_constant__ CUtensorMap tm_wo, const __grid_constant__ CUtensorMap tm_p,
             const __grid_constant__ CUtensorMap tm_x, const __grid_constant__ CUtensorMap tm_d,
             const __grid_constant__ CUtensorMap tm_g, const __grid_constant__ CUtensorMap tm_u) {
    extern __shared__ __align__(1024) uint8_t smem_raw[];
    const uint32_t sb = smem_u32(smem_raw);
    Scratch* const gs = args.gs;
    const uint32_t bar_full = sb + SM_BAR;
    const uint32_t bar_g = bar_full + 8 * 4;
    const uint32_t bar_mod = bar_g + 8;
    const uint32_t bar_go = bar_mod + 8;
    const uint32_t bar_x = bar_go + 40;
    const uint32_t bar_empty = bar_x + 8;
    const uint32_t bar_pub = bar_empty + 8 * 4;
    const uint32_t bar_qfree = bar_pub + 32;
    const uint32_t bar_out = bar_qfree + 24;
    const uint32_t bar_q3 = bar_out + 8;
    const uint32_t bar_stg = bar_q3 + 24;
    const uint32_t bar_pre = bar_q3 + 16;
    const uint32_t bar_w0 = bar_q3 + 8;
    constexpr int E0 = SPARE ? 2 : 0;

    const int c = blockIdx.x & 1;
#define ROLES() const int role = cluster_role(), j = role & 7, qb = (role >> 3) * 2 + c, rg = qb * 8 + j
    const int warp = __shfl_sync(0xffffffffu, threadIdx.x >> 5, 0);

    if (SPARE && blockIdx.x >= NCTA && warp >= 4) {
        asm volatile("barrier.cluster.arrive.relaxed.aligned;" ::: "memory");
        asm volatile("setmaxnreg.inc.sync.aligned.u32 240;");
        asm volatile("barrier.cluster.wait.aligned;" ::: "memory");
        spare_q3(gs, sb, bar_full, bar_empty, threadIdx.x & 31, warp - 4);
        asm volatile("barrier.cluster.arrive.relaxed.aligned;\nbarrier.cluster.wait.aligned;" ::: "memory");
    } else if (warp < 4) {
        asm volatile("setmaxnreg.dec.sync.aligned.u32 24;");
        ROLES();
        int lane;
        asm volatile("mov.u32 %0, %%laneid;" : "=r"(lane));
        if (warp == 2 && elect()) {
            asm volatile("prefetch.tensormap [%0];" ::"l"(&tm_x) : "memory");
#pragma unroll
            for (int i = 0; i < 28; i++) mbar_init(bar_full + 8 * i, i < 12 || (i >= 23 && i < 27) ? 1 : i < 16 ? 16 : 8);
#pragma unroll
            for (int i = 0; i <= E0; i++) {
                mbar_arrive(bar_full + 8 * i);
                asm volatile("mbarrier.arrive.shared::cta.b64 _, [%0], 16;" ::"r"(bar_empty + 8 * i) : "memory");
            }
            asm volatile("fence.mbarrier_init.release.cluster;" ::: "memory");
        }
        __syncwarp();
        asm volatile("barrier.cluster.arrive.relaxed.aligned;" ::: "memory");
        if (warp == 2 && !(SPARE && blockIdx.x >= NCTA)) {
            __nanosleep(200);
            if (elect()) {
                mbar_expect_tx(bar_x, 16 * XP);
                tma2d(sb + SM_Q, &tm_x, 0, rg * 16, bar_x);
            }
            __syncwarp();
        }
        asm volatile("barrier.cluster.wait.aligned;" ::: "memory");
        const uint32_t tag = load_tag(gs);
        if (SPARE && blockIdx.x >= NCTA) {
            if (warp == 1) {
#pragma unroll 1
                for (int e = 3; e < 83; e++) {
                    const int v = (e - 3) / 5;
                    mbar_wait_sleep(bar_empty + 8 * (e & 3), ~(e >> 2) & 1);
                    if (elect()) {
                        mbar_expect_tx(bar_full + 8 * (e & 3), SLOT);
                        tma2d_mc(sb + (e & 3) * SLOT + c * UNIT, &tm_wq, (8 * (v & 3) + 4 * c + 3) * DH + 64, (e - 3 - v * 5) * 128,
                                 bar_full + 8 * (e & 3), EVICT_NORMAL);
                    }
                }
            }
            __syncwarp();
            asm volatile("barrier.cluster.arrive.relaxed.aligned;\nbarrier.cluster.wait.aligned;" ::: "memory");
            return;
        }
        if (warp == 3) {
#pragma unroll 1
            for (int e = 4; e < 20; e++) {
                __nanosleep(e == 4 ? 2000 : 400);
                const int hd = (e * 52) >> 8, row = (e - hd * 5) * 128 + qb * 8 + (lane >> 1);
                if (lane < 16 && row < D_)
                    asm volatile("prefetch.global.L2 [%0];" ::"l"(padd(args.wq, (row * QD + (4 * j + ((0x1320 >> (4 * hd)) & 3)) * DH + (lane & 1) * 64) * 2)) : "memory");
            }
            __syncwarp();
            mbar_wait_sleep(bar_go, 0);
#pragma unroll 1
            for (int unit = 72 + blockIdx.x; unit < 216; unit += NCTA) {
                float a[8];
#pragma unroll
                for (int i = 0; i < 8; i++) a[i] = 0.f;
#pragma unroll 1
                for (int k = lane >> 1; k < D_; k += 16) {
                    const float cv = __bfloat162float(*padd(args.cvec, k * 2));
                    mod_fma(a, __ldg(reinterpret_cast<const uint4*>(padd(args.w_mod, (k * (6 * D_) + unit * 16 + (lane & 1) * 8) * 2))), rbf(cv * sigmoidf_(cv)));
                }
                const float v = mod_reduce(a, lane), v1 = __shfl_down_sync(0xffffffffu, v, 8);
                if (lane < 8) *padd(gs->mod2, ((unit - 72) * 8 + (lane & 1) * 4 + (lane & 2) + (lane >> 2)) * 4) = pack_bf16(v, v1);
            }
            __syncwarp();
            if (lane == 0) flag_release(padd(g_flag_mod, blockIdx.x * 4), tag);
#pragma unroll 1
            for (int k = 0; k < 36; k++) {
                __nanosleep(200);
                __stcg(padd(gs->h[0], (~tag & 1) * (NCTA * 36 * 512) + ((rg * 36 + k) * 32 + lane) * 16), make_uint4(0, 0, 0, 0));
            }
            __syncwarp();
            mbar_wait_sleep(bar_qfree + 16, 0);
            __nanosleep(2000);
            {
                uint4 v;
                uint32_t it = 0;
#pragma unroll 1
                do {
                    v = ld_relaxed(reinterpret_cast<const uint4*>(padd(g_flag_mod, lane * 16)));
                } while (((v.x ^ tag) | (v.y ^ tag) | (v.z ^ tag) | (v.w ^ tag)) && ++it < SPIN / 16);
                asm volatile("fence.acquire.gpu;" ::: "memory");
            }
            __syncwarp();
            {
                float w1 = 0.f, w2 = 0.f;
#pragma unroll 1
                for (int k = lane; k < D_ / 2; k += 32) {
                    const uint32_t* mp = padd(gs->mod2, k * 4);
                    const uint32_t sv = __ldcg(mp + D_ / 2), c1 = badd2(__ldcg(mp + D_), 0x3f803f80u);
                    const uint32_t wr = *reinterpret_cast<const uint32_t*>(padd(args.w_r, k * 4)), wp = bmul2(c1, wr);
                    reinterpret_cast<uint2*>(smem_raw + SM_T)[k] = make_uint2(__ldcg(mp), wp);
                    reinterpret_cast<uint2*>(smem_raw + SM_TC)[k] = make_uint2(c1, sv);
                    reinterpret_cast<uint32_t*>(smem_raw + SM_TG)[k] = __ldcg(mp + 3 * D_ / 2);
                    w1 += bf_lo(wp) + bf_hi(wp);
                    w2 += bf_lo(sv) * bf_lo(wr) + bf_hi(sv) * bf_hi(wr);
                }
#pragma unroll 1
                for (int i = 1; i < 32; i <<= 1) { w1 += __shfl_xor_sync(0xffffffffu, w1, i); w2 += __shfl_xor_sync(0xffffffffu, w2, i); }
                *reinterpret_cast<float2*>(smem_raw + SM_TS) = make_float2(w1, w2);
            }
#pragma unroll
            for (int i = 0; i < 4; i++) reinterpret_cast<uint4*>(smem_raw + SM_RED)[lane + 32 * i] = make_uint4(~0u, ~0u, ~0u, ~0u);
            asm volatile("fence.proxy.async.shared::cta;" ::: "memory");
            __syncwarp();
            if (elect()) {
                uint8_t* mb = g_frag + (size_t)rg * 8 * WREG + 3 * 4096;
#pragma unroll 1
                for (int k = 0; k < 8; k++, mb += WREG) {
#pragma unroll
                    for (int i = 0; i < 3; i++)
                        asm volatile("cp.async.bulk.global.shared::cta.bulk_group [%0], [%1], 2048;" ::"l"(mb + i * 2048), "r"(sb + SM_RED) : "memory");
                    __nanosleep(500);
                }
                asm volatile("cp.async.bulk.commit_group;\ncp.async.bulk.wait_group 0;\nfence.proxy.async.global;" ::: "memory");
            }
            __syncwarp();
            if (lane == 0) mbar_arrive(bar_mod);
            __syncwarp();
            mbar_wait_sleep(bar_go + 8, 0);
            if (elect()) asm volatile("prefetch.tensormap [%0];\nprefetch.tensormap [%1];\nprefetch.tensormap [%2];" ::"l"(&tm_x), "l"(&tm_p), "l"(&tm_d) : "memory");
            __syncwarp();
#pragma unroll 1
            for (int i = 1; i < 4; i++) {
                mbar_wait(bar_pub + 8 * i, 0);
                unsigned int* flags = padd(g_flag_part, (qb * 32 + i * 8 - 8) * 4);
                if (elect()) { flag_release(padd(flags, j * 4), tag); DBG_PG(93); }
                __syncwarp();
                const uint32_t slot = (i + 2) & 3;
                flag_wait(padd(flags, (lane & 7) * 4), tag);
                asm volatile("fence.proxy.async.global;" ::: "memory");
                if (lane == 0 && i == 3) DBG_PG(101);
                mbar_wait(bar_go + 8 + 8 * i, 0);
                mbar_wait(bar_empty + 8 * slot, i == 3);
                if (elect()) {
                    mbar_expect_tx(bar_full + 8 * slot, SLOT);
                    tma3d(sb + slot * SLOT, &tm_p, 0, j * 20 + (i - 1) * 4, qb * 8, bar_full + 8 * slot);
                    tma3d(sb + slot * SLOT + UNIT, &tm_p, 0, j * 20 + (i - 1) * 4 + 2, qb * 8, bar_full + 8 * slot);
                }
            }
        } else if (warp == 0) {
#pragma unroll 1
            for (int i = 0; i < 48; i++) {
                if (SPARE && i == 34) {
                    flag_wait(&g_flag_q3[qb * 32], tag);
                    if (elect()) {
                        asm volatile("fence.proxy.async.global;" ::: "memory");
                        mbar_expect_tx(bar_q3, UNIT);
#pragma unroll 1
                        for (int k = 0; k < 8; k++) bulk_load(sb + SM_Q + 2 * SLOT + k * 4096 + 2048, &g_q3[(rg * 8 + k) * 128], 2048, bar_q3);
                    }
                }
                if (i == 0 || i == 17 || i == 34) { mbar_wait_sleep(bar_qfree + (i >> 4) * 8, 0); __nanosleep(2000); }
                __nanosleep(500);
                if (elect()) {
                    asm volatile("mbarrier.expect_tx.shared::cta.b64 [%0], %1;" ::"r"(bar_g), "n"(1920) : "memory");
                    tma2d(sb + SM_Q + i * 1920, i < 24 ? &tm_g : &tm_u, (blockIdx.x * 36) & ~7, (i < 24 ? i : i - 24) * 24, bar_g);
                }
            }
            if (elect()) mbar_arrive(bar_g);
#pragma unroll 1
            for (int i = 0; i < 18; i++) {
                __nanosleep(400);
                if (elect()) l2_prefetch(args.w_down + (size_t)(blockIdx.x * 36 + i * 2) * D_, 4 * D_);
            }
            __syncwarp();
            mbar_wait_sleep(bar_go + 8 * 2, 0);
            uint32_t acc = 0;
#pragma unroll 1
            for (int k = lane; k < 16 * 9; k += 32) acc |= touch(padd(args.x, (rg * 16 * D_ + k * 64) * 2));
            if (acc == 0) reinterpret_cast<volatile uint32_t*>(smem_raw + SM_BAR)[127] = acc;
            __syncwarp();
            mbar_wait_sleep(bar_go + 8 * 4, 0);
            uint4* rp = padd(g_rows, (rg * 2 * RSLOT + lane) * 16);
#pragma unroll
            for (int k = 0; k < 12; k++) rp[k * 32] = make_uint4(~0u, ~0u, ~0u, ~0u);
            if (blockIdx.x < 72) {
                uint4* yp = reinterpret_cast<uint4*>(padd(g_ypart, blockIdx.x * NCTA * 64 + lane * 16));
#pragma unroll
                for (int k = 0; k < 16; k++) yp[k * 32] = make_uint4(~0u, ~0u, ~0u, ~0u);
            }
            asm volatile("fence.acq_rel.gpu;" ::: "memory");
            __syncwarp();
            if (lane == 0) mbar_arrive(bar_pre);
        } else if (warp == 1) {
            __nanosleep(300);
            uint32_t go = bar_go;
            uint64_t marks = 24 | 151 << 8 | 155 << 16 | 160ull << 24 | 165ull << 32;
#pragma unroll 1
            for (int e = E0; e < 168; e++) {
                const CUtensorMap* tm;
                int c0, c1;
                uint64_t pol = EVICT_FIRST;
                if (e == 159 || e == 164) continue;
                if (e < 21 && e != 19) {
                    const int i = SPARE && e < 12 ? e - 2 : e - (e == 20), hd = (i * 52) >> 8;
                    tm = &tm_wq; c0 = (4 * j + ((0x1320 >> (4 * hd)) & 3)) * DH + c * 64; c1 = (i - hd * 5) * 128 - 64;
                    if (SPARE && e >= 12 && e < 15) { c0 = (4 * j + 3) * DH; c1 = (2 * (e - 12) + c) * 128; }
                } else if (e < 148) {
                    const int i = max(e - 20, 0);
                    const bool isk = i == 0 || ((i & 1) && i < 127);
                    const int n = isk ? (i + 1) >> 1 : (i - 1) >> 1;
                    tm = isk ? &tm_k : &tm_v; c0 = c * 64; c1 = (2 * j + (n >> 5)) * S_ + (n & 15) * 128;
                    if (!(i & 32)) pol = EVICT_NORMAL;
                } else {
                    int i = e - 148 - (e > 159) - (e > 164);
                    tm = &tm_wo; c0 = (i >> 1) * 64; c1 = (4 * j + ((i & 1) ? 1 + c : 3 * c)) * DH;
                }
                const uint32_t fb = e == E0 ? bar_w0 : bar_full + 8 * (e & 3), d = sb + (e == E0 ? 6 : e & 3) * SLOT;
                if (e >= 24 && e < 152) mbar_wait_sleep(bar_empty + 8 * (e & 3), ~(e >> 2) & 1);
                else if (e != E0) mbar_wait(bar_empty + 8 * (e & 3), ~(e >> 2) & 1);
                if (elect()) {
                    mbar_expect_tx(fb, SLOT);
                    tma2d_mc(d + c * UNIT, tm, c0, c1, fb, pol);
                    const int i = e - PF_KV;
                    if (i >= 0 && i < 128 && !(i & 32))
                        l2_prefetch(((i & 1) ? args.vc : args.kc) + (size_t)((2 * j + (i >> 6)) * S_ + (i & 30) * 64) * DH + qb * 1024, 2048);
                    if (e >= PF_WO && e < PF_WO + 18) l2_prefetch(args.wo + (size_t)blockIdx.x * (QD * D_ / NCTA) + (e - PF_WO) * 1024, 2048);
                    if (e == (marks & 255)) mbar_arrive(go);
                }
                if (e == (marks & 255)) { go += 8; marks >>= 8; }
            }
            asm volatile("fence.proxy.async.global;" ::: "memory");
            mbar_wait(bar_empty, 1);
            if (elect()) {
                mbar_expect_tx(bar_full, 16 * XP);
                tma2d(sb, &tm_x, 0, rg * 16, bar_full);
            }
            mbar_wait(bar_empty + 16, 1);
            if (elect()) {
                mbar_expect_tx(bar_full + 16, SLOT);
                tma3d(sb + 2 * SLOT, &tm_p, 0, j * 20 + 12, qb * 8, bar_full + 16);
                tma3d(sb + 2 * SLOT + UNIT, &tm_p, 0, j * 20 + 14, qb * 8, bar_full + 16);
            }
            mbar_wait(bar_empty + 24, 1);
            __nanosleep(300);
            if (elect()) {
                mbar_expect_tx(bar_full + 24, UNIT);
                tma3d(sb + 3 * SLOT, &tm_p, 0, j * 20 + 16, qb * 8, bar_full + 24);
            }
            mbar_wait(bar_empty + 8, 0);
            mbar_wait(bar_empty + 16, 0);
            __nanosleep(300);
            if (elect()) {
#pragma unroll
                for (int i = 1; i < 3; i++) {
                    mbar_expect_tx(bar_full + 8 * i, 18 * XP);
                    tma2d(sb + i * SLOT, &tm_d, 0, blockIdx.x * 36 + (i - 1) * 18, bar_full + 8 * i);
                }
            }
        } else {
            if (elect()) asm volatile("prefetch.tensormap [%0];\nprefetch.tensormap [%1];\nprefetch.tensormap [%2];" ::"l"(&tm_k), "l"(&tm_v), "l"(&tm_wo) : "memory");
            if (SPARE) {
                mbar_wait_sleep(bar_pub, 0);
                if (lane == 0) flag_release(padd(g_flag_h, rg * 128), tag);
                __syncwarp();
            }
            bar_sync(1, 192);
#pragma unroll 1
            for (uint32_t e = E0 + 5; e < 20; e++) {
                mbar_wait(bar_full + 8 * (e & 3), (e >> 2) & 1);
                if (!(((SPARE ? 0xa080 : 0x8420) >> e) & 1)) bar_sync(1, 192);
            }
#pragma unroll 1
            for (uint32_t e = 20; e < 148; e++) {
                mbar_wait_sleep(bar_full + 8 * (e & 3), (e >> 2) & 1);
                if (SPARE && e == 113) mbar_wait(bar_q3, 0);
                if (e & 1) bar_sync(1, 192);
                if (!(e & 1) || e == 147) bar_sync(4, 160);
            }
#pragma unroll 1
            for (uint32_t e = 148; e < 168; e++) {
                mbar_wait(bar_full + 8 * (e & 3), (e >> 2) & 1);
                if (e != 159 && e != 164) bar_sync(1, 192);
            }
        }
        __syncwarp();
        uint32_t rows = 0x1111u << warp;
        auto store_rows = [&](uint32_t m) {
#pragma unroll 1
            for (; m; m &= m - 1) {
                const int i = __ffs(m) - 1;
                asm volatile("cp.async.bulk.global.shared::cta.bulk_group.L2::cache_hint [%0], [%1], %2, %3;"
                             ::"l"(padd(args.out, (rg * 16 + i) * (D_ * 2))), "r"(sb + i * XP), "n"(NOOUT ? 16 : D_ * 2), "l"(EVICT_FIRST) : "memory");
            }
        };
        if (OE) {
            mbar_wait_sleep(bar_stg, 0);
            if (OED) __nanosleep(OED);
            const uint32_t early = rows & ((1u << (4 * OE)) - 1) & ~lds32(sb + SM_RED + 72);
            rows &= ~early;
            if (elect()) {
                asm volatile("fence.proxy.async.shared::cta;" ::: "memory");
                store_rows(early);
            }
        }
        mbar_wait_sleep(bar_out, 0);
        if (blockIdx.x == 127 && warp == 0 && lane == 0) gs->epoch[0] = tag;
        if (elect()) {
            asm volatile("fence.proxy.async.shared::cta;" ::: "memory");
            const uint2 sel = lds64(sb + SM_RED + 64);
            if ((sel.x >> 4) == rg) rows &= ~(1u << (sel.x & 15));
            if ((sel.y >> 4) == rg) rows &= ~(1u << (sel.y & 15));
            store_rows(rows);
            asm volatile("cp.async.bulk.commit_group;\ncp.async.bulk.wait_group.read 0;" ::: "memory");
        }
    } else {
        uint32_t cv[2] = {0, 0}, tag0 = 0;
        {
            uint32_t ws, t, b;
            asm volatile("mov.u32 %0, smem_raw;\nmov.u32 %1, %%tid.x;\nmov.u32 %2, %%ctaid.x;" : "=r"(ws), "=r"(t), "=r"(b));
            t -= 128;
            const uint32_t* cp = padd(reinterpret_cast<const uint32_t*>(args.cvec), (t & 0xe0) + (t & 7) * 4);
            asm volatile("{\n.reg .pred p, q, r;\nsetp.lt.u32 r, %8, 256;\nsetp.lt.and.u32 p, %9, 72, r;\nsetp.lt.and.u32 q, %8, 128, p;\n"
                         "@p ld.global.nc.u32 %0, [%5];\n@q ld.global.nc.u32 %1, [%6 + 1024];\n@r ld.global.ca.u32 %2, [%7];\n"
                         "@p cp.async.cg.shared.global [%3], [%4], 16;\n@p cp.async.cg.shared.global [%3 + 4096], [%4 + 884736], 16;\n"
                         "@p cp.async.cg.shared.global [%3 + 8192], [%4 + 1769472], 16;\n@p cp.async.cg.shared.global [%3 + 12288], [%4 + 2654208], 16;\n"
                         "@q cp.async.cg.shared.global [%3 + 16384], [%4 + 3538944], 16;\n}"
                         : "+r"(cv[0]), "+r"(cv[1]), "+r"(tag0)
                         : "r"(ws + SM_Q + SLOT + t * 16), "l"(padd(args.w_mod, (t >> 1 & 127) * (12 * D_) + (t & 1) * 16 + b * 32)),
                           "l"(padd(cp, (t & 24) * 32)), "l"(cp), "l"(padd(gs->epoch, b >> 8)), "r"(t), "r"(b) : "memory");
        }
        uint32_t tag = __shfl_sync(0xffffffffu, tag0, 0);
        asm volatile("barrier.cluster.arrive.relaxed.aligned;" ::: "memory");
        asm volatile("setmaxnreg.inc.sync.aligned.u32 240;");
        const int lane = threadIdx.x & 31;
        const int cw = warp - 4;
        const int w = cw >> 2;
        const int tid = threadIdx.x - 128;
        ROLES();
        float* red = reinterpret_cast<float*>(smem_raw + SM_RED);
        DBG_INIT();
        DBG_G(120);
        DBG_T(100);

        {
            if (blockIdx.x < 72) {
                uint32_t sa[10];
#pragma unroll
                for (int i = 0; i < 2; i++) {
                    const float lo = bf_lo(cv[i]), hi = bf_hi(cv[i]);
                    cv[i] = pack_bf16(lo * sigmoidf_(lo), hi * sigmoidf_(hi));
                }
#pragma unroll
                for (int i = 0; i < 10; i++) sa[i] = __shfl_sync(0xffffffffu, cv[i >> 3], (i & 7) * 4 + (lane & 3));
                uint2* mdst = &gs->mod1[(tid >> 3) * D_ + blockIdx.x * 8 + (tid & 7)];
                anchor(bar_full + 504, sa[0] & sa[1] & sa[2] & sa[3] & sa[4] & sa[5] & sa[6] & sa[7] & sa[8] & sa[9] & (uint32_t)(uintptr_t)mdst & (uint32_t)((uintptr_t)mdst >> 32));
                asm volatile("cp.async.wait_all;" ::: "memory");
                __syncwarp();
                const uint32_t ws = sb + SM_Q + SLOT + cw * 512 + (lane & 15) * 32 + (lane & 16);
                float d[16];
#pragma unroll
                for (int i = 0; i < 16; i++) d[i] = 0.f;
#pragma unroll
                for (int i = 0; i < 5; i++) {
                    const uint4 b = ldsm4t(ws + (i < 4 || cw < 4 ? i * 4096 : 0));
                    mma16816(d + 8 * (i & 1), sa[2 * i], sa[2 * i], sa[2 * i + 1], sa[2 * i + 1], b.x, b.y);
                    mma16816(d + 8 * (i & 1) + 4, sa[2 * i], sa[2 * i], sa[2 * i + 1], sa[2 * i + 1], b.z, b.w);
                }
                if (lane < 8) reinterpret_cast<float2*>(red)[lane * 8 + cw] = (lane & 4) ? make_float2(d[4] + d[12], d[5] + d[13]) : make_float2(d[0] + d[8], d[1] + d[9]);
                bar_sync(3, 256);
                if (tid < 8 * MREP) {
                    const float4* r = reinterpret_cast<const float4*>(red) + (tid & 7) * 4;
                    const float4 r0 = r[0], r1 = r[1], r2 = r[2], r3 = r[3];
                    st_relaxed64(mdst, pack_bf16(((r0.x + r0.z) + (r1.x + r1.z)) + ((r2.x + r2.z) + (r3.x + r3.z)),
                                                 ((r0.y + r0.w) + (r1.y + r1.w)) + ((r2.y + r2.w) + (r3.y + r3.w))), tag + 1);
                }
            }
            DBG_G(106);
            asm volatile("barrier.cluster.wait.aligned;" ::: "memory");
            mbar_wait(bar_x, 0);
            asm volatile("add.u32 %0, %0, 1;" : "+r"(tag));
            uint32_t x[20];
            float st[12], st2[12];
            rows_load(x, sb + SM_Q + (lane & 15) * XP + (lane >> 4) * 16 + cw * 32, cw);
#pragma unroll
            for (int i = 0; i < 12; i++) { st[i] = 0.f; st2[i] = 0.f; }
#pragma unroll
            for (int k = 0; k < 9; k++) stats_add((k & 1) ? st2 : st, x[2 * k], x[2 * k + 1], 0x3f803f80u);
#pragma unroll
            for (int i = 0; i < 12; i++) st[i] += st2[i];
            uint32_t mean2;
            float dot;
            const float rsd = rows_stats(st, reinterpret_cast<float4*>(red + 128), cw, lane, mean2, dot);
            const uint4* mp = reinterpret_cast<const uint4*>(gs->mod1 + ((blockIdx.x >> 1) & (MREP - 1)) * D_) + min(tid, D_ / 4 - 1);
            uint4 v0 = make_uint4(0, tag, 0, tag), v1 = v0;
            auto look = [&]() {
                asm volatile("{\n.reg .pred p;\n.reg .b64 a, b, c, d;\nsetp.lt.s32 p, %9, 5;\nmov.b64 a, {%0, %1};\nmov.b64 b, {%2, %3};\n"
                             "mov.b64 c, {%4, %5};\nmov.b64 d, {%6, %7};\n@p ld.relaxed.gpu.global.v2.b64 {a, b}, [%8];\n"
                             "@p ld.relaxed.gpu.global.v2.b64 {c, d}, [%8 + 2304];\n"
                             "mov.b64 {%0, %1}, a;\nmov.b64 {%2, %3}, b;\nmov.b64 {%4, %5}, c;\nmov.b64 {%6, %7}, d;\n}"
                             : "+r"(v0.x), "+r"(v0.y), "+r"(v0.z), "+r"(v0.w), "+r"(v1.x), "+r"(v1.y), "+r"(v1.z), "+r"(v1.w)
                             : "l"(mp), "r"(cw) : "memory");
            };
            rows_normalise(x, x, mean2, rsd, lane, look);
            fence_regs(x);
            uint32_t it = 0;
#pragma unroll 1
            while (((v0.y ^ tag) | (v0.w ^ tag) | (v1.y ^ tag) | (v1.w ^ tag)) && ++it < SPIN / 16) look();
            uint4* smod = reinterpret_cast<uint4*>(smem_raw + SM_Q + M_MOD);
            if (tid < D_ / 4) smod[tid] = make_uint4(badd2(v1.x, 0x3f803f80u), v0.x, badd2(v1.z, 0x3f803f80u), v0.z);
            uint4* hdst = g_h + (size_t)(rg * 36 + cw) * 32 + lane;
            uint2* hdst2 = reinterpret_cast<uint2*>(g_h + (size_t)(rg * 36 + 32) * 32) + tid;
            bar_sync(3, 256);
            DBG_G(107);
#pragma unroll
            for (int k = 0; k < 9; k++) {
                const uint2 cs = lds64(sb + SM_Q + M_MOD + (cw * 8 + (lane & 3) + (k < 8 ? (k >> 1) * 64 + (k & 1) * 4 : 256 - cw * 4)) * 8);
                const uint32_t c1 = cs.x, sa = cs.y;
                x[2 * k] = badd2(bmul2(x[2 * k], c1), sa);
                if (x[2 * k] == 0) x[2 * k] = 0x8000u;
                x[2 * k + 1] = badd2(bmul2(x[2 * k + 1], c1), sa);
            }
#pragma unroll
            for (int ch = 0; ch < 4; ch++) st_relaxed4(hdst + ch * 256, x[4 * ch], x[4 * ch + 1], x[4 * ch + 2], x[4 * ch + 3]);
            st_relaxed64(hdst2, x[16], x[17]);
            __syncwarp();
            if (SPARE && lane == 0) mbar_arrive(bar_pub);
            DBG_G(108);
        }

        uint32_t rel_base;
        asm("mapa.shared::cluster.u32 %0, %1, %2;" : "=r"(rel_base) : "r"(bar_empty), "r"(lane & 1));
        auto release = [&](uint32_t slot) { if (lane < 2) mbar_arrive_cluster(rel_base + 8 * slot); };
        uint32_t q[32], p[32];
        float s[64], o[64];

        const int lw = cw & 3;
        const uint32_t relw = lw == 2 && lane < 8, handw = lw == 2 || cw == 1;
        auto release4 = [&](uint32_t off, uint32_t on = 1) {
            asm volatile("{\n.reg .pred p;\nsetp.ne.b32 p, %1, 0;\n@p mbarrier.arrive.shared::cluster.b64 _, [%0];\n}" ::"r"(rel_base + off), "r"(relw & on) : "memory"); };
        auto handoff = [&](uint32_t on = 1) {
            asm volatile("{\n.reg .pred p;\nsetp.ne.b32 p, %1, 0;\n@p bar.arrive %0, 192;\n}" ::"r"(2 - w), "r"(handw & on) : "memory"); };
        if (cw == 6) bar_arrive(1, 192);

        uint4* qpark = reinterpret_cast<uint4*>(smem_raw + SM_Q - SLOT) + cw * 256 + lane;
        {
            uint32_t h[144];
            const uint4* hf = g_h + (size_t)(qb * 8 + cw) * (36 * 32) + lane;
            auto load_h = [&](auto lo, auto hi) {
#pragma unroll
                for (int ks = lo.value; ks < hi.value; ks++) {
                    const uint4 v = h_frag(hf, ks, lane);
                    h[4 * ks] = v.x; h[4 * ks + 1] = v.y; h[4 * ks + 2] = v.z; h[4 * ks + 3] = v.w;
                }
            };
            auto check_h = [&](auto lo, auto hi) {
                uint32_t it = 0;
                bool miss;
#pragma unroll 1
                do {
                    uint32_t mn = ~0u;
#pragma unroll
                    for (int ks = lo.value; ks < hi.value; ks++) mn = __vimin3_u32(mn, h[4 * ks], h[4 * ks + 2]);
                    miss = __any_sync(0xffffffffu, mn == 0);
                    if (miss) load_h(lo, hi);
                    asm volatile("add.u32 %0, %0, 1;" : "+r"(it));
                } while (miss && it < SPIN / 16);
            };
            auto check_h2 = [&](auto lo, auto hi, auto nx) {
                float f0 = __uint_as_float(~0u), f1 = f0;
                hold(f0, f1);
                auto low = [&]() {
                    uint32_t m0 = __float_as_uint(f0), m1 = m0;
#pragma unroll
                    for (int ks = lo.value; ks < hi.value; ks += 2) { m0 = __vimin3_u32(m0, h[4 * ks], h[4 * ks + 2]); m1 = __vimin3_u32(m1, h[4 * ks + 4], h[4 * ks + 6]); }
                    return min(m0, m1);
                };
                anchor(const_cast<uint4*>(hf), h[4 * hi.value - 1] & __float_as_uint(f0));
                load_h(hi, nx);
                if (__any_sync(0xffffffffu, low() == 0)) {
                    uint32_t it = 0;
#pragma unroll 1
                    do load_h(lo, hi); while (__any_sync(0xffffffffu, low() == 0) && ++it < SPIN / 16);
                }
            };
            __nanosleep(300);
            load_h(IC<0>{}, IC<4>{});
            DBG_T(104); DBG_G(109);
            mbar_wait(bar_w0, 0);
#pragma unroll
            for (int e = E0 + 1; e < E0 + 3; e++) mbar_wait(bar_full + 8 * (e & 3), e >> 2);
#pragma unroll
            for (int i = 0; i < 64; i++) o[i] = 0.f;
            auto group = [&](auto tc, auto ec) {
                constexpr int t = tc.value, e = ec.value, k0 = t ? 8 * t - 4 : 0;
                constexpr bool first = e < E0 + 5, turns = e >= E0 + 4;
                uint64_t dv = (first ? args.d0 : desc_lo(0, UNIT) | (0x40000040ull << 32)) + ((t ? 0 : 512) + (e == E0 ? 6 : e & 3) * (SLOT / 16));
                if (first && t == 0) check_h(IC<0>{}, IC<4>{});
                if (first && t >= 3) mbar_wait(bar_full + 8 * (e & 3), e >> 2);
                if (first && t > 0) check_h2(IC<k0>{}, IC<8 * t + 4>{}, IC<t < 4 ? 8 * t + 12 : 0>{});
                if (t != 1 && turns) bar_sync(1 + w, 192);
                if (t != 1 || first) WG_FENCE();
#pragma unroll
                for (int ks = k0; ks < 8 * t + 4; ks++) {
                    mma_rs128<1>(o, h[4 * ks], h[4 * ks + 1], h[4 * ks + 2], h[4 * ks + 3], dv, ks);
                    if (t && turns && ks == k0 + QSPLIT - 1) WG_COMMIT();
                }
                if (t || first) WG_COMMIT();
                if (first && t == 0) load_h(IC<4>{}, IC<12>{});
                if (t > 0) {
                    WG_WAIT(1);
                    if (turns) handoff();
                    if ((t == 1 && !first) || (t > 1 && e <= E0 + 4)) release4(8 * ((e - 1) & 3));
                    if (turns && e != 18) { WG_WAIT(0); release4(8 * (e & 3)); }
                }
            };
            auto head = [&](auto ec, int slot) {
                constexpr int e = ec.value;
                fence_regs(o);
                group(IC<0>{}, IC<e>{}); group(IC<1>{}, IC<e + 1>{}); group(IC<2>{}, IC<e + 2>{}); group(IC<3>{}, IC<e + 3>{});
                if (e == 15) return;
                group(IC<4>{}, IC<e + 4>{});
                fence_regs(o);
#pragma unroll
                for (int i = 0; i < 8; i++)
                    qpark[slot * 2048 + i * 32] = make_uint4(pack_bf16(o[8 * i], o[8 * i + 1]), pack_bf16(o[8 * i + 2], o[8 * i + 3]),
                                                             pack_bf16(o[8 * i + 4], o[8 * i + 5]), pack_bf16(o[8 * i + 6], o[8 * i + 7]));
            };
            head(IC<E0>{}, 1);
            head(IC<E0 + 5>{}, 2);
            if (SPARE) {
                float (&u)[32] = reinterpret_cast<float (&)[32]>(o);
                fence_regs(u);
#pragma unroll
                for (int t = 0; t < 2; t++) {
                    uint64_t dv = args.d0 + t * (SLOT / 16);
                    bar_sync(1 + w, 192);
                    WG_FENCE();
#pragma unroll
                    for (int ks = 0; ks < 16 + 4 * t; ks++) {
                        mma_rs64<1>(u, h[64 * t + 4 * ks], h[64 * t + 4 * ks + 1], h[64 * t + 4 * ks + 2], h[64 * t + 4 * ks + 3], dv, ks | t);
                        if (ks == 2 * QSPLIT + 4 * t - 1) WG_COMMIT();
                    }
                    WG_COMMIT();
                    WG_WAIT(1);
                    handoff();
                    WG_WAIT(0);
                    release4(8 * t);
                }
                fence_regs(u);
                release4(16);
#pragma unroll
                for (int i = 0; i < 4; i++)
                    qpark[3 * 2048 + i * 32] = make_uint4(pack_bf16(u[8 * i], u[8 * i + 1]), pack_bf16(u[8 * i + 2], u[8 * i + 3]),
                                                          pack_bf16(u[8 * i + 4], u[8 * i + 5]), pack_bf16(u[8 * i + 6], u[8 * i + 7]));
            } else {
                head(IC<10>{}, 3);
            }
            head(IC<15>{}, 0);
#pragma unroll
            for (int i = 0; i < 8; i++) {
                const uint4 v = lds128(smem_u32(qpark + 2048 + i * 32));
                q[4 * i] = v.x; q[4 * i + 1] = v.y; q[4 * i + 2] = v.z; q[4 * i + 3] = v.w;
            }
#pragma unroll
            for (int i = 0; i < 32; i++) p[i] = h[112 + i];
            WG_WAIT(0);
            fence_regs(o);
            release4(16);
        }
        DBG_T(105);
        DBG_G(125);

        uint8_t* frag = reinterpret_cast<uint8_t*>(__shfl_sync(0xffffffffu, reinterpret_cast<unsigned long long>(g_frag + (size_t)(rg * 8 + cw) * WREG + lane * 16), lane));
        const uint4* qnext = reinterpret_cast<const uint4*>(__shfl_sync(0xffffffffu, reinterpret_cast<unsigned long long>(padd(smem_raw, SM_Q + tid * 16 + cw * 3584)), lane));
        uint8_t* odst = reinterpret_cast<uint8_t*>(const_cast<uint4*>(qnext));
        qnext -= 2048;
        float m0, m1, l0 = 0.25f, l1 = 0.25f, t0, t1;
        uint32_t bad = 0;
        auto finish = [&](auto lo, auto hi, uint32_t bit, auto sink) {
#pragma unroll
            for (int i = lo.value; i < hi.value; i++) {
                const uint32_t v0 = pack_bf16(o[8 * i] * t0, o[8 * i + 1] * t0), v1 = pack_bf16(o[8 * i + 2] * t1, o[8 * i + 3] * t1);
                const uint32_t v2 = pack_bf16(o[8 * i + 4] * t0, o[8 * i + 5] * t0), v3 = pack_bf16(o[8 * i + 6] * t1, o[8 * i + 7] * t1);
                if (i == 0 && fabsf(o[0] * t0) >= 0x1p-31f) bad |= bit << 8;
                sink(i, v0, v1, v2, v3);
            }
        };
        float lq[6];
        auto row_parts = [&]() {
#pragma unroll
            for (int i = 0; i < 3; i++) { lq[i] = __shfl_xor_sync(0xffffffffu, l0, i + 1); lq[3 + i] = __shfl_xor_sync(0xffffffffu, l1, i + 1); }
        };
        auto row_sums = [&](uint32_t bit) {
            t0 = (l0 + lq[0]) + (lq[1] + lq[2]); t1 = (l1 + lq[3]) + (lq[4] + lq[5]);
            if (!(t0 >= LMIN && t0 < LMAX && t1 >= LMIN && t1 < LMAX)) bad |= bit;
        };
        auto issue_pv = [&](uint64_t dv, int acc) {
            asm volatile("{\n.reg .pred p;\nsetp.eq.b32 p, %0, 0;\n@p bar.sync 4, 160;\n}" ::"r"(w) : "memory");
#pragma unroll
            for (int ks = 0; ks < 8; ks++)
                mma_rs128<1>(o, p[4 * ks], p[4 * ks + 1], p[4 * ks + 2], p[4 * ks + 3], dv, ks ? 1 : acc);
            WG_COMMIT();
        };
#pragma unroll
        for (int i = 0; i < 64; i++) s[i] = 0.f;
        uint64_t dv_lo = args.d0;
        uint32_t voff = 0;
        auto issue_qk = [&]() {
            uint64_t dk = dv_lo ^ (desc_lo(0, UNIT) ^ desc_lo(3 * SLOT, 16));
            bar_sync(1 + w, 192);
            fence_regs(s); fence_regs(q); fence_regs(o); fence_regs(p);
            WG_FENCE();
#pragma unroll
            for (int ks = 0; ks < 8; ks++)
                if (ks == 3) mma_rs128<0, 1018>(s, q[4 * ks], q[4 * ks + 1], q[4 * ks + 2], q[4 * ks + 3], dk, 1);
                else mma_rs128<0, 2>(s, q[4 * ks], q[4 * ks + 1], q[4 * ks + 2], q[4 * ks + 3], dk, ks != 0);
            WG_COMMIT();
        };
        auto to_frag = [&](int i, uint32_t v0, uint32_t v1, uint32_t v2, uint32_t v3) {
            *reinterpret_cast<uint4*>(odst + i * 512) = make_uint4(v0, v1, v2, v3); };
        int n = 0;
        auto scores_ready = [&]() {
            WG_WAIT(1);
            fence_regs(s); fence_regs(q);
        };
        auto pass_on = [&]() {
            release4(voff ^ 24);
            handoff();
        };
#pragma unroll 1
        for (;;) {
            {
                {
                    asm volatile("st.shared.v2.f32 [%0], {%1, %2};" ::"r"(sb + SM_RED + tid * 8), "f"(l0), "f"(l1) : "memory");
                    __syncwarp();
                    const uint4 a = lds128(sb + SM_RED + (tid & ~3) * 8), b = lds128(sb + SM_RED + (tid & ~3) * 8 + 16);
                    l0 = __uint_as_float(a.x); lq[0] = __uint_as_float(a.z); lq[1] = __uint_as_float(b.x); lq[2] = __uint_as_float(b.z);
                    l1 = __uint_as_float(a.y); lq[3] = __uint_as_float(a.w); lq[4] = __uint_as_float(b.y); lq[5] = __uint_as_float(b.w);
                }
                issue_qk();
                hold(l0, l1);
                row_sums(1u << (n >> 4));
                t0 = rcp_fast(t0); t1 = rcp_fast(t1);
                l0 = 0.f; l1 = 0.f;
                odst = n ? frag + ((n >> 4) - 1) * 4096 : odst;
                qnext = n == 48 ? reinterpret_cast<const uint4*>(frag) : qnext + 2048;
                anchor(bar_full + 504, (t0 + t1) * __uint_as_float((bad ^ (uint32_t)(uintptr_t)odst ^ (uint32_t)(uintptr_t)qnext) & 0x3fffffff));
                asm volatile("{\n.reg .pred p;\nsetp.ne.b32 p, %1, 0;\n@p mbarrier.arrive.shared::cta.b64 _, [%0];\n}"
                             ::"r"(bar_qfree + (n >> 1) - 8), "r"(lane ? 0 : n) : "memory");
                issue_pv(dv_lo, 1);
                scores_ready();
                const uint32_t a = pack_bf16(fmaxf(fmaxf(s[0], s[1]), fmaxf(s[4], s[5])), fmaxf(fmaxf(s[2], s[3]), fmaxf(s[6], s[7])));
                const uint32_t b = bmax2(bmax2(a, __shfl_xor_sync(0xffffffffu, a, 1)), bmax2(__shfl_xor_sync(0xffffffffu, a, 2), __shfl_xor_sync(0xffffffffu, a, 3)));
                pass_on();
                m0 = fmaf(-CS, bf_lo(b), -POFF); m1 = fmaf(-CS, bf_hi(b), -POFF);
            }
#pragma unroll 1
            for (;;) {
                DBG_T(n);
#pragma unroll
                for (int i = 0; i < 4 * STAGE; i++) s[i] = fmaf(s[i], CS, (i & 2) ? m1 : m0);
#pragma unroll
                for (int i = 0; i < 4 * SPLIT; i++) s[i] = ex2(s[i]);
#pragma unroll
                for (int i = 0; i < SPLIT; i++) { l0 += s[4 * i] + s[4 * i + 1]; l1 += s[4 * i + 2] + s[4 * i + 3]; }
                m0 = fmaf(l0, 0.f, m0); m1 = fmaf(l1, 0.f, m1);
                anchor(bar_full + 504, l0 + l1);
                WG_WAIT(0);
                fence_regs(o); fence_regs(p);
                release4(voff);
                dv_lo ^= 2 * SLOT / 16;
                voff ^= 16;
                n++;
#pragma unroll
                for (int i = 4 * STAGE; i < 64; i++) s[i] = fmaf(s[i], CS, (i & 2) ? m1 : m0);
#pragma unroll
                for (int i = 4 * SPLIT; i < 64; i++) s[i] = ex2(s[i]);
#pragma unroll
                for (int i = SPLIT; i < 16; i++) { l0 += s[4 * i] + s[4 * i + 1]; l1 += s[4 * i + 2] + s[4 * i + 3]; }
#pragma unroll
                for (int i = 0; i < 32; i++) p[i] = pack_bf16(s[2 * i], s[2 * i + 1]);
                const int jn = n & 15;
                if (jn > 1) {
                    issue_qk();
                    if ((n & 10) == 2) {
                        if (n & 1) {
#pragma unroll
                            for (int i = 0; i < 64; i++) o[i] *= (i & 2) ? t1 : t0;
                        } else {
                            row_parts();
                            row_sums(2u << (n >> 4));
                            const uint32_t e0 = __float_as_uint(t0) >> 23, e1 = __float_as_uint(t1) >> 23;
                            m0 -= __uint_as_float(0x4b000000u | e0) - (8388608.f + 127.f - POFF);
                            m1 -= __uint_as_float(0x4b000000u | e1) - (8388608.f + 127.f - POFF);
                            t0 = __uint_as_float((254 - (int)POFF - e0) << 23); t1 = __uint_as_float((254 - (int)POFF - e1) << 23);
                            l0 *= t0; l1 *= t1;
                        }
                    }
                    fence_regs(o);
                    WG_FENCE();
                    issue_pv(dv_lo, 1);
                    scores_ready();
                    pass_on();
                    if (jn != 15) continue;
#pragma unroll
                    for (int i = 0; i < 8; i++) {
                        const uint4 v = qnext[i * 32];
                        q[4 * i] = v.x; q[4 * i + 1] = v.y; q[4 * i + 2] = v.z; q[4 * i + 3] = v.w;
                    }
                    continue;
                }
                if (jn == 0) break;
                finish(IC<0>{}, IC<ESPLIT>{}, 1u << (n >> 4), to_frag);
                issue_qk();
                hold(t0, t1);
                finish(IC<ESPLIT>{}, IC<8>{}, 1u << (n >> 4), to_frag);
                WG_FENCE();
                issue_pv(dv_lo, 0);
                scores_ready();
                pass_on();
            }
            if (n == 64) break;
        }
        DBG_T(64);
        uint32_t a1[32], a2[32];
        bar_sync(1 + w, 192);
        fence_regs(o); fence_regs(p);
        WG_FENCE();
        issue_pv(args.d0 + 3 * SLOT / 16, 1);
        handoff();
        mbar_wait(bar_mod, 0);
        const int tid_ = __shfl_sync(0xffffffffu, tid, lane);
        row_parts();
        row_sums(16);
        t0 = rcp_fast(t0); t1 = rcp_fast(t1);
        anchor(frag, q[0] & q[4] & q[8] & q[12] & q[16] & q[20] & q[24] & q[28] & __float_as_uint(t0) & __float_as_uint(t1) & tid_);
        frag_load(a1, frag + 4096);
        frag_load<0, 4>(a2, frag + 8192);
        anchor(frag, bad);
        WG_WAIT(0);
        fence_regs(o); fence_regs(p);
        release4(24);
        finish(IC<0>{}, IC<8>{}, 16, [&](int i, uint32_t v0, uint32_t v1, uint32_t v2, uint32_t v3) {
            p[4 * i] = v0; p[4 * i + 1] = v1; p[4 * i + 2] = v2; p[4 * i + 3] = v3; });
        anchor(frag, p[31] & p[15]);
        frag_load<4, 8>(a2, frag + 8192);
        bad = __reduce_or_sync(0xffffffffu, bad);
        bad = ((bad | ~(bad >> 8)) >> 1) & 15;
        if (__builtin_expect(bad != 0, 0)) {
            uint8_t* keep = g_keep + (size_t)(rg * 8 + cw) * 4096 + lane * 16;
            frag_store(keep, p);
            attn_fallback(bad, tag, gs, frag, keep, args.wq, args.kc, args.vc);
            frag_load(q, frag); frag_load(a1, frag + 4096); frag_load(a2, frag + 8192); frag_load(p, keep);
            anchor(frag, q[0] & q[4] & q[8] & q[12] & q[16] & q[20] & q[24] & q[28] & p[0] & p[4] & p[8] & p[12] & p[16] & p[20] & p[24] & p[28]);
        }
        DBG_T(80);
        DBG_G(124);

        const uint32_t eye = (tid_ >> 3 & 3) == (tid_ & 3) ? 0x3f80u << ((tid_ & 4) * 4) : 0;
        auto sum8 = [&](uint32_t* r, const uint4 (&v)[8]) {
            float d[16];
#pragma unroll
            for (int i = 0; i < 16; i++) d[i] = 0.f;
#pragma unroll
            for (int src = 0; src < 8; src++) {
                mma1688(d + 8 * (src & 1), v[src].x, v[src].y, eye);
                mma1688(d + 8 * (src & 1) + 4, v[src].z, v[src].w, eye);
            }
#pragma unroll
            for (int i = 0; i < 4; i++) r[i] = pack_bf16(d[2 * i] + d[8 + 2 * i], d[2 * i + 1] + d[9 + 2 * i]);
        };
        uint4 v2[8], v3[8], wf[23];
        uint2 u4[8], gw[9];
        uint32_t x1[20], xs, pa, ta;
        const uint8_t *mb, *mb4;
        auto load_wf = [&](auto lo, auto hi) {
            const uint32_t wa = sb + SM_Q + ((tid_ & 8) * (D_ / 8) + cw * 16 + (tid_ & 7) + (tid_ & 16) / 2) * 80;
            const uint32_t wb = wa + (512 - cw * 8) * 80 - (tid_ & 16) * 39;
#pragma unroll
            for (int i = lo.value; i < hi.value; i++) wf[i] = ldsm4t(i < 20 ? wa + (i / 5) * 10240 + (i % 5) * 16 : wb + (i - 20) * 32);
        };
        uint32_t at[18];
        {
            float (&u)[32] = reinterpret_cast<float (&)[32]>(o);
            uint32_t off = 0;
            auto turn = [&](const uint32_t (&a)[32], const uint32_t (&b)[32], int acc) {
                uint64_t dv = args.d0 + off * (SLOT / 128);
                bar_sync(1 + w, 192);
                fence_regs(u);
                WG_FENCE();
#pragma unroll
                for (int ks = 0; ks < 16; ks++) {
                    const uint32_t* f = ks < 8 ? &a[4 * ks] : &b[4 * ks - 32];
                    mma_rs64<1>(u, f[0], f[1], f[2], f[3], dv, ks | acc);
                    if (ks == OSPLIT - 1) WG_COMMIT();
                }
                WG_COMMIT();
                WG_WAIT(1);
            };
            auto done = [&]() {
                WG_WAIT(0);
                fence_regs(u);
                release4(off);
                off = (off + 8) & 24;
            };
            auto store = [&](uint8_t* dst) {
#pragma unroll
                for (int i = 0; i < 4; i++)
                    st_relaxed4(dst + i * 512, pack_bf16(u[8 * i], u[8 * i + 1]), pack_bf16(u[8 * i + 2], u[8 * i + 3]),
                                pack_bf16(u[8 * i + 4], u[8 * i + 5]), pack_bf16(u[8 * i + 6], u[8 * i + 7]));
            };
            pa = sb + w * (UNIT - 2048) + tid_ * 16;
#pragma unroll
            for (int i = 0; i < 8; i++) at[i] = 0;
            fence_regs(q); fence_regs(p);
            uint8_t* dst = frag;
#pragma unroll
            for (int i = 0; i < 8; i++) asm volatile("" : "=r"(v2[i].x), "=r"(v2[i].y), "=r"(v2[i].z), "=r"(v2[i].w));
#pragma unroll 1
            for (int k = 0; k < 8; k++, dst += 2048) {
                const uint32_t poff = (off + 8) & 24;
                const bool sum = (0xa0 >> k) & 1;
                turn(q, p, 0);
                handoff();
                auto sum_p = [&](auto lo, auto hi) {
#pragma unroll
                    for (int i = lo.value; i < hi.value; i++) {
                        float a[8], b[8];
#pragma unroll
                        for (int src = 0; src < 8; src++) {
                            const uint32_t x = i == 0 ? v2[src].x : i == 1 ? v2[src].y : i == 2 ? v2[src].z : v2[src].w;
                            a[src] = bf_lo(x); b[src] = bf_hi(x);
                        }
                        at[i] = at[4 + i];
                        at[4 + i] = pack_bf16(((a[0] + a[2]) + (a[4] + a[6])) + ((a[1] + a[3]) + (a[5] + a[7])),
                                              ((b[0] + b[2]) + (b[4] + b[6])) + ((b[1] + b[3]) + (b[5] + b[7])));
                    }
                };
                if (sum) {
                    mbar_wait(bar_full + poff, 1);
#pragma unroll
                    for (int src = 0; src < 8; src++) v2[src] = lds128(pa + poff * (SLOT / 8) + src * 2048);
                    __syncwarp();
                    release(poff >> 3);
                    done();
                    off = (off + 8) & 24;
                    sum_p(IC<0>{}, IC<2>{});
                } else {
                    done();
                }
                turn(a1, a2, 1);
                handoff();
                if (sum) sum_p(IC<2>{}, IC<4>{});
                done();
                store(dst);
                __syncwarp();
                asm volatile("{\n.reg .pred p;\nsetp.ne.b32 p, %1, 0;\n@p mbarrier.arrive.shared::cta.b64 _, [%0];\n}"
                             ::"r"(bar_pub + 4 + 4 * k), "r"(lane ? 0 : (0x2a >> k) & 1) : "memory");
            }
            turn(q, p, 0);
            handoff();
            mb = padd(g_frag, (qb * 64 + j) * WREG + 3 * 4096 + tid_ * 16);
            mb4 = padd(mb, 4096 + ((cw >> 1) - cw) * 512 + (cw & 1) * 8);
            xs = sb + (tid_ & 15) * XP + (tid_ & 16) + cw * 32;
            ta = sb + (cw * 8 + (tid_ & 3)) * 8;
#pragma unroll
            for (int k = 0; k < 9; k++) {
                gw[k] = lds64(ta + SM_T + (k < 8 ? (k >> 1) * 64 + (k & 1) * 4 : 256 - cw * 4) * 8);
                if (!(tid_ & 4)) gw[k].y = 0x3f803f80u;
            }
            mbar_wait(bar_g, 0);
            if (T_X) mbar_wait(bar_full, 0);
            done();
            if (T_X) rows_load(x1, xs, cw);
            load_wf(IC<0>{}, IC<WF0>{});
            turn(a1, a2, 1);
            if (w == 0) handoff();
            done();
            store(dst);
            if (!T_X) { mbar_wait(bar_full, 0); rows_load(x1, xs, cw); }
            if (w == 0) bar_sync(5, 256); else bar_arrive(5, 256);
        }
        DBG_T(81);
        DBG_G(122);

        {
        const int tid = tid_, lane = tid & 31;
        const int g8 = lane >> 2, qd = lane & 3, l16 = lane & 15;
        uint32_t h2[18], gb[9], k1, k2;
        float4* rec = reinterpret_cast<float4*>(red + 128);
        const uint2* candp = reinterpret_cast<const uint2*>(padd(g_cand, ((blockIdx.x & (CREP - 1)) * NCTA + (tid >> 1)) * 32 + (tid & 1) * 8));
        uint2 cd;
        auto stage_out = [&]() {
#pragma unroll
            for (int k = 0; k < 9; k++) {
                x1[2 * k] = badd2(x1[2 * k], bmul2(gb[k], h2[2 * k]));
                x1[2 * k + 1] = badd2(x1[2 * k + 1], bmul2(gb[k], h2[2 * k + 1]));
            }
#pragma unroll
            for (int ch = 0; ch < 4; ch++) stsm_x4(xs + ch * 256, x1[4 * ch], x1[4 * ch + 1], x1[4 * ch + 2], x1[4 * ch + 3]);
            asm volatile("stmatrix.sync.aligned.m8n8.x2.shared.b16 [%0], {%1, %2};" ::"r"(xs + 1024 - cw * 16), "r"(x1[16]), "r"(x1[17]) : "memory");
        };
        {
            uint32_t it = 0, miss;
            mbar_wait(bar_full + 8, 0);
            if (T_B) mbar_wait(bar_full + 16, 0);
#pragma unroll
            for (int src = 0; src < 8; src++) v2[src] = lds128(pa + SLOT + src * 2048);
#pragma unroll
            for (int src = 0; src < 8 * T_B; src++) v3[src] = lds128(pa + 2 * SLOT + src * 2048);
            sum8(at + 8, v2);
            float st[12];
#pragma unroll
            for (int i = 0; i < 12; i++) st[i] = 0.f;
            auto add_pair = [&](int k) {
                x1[2 * k] = badd2(x1[2 * k], bmul2(gw[k].x, at[2 * k]));
                x1[2 * k + 1] = badd2(x1[2 * k + 1], bmul2(gw[k].x, at[2 * k + 1]));
                stats_add(st, x1[2 * k], x1[2 * k + 1], gw[k].y);
            };
#pragma unroll
            for (int k = 0; k < 6; k++) add_pair(k);
            if (!T_B) mbar_wait(bar_full + 16, 0);
#pragma unroll
            for (int src = 0; src < 8 * !T_B; src++) v3[src] = lds128(pa + 2 * SLOT + src * 2048);
            miss = __vimax3_u32(__vimax3_u32(v3[0].x, v3[0].z, v3[1].x), __vimax3_u32(v3[1].z, v3[2].x, v3[2].z), __vimax3_u32(v3[3].x, v3[3].z, v3[4].x));
            miss = __vimax3_u32(miss, __vimax3_u32(v3[4].z, v3[5].x, v3[5].z), max(__vimax3_u32(v3[6].x, v3[6].z, v3[7].x), v3[7].z));
            if (!T_C || __any_sync(0xffffffffu, miss == ~0u))
#pragma unroll 1
            do {
                miss = 0;
#pragma unroll
                for (int src = 0; src < 8; src++) reload16(v3[src], mb + (size_t)src * 8 * WREG, miss);
            } while (__any_sync(0xffffffffu, miss) && ++it < SPIN / 16);
            if (lane < 4) mbar_arrive_cluster(rel_base + 8 * (1 + (lane >> 1)));
            sum8(at + 12, v3);
            add_pair(6); add_pair(7);
            load_wf(IC<WF0>{}, IC<WF1>{});
            uint2 cs[9];
#pragma unroll
            for (int k = 0; k < 9; k++) cs[k] = lds64(ta + SM_TC + (k < 8 ? (k >> 1) * 64 + (k & 1) * 4 : 256 - cw * 4) * 8);
            mbar_wait(bar_pre, 0);
            mbar_wait(bar_full + 24, 0);
#pragma unroll
            for (int src = 0; src < 8; src++) u4[src] = lds64(sb + 3 * SLOT + src * 2048 + (cw >> 1) * 512 + lane * 16 + (cw & 1) * 8);
            miss = __vimax3_u32(__vimax3_u32(u4[0].x, u4[1].x, u4[2].x), __vimax3_u32(u4[3].x, u4[4].x, u4[5].x), max(u4[6].x, u4[7].x));
            if (!T_C || __any_sync(0xffffffffu, miss == ~0u))
#pragma unroll 1
            do {
                miss = 0;
#pragma unroll
                for (int src = 0; src < 8; src++) reload8(u4[src], mb4 + (size_t)src * 8 * WREG, miss);
            } while (__any_sync(0xffffffffu, miss) && ++it < SPIN / 16);
            float d[8] = {0.f, 0.f, 0.f, 0.f, 0.f, 0.f, 0.f, 0.f};
#pragma unroll
            for (int i = 0; i < 4; i++) mma16816(d + 4 * (i & 1), u4[2 * i].x, u4[2 * i].y, u4[2 * i + 1].x, u4[2 * i + 1].y, eye, eye);
            at[16] = pack_bf16(d[0] + d[4], d[1] + d[5]); at[17] = pack_bf16(d[2] + d[6], d[3] + d[7]);
            add_pair(8);
            DBG_G(123);
            const float2 ws = *reinterpret_cast<const float2*>(smem_raw + SM_TS);
            uint4* cdst = padd(g_cand, (tid * NCTA + rg) * 32);
            uint32_t mean2;
            float dot;
            const float rsd = rows_stats(st, rec, cw, lane, mean2, dot);
            const uint32_t b = __float_as_uint(fmaf(fmaf(-bf_lo(mean2), ws.x, dot), rsd, ws.y));
            const uint32_t key = (((b & 0x80000000u) ? ~b : (b | 0x80000000u)) | 2047u) - (rg * 16 + l16);
            top2(key, k1, k2);
            if (tid < CREP) st_relaxed(cdst, k1, tag, k2, tag);
            cd = ld_relaxed64(candp);
            rows_normalise(h2, x1, mean2, rsd, lane, [&]() {
#pragma unroll
                for (int k = 0; k < 9; k++) gb[k] = lds32(sb + SM_TG + (cw * 8 + qd + (k < 8 ? (k >> 1) * 64 + (k & 1) * 4 : 256 - cw * 4)) * 4);
                load_wf(IC<WF1>{}, IC<WF2>{});
            });
#pragma unroll
            for (int k = 0; k < 18; k++) h2[k] = badd2(bmul2(h2[k], cs[k >> 1].x), cs[k >> 1].y);
            const uint32_t r1 = ~k1 & 15, r2 = ~k2 & 15;
            uint32_t todo = ((r1 & 7) == g8) | ((r2 & 7) == g8) << 1;
#pragma unroll 1
            while (todo) {
                const bool second = !(todo & 1), hi = (second ? r2 : r1) & 8;
                uint4* dst = padd(g_rows, ((rg * 2 + second) * RSLOT + cw * 24 + qd) * 16);
                uint32_t r[18];
#pragma unroll
                for (int k = 0; k < 9; k++) { r[k] = hi ? h2[2 * k + 1] : h2[2 * k]; r[9 + k] = hi ? x1[2 * k + 1] : x1[2 * k]; }
                fence_regs(r);
                st_relaxed(dst, r[0], r[1], r[2], r[3]);
                st_relaxed(dst + 8, r[4], r[5], r[6], r[7]);
                st_relaxed64(reinterpret_cast<uint2*>(padd(dst, 256 - qd * 8)), r[8], r[17]);
                st_relaxed(dst + 4, r[9], r[10], r[11], r[12]);
                st_relaxed(dst + 12, r[13], r[14], r[15], r[16]);
                todo &= todo - 1;
            }
            __syncwarp();

            stage_out();
            if (OE) {
                __syncwarp();
                if (lane == 0) { reinterpret_cast<uint32_t*>(red)[18] = (1u << r1) | (1u << r2); mbar_arrive(bar_stg); }
            }
        }
        DBG_G(110);
        float4* part = reinterpret_cast<float4*>(smem_raw + 3 * SLOT + UNIT + 8192);
        bf16* act = reinterpret_cast<bf16*>(smem_raw + 3 * SLOT + UNIT + 4096);
        {
            uint32_t it = 0;
            const bool own = (tid >> 1) == rg;
            const uint32_t ks = sb + 3 * SLOT + UNIT + 5120;
#pragma unroll 1
            while (T_U ? __any_sync(0xffffffffu, cd.y != tag && !own) && ++it < SPIN / 16 : cd.y != tag && !own && ++it < SPIN / 16) {
                if (T_U) asm volatile("{\n.reg .pred p;\n.reg .b64 u;\nsetp.ne.u32 p, %1, %3;\nmov.b64 u, {%0, %1};\n"
                             "@p ld.relaxed.gpu.global.b64 u, [%2];\nmov.b64 {%0, %1}, u;\n}" : "+r"(cd.x), "+r"(cd.y) : "l"(candp), "r"(tag) : "memory");
                else cd = ld_relaxed64(candp);
            }
            asm volatile("st.shared.u32 [%0], %1;" ::"r"(ks + tid * 4), "r"(own ? (tid & 1) ? k2 : k1 : cd.x) : "memory");
            bar_sync(3, 256);
            DBG_G(111);
            const uint4 a = lds128(ks + lane * 16), b = lds128(ks + 512 + lane * 16);
            const uint32_t a1 = max(a.x, a.z), a2 = __vimax3_u32(min(a.x, a.z), a.y, a.w);
            const uint32_t b1 = max(b.x, b.z), b2 = __vimax3_u32(min(b.x, b.z), b.y, b.w);
            const uint32_t c1 = max(a1, b1), c2 = __vimax3_u32(min(a1, b1), a2, b2);
            k1 = __reduce_max_sync(0xffffffffu, c1);
            k2 = __reduce_max_sync(0xffffffffu, c1 == k1 ? c2 : c1);
        }
        const int sel0 = ~k1 & 2047, sel1 = ~k2 & 2047;
        const uint32_t slot0 = (sel0 >> 4) * 2, slot1 = (sel1 >> 4) * 2 + ((sel0 ^ sel1) < 16);
        uint4 da[13];
        {
            const uint4* hp = padd(g_rows, (((g8 & 1) ? slot1 : slot0) * RSLOT + cw * 24 + qd) * 16);
            const uint2* hp2 = reinterpret_cast<const uint2*>(padd(hp, 256 - qd * 8));
            uint4 hv[2] = {ld_relaxed2(hp), ld_relaxed2(hp + 8)};
            uint2 hw = ld_relaxed64(hp2);
            if (tid == 255) {
                reinterpret_cast<int2*>(red)[8] = make_int2(sel0, sel1);
                mbar_arrive(bar_out);
            }
            load_wf(IC<WF2>{}, IC<23>{});
            mbar_wait(bar_full + 8, 1);
            mbar_wait(bar_full + 16, 1);
            auto load_d = [&](auto lo, auto hi) {
                const int r = (lane & 7) + (lane & 16) / 2;
                const uint32_t d0 = sb + SLOT + r * XP + cw * 144 + (lane & 8) * 2, d1 = d0 + (r < 2 ? 16 * XP : SLOT - 2 * XP);
                const uint32_t d2 = sb + 2 * SLOT + (14 + (lane & 3)) * XP + cw * 144 + (lane >> 3) * 16;
#pragma unroll
                for (int i = lo.value; i < hi.value; i++) da[i] = ldsm4t(i < 10 ? ((i & 1) ? d1 : d0) + (i >> 1) * 32 : d2 + (i - 10) * 64);
            };
            load_d(IC<0>{}, IC<DL>{});
            uint32_t it = 0, miss;
            float f0 = 1.f, f1 = 1.f;
            hold(f0, f1);
            if (!T_C || __any_sync(0xffffffffu, max(__vimax3_u32(__vimax3_u32(__float_as_uint(f0), hv[0].x, hv[0].z), hv[1].x, hv[1].z), hw.x) == ~0u))
#pragma unroll 1
            do {
                miss = 0;
                reload16(hv[0], hp, miss);
                reload16(hv[1], hp + 8, miss);
                reload8(hw, hp2, miss);
            } while (__any_sync(0xffffffffu, miss) && ++it < SPIN / 16);
            DBG_G(112);
            if (!T_D) load_d(IC<DL>{}, IC<13>{});
            float acc[20];
#pragma unroll
            for (int i = 0; i < 20; i++) acc[i] = 0.f;
#pragma unroll
            for (int i = 0; i < 5; i++) mma1688(acc + 4 * i, (i & 1) ? wf[20 + i / 2].z : wf[20 + i / 2].x, (i & 1) ? wf[20 + i / 2].w : wf[20 + i / 2].y, hw.x);
#pragma unroll
            for (int i = 0; i < 20; i++)
                mma16816(acc + 4 * (i % 5), wf[i].x, wf[i].y, wf[i].z, wf[i].w, (i / 5 & 1) ? hv[i / 10].z : hv[i / 10].x, (i / 5 & 1) ? hv[i / 10].w : hv[i / 10].y);
            if (qd == 0) {
#pragma unroll
                for (int i = 0; i < 5; i++) part[cw * 40 + i * 8 + g8] = make_float4(acc[4 * i], acc[4 * i + 1], acc[4 * i + 2], acc[4 * i + 3]);
            }
            if (T_D) load_d(IC<DL>{}, IC<13>{});
        }
        {
            uint2* dst = padd(g_ypart, ((cw * 9 * NCTA + blockIdx.x) * 8 + g8) * 8);
            bar_sync(3, 256);
            if (cw < 5) {
                const float* pp = reinterpret_cast<const float*>(part) + ((blockIdx.x & 1) << 4) + tid;
                const float g = rbf(((pp[0] + pp[160]) + (pp[320] + pp[480])) + ((pp[640] + pp[800]) + (pp[960] + pp[1120])));
                const float v = rbf(g * sigmoidf_(g)) * __shfl_down_sync(0xffffffffu, g, 2);
                if (!(tid & 2)) act[(tid & 1) * 56 + (tid >> 2)] = __float2bfloat16_rn(tid < 144 ? v : 0.f);
            }
            bar_sync(3, 256);
            DBG_G(113);
            const uint32_t ap = sb + 3 * SLOT + UNIT + 4096 + (lane & 1) * 112 + (lane >> 3) * 16;
            const uint4 b0 = ldsm4(ap);
            const uint32_t b1 = lds32(sb + 3 * SLOT + UNIT + 4096 + (g8 & 1) * 112 + 64 + qd * 4);
            float y[20];
#pragma unroll
            for (int i = 0; i < 20; i++) y[i] = 0.f;
#pragma unroll
            for (int i = 0; i < 5; i++) {
                mma16816(y + 4 * i, da[2 * i].x, da[2 * i].y, da[2 * i].z, da[2 * i].w, b0.x, b0.y);
                mma16816(y + 4 * i, da[2 * i + 1].x, da[2 * i + 1].y, da[2 * i + 1].z, da[2 * i + 1].w, b0.z, b0.w);
                mma1688(y + 4 * i, (i & 1) ? da[10 + i / 2].z : da[10 + i / 2].x, (i & 1) ? da[10 + i / 2].w : da[10 + i / 2].y, b1);
            }
            if (qd == 0) {
#pragma unroll
                for (int i = 0; i < 9; i++)
                    asm volatile("st.relaxed.gpu.global.v2.f32 [%0], {%1, %2};" ::"l"(dst + i * (NCTA * 8)), "f"(y[2 * i]), "f"(y[2 * i + 1]) : "memory");
            }
        }
        DBG_G(114);
        if (blockIdx.x < 72) {
            const int G = blockIdx.x, tok = g8 & 1, cp = G * 4 + qd;
            const uint2* src = padd(g_ypart, (blockIdx.x * NCTA * 8 + tid) * 8);
            if (RD) __nanosleep(RD);
            const uint8_t* hsrc = reinterpret_cast<const uint8_t*>(padd(g_rows, (tok ? slot1 : slot0) * (RSLOT * 16) +
                (G < 64 ? (G >> 1 & 7) * 384 + (G >> 5) * 128 + qd * 16 + (G >> 1 & 8) + (G & 1) * 4 : (G - 64) * 384 + 256 + qd * 8)));
            const uint8_t* xsrc = hsrc + (G < 64 ? 64 : 4);
            uint32_t* dst = padd(reinterpret_cast<uint32_t*>(args.out), (tok ? sel1 : sel0) * (D_ * 2) + cp * 4);
            const uint32_t gb = reinterpret_cast<const uint32_t*>(smem_raw + SM_TG)[cp];
            const uint32_t ksel = ((tok ? k2 : k1) & ~2047u) | 1024u;
            const float sg = sigmoidf_(rbf(__uint_as_float((ksel & 0x80000000u) ? (ksel & 0x7fffffffu) : ~ksel)));
            uint2 v[4];
            uint32_t hv = 0, xv = 0, it = 0, miss;
            if (cw == 0) { hv = ld_relaxed32(hsrc); xv = ld_relaxed32(xsrc); }
#pragma unroll
            for (int i = 0; i < 4; i++) v[i] = make_uint2(~0u, 0);
#pragma unroll 1
            do {
#pragma unroll
                for (int i = 0; i < 4; i++) reload8(v[i], src + i * 256, miss);
                if (RP > 1) __nanosleep(RP);
            } while (__any_sync(0xffffffffu, max(__vimax3_u32(v[0].x, v[1].x, v[2].x), v[3].x) == ~0u) && ++it < SPIN / 16);
#pragma unroll 1
            while (max(hv, xv) == ~0u && ++it < SPIN / 16) { hv = ld_relaxed32(hsrc); xv = ld_relaxed32(xsrc); }
            __syncwarp();
            float y0 = (__uint_as_float(v[0].x) + __uint_as_float(v[1].x)) + (__uint_as_float(v[2].x) + __uint_as_float(v[3].x));
            float y1 = (__uint_as_float(v[0].y) + __uint_as_float(v[1].y)) + (__uint_as_float(v[2].y) + __uint_as_float(v[3].y));
            y0 += __shfl_xor_sync(0xffffffffu, y0, 8); y1 += __shfl_xor_sync(0xffffffffu, y1, 8);
            y0 += __shfl_xor_sync(0xffffffffu, y0, 16); y1 += __shfl_xor_sync(0xffffffffu, y1, 16);
            if (lane < 8) reinterpret_cast<float2*>(rec)[cw * 8 + lane] = make_float2(y0, y1);
            bar_sync(3, 256);
            if (cw == 0) {
                const float4 t0_ = rec[(lane >> 3) * 4 + qd], t1_ = rec[16 + (lane >> 3) * 4 + qd];
                y0 = tok ? t0_.y + t1_.y : t0_.x + t1_.x; y1 = tok ? t0_.w + t1_.w : t0_.z + t1_.z;
                y0 += __shfl_xor_sync(0xffffffffu, y0, 8); y1 += __shfl_xor_sync(0xffffffffu, y1, 8);
                y0 += __shfl_xor_sync(0xffffffffu, y0, 16); y1 += __shfl_xor_sync(0xffffffffu, y1, 16);
                const uint32_t y2 = bmul2(pack_bf16(y0, y1), pack_bf16(sg, sg));
                if (lane < 8) *dst = badd2(xv, bmul2(gb, badd2(hv, y2)));
            }
        }
        }
        DBG_T(88);
        DBG_G(121);
    }
}

typedef CUresult (*EncodeFn)(CUtensorMap*, CUtensorMapDataType, cuuint32_t, void*, const cuuint64_t*, const cuuint64_t*,
                             const cuuint32_t*, const cuuint32_t*, CUtensorMapInterleave, CUtensorMapSwizzle,
                             CUtensorMapL2promotion, CUtensorMapFloatOOBfill);

static void make_map(EncodeFn enc, CUtensorMap* m, const void* ptr, int rank, const cuuint64_t* dims,
                     const cuuint64_t* strides, const cuuint32_t* box, CUtensorMapSwizzle sw = CU_TENSOR_MAP_SWIZZLE_128B,
                     CUtensorMapDataType dt = CU_TENSOR_MAP_DATA_TYPE_BFLOAT16) {
    const cuuint32_t es[3] = {1, 1, 1};
    enc(m, dt, rank, const_cast<void*>(ptr), dims, strides, box, es,
        CU_TENSOR_MAP_INTERLEAVE_NONE, sw, CU_TENSOR_MAP_L2_PROMOTION_L2_128B,
        CU_TENSOR_MAP_FLOAT_OOB_FILL_NONE);
}

extern "C" void kernel_launch(void* const* d_in, const int* in_sizes, int n_in, void* d_out, int out_size) {
    const bf16* x = (const bf16*)d_in[0];
    const bf16* kc = (const bf16*)d_in[1];
    const bf16* vc = (const bf16*)d_in[2];
    const bf16* wq = (const bf16*)d_in[3];
    const bf16* wo = (const bf16*)d_in[4];
    const bf16* w_r = (const bf16*)d_in[6];
    const bf16* w_gate = (const bf16*)d_in[7];
    const bf16* w_up = (const bf16*)d_in[8];
    const bf16* w_down = (const bf16*)d_in[9];
    const bf16* cvec = (const bf16*)d_in[10];
    const bf16* w_mod = (const bf16*)d_in[11];
    bf16* out = (bf16*)d_out;

    void* fn = nullptr;
    cudaDriverEntryPointQueryResult qr;
    cudaGetDriverEntryPoint("cuTensorMapEncodeTiled", &fn, cudaEnableDefault, &qr);
    EncodeFn enc = (EncodeFn)fn;
    void* p_s;
    cudaGetSymbolAddress(&p_s, g_s);

    CUtensorMap tm_wq, tm_k, tm_v, tm_wo, tm_p, tm_x, tm_d, tm_g, tm_u;
    { cuuint64_t d[2] = {QD, D_}, s[1] = {QD * 2}; cuuint32_t b[2] = {64, 128}; make_map(enc, &tm_wq, wq, 2, d, s, b); }
    { cuuint64_t d[2] = {DH, HKV * S_}, s[1] = {DH * 2}; cuuint32_t b[2] = {64, 128};
      make_map(enc, &tm_k, kc, 2, d, s, b); make_map(enc, &tm_v, vc, 2, d, s, b); }
    { cuuint64_t d[2] = {D_, QD}, s[1] = {D_ * 2}; cuuint32_t b[2] = {64, 128}; make_map(enc, &tm_wo, wo, 2, d, s, b); }
    { cuuint64_t d[3] = {256, 160, NCTA}, s[2] = {1024, 8 * WREG}; cuuint32_t b[3] = {256, 2, 8};
      make_map(enc, &tm_p, ((Scratch*)p_s)->frag, 3, d, s, b, CU_TENSOR_MAP_SWIZZLE_NONE, CU_TENSOR_MAP_DATA_TYPE_UINT32); }
    { cuuint64_t d[2] = {D_ / 4, S_}, s[1] = {D_ * 2}; cuuint32_t b[2] = {XP / 8, 16};
      make_map(enc, &tm_x, x, 2, d, s, b, CU_TENSOR_MAP_SWIZZLE_NONE, CU_TENSOR_MAP_DATA_TYPE_UINT64); }
    { cuuint64_t d[2] = {D_ / 4, F_}, s[1] = {D_ * 2}; cuuint32_t b[2] = {XP / 8, 18};
      make_map(enc, &tm_d, w_down, 2, d, s, b, CU_TENSOR_MAP_SWIZZLE_NONE, CU_TENSOR_MAP_DATA_TYPE_UINT64); }
    { cuuint64_t d[2] = {F_, D_}, s[1] = {F_ * 2}; cuuint32_t b[2] = {40, 24};
      make_map(enc, &tm_g, w_gate, 2, d, s, b, CU_TENSOR_MAP_SWIZZLE_NONE); make_map(enc, &tm_u, w_up, 2, d, s, b, CU_TENSOR_MAP_SWIZZLE_NONE); }

    cudaFuncSetAttribute(fused_kernel<true>, cudaFuncAttributeMaxDynamicSharedMemorySize, SM_TOTAL);
    cudaFuncSetAttribute(fused_kernel<false>, cudaFuncAttributeMaxDynamicSharedMemorySize, SM_TOTAL);
    cudaLaunchConfig_t cfg = {};
    cfg.gridDim = NCTA + 4; cfg.blockDim = 384; cfg.dynamicSmemBytes = SM_TOTAL;
    cudaLaunchAttribute at;
    at.id = cudaLaunchAttributeClusterDimension; at.val.clusterDim.x = 2; at.val.clusterDim.y = 1; at.val.clusterDim.z = 1;
    cfg.attrs = &at; cfg.numAttrs = 1;
    int ncl = 0;
    if (cudaOccupancyMaxActiveClusters(&ncl, fused_kernel<true>, &cfg) != cudaSuccess) { ncl = 0; cudaGetLastError(); }
    Args args{w_mod, cvec, (Scratch*)p_s, desc_lo(0, UNIT) | (0x40000040ull << 32), out, x, kc, vc, wq, wo, w_r, w_down};
    if (USE_SPARE && ncl >= NCTA / 2 + 2)
        fused_kernel<true><<<NCTA + 4, 384, SM_TOTAL>>>(args, tm_wq, tm_k, tm_v, tm_wo, tm_p, tm_x, tm_d, tm_g, tm_u);
    else
        fused_kernel<false><<<NCTA, 384, SM_TOTAL>>>(args, tm_wq, tm_k, tm_v, tm_wo, tm_p, tm_x, tm_d, tm_g, tm_u);
}
```

```cpp
#include <cuda_runtime.h>
#include <cuda_bf16.h>
#include <cuda.h>
#include <stdint.h>
#include <math.h>

typedef __nv_bfloat16 bf16;

constexpr int S_ = 2048;
constexpr int D_ = 576;
constexpr int HQ = 32, HKV = 16, DH = 128;
constexpr int F_ = 4608;
constexpr int QD = HQ * DH;

constexpr int NCTA = 128;
constexpr int WREG = 5 * 4096;
constexpr int CREP = 8;
constexpr int RSLOT = 192;
constexpr int MREP = 4;
struct Scratch {
    unsigned int epoch[128];
    unsigned int flag_mod[NCTA];
    unsigned int flag_part[16 * 32];
    unsigned int flag_q3[16 * 32];
    unsigned int flag_h[NCTA * 32];
    uint2 mod1[MREP * D_];
    uint32_t mod2[4 * D_];
    uint4 cand[CREP * NCTA * 2];
    uint2 ypart[72 * NCTA * 8];
    uint4 h[2][NCTA * 36 * 32];
    uint4 q3[NCTA * 8 * 128];
    uint4 rows[NCTA * 2 * RSLOT];
    uint8_t frag[NCTA * 8 * WREG];
    uint8_t keep[NCTA * 8 * 4096];
};
__device__ __align__(1024) Scratch g_s;
#define g_h gs->h[tag & 1]
#define g_q3 gs->q3
#define g_keep gs->keep
#define g_flag_h gs->flag_h
#define g_flag_part gs->flag_part
#define g_flag_mod gs->flag_mod
#define g_flag_q3 gs->flag_q3
#define g_frag gs->frag
#define g_cand gs->cand
#define g_ypart gs->ypart
#define g_rows gs->rows

#define DBG_INIT()
#define DBG_P(i)
#define DBG_PG(i)
#define DBG_T(i)
#define DBG_G(i)

__device__ __forceinline__ uint32_t pack_bf16(float lo, float hi) {
    uint32_t r;
    asm("cvt.rn.bf16x2.f32 %0, %1, %2;" : "=r"(r) : "f"(hi), "f"(lo));
    return r;
}
__device__ __forceinline__ float rbf(float x) { return __uint_as_float(pack_bf16(0.f, x)); }
__device__ __forceinline__ float bf_lo(uint32_t v) { return __uint_as_float(v << 16); }
__device__ __forceinline__ float bf_hi(uint32_t v) { return __uint_as_float(v & 0xffff0000u); }
__device__ __forceinline__ float ex2(float x) {
    float y;
    asm("ex2.approx.ftz.f32 %0, %1;" : "=f"(y) : "f"(x));
    return y;
}
template <class T>
__device__ __forceinline__ T* padd(T* p, uint32_t off) {
    unsigned long long r;
    asm("{\n.reg .b32 l, h;\nmov.b64 {l, h}, %1;\nadd.cc.u32 l, l, %2;\naddc.u32 h, h, 0;\nmov.b64 %0, {l, h};\n}" : "=l"(r) : "l"(p), "r"(off));
    return reinterpret_cast<T*>(r);
}
__device__ __forceinline__ uint32_t smem_u32(const void* p) { return (uint32_t)__cvta_generic_to_shared(p); }
__device__ __forceinline__ void mbar_init(uint32_t bar, uint32_t cnt) {
    asm volatile("mbarrier.init.shared::cta.b64 [%0], %1;" ::"r"(bar), "r"(cnt) : "memory");
}
__device__ __forceinline__ void mbar_expect_tx(uint32_t bar, uint32_t bytes) {
    asm volatile("mbarrier.arrive.expect_tx.shared::cta.b64 _, [%0], %1;" ::"r"(bar), "r"(bytes) : "memory");
}
__device__ __forceinline__ void mbar_arrive(uint32_t bar) {
    asm volatile("mbarrier.arrive.shared::cta.b64 _, [%0];" ::"r"(bar) : "memory");
}
__device__ __forceinline__ void mbar_arrive_cluster(uint32_t cluster_addr) {
    asm volatile("mbarrier.arrive.shared::cluster.b64 _, [%0];" ::"r"(cluster_addr) : "memory");
}
constexpr uint32_t SPIN = 1u << 20;
__device__ __forceinline__ void mbar_wait(uint32_t bar, uint32_t parity) {
    asm volatile("{\n.reg .pred p;\n.reg .b32 c;\nmov.b32 c, 0;\n"
                 "W_%=:\nmbarrier.try_wait.parity.shared::cta.b64 p, [%0], %1;\n"
                 "add.u32 c, c, 1;\nsetp.lt.and.u32 p, c, 0x100000, !p;\n@p bra W_%=;\n}"
                 ::"r"(bar), "r"(parity) : "memory");
}
__device__ __forceinline__ void anchor(uint32_t addr, float v) {
    asm volatile("{\n.reg .pred p;\nsetp.lt.f32 p, %1, 0f00000000;\n@p st.volatile.shared.f32 [%0], %1;\n}" ::"r"(addr), "f"(v) : "memory");
}
__device__ __forceinline__ void anchor(uint32_t addr, uint32_t v) {
    asm volatile("{\n.reg .pred p;\nsetp.eq.u32 p, %1, 0xffffffff;\n@p st.volatile.shared.u32 [%0], %1;\n}" ::"r"(addr), "r"(v) : "memory");
}
__device__ __forceinline__ void anchor(void* p, uint32_t v) {
    asm volatile("{\n.reg .pred p;\nsetp.eq.u32 p, %1, 0xffffffff;\n@p st.volatile.u32 [%0], %1;\n}" ::"l"(p), "r"(v) : "memory");
}
__device__ __forceinline__ void hold(float& a, float& b) {
    asm volatile("{\n.reg .pred p;\n.reg .b64 t;\n.reg .b32 l, h;\nmov.u64 t, %%clock64;\nmov.b64 {l, h}, t;\nsetp.eq.u32 p, h, 0xffffffff;\n"
                 "@p mov.f32 %0, 0f00000000;\n@p mov.f32 %1, 0f00000000;\n}" : "+f"(a), "+f"(b) :: "memory");
}
__device__ __forceinline__ void mbar_wait_sleep(uint32_t bar, uint32_t parity) {
    asm volatile("{\n.reg .pred p;\n.reg .b32 c;\nmov.b32 c, 0;\n"
                 "W_%=:\nmbarrier.try_wait.parity.shared::cta.b64 p, [%0], %1, 5000;\n"
                 "add.u32 c, c, 1;\nsetp.lt.and.u32 p, c, 0x20000, !p;\n@p bra W_%=;\n}"
                 ::"r"(bar), "r"(parity) : "memory");
}
__device__ __forceinline__ uint32_t load_tag(const Scratch* gs) {
    uint32_t tag;
    asm volatile("ld.global.ca.u32 %0, [%1];" : "=r"(tag) : "l"(gs->epoch) : "memory");
    return tag + 1;
}
__device__ __forceinline__ uint4 ld_relaxed(const uint4* p) {
    uint4 v;
    asm volatile("ld.relaxed.gpu.global.v4.u32 {%0,%1,%2,%3}, [%4];" : "=r"(v.x), "=r"(v.y), "=r"(v.z), "=r"(v.w) : "l"(p) : "memory");
    return v;
}
__device__ __forceinline__ void st_relaxed(uint4* p, uint32_t a, uint32_t b, uint32_t c, uint32_t d) {
    asm volatile("{\n.reg .b64 u, v;\nmov.b64 u, {%1, %2};\nmov.b64 v, {%3, %4};\nst.relaxed.gpu.global.v2.b64 [%0], {u, v};\n}"
                 ::"l"(p), "r"(a), "r"(b), "r"(c), "r"(d) : "memory");
}
__device__ __forceinline__ void st_relaxed4(void* p, uint32_t a, uint32_t b, uint32_t c, uint32_t d) {
    asm volatile("st.relaxed.gpu.global.v4.u32 [%0], {%1, %2, %3, %4};" ::"l"(p), "r"(a), "r"(b), "r"(c), "r"(d) : "memory");
}
__device__ __forceinline__ uint2 ld_relaxed64(const uint2* p) {
    uint2 v;
    asm volatile("{\n.reg .b64 u;\nld.relaxed.gpu.global.b64 u, [%2];\nmov.b64 {%0, %1}, u;\n}" : "=r"(v.x), "=r"(v.y) : "l"(p) : "memory");
    return v;
}
__device__ __forceinline__ void st_relaxed64(uint2* p, uint32_t a, uint32_t b) {
    asm volatile("{\n.reg .b64 u;\nmov.b64 u, {%1, %2};\nst.relaxed.gpu.global.b64 [%0], u;\n}" ::"l"(p), "r"(a), "r"(b) : "memory");
}
__device__ __forceinline__ uint4 ld_relaxed2(const uint4* p) {
    uint4 v;
    asm volatile("{\n.reg .b64 u, w;\nld.relaxed.gpu.global.v2.b64 {u, w}, [%4];\nmov.b64 {%0, %1}, u;\nmov.b64 {%2, %3}, w;\n}"
                 : "=r"(v.x), "=r"(v.y), "=r"(v.z), "=r"(v.w) : "l"(p) : "memory");
    return v;
}
__device__ __forceinline__ void reload16(uint4& v, const void* p, uint32_t& miss) {
    asm volatile("{\n.reg .pred p;\n.reg .b32 m;\n.reg .b64 u, w;\nmax.u32 m, %0, %2;\nsetp.eq.u32 p, m, 0xffffffff;\n"
                 "mov.b64 u, {%0, %1};\nmov.b64 w, {%2, %3};\n@p ld.relaxed.gpu.global.v2.b64 {u, w}, [%5];\n"
                 "mov.b64 {%0, %1}, u;\nmov.b64 {%2, %3}, w;\n@p mov.u32 %4, 1;\n}"
                 : "+r"(v.x), "+r"(v.y), "+r"(v.z), "+r"(v.w), "+r"(miss) : "l"(p) : "memory");
}
__device__ __forceinline__ void reload8(uint2& v, const void* p, uint32_t& miss) {
    asm volatile("{\n.reg .pred p;\n.reg .b64 u;\nsetp.eq.u32 p, %0, 0xffffffff;\nmov.b64 u, {%0, %1};\n"
                 "@p ld.relaxed.gpu.global.b64 u, [%3];\nmov.b64 {%0, %1}, u;\n@p mov.u32 %2, 1;\n}"
                 : "+r"(v.x), "+r"(v.y), "+r"(miss) : "l"(p) : "memory");
}
__device__ __forceinline__ uint32_t ld_relaxed32(const void* p) {
    uint32_t v;
    asm volatile("ld.relaxed.gpu.global.u32 %0, [%1];" : "=r"(v) : "l"(p) : "memory");
    return v;
}
__device__ __forceinline__ void flag_wait(const unsigned int* p, uint32_t tag) {
    uint32_t v, it = 0;
#pragma unroll 1
    do {
        asm volatile("ld.relaxed.gpu.global.u32 %0, [%1];" : "=r"(v) : "l"(p) : "memory");
    } while (__any_sync(0xffffffffu, v != tag) && ++it < SPIN / 16);
    asm volatile("fence.acquire.gpu;" ::: "memory");
    __syncwarp();
}
__device__ __forceinline__ bool elect() {
    uint32_t p;
    asm volatile("{\n.reg .pred p;\nelect.sync _|p, 0xffffffff;\nselp.u32 %0, 1, 0, p;\n}" : "=r"(p));
    return p;
}
__device__ __forceinline__ void flag_release(unsigned int* p, uint32_t tag) {
    asm volatile("st.release.gpu.global.u32 [%0], %1;" ::"l"(p), "r"(tag) : "memory");
}
__device__ __forceinline__ uint32_t touch(const void* p) {
    uint32_t v;
    asm volatile("ld.global.nc.L1::no_allocate.L2::128B.u32 %0, [%1];" : "=r"(v) : "l"(p));
    return v;
}
__device__ __forceinline__ void bar_sync(int id, int n) { asm volatile("bar.sync %0, %1;" ::"r"(id), "r"(n) : "memory"); }
__device__ __forceinline__ void bar_arrive(int id, int n) { asm volatile("bar.arrive %0, %1;" ::"r"(id), "r"(n) : "memory"); }

constexpr uint64_t EVICT_NORMAL = 0x1000000000000000ull, EVICT_FIRST = 0x12F0000000000000ull;
__device__ __forceinline__ void tma2d(uint32_t dst, const CUtensorMap* m, int c0, int c1, uint32_t bar) {
    asm volatile("cp.async.bulk.tensor.2d.shared::cluster.global.mbarrier::complete_tx::bytes.L2::cache_hint [%0], [%1, {%3, %4}], [%2], %5;"
                 ::"r"(dst), "l"(m), "r"(bar), "r"(c0), "r"(c1), "l"(EVICT_FIRST) : "memory");
}
__device__ __forceinline__ void tma2d_mc(uint32_t dst, const CUtensorMap* m, int c0, int c1, uint32_t bar, uint64_t pol) {
    asm volatile("cp.async.bulk.tensor.2d.shared::cluster.global.mbarrier::complete_tx::bytes.multicast::cluster.L2::cache_hint [%0], [%1, {%3, %4}], [%2], %5, %6;"
                 ::"r"(dst), "l"(m), "r"(bar), "r"(c0), "r"(c1), "h"((uint16_t)3), "l"(pol) : "memory");
}
__device__ __forceinline__ void tma3d(uint32_t dst, const CUtensorMap* m, int c0, int c1, int c2, uint32_t bar) {
    asm volatile("cp.async.bulk.tensor.3d.shared::cluster.global.mbarrier::complete_tx::bytes.L2::cache_hint [%0], [%1, {%3, %4, %5}], [%2], %6;"
                 ::"r"(dst), "l"(m), "r"(bar), "r"(c0), "r"(c1), "r"(c2), "l"(EVICT_FIRST) : "memory");
}
__device__ __forceinline__ void bulk_load(uint32_t dst, const void* src, uint32_t bytes, uint32_t bar) {
    asm volatile("cp.async.bulk.shared::cluster.global.mbarrier::complete_tx::bytes [%0], [%1], %2, [%3];"
                 ::"r"(dst), "l"(src), "r"(bytes), "r"(bar) : "memory");
}
__device__ __forceinline__ void l2_prefetch(const void* src, uint32_t bytes) {
    asm volatile("cp.async.bulk.prefetch.L2.global [%0], %1;" ::"l"(src), "r"(bytes) : "memory");
}
__device__ __forceinline__ uint32_t bmul2(uint32_t a, uint32_t b) { uint32_t r; asm("mul.rn.bf16x2 %0, %1, %2;" : "=r"(r) : "r"(a), "r"(b)); return r; }
__device__ __forceinline__ uint32_t badd2(uint32_t a, uint32_t b) { uint32_t r; asm("add.rn.bf16x2 %0, %1, %2;" : "=r"(r) : "r"(a), "r"(b)); return r; }
__device__ __forceinline__ uint32_t bsub2(uint32_t a, uint32_t b) { uint32_t r; asm("sub.rn.bf16x2 %0, %1, %2;" : "=r"(r) : "r"(a), "r"(b)); return r; }
__device__ __forceinline__ uint32_t bmax2(uint32_t a, uint32_t b) { uint32_t r; asm("max.bf16x2 %0, %1, %2;" : "=r"(r) : "r"(a), "r"(b)); return r; }
__device__ __forceinline__ uint4 lds128(uint32_t a) { uint4 v; asm volatile("ld.shared.v4.u32 {%0,%1,%2,%3}, [%4];" : "=r"(v.x), "=r"(v.y), "=r"(v.z), "=r"(v.w) : "r"(a) : "memory"); return v; }
__device__ __forceinline__ uint2 lds64(uint32_t a) { uint2 v; asm volatile("ld.shared.v2.u32 {%0,%1}, [%2];" : "=r"(v.x), "=r"(v.y) : "r"(a) : "memory"); return v; }
__device__ __forceinline__ uint32_t lds32(uint32_t a) { uint32_t v; asm volatile("ld.shared.u32 %0, [%1];" : "=r"(v) : "r"(a) : "memory"); return v; }
__device__ __forceinline__ uint4 ldsm4(uint32_t a) {
    uint4 v;
    asm volatile("ldmatrix.sync.aligned.m8n8.x4.shared.b16 {%0,%1,%2,%3}, [%4];" : "=r"(v.x), "=r"(v.y), "=r"(v.z), "=r"(v.w) : "r"(a) : "memory");
    return v;
}
__device__ __forceinline__ uint4 ldsm4t(uint32_t a) {
    uint4 v;
    asm volatile("ldmatrix.sync.aligned.m8n8.x4.trans.shared.b16 {%0,%1,%2,%3}, [%4];" : "=r"(v.x), "=r"(v.y), "=r"(v.z), "=r"(v.w) : "r"(a) : "memory");
    return v;
}
__device__ __forceinline__ void mma1688(float* d, uint32_t a0, uint32_t a1, uint32_t b) {
    asm("mma.sync.aligned.m16n8k8.row.col.f32.bf16.bf16.f32 {%0,%1,%2,%3}, {%4,%5}, {%6}, {%0,%1,%2,%3};"
        : "+f"(d[0]), "+f"(d[1]), "+f"(d[2]), "+f"(d[3]) : "r"(a0), "r"(a1), "r"(b));
}
__device__ __forceinline__ void mma16816(float* d, uint32_t a0, uint32_t a1, uint32_t a2, uint32_t a3, uint32_t b0, uint32_t b1) {
    asm("mma.sync.aligned.m16n8k16.row.col.f32.bf16.bf16.f32 {%0,%1,%2,%3}, {%4,%5,%6,%7}, {%8,%9}, {%0,%1,%2,%3};"
                 : "+f"(d[0]), "+f"(d[1]), "+f"(d[2]), "+f"(d[3]) : "r"(a0), "r"(a1), "r"(a2), "r"(a3), "r"(b0), "r"(b1));
}
__device__ __forceinline__ void stsm_x4(uint32_t addr, uint32_t a, uint32_t b, uint32_t c, uint32_t d) {
    asm volatile("stmatrix.sync.aligned.m8n8.x4.shared.b16 [%0], {%1, %2, %3, %4};"
                 ::"r"(addr), "r"(a), "r"(b), "r"(c), "r"(d) : "memory");
}

__device__ __forceinline__ uint64_t mkdesc(uint32_t addr, uint32_t lbo, uint32_t sbo) {
    return (uint64_t)((addr & 0x3FFFF) >> 4) | ((uint64_t)(lbo >> 4) << 16) | ((uint64_t)(sbo >> 4) << 32) | (1ull << 62);
}
constexpr uint32_t SM0 = 1024;
__host__ __device__ constexpr uint32_t desc_lo(uint32_t off, uint32_t lbo) { return ((SM0 + off) >> 4) | ((lbo >> 4) << 16); }
#define WG_FENCE() asm volatile("wgmma.fence.sync.aligned;" ::: "memory")
#define WG_COMMIT() asm volatile("wgmma.commit_group.sync.aligned;" ::: "memory")
#define WG_WAIT(n) asm volatile("wgmma.wait_group.sync.aligned %0;" ::"n"(n) : "memory")

#define F8(a, i) "+f"(a[i]), "+f"(a[i + 1]), "+f"(a[i + 2]), "+f"(a[i + 3]), "+f"(a[i + 4]), "+f"(a[i + 5]), "+f"(a[i + 6]), "+f"(a[i + 7])
#define F16(a, i) F8(a, i), F8(a, i + 8)
#define F64(a) F16(a, 0), F16(a, 16), F16(a, 32), F16(a, 48)
#define F32(a) F16(a, 0), F16(a, 16)
#define L64 "%0,%1,%2,%3,%4,%5,%6,%7,%8,%9,%10,%11,%12,%13,%14,%15,%16,%17,%18,%19,%20,%21,%22,%23,%24,%25,%26,%27,%28,%29,%30,%31,%32,%33,%34,%35,%36,%37,%38,%39,%40,%41,%42,%43,%44,%45,%46,%47,%48,%49,%50,%51,%52,%53,%54,%55,%56,%57,%58,%59,%60,%61,%62,%63"
#define L32 "%0,%1,%2,%3,%4,%5,%6,%7,%8,%9,%10,%11,%12,%13,%14,%15,%16,%17,%18,%19,%20,%21,%22,%23,%24,%25,%26,%27,%28,%29,%30,%31"

template <int TB, int STEP = 128>
__device__ __forceinline__ void mma_rs128(float (&d)[64], uint32_t a0, uint32_t a1, uint32_t a2, uint32_t a3, uint64_t& b, int acc) {
    asm volatile("{\n.reg .pred p;\nsetp.ne.b32 p, %69, 0;\n"
                 "wgmma.mma_async.sync.aligned.m64n128k16.f32.bf16.bf16 {" L64 "}, {%65,%66,%67,%68}, %64, p, 1, 1, %70;\nadd.s64 %64, %64, %71;\n}"
                 : F64(d), "+l"(b) : "r"(a0), "r"(a1), "r"(a2), "r"(a3), "r"(acc), "n"(TB), "n"(STEP));
}
template <int TB>
__device__ __forceinline__ void mma_rs64(float (&d)[32], uint32_t a0, uint32_t a1, uint32_t a2, uint32_t a3, uint64_t& b, int acc) {
    asm volatile("{\n.reg .pred p;\nsetp.ne.b32 p, %37, 0;\n"
                 "wgmma.mma_async.sync.aligned.m64n64k16.f32.bf16.bf16 {" L32 "}, {%33,%34,%35,%36}, %32, p, 1, 1, %38;\nadd.s64 %32, %32, 128;\n}"
                 : F32(d), "+l"(b) : "r"(a0), "r"(a1), "r"(a2), "r"(a3), "r"(acc), "n"(TB));
}
template <int N>
__device__ __forceinline__ void fence_regs(float (&d)[N]) {
#pragma unroll
    for (int i = 0; i < N; i++) asm volatile("" : "+f"(d[i])::"memory");
}
template <int N>
__device__ __forceinline__ void fence_regs(uint32_t (&d)[N]) {
#pragma unroll
    for (int i = 0; i < N; i++) asm volatile("" : "+r"(d[i])::"memory");
}

template <int V> struct IC { static constexpr int value = V; };

constexpr int SLOT = 32768, UNIT = 16384;
constexpr int SM_Q = 4 * SLOT;
constexpr int SM_BAR = 7 * SLOT;
constexpr int SM_RED = SM_BAR + 512;
constexpr int SM_TOTAL = SM_BAR + 3072;
constexpr int XP = D_ * 2 + 16;
constexpr int M_MOD = 16 * XP;
constexpr int SM_T = SM_Q + 2 * D_ * 80, SM_TC = SM_T + D_ * 4, SM_TG = SM_TC + D_ * 4, SM_TS = SM_TG + D_ * 2;
constexpr float CS = 0.08838834764831845f * 1.4426950408889634f;
#define USE_SPARE 1
constexpr float POFF = 102.f, LMIN = 0x1p-104f;
#define LMAX 0.5f
constexpr int SPLIT = 10;
constexpr int STAGE = 11;
constexpr int ESPLIT = 3;
constexpr int QSPLIT = 4, OSPLIT = 6;
constexpr int WF0 = 3, WF1 = 13, WF2 = 19, DL = 9;
constexpr int PF_KV = 4, PF_WO = 120, PF_O = 140;

__device__ __forceinline__ int cluster_role() {
    int k;
    asm volatile("mov.u32 %0, %%ctaid.x;" : "=r"(k));
    k >>= 1;
    const int r = ((k - 36) * 37) >> 8, i = k - 36 - r * 7;
    return k < 4 ? 12 + k : k < 36 ? ((k - 4) & 7) * 8 + ((k - 4) >> 3) : (i + (i > 0)) * 8 + ((4 + r) & 7);
}

struct Args {
    const bf16 *w_mod, *cvec;
    Scratch* gs;
    uint64_t d0;
    bf16* out;
    const bf16 *x, *kc, *vc, *wq, *wo, *w_r, *w_down;
};

__device__ __forceinline__ void frag_store(uint8_t* p, const uint32_t (&a)[32]) {
#pragma unroll
    for (int i = 0; i < 8; i++)
        __stcg(reinterpret_cast<uint4*>(p + i * 512), make_uint4(a[4 * i], a[4 * i + 1], a[4 * i + 2], a[4 * i + 3]));
}
template <int LO = 0, int HI = 8>
__device__ __forceinline__ void frag_load(uint32_t (&a)[32], const uint8_t* p) {
#pragma unroll
    for (int i = LO; i < HI; i++) {
        const uint4 v = ld_relaxed(reinterpret_cast<const uint4*>(p + i * 512));
        a[4 * i] = v.x; a[4 * i + 1] = v.y; a[4 * i + 2] = v.z; a[4 * i + 3] = v.w;
    }
}
__device__ __forceinline__ float quad_sum(float v) {
    v += __shfl_xor_sync(0xffffffffu, v, 1);
    return v + __shfl_xor_sync(0xffffffffu, v, 2);
}
__device__ __forceinline__ float quad_max(float v) {
    v = fmaxf(v, __shfl_xor_sync(0xffffffffu, v, 1));
    return fmaxf(v, __shfl_xor_sync(0xffffffffu, v, 2));
}
__device__ __forceinline__ float rcp_fast(float x) { float y; asm("rcp.approx.ftz.f32 %0, %1;" : "=f"(y) : "f"(x)); return y; }
__device__ __forceinline__ float sigmoidf_(float x) { return rcp_fast(1.f + ex2(-1.4426950408889634f * x)); }
__device__ __forceinline__ void top2(uint32_t k, uint32_t& k1, uint32_t& k2) {
    k1 = __reduce_max_sync(0xffffffffu, k);
    k2 = __reduce_max_sync(0xffffffffu, k == k1 ? 0 : k);
}

__device__ __forceinline__ void mod_fma(float (&a)[8], const uint4 w, float sc) {
    a[0] += sc * bf_lo(w.x); a[1] += sc * bf_hi(w.x); a[2] += sc * bf_lo(w.y); a[3] += sc * bf_hi(w.y);
    a[4] += sc * bf_lo(w.z); a[5] += sc * bf_hi(w.z); a[6] += sc * bf_lo(w.w); a[7] += sc * bf_hi(w.w);
}
__device__ __forceinline__ float mod_reduce(float (&a)[8], int lane) {
#pragma unroll
    for (int h = 4; h > 0; h >>= 1) {
        const bool up = lane & (8 / h);
#pragma unroll
        for (int i = 0; i < h; i++)
            a[i] = (up ? a[i + h] : a[i]) + __shfl_xor_sync(0xffffffffu, up ? a[i] : a[i + h], 8 / h);
    }
    return a[0] + __shfl_xor_sync(0xffffffffu, a[0], 16);
}

__device__ __forceinline__ float ln_stats(float sum, float sq, uint32_t& mean2) {
    const float mean = sum * (1.f / D_);
    const float var = fmaxf(fmaf(-mean, mean, sq * (1.f / D_)), 0.f);
    float sd;
    asm("sqrt.approx.ftz.f32 %0, %1;" : "=f"(sd) : "f"(rbf(rbf(var) + 1e-5f)));
    mean2 = pack_bf16(mean, mean);
    return rcp_fast(rbf(sd));
}
__device__ __forceinline__ uint32_t ln_pair(uint32_t x, uint32_t mean2, float rsd) {
    const uint32_t d = bsub2(x, mean2);
    return pack_bf16(bf_lo(d) * rsd, bf_hi(d) * rsd);
}
__device__ __forceinline__ void rows_load(uint32_t (&x)[20], uint32_t xs, int cw) {
#pragma unroll
    for (int ch = 0; ch < 5; ch++) {
        const uint4 v = ldsm4(ch < 4 ? xs + ch * 256 : xs + 1024 - cw * 16);
        x[4 * ch] = v.x; x[4 * ch + 1] = v.y; x[4 * ch + 2] = v.z; x[4 * ch + 3] = v.w;
    }
}
__device__ __forceinline__ void stats_add(float (&st)[12], uint32_t a, uint32_t b, uint32_t w) {
    mma1688(st, a, b, w);
    mma1688(st + 4, a, b, a);
    mma1688(st + 8, a, b, b);
}
__device__ __forceinline__ float rows_stats(const float (&st)[12], float4* rec, int cw, int lane, uint32_t& mean2, float& dot) {
    const int g8 = lane >> 2;
    if ((g8 >> 1) == (lane & 3)) {
        rec[cw * 16 + g8] = make_float4(st[0], (g8 & 1) ? st[5] : st[4], st[1], 0.f);
        rec[cw * 16 + 8 + g8] = make_float4(st[2], (g8 & 1) ? st[11] : st[10], st[3], 0.f);
    }
    bar_sync(3, 256);
    const float4* r = rec + (lane >> 4) * 64 + (lane & 15);
    const float4 s0 = r[0], s1 = r[16], s2 = r[32], s3 = r[48];
    const float sum = (s0.x + s1.x) + (s2.x + s3.x), sq = (s0.y + s1.y) + (s2.y + s3.y);
    dot = (s0.z + s1.z) + (s2.z + s3.z);
    dot += __shfl_xor_sync(0xffffffffu, dot, 16);
    return ln_stats(sum + __shfl_xor_sync(0xffffffffu, sum, 16), sq + __shfl_xor_sync(0xffffffffu, sq, 16), mean2);
}
template <class F>
__device__ __forceinline__ void rows_normalise(uint32_t* y, const uint32_t* x, uint32_t mean2, float rsd, int lane, F loads) {
    const int g8 = lane >> 2;
    const uint32_t ma2 = __shfl_sync(0xffffffffu, mean2, g8), mb2 = __shfl_sync(0xffffffffu, mean2, g8 + 8);
    const float ra = __shfl_sync(0xffffffffu, rsd, g8), rb = __shfl_sync(0xffffffffu, rsd, g8 + 8);
    loads();
#pragma unroll
    for (int k = 0; k < 9; k++) { y[2 * k] = ln_pair(x[2 * k], ma2, ra); y[2 * k + 1] = ln_pair(x[2 * k + 1], mb2, rb); }
}

__device__ __forceinline__ uint4 h_frag(const uint4* hf, int ks, int lane) {
    if (ks < 32) return ld_relaxed2(hf + ks * 32);
    const uint2* p = reinterpret_cast<const uint2*>(padd(hf, 256 - lane * 8) + ks * 32 - 16);
    const uint2 a = ld_relaxed64(p), b = ld_relaxed64(p + 32);
    return make_uint4(a.x, a.y, b.x, b.y);
}

__device__ __noinline__ void attn_fallback(uint32_t bad, uint32_t tag, const Scratch* gs, uint8_t* frag, uint8_t* keep, const bf16* wq, const bf16* kc, const bf16* vc) {
  const int lane = threadIdx.x & 31, g8 = lane >> 2, qd = lane & 3;
  const int role = cluster_role(), j = role & 7, qb = (role >> 3) * 2 + (blockIdx.x & 1);
  const uint4* hf = g_h + (size_t)(qb * 8 + (threadIdx.x >> 5) - 4) * (36 * 32) + lane;
#pragma unroll 1
  for (int t = 0; t < 4; t++) {
    if (!((bad >> t) & 1)) continue;
    const bf16 *wqp = wq + (4 * j + t) * DH, *kp = kc + (size_t)(2 * j + (t >> 1)) * S_ * DH, *vp = vc + (size_t)(2 * j + (t >> 1)) * S_ * DH;
    uint32_t q[32];
    float o[64];
#pragma unroll
    for (int i = 0; i < 64; i++) o[i] = 0.f;
#pragma unroll 1
    for (int ks = 0; ks < 36; ks++) {
        const uint4 a = h_frag(hf, ks, lane);
        const unsigned short* wr = reinterpret_cast<const unsigned short*>(wqp + (size_t)(ks * 16 + 2 * qd) * QD + g8);
#pragma unroll
        for (int dt = 0; dt < 16; dt++) {
            const uint32_t b0 = __ldg(wr + dt * 8) | ((uint32_t)__ldg(wr + dt * 8 + QD) << 16);
            const uint32_t b1 = __ldg(wr + dt * 8 + 8 * QD) | ((uint32_t)__ldg(wr + dt * 8 + 9 * QD) << 16);
            mma16816(o + 4 * dt, a.x, a.y, a.z, a.w, b0, b1);
        }
    }
#pragma unroll
    for (int i = 0; i < 32; i++) q[i] = pack_bf16(o[2 * i], o[2 * i + 1]);
#pragma unroll
    for (int i = 0; i < 64; i++) o[i] = 0.f;
    float m0 = -INFINITY, m1 = -INFINITY, l0 = 0.f, l1 = 0.f;
#pragma unroll 1
    for (int key = 0; key < S_; key += 16) {
        float sc[8];
#pragma unroll
        for (int i = 0; i < 8; i++) sc[i] = 0.f;
#pragma unroll
        for (int nt = 0; nt < 2; nt++) {
            const uint32_t* kr = reinterpret_cast<const uint32_t*>(kp + (size_t)(key + nt * 8 + g8) * DH) + qd;
#pragma unroll
            for (int ks = 0; ks < 8; ks++)
                mma16816(sc + 4 * nt, q[4 * ks], q[4 * ks + 1], q[4 * ks + 2], q[4 * ks + 3], __ldg(kr + ks * 8), __ldg(kr + ks * 8 + 4));
        }
        const float n0 = quad_max(fmaxf(fmaxf(m0, fmaxf(sc[0], sc[1])), fmaxf(sc[4], sc[5])));
        const float n1 = quad_max(fmaxf(fmaxf(m1, fmaxf(sc[2], sc[3])), fmaxf(sc[6], sc[7])));
        const float f0 = ex2((m0 - n0) * CS), f1 = ex2((m1 - n1) * CS);
        m0 = n0; m1 = n1;
#pragma unroll
        for (int i = 0; i < 8; i++) sc[i] = ex2((sc[i] - ((i & 2) ? n1 : n0)) * CS);
        l0 = l0 * f0 + (sc[0] + sc[1]) + (sc[4] + sc[5]);
        l1 = l1 * f1 + (sc[2] + sc[3]) + (sc[6] + sc[7]);
        const uint32_t e0 = pack_bf16(sc[0], sc[1]), e1 = pack_bf16(sc[2], sc[3]), e2 = pack_bf16(sc[4], sc[5]), e3 = pack_bf16(sc[6], sc[7]);
        const unsigned short* vr = reinterpret_cast<const unsigned short*>(vp + (size_t)(key + 2 * qd) * DH + g8);
#pragma unroll
        for (int dt = 0; dt < 16; dt++) {
            o[4 * dt] *= f0; o[4 * dt + 1] *= f0; o[4 * dt + 2] *= f1; o[4 * dt + 3] *= f1;
            const uint32_t b0 = __ldg(vr + dt * 8) | ((uint32_t)__ldg(vr + dt * 8 + DH) << 16);
            const uint32_t b1 = __ldg(vr + dt * 8 + 8 * DH) | ((uint32_t)__ldg(vr + dt * 8 + 9 * DH) << 16);
            mma16816(o + 4 * dt, e0, e1, e2, e3, b0, b1);
        }
    }
    const float i0 = 1.f / quad_sum(l0), i1 = 1.f / quad_sum(l1);
#pragma unroll
    for (int i = 0; i < 16; i++) {
        q[2 * i] = pack_bf16(o[4 * i] * i0, o[4 * i + 1] * i0);
        q[2 * i + 1] = pack_bf16(o[4 * i + 2] * i1, o[4 * i + 3] * i1);
    }
    frag_store(t < 3 ? frag + t * 4096 : keep, q);
  }
}

__device__ __forceinline__ void spare_q3(Scratch* gs, uint32_t sb, uint32_t bar_full, uint32_t bar_empty, int lane, int cw) {
    const uint32_t tag = load_tag(gs);
    uint32_t rel_base, e = 3;
    asm("mapa.shared::cluster.u32 %0, %1, %2;" : "=r"(rel_base) : "r"(bar_empty), "r"(lane & 1));
#pragma unroll 1
    for (int qb = blockIdx.x - NCTA; qb < 16; qb += 4) {
        uint32_t h[144];
        float o[64];
        flag_wait(&g_flag_h[(qb * 8 + cw) * 32], tag);
        const uint4* hf = g_h + (size_t)(qb * 8 + cw) * (36 * 32) + lane;
#pragma unroll
        for (int ks = 0; ks < 36; ks++) {
            const uint4 v = h_frag(hf, ks, lane);
            h[4 * ks] = v.x; h[4 * ks + 1] = v.y; h[4 * ks + 2] = v.z; h[4 * ks + 3] = v.w;
        }
#pragma unroll
        for (int i = 0; i < 64; i++) o[i] = 0.f;
#pragma unroll 1
        for (int v = 0; v < 4; v++) {
            fence_regs(o);
#pragma unroll
            for (int t = 0; t < 5; t++) {
                mbar_wait(bar_full + 8 * (e & 3), (e >> 2) & 1);
                uint64_t dv = mkdesc(sb + (e & 3) * SLOT, UNIT, 1024);
                WG_FENCE();
#pragma unroll
                for (int ks = 0; ks < (t < 4 ? 8 : 4); ks++)
                    mma_rs128<1>(o, h[32 * t + 4 * ks], h[32 * t + 4 * ks + 1], h[32 * t + 4 * ks + 2], h[32 * t + 4 * ks + 3], dv, ks | t);
                WG_COMMIT();
                if (t > 0) { WG_WAIT(1); if (lane < 2) mbar_arrive_cluster(rel_base + 8 * ((e - 1) & 3)); }
                e++;
            }
            WG_WAIT(0);
            fence_regs(o);
            if (lane < 2) mbar_arrive_cluster(rel_base + 8 * ((e - 1) & 3));
            uint4* dst = &g_q3[((qb * 8 + 2 * v) * 8 + cw) * 128 + lane];
#pragma unroll
            for (int i = 0; i < 8; i++)
                __stcg(dst + (i >> 2) * 1024 + (i & 3) * 32, make_uint4(pack_bf16(o[8 * i], o[8 * i + 1]), pack_bf16(o[8 * i + 2], o[8 * i + 3]),
                                                                        pack_bf16(o[8 * i + 4], o[8 * i + 5]), pack_bf16(o[8 * i + 6], o[8 * i + 7])));
        }
        bar_sync(3, 256);
        if (cw == 0 && lane == 0) flag_release(&g_flag_q3[qb * 32], tag);
        __syncwarp();
    }
}

template <bool SPARE>
__global__ void __cluster_dims__(2, 1, 1) __launch_bounds__(384, 1)
fused_kernel(const Args args, const __grid_constant__ CUtensorMap tm_wq,
             const __grid_constant__ CUtensorMap tm_k, const __grid_constant__ CUtensorMap tm_v,
             const __grid_constant__ CUtensorMap tm_wo, const __grid_constant__ CUtensorMap tm_p,
             const __grid_constant__ CUtensorMap tm_x, const __grid_constant__ CUtensorMap tm_d,
             const __grid_constant__ CUtensorMap tm_g, const __grid_constant__ CUtensorMap tm_u) {
    extern __shared__ __align__(1024) uint8_t smem_raw[];
    const uint32_t sb = smem_u32(smem_raw);
    Scratch* const gs = args.gs;
    const uint32_t bar_full = sb + SM_BAR;
    const uint32_t bar_g = bar_full + 8 * 4;
    const uint32_t bar_mod = bar_g + 8;
    const uint32_t bar_go = bar_mod + 8;
    const uint32_t bar_x = bar_go + 40;
    const uint32_t bar_empty = bar_x + 8;
    const uint32_t bar_pub = bar_empty + 8 * 4;
    const uint32_t bar_qfree = bar_pub + 32;
    const uint32_t bar_out = bar_qfree + 24;
    const uint32_t bar_q3 = bar_out + 8;
    const uint32_t bar_pre = bar_q3 + 16;
    const uint32_t bar_w0 = bar_q3 + 8;
    constexpr int E0 = SPARE ? 2 : 0;

    const int c = blockIdx.x & 1;
#define ROLES() const int role = cluster_role(), j = role & 7, qb = (role >> 3) * 2 + c, rg = qb * 8 + j
    const int warp = __shfl_sync(0xffffffffu, threadIdx.x >> 5, 0);

    if (SPARE && blockIdx.x >= NCTA && warp >= 4) {
        asm volatile("barrier.cluster.arrive.relaxed.aligned;" ::: "memory");
        asm volatile("setmaxnreg.inc.sync.aligned.u32 240;");
        asm volatile("barrier.cluster.wait.aligned;" ::: "memory");
        spare_q3(gs, sb, bar_full, bar_empty, threadIdx.x & 31, warp - 4);
        asm volatile("barrier.cluster.arrive.relaxed.aligned;\nbarrier.cluster.wait.aligned;" ::: "memory");
    } else if (warp < 4) {
        asm volatile("setmaxnreg.dec.sync.aligned.u32 24;");
        ROLES();
        int lane;
        asm volatile("mov.u32 %0, %%laneid;" : "=r"(lane));
        if (warp == 2 && elect()) {
            asm volatile("prefetch.tensormap [%0];" ::"l"(&tm_x) : "memory");
#pragma unroll
            for (int i = 0; i < 27; i++) mbar_init(bar_full + 8 * i, i < 12 || i >= 23 ? 1 : i < 16 ? 16 : 8);
#pragma unroll
            for (int i = 0; i <= E0; i++) {
                mbar_arrive(bar_full + 8 * i);
                asm volatile("mbarrier.arrive.shared::cta.b64 _, [%0], 16;" ::"r"(bar_empty + 8 * i) : "memory");
            }
            asm volatile("fence.mbarrier_init.release.cluster;" ::: "memory");
        }
        __syncwarp();
        asm volatile("barrier.cluster.arrive.relaxed.aligned;" ::: "memory");
        if (warp == 2 && !(SPARE && blockIdx.x >= NCTA)) {
            __nanosleep(200);
            if (elect()) {
                mbar_expect_tx(bar_x, 16 * XP);
                tma2d(sb + SM_Q, &tm_x, 0, rg * 16, bar_x);
            }
            __syncwarp();
        }
        asm volatile("barrier.cluster.wait.aligned;" ::: "memory");
        const uint32_t tag = load_tag(gs);
        if (SPARE && blockIdx.x >= NCTA) {
            if (warp == 1) {
#pragma unroll 1
                for (int e = 3; e < 83; e++) {
                    const int v = (e - 3) / 5;
                    mbar_wait_sleep(bar_empty + 8 * (e & 3), ~(e >> 2) & 1);
                    if (elect()) {
                        mbar_expect_tx(bar_full + 8 * (e & 3), SLOT);
                        tma2d_mc(sb + (e & 3) * SLOT + c * UNIT, &tm_wq, (8 * (v & 3) + 4 * c + 3) * DH + 64, (e - 3 - v * 5) * 128,
                                 bar_full + 8 * (e & 3), EVICT_NORMAL);
                    }
                }
            }
            __syncwarp();
            asm volatile("barrier.cluster.arrive.relaxed.aligned;\nbarrier.cluster.wait.aligned;" ::: "memory");
            return;
        }
        if (warp == 3) {
#pragma unroll 1
            for (int e = 4; e < 20; e++) {
                __nanosleep(e == 4 ? 2000 : 400);
                const int hd = (e * 52) >> 8, row = (e - hd * 5) * 128 + qb * 8 + (lane >> 1);
                if (lane < 16 && row < D_)
                    asm volatile("prefetch.global.L2 [%0];" ::"l"(padd(args.wq, (row * QD + (4 * j + ((0x1320 >> (4 * hd)) & 3)) * DH + (lane & 1) * 64) * 2)) : "memory");
            }
            __syncwarp();
            mbar_wait_sleep(bar_go, 0);
#pragma unroll 1
            for (int unit = 72 + blockIdx.x; unit < 216; unit += NCTA) {
                float a[8];
#pragma unroll
                for (int i = 0; i < 8; i++) a[i] = 0.f;
#pragma unroll 1
                for (int k = lane >> 1; k < D_; k += 16) {
                    const float cv = __bfloat162float(*padd(args.cvec, k * 2));
                    mod_fma(a, __ldg(reinterpret_cast<const uint4*>(padd(args.w_mod, (k * (6 * D_) + unit * 16 + (lane & 1) * 8) * 2))), rbf(cv * sigmoidf_(cv)));
                }
                const float v = mod_reduce(a, lane), v1 = __shfl_down_sync(0xffffffffu, v, 8);
                if (lane < 8) *padd(gs->mod2, ((unit - 72) * 8 + (lane & 1) * 4 + (lane & 2) + (lane >> 2)) * 4) = pack_bf16(v, v1);
            }
            __syncwarp();
            if (lane == 0) flag_release(padd(g_flag_mod, blockIdx.x * 4), tag);
#pragma unroll 1
            for (int k = 0; k < 36; k++) {
                __nanosleep(200);
                __stcg(padd(gs->h[0], (~tag & 1) * (NCTA * 36 * 512) + ((rg * 36 + k) * 32 + lane) * 16), make_uint4(0, 0, 0, 0));
            }
            __syncwarp();
            mbar_wait_sleep(bar_qfree + 16, 0);
            __nanosleep(2000);
            {
                uint4 v;
                uint32_t it = 0;
#pragma unroll 1
                do {
                    v = ld_relaxed(reinterpret_cast<const uint4*>(padd(g_flag_mod, lane * 16)));
                } while (((v.x ^ tag) | (v.y ^ tag) | (v.z ^ tag) | (v.w ^ tag)) && ++it < SPIN / 16);
                asm volatile("fence.acquire.gpu;" ::: "memory");
            }
            __syncwarp();
            {
                float w1 = 0.f, w2 = 0.f;
#pragma unroll 1
                for (int k = lane; k < D_ / 2; k += 32) {
                    const uint32_t* mp = padd(gs->mod2, k * 4);
                    const uint32_t sv = __ldcg(mp + D_ / 2), c1 = badd2(__ldcg(mp + D_), 0x3f803f80u);
                    const uint32_t wr = *reinterpret_cast<const uint32_t*>(padd(args.w_r, k * 4)), wp = bmul2(c1, wr);
                    reinterpret_cast<uint2*>(smem_raw + SM_T)[k] = make_uint2(__ldcg(mp), wp);
                    reinterpret_cast<uint2*>(smem_raw + SM_TC)[k] = make_uint2(c1, sv);
                    reinterpret_cast<uint32_t*>(smem_raw + SM_TG)[k] = __ldcg(mp + 3 * D_ / 2);
                    w1 += bf_lo(wp) + bf_hi(wp);
                    w2 += bf_lo(sv) * bf_lo(wr) + bf_hi(sv) * bf_hi(wr);
                }
#pragma unroll 1
                for (int i = 1; i < 32; i <<= 1) { w1 += __shfl_xor_sync(0xffffffffu, w1, i); w2 += __shfl_xor_sync(0xffffffffu, w2, i); }
                *reinterpret_cast<float2*>(smem_raw + SM_TS) = make_float2(w1, w2);
            }
#pragma unroll
            for (int i = 0; i < 4; i++) reinterpret_cast<uint4*>(smem_raw + SM_RED)[lane + 32 * i] = make_uint4(~0u, ~0u, ~0u, ~0u);
            asm volatile("fence.proxy.async.shared::cta;" ::: "memory");
            __syncwarp();
            if (elect()) {
                uint8_t* mb = g_frag + (size_t)rg * 8 * WREG + 3 * 4096;
#pragma unroll 1
                for (int k = 0; k < 8; k++, mb += WREG) {
#pragma unroll
                    for (int i = 0; i < 3; i++)
                        asm volatile("cp.async.bulk.global.shared::cta.bulk_group [%0], [%1], 2048;" ::"l"(mb + i * 2048), "r"(sb + SM_RED) : "memory");
                    __nanosleep(500);
                }
                asm volatile("cp.async.bulk.commit_group;\ncp.async.bulk.wait_group 0;\nfence.proxy.async.global;" ::: "memory");
            }
            __syncwarp();
            if (lane == 0) mbar_arrive(bar_mod);
            __syncwarp();
            mbar_wait_sleep(bar_go + 8, 0);
            if (elect()) asm volatile("prefetch.tensormap [%0];\nprefetch.tensormap [%1];\nprefetch.tensormap [%2];" ::"l"(&tm_x), "l"(&tm_p), "l"(&tm_d) : "memory");
            __syncwarp();
#pragma unroll 1
            for (int i = 1; i < 4; i++) {
                mbar_wait(bar_pub + 8 * i, 0);
                unsigned int* flags = padd(g_flag_part, (qb * 32 + i * 8 - 8) * 4);
                if (elect()) { flag_release(padd(flags, j * 4), tag); DBG_PG(93); }
                __syncwarp();
                const uint32_t slot = (i + 2) & 3;
                flag_wait(padd(flags, (lane & 7) * 4), tag);
                asm volatile("fence.proxy.async.global;" ::: "memory");
                if (lane == 0 && i == 3) DBG_PG(101);
                mbar_wait(bar_go + 8 + 8 * i, 0);
                mbar_wait(bar_empty + 8 * slot, i == 3);
                if (elect()) {
                    mbar_expect_tx(bar_full + 8 * slot, SLOT);
                    tma3d(sb + slot * SLOT, &tm_p, 0, j * 20 + (i - 1) * 4, qb * 8, bar_full + 8 * slot);
                    tma3d(sb + slot * SLOT + UNIT, &tm_p, 0, j * 20 + (i - 1) * 4 + 2, qb * 8, bar_full + 8 * slot);
                }
            }
        } else if (warp == 0) {
#pragma unroll 1
            for (int i = 0; i < 48; i++) {
                if (SPARE && i == 34) {
                    flag_wait(&g_flag_q3[qb * 32], tag);
                    if (elect()) {
                        asm volatile("fence.proxy.async.global;" ::: "memory");
                        mbar_expect_tx(bar_q3, UNIT);
#pragma unroll 1
                        for (int k = 0; k < 8; k++) bulk_load(sb + SM_Q + 2 * SLOT + k * 4096 + 2048, &g_q3[(rg * 8 + k) * 128], 2048, bar_q3);
                    }
                }
                if (i == 0 || i == 17 || i == 34) { mbar_wait_sleep(bar_qfree + (i >> 4) * 8, 0); __nanosleep(2000); }
                __nanosleep(500);
                if (elect()) {
                    asm volatile("mbarrier.expect_tx.shared::cta.b64 [%0], %1;" ::"r"(bar_g), "n"(1920) : "memory");
                    tma2d(sb + SM_Q + i * 1920, i < 24 ? &tm_g : &tm_u, (blockIdx.x * 36) & ~7, (i < 24 ? i : i - 24) * 24, bar_g);
                }
            }
            if (elect()) mbar_arrive(bar_g);
#pragma unroll 1
            for (int i = 0; i < 18; i++) {
                __nanosleep(400);
                if (elect()) l2_prefetch(args.w_down + (size_t)(blockIdx.x * 36 + i * 2) * D_, 4 * D_);
            }
            __syncwarp();
            mbar_wait_sleep(bar_go + 8 * 2, 0);
            uint32_t acc = 0;
#pragma unroll 1
            for (int k = lane; k < 16 * 9; k += 32) acc |= touch(padd(args.x, (rg * 16 * D_ + k * 64) * 2));
            if (acc == 0) reinterpret_cast<volatile uint32_t*>(smem_raw + SM_BAR)[127] = acc;
            __syncwarp();
            mbar_wait_sleep(bar_go + 8 * 4, 0);
            uint4* rp = padd(g_rows, (rg * 2 * RSLOT + lane) * 16);
#pragma unroll
            for (int k = 0; k < 12; k++) rp[k * 32] = make_uint4(~0u, ~0u, ~0u, ~0u);
            if (blockIdx.x < 72) {
                uint4* yp = reinterpret_cast<uint4*>(padd(g_ypart, blockIdx.x * NCTA * 64 + lane * 16));
#pragma unroll
                for (int k = 0; k < 16; k++) yp[k * 32] = make_uint4(~0u, ~0u, ~0u, ~0u);
            }
            asm volatile("fence.acq_rel.gpu;" ::: "memory");
            __syncwarp();
            if (lane == 0) mbar_arrive(bar_pre);
        } else if (warp == 1) {
            __nanosleep(300);
            uint32_t go = bar_go;
            uint64_t marks = 24 | 151 << 8 | 155 << 16 | 160ull << 24 | 165ull << 32;
#pragma unroll 1
            for (int e = E0; e < 168; e++) {
                const CUtensorMap* tm;
                int c0, c1;
                uint64_t pol = EVICT_FIRST;
                if (e == 159 || e == 164) continue;
                if (e < 21 && e != 19) {
                    const int i = SPARE && e < 12 ? e - 2 : e - (e == 20), hd = (i * 52) >> 8;
                    tm = &tm_wq; c0 = (4 * j + ((0x1320 >> (4 * hd)) & 3)) * DH + c * 64; c1 = (i - hd * 5) * 128 - 64;
                    if (SPARE && e >= 12 && e < 15) { c0 = (4 * j + 3) * DH; c1 = (2 * (e - 12) + c) * 128; }
                } else if (e < 148) {
                    const int i = max(e - 20, 0);
                    const bool isk = i == 0 || ((i & 1) && i < 127);
                    const int n = isk ? (i + 1) >> 1 : (i - 1) >> 1;
                    tm = isk ? &tm_k : &tm_v; c0 = c * 64; c1 = (2 * j + (n >> 5)) * S_ + (n & 15) * 128;
                    if (!(i & 32)) pol = EVICT_NORMAL;
                } else {
                    int i = e - 148 - (e > 159) - (e > 164);
                    tm = &tm_wo; c0 = (i >> 1) * 64; c1 = (4 * j + ((i & 1) ? 1 + c : 3 * c)) * DH;
                }
                const uint32_t fb = e == E0 ? bar_w0 : bar_full + 8 * (e & 3), d = sb + (e == E0 ? 6 : e & 3) * SLOT;
                if (e >= 24 && e < 152) mbar_wait_sleep(bar_empty + 8 * (e & 3), ~(e >> 2) & 1);
                else if (e != E0) mbar_wait(bar_empty + 8 * (e & 3), ~(e >> 2) & 1);
                if (elect()) {
                    mbar_expect_tx(fb, SLOT);
                    tma2d_mc(d + c * UNIT, tm, c0, c1, fb, pol);
                    const int i = e - PF_KV;
                    if (i >= 0 && i < 128 && !(i & 32))
                        l2_prefetch(((i & 1) ? args.vc : args.kc) + (size_t)((2 * j + (i >> 6)) * S_ + (i & 30) * 64) * DH + qb * 1024, 2048);
                    if (e >= PF_WO && e < PF_WO + 18) l2_prefetch(args.wo + (size_t)blockIdx.x * (QD * D_ / NCTA) + (e - PF_WO) * 1024, 2048);
                    if (e >= PF_O && e < PF_O + 8) l2_prefetch(g_frag + (size_t)(rg * 8 + e - PF_O) * WREG, 4096);
                    if (e == (marks & 255)) mbar_arrive(go);
                }
                if (e == (marks & 255)) { go += 8; marks >>= 8; }
            }
            asm volatile("fence.proxy.async.global;" ::: "memory");
            mbar_wait(bar_empty, 1);
            if (elect()) {
                mbar_expect_tx(bar_full, 16 * XP);
                tma2d(sb, &tm_x, 0, rg * 16, bar_full);
            }
            mbar_wait(bar_empty + 16, 1);
            if (elect()) {
                mbar_expect_tx(bar_full + 16, SLOT);
                tma3d(sb + 2 * SLOT, &tm_p, 0, j * 20 + 12, qb * 8, bar_full + 16);
                tma3d(sb + 2 * SLOT + UNIT, &tm_p, 0, j * 20 + 14, qb * 8, bar_full + 16);
            }
            mbar_wait(bar_empty + 24, 1);
            __nanosleep(300);
            if (elect()) {
                mbar_expect_tx(bar_full + 24, UNIT);
                tma3d(sb + 3 * SLOT, &tm_p, 0, j * 20 + 16, qb * 8, bar_full + 24);
            }
            mbar_wait(bar_empty + 8, 0);
            mbar_wait(bar_empty + 16, 0);
            __nanosleep(300);
            if (elect()) {
#pragma unroll
                for (int i = 1; i < 3; i++) {
                    mbar_expect_tx(bar_full + 8 * i, 18 * XP);
                    tma2d(sb + i * SLOT, &tm_d, 0, blockIdx.x * 36 + (i - 1) * 18, bar_full + 8 * i);
                }
            }
        } else {
            if (elect()) asm volatile("prefetch.tensormap [%0];\nprefetch.tensormap [%1];\nprefetch.tensormap [%2];" ::"l"(&tm_k), "l"(&tm_v), "l"(&tm_wo) : "memory");
            if (SPARE) {
                mbar_wait_sleep(bar_pub, 0);
                if (lane == 0) flag_release(padd(g_flag_h, rg * 128), tag);
                __syncwarp();
            }
            bar_sync(1, 192);
#pragma unroll 1
            for (uint32_t e = E0 + 5; e < 20; e++) {
                mbar_wait(bar_full + 8 * (e & 3), (e >> 2) & 1);
                if (!(((SPARE ? 0xa080 : 0x8420) >> e) & 1)) bar_sync(1, 192);
            }
#pragma unroll 1
            for (uint32_t e = 20; e < 148; e++) {
                mbar_wait_sleep(bar_full + 8 * (e & 3), (e >> 2) & 1);
                if (SPARE && e == 113) mbar_wait(bar_q3, 0);
                if (e & 1) bar_sync(1, 192);
                if (!(e & 1) || e == 147) bar_sync(4, 160);
            }
#pragma unroll 1
            for (uint32_t e = 148; e < 168; e++) {
                mbar_wait(bar_full + 8 * (e & 3), (e >> 2) & 1);
                if (e != 159 && e != 164) bar_sync(1, 192);
            }
        }
        __syncwarp();
        uint32_t rows = 0x1111u << warp;
        auto store_rows = [&](uint32_t m) {
#pragma unroll 1
            for (; m; m &= m - 1) {
                const int i = __ffs(m) - 1;
                asm volatile("cp.async.bulk.global.shared::cta.bulk_group.L2::cache_hint [%0], [%1], %2, %3;"
                             ::"l"(padd(args.out, (rg * 16 + i) * (D_ * 2))), "r"(sb + i * XP), "n"(D_ * 2), "l"(EVICT_FIRST) : "memory");
            }
        };
        mbar_wait_sleep(bar_out, 0);
        if (blockIdx.x == 127 && warp == 0 && lane == 0) gs->epoch[0] = tag;
        if (elect()) {
            asm volatile("fence.proxy.async.shared::cta;" ::: "memory");
            const uint2 sel = lds64(sb + SM_RED + 64);
            if ((sel.x >> 4) == rg) rows &= ~(1u << (sel.x & 15));
            if ((sel.y >> 4) == rg) rows &= ~(1u << (sel.y & 15));
            store_rows(rows);
            asm volatile("cp.async.bulk.commit_group;\ncp.async.bulk.wait_group.read 0;" ::: "memory");
        }
    } else {
        uint32_t cv[2] = {0, 0}, tag0 = 0;
        {
            uint32_t ws, t, b;
            asm volatile("mov.u32 %0, smem_raw;\nmov.u32 %1, %%tid.x;\nmov.u32 %2, %%ctaid.x;" : "=r"(ws), "=r"(t), "=r"(b));
            t -= 128;
            const uint32_t* cp = padd(reinterpret_cast<const uint32_t*>(args.cvec), (t & 0xe0) + (t & 7) * 4);
            asm volatile("{\n.reg .pred p, q, r;\nsetp.lt.u32 r, %8, 256;\nsetp.lt.and.u32 p, %9, 72, r;\nsetp.lt.and.u32 q, %8, 128, p;\n"
                         "@p ld.global.nc.u32 %0, [%5];\n@q ld.global.nc.u32 %1, [%6 + 1024];\n@r ld.global.ca.u32 %2, [%7];\n"
                         "@p cp.async.cg.shared.global [%3], [%4], 16;\n@p cp.async.cg.shared.global [%3 + 4096], [%4 + 884736], 16;\n"
                         "@p cp.async.cg.shared.global [%3 + 8192], [%4 + 1769472], 16;\n@p cp.async.cg.shared.global [%3 + 12288], [%4 + 2654208], 16;\n"
                         "@q cp.async.cg.shared.global [%3 + 16384], [%4 + 3538944], 16;\n}"
                         : "+r"(cv[0]), "+r"(cv[1]), "+r"(tag0)
                         : "r"(ws + SM_Q + SLOT + t * 16), "l"(padd(args.w_mod, (t >> 1 & 127) * (12 * D_) + (t & 1) * 16 + b * 32)),
                           "l"(padd(cp, (t & 24) * 32)), "l"(cp), "l"(padd(gs->epoch, b >> 8)), "r"(t), "r"(b) : "memory");
        }
        uint32_t tag = __shfl_sync(0xffffffffu, tag0, 0);
        asm volatile("barrier.cluster.arrive.relaxed.aligned;" ::: "memory");
        asm volatile("setmaxnreg.inc.sync.aligned.u32 240;");
        const int lane = threadIdx.x & 31;
        const int cw = warp - 4;
        const int w = cw >> 2;
        const int tid = threadIdx.x - 128;
        ROLES();
        float* red = reinterpret_cast<float*>(smem_raw + SM_RED);
        DBG_INIT();
        DBG_G(120);
        DBG_T(100);

        {
            if (blockIdx.x < 72) {
                uint32_t sa[10];
#pragma unroll
                for (int i = 0; i < 2; i++) {
                    const float lo = bf_lo(cv[i]), hi = bf_hi(cv[i]);
                    cv[i] = pack_bf16(lo * sigmoidf_(lo), hi * sigmoidf_(hi));
                }
#pragma unroll
                for (int i = 0; i < 10; i++) sa[i] = __shfl_sync(0xffffffffu, cv[i >> 3], (i & 7) * 4 + (lane & 3));
                uint2* mdst = &gs->mod1[(tid >> 3) * D_ + blockIdx.x * 8 + (tid & 7)];
                anchor(bar_full + 504, sa[0] & sa[1] & sa[2] & sa[3] & sa[4] & sa[5] & sa[6] & sa[7] & sa[8] & sa[9] & (uint32_t)(uintptr_t)mdst & (uint32_t)((uintptr_t)mdst >> 32));
                asm volatile("cp.async.wait_all;" ::: "memory");
                __syncwarp();
                const uint32_t ws = sb + SM_Q + SLOT + cw * 512 + (lane & 15) * 32 + (lane & 16);
                float d[16];
#pragma unroll
                for (int i = 0; i < 16; i++) d[i] = 0.f;
#pragma unroll
                for (int i = 0; i < 5; i++) {
                    const uint4 b = ldsm4t(ws + (i < 4 || cw < 4 ? i * 4096 : 0));
                    mma16816(d + 8 * (i & 1), sa[2 * i], sa[2 * i], sa[2 * i + 1], sa[2 * i + 1], b.x, b.y);
                    mma16816(d + 8 * (i & 1) + 4, sa[2 * i], sa[2 * i], sa[2 * i + 1], sa[2 * i + 1], b.z, b.w);
                }
                if (lane < 8) reinterpret_cast<float2*>(red)[lane * 8 + cw] = (lane & 4) ? make_float2(d[4] + d[12], d[5] + d[13]) : make_float2(d[0] + d[8], d[1] + d[9]);
                bar_sync(3, 256);
                if (tid < 8 * MREP) {
                    const float4* r = reinterpret_cast<const float4*>(red) + (tid & 7) * 4;
                    const float4 r0 = r[0], r1 = r[1], r2 = r[2], r3 = r[3];
                    st_relaxed64(mdst, pack_bf16(((r0.x + r0.z) + (r1.x + r1.z)) + ((r2.x + r2.z) + (r3.x + r3.z)),
                                                 ((r0.y + r0.w) + (r1.y + r1.w)) + ((r2.y + r2.w) + (r3.y + r3.w))), tag + 1);
                }
            }
            DBG_G(106);
            asm volatile("barrier.cluster.wait.aligned;" ::: "memory");
            mbar_wait(bar_x, 0);
            asm volatile("add.u32 %0, %0, 1;" : "+r"(tag));
            uint32_t x[20];
            float st[12], st2[12];
            rows_load(x, sb + SM_Q + (lane & 15) * XP + (lane >> 4) * 16 + cw * 32, cw);
#pragma unroll
            for (int i = 0; i < 12; i++) { st[i] = 0.f; st2[i] = 0.f; }
#pragma unroll
            for (int k = 0; k < 9; k++) stats_add((k & 1) ? st2 : st, x[2 * k], x[2 * k + 1], 0x3f803f80u);
#pragma unroll
            for (int i = 0; i < 12; i++) st[i] += st2[i];
            uint32_t mean2;
            float dot;
            const float rsd = rows_stats(st, reinterpret_cast<float4*>(red + 128), cw, lane, mean2, dot);
            const uint4* mp = reinterpret_cast<const uint4*>(gs->mod1 + ((blockIdx.x >> 1) & (MREP - 1)) * D_) + min(tid, D_ / 4 - 1);
            uint4 v0 = make_uint4(0, tag, 0, tag), v1 = v0;
            auto look = [&]() {
                asm volatile("{\n.reg .pred p;\n.reg .b64 a, b, c, d;\nsetp.lt.s32 p, %9, 5;\nmov.b64 a, {%0, %1};\nmov.b64 b, {%2, %3};\n"
                             "mov.b64 c, {%4, %5};\nmov.b64 d, {%6, %7};\n@p ld.relaxed.gpu.global.v2.b64 {a, b}, [%8];\n"
                             "@p ld.relaxed.gpu.global.v2.b64 {c, d}, [%8 + 2304];\n"
                             "mov.b64 {%0, %1}, a;\nmov.b64 {%2, %3}, b;\nmov.b64 {%4, %5}, c;\nmov.b64 {%6, %7}, d;\n}"
                             : "+r"(v0.x), "+r"(v0.y), "+r"(v0.z), "+r"(v0.w), "+r"(v1.x), "+r"(v1.y), "+r"(v1.z), "+r"(v1.w)
                             : "l"(mp), "r"(cw) : "memory");
            };
            rows_normalise(x, x, mean2, rsd, lane, look);
            fence_regs(x);
            uint32_t it = 0;
#pragma unroll 1
            while (((v0.y ^ tag) | (v0.w ^ tag) | (v1.y ^ tag) | (v1.w ^ tag)) && ++it < SPIN / 16) look();
            uint4* smod = reinterpret_cast<uint4*>(smem_raw + SM_Q + M_MOD);
            if (tid < D_ / 4) smod[tid] = make_uint4(badd2(v1.x, 0x3f803f80u), v0.x, badd2(v1.z, 0x3f803f80u), v0.z);
            uint4* hdst = g_h + (size_t)(rg * 36 + cw) * 32 + lane;
            uint2* hdst2 = reinterpret_cast<uint2*>(g_h + (size_t)(rg * 36 + 32) * 32) + tid;
            bar_sync(3, 256);
            DBG_G(107);
#pragma unroll
            for (int k = 0; k < 9; k++) {
                const uint2 cs = lds64(sb + SM_Q + M_MOD + (cw * 8 + (lane & 3) + (k < 8 ? (k >> 1) * 64 + (k & 1) * 4 : 256 - cw * 4)) * 8);
                const uint32_t c1 = cs.x, sa = cs.y;
                x[2 * k] = badd2(bmul2(x[2 * k], c1), sa);
                if (x[2 * k] == 0) x[2 * k] = 0x8000u;
                x[2 * k + 1] = badd2(bmul2(x[2 * k + 1], c1), sa);
            }
#pragma unroll
            for (int ch = 0; ch < 4; ch++) st_relaxed4(hdst + ch * 256, x[4 * ch], x[4 * ch + 1], x[4 * ch + 2], x[4 * ch + 3]);
            st_relaxed64(hdst2, x[16], x[17]);
            __syncwarp();
            if (SPARE && lane == 0) mbar_arrive(bar_pub);
            DBG_G(108);
        }

        uint32_t rel_base;
        asm("mapa.shared::cluster.u32 %0, %1, %2;" : "=r"(rel_base) : "r"(bar_empty), "r"(lane & 1));
        auto release = [&](uint32_t slot) { if (lane < 2) mbar_arrive_cluster(rel_base + 8 * slot); };
        uint32_t q[32], p[32];
        float s[64], o[64];

        const int lw = cw & 3;
        const uint32_t relw = lw == 2 && lane < 8, handw = lw == 2 || cw == 1;
        auto release4 = [&](uint32_t off, uint32_t on = 1) {
            asm volatile("{\n.reg .pred p;\nsetp.ne.b32 p, %1, 0;\n@p mbarrier.arrive.shared::cluster.b64 _, [%0];\n}" ::"r"(rel_base + off), "r"(relw & on) : "memory"); };
        auto handoff = [&](uint32_t on = 1) {
            asm volatile("{\n.reg .pred p;\nsetp.ne.b32 p, %1, 0;\n@p bar.arrive %0, 192;\n}" ::"r"(2 - w), "r"(handw & on) : "memory"); };
        if (cw == 6) bar_arrive(1, 192);

        uint4* qpark = reinterpret_cast<uint4*>(smem_raw + SM_Q - SLOT) + cw * 256 + lane;
        {
            uint32_t h[144];
            const uint4* hf = g_h + (size_t)(qb * 8 + cw) * (36 * 32) + lane;
            auto load_h = [&](auto lo, auto hi) {
#pragma unroll
                for (int ks = lo.value; ks < hi.value; ks++) {
                    const uint4 v = h_frag(hf, ks, lane);
                    h[4 * ks] = v.x; h[4 * ks + 1] = v.y; h[4 * ks + 2] = v.z; h[4 * ks + 3] = v.w;
                }
            };
            auto check_h = [&](auto lo, auto hi) {
                uint32_t it = 0;
                bool miss;
#pragma unroll 1
                do {
                    uint32_t mn = ~0u;
#pragma unroll
                    for (int ks = lo.value; ks < hi.value; ks++) mn = __vimin3_u32(mn, h[4 * ks], h[4 * ks + 2]);
                    miss = __any_sync(0xffffffffu, mn == 0);
                    if (miss) load_h(lo, hi);
                    asm volatile("add.u32 %0, %0, 1;" : "+r"(it));
                } while (miss && it < SPIN / 16);
            };
            auto check_h2 = [&](auto lo, auto hi, auto nx) {
                float f0 = __uint_as_float(~0u), f1 = f0;
                hold(f0, f1);
                auto low = [&]() {
                    uint32_t m0 = __float_as_uint(f0), m1 = m0;
#pragma unroll
                    for (int ks = lo.value; ks < hi.value; ks += 2) { m0 = __vimin3_u32(m0, h[4 * ks], h[4 * ks + 2]); m1 = __vimin3_u32(m1, h[4 * ks + 4], h[4 * ks + 6]); }
                    return min(m0, m1);
                };
                anchor(const_cast<uint4*>(hf), h[4 * hi.value - 1] & __float_as_uint(f0));
                load_h(hi, nx);
                if (__any_sync(0xffffffffu, low() == 0)) {
                    uint32_t it = 0;
#pragma unroll 1
                    do load_h(lo, hi); while (__any_sync(0xffffffffu, low() == 0) && ++it < SPIN / 16);
                }
            };
            __nanosleep(300);
            load_h(IC<0>{}, IC<4>{});
            DBG_T(104); DBG_G(109);
            mbar_wait(bar_w0, 0);
#pragma unroll
            for (int e = E0 + 1; e < E0 + 3; e++) mbar_wait(bar_full + 8 * (e & 3), e >> 2);
#pragma unroll
            for (int i = 0; i < 64; i++) o[i] = 0.f;
            auto group = [&](auto tc, auto ec) {
                constexpr int t = tc.value, e = ec.value, k0 = t ? 8 * t - 4 : 0;
                constexpr bool first = e < E0 + 5, turns = e >= E0 + 4;
                uint64_t dv = (first ? args.d0 : desc_lo(0, UNIT) | (0x40000040ull << 32)) + ((t ? 0 : 512) + (e == E0 ? 6 : e & 3) * (SLOT / 16));
                if (first && t == 0) check_h(IC<0>{}, IC<4>{});
                if (first && t >= 3) mbar_wait(bar_full + 8 * (e & 3), e >> 2);
                if (first && t > 0) check_h2(IC<k0>{}, IC<8 * t + 4>{}, IC<t < 4 ? 8 * t + 12 : 0>{});
                if (t != 1 && turns) bar_sync(1 + w, 192);
                if (t != 1 || first) WG_FENCE();
#pragma unroll
                for (int ks = k0; ks < 8 * t + 4; ks++) {
                    mma_rs128<1>(o, h[4 * ks], h[4 * ks + 1], h[4 * ks + 2], h[4 * ks + 3], dv, ks);
                    if (t && turns && ks == k0 + QSPLIT - 1) WG_COMMIT();
                }
                if (t || first) WG_COMMIT();
                if (first && t == 0) load_h(IC<4>{}, IC<12>{});
                if (t > 0) {
                    WG_WAIT(1);
                    if (turns) handoff();
                    if ((t == 1 && !first) || (t > 1 && e <= E0 + 4)) release4(8 * ((e - 1) & 3));
                    if (turns && e != 18) { WG_WAIT(0); release4(8 * (e & 3)); }
                }
            };
            auto head = [&](auto ec, int slot) {
                constexpr int e = ec.value;
                fence_regs(o);
                group(IC<0>{}, IC<e>{}); group(IC<1>{}, IC<e + 1>{}); group(IC<2>{}, IC<e + 2>{}); group(IC<3>{}, IC<e + 3>{});
                if (e == 15) return;
                group(IC<4>{}, IC<e + 4>{});
                fence_regs(o);
#pragma unroll
                for (int i = 0; i < 8; i++)
                    qpark[slot * 2048 + i * 32] = make_uint4(pack_bf16(o[8 * i], o[8 * i + 1]), pack_bf16(o[8 * i + 2], o[8 * i + 3]),
                                                             pack_bf16(o[8 * i + 4], o[8 * i + 5]), pack_bf16(o[8 * i + 6], o[8 * i + 7]));
            };
            head(IC<E0>{}, 1);
            head(IC<E0 + 5>{}, 2);
            if (SPARE) {
                float (&u)[32] = reinterpret_cast<float (&)[32]>(o);
                fence_regs(u);
#pragma unroll
                for (int t = 0; t < 2; t++) {
                    uint64_t dv = args.d0 + t * (SLOT / 16);
                    bar_sync(1 + w, 192);
                    WG_FENCE();
#pragma unroll
                    for (int ks = 0; ks < 16 + 4 * t; ks++) {
                        mma_rs64<1>(u, h[64 * t + 4 * ks], h[64 * t + 4 * ks + 1], h[64 * t + 4 * ks + 2], h[64 * t + 4 * ks + 3], dv, ks | t);
                        if (ks == 2 * QSPLIT + 4 * t - 1) WG_COMMIT();
                    }
                    WG_COMMIT();
                    WG_WAIT(1);
                    handoff();
                    WG_WAIT(0);
                    release4(8 * t);
                }
                fence_regs(u);
                release4(16);
#pragma unroll
                for (int i = 0; i < 4; i++)
                    qpark[3 * 2048 + i * 32] = make_uint4(pack_bf16(u[8 * i], u[8 * i + 1]), pack_bf16(u[8 * i + 2], u[8 * i + 3]),
                                                          pack_bf16(u[8 * i + 4], u[8 * i + 5]), pack_bf16(u[8 * i + 6], u[8 * i + 7]));
            } else {
                head(IC<10>{}, 3);
            }
            head(IC<15>{}, 0);
#pragma unroll
            for (int i = 0; i < 8; i++) {
                const uint4 v = lds128(smem_u32(qpark + 2048 + i * 32));
                q[4 * i] = v.x; q[4 * i + 1] = v.y; q[4 * i + 2] = v.z; q[4 * i + 3] = v.w;
            }
#pragma unroll
            for (int i = 0; i < 32; i++) p[i] = h[112 + i];
            WG_WAIT(0);
            fence_regs(o);
            release4(16);
        }
        DBG_T(105);
        DBG_G(125);

        uint8_t* frag = reinterpret_cast<uint8_t*>(__shfl_sync(0xffffffffu, reinterpret_cast<unsigned long long>(g_frag + (size_t)(rg * 8 + cw) * WREG + lane * 16), lane));
        const uint4* qnext = reinterpret_cast<const uint4*>(__shfl_sync(0xffffffffu, reinterpret_cast<unsigned long long>(padd(smem_raw, SM_Q + tid * 16 + cw * 3584)), lane));
        uint8_t* odst = reinterpret_cast<uint8_t*>(const_cast<uint4*>(qnext));
        qnext -= 2048;
        float m0, m1, l0 = 0.25f, l1 = 0.25f, t0, t1;
        uint32_t bad = 0;
        auto finish = [&](auto lo, auto hi, uint32_t bit, auto sink) {
#pragma unroll
            for (int i = lo.value; i < hi.value; i++) {
                const uint32_t v0 = pack_bf16(o[8 * i] * t0, o[8 * i + 1] * t0), v1 = pack_bf16(o[8 * i + 2] * t1, o[8 * i + 3] * t1);
                const uint32_t v2 = pack_bf16(o[8 * i + 4] * t0, o[8 * i + 5] * t0), v3 = pack_bf16(o[8 * i + 6] * t1, o[8 * i + 7] * t1);
                if (i == 0 && fabsf(o[0] * t0) >= 0x1p-31f) bad |= bit << 8;
                sink(i, v0, v1, v2, v3);
            }
        };
        float lq[6];
        auto row_parts = [&]() {
#pragma unroll
            for (int i = 0; i < 3; i++) { lq[i] = __shfl_xor_sync(0xffffffffu, l0, i + 1); lq[3 + i] = __shfl_xor_sync(0xffffffffu, l1, i + 1); }
        };
        auto row_sums = [&](uint32_t bit) {
            t0 = (l0 + lq[0]) + (lq[1] + lq[2]); t1 = (l1 + lq[3]) + (lq[4] + lq[5]);
            if (!(t0 >= LMIN && t0 < LMAX && t1 >= LMIN && t1 < LMAX)) bad |= bit;
        };
        auto issue_pv = [&](uint64_t dv, int acc) {
            asm volatile("{\n.reg .pred p;\nsetp.eq.b32 p, %0, 0;\n@p bar.sync 4, 160;\n}" ::"r"(w) : "memory");
#pragma unroll
            for (int ks = 0; ks < 8; ks++)
                mma_rs128<1>(o, p[4 * ks], p[4 * ks + 1], p[4 * ks + 2], p[4 * ks + 3], dv, ks ? 1 : acc);
            WG_COMMIT();
        };
#pragma unroll
        for (int i = 0; i < 64; i++) s[i] = 0.f;
        uint64_t dv_lo = args.d0;
        uint32_t voff = 0;
        auto issue_qk = [&]() {
            uint64_t dk = dv_lo ^ (desc_lo(0, UNIT) ^ desc_lo(3 * SLOT, 16));
            bar_sync(1 + w, 192);
            fence_regs(s); fence_regs(q); fence_regs(o); fence_regs(p);
            WG_FENCE();
#pragma unroll
            for (int ks = 0; ks < 8; ks++)
                if (ks == 3) mma_rs128<0, 1018>(s, q[4 * ks], q[4 * ks + 1], q[4 * ks + 2], q[4 * ks + 3], dk, 1);
                else mma_rs128<0, 2>(s, q[4 * ks], q[4 * ks + 1], q[4 * ks + 2], q[4 * ks + 3], dk, ks != 0);
            WG_COMMIT();
        };
        auto to_frag = [&](int i, uint32_t v0, uint32_t v1, uint32_t v2, uint32_t v3) {
            *reinterpret_cast<uint4*>(odst + i * 512) = make_uint4(v0, v1, v2, v3); };
        int n = 0;
        auto scores_ready = [&]() {
            WG_WAIT(1);
            fence_regs(s); fence_regs(q);
        };
        auto pass_on = [&]() {
            release4(voff ^ 24);
            handoff();
        };
#pragma unroll 1
        for (;;) {
            {
                {
                    asm volatile("st.shared.v2.f32 [%0], {%1, %2};" ::"r"(sb + SM_RED + tid * 8), "f"(l0), "f"(l1) : "memory");
                    __syncwarp();
                    const uint4 a = lds128(sb + SM_RED + (tid & ~3) * 8), b = lds128(sb + SM_RED + (tid & ~3) * 8 + 16);
                    l0 = __uint_as_float(a.x); lq[0] = __uint_as_float(a.z); lq[1] = __uint_as_float(b.x); lq[2] = __uint_as_float(b.z);
                    l1 = __uint_as_float(a.y); lq[3] = __uint_as_float(a.w); lq[4] = __uint_as_float(b.y); lq[5] = __uint_as_float(b.w);
                }
                issue_qk();
                hold(l0, l1);
                row_sums(1u << (n >> 4));
                t0 = rcp_fast(t0); t1 = rcp_fast(t1);
                l0 = 0.f; l1 = 0.f;
                odst = n ? frag + ((n >> 4) - 1) * 4096 : odst;
                qnext = n == 48 ? reinterpret_cast<const uint4*>(frag) : qnext + 2048;
                anchor(bar_full + 504, (t0 + t1) * __uint_as_float((bad ^ (uint32_t)(uintptr_t)odst ^ (uint32_t)(uintptr_t)qnext) & 0x3fffffff));
                asm volatile("{\n.reg .pred p;\nsetp.ne.b32 p, %1, 0;\n@p mbarrier.arrive.shared::cta.b64 _, [%0];\n}"
                             ::"r"(bar_qfree + (n >> 1) - 8), "r"(lane ? 0 : n) : "memory");
                issue_pv(dv_lo, 1);
                scores_ready();
                const uint32_t a = pack_bf16(fmaxf(fmaxf(s[0], s[1]), fmaxf(s[4], s[5])), fmaxf(fmaxf(s[2], s[3]), fmaxf(s[6], s[7])));
                const uint32_t b = bmax2(bmax2(a, __shfl_xor_sync(0xffffffffu, a, 1)), bmax2(__shfl_xor_sync(0xffffffffu, a, 2), __shfl_xor_sync(0xffffffffu, a, 3)));
                pass_on();
                m0 = fmaf(-CS, bf_lo(b), -POFF); m1 = fmaf(-CS, bf_hi(b), -POFF);
            }
#pragma unroll 1
            for (;;) {
                DBG_T(n);
#pragma unroll
                for (int i = 0; i < 4 * STAGE; i++) s[i] = fmaf(s[i], CS, (i & 2) ? m1 : m0);
#pragma unroll
                for (int i = 0; i < 4 * SPLIT; i++) s[i] = ex2(s[i]);
#pragma unroll
                for (int i = 0; i < SPLIT; i++) { l0 += s[4 * i] + s[4 * i + 1]; l1 += s[4 * i + 2] + s[4 * i + 3]; }
                m0 = fmaf(l0, 0.f, m0); m1 = fmaf(l1, 0.f, m1);
                anchor(bar_full + 504, l0 + l1);
                WG_WAIT(0);
                fence_regs(o); fence_regs(p);
                release4(voff);
                dv_lo ^= 2 * SLOT / 16;
                voff ^= 16;
                n++;
#pragma unroll
                for (int i = 4 * STAGE; i < 64; i++) s[i] = fmaf(s[i], CS, (i & 2) ? m1 : m0);
#pragma unroll
                for (int i = 4 * SPLIT; i < 64; i++) s[i] = ex2(s[i]);
#pragma unroll
                for (int i = SPLIT; i < 16; i++) { l0 += s[4 * i] + s[4 * i + 1]; l1 += s[4 * i + 2] + s[4 * i + 3]; }
#pragma unroll
                for (int i = 0; i < 32; i++) p[i] = pack_bf16(s[2 * i], s[2 * i + 1]);
                const int jn = n & 15;
                if (jn > 1) {
                    issue_qk();
                    if ((n & 10) == 2) {
                        if (n & 1) {
#pragma unroll
                            for (int i = 0; i < 64; i++) o[i] *= (i & 2) ? t1 : t0;
                        } else {
                            row_parts();
                            row_sums(2u << (n >> 4));
                            const uint32_t e0 = __float_as_uint(t0) >> 23, e1 = __float_as_uint(t1) >> 23;
                            m0 -= __uint_as_float(0x4b000000u | e0) - (8388608.f + 127.f - POFF);
                            m1 -= __uint_as_float(0x4b000000u | e1) - (8388608.f + 127.f - POFF);
                            t0 = __uint_as_float((254 - (int)POFF - e0) << 23); t1 = __uint_as_float((254 - (int)POFF - e1) << 23);
                            l0 *= t0; l1 *= t1;
                        }
                    }
                    fence_regs(o);
                    WG_FENCE();
                    issue_pv(dv_lo, 1);
                    scores_ready();
                    pass_on();
                    if (jn != 15) continue;
#pragma unroll
                    for (int i = 0; i < 8; i++) {
                        const uint4 v = qnext[i * 32];
                        q[4 * i] = v.x; q[4 * i + 1] = v.y; q[4 * i + 2] = v.z; q[4 * i + 3] = v.w;
                    }
                    continue;
                }
                if (jn == 0) break;
                finish(IC<0>{}, IC<ESPLIT>{}, 1u << (n >> 4), to_frag);
                issue_qk();
                hold(t0, t1);
                finish(IC<ESPLIT>{}, IC<8>{}, 1u << (n >> 4), to_frag);
                WG_FENCE();
                issue_pv(dv_lo, 0);
                scores_ready();
                pass_on();
            }
            if (n == 64) break;
        }
        DBG_T(64);
        uint32_t a1[32], a2[32];
        bar_sync(1 + w, 192);
        fence_regs(o); fence_regs(p);
        WG_FENCE();
        issue_pv(args.d0 + 3 * SLOT / 16, 1);
        handoff();
        mbar_wait(bar_mod, 0);
        const int tid_ = __shfl_sync(0xffffffffu, tid, lane);
        row_parts();
        row_sums(16);
        t0 = rcp_fast(t0); t1 = rcp_fast(t1);
        anchor(frag, q[0] & q[4] & q[8] & q[12] & q[16] & q[20] & q[24] & q[28] & __float_as_uint(t0) & __float_as_uint(t1) & tid_);
        frag_load(a1, frag + 4096);
        frag_load<0, 4>(a2, frag + 8192);
        anchor(frag, bad);
        WG_WAIT(0);
        fence_regs(o); fence_regs(p);
        release4(24);
        finish(IC<0>{}, IC<8>{}, 16, [&](int i, uint32_t v0, uint32_t v1, uint32_t v2, uint32_t v3) {
            p[4 * i] = v0; p[4 * i + 1] = v1; p[4 * i + 2] = v2; p[4 * i + 3] = v3; });
        anchor(frag, p[31] & p[15]);
        frag_load<4, 8>(a2, frag + 8192);
        bad = __reduce_or_sync(0xffffffffu, bad);
        bad = ((bad | ~(bad >> 8)) >> 1) & 15;
        if (__builtin_expect(bad != 0, 0)) {
            uint8_t* keep = g_keep + (size_t)(rg * 8 + cw) * 4096 + lane * 16;
            frag_store(keep, p);
            attn_fallback(bad, tag, gs, frag, keep, args.wq, args.kc, args.vc);
            frag_load(q, frag); frag_load(a1, frag + 4096); frag_load(a2, frag + 8192); frag_load(p, keep);
            anchor(frag, q[0] & q[4] & q[8] & q[12] & q[16] & q[20] & q[24] & q[28] & p[0] & p[4] & p[8] & p[12] & p[16] & p[20] & p[24] & p[28]);
        }
        DBG_T(80);
        DBG_G(124);

        const uint32_t eye = (tid_ >> 3 & 3) == (tid_ & 3) ? 0x3f80u << ((tid_ & 4) * 4) : 0;
        auto sum8 = [&](uint32_t* r, const uint4 (&v)[8]) {
            float d[16];
#pragma unroll
            for (int i = 0; i < 16; i++) d[i] = 0.f;
#pragma unroll
            for (int src = 0; src < 8; src++) {
                mma1688(d + 8 * (src & 1), v[src].x, v[src].y, eye);
                mma1688(d + 8 * (src & 1) + 4, v[src].z, v[src].w, eye);
            }
#pragma unroll
            for (int i = 0; i < 4; i++) r[i] = pack_bf16(d[2 * i] + d[8 + 2 * i], d[2 * i + 1] + d[9 + 2 * i]);
        };
        uint4 v2[8], v3[8], wf[23];
        uint2 u4[8], gw[9];
        uint32_t x1[20], xs, pa, ta;
        const uint8_t *mb, *mb4;
        auto load_wf = [&](auto lo, auto hi) {
            const uint32_t wa = sb + SM_Q + ((tid_ & 8) * (D_ / 8) + cw * 16 + (tid_ & 7) + (tid_ & 16) / 2) * 80;
            const uint32_t wb = wa + (512 - cw * 8) * 80 - (tid_ & 16) * 39;
#pragma unroll
            for (int i = lo.value; i < hi.value; i++) wf[i] = ldsm4t(i < 20 ? wa + (i / 5) * 10240 + (i % 5) * 16 : wb + (i - 20) * 32);
        };
        uint32_t at[18];
        {
            float (&u)[32] = reinterpret_cast<float (&)[32]>(o);
            uint32_t off = 0;
            auto turn = [&](const uint32_t (&a)[32], const uint32_t (&b)[32], int acc) {
                uint64_t dv = args.d0 + off * (SLOT / 128);
                bar_sync(1 + w, 192);
                fence_regs(u);
                WG_FENCE();
#pragma unroll
                for (int ks = 0; ks < 16; ks++) {
                    const uint32_t* f = ks < 8 ? &a[4 * ks] : &b[4 * ks - 32];
                    mma_rs64<1>(u, f[0], f[1], f[2], f[3], dv, ks | acc);
                    if (ks == OSPLIT - 1) WG_COMMIT();
                }
                WG_COMMIT();
                WG_WAIT(1);
            };
            auto done = [&]() {
                WG_WAIT(0);
                fence_regs(u);
                release4(off);
                off = (off + 8) & 24;
            };
            auto store = [&](uint8_t* dst) {
#pragma unroll
                for (int i = 0; i < 4; i++)
                    st_relaxed4(dst + i * 512, pack_bf16(u[8 * i], u[8 * i + 1]), pack_bf16(u[8 * i + 2], u[8 * i + 3]),
                                pack_bf16(u[8 * i + 4], u[8 * i + 5]), pack_bf16(u[8 * i + 6], u[8 * i + 7]));
            };
            pa = sb + w * (UNIT - 2048) + tid_ * 16;
#pragma unroll
            for (int i = 0; i < 8; i++) at[i] = 0;
            fence_regs(q); fence_regs(p);
            uint8_t* dst = frag;
#pragma unroll
            for (int i = 0; i < 8; i++) asm volatile("" : "=r"(v2[i].x), "=r"(v2[i].y), "=r"(v2[i].z), "=r"(v2[i].w));
#pragma unroll 1
            for (int k = 0; k < 8; k++, dst += 2048) {
                const uint32_t poff = (off + 8) & 24;
                const bool sum = (0xa0 >> k) & 1;
                turn(q, p, 0);
                handoff();
                auto sum_p = [&](auto lo, auto hi) {
#pragma unroll
                    for (int i = lo.value; i < hi.value; i++) {
                        float a[8], b[8];
#pragma unroll
                        for (int src = 0; src < 8; src++) {
                            const uint32_t x = i == 0 ? v2[src].x : i == 1 ? v2[src].y : i == 2 ? v2[src].z : v2[src].w;
                            a[src] = bf_lo(x); b[src] = bf_hi(x);
                        }
                        at[i] = at[4 + i];
                        at[4 + i] = pack_bf16(((a[0] + a[2]) + (a[4] + a[6])) + ((a[1] + a[3]) + (a[5] + a[7])),
                                              ((b[0] + b[2]) + (b[4] + b[6])) + ((b[1] + b[3]) + (b[5] + b[7])));
                    }
                };
                if (sum) {
                    mbar_wait(bar_full + poff, 1);
#pragma unroll
                    for (int src = 0; src < 8; src++) v2[src] = lds128(pa + poff * (SLOT / 8) + src * 2048);
                    __syncwarp();
                    release(poff >> 3);
                    done();
                    off = (off + 8) & 24;
                    sum_p(IC<0>{}, IC<2>{});
                } else {
                    done();
                }
                turn(a1, a2, 1);
                handoff();
                if (sum) sum_p(IC<2>{}, IC<4>{});
                done();
                store(dst);
                __syncwarp();
                asm volatile("{\n.reg .pred p;\nsetp.ne.b32 p, %1, 0;\n@p mbarrier.arrive.shared::cta.b64 _, [%0];\n}"
                             ::"r"(bar_pub + 4 + 4 * k), "r"(lane ? 0 : (0x2a >> k) & 1) : "memory");
            }
            turn(q, p, 0);
            handoff();
            mb = padd(g_frag, (qb * 64 + j) * WREG + 3 * 4096 + tid_ * 16);
            mb4 = padd(mb, 4096 + ((cw >> 1) - cw) * 512 + (cw & 1) * 8);
            xs = sb + (tid_ & 15) * XP + (tid_ & 16) + cw * 32;
            ta = sb + (cw * 8 + (tid_ & 3)) * 8;
#pragma unroll
            for (int k = 0; k < 9; k++) {
                gw[k] = lds64(ta + SM_T + (k < 8 ? (k >> 1) * 64 + (k & 1) * 4 : 256 - cw * 4) * 8);
                if (!(tid_ & 4)) gw[k].y = 0x3f803f80u;
            }
            mbar_wait(bar_g, 0);
            done();
            load_wf(IC<0>{}, IC<WF0>{});
            turn(a1, a2, 1);
            if (w == 0) handoff();
            done();
            store(dst);
            mbar_wait(bar_full, 0);
            rows_load(x1, xs, cw);
            if (w == 0) bar_sync(5, 256); else bar_arrive(5, 256);
        }
        DBG_T(81);
        DBG_G(122);

        {
        const int tid = tid_, lane = tid & 31;
        const int g8 = lane >> 2, qd = lane & 3, l16 = lane & 15;
        uint32_t h2[18], gb[9], k1, k2;
        float4* rec = reinterpret_cast<float4*>(red + 128);
        const uint2* candp = reinterpret_cast<const uint2*>(padd(g_cand, ((blockIdx.x & (CREP - 1)) * NCTA + (tid >> 1)) * 32 + (tid & 1) * 8));
        uint2 cd;
        auto stage_out = [&]() {
#pragma unroll
            for (int k = 0; k < 9; k++) {
                x1[2 * k] = badd2(x1[2 * k], bmul2(gb[k], h2[2 * k]));
                x1[2 * k + 1] = badd2(x1[2 * k + 1], bmul2(gb[k], h2[2 * k + 1]));
            }
#pragma unroll
            for (int ch = 0; ch < 4; ch++) stsm_x4(xs + ch * 256, x1[4 * ch], x1[4 * ch + 1], x1[4 * ch + 2], x1[4 * ch + 3]);
            asm volatile("stmatrix.sync.aligned.m8n8.x2.shared.b16 [%0], {%1, %2};" ::"r"(xs + 1024 - cw * 16), "r"(x1[16]), "r"(x1[17]) : "memory");
        };
        {
            uint32_t it = 0, miss;
            mbar_wait(bar_full + 8, 0);
#pragma unroll
            for (int src = 0; src < 8; src++) v2[src] = lds128(pa + SLOT + src * 2048);
            sum8(at + 8, v2);
            float st[12];
#pragma unroll
            for (int i = 0; i < 12; i++) st[i] = 0.f;
            auto add_pair = [&](int k) {
                x1[2 * k] = badd2(x1[2 * k], bmul2(gw[k].x, at[2 * k]));
                x1[2 * k + 1] = badd2(x1[2 * k + 1], bmul2(gw[k].x, at[2 * k + 1]));
                stats_add(st, x1[2 * k], x1[2 * k + 1], gw[k].y);
            };
#pragma unroll
            for (int k = 0; k < 6; k++) add_pair(k);
            mbar_wait(bar_full + 16, 0);
#pragma unroll
            for (int src = 0; src < 8; src++) v3[src] = lds128(pa + 2 * SLOT + src * 2048);
            miss = __vimax3_u32(__vimax3_u32(v3[0].x, v3[0].z, v3[1].x), __vimax3_u32(v3[1].z, v3[2].x, v3[2].z), __vimax3_u32(v3[3].x, v3[3].z, v3[4].x));
            miss = __vimax3_u32(miss, __vimax3_u32(v3[4].z, v3[5].x, v3[5].z), max(__vimax3_u32(v3[6].x, v3[6].z, v3[7].x), v3[7].z));
            if (__any_sync(0xffffffffu, miss == ~0u))
#pragma unroll 1
            do {
                miss = 0;
#pragma unroll
                for (int src = 0; src < 8; src++) reload16(v3[src], mb + (size_t)src * 8 * WREG, miss);
            } while (__any_sync(0xffffffffu, miss) && ++it < SPIN / 16);
            if (lane < 4) mbar_arrive_cluster(rel_base + 8 * (1 + (lane >> 1)));
            sum8(at + 12, v3);
            add_pair(6); add_pair(7);
            load_wf(IC<WF0>{}, IC<WF1>{});
            uint2 cs[9];
#pragma unroll
            for (int k = 0; k < 9; k++) cs[k] = lds64(ta + SM_TC + (k < 8 ? (k >> 1) * 64 + (k & 1) * 4 : 256 - cw * 4) * 8);
            mbar_wait(bar_pre, 0);
            mbar_wait(bar_full + 24, 0);
#pragma unroll
            for (int src = 0; src < 8; src++) u4[src] = lds64(sb + 3 * SLOT + src * 2048 + (cw >> 1) * 512 + lane * 16 + (cw & 1) * 8);
            miss = __vimax3_u32(__vimax3_u32(u4[0].x, u4[1].x, u4[2].x), __vimax3_u32(u4[3].x, u4[4].x, u4[5].x), max(u4[6].x, u4[7].x));
            if (__any_sync(0xffffffffu, miss == ~0u))
#pragma unroll 1
            do {
                miss = 0;
#pragma unroll
                for (int src = 0; src < 8; src++) reload8(u4[src], mb4 + (size_t)src * 8 * WREG, miss);
            } while (__any_sync(0xffffffffu, miss) && ++it < SPIN / 16);
            float d[8] = {0.f, 0.f, 0.f, 0.f, 0.f, 0.f, 0.f, 0.f};
#pragma unroll
            for (int i = 0; i < 4; i++) mma16816(d + 4 * (i & 1), u4[2 * i].x, u4[2 * i].y, u4[2 * i + 1].x, u4[2 * i + 1].y, eye, eye);
            at[16] = pack_bf16(d[0] + d[4], d[1] + d[5]); at[17] = pack_bf16(d[2] + d[6], d[3] + d[7]);
            add_pair(8);
            DBG_G(123);
            const float2 ws = *reinterpret_cast<const float2*>(smem_raw + SM_TS);
            uint4* cdst = padd(g_cand, (tid * NCTA + rg) * 32);
            uint32_t mean2;
            float dot;
            const float rsd = rows_stats(st, rec, cw, lane, mean2, dot);
            const uint32_t b = __float_as_uint(fmaf(fmaf(-bf_lo(mean2), ws.x, dot), rsd, ws.y));
            const uint32_t key = (((b & 0x80000000u) ? ~b : (b | 0x80000000u)) | 2047u) - (rg * 16 + l16);
            top2(key, k1, k2);
            if (tid < CREP) st_relaxed(cdst, k1, tag, k2, tag);
            cd = ld_relaxed64(candp);
            rows_normalise(h2, x1, mean2, rsd, lane, [&]() {
#pragma unroll
                for (int k = 0; k < 9; k++) gb[k] = lds32(sb + SM_TG + (cw * 8 + qd + (k < 8 ? (k >> 1) * 64 + (k & 1) * 4 : 256 - cw * 4)) * 4);
                load_wf(IC<WF1>{}, IC<WF2>{});
            });
#pragma unroll
            for (int k = 0; k < 18; k++) h2[k] = badd2(bmul2(h2[k], cs[k >> 1].x), cs[k >> 1].y);
            const uint32_t r1 = ~k1 & 15, r2 = ~k2 & 15;
            uint32_t todo = ((r1 & 7) == g8) | ((r2 & 7) == g8) << 1;
#pragma unroll 1
            while (todo) {
                const bool second = !(todo & 1), hi = (second ? r2 : r1) & 8;
                uint4* dst = padd(g_rows, ((rg * 2 + second) * RSLOT + cw * 24 + qd) * 16);
                uint32_t r[18];
#pragma unroll
                for (int k = 0; k < 9; k++) { r[k] = hi ? h2[2 * k + 1] : h2[2 * k]; r[9 + k] = hi ? x1[2 * k + 1] : x1[2 * k]; }
                fence_regs(r);
                st_relaxed(dst, r[0], r[1], r[2], r[3]);
                st_relaxed(dst + 8, r[4], r[5], r[6], r[7]);
                st_relaxed64(reinterpret_cast<uint2*>(padd(dst, 256 - qd * 8)), r[8], r[17]);
                st_relaxed(dst + 4, r[9], r[10], r[11], r[12]);
                st_relaxed(dst + 12, r[13], r[14], r[15], r[16]);
                todo &= todo - 1;
            }
            __syncwarp();

            stage_out();
        }
        DBG_G(110);
        float4* part = reinterpret_cast<float4*>(smem_raw + 3 * SLOT + UNIT + 8192);
        bf16* act = reinterpret_cast<bf16*>(smem_raw + 3 * SLOT + UNIT + 4096);
        {
            uint32_t it = 0;
            const bool own = (tid >> 1) == rg;
            const uint32_t ks = sb + 3 * SLOT + UNIT + 5120;
#pragma unroll 1
            while (__any_sync(0xffffffffu, cd.y != tag && !own) && ++it < SPIN / 16)
                asm volatile("{\n.reg .pred p;\n.reg .b64 u;\nsetp.ne.u32 p, %1, %3;\nmov.b64 u, {%0, %1};\n"
                             "@p ld.relaxed.gpu.global.b64 u, [%2];\nmov.b64 {%0, %1}, u;\n}" : "+r"(cd.x), "+r"(cd.y) : "l"(candp), "r"(tag) : "memory");
            asm volatile("st.shared.u32 [%0], %1;" ::"r"(ks + tid * 4), "r"(own ? (tid & 1) ? k2 : k1 : cd.x) : "memory");
            bar_sync(3, 256);
            DBG_G(111);
            const uint4 a = lds128(ks + lane * 16), b = lds128(ks + 512 + lane * 16);
            const uint32_t a1 = max(a.x, a.z), a2 = __vimax3_u32(min(a.x, a.z), a.y, a.w);
            const uint32_t b1 = max(b.x, b.z), b2 = __vimax3_u32(min(b.x, b.z), b.y, b.w);
            const uint32_t c1 = max(a1, b1), c2 = __vimax3_u32(min(a1, b1), a2, b2);
            k1 = __reduce_max_sync(0xffffffffu, c1);
            k2 = __reduce_max_sync(0xffffffffu, c1 == k1 ? c2 : c1);
        }
        const int sel0 = ~k1 & 2047, sel1 = ~k2 & 2047;
        const uint32_t slot0 = (sel0 >> 4) * 2, slot1 = (sel1 >> 4) * 2 + ((sel0 ^ sel1) < 16);
        uint4 da[13];
        {
            const uint4* hp = padd(g_rows, (((g8 & 1) ? slot1 : slot0) * RSLOT + cw * 24 + qd) * 16);
            const uint2* hp2 = reinterpret_cast<const uint2*>(padd(hp, 256 - qd * 8));
            uint4 hv[2] = {ld_relaxed2(hp), ld_relaxed2(hp + 8)};
            uint2 hw = ld_relaxed64(hp2);
            if (tid == 255) {
                reinterpret_cast<int2*>(red)[8] = make_int2(sel0, sel1);
                mbar_arrive(bar_out);
            }
            load_wf(IC<WF2>{}, IC<23>{});
            mbar_wait(bar_full + 8, 1);
            mbar_wait(bar_full + 16, 1);
            auto load_d = [&](auto lo, auto hi) {
                const int r = (lane & 7) + (lane & 16) / 2;
                const uint32_t d0 = sb + SLOT + r * XP + cw * 144 + (lane & 8) * 2, d1 = d0 + (r < 2 ? 16 * XP : SLOT - 2 * XP);
                const uint32_t d2 = sb + 2 * SLOT + (14 + (lane & 3)) * XP + cw * 144 + (lane >> 3) * 16;
#pragma unroll
                for (int i = lo.value; i < hi.value; i++) da[i] = ldsm4t(i < 10 ? ((i & 1) ? d1 : d0) + (i >> 1) * 32 : d2 + (i - 10) * 64);
            };
            load_d(IC<0>{}, IC<DL>{});
            uint32_t it = 0, miss;
            float f0 = 1.f, f1 = 1.f;
            hold(f0, f1);
            if (__any_sync(0xffffffffu, max(__vimax3_u32(__vimax3_u32(__float_as_uint(f0), hv[0].x, hv[0].z), hv[1].x, hv[1].z), hw.x) == ~0u))
#pragma unroll 1
            do {
                miss = 0;
                reload16(hv[0], hp, miss);
                reload16(hv[1], hp + 8, miss);
                reload8(hw, hp2, miss);
            } while (__any_sync(0xffffffffu, miss) && ++it < SPIN / 16);
            DBG_G(112);
            float acc[20];
#pragma unroll
            for (int i = 0; i < 20; i++) acc[i] = 0.f;
#pragma unroll
            for (int i = 0; i < 5; i++) mma1688(acc + 4 * i, (i & 1) ? wf[20 + i / 2].z : wf[20 + i / 2].x, (i & 1) ? wf[20 + i / 2].w : wf[20 + i / 2].y, hw.x);
#pragma unroll
            for (int i = 0; i < 20; i++)
                mma16816(acc + 4 * (i % 5), wf[i].x, wf[i].y, wf[i].z, wf[i].w, (i / 5 & 1) ? hv[i / 10].z : hv[i / 10].x, (i / 5 & 1) ? hv[i / 10].w : hv[i / 10].y);
            if (qd == 0) {
#pragma unroll
                for (int i = 0; i < 5; i++) part[cw * 40 + i * 8 + g8] = make_float4(acc[4 * i], acc[4 * i + 1], acc[4 * i + 2], acc[4 * i + 3]);
            }
            load_d(IC<DL>{}, IC<13>{});
        }
        {
            uint2* dst = padd(g_ypart, ((cw * 9 * NCTA + blockIdx.x) * 8 + g8) * 8);
            bar_sync(3, 256);
            if (cw < 5) {
                const float* pp = reinterpret_cast<const float*>(part) + ((blockIdx.x & 1) << 4) + tid;
                const float g = rbf(((pp[0] + pp[160]) + (pp[320] + pp[480])) + ((pp[640] + pp[800]) + (pp[960] + pp[1120])));
                const float v = rbf(g * sigmoidf_(g)) * __shfl_down_sync(0xffffffffu, g, 2);
                if (!(tid & 2)) act[(tid & 1) * 56 + (tid >> 2)] = __float2bfloat16_rn(tid < 144 ? v : 0.f);
            }
            bar_sync(3, 256);
            DBG_G(113);
            const uint32_t ap = sb + 3 * SLOT + UNIT + 4096 + (lane & 1) * 112 + (lane >> 3) * 16;
            const uint4 b0 = ldsm4(ap);
            const uint32_t b1 = lds32(sb + 3 * SLOT + UNIT + 4096 + (g8 & 1) * 112 + 64 + qd * 4);
            float y[20];
#pragma unroll
            for (int i = 0; i < 20; i++) y[i] = 0.f;
#pragma unroll
            for (int i = 0; i < 5; i++) {
                mma16816(y + 4 * i, da[2 * i].x, da[2 * i].y, da[2 * i].z, da[2 * i].w, b0.x, b0.y);
                mma16816(y + 4 * i, da[2 * i + 1].x, da[2 * i + 1].y, da[2 * i + 1].z, da[2 * i + 1].w, b0.z, b0.w);
                mma1688(y + 4 * i, (i & 1) ? da[10 + i / 2].z : da[10 + i / 2].x, (i & 1) ? da[10 + i / 2].w : da[10 + i / 2].y, b1);
            }
            if (qd == 0) {
#pragma unroll
                for (int i = 0; i < 9; i++)
                    asm volatile("st.relaxed.gpu.global.v2.f32 [%0], {%1, %2};" ::"l"(dst + i * (NCTA * 8)), "f"(y[2 * i]), "f"(y[2 * i + 1]) : "memory");
            }
        }
        DBG_G(114);
        if (blockIdx.x < 72) {
            const int G = blockIdx.x, tok = g8 & 1, cp = G * 4 + qd;
            const uint2* src = padd(g_ypart, (blockIdx.x * NCTA * 8 + tid) * 8);
            const uint8_t* hsrc = reinterpret_cast<const uint8_t*>(padd(g_rows, (tok ? slot1 : slot0) * (RSLOT * 16) +
                (G < 64 ? (G >> 1 & 7) * 384 + (G >> 5) * 128 + qd * 16 + (G >> 1 & 8) + (G & 1) * 4 : (G - 64) * 384 + 256 + qd * 8)));
            const uint8_t* xsrc = hsrc + (G < 64 ? 64 : 4);
            uint32_t* dst = padd(reinterpret_cast<uint32_t*>(args.out), (tok ? sel1 : sel0) * (D_ * 2) + cp * 4);
            const uint32_t gb = reinterpret_cast<const uint32_t*>(smem_raw + SM_TG)[cp];
            const uint32_t ksel = ((tok ? k2 : k1) & ~2047u) | 1024u;
            const float sg = sigmoidf_(rbf(__uint_as_float((ksel & 0x80000000u) ? (ksel & 0x7fffffffu) : ~ksel)));
            uint2 v[4];
            uint32_t hv = 0, xv = 0, it = 0, miss;
            if (cw == 0) { hv = ld_relaxed32(hsrc); xv = ld_relaxed32(xsrc); }
#pragma unroll
            for (int i = 0; i < 4; i++) v[i] = make_uint2(~0u, 0);
#pragma unroll 1
            do {
#pragma unroll
                for (int i = 0; i < 4; i++) reload8(v[i], src + i * 256, miss);
            } while (__any_sync(0xffffffffu, max(__vimax3_u32(v[0].x, v[1].x, v[2].x), v[3].x) == ~0u) && ++it < SPIN / 16);
#pragma unroll 1
            while (max(hv, xv) == ~0u && ++it < SPIN / 16) { hv = ld_relaxed32(hsrc); xv = ld_relaxed32(xsrc); }
            __syncwarp();
            float y0 = (__uint_as_float(v[0].x) + __uint_as_float(v[1].x)) + (__uint_as_float(v[2].x) + __uint_as_float(v[3].x));
            float y1 = (__uint_as_float(v[0].y) + __uint_as_float(v[1].y)) + (__uint_as_float(v[2].y) + __uint_as_float(v[3].y));
            y0 += __shfl_xor_sync(0xffffffffu, y0, 8); y1 += __shfl_xor_sync(0xffffffffu, y1, 8);
            y0 += __shfl_xor_sync(0xffffffffu, y0, 16); y1 += __shfl_xor_sync(0xffffffffu, y1, 16);
            if (lane < 8) reinterpret_cast<float2*>(rec)[cw * 8 + lane] = make_float2(y0, y1);
            bar_sync(3, 256);
            if (cw == 0) {
                const float4 t0_ = rec[(lane >> 3) * 4 + qd], t1_ = rec[16 + (lane >> 3) * 4 + qd];
                y0 = tok ? t0_.y + t1_.y : t0_.x + t1_.x; y1 = tok ? t0_.w + t1_.w : t0_.z + t1_.z;
                y0 += __shfl_xor_sync(0xffffffffu, y0, 8); y1 += __shfl_xor_sync(0xffffffffu, y1, 8);
                y0 += __shfl_xor_sync(0xffffffffu, y0, 16); y1 += __shfl_xor_sync(0xffffffffu, y1, 16);
                const uint32_t y2 = bmul2(pack_bf16(y0, y1), pack_bf16(sg, sg));
                if (lane < 8) *dst = badd2(xv, bmul2(gb, badd2(hv, y2)));
            }
        }
        }
        DBG_T(88);
        DBG_G(121);
    }
}

typedef CUresult (*EncodeFn)(CUtensorMap*, CUtensorMapDataType, cuuint32_t, void*, const cuuint64_t*, const cuuint64_t*,
                             const cuuint32_t*, const cuuint32_t*, CUtensorMapInterleave, CUtensorMapSwizzle,
                             CUtensorMapL2promotion, CUtensorMapFloatOOBfill);

static void make_map(EncodeFn enc, CUtensorMap* m, const void* ptr, int rank, const cuuint64_t* dims,
                     const cuuint64_t* strides, const cuuint32_t* box, CUtensorMapSwizzle sw = CU_TENSOR_MAP_SWIZZLE_128B,
                     CUtensorMapDataType dt = CU_TENSOR_MAP_DATA_TYPE_BFLOAT16) {
    const cuuint32_t es[3] = {1, 1, 1};
    enc(m, dt, rank, const_cast<void*>(ptr), dims, strides, box, es,
        CU_TENSOR_MAP_INTERLEAVE_NONE, sw, CU_TENSOR_MAP_L2_PROMOTION_L2_128B,
        CU_TENSOR_MAP_FLOAT_OOB_FILL_NONE);
}

extern "C" void kernel_launch(void* const* d_in, const int* in_sizes, int n_in, void* d_out, int out_size) {
    const bf16* x = (const bf16*)d_in[0];
    const bf16* kc = (const bf16*)d_in[1];
    const bf16* vc = (const bf16*)d_in[2];
    const bf16* wq = (const bf16*)d_in[3];
    const bf16* wo = (const bf16*)d_in[4];
    const bf16* w_r = (const bf16*)d_in[6];
    const bf16* w_gate = (const bf16*)d_in[7];
    const bf16* w_up = (const bf16*)d_in[8];
    const bf16* w_down = (const bf16*)d_in[9];
    const bf16* cvec = (const bf16*)d_in[10];
    const bf16* w_mod = (const bf16*)d_in[11];
    bf16* out = (bf16*)d_out;

    void* fn = nullptr;
    cudaDriverEntryPointQueryResult qr;
    cudaGetDriverEntryPoint("cuTensorMapEncodeTiled", &fn, cudaEnableDefault, &qr);
    EncodeFn enc = (EncodeFn)fn;
    void* p_s;
    cudaGetSymbolAddress(&p_s, g_s);

    CUtensorMap tm_wq, tm_k, tm_v, tm_wo, tm_p, tm_x, tm_d, tm_g, tm_u;
    { cuuint64_t d[2] = {QD, D_}, s[1] = {QD * 2}; cuuint32_t b[2] = {64, 128}; make_map(enc, &tm_wq, wq, 2, d, s, b); }
    { cuuint64_t d[2] = {DH, HKV * S_}, s[1] = {DH * 2}; cuuint32_t b[2] = {64, 128};
      make_map(enc, &tm_k, kc, 2, d, s, b); make_map(enc, &tm_v, vc, 2, d, s, b); }
    { cuuint64_t d[2] = {D_, QD}, s[1] = {D_ * 2}; cuuint32_t b[2] = {64, 128}; make_map(enc, &tm_wo, wo, 2, d, s, b); }
    { cuuint64_t d[3] = {256, 160, NCTA}, s[2] = {1024, 8 * WREG}; cuuint32_t b[3] = {256, 2, 8};
      make_map(enc, &tm_p, ((Scratch*)p_s)->frag, 3, d, s, b, CU_TENSOR_MAP_SWIZZLE_NONE, CU_TENSOR_MAP_DATA_TYPE_UINT32); }
    { cuuint64_t d[2] = {D_ / 4, S_}, s[1] = {D_ * 2}; cuuint32_t b[2] = {XP / 8, 16};
      make_map(enc, &tm_x, x, 2, d, s, b, CU_TENSOR_MAP_SWIZZLE_NONE, CU_TENSOR_MAP_DATA_TYPE_UINT64); }
    { cuuint64_t d[2] = {D_ / 4, F_}, s[1] = {D_ * 2}; cuuint32_t b[2] = {XP / 8, 18};
      make_map(enc, &tm_d, w_down, 2, d, s, b, CU_TENSOR_MAP_SWIZZLE_NONE, CU_TENSOR_MAP_DATA_TYPE_UINT64); }
    { cuuint64_t d[2] = {F_, D_}, s[1] = {F_ * 2}; cuuint32_t b[2] = {40, 24};
      make_map(enc, &tm_g, w_gate, 2, d, s, b, CU_TENSOR_MAP_SWIZZLE_NONE); make_map(enc, &tm_u, w_up, 2, d, s, b, CU_TENSOR_MAP_SWIZZLE_NONE); }

    cudaFuncSetAttribute(fused_kernel<true>, cudaFuncAttributeMaxDynamicSharedMemorySize, SM_TOTAL);
    cudaFuncSetAttribute(fused_kernel<false>, cudaFuncAttributeMaxDynamicSharedMemorySize, SM_TOTAL);
    cudaLaunchConfig_t cfg = {};
    cfg.gridDim = NCTA + 4; cfg.blockDim = 384; cfg.dynamicSmemBytes = SM_TOTAL;
    cudaLaunchAttribute at;
    at.id = cudaLaunchAttributeClusterDimension; at.val.clusterDim.x = 2; at.val.clusterDim.y = 1; at.val.clusterDim.z = 1;
    cfg.attrs = &at; cfg.numAttrs = 1;
    int ncl = 0;
    if (cudaOccupancyMaxActiveClusters(&ncl, fused_kernel<true>, &cfg) != cudaSuccess) { ncl = 0; cudaGetLastError(); }
    Args args{w_mod, cvec, (Scratch*)p_s, desc_lo(0, UNIT) | (0x40000040ull << 32), out, x, kc, vc, wq, wo, w_r, w_down};
    if (USE_SPARE && ncl >= NCTA / 2 + 2)
        fused_kernel<true><<<NCTA + 4, 384, SM_TOTAL>>>(args, tm_wq, tm_k, tm_v, tm_wo, tm_p, tm_x, tm_d, tm_g, tm_u);
    else
        fused_kernel<false><<<NCTA, 384, SM_TOTAL>>>(args, tm_wq, tm_k, tm_v, tm_wo, tm_p, tm_x, tm_d, tm_g, tm_u);
}
```

```cpp
#include <cuda_runtime.h>
#include <cuda_bf16.h>
#include <cuda.h>
#include <stdint.h>
#include <math.h>

typedef __nv_bfloat16 bf16;

constexpr int S_ = 2048;
constexpr int D_ = 576;
constexpr int HQ = 32, HKV = 16, DH = 128;
constexpr int F_ = 4608;
constexpr int QD = HQ * DH;

constexpr int NCTA = 128;
constexpr int WREG = 5 * 4096;
constexpr int CREP = 8;
constexpr int RSLOT = 192;
constexpr int MREP = 4;
struct Scratch {
    unsigned int epoch[128];
    unsigned int flag_mod[NCTA];
    unsigned int flag_part[16 * 256];
    unsigned int flag_q3[16 * 32];
    unsigned int flag_h[NCTA * 32];
    uint2 mod1[MREP * D_];
    uint32_t mod2[4 * D_];
    uint4 cand[CREP * NCTA * 2];
    uint2 ypart[72 * NCTA * 8];
    uint4 h[2][NCTA * 36 * 32];
    uint4 q3[NCTA * 8 * 128];
    uint4 rows[NCTA * 2 * RSLOT];
    uint8_t frag[NCTA * 8 * WREG];
    uint8_t keep[NCTA * 8 * 4096];
};
__device__ __align__(1024) Scratch g_s;
#define g_h gs->h[tag & 1]
#define g_q3 gs->q3
#define g_keep gs->keep
#define g_flag_h gs->flag_h
#define g_flag_part gs->flag_part
#define g_flag_mod gs->flag_mod
#define g_flag_q3 gs->flag_q3
#define g_frag gs->frag
#define g_cand gs->cand
#define g_ypart gs->ypart
#define g_rows gs->rows

#define DBG_INIT()
#define DBG_P(i)
#define DBG_PG(i)
#define DBG_T(i)
#define DBG_G(i)

__device__ __forceinline__ uint32_t pack_bf16(float lo, float hi) {
    uint32_t r;
    asm("cvt.rn.bf16x2.f32 %0, %1, %2;" : "=r"(r) : "f"(hi), "f"(lo));
    return r;
}
__device__ __forceinline__ float rbf(float x) { return __uint_as_float(pack_bf16(0.f, x)); }
__device__ __forceinline__ float bf_lo(uint32_t v) { return __uint_as_float(v << 16); }
__device__ __forceinline__ float bf_hi(uint32_t v) { return __uint_as_float(v & 0xffff0000u); }
__device__ __forceinline__ float ex2(float x) {
    float y;
    asm("ex2.approx.ftz.f32 %0, %1;" : "=f"(y) : "f"(x));
    return y;
}
template <class T>
__device__ __forceinline__ T* padd(T* p, uint32_t off) {
    unsigned long long r;
    asm("{\n.reg .b32 l, h;\nmov.b64 {l, h}, %1;\nadd.cc.u32 l, l, %2;\naddc.u32 h, h, 0;\nmov.b64 %0, {l, h};\n}" : "=l"(r) : "l"(p), "r"(off));
    return reinterpret_cast<T*>(r);
}
__device__ __forceinline__ uint32_t smem_u32(const void* p) { return (uint32_t)__cvta_generic_to_shared(p); }
__device__ __forceinline__ void mbar_init(uint32_t bar, uint32_t cnt) {
    asm volatile("mbarrier.init.shared::cta.b64 [%0], %1;" ::"r"(bar), "r"(cnt) : "memory");
}
__device__ __forceinline__ void mbar_expect_tx(uint32_t bar, uint32_t bytes) {
    asm volatile("mbarrier.arrive.expect_tx.shared::cta.b64 _, [%0], %1;" ::"r"(bar), "r"(bytes) : "memory");
}
__device__ __forceinline__ void mbar_arrive(uint32_t bar) {
    asm volatile("mbarrier.arrive.shared::cta.b64 _, [%0];" ::"r"(bar) : "memory");
}
__device__ __forceinline__ void arrive_if(uint32_t bar, bool on) {
    asm volatile("{\n.reg .pred p;\nsetp.ne.b32 p, %1, 0;\n@p mbarrier.arrive.shared::cta.b64 _, [%0];\n}" ::"r"(bar), "r"((uint32_t)on) : "memory");
}
__device__ __forceinline__ void mbar_arrive_cluster(uint32_t cluster_addr) {
    asm volatile("mbarrier.arrive.shared::cluster.b64 _, [%0];" ::"r"(cluster_addr) : "memory");
}
constexpr uint32_t SPIN = 1u << 20;
__device__ __forceinline__ void mbar_wait(uint32_t bar, uint32_t parity) {
    asm volatile("{\n.reg .pred p;\n.reg .b32 c;\nmov.b32 c, 0;\n"
                 "W_%=:\nmbarrier.try_wait.parity.shared::cta.b64 p, [%0], %1;\n"
                 "add.u32 c, c, 1;\nsetp.lt.and.u32 p, c, 0x100000, !p;\n@p bra W_%=;\n}"
                 ::"r"(bar), "r"(parity) : "memory");
}
__device__ __forceinline__ void anchor(uint32_t addr, float v) {
    asm volatile("{\n.reg .pred p;\nsetp.lt.f32 p, %1, 0f00000000;\n@p st.volatile.shared.f32 [%0], %1;\n}" ::"r"(addr), "f"(v) : "memory");
}
__device__ __forceinline__ void anchor(uint32_t addr, uint32_t v) {
    asm volatile("{\n.reg .pred p;\nsetp.eq.u32 p, %1, 0xffffffff;\n@p st.volatile.shared.u32 [%0], %1;\n}" ::"r"(addr), "r"(v) : "memory");
}
__device__ __forceinline__ void anchor(void* p, uint32_t v) {
    asm volatile("{\n.reg .pred p;\nsetp.eq.u32 p, %1, 0xffffffff;\n@p st.volatile.u32 [%0], %1;\n}" ::"l"(p), "r"(v) : "memory");
}
__device__ __forceinline__ void hold(float& a, float& b) {
    asm volatile("{\n.reg .pred p;\n.reg .b64 t;\n.reg .b32 l, h;\nmov.u64 t, %%clock64;\nmov.b64 {l, h}, t;\nsetp.eq.u32 p, h, 0xffffffff;\n"
                 "@p mov.f32 %0, 0f00000000;\n@p mov.f32 %1, 0f00000000;\n}" : "+f"(a), "+f"(b) :: "memory");
}
__device__ __forceinline__ void mbar_wait_sleep(uint32_t bar, uint32_t parity) {
    asm volatile("{\n.reg .pred p;\n.reg .b32 c;\nmov.b32 c, 0;\n"
                 "W_%=:\nmbarrier.try_wait.parity.shared::cta.b64 p, [%0], %1, 5000;\n"
                 "add.u32 c, c, 1;\nsetp.lt.and.u32 p, c, 0x20000, !p;\n@p bra W_%=;\n}"
                 ::"r"(bar), "r"(parity) : "memory");
}
__device__ __forceinline__ uint32_t load_tag(const Scratch* gs) {
    uint32_t tag;
    asm volatile("ld.global.ca.u32 %0, [%1];" : "=r"(tag) : "l"(gs->epoch) : "memory");
    return tag + 1;
}
__device__ __forceinline__ uint4 ld_relaxed(const uint4* p) {
    uint4 v;
    asm volatile("ld.relaxed.gpu.global.v4.u32 {%0,%1,%2,%3}, [%4];" : "=r"(v.x), "=r"(v.y), "=r"(v.z), "=r"(v.w) : "l"(p) : "memory");
    return v;
}
__device__ __forceinline__ void st_relaxed(uint4* p, uint32_t a, uint32_t b, uint32_t c, uint32_t d) {
    asm volatile("{\n.reg .b64 u, v;\nmov.b64 u, {%1, %2};\nmov.b64 v, {%3, %4};\nst.relaxed.gpu.global.v2.b64 [%0], {u, v};\n}"
                 ::"l"(p), "r"(a), "r"(b), "r"(c), "r"(d) : "memory");
}
__device__ __forceinline__ void st_relaxed4(void* p, uint32_t a, uint32_t b, uint32_t c, uint32_t d) {
    asm volatile("st.relaxed.gpu.global.v4.u32 [%0], {%1, %2, %3, %4};" ::"l"(p), "r"(a), "r"(b), "r"(c), "r"(d) : "memory");
}
__device__ __forceinline__ uint2 ld_relaxed64(const uint2* p) {
    uint2 v;
    asm volatile("{\n.reg .b64 u;\nld.relaxed.gpu.global.b64 u, [%2];\nmov.b64 {%0, %1}, u;\n}" : "=r"(v.x), "=r"(v.y) : "l"(p) : "memory");
    return v;
}
__device__ __forceinline__ void st_relaxed64(uint2* p, uint32_t a, uint32_t b) {
    asm volatile("{\n.reg .b64 u;\nmov.b64 u, {%1, %2};\nst.relaxed.gpu.global.b64 [%0], u;\n}" ::"l"(p), "r"(a), "r"(b) : "memory");
}
__device__ __forceinline__ uint4 ld_relaxed2(const uint4* p) {
    uint4 v;
    asm volatile("{\n.reg .b64 u, w;\nld.relaxed.gpu.global.v2.b64 {u, w}, [%4];\nmov.b64 {%0, %1}, u;\nmov.b64 {%2, %3}, w;\n}"
                 : "=r"(v.x), "=r"(v.y), "=r"(v.z), "=r"(v.w) : "l"(p) : "memory");
    return v;
}
__device__ __forceinline__ void reload16(uint4& v, const void* p, uint32_t& miss) {
    asm volatile("{\n.reg .pred p;\n.reg .b32 m;\n.reg .b64 u, w;\nmax.u32 m, %0, %2;\nsetp.eq.u32 p, m, 0xffffffff;\n"
                 "mov.b64 u, {%0, %1};\nmov.b64 w, {%2, %3};\n@p ld.relaxed.gpu.global.v2.b64 {u, w}, [%5];\n"
                 "mov.b64 {%0, %1}, u;\nmov.b64 {%2, %3}, w;\n@p mov.u32 %4, 1;\n}"
                 : "+r"(v.x), "+r"(v.y), "+r"(v.z), "+r"(v.w), "+r"(miss) : "l"(p) : "memory");
}
__device__ __forceinline__ void reload8(uint2& v, const void* p, uint32_t& miss) {
    asm volatile("{\n.reg .pred p;\n.reg .b64 u;\nsetp.eq.u32 p, %0, 0xffffffff;\nmov.b64 u, {%0, %1};\n"
                 "@p ld.relaxed.gpu.global.b64 u, [%3];\nmov.b64 {%0, %1}, u;\n@p mov.u32 %2, 1;\n}"
                 : "+r"(v.x), "+r"(v.y), "+r"(miss) : "l"(p) : "memory");
}
__device__ __forceinline__ uint32_t ld_relaxed32(const void* p) {
    uint32_t v;
    asm volatile("ld.relaxed.gpu.global.u32 %0, [%1];" : "=r"(v) : "l"(p) : "memory");
    return v;
}
__device__ __forceinline__ void flag_wait(const unsigned int* p, uint32_t tag) {
    uint32_t v, it = 0;
#pragma unroll 1
    do {
        asm volatile("ld.relaxed.gpu.global.u32 %0, [%1];" : "=r"(v) : "l"(p) : "memory");
    } while (__any_sync(0xffffffffu, v != tag) && ++it < SPIN / 16);
    asm volatile("fence.acquire.gpu;" ::: "memory");
    __syncwarp();
}
__device__ __forceinline__ bool elect() {
    uint32_t p;
    asm volatile("{\n.reg .pred p;\nelect.sync _|p, 0xffffffff;\nselp.u32 %0, 1, 0, p;\n}" : "=r"(p));
    return p;
}
__device__ __forceinline__ void flag_release(unsigned int* p, uint32_t tag) {
    asm volatile("st.release.gpu.global.u32 [%0], %1;" ::"l"(p), "r"(tag) : "memory");
}
__device__ __forceinline__ uint32_t touch(const void* p) {
    uint32_t v;
    asm volatile("ld.global.nc.L1::no_allocate.L2::128B.u32 %0, [%1];" : "=r"(v) : "l"(p));
    return v;
}
__device__ __forceinline__ void bar_sync(int id, int n) { asm volatile("bar.sync %0, %1;" ::"r"(id), "r"(n) : "memory"); }
__device__ __forceinline__ void bar_arrive(int id, int n) { asm volatile("bar.arrive %0, %1;" ::"r"(id), "r"(n) : "memory"); }

constexpr uint64_t EVICT_NORMAL = 0x1000000000000000ull, EVICT_FIRST = 0x12F0000000000000ull;
__device__ __forceinline__ void tma2d(uint32_t dst, const CUtensorMap* m, int c0, int c1, uint32_t bar) {
    asm volatile("cp.async.bulk.tensor.2d.shared::cluster.global.mbarrier::complete_tx::bytes.L2::cache_hint [%0], [%1, {%3, %4}], [%2], %5;"
                 ::"r"(dst), "l"(m), "r"(bar), "r"(c0), "r"(c1), "l"(EVICT_FIRST) : "memory");
}
__device__ __forceinline__ void tma2d_mc(uint32_t dst, const CUtensorMap* m, int c0, int c1, uint32_t bar, uint64_t pol) {
    asm volatile("cp.async.bulk.tensor.2d.shared::cluster.global.mbarrier::complete_tx::bytes.multicast::cluster.L2::cache_hint [%0], [%1, {%3, %4}], [%2], %5, %6;"
                 ::"r"(dst), "l"(m), "r"(bar), "r"(c0), "r"(c1), "h"((uint16_t)3), "l"(pol) : "memory");
}
__device__ __forceinline__ void tma3d(uint32_t dst, const CUtensorMap* m, int c0, int c1, int c2, uint32_t bar) {
    asm volatile("cp.async.bulk.tensor.3d.shared::cluster.global.mbarrier::complete_tx::bytes.L2::cache_hint [%0], [%1, {%3, %4, %5}], [%2], %6;"
                 ::"r"(dst), "l"(m), "r"(bar), "r"(c0), "r"(c1), "r"(c2), "l"(EVICT_FIRST) : "memory");
}
__device__ __forceinline__ void bulk_load(uint32_t dst, const void* src, uint32_t bytes, uint32_t bar) {
    asm volatile("cp.async.bulk.shared::cluster.global.mbarrier::complete_tx::bytes [%0], [%1], %2, [%3];"
                 ::"r"(dst), "l"(src), "r"(bytes), "r"(bar) : "memory");
}
__device__ __forceinline__ void l2_prefetch(const void* src, uint32_t bytes) {
    asm volatile("cp.async.bulk.prefetch.L2.global [%0], %1;" ::"l"(src), "r"(bytes) : "memory");
}
__device__ __forceinline__ uint32_t bmul2(uint32_t a, uint32_t b) { uint32_t r; asm("mul.rn.bf16x2 %0, %1, %2;" : "=r"(r) : "r"(a), "r"(b)); return r; }
__device__ __forceinline__ uint32_t badd2(uint32_t a, uint32_t b) { uint32_t r; asm("add.rn.bf16x2 %0, %1, %2;" : "=r"(r) : "r"(a), "r"(b)); return r; }
__device__ __forceinline__ uint32_t bsub2(uint32_t a, uint32_t b) { uint32_t r; asm("sub.rn.bf16x2 %0, %1, %2;" : "=r"(r) : "r"(a), "r"(b)); return r; }
__device__ __forceinline__ uint32_t bmax2(uint32_t a, uint32_t b) { uint32_t r; asm("max.bf16x2 %0, %1, %2;" : "=r"(r) : "r"(a), "r"(b)); return r; }
__device__ __forceinline__ uint4 lds128(uint32_t a) { uint4 v; asm volatile("ld.shared.v4.u32 {%0,%1,%2,%3}, [%4];" : "=r"(v.x), "=r"(v.y), "=r"(v.z), "=r"(v.w) : "r"(a) : "memory"); return v; }
__device__ __forceinline__ uint2 lds64(uint32_t a) { uint2 v; asm volatile("ld.shared.v2.u32 {%0,%1}, [%2];" : "=r"(v.x), "=r"(v.y) : "r"(a) : "memory"); return v; }
__device__ __forceinline__ uint32_t lds32(uint32_t a) { uint32_t v; asm volatile("ld.shared.u32 %0, [%1];" : "=r"(v) : "r"(a) : "memory"); return v; }
__device__ __forceinline__ uint4 ldsm4(uint32_t a) {
    uint4 v;
    asm volatile("ldmatrix.sync.aligned.m8n8.x4.shared.b16 {%0,%1,%2,%3}, [%4];" : "=r"(v.x), "=r"(v.y), "=r"(v.z), "=r"(v.w) : "r"(a) : "memory");
    return v;
}
__device__ __forceinline__ uint4 ldsm4t(uint32_t a) {
    uint4 v;
    asm volatile("ldmatrix.sync.aligned.m8n8.x4.trans.shared.b16 {%0,%1,%2,%3}, [%4];" : "=r"(v.x), "=r"(v.y), "=r"(v.z), "=r"(v.w) : "r"(a) : "memory");
    return v;
}
__device__ __forceinline__ void mma1688(float* d, uint32_t a0, uint32_t a1, uint32_t b) {
    asm("mma.sync.aligned.m16n8k8.row.col.f32.bf16.bf16.f32 {%0,%1,%2,%3}, {%4,%5}, {%6}, {%0,%1,%2,%3};"
        : "+f"(d[0]), "+f"(d[1]), "+f"(d[2]), "+f"(d[3]) : "r"(a0), "r"(a1), "r"(b));
}
__device__ __forceinline__ void mma16816(float* d, uint32_t a0, uint32_t a1, uint32_t a2, uint32_t a3, uint32_t b0, uint32_t b1) {
    asm("mma.sync.aligned.m16n8k16.row.col.f32.bf16.bf16.f32 {%0,%1,%2,%3}, {%4,%5,%6,%7}, {%8,%9}, {%0,%1,%2,%3};"
                 : "+f"(d[0]), "+f"(d[1]), "+f"(d[2]), "+f"(d[3]) : "r"(a0), "r"(a1), "r"(a2), "r"(a3), "r"(b0), "r"(b1));
}
__device__ __forceinline__ void stsm_x4(uint32_t addr, uint32_t a, uint32_t b, uint32_t c, uint32_t d) {
    asm volatile("stmatrix.sync.aligned.m8n8.x4.shared.b16 [%0], {%1, %2, %3, %4};"
                 ::"r"(addr), "r"(a), "r"(b), "r"(c), "r"(d) : "memory");
}

__device__ __forceinline__ uint64_t mkdesc(uint32_t addr, uint32_t lbo, uint32_t sbo) {
    return (uint64_t)((addr & 0x3FFFF) >> 4) | ((uint64_t)(lbo >> 4) << 16) | ((uint64_t)(sbo >> 4) << 32) | (1ull << 62);
}
constexpr uint32_t SM0 = 1024;
__host__ __device__ constexpr uint32_t desc_lo(uint32_t off, uint32_t lbo) { return ((SM0 + off) >> 4) | ((lbo >> 4) << 16); }
#define WG_FENCE() asm volatile("wgmma.fence.sync.aligned;" ::: "memory")
#define WG_COMMIT() asm volatile("wgmma.commit_group.sync.aligned;" ::: "memory")
#define WG_WAIT(n) asm volatile("wgmma.wait_group.sync.aligned %0;" ::"n"(n) : "memory")

#define F8(a, i) "+f"(a[i]), "+f"(a[i + 1]), "+f"(a[i + 2]), "+f"(a[i + 3]), "+f"(a[i + 4]), "+f"(a[i + 5]), "+f"(a[i + 6]), "+f"(a[i + 7])
#define F16(a, i) F8(a, i), F8(a, i + 8)
#define F64(a) F16(a, 0), F16(a, 16), F16(a, 32), F16(a, 48)
#define F32(a) F16(a, 0), F16(a, 16)
#define L64 "%0,%1,%2,%3,%4,%5,%6,%7,%8,%9,%10,%11,%12,%13,%14,%15,%16,%17,%18,%19,%20,%21,%22,%23,%24,%25,%26,%27,%28,%29,%30,%31,%32,%33,%34,%35,%36,%37,%38,%39,%40,%41,%42,%43,%44,%45,%46,%47,%48,%49,%50,%51,%52,%53,%54,%55,%56,%57,%58,%59,%60,%61,%62,%63"
#define L32 "%0,%1,%2,%3,%4,%5,%6,%7,%8,%9,%10,%11,%12,%13,%14,%15,%16,%17,%18,%19,%20,%21,%22,%23,%24,%25,%26,%27,%28,%29,%30,%31"

template <int TB, int STEP = 128>
__device__ __forceinline__ void mma_rs128(float (&d)[64], uint32_t a0, uint32_t a1, uint32_t a2, uint32_t a3, uint64_t& b, int acc) {
    asm volatile("{\n.reg .pred p;\nsetp.ne.b32 p, %69, 0;\n"
                 "wgmma.mma_async.sync.aligned.m64n128k16.f32.bf16.bf16 {" L64 "}, {%65,%66,%67,%68}, %64, p, 1, 1, %70;\nadd.s64 %64, %64, %71;\n}"
                 : F64(d), "+l"(b) : "r"(a0), "r"(a1), "r"(a2), "r"(a3), "r"(acc), "n"(TB), "n"(STEP));
}
template <int TB>
__device__ __forceinline__ void mma_rs64(float (&d)[32], uint32_t a0, uint32_t a1, uint32_t a2, uint32_t a3, uint64_t& b, int acc) {
    asm volatile("{\n.reg .pred p;\nsetp.ne.b32 p, %37, 0;\n"
                 "wgmma.mma_async.sync.aligned.m64n64k16.f32.bf16.bf16 {" L32 "}, {%33,%34,%35,%36}, %32, p, 1, 1, %38;\nadd.s64 %32, %32, 128;\n}"
                 : F32(d), "+l"(b) : "r"(a0), "r"(a1), "r"(a2), "r"(a3), "r"(acc), "n"(TB));
}
template <int N>
__device__ __forceinline__ void fence_regs(float (&d)[N]) {
#pragma unroll
    for (int i = 0; i < N; i++) asm volatile("" : "+f"(d[i])::"memory");
}
template <int N>
__device__ __forceinline__ void fence_regs(uint32_t (&d)[N]) {
#pragma unroll
    for (int i = 0; i < N; i++) asm volatile("" : "+r"(d[i])::"memory");
}

template <int V> struct IC { static constexpr int value = V; };

constexpr int SLOT = 32768, UNIT = 16384;
constexpr int SM_Q = 4 * SLOT;
constexpr int SM_BAR = 7 * SLOT;
constexpr int SM_RED = SM_BAR + 512;
constexpr int SM_TOTAL = SM_BAR + 3072;
constexpr int XP = D_ * 2 + 16;
constexpr int M_MOD = 16 * XP;
constexpr int SM_T = SM_Q + 2 * D_ * 80, SM_TC = SM_T + D_ * 4, SM_TG = SM_TC + D_ * 4, SM_TS = SM_TG + D_ * 2;
constexpr float CS = 0.08838834764831845f * 1.4426950408889634f;
#define WFL 1
#define WCA 1
#define USE_SPARE 1
constexpr float POFF = 102.f, LMIN = 0x1p-104f;
#define LMAX 0.5f
constexpr int SPLIT = 10;
constexpr int STAGE = 11;
constexpr int ESPLIT = 3;
constexpr int QSPLIT = 4, OSPLIT = 6;
constexpr int WF0 = 3, WF1 = 13, WF2 = 19, DL = 9;
constexpr int PF_KV = 8;
constexpr int PF_WO = 50, PF_O = 60;

__device__ __forceinline__ int cluster_role() {
    int k;
    asm volatile("mov.u32 %0, %%ctaid.x;" : "=r"(k));
    const int c = (k & 1) << 6;
    k >>= 1;
    const int r = ((k - 36) * 37) >> 8, i = k - 36 - r * 7;
    return c + (k < 4 ? 12 + k : k < 36 ? ((k - 4) & 7) * 8 + ((k - 4) >> 3) : (i + (i > 0)) * 8 + ((4 + r) & 7));
}

struct Args {
    const bf16 *w_mod, *cvec;
    Scratch* gs;
    uint64_t d0;
    bf16* out;
    const bf16 *x, *kc, *vc, *wq, *wo, *w_r, *w_down;
};

__device__ __forceinline__ void frag_store(uint8_t* p, const uint32_t (&a)[32]) {
#pragma unroll
    for (int i = 0; i < 8; i++)
        __stcg(reinterpret_cast<uint4*>(p + i * 512), make_uint4(a[4 * i], a[4 * i + 1], a[4 * i + 2], a[4 * i + 3]));
}
template <int LO = 0, int HI = 8>
__device__ __forceinline__ void frag_load(uint32_t (&a)[32], const uint8_t* p) {
#pragma unroll
    for (int i = LO; i < HI; i++) {
        const uint4 v = ld_relaxed(reinterpret_cast<const uint4*>(p + i * 512));
        a[4 * i] = v.x; a[4 * i + 1] = v.y; a[4 * i + 2] = v.z; a[4 * i + 3] = v.w;
    }
}
__device__ __forceinline__ float quad_sum(float v) {
    v += __shfl_xor_sync(0xffffffffu, v, 1);
    return v + __shfl_xor_sync(0xffffffffu, v, 2);
}
__device__ __forceinline__ float quad_max(float v) {
    v = fmaxf(v, __shfl_xor_sync(0xffffffffu, v, 1));
    return fmaxf(v, __shfl_xor_sync(0xffffffffu, v, 2));
}
__device__ __forceinline__ float rcp_fast(float x) { float y; asm("rcp.approx.ftz.f32 %0, %1;" : "=f"(y) : "f"(x)); return y; }
__device__ __forceinline__ float sigmoidf_(float x) { return rcp_fast(1.f + ex2(-1.4426950408889634f * x)); }
__device__ __forceinline__ void top2(uint32_t k, uint32_t& k1, uint32_t& k2) {
    k1 = __reduce_max_sync(0xffffffffu, k);
    k2 = __reduce_max_sync(0xffffffffu, k == k1 ? 0 : k);
}

__device__ __forceinline__ void mod_fma(float (&a)[8], const uint4 w, float sc) {
    a[0] += sc * bf_lo(w.x); a[1] += sc * bf_hi(w.x); a[2] += sc * bf_lo(w.y); a[3] += sc * bf_hi(w.y);
    a[4] += sc * bf_lo(w.z); a[5] += sc * bf_hi(w.z); a[6] += sc * bf_lo(w.w); a[7] += sc * bf_hi(w.w);
}
__device__ __forceinline__ float mod_reduce(float (&a)[8], int lane) {
#pragma unroll
    for (int h = 4; h > 0; h >>= 1) {
        const bool up = lane & (8 / h);
#pragma unroll
        for (int i = 0; i < h; i++)
            a[i] = (up ? a[i + h] : a[i]) + __shfl_xor_sync(0xffffffffu, up ? a[i] : a[i + h], 8 / h);
    }
    return a[0] + __shfl_xor_sync(0xffffffffu, a[0], 16);
}

__device__ __forceinline__ float ln_stats(float sum, float sq, uint32_t& mean2) {
    const float mean = sum * (1.f / D_);
    const float var = fmaxf(fmaf(-mean, mean, sq * (1.f / D_)), 0.f);
    float sd;
    asm("sqrt.approx.ftz.f32 %0, %1;" : "=f"(sd) : "f"(rbf(rbf(var) + 1e-5f)));
    mean2 = pack_bf16(mean, mean);
    return rcp_fast(rbf(sd));
}
__device__ __forceinline__ uint32_t ln_pair(uint32_t x, uint32_t mean2, float rsd) {
    const uint32_t d = bsub2(x, mean2);
    return pack_bf16(bf_lo(d) * rsd, bf_hi(d) * rsd);
}
__device__ __forceinline__ void rows_load(uint32_t (&x)[20], uint32_t xs, int cw) {
#pragma unroll
    for (int ch = 0; ch < 5; ch++) {
        const uint4 v = ldsm4(ch < 4 ? xs + ch * 256 : xs + 1024 - cw * 16);
        x[4 * ch] = v.x; x[4 * ch + 1] = v.y; x[4 * ch + 2] = v.z; x[4 * ch + 3] = v.w;
    }
}
__device__ __forceinline__ void stats_add(float (&st)[12], uint32_t a, uint32_t b, uint32_t w) {
    mma1688(st, a, b, w);
    mma1688(st + 4, a, b, a);
    mma1688(st + 8, a, b, b);
}
__device__ __forceinline__ float rows_stats(const float (&st)[12], float4* rec, int cw, int lane, uint32_t& mean2, float& dot) {
    const int g8 = lane >> 2;
    if ((g8 >> 1) == (lane & 3)) {
        rec[cw * 16 + g8] = make_float4(st[0], (g8 & 1) ? st[5] : st[4], st[1], 0.f);
        rec[cw * 16 + 8 + g8] = make_float4(st[2], (g8 & 1) ? st[11] : st[10], st[3], 0.f);
    }
    bar_sync(3, 256);
    const float4* r = rec + (lane >> 4) * 64 + (lane & 15);
    const float4 s0 = r[0], s1 = r[16], s2 = r[32], s3 = r[48];
    const float sum = (s0.x + s1.x) + (s2.x + s3.x), sq = (s0.y + s1.y) + (s2.y + s3.y);
    dot = (s0.z + s1.z) + (s2.z + s3.z);
    dot += __shfl_xor_sync(0xffffffffu, dot, 16);
    return ln_stats(sum + __shfl_xor_sync(0xffffffffu, sum, 16), sq + __shfl_xor_sync(0xffffffffu, sq, 16), mean2);
}
template <class F>
__device__ __forceinline__ void rows_normalise(uint32_t* y, const uint32_t* x, uint32_t mean2, float rsd, int lane, F loads) {
    const int g8 = lane >> 2;
    const uint32_t ma2 = __shfl_sync(0xffffffffu, mean2, g8), mb2 = __shfl_sync(0xffffffffu, mean2, g8 + 8);
    const float ra = __shfl_sync(0xffffffffu, rsd, g8), rb = __shfl_sync(0xffffffffu, rsd, g8 + 8);
    loads();
#pragma unroll
    for (int k = 0; k < 9; k++) { y[2 * k] = ln_pair(x[2 * k], ma2, ra); y[2 * k + 1] = ln_pair(x[2 * k + 1], mb2, rb); }
}

__device__ __forceinline__ uint4 h_frag(const uint4* hf, int ks, int lane) {
    if (ks < 32) return ld_relaxed2(hf + ks * 32);
    const uint2* p = reinterpret_cast<const uint2*>(padd(hf, 256 - lane * 8) + ks * 32 - 16);
    const uint2 a = ld_relaxed64(p), b = ld_relaxed64(p + 32);
    return make_uint4(a.x, a.y, b.x, b.y);
}

__device__ __noinline__ void attn_fallback(uint32_t bad, uint32_t tag, const Scratch* gs, uint8_t* frag, uint8_t* keep, const bf16* wq, const bf16* kc, const bf16* vc) {
  const int lane = threadIdx.x & 31, g8 = lane >> 2, qd = lane & 3;
  const int role = cluster_role(), j = role & 7, qb = (role >> 2 & 14) + (role >> 6);
  const uint4* hf = g_h + (size_t)(qb * 8 + (threadIdx.x >> 5) - 4) * (36 * 32) + lane;
#pragma unroll 1
  for (int t = 0; t < 4; t++) {
    if (!((bad >> t) & 1)) continue;
    const bf16 *wqp = wq + (4 * j + t) * DH, *kp = kc + (size_t)(2 * j + (t >> 1)) * S_ * DH, *vp = vc + (size_t)(2 * j + (t >> 1)) * S_ * DH;
    uint32_t q[32];
    float o[64];
#pragma unroll
    for (int i = 0; i < 64; i++) o[i] = 0.f;
#pragma unroll 1
    for (int ks = 0; ks < 36; ks++) {
        const uint4 a = h_frag(hf, ks, lane);
        const unsigned short* wr = reinterpret_cast<const unsigned short*>(wqp + (size_t)(ks * 16 + 2 * qd) * QD + g8);
#pragma unroll
        for (int dt = 0; dt < 16; dt++) {
            const uint32_t b0 = __ldg(wr + dt * 8) | ((uint32_t)__ldg(wr + dt * 8 + QD) << 16);
            const uint32_t b1 = __ldg(wr + dt * 8 + 8 * QD) | ((uint32_t)__ldg(wr + dt * 8 + 9 * QD) << 16);
            mma16816(o + 4 * dt, a.x, a.y, a.z, a.w, b0, b1);
        }
    }
#pragma unroll
    for (int i = 0; i < 32; i++) q[i] = pack_bf16(o[2 * i], o[2 * i + 1]);
#pragma unroll
    for (int i = 0; i < 64; i++) o[i] = 0.f;
    float m0 = -INFINITY, m1 = -INFINITY, l0 = 0.f, l1 = 0.f;
#pragma unroll 1
    for (int key = 0; key < S_; key += 16) {
        float sc[8];
#pragma unroll
        for (int i = 0; i < 8; i++) sc[i] = 0.f;
#pragma unroll
        for (int nt = 0; nt < 2; nt++) {
            const uint32_t* kr = reinterpret_cast<const uint32_t*>(kp + (size_t)(key + nt * 8 + g8) * DH) + qd;
#pragma unroll
            for (int ks = 0; ks < 8; ks++)
                mma16816(sc + 4 * nt, q[4 * ks], q[4 * ks + 1], q[4 * ks + 2], q[4 * ks + 3], __ldg(kr + ks * 8), __ldg(kr + ks * 8 + 4));
        }
        const float n0 = quad_max(fmaxf(fmaxf(m0, fmaxf(sc[0], sc[1])), fmaxf(sc[4], sc[5])));
        const float n1 = quad_max(fmaxf(fmaxf(m1, fmaxf(sc[2], sc[3])), fmaxf(sc[6], sc[7])));
        const float f0 = ex2((m0 - n0) * CS), f1 = ex2((m1 - n1) * CS);
        m0 = n0; m1 = n1;
#pragma unroll
        for (int i = 0; i < 8; i++) sc[i] = ex2((sc[i] - ((i & 2) ? n1 : n0)) * CS);
        l0 = l0 * f0 + (sc[0] + sc[1]) + (sc[4] + sc[5]);
        l1 = l1 * f1 + (sc[2] + sc[3]) + (sc[6] + sc[7]);
        const uint32_t e0 = pack_bf16(sc[0], sc[1]), e1 = pack_bf16(sc[2], sc[3]), e2 = pack_bf16(sc[4], sc[5]), e3 = pack_bf16(sc[6], sc[7]);
        const unsigned short* vr = reinterpret_cast<const unsigned short*>(vp + (size_t)(key + 2 * qd) * DH + g8);
#pragma unroll
        for (int dt = 0; dt < 16; dt++) {
            o[4 * dt] *= f0; o[4 * dt + 1] *= f0; o[4 * dt + 2] *= f1; o[4 * dt + 3] *= f1;
            const uint32_t b0 = __ldg(vr + dt * 8) | ((uint32_t)__ldg(vr + dt * 8 + DH) << 16);
            const uint32_t b1 = __ldg(vr + dt * 8 + 8 * DH) | ((uint32_t)__ldg(vr + dt * 8 + 9 * DH) << 16);
            mma16816(o + 4 * dt, e0, e1, e2, e3, b0, b1);
        }
    }
    const float i0 = 1.f / quad_sum(l0), i1 = 1.f / quad_sum(l1);
#pragma unroll
    for (int i = 0; i < 16; i++) {
        q[2 * i] = pack_bf16(o[4 * i] * i0, o[4 * i + 1] * i0);
        q[2 * i + 1] = pack_bf16(o[4 * i + 2] * i1, o[4 * i + 3] * i1);
    }
    frag_store(t < 3 ? frag + t * 4096 : keep, q);
  }
}

__device__ __forceinline__ void spare_q3(Scratch* gs, uint32_t sb, uint32_t bar_full, uint32_t bar_empty, int lane, int cw) {
    const uint32_t tag = load_tag(gs);
    uint32_t rel_base, e = 3;
    asm("mapa.shared::cluster.u32 %0, %1, %2;" : "=r"(rel_base) : "r"(bar_empty), "r"(lane & 1));
#pragma unroll 1
    for (int qb = blockIdx.x - NCTA; qb < 16; qb += 4) {
        uint32_t h[144];
        float o[64];
        flag_wait(&g_flag_h[(qb * 8 + cw) * 32], tag);
        const uint4* hf = g_h + (size_t)(qb * 8 + cw) * (36 * 32) + lane;
#pragma unroll
        for (int ks = 0; ks < 36; ks++) {
            const uint4 v = h_frag(hf, ks, lane);
            h[4 * ks] = v.x; h[4 * ks + 1] = v.y; h[4 * ks + 2] = v.z; h[4 * ks + 3] = v.w;
        }
#pragma unroll
        for (int i = 0; i < 64; i++) o[i] = 0.f;
#pragma unroll 1
        for (int v = 0; v < 4; v++) {
            fence_regs(o);
#pragma unroll
            for (int t = 0; t < 5; t++) {
                mbar_wait(bar_full + 8 * (e & 3), (e >> 2) & 1);
                uint64_t dv = mkdesc(sb + (e & 3) * SLOT, UNIT, 1024);
                WG_FENCE();
#pragma unroll
                for (int ks = 0; ks < (t < 4 ? 8 : 4); ks++)
                    mma_rs128<1>(o, h[32 * t + 4 * ks], h[32 * t + 4 * ks + 1], h[32 * t + 4 * ks + 2], h[32 * t + 4 * ks + 3], dv, ks | t);
                WG_COMMIT();
                if (t > 0) { WG_WAIT(1); if (lane < 2) mbar_arrive_cluster(rel_base + 8 * ((e - 1) & 3)); }
                e++;
            }
            WG_WAIT(0);
            fence_regs(o);
            if (lane < 2) mbar_arrive_cluster(rel_base + 8 * ((e - 1) & 3));
            uint4* dst = &g_q3[((qb * 8 + 2 * v) * 8 + cw) * 128 + lane];
#pragma unroll
            for (int i = 0; i < 8; i++)
                __stcg(dst + (i >> 2) * 1024 + (i & 3) * 32, make_uint4(pack_bf16(o[8 * i], o[8 * i + 1]), pack_bf16(o[8 * i + 2], o[8 * i + 3]),
                                                                        pack_bf16(o[8 * i + 4], o[8 * i + 5]), pack_bf16(o[8 * i + 6], o[8 * i + 7])));
        }
        bar_sync(3, 256);
        if (cw == 0 && lane == 0) flag_release(&g_flag_q3[qb * 32], tag);
        __syncwarp();
    }
}

template <bool SPARE>
__global__ void __cluster_dims__(2, 1, 1) __launch_bounds__(384, 1)
fused_kernel(const Args args, const __grid_constant__ CUtensorMap tm_wq,
             const __grid_constant__ CUtensorMap tm_k, const __grid_constant__ CUtensorMap tm_v,
             const __grid_constant__ CUtensorMap tm_wo, const __grid_constant__ CUtensorMap tm_p,
             const __grid_constant__ CUtensorMap tm_x, const __grid_constant__ CUtensorMap tm_d,
             const __grid_constant__ CUtensorMap tm_g, const __grid_constant__ CUtensorMap tm_u) {
    extern __shared__ __align__(1024) uint8_t smem_raw[];
    const uint32_t sb = smem_u32(smem_raw);
    Scratch* const gs = args.gs;
    const uint32_t bar_full = sb + SM_BAR;
    const uint32_t bar_g = bar_full + 8 * 4;
    const uint32_t bar_mod = bar_g + 8;
    const uint32_t bar_go = bar_mod + 8;
    const uint32_t bar_x = bar_go + 40;
    const uint32_t bar_empty = bar_x + 8;
    const uint32_t bar_pub = bar_empty + 8 * 4;
    const uint32_t bar_qfree = bar_pub + 32;
    const uint32_t bar_out = bar_qfree + 24;
    const uint32_t bar_q3 = bar_out + 8;
    const uint32_t bar_pre = bar_q3 + 16;
    const uint32_t bar_w0 = bar_q3 + 8;
    constexpr int E0 = SPARE ? 2 : 0;

#define ROLES() const int role = cluster_role(), c = role >> 6, j = role & 7, qb = (role >> 2 & 14) + c, rg = qb * 8 + j; uint32_t bx; asm volatile("mov.u32 %0, %%ctaid.x;" : "=r"(bx))
    const int warp = __shfl_sync(0xffffffffu, threadIdx.x >> 5, 0);

    if (SPARE && blockIdx.x >= NCTA && warp >= 4) {
        asm volatile("barrier.cluster.arrive.relaxed.aligned;" ::: "memory");
        asm volatile("setmaxnreg.inc.sync.aligned.u32 240;");
        asm volatile("barrier.cluster.wait.aligned;" ::: "memory");
        spare_q3(gs, sb, bar_full, bar_empty, threadIdx.x & 31, warp - 4);
        asm volatile("barrier.cluster.arrive.relaxed.aligned;\nbarrier.cluster.wait.aligned;" ::: "memory");
    } else if (warp < 4) {
        asm volatile("setmaxnreg.dec.sync.aligned.u32 24;");
        ROLES();
        int lane;
        asm volatile("mov.u32 %0, %%laneid;" : "=r"(lane));
        if (warp == 2 && elect()) {
            asm volatile("prefetch.tensormap [%0];" ::"l"(&tm_x) : "memory");
#pragma unroll
            for (int i = 0; i < 27; i++) mbar_init(bar_full + 8 * i, i < 12 || i >= 23 ? 1 : i < 16 ? 16 : 8);
#pragma unroll
            for (int i = 0; i <= E0; i++) {
                mbar_arrive(bar_full + 8 * i);
                asm volatile("mbarrier.arrive.shared::cta.b64 _, [%0], 16;" ::"r"(bar_empty + 8 * i) : "memory");
            }
            asm volatile("fence.mbarrier_init.release.cluster;" ::: "memory");
        }
        __syncwarp();
        asm volatile("barrier.cluster.arrive.relaxed.aligned;" ::: "memory");
        if (warp == 2 && !(SPARE && bx >= NCTA)) {
            __nanosleep(200);
            if (elect()) {
                mbar_expect_tx(bar_x, 16 * XP);
                tma2d(sb + SM_Q, &tm_x, 0, rg * 16, bar_x);
            }
            __syncwarp();
        }
        asm volatile("barrier.cluster.wait.aligned;" ::: "memory");
        const uint32_t tag = load_tag(gs);
        if (SPARE && bx >= NCTA) {
            if (warp == 1) {
#pragma unroll 1
                for (int e = 3; e < 83; e++) {
                    const int v = (e - 3) / 5;
                    mbar_wait_sleep(bar_empty + 8 * (e & 3), ~(e >> 2) & 1);
                    if (elect()) {
                        mbar_expect_tx(bar_full + 8 * (e & 3), SLOT);
                        tma2d_mc(sb + (e & 3) * SLOT + c * UNIT, &tm_wq, (8 * (v & 3) + 4 * c + 3) * DH + 64, (e - 3 - v * 5) * 128,
                                 bar_full + 8 * (e & 3), EVICT_NORMAL);
                    }
                }
            }
            __syncwarp();
            asm volatile("barrier.cluster.arrive.relaxed.aligned;\nbarrier.cluster.wait.aligned;" ::: "memory");
            return;
        }
        if (warp == 3) {
#pragma unroll 1
            for (int e = 4; e < 20; e++) {
                __nanosleep(e == 4 ? 2000 : 400);
                const int hd = (e * 52) >> 8, row = (e - hd * 5) * 128 + qb * 8 + (lane >> 1);
                if (lane < 16 && row < D_)
                    asm volatile("prefetch.global.L2 [%0];" ::"l"(padd(args.wq, (row * QD + (4 * j + ((0x1320 >> (4 * hd)) & 3)) * DH + (lane & 1) * 64) * 2)) : "memory");
            }
            __syncwarp();
            mbar_wait_sleep(bar_go, 0);
            __nanosleep(2000);
#pragma unroll 1
            for (int unit = 72 + bx; unit < 216; unit += NCTA) {
                float a[8];
#pragma unroll
                for (int i = 0; i < 8; i++) a[i] = 0.f;
#pragma unroll 1
                for (int k = lane >> 1; k < D_; k += 16) {
                    const float cv = __bfloat162float(*padd(args.cvec, k * 2));
                    mod_fma(a, __ldg(reinterpret_cast<const uint4*>(padd(args.w_mod, (k * (6 * D_) + unit * 16 + (lane & 1) * 8) * 2))), rbf(cv * sigmoidf_(cv)));
                }
                const float v = mod_reduce(a, lane), v1 = __shfl_down_sync(0xffffffffu, v, 8);
                if (lane < 8) *padd(gs->mod2, ((unit - 72) * 8 + (lane & 1) * 4 + (lane & 2) + (lane >> 2)) * 4) = pack_bf16(v, v1);
            }
            __syncwarp();
            if (lane == 0) flag_release(padd(g_flag_mod, bx * 4), tag);
#pragma unroll 1
            for (int k = 0; k < 36; k++) {
                __nanosleep(200);
                __stcg(padd(gs->h[0], (~tag & 1) * (NCTA * 36 * 512) + ((rg * 36 + k) * 32 + lane) * 16), make_uint4(0, 0, 0, 0));
            }
            __syncwarp();
            mbar_wait_sleep(bar_qfree + 16, 0);
            __nanosleep(2000);
            {
                uint4 v;
                uint32_t it = 0;
#pragma unroll 1
                do {
                    v = ld_relaxed(reinterpret_cast<const uint4*>(padd(g_flag_mod, lane * 16)));
                } while (((v.x ^ tag) | (v.y ^ tag) | (v.z ^ tag) | (v.w ^ tag)) && ++it < SPIN / 16);
                asm volatile("fence.acquire.gpu;" ::: "memory");
            }
            __syncwarp();
            {
                float w1 = 0.f, w2 = 0.f;
#pragma unroll 1
                for (int k = lane; k < D_ / 2; k += 32) {
                    const uint32_t* mp = padd(gs->mod2, k * 4);
                    const uint32_t sv = __ldcg(mp + D_ / 2), c1 = badd2(__ldcg(mp + D_), 0x3f803f80u);
                    const uint32_t wr = *reinterpret_cast<const uint32_t*>(padd(args.w_r, k * 4)), wp = bmul2(c1, wr);
                    reinterpret_cast<uint2*>(smem_raw + SM_T)[k] = make_uint2(__ldcg(mp), wp);
                    reinterpret_cast<uint2*>(smem_raw + SM_TC)[k] = make_uint2(c1, sv);
                    reinterpret_cast<uint32_t*>(smem_raw + SM_TG)[k] = __ldcg(mp + 3 * D_ / 2);
                    w1 += bf_lo(wp) + bf_hi(wp);
                    w2 += bf_lo(sv) * bf_lo(wr) + bf_hi(sv) * bf_hi(wr);
                }
#pragma unroll 1
                for (int i = 1; i < 32; i <<= 1) { w1 += __shfl_xor_sync(0xffffffffu, w1, i); w2 += __shfl_xor_sync(0xffffffffu, w2, i); }
                *reinterpret_cast<float2*>(smem_raw + SM_TS) = make_float2(w1, w2);
            }
#pragma unroll
            for (int i = 0; i < 4; i++) reinterpret_cast<uint4*>(smem_raw + SM_RED)[lane + 32 * i] = make_uint4(~0u, ~0u, ~0u, ~0u);
            asm volatile("fence.proxy.async.shared::cta;" ::: "memory");
            __syncwarp();
            if (elect()) {
                uint8_t* mb = g_frag + (size_t)rg * 8 * WREG + 3 * 4096;
#pragma unroll 1
                for (int k = 0; k < 8; k++, mb += WREG) {
#pragma unroll
                    for (int i = 0; i < 3; i++)
                        asm volatile("cp.async.bulk.global.shared::cta.bulk_group [%0], [%1], 2048;" ::"l"(mb + i * 2048), "r"(sb + SM_RED) : "memory");
                    __nanosleep(500);
                }
                asm volatile("cp.async.bulk.commit_group;\ncp.async.bulk.wait_group 0;\nfence.proxy.async.global;" ::: "memory");
            }
            __syncwarp();
            if (lane == 0) mbar_arrive(bar_mod);
            __syncwarp();
            mbar_wait_sleep(bar_go + 8, 0);
            if (elect()) asm volatile("prefetch.tensormap [%0];\nprefetch.tensormap [%1];\nprefetch.tensormap [%2];" ::"l"(&tm_x), "l"(&tm_p), "l"(&tm_d) : "memory");
            __syncwarp();
            if (WFL && lane < 24) *padd(g_flag_part, qb * 1024 + (lane >> 3) * 256 + j * 32 + (lane & 7) * 4) = 0;
            __syncwarp();
#pragma unroll 1
            for (int i = 1; i < 4; i++) {
                mbar_wait(bar_pub + 8 * i, 0);
                unsigned int* flags = padd(g_flag_part, qb * 1024 + (i - 1) * (WFL ? 256 : 32));
                if (elect()) { flag_release(padd(flags, j * (WFL ? 32 : 4)), tag); DBG_PG(93); }
                __syncwarp();
                const uint32_t slot = (i + 2) & 3;
                flag_wait(padd(flags, (lane & 7) * (WFL ? 32 : 4)), tag);
                asm volatile("fence.proxy.async.global;" ::: "memory");
                if (lane == 0 && i == 3) DBG_PG(101);
                mbar_wait(bar_go + 8 + 8 * i, 0);
                mbar_wait(bar_empty + 8 * slot, i == 3);
                if (elect()) {
                    mbar_expect_tx(bar_full + 8 * slot, SLOT);
                    tma3d(sb + slot * SLOT, &tm_p, 0, j * 20 + (i - 1) * 4, qb * 8, bar_full + 8 * slot);
                    tma3d(sb + slot * SLOT + UNIT, &tm_p, 0, j * 20 + (i - 1) * 4 + 2, qb * 8, bar_full + 8 * slot);
                }
            }
        } else if (warp == 0) {
#pragma unroll 1
            for (int i = 0; i < 48; i++) {
                if (SPARE && i == 34) {
                    flag_wait(&g_flag_q3[qb * 32], tag);
                    if (elect()) {
                        asm volatile("fence.proxy.async.global;" ::: "memory");
                        mbar_expect_tx(bar_q3, UNIT);
#pragma unroll 1
                        for (int k = 0; k < 8; k++) bulk_load(sb + SM_Q + 2 * SLOT + k * 4096 + 2048, &g_q3[(rg * 8 + k) * 128], 2048, bar_q3);
                    }
                }
                if (i == 0 || i == 17 || i == 34) { mbar_wait_sleep(bar_qfree + (i >> 4) * 8, 0); __nanosleep(2000); }
                __nanosleep(500);
                if (elect()) {
                    asm volatile("mbarrier.expect_tx.shared::cta.b64 [%0], %1;" ::"r"(bar_g), "n"(1920) : "memory");
                    tma2d(sb + SM_Q + i * 1920, i < 24 ? &tm_g : &tm_u, (bx * 36) & ~7, (i < 24 ? i : i - 24) * 24, bar_g);
                }
            }
            if (elect()) mbar_arrive(bar_g);
#pragma unroll 1
            for (int i = 0; i < 18; i++) {
                __nanosleep(400);
                if (elect()) l2_prefetch(args.w_down + (size_t)(bx * 36 + i * 2) * D_, 4 * D_);
            }
            __syncwarp();
            mbar_wait_sleep(bar_go + 8 * 2, 0);
            uint32_t acc = 0;
#pragma unroll 1
            for (int k = lane; k < 16 * 9; k += 32) acc |= touch(padd(args.x, (rg * 16 * D_ + k * 64) * 2));
            if (acc == 0) reinterpret_cast<volatile uint32_t*>(smem_raw + SM_BAR)[127] = acc;
            __syncwarp();
            mbar_wait_sleep(bar_go + 8 * 4, 0);
            if (WCA && lane < 2 * CREP) *padd(g_cand, ((lane >> 1) * NCTA + rg) * 32 + (lane & 1) * 16) = make_uint4(0, 0, 0, 0);
            uint4* rp = padd(g_rows, (rg * 2 * RSLOT + lane) * 16);
#pragma unroll
            for (int k = 0; k < 12; k++) rp[k * 32] = make_uint4(~0u, ~0u, ~0u, ~0u);
            if (bx < 72) {
                uint4* yp = reinterpret_cast<uint4*>(padd(g_ypart, bx * NCTA * 64 + lane * 16));
#pragma unroll
                for (int k = 0; k < 16; k++) yp[k * 32] = make_uint4(~0u, ~0u, ~0u, ~0u);
            }
            asm volatile("fence.acq_rel.gpu;" ::: "memory");
            __syncwarp();
            if (lane == 0) mbar_arrive(bar_pre);
        } else if (warp == 1) {
            __nanosleep(100);
            auto put = [&](uint32_t fb, uint32_t slot, const CUtensorMap* tm, int c0, int c1, uint64_t pol) {
                if (elect()) {
                    mbar_expect_tx(fb, SLOT);
                    tma2d_mc(sb + slot * SLOT + c * UNIT, tm, c0, c1, fb, pol);
                }
            };
            auto prefetch_kv = [&](int n) {
                if (elect()) {
                    const size_t off = (size_t)((2 * j + (n >> 5)) * S_ + (n & 15) * 128) * DH + qb * 1024;
                    l2_prefetch(args.kc + off, 2048);
                    l2_prefetch(args.vc + off, 2048);
                }
            };
            put(bar_w0, 6, &tm_wq, 4 * j * DH + c * 64, -64, EVICT_FIRST);
#pragma unroll 1
            for (int e = E0 + 1; e < 19; e++) {
                const int i = SPARE && e < 12 ? e - 2 : e, hd = (i * 52) >> 8;
                const bool half = SPARE && hd == 2;
                const int c0 = (4 * j + ((0x1320 >> (4 * hd)) & 3)) * DH + (half ? 0 : c * 64);
                const int c1 = half ? (2 * (e - 12) + c) * 128 : (i - hd * 5) * 128 - 64;
                if (e < E0 + 5) __nanosleep(300);
                mbar_wait(bar_empty + 8 * (e & 3), ~(e >> 2) & 1);
                put(bar_full + 8 * (e & 3), e & 3, &tm_wq, c0, c1, EVICT_FIRST);
                if (e >= PF_KV && !(e & 1)) prefetch_kv((e - PF_KV) >> 1);
            }
            mbar_wait(bar_empty + 24, 1);
            put(bar_full + 24, 3, &tm_k, c * 64, 2 * j * S_, EVICT_NORMAL);
            mbar_wait(bar_empty, 0);
            put(bar_full, 0, &tm_wq, (4 * j + 1) * DH + c * 64, 448, EVICT_FIRST);
            prefetch_kv((20 - PF_KV) >> 1);
            if (elect()) mbar_arrive(bar_go);
#pragma unroll 1
            for (int n = 1; n < 64; n++) {
                const uint32_t sv = (n & 1) * 2, sk = sv ^ 3;
                const int m = n - 1;
                mbar_wait_sleep(bar_empty + 8 * sk, ~((n + 9) >> 1) & 1);
                put(bar_full + 8 * sk, sk, &tm_k, c * 64, (2 * j + (n >> 5)) * S_ + (n & 15) * 128, (n & 16) ? EVICT_FIRST : EVICT_NORMAL);
                mbar_wait_sleep(bar_empty + 8 * sv, (n >> 1) & 1);
                put(bar_full + 8 * sv, sv, &tm_v, c * 64, (2 * j + (m >> 5)) * S_ + (m & 15) * 128, (m & 16) ? EVICT_FIRST : EVICT_NORMAL);
                const int pn = n + ((20 - PF_KV) >> 1);
                if (!(pn & 80)) prefetch_kv(pn);
                if (n >= PF_WO) {
                    if (elect()) {
                        if (n < PF_WO + 9) l2_prefetch(args.wo + (size_t)bx * (QD * D_ / NCTA) + (n - PF_WO) * 2048, 4096);
                        if (n >= PF_O) {
                            l2_prefetch(g_frag + (size_t)(rg * 8 + 2 * (n - PF_O)) * WREG, 4096);
                            l2_prefetch(g_frag + (size_t)(rg * 8 + 2 * (n - PF_O) + 1) * WREG, 4096);
                        }
                    }
                }
            }
            mbar_wait_sleep(bar_empty + 24, 1);
            put(bar_full + 24, 3, &tm_v, c * 64, (2 * j + 1) * S_ + 15 * 128, EVICT_FIRST);
#pragma unroll 1
            for (int i = 0; i < 18; i++) {
                const int e = 148 + i + (i > 10) + (i > 14);
                mbar_wait_sleep(bar_empty + 8 * (e & 3), ~(e >> 2) & 1);
                put(bar_full + 8 * (e & 3), e & 3, &tm_wo, (i >> 1) * 64, (4 * j + ((i & 1) ? 1 + c : 3 * c)) * DH, EVICT_FIRST);
                arrive_if(bar_go + 2 + 2 * i, elect() && (i & 3) == 3);
            }
            asm volatile("fence.proxy.async.global;" ::: "memory");
            mbar_wait(bar_empty, 1);
            if (elect()) {
                mbar_expect_tx(bar_full, 16 * XP);
                tma2d(sb, &tm_x, 0, rg * 16, bar_full);
            }
            mbar_wait(bar_empty + 16, 1);
            if (elect()) {
                mbar_expect_tx(bar_full + 16, SLOT);
                tma3d(sb + 2 * SLOT, &tm_p, 0, j * 20 + 12, qb * 8, bar_full + 16);
                tma3d(sb + 2 * SLOT + UNIT, &tm_p, 0, j * 20 + 14, qb * 8, bar_full + 16);
            }
            mbar_wait(bar_empty + 24, 1);
            __nanosleep(300);
            if (elect()) {
                mbar_expect_tx(bar_full + 24, UNIT);
                tma3d(sb + 3 * SLOT, &tm_p, 0, j * 20 + 16, qb * 8, bar_full + 24);
            }
            mbar_wait(bar_empty + 8, 0);
            mbar_wait(bar_empty + 16, 0);
            __nanosleep(300);
            if (elect()) {
#pragma unroll
                for (int i = 1; i < 3; i++) {
                    mbar_expect_tx(bar_full + 8 * i, 18 * XP);
                    tma2d(sb + i * SLOT, &tm_d, 0, bx * 36 + (i - 1) * 18, bar_full + 8 * i);
                }
            }
        } else {
            if (elect()) asm volatile("prefetch.tensormap [%0];\nprefetch.tensormap [%1];\nprefetch.tensormap [%2];" ::"l"(&tm_k), "l"(&tm_v), "l"(&tm_wo) : "memory");
            if (SPARE) {
                mbar_wait_sleep(bar_pub, 0);
                if (lane == 0) flag_release(padd(g_flag_h, rg * 128), tag);
                __syncwarp();
            }
            bar_sync(1, 192);
#pragma unroll 1
            for (uint32_t e = E0 + 5; e < 20; e++) {
                mbar_wait(bar_full + 8 * (e & 3), (e >> 2) & 1);
                if (!(((SPARE ? 0xa080 : 0x8420) >> e) & 1)) bar_sync(1, 192);
            }
#pragma unroll 1
            for (uint32_t e = 20; e < 148; e += 2) {
                mbar_wait_sleep(bar_full + 8 * (e & 3), (e >> 2) & 1);
                bar_sync(4, 160);
                if (SPARE && e == 112) mbar_wait(bar_q3, 0);
                mbar_wait_sleep(bar_full + 8 + 8 * (e & 3), (e >> 2) & 1);
                bar_sync(1, 192);
            }
            bar_sync(4, 160);
#pragma unroll 1
            for (uint32_t e = 148; e < 168; e++) {
                mbar_wait(bar_full + 8 * (e & 3), (e >> 2) & 1);
                if (e != 159 && e != 164) bar_sync(1, 192);
            }
        }
        __syncwarp();
        uint32_t rows = 0x1111u << warp;
        auto store_rows = [&](uint32_t m) {
#pragma unroll 1
            for (; m; m &= m - 1) {
                const int i = __ffs(m) - 1;
                asm volatile("cp.async.bulk.global.shared::cta.bulk_group.L2::cache_hint [%0], [%1], %2, %3;"
                             ::"l"(padd(args.out, (rg * 16 + i) * (D_ * 2))), "r"(sb + i * XP), "n"(D_ * 2), "l"(EVICT_FIRST) : "memory");
            }
        };
        mbar_wait_sleep(bar_out, 0);
        if (bx == 127 && warp == 0 && lane == 0) gs->epoch[0] = tag;
        if (elect()) {
            asm volatile("fence.proxy.async.shared::cta;" ::: "memory");
            const uint2 sel = lds64(sb + SM_RED + 64);
            if ((sel.x >> 4) == rg) rows &= ~(1u << (sel.x & 15));
            if ((sel.y >> 4) == rg) rows &= ~(1u << (sel.y & 15));
            store_rows(rows);
            asm volatile("cp.async.bulk.commit_group;\ncp.async.bulk.wait_group.read 0;" ::: "memory");
        }
    } else {
        uint32_t cv[2] = {0, 0}, tag0 = 0;
        {
            uint32_t ws, t, b;
            asm volatile("mov.u32 %0, smem_raw;\nmov.u32 %1, %%tid.x;\nmov.u32 %2, %%ctaid.x;" : "=r"(ws), "=r"(t), "=r"(b));
            t -= 128;
            const uint32_t* cp = padd(reinterpret_cast<const uint32_t*>(args.cvec), (t & 0xe0) + (t & 7) * 4);
            asm volatile("{\n.reg .pred p, q, r;\nsetp.lt.u32 r, %8, 256;\nsetp.lt.and.u32 p, %9, 72, r;\nsetp.lt.and.u32 q, %8, 128, p;\n"
                         "@p ld.global.nc.u32 %0, [%5];\n@q ld.global.nc.u32 %1, [%6 + 1024];\n@r ld.global.ca.u32 %2, [%7];\n"
                         "@p cp.async.cg.shared.global [%3], [%4], 16;\n@p cp.async.cg.shared.global [%3 + 4096], [%4 + 884736], 16;\n"
                         "@p cp.async.cg.shared.global [%3 + 8192], [%4 + 1769472], 16;\n@p cp.async.cg.shared.global [%3 + 12288], [%4 + 2654208], 16;\n"
                         "@q cp.async.cg.shared.global [%3 + 16384], [%4 + 3538944], 16;\n}"
                         : "+r"(cv[0]), "+r"(cv[1]), "+r"(tag0)
                         : "r"(ws + SM_Q + SLOT + t * 16), "l"(padd(args.w_mod, (t >> 1 & 127) * (12 * D_) + (t & 1) * 16 + b * 32)),
                           "l"(padd(cp, (t & 24) * 32)), "l"(cp), "l"(padd(gs->epoch, b >> 8)), "r"(t), "r"(b) : "memory");
        }
        uint32_t tag = __shfl_sync(0xffffffffu, tag0, 0);
        asm volatile("barrier.cluster.arrive.relaxed.aligned;" ::: "memory");
        asm volatile("setmaxnreg.inc.sync.aligned.u32 240;");
        const int lane = threadIdx.x & 31;
        const int cw = warp - 4;
        const int w = cw >> 2;
        const int tid = threadIdx.x - 128;
        ROLES();
        float* red = reinterpret_cast<float*>(smem_raw + SM_RED);
        DBG_INIT();
        DBG_G(120);
        DBG_T(100);

        {
            if (bx < 72) {
                uint2* mdst = &gs->mod1[(tid >> 3) * D_ + bx * 8 + (tid & 7)];
                if (tid < 8 * MREP) st_relaxed64(mdst, 0, 0);
                uint32_t sa[10];
#pragma unroll
                for (int i = 0; i < 2; i++) {
                    const float lo = bf_lo(cv[i]), hi = bf_hi(cv[i]);
                    cv[i] = pack_bf16(lo * sigmoidf_(lo), hi * sigmoidf_(hi));
                }
#pragma unroll
                for (int i = 0; i < 10; i++) sa[i] = __shfl_sync(0xffffffffu, cv[i >> 3], (i & 7) * 4 + (lane & 3));
                anchor(bar_full + 504, sa[0] & sa[1] & sa[2] & sa[3] & sa[4] & sa[5] & sa[6] & sa[7] & sa[8] & sa[9] & (uint32_t)(uintptr_t)mdst & (uint32_t)((uintptr_t)mdst >> 32));
                asm volatile("cp.async.wait_all;" ::: "memory");
                __syncwarp();
                const uint32_t ws = sb + SM_Q + SLOT + cw * 512 + (lane & 15) * 32 + (lane & 16);
                float d[16];
#pragma unroll
                for (int i = 0; i < 16; i++) d[i] = 0.f;
#pragma unroll
                for (int i = 0; i < 5; i++) {
                    const uint4 b = ldsm4t(ws + (i < 4 || cw < 4 ? i * 4096 : 0));
                    mma16816(d + 8 * (i & 1), sa[2 * i], sa[2 * i], sa[2 * i + 1], sa[2 * i + 1], b.x, b.y);
                    mma16816(d + 8 * (i & 1) + 4, sa[2 * i], sa[2 * i], sa[2 * i + 1], sa[2 * i + 1], b.z, b.w);
                }
                if (lane < 8) reinterpret_cast<float2*>(red)[lane * 8 + cw] = (lane & 4) ? make_float2(d[4] + d[12], d[5] + d[13]) : make_float2(d[0] + d[8], d[1] + d[9]);
                bar_sync(3, 256);
                if (tid < 8 * MREP) {
                    const float4* r = reinterpret_cast<const float4*>(red) + (tid & 7) * 4;
                    const float4 r0 = r[0], r1 = r[1], r2 = r[2], r3 = r[3];
                    st_relaxed64(mdst, pack_bf16(((r0.x + r0.z) + (r1.x + r1.z)) + ((r2.x + r2.z) + (r3.x + r3.z)),
                                                 ((r0.y + r0.w) + (r1.y + r1.w)) + ((r2.y + r2.w) + (r3.y + r3.w))), tag + 1);
                }
            }
            if (cw < 4) st_relaxed4(gs->h[~tag & 1] + (size_t)(rg * 36 + cw) * 32 + lane, 0, 0, 0, 0);
            DBG_G(106);
            asm volatile("barrier.cluster.wait.aligned;" ::: "memory");
            mbar_wait(bar_x, 0);
            asm volatile("add.u32 %0, %0, 1;" : "+r"(tag));
            uint32_t x[20];
            float st[12], st2[12];
            rows_load(x, sb + SM_Q + (lane & 15) * XP + (lane >> 4) * 16 + cw * 32, cw);
#pragma unroll
            for (int i = 0; i < 12; i++) { st[i] = 0.f; st2[i] = 0.f; }
#pragma unroll
            for (int k = 0; k < 9; k++) stats_add((k & 1) ? st2 : st, x[2 * k], x[2 * k + 1], 0x3f803f80u);
#pragma unroll
            for (int i = 0; i < 12; i++) st[i] += st2[i];
            uint32_t mean2;
            float dot;
            const float rsd = rows_stats(st, reinterpret_cast<float4*>(red + 128), cw, lane, mean2, dot);
            const uint4* mp = reinterpret_cast<const uint4*>(gs->mod1 + ((bx >> 1) & (MREP - 1)) * D_) + min(tid, D_ / 4 - 1);
            uint4 v0 = make_uint4(0, tag, 0, tag), v1 = v0;
            auto look = [&]() {
                asm volatile("{\n.reg .pred p;\n.reg .b64 a, b, c, d;\nsetp.lt.s32 p, %9, 5;\nmov.b64 a, {%0, %1};\nmov.b64 b, {%2, %3};\n"
                             "mov.b64 c, {%4, %5};\nmov.b64 d, {%6, %7};\n@p ld.relaxed.gpu.global.v2.b64 {a, b}, [%8];\n"
                             "@p ld.relaxed.gpu.global.v2.b64 {c, d}, [%8 + 2304];\n"
                             "mov.b64 {%0, %1}, a;\nmov.b64 {%2, %3}, b;\nmov.b64 {%4, %5}, c;\nmov.b64 {%6, %7}, d;\n}"
                             : "+r"(v0.x), "+r"(v0.y), "+r"(v0.z), "+r"(v0.w), "+r"(v1.x), "+r"(v1.y), "+r"(v1.z), "+r"(v1.w)
                             : "l"(mp), "r"(cw) : "memory");
            };
            rows_normalise(x, x, mean2, rsd, lane, look);
            fence_regs(x);
            uint32_t it = 0;
#pragma unroll 1
            while (((v0.y ^ tag) | (v0.w ^ tag) | (v1.y ^ tag) | (v1.w ^ tag)) && ++it < SPIN / 16) look();
            uint4* smod = reinterpret_cast<uint4*>(smem_raw + SM_Q + M_MOD);
            if (tid < D_ / 4) smod[tid] = make_uint4(badd2(v1.x, 0x3f803f80u), v0.x, badd2(v1.z, 0x3f803f80u), v0.z);
            uint4* hdst = g_h + (size_t)(rg * 36 + cw) * 32 + lane;
            uint2* hdst2 = reinterpret_cast<uint2*>(g_h + (size_t)(rg * 36 + 32) * 32) + tid;
            bar_sync(3, 256);
            DBG_G(107);
#pragma unroll
            for (int k = 0; k < 9; k++) {
                const uint2 cs = lds64(sb + SM_Q + M_MOD + (cw * 8 + (lane & 3) + (k < 8 ? (k >> 1) * 64 + (k & 1) * 4 : 256 - cw * 4)) * 8);
                const uint32_t c1 = cs.x, sa = cs.y;
                x[2 * k] = badd2(bmul2(x[2 * k], c1), sa);
                if (x[2 * k] == 0) x[2 * k] = 0x8000u;
                x[2 * k + 1] = badd2(bmul2(x[2 * k + 1], c1), sa);
            }
#pragma unroll
            for (int ch = 0; ch < 4; ch++) st_relaxed4(hdst + ch * 256, x[4 * ch], x[4 * ch + 1], x[4 * ch + 2], x[4 * ch + 3]);
            st_relaxed64(hdst2, x[16], x[17]);
            __syncwarp();
            if (SPARE && lane == 0) mbar_arrive(bar_pub);
            DBG_G(108);
        }

        uint32_t rel_base;
        asm("mapa.shared::cluster.u32 %0, %1, %2;" : "=r"(rel_base) : "r"(bar_empty), "r"(lane & 1));
        auto release = [&](uint32_t slot) { if (lane < 2) mbar_arrive_cluster(rel_base + 8 * slot); };
        uint32_t q[32], p[32];
        float s[64], o[64];

        const int lw = cw & 3;
        const uint32_t relw = lw == 2 && lane < 8, handw = lw == 2 || cw == 1;
        auto release4 = [&](uint32_t off, uint32_t on = 1) {
            asm volatile("{\n.reg .pred p;\nsetp.ne.b32 p, %1, 0;\n@p mbarrier.arrive.shared::cluster.b64 _, [%0];\n}" ::"r"(rel_base + off), "r"(relw & on) : "memory"); };
        auto handoff = [&](uint32_t on = 1) {
            asm volatile("{\n.reg .pred p;\nsetp.ne.b32 p, %1, 0;\n@p bar.arrive %0, 192;\n}" ::"r"(2 - w), "r"(handw & on) : "memory"); };
        if (cw == 6) bar_arrive(1, 192);

        uint4* qpark = reinterpret_cast<uint4*>(smem_raw + SM_Q - SLOT) + cw * 256 + lane;
        {
            uint32_t h[144];
            const uint4* hf = g_h + (size_t)(qb * 8 + cw) * (36 * 32) + lane;
            auto load_h = [&](auto lo, auto hi) {
#pragma unroll
                for (int ks = lo.value; ks < hi.value; ks++) {
                    const uint4 v = h_frag(hf, ks, lane);
                    h[4 * ks] = v.x; h[4 * ks + 1] = v.y; h[4 * ks + 2] = v.z; h[4 * ks + 3] = v.w;
                }
            };
            auto check_h = [&](auto lo, auto hi) {
                uint32_t it = 0;
                bool miss;
#pragma unroll 1
                do {
                    uint32_t mn = ~0u;
#pragma unroll
                    for (int ks = lo.value; ks < hi.value; ks++) mn = __vimin3_u32(mn, h[4 * ks], h[4 * ks + 2]);
                    miss = __any_sync(0xffffffffu, mn == 0);
                    if (miss) load_h(lo, hi);
                    asm volatile("add.u32 %0, %0, 1;" : "+r"(it));
                } while (miss && it < SPIN / 16);
            };
            auto check_h2 = [&](auto lo, auto hi, auto nx) {
                float f0 = __uint_as_float(~0u), f1 = f0;
                hold(f0, f1);
                auto low = [&]() {
                    uint32_t m0 = __float_as_uint(f0), m1 = m0;
#pragma unroll
                    for (int ks = lo.value; ks < hi.value; ks += 2) { m0 = __vimin3_u32(m0, h[4 * ks], h[4 * ks + 2]); m1 = __vimin3_u32(m1, h[4 * ks + 4], h[4 * ks + 6]); }
                    return min(m0, m1);
                };
                anchor(const_cast<uint4*>(hf), h[4 * hi.value - 1] & __float_as_uint(f0));
                load_h(hi, nx);
                if (__any_sync(0xffffffffu, low() == 0)) {
                    uint32_t it = 0;
#pragma unroll 1
                    do load_h(lo, hi); while (__any_sync(0xffffffffu, low() == 0) && ++it < SPIN / 16);
                }
            };
            __nanosleep(100);
            load_h(IC<0>{}, IC<4>{});
            DBG_T(104); DBG_G(109);
            mbar_wait(bar_w0, 0);
#pragma unroll
            for (int e = E0 + 1; e < E0 + 3; e++) mbar_wait(bar_full + 8 * (e & 3), e >> 2);
#pragma unroll
            for (int i = 0; i < 64; i++) o[i] = 0.f;
            auto group = [&](auto tc, auto ec) {
                constexpr int t = tc.value, e = ec.value, k0 = t ? 8 * t - 4 : 0;
                constexpr bool first = e < E0 + 5, turns = e >= E0 + 4;
                uint64_t dv = (first ? args.d0 : desc_lo(0, UNIT) | (0x40000040ull << 32)) + ((t ? 0 : 512) + (e == E0 ? 6 : e & 3) * (SLOT / 16));
                if (first && t == 0) check_h(IC<0>{}, IC<4>{});
                if (first && t >= 3) mbar_wait(bar_full + 8 * (e & 3), e >> 2);
                if (first && t > 0) check_h2(IC<k0>{}, IC<8 * t + 4>{}, IC<t < 4 ? 8 * t + 12 : 0>{});
                if (t != 1 && turns) bar_sync(1 + w, 192);
                if (t != 1 || first) WG_FENCE();
#pragma unroll
                for (int ks = k0; ks < 8 * t + 4; ks++) {
                    mma_rs128<1>(o, h[4 * ks], h[4 * ks + 1], h[4 * ks + 2], h[4 * ks + 3], dv, ks);
                    if (t && turns && ks == k0 + QSPLIT - 1) WG_COMMIT();
                }
                if (t || first) WG_COMMIT();
                if (first && t == 0) load_h(IC<4>{}, IC<12>{});
                if (t > 0) {
                    WG_WAIT(1);
                    if (turns) handoff();
                    if ((t == 1 && !first) || (t > 1 && e <= E0 + 4)) release4(8 * ((e - 1) & 3));
                    if (turns && e != 18) { WG_WAIT(0); release4(8 * (e & 3)); }
                }
            };
            auto head = [&](auto ec, int slot) {
                constexpr int e = ec.value;
                fence_regs(o);
                group(IC<0>{}, IC<e>{}); group(IC<1>{}, IC<e + 1>{}); group(IC<2>{}, IC<e + 2>{}); group(IC<3>{}, IC<e + 3>{});
                if (e == 15) return;
                group(IC<4>{}, IC<e + 4>{});
                fence_regs(o);
#pragma unroll
                for (int i = 0; i < 8; i++)
                    qpark[slot * 2048 + i * 32] = make_uint4(pack_bf16(o[8 * i], o[8 * i + 1]), pack_bf16(o[8 * i + 2], o[8 * i + 3]),
                                                             pack_bf16(o[8 * i + 4], o[8 * i + 5]), pack_bf16(o[8 * i + 6], o[8 * i + 7]));
            };
            head(IC<E0>{}, 1);
            head(IC<E0 + 5>{}, 2);
            if (SPARE) {
                float (&u)[32] = reinterpret_cast<float (&)[32]>(o);
                fence_regs(u);
#pragma unroll
                for (int t = 0; t < 2; t++) {
                    uint64_t dv = args.d0 + t * (SLOT / 16);
                    bar_sync(1 + w, 192);
                    WG_FENCE();
#pragma unroll
                    for (int ks = 0; ks < 16 + 4 * t; ks++) {
                        mma_rs64<1>(u, h[64 * t + 4 * ks], h[64 * t + 4 * ks + 1], h[64 * t + 4 * ks + 2], h[64 * t + 4 * ks + 3], dv, ks | t);
                        if (ks == 2 * QSPLIT + 4 * t - 1) WG_COMMIT();
                    }
                    WG_COMMIT();
                    WG_WAIT(1);
                    handoff();
                    WG_WAIT(0);
                    release4(8 * t);
                }
                fence_regs(u);
                release4(16);
#pragma unroll
                for (int i = 0; i < 4; i++)
                    qpark[3 * 2048 + i * 32] = make_uint4(pack_bf16(u[8 * i], u[8 * i + 1]), pack_bf16(u[8 * i + 2], u[8 * i + 3]),
                                                          pack_bf16(u[8 * i + 4], u[8 * i + 5]), pack_bf16(u[8 * i + 6], u[8 * i + 7]));
            } else {
                head(IC<10>{}, 3);
            }
            head(IC<15>{}, 0);
#pragma unroll
            for (int i = 0; i < 8; i++) {
                const uint4 v = lds128(smem_u32(qpark + 2048 + i * 32));
                q[4 * i] = v.x; q[4 * i + 1] = v.y; q[4 * i + 2] = v.z; q[4 * i + 3] = v.w;
            }
#pragma unroll
            for (int i = 0; i < 32; i++) p[i] = h[112 + i];
            WG_WAIT(0);
            fence_regs(o);
            release4(16);
        }
        DBG_T(105);
        DBG_G(125);

        uint8_t* frag = reinterpret_cast<uint8_t*>(__shfl_sync(0xffffffffu, reinterpret_cast<unsigned long long>(g_frag + (size_t)(rg * 8 + cw) * WREG + lane * 16), lane));
        const uint4* qnext = reinterpret_cast<const uint4*>(__shfl_sync(0xffffffffu, reinterpret_cast<unsigned long long>(padd(smem_raw, SM_Q + tid * 16 + cw * 3584)), lane));
        uint8_t* odst = reinterpret_cast<uint8_t*>(const_cast<uint4*>(qnext));
        qnext -= 2048;
        float m0, m1, l0 = 0.25f, l1 = 0.25f, t0, t1;
        uint32_t bad = 0;
        auto finish = [&](auto lo, auto hi, uint32_t bit, auto sink) {
#pragma unroll
            for (int i = lo.value; i < hi.value; i++) {
                const uint32_t v0 = pack_bf16(o[8 * i] * t0, o[8 * i + 1] * t0), v1 = pack_bf16(o[8 * i + 2] * t1, o[8 * i + 3] * t1);
                const uint32_t v2 = pack_bf16(o[8 * i + 4] * t0, o[8 * i + 5] * t0), v3 = pack_bf16(o[8 * i + 6] * t1, o[8 * i + 7] * t1);
                if (i == 0 && fabsf(o[0] * t0) >= 0x1p-31f) bad |= bit << 8;
                sink(i, v0, v1, v2, v3);
            }
        };
        float lq[6];
        auto row_parts = [&]() {
#pragma unroll
            for (int i = 0; i < 3; i++) { lq[i] = __shfl_xor_sync(0xffffffffu, l0, i + 1); lq[3 + i] = __shfl_xor_sync(0xffffffffu, l1, i + 1); }
        };
        auto row_sums = [&](uint32_t bit) {
            t0 = (l0 + lq[0]) + (lq[1] + lq[2]); t1 = (l1 + lq[3]) + (lq[4] + lq[5]);
            if (!(t0 >= LMIN && t0 < LMAX && t1 >= LMIN && t1 < LMAX)) bad |= bit;
        };
        auto issue_pv = [&](uint64_t dv, int acc) {
            asm volatile("{\n.reg .pred p;\nsetp.eq.b32 p, %0, 0;\n@p bar.sync 4, 160;\n}" ::"r"(w) : "memory");
#pragma unroll
            for (int ks = 0; ks < 8; ks++)
                mma_rs128<1>(o, p[4 * ks], p[4 * ks + 1], p[4 * ks + 2], p[4 * ks + 3], dv, ks ? 1 : acc);
            WG_COMMIT();
        };
#pragma unroll
        for (int i = 0; i < 64; i++) s[i] = 0.f;
        uint64_t dv_lo = args.d0;
        uint32_t voff = 0;
        auto issue_qk = [&]() {
            uint64_t dk = dv_lo ^ (desc_lo(0, UNIT) ^ desc_lo(3 * SLOT, 16));
            bar_sync(1 + w, 192);
            fence_regs(s); fence_regs(q); fence_regs(o); fence_regs(p);
            WG_FENCE();
#pragma unroll
            for (int ks = 0; ks < 8; ks++)
                if (ks == 3) mma_rs128<0, 1018>(s, q[4 * ks], q[4 * ks + 1], q[4 * ks + 2], q[4 * ks + 3], dk, 1);
                else mma_rs128<0, 2>(s, q[4 * ks], q[4 * ks + 1], q[4 * ks + 2], q[4 * ks + 3], dk, ks != 0);
            WG_COMMIT();
        };
        auto to_frag = [&](int i, uint32_t v0, uint32_t v1, uint32_t v2, uint32_t v3) {
            *reinterpret_cast<uint4*>(odst + i * 512) = make_uint4(v0, v1, v2, v3); };
        int n = 0;
        auto scores_ready = [&]() {
            WG_WAIT(1);
            fence_regs(s); fence_regs(q);
        };
        auto pass_on = [&]() {
            release4(voff ^ 24);
            handoff();
        };
#pragma unroll 1
        for (;;) {
            {
                {
                    asm volatile("st.shared.v2.f32 [%0], {%1, %2};" ::"r"(sb + SM_RED + tid * 8), "f"(l0), "f"(l1) : "memory");
                    __syncwarp();
                    const uint4 a = lds128(sb + SM_RED + (tid & ~3) * 8), b = lds128(sb + SM_RED + (tid & ~3) * 8 + 16);
                    l0 = __uint_as_float(a.x); lq[0] = __uint_as_float(a.z); lq[1] = __uint_as_float(b.x); lq[2] = __uint_as_float(b.z);
                    l1 = __uint_as_float(a.y); lq[3] = __uint_as_float(a.w); lq[4] = __uint_as_float(b.y); lq[5] = __uint_as_float(b.w);
                }
                issue_qk();
                hold(l0, l1);
                row_sums(1u << (n >> 4));
                t0 = rcp_fast(t0); t1 = rcp_fast(t1);
                l0 = 0.f; l1 = 0.f;
                odst = n ? frag + ((n >> 4) - 1) * 4096 : odst;
                qnext = n == 48 ? reinterpret_cast<const uint4*>(frag) : qnext + 2048;
                anchor(bar_full + 504, (t0 + t1) * __uint_as_float((bad ^ (uint32_t)(uintptr_t)odst ^ (uint32_t)(uintptr_t)qnext) & 0x3fffffff));
                asm volatile("{\n.reg .pred p;\nsetp.ne.b32 p, %1, 0;\n@p mbarrier.arrive.shared::cta.b64 _, [%0];\n}"
                             ::"r"(bar_qfree + (n >> 1) - 8), "r"(lane ? 0 : n) : "memory");
                issue_pv(dv_lo, 1);
                scores_ready();
                const uint32_t a = pack_bf16(fmaxf(fmaxf(s[0], s[1]), fmaxf(s[4], s[5])), fmaxf(fmaxf(s[2], s[3]), fmaxf(s[6], s[7])));
                const uint32_t b = bmax2(bmax2(a, __shfl_xor_sync(0xffffffffu, a, 1)), bmax2(__shfl_xor_sync(0xffffffffu, a, 2), __shfl_xor_sync(0xffffffffu, a, 3)));
                pass_on();
                m0 = fmaf(-CS, bf_lo(b), -POFF); m1 = fmaf(-CS, bf_hi(b), -POFF);
            }
#pragma unroll 1
            for (;;) {
                DBG_T(n);
#pragma unroll
                for (int i = 0; i < 4 * STAGE; i++) s[i] = fmaf(s[i], CS, (i & 2) ? m1 : m0);
#pragma unroll
                for (int i = 0; i < 4 * SPLIT; i++) s[i] = ex2(s[i]);
#pragma unroll
                for (int i = 0; i < SPLIT; i++) { l0 += s[4 * i] + s[4 * i + 1]; l1 += s[4 * i + 2] + s[4 * i + 3]; }
                m0 = fmaf(l0, 0.f, m0); m1 = fmaf(l1, 0.f, m1);
                anchor(bar_full + 504, l0 + l1);
                WG_WAIT(0);
                fence_regs(o); fence_regs(p);
                release4(voff);
                dv_lo ^= 2 * SLOT / 16;
                voff ^= 16;
                n++;
#pragma unroll
                for (int i = 4 * STAGE; i < 64; i++) s[i] = fmaf(s[i], CS, (i & 2) ? m1 : m0);
#pragma unroll
                for (int i = 4 * SPLIT; i < 64; i++) s[i] = ex2(s[i]);
#pragma unroll
                for (int i = SPLIT; i < 16; i++) { l0 += s[4 * i] + s[4 * i + 1]; l1 += s[4 * i + 2] + s[4 * i + 3]; }
#pragma unroll
                for (int i = 0; i < 32; i++) p[i] = pack_bf16(s[2 * i], s[2 * i + 1]);
                const int jn = n & 15;
                if (jn > 1) {
                    issue_qk();
                    if ((n & 10) == 2) {
                        if (n & 1) {
#pragma unroll
                            for (int i = 0; i < 64; i++) o[i] *= (i & 2) ? t1 : t0;
                        } else {
                            row_parts();
                            row_sums(2u << (n >> 4));
                            const uint32_t e0 = __float_as_uint(t0) >> 23, e1 = __float_as_uint(t1) >> 23;
                            m0 -= __uint_as_float(0x4b000000u | e0) - (8388608.f + 127.f - POFF);
                            m1 -= __uint_as_float(0x4b000000u | e1) - (8388608.f + 127.f - POFF);
                            t0 = __uint_as_float((254 - (int)POFF - e0) << 23); t1 = __uint_as_float((254 - (int)POFF - e1) << 23);
                            l0 *= t0; l1 *= t1;
                        }
                    }
                    fence_regs(o);
                    WG_FENCE();
                    issue_pv(dv_lo, 1);
                    scores_ready();
                    pass_on();
                    if (jn != 15) continue;
#pragma unroll
                    for (int i = 0; i < 8; i++) {
                        const uint4 v = qnext[i * 32];
                        q[4 * i] = v.x; q[4 * i + 1] = v.y; q[4 * i + 2] = v.z; q[4 * i + 3] = v.w;
                    }
                    continue;
                }
                if (jn == 0) break;
                finish(IC<0>{}, IC<ESPLIT>{}, 1u << (n >> 4), to_frag);
                issue_qk();
                hold(t0, t1);
                finish(IC<ESPLIT>{}, IC<8>{}, 1u << (n >> 4), to_frag);
                WG_FENCE();
                issue_pv(dv_lo, 0);
                scores_ready();
                pass_on();
            }
            if (n == 64) break;
        }
        DBG_T(64);
        uint32_t a1[32], a2[32];
        bar_sync(1 + w, 192);
        fence_regs(o); fence_regs(p);
        WG_FENCE();
        issue_pv(args.d0 + 3 * SLOT / 16, 1);
        handoff();
        mbar_wait(bar_mod, 0);
        const int tid_ = __shfl_sync(0xffffffffu, tid, lane);
        row_parts();
        row_sums(16);
        t0 = rcp_fast(t0); t1 = rcp_fast(t1);
        anchor(frag, q[0] & q[4] & q[8] & q[12] & q[16] & q[20] & q[24] & q[28] & __float_as_uint(t0) & __float_as_uint(t1) & tid_);
        frag_load(a1, frag + 4096);
        frag_load<0, 4>(a2, frag + 8192);
        anchor(frag, bad);
        WG_WAIT(0);
        fence_regs(o); fence_regs(p);
        release4(24);
        finish(IC<0>{}, IC<8>{}, 16, [&](int i, uint32_t v0, uint32_t v1, uint32_t v2, uint32_t v3) {
            p[4 * i] = v0; p[4 * i + 1] = v1; p[4 * i + 2] = v2; p[4 * i + 3] = v3; });
        anchor(frag, p[31] & p[15]);
        frag_load<4, 8>(a2, frag + 8192);
        bad = __reduce_or_sync(0xffffffffu, bad);
        bad = ((bad | ~(bad >> 8)) >> 1) & 15;
        if (__builtin_expect(bad != 0, 0)) {
            uint8_t* keep = g_keep + (size_t)(rg * 8 + cw) * 4096 + lane * 16;
            frag_store(keep, p);
            attn_fallback(bad, tag, gs, frag, keep, args.wq, args.kc, args.vc);
            frag_load(q, frag); frag_load(a1, frag + 4096); frag_load(a2, frag + 8192); frag_load(p, keep);
            anchor(frag, q[0] & q[4] & q[8] & q[12] & q[16] & q[20] & q[24] & q[28] & p[0] & p[4] & p[8] & p[12] & p[16] & p[20] & p[24] & p[28]);
        }
        DBG_T(80);
        DBG_G(124);

        const uint32_t eye = (tid_ >> 3 & 3) == (tid_ & 3) ? 0x3f80u << ((tid_ & 4) * 4) : 0;
        auto sum8 = [&](uint32_t* r, const uint4 (&v)[8]) {
            float d[16];
#pragma unroll
            for (int i = 0; i < 16; i++) d[i] = 0.f;
#pragma unroll
            for (int src = 0; src < 8; src++) {
                mma1688(d + 8 * (src & 1), v[src].x, v[src].y, eye);
                mma1688(d + 8 * (src & 1) + 4, v[src].z, v[src].w, eye);
            }
#pragma unroll
            for (int i = 0; i < 4; i++) r[i] = pack_bf16(d[2 * i] + d[8 + 2 * i], d[2 * i + 1] + d[9 + 2 * i]);
        };
        uint4 v2[8], v3[8], wf[23];
        uint2 u4[8], gw[9];
        uint32_t x1[20], xs, pa, ta;
        const uint8_t *mb, *mb4;
        auto load_wf = [&](auto lo, auto hi) {
            const uint32_t wa = sb + SM_Q + ((tid_ & 8) * (D_ / 8) + cw * 16 + (tid_ & 7) + (tid_ & 16) / 2) * 80;
            const uint32_t wb = wa + (512 - cw * 8) * 80 - (tid_ & 16) * 39;
#pragma unroll
            for (int i = lo.value; i < hi.value; i++) wf[i] = ldsm4t(i < 20 ? wa + (i / 5) * 10240 + (i % 5) * 16 : wb + (i - 20) * 32);
        };
        uint32_t at[18];
        {
            float (&u)[32] = reinterpret_cast<float (&)[32]>(o);
            uint32_t off = 0;
            auto turn = [&](const uint32_t (&a)[32], const uint32_t (&b)[32], int acc) {
                uint64_t dv = args.d0 + off * (SLOT / 128);
                bar_sync(1 + w, 192);
                fence_regs(u);
                WG_FENCE();
#pragma unroll
                for (int ks = 0; ks < 16; ks++) {
                    const uint32_t* f = ks < 8 ? &a[4 * ks] : &b[4 * ks - 32];
                    mma_rs64<1>(u, f[0], f[1], f[2], f[3], dv, ks | acc);
                    if (ks == OSPLIT - 1) WG_COMMIT();
                }
                WG_COMMIT();
                WG_WAIT(1);
            };
            auto done = [&]() {
                WG_WAIT(0);
                fence_regs(u);
                release4(off);
                off = (off + 8) & 24;
            };
            auto store = [&](uint8_t* dst) {
#pragma unroll
                for (int i = 0; i < 4; i++)
                    st_relaxed4(dst + i * 512, pack_bf16(u[8 * i], u[8 * i + 1]), pack_bf16(u[8 * i + 2], u[8 * i + 3]),
                                pack_bf16(u[8 * i + 4], u[8 * i + 5]), pack_bf16(u[8 * i + 6], u[8 * i + 7]));
            };
            pa = sb + w * (UNIT - 2048) + tid_ * 16;
#pragma unroll
            for (int i = 0; i < 8; i++) at[i] = 0;
            fence_regs(q); fence_regs(p);
            uint8_t* dst = frag;
#pragma unroll
            for (int i = 0; i < 8; i++) asm volatile("" : "=r"(v2[i].x), "=r"(v2[i].y), "=r"(v2[i].z), "=r"(v2[i].w));
#pragma unroll 1
            for (int k = 0; k < 8; k++, dst += 2048) {
                const uint32_t poff = (off + 8) & 24;
                const bool sum = (0xa0 >> k) & 1;
                turn(q, p, 0);
                handoff();
                auto sum_p = [&](auto lo, auto hi) {
#pragma unroll
                    for (int i = lo.value; i < hi.value; i++) {
                        float a[8], b[8];
#pragma unroll
                        for (int src = 0; src < 8; src++) {
                            const uint32_t x = i == 0 ? v2[src].x : i == 1 ? v2[src].y : i == 2 ? v2[src].z : v2[src].w;
                            a[src] = bf_lo(x); b[src] = bf_hi(x);
                        }
                        at[i] = at[4 + i];
                        at[4 + i] = pack_bf16(((a[0] + a[2]) + (a[4] + a[6])) + ((a[1] + a[3]) + (a[5] + a[7])),
                                              ((b[0] + b[2]) + (b[4] + b[6])) + ((b[1] + b[3]) + (b[5] + b[7])));
                    }
                };
                if (sum) {
                    mbar_wait(bar_full + poff, 1);
#pragma unroll
                    for (int src = 0; src < 8; src++) v2[src] = lds128(pa + poff * (SLOT / 8) + src * 2048);
                    __syncwarp();
                    release(poff >> 3);
                    done();
                    off = (off + 8) & 24;
                    sum_p(IC<0>{}, IC<2>{});
                } else {
                    done();
                }
                turn(a1, a2, 1);
                handoff();
                if (sum) sum_p(IC<2>{}, IC<4>{});
                done();
                store(dst);
                __syncwarp();
                asm volatile("{\n.reg .pred p;\nsetp.ne.b32 p, %1, 0;\n@p mbarrier.arrive.shared::cta.b64 _, [%0];\n}"
                             ::"r"(bar_pub + 4 + 4 * k), "r"(lane ? 0 : (0x2a >> k) & 1) : "memory");
            }
            turn(q, p, 0);
            handoff();
            mb = padd(g_frag, (qb * 64 + j) * WREG + 3 * 4096 + tid_ * 16);
            mb4 = padd(mb, 4096 + ((cw >> 1) - cw) * 512 + (cw & 1) * 8);
            xs = sb + (tid_ & 15) * XP + (tid_ & 16) + cw * 32;
            ta = sb + (cw * 8 + (tid_ & 3)) * 8;
#pragma unroll
            for (int k = 0; k < 9; k++) {
                gw[k] = lds64(ta + SM_T + (k < 8 ? (k >> 1) * 64 + (k & 1) * 4 : 256 - cw * 4) * 8);
                if (!(tid_ & 4)) gw[k].y = 0x3f803f80u;
            }
            mbar_wait(bar_g, 0);
            done();
            load_wf(IC<0>{}, IC<WF0>{});
            turn(a1, a2, 1);
            if (w == 0) handoff();
            done();
            store(dst);
            mbar_wait(bar_full, 0);
            rows_load(x1, xs, cw);
            if (w == 0) bar_sync(5, 256); else bar_arrive(5, 256);
        }
        DBG_T(81);
        DBG_G(122);

        {
        const int tid = tid_, lane = tid & 31;
        const int g8 = lane >> 2, qd = lane & 3, l16 = lane & 15;
        uint32_t h2[18], gb[9], k1, k2;
        float4* rec = reinterpret_cast<float4*>(red + 128);
        const uint2* candp = reinterpret_cast<const uint2*>(padd(g_cand, ((bx & (CREP - 1)) * NCTA + (tid >> 1)) * 32 + (tid & 1) * 8));
        uint2 cd;
        auto stage_out = [&]() {
#pragma unroll
            for (int k = 0; k < 9; k++) {
                x1[2 * k] = badd2(x1[2 * k], bmul2(gb[k], h2[2 * k]));
                x1[2 * k + 1] = badd2(x1[2 * k + 1], bmul2(gb[k], h2[2 * k + 1]));
            }
#pragma unroll
            for (int ch = 0; ch < 4; ch++) stsm_x4(xs + ch * 256, x1[4 * ch], x1[4 * ch + 1], x1[4 * ch + 2], x1[4 * ch + 3]);
            asm volatile("stmatrix.sync.aligned.m8n8.x2.shared.b16 [%0], {%1, %2};" ::"r"(xs + 1024 - cw * 16), "r"(x1[16]), "r"(x1[17]) : "memory");
        };
        {
            uint32_t it = 0, miss;
            mbar_wait(bar_full + 8, 0);
#pragma unroll
            for (int src = 0; src < 8; src++) v2[src] = lds128(pa + SLOT + src * 2048);
            sum8(at + 8, v2);
            float st[12];
#pragma unroll
            for (int i = 0; i < 12; i++) st[i] = 0.f;
            auto add_pair = [&](int k) {
                x1[2 * k] = badd2(x1[2 * k], bmul2(gw[k].x, at[2 * k]));
                x1[2 * k + 1] = badd2(x1[2 * k + 1], bmul2(gw[k].x, at[2 * k + 1]));
                stats_add(st, x1[2 * k], x1[2 * k + 1], gw[k].y);
            };
#pragma unroll
            for (int k = 0; k < 6; k++) add_pair(k);
            mbar_wait(bar_full + 16, 0);
#pragma unroll
            for (int src = 0; src < 8; src++) v3[src] = lds128(pa + 2 * SLOT + src * 2048);
            miss = __vimax3_u32(__vimax3_u32(v3[0].x, v3[0].z, v3[1].x), __vimax3_u32(v3[1].z, v3[2].x, v3[2].z), __vimax3_u32(v3[3].x, v3[3].z, v3[4].x));
            miss = __vimax3_u32(miss, __vimax3_u32(v3[4].z, v3[5].x, v3[5].z), max(__vimax3_u32(v3[6].x, v3[6].z, v3[7].x), v3[7].z));
            if (__any_sync(0xffffffffu, miss == ~0u))
#pragma unroll 1
            do {
                miss = 0;
#pragma unroll
                for (int src = 0; src < 8; src++) reload16(v3[src], mb + (size_t)src * 8 * WREG, miss);
            } while (__any_sync(0xffffffffu, miss) && ++it < SPIN / 16);
            if (lane < 4) mbar_arrive_cluster(rel_base + 8 * (1 + (lane >> 1)));
            sum8(at + 12, v3);
            add_pair(6); add_pair(7);
            load_wf(IC<WF0>{}, IC<WF1>{});
            uint2 cs[9];
#pragma unroll
            for (int k = 0; k < 9; k++) cs[k] = lds64(ta + SM_TC + (k < 8 ? (k >> 1) * 64 + (k & 1) * 4 : 256 - cw * 4) * 8);
            mbar_wait(bar_pre, 0);
            mbar_wait(bar_full + 24, 0);
#pragma unroll
            for (int src = 0; src < 8; src++) u4[src] = lds64(sb + 3 * SLOT + src * 2048 + (cw >> 1) * 512 + lane * 16 + (cw & 1) * 8);
            miss = __vimax3_u32(__vimax3_u32(u4[0].x, u4[1].x, u4[2].x), __vimax3_u32(u4[3].x, u4[4].x, u4[5].x), max(u4[6].x, u4[7].x));
            if (__any_sync(0xffffffffu, miss == ~0u))
#pragma unroll 1
            do {
                miss = 0;
#pragma unroll
                for (int src = 0; src < 8; src++) reload8(u4[src], mb4 + (size_t)src * 8 * WREG, miss);
            } while (__any_sync(0xffffffffu, miss) && ++it < SPIN / 16);
            float d[8] = {0.f, 0.f, 0.f, 0.f, 0.f, 0.f, 0.f, 0.f};
#pragma unroll
            for (int i = 0; i < 4; i++) mma16816(d + 4 * (i & 1), u4[2 * i].x, u4[2 * i].y, u4[2 * i + 1].x, u4[2 * i + 1].y, eye, eye);
            at[16] = pack_bf16(d[0] + d[4], d[1] + d[5]); at[17] = pack_bf16(d[2] + d[6], d[3] + d[7]);
            add_pair(8);
            DBG_G(123);
            const float2 ws = *reinterpret_cast<const float2*>(smem_raw + SM_TS);
            uint4* cdst = padd(g_cand, (tid * NCTA + rg) * 32);
            uint32_t mean2;
            float dot;
            const float rsd = rows_stats(st, rec, cw, lane, mean2, dot);
            const uint32_t b = __float_as_uint(fmaf(fmaf(-bf_lo(mean2), ws.x, dot), rsd, ws.y));
            const uint32_t key = (((b & 0x80000000u) ? ~b : (b | 0x80000000u)) | 2047u) - (rg * 16 + l16);
            top2(key, k1, k2);
            if (tid < CREP) st_relaxed(cdst, k1, tag, k2, tag);
            cd = ld_relaxed64(candp);
            rows_normalise(h2, x1, mean2, rsd, lane, [&]() {
#pragma unroll
                for (int k = 0; k < 9; k++) gb[k] = lds32(sb + SM_TG + (cw * 8 + qd + (k < 8 ? (k >> 1) * 64 + (k & 1) * 4 : 256 - cw * 4)) * 4);
                load_wf(IC<WF1>{}, IC<WF2>{});
            });
#pragma unroll
            for (int k = 0; k < 18; k++) h2[k] = badd2(bmul2(h2[k], cs[k >> 1].x), cs[k >> 1].y);
            const uint32_t r1 = ~k1 & 15, r2 = ~k2 & 15;
            uint32_t todo = ((r1 & 7) == g8) | ((r2 & 7) == g8) << 1;
#pragma unroll 1
            while (todo) {
                const bool second = !(todo & 1), hi = (second ? r2 : r1) & 8;
                uint4* dst = padd(g_rows, ((rg * 2 + second) * RSLOT + cw * 24 + qd) * 16);
                uint32_t r[18];
#pragma unroll
                for (int k = 0; k < 9; k++) { r[k] = hi ? h2[2 * k + 1] : h2[2 * k]; r[9 + k] = hi ? x1[2 * k + 1] : x1[2 * k]; }
                fence_regs(r);
                st_relaxed(dst, r[0], r[1], r[2], r[3]);
                st_relaxed(dst + 8, r[4], r[5], r[6], r[7]);
                st_relaxed64(reinterpret_cast<uint2*>(padd(dst, 256 - qd * 8)), r[8], r[17]);
                st_relaxed(dst + 4, r[9], r[10], r[11], r[12]);
                st_relaxed(dst + 12, r[13], r[14], r[15], r[16]);
                todo &= todo - 1;
            }
            __syncwarp();

            stage_out();
        }
        DBG_G(110);
        float4* part = reinterpret_cast<float4*>(smem_raw + 3 * SLOT + UNIT + 8192);
        bf16* act = reinterpret_cast<bf16*>(smem_raw + 3 * SLOT + UNIT + 4096);
        {
            uint32_t it = 0;
            const bool own = (tid >> 1) == rg;
            const uint32_t ks = sb + 3 * SLOT + UNIT + 5120;
#pragma unroll 1
            while (__any_sync(0xffffffffu, cd.y != tag && !own) && ++it < SPIN / 16)
                asm volatile("{\n.reg .pred p;\n.reg .b64 u;\nsetp.ne.u32 p, %1, %3;\nmov.b64 u, {%0, %1};\n"
                             "@p ld.relaxed.gpu.global.b64 u, [%2];\nmov.b64 {%0, %1}, u;\n}" : "+r"(cd.x), "+r"(cd.y) : "l"(candp), "r"(tag) : "memory");
            asm volatile("st.shared.u32 [%0], %1;" ::"r"(ks + tid * 4), "r"(own ? (tid & 1) ? k2 : k1 : cd.x) : "memory");
            bar_sync(3, 256);
            DBG_G(111);
            const uint4 a = lds128(ks + lane * 16), b = lds128(ks + 512 + lane * 16);
            const uint32_t a1 = max(a.x, a.z), a2 = __vimax3_u32(min(a.x, a.z), a.y, a.w);
            const uint32_t b1 = max(b.x, b.z), b2 = __vimax3_u32(min(b.x, b.z), b.y, b.w);
            const uint32_t c1 = max(a1, b1), c2 = __vimax3_u32(min(a1, b1), a2, b2);
            k1 = __reduce_max_sync(0xffffffffu, c1);
            k2 = __reduce_max_sync(0xffffffffu, c1 == k1 ? c2 : c1);
        }
        const int sel0 = ~k1 & 2047, sel1 = ~k2 & 2047;
        const uint32_t slot0 = (sel0 >> 4) * 2, slot1 = (sel1 >> 4) * 2 + ((sel0 ^ sel1) < 16);
        uint4 da[13];
        {
            const uint4* hp = padd(g_rows, (((g8 & 1) ? slot1 : slot0) * RSLOT + cw * 24 + qd) * 16);
            const uint2* hp2 = reinterpret_cast<const uint2*>(padd(hp, 256 - qd * 8));
            uint4 hv[2] = {ld_relaxed2(hp), ld_relaxed2(hp + 8)};
            uint2 hw = ld_relaxed64(hp2);
            if (tid == 255) {
                reinterpret_cast<int2*>(red)[8] = make_int2(sel0, sel1);
                mbar_arrive(bar_out);
            }
            load_wf(IC<WF2>{}, IC<23>{});
            mbar_wait(bar_full + 8, 1);
            mbar_wait(bar_full + 16, 1);
            auto load_d = [&](auto lo, auto hi) {
                const int r = (lane & 7) + (lane & 16) / 2;
                const uint32_t d0 = sb + SLOT + r * XP + cw * 144 + (lane & 8) * 2, d1 = d0 + (r < 2 ? 16 * XP : SLOT - 2 * XP);
                const uint32_t d2 = sb + 2 * SLOT + (14 + (lane & 3)) * XP + cw * 144 + (lane >> 3) * 16;
#pragma unroll
                for (int i = lo.value; i < hi.value; i++) da[i] = ldsm4t(i < 10 ? ((i & 1) ? d1 : d0) + (i >> 1) * 32 : d2 + (i - 10) * 64);
            };
            load_d(IC<0>{}, IC<DL>{});
            uint32_t it = 0, miss;
            float f0 = 1.f, f1 = 1.f;
            hold(f0, f1);
            if (__any_sync(0xffffffffu, max(__vimax3_u32(__vimax3_u32(__float_as_uint(f0), hv[0].x, hv[0].z), hv[1].x, hv[1].z), hw.x) == ~0u))
#pragma unroll 1
            do {
                miss = 0;
                reload16(hv[0], hp, miss);
                reload16(hv[1], hp + 8, miss);
                reload8(hw, hp2, miss);
            } while (__any_sync(0xffffffffu, miss) && ++it < SPIN / 16);
            DBG_G(112);
            float acc[20];
#pragma unroll
            for (int i = 0; i < 20; i++) acc[i] = 0.f;
#pragma unroll
            for (int i = 0; i < 5; i++) mma1688(acc + 4 * i, (i & 1) ? wf[20 + i / 2].z : wf[20 + i / 2].x, (i & 1) ? wf[20 + i / 2].w : wf[20 + i / 2].y, hw.x);
#pragma unroll
            for (int i = 0; i < 20; i++)
                mma16816(acc + 4 * (i % 5), wf[i].x, wf[i].y, wf[i].z, wf[i].w, (i / 5 & 1) ? hv[i / 10].z : hv[i / 10].x, (i / 5 & 1) ? hv[i / 10].w : hv[i / 10].y);
            if (qd == 0) {
#pragma unroll
                for (int i = 0; i < 5; i++) part[cw * 40 + i * 8 + g8] = make_float4(acc[4 * i], acc[4 * i + 1], acc[4 * i + 2], acc[4 * i + 3]);
            }
            load_d(IC<DL>{}, IC<13>{});
        }
        {
            uint2* dst = padd(g_ypart, ((cw * 9 * NCTA + bx) * 8 + g8) * 8);
            bar_sync(3, 256);
            if (cw < 5) {
                const float* pp = reinterpret_cast<const float*>(part) + ((bx & 1) << 4) + tid;
                const float g = rbf(((pp[0] + pp[160]) + (pp[320] + pp[480])) + ((pp[640] + pp[800]) + (pp[960] + pp[1120])));
                const float v = rbf(g * sigmoidf_(g)) * __shfl_down_sync(0xffffffffu, g, 2);
                if (!(tid & 2)) act[(tid & 1) * 56 + (tid >> 2)] = __float2bfloat16_rn(tid < 144 ? v : 0.f);
            }
            bar_sync(3, 256);
            DBG_G(113);
            const uint32_t ap = sb + 3 * SLOT + UNIT + 4096 + (lane & 1) * 112 + (lane >> 3) * 16;
            const uint4 b0 = ldsm4(ap);
            const uint32_t b1 = lds32(sb + 3 * SLOT + UNIT + 4096 + (g8 & 1) * 112 + 64 + qd * 4);
            float y[20];
#pragma unroll
            for (int i = 0; i < 20; i++) y[i] = 0.f;
#pragma unroll
            for (int i = 0; i < 5; i++) {
                mma16816(y + 4 * i, da[2 * i].x, da[2 * i].y, da[2 * i].z, da[2 * i].w, b0.x, b0.y);
                mma16816(y + 4 * i, da[2 * i + 1].x, da[2 * i + 1].y, da[2 * i + 1].z, da[2 * i + 1].w, b0.z, b0.w);
                mma1688(y + 4 * i, (i & 1) ? da[10 + i / 2].z : da[10 + i / 2].x, (i & 1) ? da[10 + i / 2].w : da[10 + i / 2].y, b1);
            }
            if (qd == 0) {
#pragma unroll
                for (int i = 0; i < 9; i++)
                    asm volatile("st.relaxed.gpu.global.v2.f32 [%0], {%1, %2};" ::"l"(dst + i * (NCTA * 8)), "f"(y[2 * i]), "f"(y[2 * i + 1]) : "memory");
            }
        }
        DBG_G(114);
        if (bx < 72) {
            const int G = bx, tok = g8 & 1, cp = G * 4 + qd;
            const uint2* src = padd(g_ypart, (bx * NCTA * 8 + tid) * 8);
            const uint8_t* hsrc = reinterpret_cast<const uint8_t*>(padd(g_rows, (tok ? slot1 : slot0) * (RSLOT * 16) +
                (G < 64 ? (G >> 1 & 7) * 384 + (G >> 5) * 128 + qd * 16 + (G >> 1 & 8) + (G & 1) * 4 : (G - 64) * 384 + 256 + qd * 8)));
            const uint8_t* xsrc = hsrc + (G < 64 ? 64 : 4);
            uint32_t* dst = padd(reinterpret_cast<uint32_t*>(args.out), (tok ? sel1 : sel0) * (D_ * 2) + cp * 4);
            const uint32_t gb = reinterpret_cast<const uint32_t*>(smem_raw + SM_TG)[cp];
            const uint32_t ksel = ((tok ? k2 : k1) & ~2047u) | 1024u;
            const float sg = sigmoidf_(rbf(__uint_as_float((ksel & 0x80000000u) ? (ksel & 0x7fffffffu) : ~ksel)));
            uint2 v[4];
            uint32_t hv = 0, xv = 0, it = 0, miss;
            if (cw == 0) { hv = ld_relaxed32(hsrc); xv = ld_relaxed32(xsrc); }
#pragma unroll
            for (int i = 0; i < 4; i++) v[i] = make_uint2(~0u, 0);
#pragma unroll 1
            do {
#pragma unroll
                for (int i = 0; i < 4; i++) reload8(v[i], src + i * 256, miss);
            } while (__any_sync(0xffffffffu, max(__vimax3_u32(v[0].x, v[1].x, v[2].x), v[3].x) == ~0u) && ++it < SPIN / 16);
#pragma unroll 1
            while (max(hv, xv) == ~0u && ++it < SPIN / 16) { hv = ld_relaxed32(hsrc); xv = ld_relaxed32(xsrc); }
            __syncwarp();
            float y0 = (__uint_as_float(v[0].x) + __uint_as_float(v[1].x)) + (__uint_as_float(v[2].x) + __uint_as_float(v[3].x));
            float y1 = (__uint_as_float(v[0].y) + __uint_as_float(v[1].y)) + (__uint_as_float(v[2].y) + __uint_as_float(v[3].y));
            y0 += __shfl_xor_sync(0xffffffffu, y0, 8); y1 += __shfl_xor_sync(0xffffffffu, y1, 8);
            y0 += __shfl_xor_sync(0xffffffffu, y0, 16); y1 += __shfl_xor_sync(0xffffffffu, y1, 16);
            if (lane < 8) reinterpret_cast<float2*>(rec)[cw * 8 + lane] = make_float2(y0, y1);
            bar_sync(3, 256);
            if (cw == 0) {
                const float4 t0_ = rec[(lane >> 3) * 4 + qd], t1_ = rec[16 + (lane >> 3) * 4 + qd];
                y0 = tok ? t0_.y + t1_.y : t0_.x + t1_.x; y1 = tok ? t0_.w + t1_.w : t0_.z + t1_.z;
                y0 += __shfl_xor_sync(0xffffffffu, y0, 8); y1 += __shfl_xor_sync(0xffffffffu, y1, 8);
                y0 += __shfl_xor_sync(0xffffffffu, y0, 16); y1 += __shfl_xor_sync(0xffffffffu, y1, 16);
                const uint32_t y2 = bmul2(pack_bf16(y0, y1), pack_bf16(sg, sg));
                if (lane < 8) *dst = badd2(xv, bmul2(gb, badd2(hv, y2)));
            }
        }
        }
        DBG_T(88);
        DBG_G(121);
    }
}

typedef CUresult (*EncodeFn)(CUtensorMap*, CUtensorMapDataType, cuuint32_t, void*, const cuuint64_t*, const cuuint64_t*,
                             const cuuint32_t*, const cuuint32_t*, CUtensorMapInterleave, CUtensorMapSwizzle,
                             CUtensorMapL2promotion, CUtensorMapFloatOOBfill);

static void make_map(EncodeFn enc, CUtensorMap* m, const void* ptr, int rank, const cuuint64_t* dims,
                     const cuuint64_t* strides, const cuuint32_t* box, CUtensorMapSwizzle sw = CU_TENSOR_MAP_SWIZZLE_128B,
                     CUtensorMapDataType dt = CU_TENSOR_MAP_DATA_TYPE_BFLOAT16) {
    const cuuint32_t es[3] = {1, 1, 1};
    enc(m, dt, rank, const_cast<void*>(ptr), dims, strides, box, es,
        CU_TENSOR_MAP_INTERLEAVE_NONE, sw, CU_TENSOR_MAP_L2_PROMOTION_L2_128B,
        CU_TENSOR_MAP_FLOAT_OOB_FILL_NONE);
}

extern "C" void kernel_launch(void* const* d_in, const int* in_sizes, int n_in, void* d_out, int out_size) {
    const bf16* x = (const bf16*)d_in[0];
    const bf16* kc = (const bf16*)d_in[1];
    const bf16* vc = (const bf16*)d_in[2];
    const bf16* wq = (const bf16*)d_in[3];
    const bf16* wo = (const bf16*)d_in[4];
    const bf16* w_r = (const bf16*)d_in[6];
    const bf16* w_gate = (const bf16*)d_in[7];
    const bf16* w_up = (const bf16*)d_in[8];
    const bf16* w_down = (const bf16*)d_in[9];
    const bf16* cvec = (const bf16*)d_in[10];
    const bf16* w_mod = (const bf16*)d_in[11];
    bf16* out = (bf16*)d_out;

    void* fn = nullptr;
    cudaDriverEntryPointQueryResult qr;
    cudaGetDriverEntryPoint("cuTensorMapEncodeTiled", &fn, cudaEnableDefault, &qr);
    EncodeFn enc = (EncodeFn)fn;
    void* p_s;
    cudaGetSymbolAddress(&p_s, g_s);

    CUtensorMap tm_wq, tm_k, tm_v, tm_wo, tm_p, tm_x, tm_d, tm_g, tm_u;
    { cuuint64_t d[2] = {QD, D_}, s[1] = {QD * 2}; cuuint32_t b[2] = {64, 128}; make_map(enc, &tm_wq, wq, 2, d, s, b); }
    { cuuint64_t d[2] = {DH, HKV * S_}, s[1] = {DH * 2}; cuuint32_t b[2] = {64, 128};
      make_map(enc, &tm_k, kc, 2, d, s, b); make_map(enc, &tm_v, vc, 2, d, s, b); }
    { cuuint64_t d[2] = {D_, QD}, s[1] = {D_ * 2}; cuuint32_t b[2] = {64, 128}; make_map(enc, &tm_wo, wo, 2, d, s, b); }
    { cuuint64_t d[3] = {256, 160, NCTA}, s[2] = {1024, 8 * WREG}; cuuint32_t b[3] = {256, 2, 8};
      make_map(enc, &tm_p, ((Scratch*)p_s)->frag, 3, d, s, b, CU_TENSOR_MAP_SWIZZLE_NONE, CU_TENSOR_MAP_DATA_TYPE_UINT32); }
    { cuuint64_t d[2] = {D_ / 4, S_}, s[1] = {D_ * 2}; cuuint32_t b[2] = {XP / 8, 16};
      make_map(enc, &tm_x, x, 2, d, s, b, CU_TENSOR_MAP_SWIZZLE_NONE, CU_TENSOR_MAP_DATA_TYPE_UINT64); }
    { cuuint64_t d[2] = {D_ / 4, F_}, s[1] = {D_ * 2}; cuuint32_t b[2] = {XP / 8, 18};
      make_map(enc, &tm_d, w_down, 2, d, s, b, CU_TENSOR_MAP_SWIZZLE_NONE, CU_TENSOR_MAP_DATA_TYPE_UINT64); }
    { cuuint64_t d[2] = {F_, D_}, s[1] = {F_ * 2}; cuuint32_t b[2] = {40, 24};
      make_map(enc, &tm_g, w_gate, 2, d, s, b, CU_TENSOR_MAP_SWIZZLE_NONE); make_map(enc, &tm_u, w_up, 2, d, s, b, CU_TENSOR_MAP_SWIZZLE_NONE); }

    cudaFuncSetAttribute(fused_kernel<true>, cudaFuncAttributeMaxDynamicSharedMemorySize, SM_TOTAL);
    cudaFuncSetAttribute(fused_kernel<false>, cudaFuncAttributeMaxDynamicSharedMemorySize, SM_TOTAL);
    cudaLaunchConfig_t cfg = {};
    cfg.gridDim = NCTA + 4; cfg.blockDim = 384; cfg.dynamicSmemBytes = SM_TOTAL;
    cudaLaunchAttribute at;
    at.id = cudaLaunchAttributeClusterDimension; at.val.clusterDim.x = 2; at.val.clusterDim.y = 1; at.val.clusterDim.z = 1;
    cfg.attrs = &at; cfg.numAttrs = 1;
    int ncl = 0;
    if (cudaOccupancyMaxActiveClusters(&ncl, fused_kernel<true>, &cfg) != cudaSuccess) { ncl = 0; cudaGetLastError(); }
    Args args{w_mod, cvec, (Scratch*)p_s, desc_lo(0, UNIT) | (0x40000040ull << 32), out, x, kc, vc, wq, wo, w_r, w_down};
    if (USE_SPARE && ncl >= NCTA / 2 + 2)
        fused_kernel<true><<<NCTA + 4, 384, SM_TOTAL>>>(args, tm_wq, tm_k, tm_v, tm_wo, tm_p, tm_x, tm_d, tm_g, tm_u);
    else
        fused_kernel<false><<<NCTA, 384, SM_TOTAL>>>(args, tm_wq, tm_k, tm_v, tm_wo, tm_p, tm_x, tm_d, tm_g, tm_u);
}
```

```cpp
#include <cuda_runtime.h>
#include <cuda_bf16.h>
#include <cuda.h>
#include <stdint.h>
#include <math.h>

typedef __nv_bfloat16 bf16;

constexpr int S_ = 2048;
constexpr int D_ = 576;
constexpr int HQ = 32, HKV = 16, DH = 128;
constexpr int F_ = 4608;
constexpr int QD = HQ * DH;

constexpr int NCTA = 128;
constexpr int WREG = 5 * 4096;
constexpr int CREP = 8;
constexpr int RSLOT = 192;
constexpr int MREP = 4;
struct Scratch {
    unsigned int epoch[128];
    unsigned int flag_mod[NCTA];
    unsigned int flag_part[16 * 256];
    unsigned int flag_q3[16 * 32];
    unsigned int flag_h[NCTA * 32];
    uint2 mod1[MREP * D_];
    uint32_t mod2[4 * D_];
    uint4 cand[CREP * NCTA * 2];
    uint2 ypart[72 * NCTA * 8];
    uint4 h[2][NCTA * 36 * 32];
    uint4 q3[NCTA * 8 * 128];
    uint4 rows[NCTA * 2 * RSLOT];
    uint8_t frag[NCTA * 8 * WREG];
    uint8_t keep[NCTA * 8 * 4096];
};
__device__ __align__(1024) Scratch g_s;
#define g_h gs->h[tag & 1]
#define g_q3 gs->q3
#define g_keep gs->keep
#define g_flag_h gs->flag_h
#define g_flag_part gs->flag_part
#define g_flag_mod gs->flag_mod
#define g_flag_q3 gs->flag_q3
#define g_frag gs->frag
#define g_cand gs->cand
#define g_ypart gs->ypart
#define g_rows gs->rows

#define DBG_INIT()
#define DBG_P(i)
#define DBG_PG(i)
#define DBG_T(i)
#define DBG_G(i)

__device__ __forceinline__ uint32_t pack_bf16(float lo, float hi) {
    uint32_t r;
    asm("cvt.rn.bf16x2.f32 %0, %1, %2;" : "=r"(r) : "f"(hi), "f"(lo));
    return r;
}
__device__ __forceinline__ float rbf(float x) { return __uint_as_float(pack_bf16(0.f, x)); }
__device__ __forceinline__ float bf_lo(uint32_t v) { return __uint_as_float(v << 16); }
__device__ __forceinline__ float bf_hi(uint32_t v) { return __uint_as_float(v & 0xffff0000u); }
__device__ __forceinline__ float ex2(float x) {
    float y;
    asm("ex2.approx.ftz.f32 %0, %1;" : "=f"(y) : "f"(x));
    return y;
}
template <class T>
__device__ __forceinline__ T* padd(T* p, uint32_t off) {
    unsigned long long r;
    asm("{\n.reg .b32 l, h;\nmov.b64 {l, h}, %1;\nadd.cc.u32 l, l, %2;\naddc.u32 h, h, 0;\nmov.b64 %0, {l, h};\n}" : "=l"(r) : "l"(p), "r"(off));
    return reinterpret_cast<T*>(r);
}
__device__ __forceinline__ uint32_t smem_u32(const void* p) { return (uint32_t)__cvta_generic_to_shared(p); }
__device__ __forceinline__ void mbar_init(uint32_t bar, uint32_t cnt) {
    asm volatile("mbarrier.init.shared::cta.b64 [%0], %1;" ::"r"(bar), "r"(cnt) : "memory");
}
__device__ __forceinline__ void mbar_expect_tx(uint32_t bar, uint32_t bytes) {
    asm volatile("mbarrier.arrive.expect_tx.shared::cta.b64 _, [%0], %1;" ::"r"(bar), "r"(bytes) : "memory");
}
__device__ __forceinline__ void mbar_arrive(uint32_t bar) {
    asm volatile("mbarrier.arrive.shared::cta.b64 _, [%0];" ::"r"(bar) : "memory");
}
__device__ __forceinline__ void arrive_if(uint32_t bar, bool on) {
    asm volatile("{\n.reg .pred p;\nsetp.ne.b32 p, %1, 0;\n@p mbarrier.arrive.shared::cta.b64 _, [%0];\n}" ::"r"(bar), "r"((uint32_t)on) : "memory");
}
__device__ __forceinline__ void mbar_arrive_cluster(uint32_t cluster_addr) {
    asm volatile("mbarrier.arrive.shared::cluster.b64 _, [%0];" ::"r"(cluster_addr) : "memory");
}
constexpr uint32_t SPIN = 1u << 20;
__device__ __forceinline__ void mbar_wait(uint32_t bar, uint32_t parity) {
    asm volatile("{\n.reg .pred p;\n.reg .b32 c;\nmov.b32 c, 0;\n"
                 "W_%=:\nmbarrier.try_wait.parity.shared::cta.b64 p, [%0], %1;\n"
                 "add.u32 c, c, 1;\nsetp.lt.and.u32 p, c, 0x100000, !p;\n@p bra W_%=;\n}"
                 ::"r"(bar), "r"(parity) : "memory");
}
__device__ __forceinline__ void anchor(uint32_t addr, float v) {
    asm volatile("{\n.reg .pred p;\nsetp.lt.f32 p, %1, 0f00000000;\n@p st.volatile.shared.f32 [%0], %1;\n}" ::"r"(addr), "f"(v) : "memory");
}
__device__ __forceinline__ void anchor(uint32_t addr, uint32_t v) {
    asm volatile("{\n.reg .pred p;\nsetp.eq.u32 p, %1, 0xffffffff;\n@p st.volatile.shared.u32 [%0], %1;\n}" ::"r"(addr), "r"(v) : "memory");
}
__device__ __forceinline__ void anchor(void* p, uint32_t v) {
    asm volatile("{\n.reg .pred p;\nsetp.eq.u32 p, %1, 0xffffffff;\n@p st.volatile.u32 [%0], %1;\n}" ::"l"(p), "r"(v) : "memory");
}
__device__ __forceinline__ void hold(float& a, float& b) {
    asm volatile("{\n.reg .pred p;\n.reg .b64 t;\n.reg .b32 l, h;\nmov.u64 t, %%clock64;\nmov.b64 {l, h}, t;\nsetp.eq.u32 p, h, 0xffffffff;\n"
                 "@p mov.f32 %0, 0f00000000;\n@p mov.f32 %1, 0f00000000;\n}" : "+f"(a), "+f"(b) :: "memory");
}
__device__ __forceinline__ void mbar_wait_sleep(uint32_t bar, uint32_t parity) {
    asm volatile("{\n.reg .pred p;\n.reg .b32 c;\nmov.b32 c, 0;\n"
                 "W_%=:\nmbarrier.try_wait.parity.shared::cta.b64 p, [%0], %1, 5000;\n"
                 "add.u32 c, c, 1;\nsetp.lt.and.u32 p, c, 0x20000, !p;\n@p bra W_%=;\n}"
                 ::"r"(bar), "r"(parity) : "memory");
}
__device__ __forceinline__ uint32_t load_tag(const Scratch* gs) {
    uint32_t tag;
    asm volatile("ld.global.ca.u32 %0, [%1];" : "=r"(tag) : "l"(gs->epoch) : "memory");
    return tag + 1;
}
__device__ __forceinline__ uint4 ld_relaxed(const uint4* p) {
    uint4 v;
    asm volatile("ld.relaxed.gpu.global.v4.u32 {%0,%1,%2,%3}, [%4];" : "=r"(v.x), "=r"(v.y), "=r"(v.z), "=r"(v.w) : "l"(p) : "memory");
    return v;
}
__device__ __forceinline__ void st_relaxed(uint4* p, uint32_t a, uint32_t b, uint32_t c, uint32_t d) {
    asm volatile("{\n.reg .b64 u, v;\nmov.b64 u, {%1, %2};\nmov.b64 v, {%3, %4};\nst.relaxed.gpu.global.v2.b64 [%0], {u, v};\n}"
                 ::"l"(p), "r"(a), "r"(b), "r"(c), "r"(d) : "memory");
}
__device__ __forceinline__ void st_relaxed4(void* p, uint32_t a, uint32_t b, uint32_t c, uint32_t d) {
    asm volatile("st.relaxed.gpu.global.v4.u32 [%0], {%1, %2, %3, %4};" ::"l"(p), "r"(a), "r"(b), "r"(c), "r"(d) : "memory");
}
__device__ __forceinline__ uint2 ld_relaxed64(const uint2* p) {
    uint2 v;
    asm volatile("{\n.reg .b64 u;\nld.relaxed.gpu.global.b64 u, [%2];\nmov.b64 {%0, %1}, u;\n}" : "=r"(v.x), "=r"(v.y) : "l"(p) : "memory");
    return v;
}
__device__ __forceinline__ void st_relaxed64(uint2* p, uint32_t a, uint32_t b) {
    asm volatile("{\n.reg .b64 u;\nmov.b64 u, {%1, %2};\nst.relaxed.gpu.global.b64 [%0], u;\n}" ::"l"(p), "r"(a), "r"(b) : "memory");
}
__device__ __forceinline__ uint4 ld_relaxed2(const uint4* p) {
    uint4 v;
    asm volatile("{\n.reg .b64 u, w;\nld.relaxed.gpu.global.v2.b64 {u, w}, [%4];\nmov.b64 {%0, %1}, u;\nmov.b64 {%2, %3}, w;\n}"
                 : "=r"(v.x), "=r"(v.y), "=r"(v.z), "=r"(v.w) : "l"(p) : "memory");
    return v;
}
__device__ __forceinline__ void reload16(uint4& v, const void* p, uint32_t& miss) {
    asm volatile("{\n.reg .pred p;\n.reg .b32 m;\n.reg .b64 u, w;\nmax.u32 m, %0, %2;\nsetp.eq.u32 p, m, 0xffffffff;\n"
                 "mov.b64 u, {%0, %1};\nmov.b64 w, {%2, %3};\n@p ld.relaxed.gpu.global.v2.b64 {u, w}, [%5];\n"
                 "mov.b64 {%0, %1}, u;\nmov.b64 {%2, %3}, w;\n@p mov.u32 %4, 1;\n}"
                 : "+r"(v.x), "+r"(v.y), "+r"(v.z), "+r"(v.w), "+r"(miss) : "l"(p) : "memory");
}
__device__ __forceinline__ void reload8(uint2& v, const void* p, uint32_t& miss) {
    asm volatile("{\n.reg .pred p;\n.reg .b64 u;\nsetp.eq.u32 p, %0, 0xffffffff;\nmov.b64 u, {%0, %1};\n"
                 "@p ld.relaxed.gpu.global.b64 u, [%3];\nmov.b64 {%0, %1}, u;\n@p mov.u32 %2, 1;\n}"
                 : "+r"(v.x), "+r"(v.y), "+r"(miss) : "l"(p) : "memory");
}
__device__ __forceinline__ uint32_t ld_relaxed32(const void* p) {
    uint32_t v;
    asm volatile("ld.relaxed.gpu.global.u32 %0, [%1];" : "=r"(v) : "l"(p) : "memory");
    return v;
}
__device__ __forceinline__ void flag_wait(const unsigned int* p, uint32_t tag) {
    uint32_t v, it = 0;
#pragma unroll 1
    do {
        asm volatile("ld.relaxed.gpu.global.u32 %0, [%1];" : "=r"(v) : "l"(p) : "memory");
    } while (__any_sync(0xffffffffu, v != tag) && ++it < SPIN / 16);
    asm volatile("fence.acquire.gpu;" ::: "memory");
    __syncwarp();
}
__device__ __forceinline__ bool elect() {
    uint32_t p;
    asm volatile("{\n.reg .pred p;\nelect.sync _|p, 0xffffffff;\nselp.u32 %0, 1, 0, p;\n}" : "=r"(p));
    return p;
}
__device__ __forceinline__ void flag_release(unsigned int* p, uint32_t tag) {
    asm volatile("st.release.gpu.global.u32 [%0], %1;" ::"l"(p), "r"(tag) : "memory");
}
__device__ __forceinline__ uint32_t touch(const void* p) {
    uint32_t v;
    asm volatile("ld.global.nc.L1::no_allocate.L2::128B.u32 %0, [%1];" : "=r"(v) : "l"(p));
    return v;
}
__device__ __forceinline__ void bar_sync(int id, int n) { asm volatile("bar.sync %0, %1;" ::"r"(id), "r"(n) : "memory"); }
__device__ __forceinline__ void bar_arrive(int id, int n) { asm volatile("bar.arrive %0, %1;" ::"r"(id), "r"(n) : "memory"); }

constexpr uint64_t EVICT_NORMAL = 0x1000000000000000ull, EVICT_FIRST = 0x12F0000000000000ull;
__device__ __forceinline__ void tma2d(uint32_t dst, const CUtensorMap* m, int c0, int c1, uint32_t bar) {
    asm volatile("cp.async.bulk.tensor.2d.shared::cluster.global.mbarrier::complete_tx::bytes.L2::cache_hint [%0], [%1, {%3, %4}], [%2], %5;"
                 ::"r"(dst), "l"(m), "r"(bar), "r"(c0), "r"(c1), "l"(EVICT_FIRST) : "memory");
}
__device__ __forceinline__ void tma2d_mc(uint32_t dst, const CUtensorMap* m, int c0, int c1, uint32_t bar, uint64_t pol) {
    asm volatile("cp.async.bulk.tensor.2d.shared::cluster.global.mbarrier::complete_tx::bytes.multicast::cluster.L2::cache_hint [%0], [%1, {%3, %4}], [%2], %5, %6;"
                 ::"r"(dst), "l"(m), "r"(bar), "r"(c0), "r"(c1), "h"((uint16_t)3), "l"(pol) : "memory");
}
__device__ __forceinline__ void tma3d(uint32_t dst, const CUtensorMap* m, int c0, int c1, int c2, uint32_t bar) {
    asm volatile("cp.async.bulk.tensor.3d.shared::cluster.global.mbarrier::complete_tx::bytes.L2::cache_hint [%0], [%1, {%3, %4, %5}], [%2], %6;"
                 ::"r"(dst), "l"(m), "r"(bar), "r"(c0), "r"(c1), "r"(c2), "l"(EVICT_FIRST) : "memory");
}
__device__ __forceinline__ void bulk_load(uint32_t dst, const void* src, uint32_t bytes, uint32_t bar) {
    asm volatile("cp.async.bulk.shared::cluster.global.mbarrier::complete_tx::bytes [%0], [%1], %2, [%3];"
                 ::"r"(dst), "l"(src), "r"(bytes), "r"(bar) : "memory");
}
__device__ __forceinline__ void l2_prefetch(const void* src, uint32_t bytes) {
    asm volatile("cp.async.bulk.prefetch.L2.global [%0], %1;" ::"l"(src), "r"(bytes) : "memory");
}
__device__ __forceinline__ uint32_t bmul2(uint32_t a, uint32_t b) { uint32_t r; asm("mul.rn.bf16x2 %0, %1, %2;" : "=r"(r) : "r"(a), "r"(b)); return r; }
__device__ __forceinline__ uint32_t badd2(uint32_t a, uint32_t b) { uint32_t r; asm("add.rn.bf16x2 %0, %1, %2;" : "=r"(r) : "r"(a), "r"(b)); return r; }
__device__ __forceinline__ uint32_t bsub2(uint32_t a, uint32_t b) { uint32_t r; asm("sub.rn.bf16x2 %0, %1, %2;" : "=r"(r) : "r"(a), "r"(b)); return r; }
__device__ __forceinline__ uint32_t bmax2(uint32_t a, uint32_t b) { uint32_t r; asm("max.bf16x2 %0, %1, %2;" : "=r"(r) : "r"(a), "r"(b)); return r; }
__device__ __forceinline__ uint4 lds128(uint32_t a) { uint4 v; asm volatile("ld.shared.v4.u32 {%0,%1,%2,%3}, [%4];" : "=r"(v.x), "=r"(v.y), "=r"(v.z), "=r"(v.w) : "r"(a) : "memory"); return v; }
__device__ __forceinline__ uint2 lds64(uint32_t a) { uint2 v; asm volatile("ld.shared.v2.u32 {%0,%1}, [%2];" : "=r"(v.x), "=r"(v.y) : "r"(a) : "memory"); return v; }
__device__ __forceinline__ uint32_t lds32(uint32_t a) { uint32_t v; asm volatile("ld.shared.u32 %0, [%1];" : "=r"(v) : "r"(a) : "memory"); return v; }
__device__ __forceinline__ uint4 ldsm4(uint32_t a) {
    uint4 v;
    asm volatile("ldmatrix.sync.aligned.m8n8.x4.shared.b16 {%0,%1,%2,%3}, [%4];" : "=r"(v.x), "=r"(v.y), "=r"(v.z), "=r"(v.w) : "r"(a) : "memory");
    return v;
}
__device__ __forceinline__ uint4 ldsm4t(uint32_t a) {
    uint4 v;
    asm volatile("ldmatrix.sync.aligned.m8n8.x4.trans.shared.b16 {%0,%1,%2,%3}, [%4];" : "=r"(v.x), "=r"(v.y), "=r"(v.z), "=r"(v.w) : "r"(a) : "memory");
    return v;
}
__device__ __forceinline__ void mma1688(float* d, uint32_t a0, uint32_t a1, uint32_t b) {
    asm("mma.sync.aligned.m16n8k8.row.col.f32.bf16.bf16.f32 {%0,%1,%2,%3}, {%4,%5}, {%6}, {%0,%1,%2,%3};"
        : "+f"(d[0]), "+f"(d[1]), "+f"(d[2]), "+f"(d[3]) : "r"(a0), "r"(a1), "r"(b));
}
__device__ __forceinline__ void mma16816(float* d, uint32_t a0, uint32_t a1, uint32_t a2, uint32_t a3, uint32_t b0, uint32_t b1) {
    asm("mma.sync.aligned.m16n8k16.row.col.f32.bf16.bf16.f32 {%0,%1,%2,%3}, {%4,%5,%6,%7}, {%8,%9}, {%0,%1,%2,%3};"
                 : "+f"(d[0]), "+f"(d[1]), "+f"(d[2]), "+f"(d[3]) : "r"(a0), "r"(a1), "r"(a2), "r"(a3), "r"(b0), "r"(b1));
}
__device__ __forceinline__ void stsm_x4(uint32_t addr, uint32_t a, uint32_t b, uint32_t c, uint32_t d) {
    asm volatile("stmatrix.sync.aligned.m8n8.x4.shared.b16 [%0], {%1, %2, %3, %4};"
                 ::"r"(addr), "r"(a), "r"(b), "r"(c), "r"(d) : "memory");
}

__device__ __forceinline__ uint64_t mkdesc(uint32_t addr, uint32_t lbo, uint32_t sbo) {
    return (uint64_t)((addr & 0x3FFFF) >> 4) | ((uint64_t)(lbo >> 4) << 16) | ((uint64_t)(sbo >> 4) << 32) | (1ull << 62);
}
constexpr uint32_t SM0 = 1024;
__host__ __device__ constexpr uint32_t desc_lo(uint32_t off, uint32_t lbo) { return ((SM0 + off) >> 4) | ((lbo >> 4) << 16); }
#define WG_FENCE() asm volatile("wgmma.fence.sync.aligned;" ::: "memory")
#define WG_COMMIT() asm volatile("wgmma.commit_group.sync.aligned;" ::: "memory")
#define WG_WAIT(n) asm volatile("wgmma.wait_group.sync.aligned %0;" ::"n"(n) : "memory")

#define F8(a, i) "+f"(a[i]), "+f"(a[i + 1]), "+f"(a[i + 2]), "+f"(a[i + 3]), "+f"(a[i + 4]), "+f"(a[i + 5]), "+f"(a[i + 6]), "+f"(a[i + 7])
#define F16(a, i) F8(a, i), F8(a, i + 8)
#define F64(a) F16(a, 0), F16(a, 16), F16(a, 32), F16(a, 48)
#define F32(a) F16(a, 0), F16(a, 16)
#define L64 "%0,%1,%2,%3,%4,%5,%6,%7,%8,%9,%10,%11,%12,%13,%14,%15,%16,%17,%18,%19,%20,%21,%22,%23,%24,%25,%26,%27,%28,%29,%30,%31,%32,%33,%34,%35,%36,%37,%38,%39,%40,%41,%42,%43,%44,%45,%46,%47,%48,%49,%50,%51,%52,%53,%54,%55,%56,%57,%58,%59,%60,%61,%62,%63"
#define L32 "%0,%1,%2,%3,%4,%5,%6,%7,%8,%9,%10,%11,%12,%13,%14,%15,%16,%17,%18,%19,%20,%21,%22,%23,%24,%25,%26,%27,%28,%29,%30,%31"

template <int TB, int STEP = 128>
__device__ __forceinline__ void mma_rs128(float (&d)[64], uint32_t a0, uint32_t a1, uint32_t a2, uint32_t a3, uint64_t& b, int acc) {
    asm volatile("{\n.reg .pred p;\nsetp.ne.b32 p, %69, 0;\n"
                 "wgmma.mma_async.sync.aligned.m64n128k16.f32.bf16.bf16 {" L64 "}, {%65,%66,%67,%68}, %64, p, 1, 1, %70;\nadd.s64 %64, %64, %71;\n}"
                 : F64(d), "+l"(b) : "r"(a0), "r"(a1), "r"(a2), "r"(a3), "r"(acc), "n"(TB), "n"(STEP));
}
template <int TB>
__device__ __forceinline__ void mma_rs64(float (&d)[32], uint32_t a0, uint32_t a1, uint32_t a2, uint32_t a3, uint64_t& b, int acc) {
    asm volatile("{\n.reg .pred p;\nsetp.ne.b32 p, %37, 0;\n"
                 "wgmma.mma_async.sync.aligned.m64n64k16.f32.bf16.bf16 {" L32 "}, {%33,%34,%35,%36}, %32, p, 1, 1, %38;\nadd.s64 %32, %32, 128;\n}"
                 : F32(d), "+l"(b) : "r"(a0), "r"(a1), "r"(a2), "r"(a3), "r"(acc), "n"(TB));
}
template <int N>
__device__ __forceinline__ void fence_regs(float (&d)[N]) {
#pragma unroll
    for (int i = 0; i < N; i++) asm volatile("" : "+f"(d[i])::"memory");
}
template <int N>
__device__ __forceinline__ void fence_regs(uint32_t (&d)[N]) {
#pragma unroll
    for (int i = 0; i < N; i++) asm volatile("" : "+r"(d[i])::"memory");
}

template <int V> struct IC { static constexpr int value = V; };

constexpr int SLOT = 32768, UNIT = 16384;
constexpr int SM_Q = 4 * SLOT;
constexpr int SM_BAR = 7 * SLOT;
constexpr int SM_RED = SM_BAR + 512;
constexpr int SM_TOTAL = SM_BAR + 3072;
constexpr int XP = D_ * 2 + 16;
constexpr int M_MOD = 16 * XP;
constexpr int SM_T = SM_Q + 2 * D_ * 80, SM_TC = SM_T + D_ * 4, SM_TG = SM_TC + D_ * 4, SM_TS = SM_TG + D_ * 2;
constexpr float CS = 0.08838834764831845f * 1.4426950408889634f;
#define USE_SPARE 1
constexpr float POFF = 102.f, LMIN = 0x1p-104f;
#define LMAX 0.5f
constexpr int SPLIT = 10;
constexpr int STAGE = 11;
constexpr int ESPLIT = 3;
constexpr int QSPLIT = 4, OSPLIT = 6;
constexpr int WF0 = 3, WF1 = 13, WF2 = 19, DL = 9;
constexpr int PF_KV = 8;
constexpr int PF_WO = 50, PF_O = 60;

__device__ __forceinline__ int cluster_role() {
    int k;
    asm volatile("mov.u32 %0, %%ctaid.x;" : "=r"(k));
    const int c = (k & 1) << 6;
    k >>= 1;
    const int r = ((k - 36) * 37) >> 8, i = k - 36 - r * 7;
    return c + (k < 4 ? 12 + k : k < 36 ? ((k - 4) & 7) * 8 + ((k - 4) >> 3) : (i + (i > 0)) * 8 + ((4 + r) & 7));
}

struct Args {
    const bf16 *w_mod, *cvec;
    Scratch* gs;
    uint64_t d0;
    bf16* out;
    const bf16 *x, *kc, *vc, *wq, *wo, *w_r, *w_down;
};

__device__ __forceinline__ void frag_store(uint8_t* p, const uint32_t (&a)[32]) {
#pragma unroll
    for (int i = 0; i < 8; i++)
        __stcg(reinterpret_cast<uint4*>(p + i * 512), make_uint4(a[4 * i], a[4 * i + 1], a[4 * i + 2], a[4 * i + 3]));
}
template <int LO = 0, int HI = 8>
__device__ __forceinline__ void frag_load(uint32_t (&a)[32], const uint8_t* p) {
#pragma unroll
    for (int i = LO; i < HI; i++) {
        const uint4 v = ld_relaxed(reinterpret_cast<const uint4*>(p + i * 512));
        a[4 * i] = v.x; a[4 * i + 1] = v.y; a[4 * i + 2] = v.z; a[4 * i + 3] = v.w;
    }
}
__device__ __forceinline__ float quad_sum(float v) {
    v += __shfl_xor_sync(0xffffffffu, v, 1);
    return v + __shfl_xor_sync(0xffffffffu, v, 2);
}
__device__ __forceinline__ float quad_max(float v) {
    v = fmaxf(v, __shfl_xor_sync(0xffffffffu, v, 1));
    return fmaxf(v, __shfl_xor_sync(0xffffffffu, v, 2));
}
__device__ __forceinline__ float rcp_fast(float x) { float y; asm("rcp.approx.ftz.f32 %0, %1;" : "=f"(y) : "f"(x)); return y; }
__device__ __forceinline__ float sigmoidf_(float x) { return rcp_fast(1.f + ex2(-1.4426950408889634f * x)); }
__device__ __forceinline__ void top2(uint32_t k, uint32_t& k1, uint32_t& k2) {
    k1 = __reduce_max_sync(0xffffffffu, k);
    k2 = __reduce_max_sync(0xffffffffu, k == k1 ? 0 : k);
}

__device__ __forceinline__ void mod_fma(float (&a)[8], const uint4 w, float sc) {
    a[0] += sc * bf_lo(w.x); a[1] += sc * bf_hi(w.x); a[2] += sc * bf_lo(w.y); a[3] += sc * bf_hi(w.y);
    a[4] += sc * bf_lo(w.z); a[5] += sc * bf_hi(w.z); a[6] += sc * bf_lo(w.w); a[7] += sc * bf_hi(w.w);
}
__device__ __forceinline__ float mod_reduce(float (&a)[8], int lane) {
#pragma unroll
    for (int h = 4; h > 0; h >>= 1) {
        const bool up = lane & (8 / h);
#pragma unroll
        for (int i = 0; i < h; i++)
            a[i] = (up ? a[i + h] : a[i]) + __shfl_xor_sync(0xffffffffu, up ? a[i] : a[i + h], 8 / h);
    }
    return a[0] + __shfl_xor_sync(0xffffffffu, a[0], 16);
}

__device__ __forceinline__ float ln_stats(float sum, float sq, uint32_t& mean2) {
    const float mean = sum * (1.f / D_);
    const float var = fmaxf(fmaf(-mean, mean, sq * (1.f / D_)), 0.f);
    float sd;
    asm("sqrt.approx.ftz.f32 %0, %1;" : "=f"(sd) : "f"(rbf(rbf(var) + 1e-5f)));
    mean2 = pack_bf16(mean, mean);
    return rcp_fast(rbf(sd));
}
__device__ __forceinline__ uint32_t ln_pair(uint32_t x, uint32_t mean2, float rsd) {
    const uint32_t d = bsub2(x, mean2);
    return pack_bf16(bf_lo(d) * rsd, bf_hi(d) * rsd);
}
__device__ __forceinline__ void rows_load(uint32_t (&x)[20], uint32_t xs, int cw) {
#pragma unroll
    for (int ch = 0; ch < 5; ch++) {
        const uint4 v = ldsm4(ch < 4 ? xs + ch * 256 : xs + 1024 - cw * 16);
        x[4 * ch] = v.x; x[4 * ch + 1] = v.y; x[4 * ch + 2] = v.z; x[4 * ch + 3] = v.w;
    }
}
__device__ __forceinline__ void stats_add(float (&st)[12], uint32_t a, uint32_t b, uint32_t w) {
    mma1688(st, a, b, w);
    mma1688(st + 4, a, b, a);
    mma1688(st + 8, a, b, b);
}
__device__ __forceinline__ float rows_stats(const float (&st)[12], float4* rec, int cw, int lane, uint32_t& mean2, float& dot) {
    const int g8 = lane >> 2;
    if ((g8 >> 1) == (lane & 3)) {
        rec[cw * 16 + g8] = make_float4(st[0], (g8 & 1) ? st[5] : st[4], st[1], 0.f);
        rec[cw * 16 + 8 + g8] = make_float4(st[2], (g8 & 1) ? st[11] : st[10], st[3], 0.f);
    }
    bar_sync(3, 256);
    const float4* r = rec + (lane >> 4) * 64 + (lane & 15);
    const float4 s0 = r[0], s1 = r[16], s2 = r[32], s3 = r[48];
    const float sum = (s0.x + s1.x) + (s2.x + s3.x), sq = (s0.y + s1.y) + (s2.y + s3.y);
    dot = (s0.z + s1.z) + (s2.z + s3.z);
    dot += __shfl_xor_sync(0xffffffffu, dot, 16);
    return ln_stats(sum + __shfl_xor_sync(0xffffffffu, sum, 16), sq + __shfl_xor_sync(0xffffffffu, sq, 16), mean2);
}
template <class F>
__device__ __forceinline__ void rows_normalise(uint32_t* y, const uint32_t* x, uint32_t mean2, float rsd, int lane, F loads) {
    const int g8 = lane >> 2;
    const uint32_t ma2 = __shfl_sync(0xffffffffu, mean2, g8), mb2 = __shfl_sync(0xffffffffu, mean2, g8 + 8);
    const float ra = __shfl_sync(0xffffffffu, rsd, g8), rb = __shfl_sync(0xffffffffu, rsd, g8 + 8);
    loads();
#pragma unroll
    for (int k = 0; k < 9; k++) { y[2 * k] = ln_pair(x[2 * k], ma2, ra); y[2 * k + 1] = ln_pair(x[2 * k + 1], mb2, rb); }
}

__device__ __forceinline__ uint4 h_frag(const uint4* hf, int ks, int lane) {
    if (ks < 32) return ld_relaxed2(hf + ks * 32);
    const uint2* p = reinterpret_cast<const uint2*>(padd(hf, 256 - lane * 8) + ks * 32 - 16);
    const uint2 a = ld_relaxed64(p), b = ld_relaxed64(p + 32);
    return make_uint4(a.x, a.y, b.x, b.y);
}

__device__ __noinline__ void attn_fallback(uint32_t bad, uint32_t tag, const Scratch* gs, uint8_t* frag, uint8_t* keep, const bf16* wq, const bf16* kc, const bf16* vc) {
  const int lane = threadIdx.x & 31, g8 = lane >> 2, qd = lane & 3;
  const int role = cluster_role(), j = role & 7, qb = (role >> 2 & 14) + (role >> 6);
  const uint4* hf = g_h + (size_t)(qb * 8 + (threadIdx.x >> 5) - 4) * (36 * 32) + lane;
#pragma unroll 1
  for (int t = 0; t < 4; t++) {
    if (!((bad >> t) & 1)) continue;
    const bf16 *wqp = wq + (4 * j + t) * DH, *kp = kc + (size_t)(2 * j + (t >> 1)) * S_ * DH, *vp = vc + (size_t)(2 * j + (t >> 1)) * S_ * DH;
    uint32_t q[32];
    float o[64];
#pragma unroll
    for (int i = 0; i < 64; i++) o[i] = 0.f;
#pragma unroll 1
    for (int ks = 0; ks < 36; ks++) {
        const uint4 a = h_frag(hf, ks, lane);
        const unsigned short* wr = reinterpret_cast<const unsigned short*>(wqp + (size_t)(ks * 16 + 2 * qd) * QD + g8);
#pragma unroll
        for (int dt = 0; dt < 16; dt++) {
            const uint32_t b0 = __ldg(wr + dt * 8) | ((uint32_t)__ldg(wr + dt * 8 + QD) << 16);
            const uint32_t b1 = __ldg(wr + dt * 8 + 8 * QD) | ((uint32_t)__ldg(wr + dt * 8 + 9 * QD) << 16);
            mma16816(o + 4 * dt, a.x, a.y, a.z, a.w, b0, b1);
        }
    }
#pragma unroll
    for (int i = 0; i < 32; i++) q[i] = pack_bf16(o[2 * i], o[2 * i + 1]);
#pragma unroll
    for (int i = 0; i < 64; i++) o[i] = 0.f;
    float m0 = -INFINITY, m1 = -INFINITY, l0 = 0.f, l1 = 0.f;
#pragma unroll 1
    for (int key = 0; key < S_; key += 16) {
        float sc[8];
#pragma unroll
        for (int i = 0; i < 8; i++) sc[i] = 0.f;
#pragma unroll
        for (int nt = 0; nt < 2; nt++) {
            const uint32_t* kr = reinterpret_cast<const uint32_t*>(kp + (size_t)(key + nt * 8 + g8) * DH) + qd;
#pragma unroll
            for (int ks = 0; ks < 8; ks++)
                mma16816(sc + 4 * nt, q[4 * ks], q[4 * ks + 1], q[4 * ks + 2], q[4 * ks + 3], __ldg(kr + ks * 8), __ldg(kr + ks * 8 + 4));
        }
        const float n0 = quad_max(fmaxf(fmaxf(m0, fmaxf(sc[0], sc[1])), fmaxf(sc[4], sc[5])));
        const float n1 = quad_max(fmaxf(fmaxf(m1, fmaxf(sc[2], sc[3])), fmaxf(sc[6], sc[7])));
        const float f0 = ex2((m0 - n0) * CS), f1 = ex2((m1 - n1) * CS);
        m0 = n0; m1 = n1;
#pragma unroll
        for (int i = 0; i < 8; i++) sc[i] = ex2((sc[i] - ((i & 2) ? n1 : n0)) * CS);
        l0 = l0 * f0 + (sc[0] + sc[1]) + (sc[4] + sc[5]);
        l1 = l1 * f1 + (sc[2] + sc[3]) + (sc[6] + sc[7]);
        const uint32_t e0 = pack_bf16(sc[0], sc[1]), e1 = pack_bf16(sc[2], sc[3]), e2 = pack_bf16(sc[4], sc[5]), e3 = pack_bf16(sc[6], sc[7]);
        const unsigned short* vr = reinterpret_cast<const unsigned short*>(vp + (size_t)(key + 2 * qd) * DH + g8);
#pragma unroll
        for (int dt = 0; dt < 16; dt++) {
            o[4 * dt] *= f0; o[4 * dt + 1] *= f0; o[4 * dt + 2] *= f1; o[4 * dt + 3] *= f1;
            const uint32_t b0 = __ldg(vr + dt * 8) | ((uint32_t)__ldg(vr + dt * 8 + DH) << 16);
            const uint32_t b1 = __ldg(vr + dt * 8 + 8 * DH) | ((uint32_t)__ldg(vr + dt * 8 + 9 * DH) << 16);
            mma16816(o + 4 * dt, e0, e1, e2, e3, b0, b1);
        }
    }
    const float i0 = 1.f / quad_sum(l0), i1 = 1.f / quad_sum(l1);
#pragma unroll
    for (int i = 0; i < 16; i++) {
        q[2 * i] = pack_bf16(o[4 * i] * i0, o[4 * i + 1] * i0);
        q[2 * i + 1] = pack_bf16(o[4 * i + 2] * i1, o[4 * i + 3] * i1);
    }
    frag_store(t < 3 ? frag + t * 4096 : keep, q);
  }
}

__device__ __forceinline__ void spare_q3(Scratch* gs, uint32_t sb, uint32_t bar_full, uint32_t bar_empty, int lane, int cw) {
    const uint32_t tag = load_tag(gs);
    uint32_t rel_base, e = 3;
    asm("mapa.shared::cluster.u32 %0, %1, %2;" : "=r"(rel_base) : "r"(bar_empty), "r"(lane & 1));
#pragma unroll 1
    for (int qb = blockIdx.x - NCTA; qb < 16; qb += 4) {
        uint32_t h[144];
        float o[64];
        flag_wait(&g_flag_h[(qb * 8 + cw) * 32], tag);
        const uint4* hf = g_h + (size_t)(qb * 8 + cw) * (36 * 32) + lane;
#pragma unroll
        for (int ks = 0; ks < 36; ks++) {
            const uint4 v = h_frag(hf, ks, lane);
            h[4 * ks] = v.x; h[4 * ks + 1] = v.y; h[4 * ks + 2] = v.z; h[4 * ks + 3] = v.w;
        }
#pragma unroll
        for (int i = 0; i < 64; i++) o[i] = 0.f;
#pragma unroll 1
        for (int v = 0; v < 4; v++) {
            fence_regs(o);
#pragma unroll
            for (int t = 0; t < 5; t++) {
                mbar_wait(bar_full + 8 * (e & 3), (e >> 2) & 1);
                uint64_t dv = mkdesc(sb + (e & 3) * SLOT, UNIT, 1024);
                WG_FENCE();
#pragma unroll
                for (int ks = 0; ks < (t < 4 ? 8 : 4); ks++)
                    mma_rs128<1>(o, h[32 * t + 4 * ks], h[32 * t + 4 * ks + 1], h[32 * t + 4 * ks + 2], h[32 * t + 4 * ks + 3], dv, ks | t);
                WG_COMMIT();
                if (t > 0) { WG_WAIT(1); if (lane < 2) mbar_arrive_cluster(rel_base + 8 * ((e - 1) & 3)); }
                e++;
            }
            WG_WAIT(0);
            fence_regs(o);
            if (lane < 2) mbar_arrive_cluster(rel_base + 8 * ((e - 1) & 3));
            uint4* dst = &g_q3[((qb * 8 + 2 * v) * 8 + cw) * 128 + lane];
#pragma unroll
            for (int i = 0; i < 8; i++)
                __stcg(dst + (i >> 2) * 1024 + (i & 3) * 32, make_uint4(pack_bf16(o[8 * i], o[8 * i + 1]), pack_bf16(o[8 * i + 2], o[8 * i + 3]),
                                                                        pack_bf16(o[8 * i + 4], o[8 * i + 5]), pack_bf16(o[8 * i + 6], o[8 * i + 7])));
        }
        bar_sync(3, 256);
        if (cw == 0 && lane == 0) flag_release(&g_flag_q3[qb * 32], tag);
        __syncwarp();
    }
}

template <bool SPARE>
__global__ void __cluster_dims__(2, 1, 1) __launch_bounds__(384, 1)
fused_kernel(const Args args, const __grid_constant__ CUtensorMap tm_wq,
             const __grid_constant__ CUtensorMap tm_k, const __grid_constant__ CUtensorMap tm_v,
             const __grid_constant__ CUtensorMap tm_wo, const __grid_constant__ CUtensorMap tm_p,
             const __grid_constant__ CUtensorMap tm_x, const __grid_constant__ CUtensorMap tm_d,
             const __grid_constant__ CUtensorMap tm_g, const __grid_constant__ CUtensorMap tm_u) {
    extern __shared__ __align__(1024) uint8_t smem_raw[];
    const uint32_t sb = smem_u32(smem_raw);
    Scratch* const gs = args.gs;
    const uint32_t bar_full = sb + SM_BAR;
    const uint32_t bar_g = bar_full + 8 * 4;
    const uint32_t bar_mod = bar_g + 8;
    const uint32_t bar_go = bar_mod + 8;
    const uint32_t bar_x = bar_go + 40;
    const uint32_t bar_empty = bar_x + 8;
    const uint32_t bar_pub = bar_empty + 8 * 4;
    const uint32_t bar_qfree = bar_pub + 32;
    const uint32_t bar_out = bar_qfree + 24;
    const uint32_t bar_q3 = bar_out + 8;
    const uint32_t bar_pre = bar_q3 + 16;
    const uint32_t bar_w0 = bar_q3 + 8;
    constexpr int E0 = SPARE ? 2 : 0;

#define ROLES() const int role = cluster_role(), c = role >> 6, j = role & 7, qb = (role >> 2 & 14) + c, rg = qb * 8 + j; uint32_t bx; asm volatile("mov.u32 %0, %%ctaid.x;" : "=r"(bx))
    const int warp = __shfl_sync(0xffffffffu, threadIdx.x >> 5, 0);

    if (SPARE && blockIdx.x >= NCTA && warp >= 4) {
        asm volatile("barrier.cluster.arrive.relaxed.aligned;" ::: "memory");
        asm volatile("setmaxnreg.inc.sync.aligned.u32 240;");
        asm volatile("barrier.cluster.wait.aligned;" ::: "memory");
        spare_q3(gs, sb, bar_full, bar_empty, threadIdx.x & 31, warp - 4);
        asm volatile("barrier.cluster.arrive.relaxed.aligned;\nbarrier.cluster.wait.aligned;" ::: "memory");
    } else if (warp < 4) {
        asm volatile("setmaxnreg.dec.sync.aligned.u32 24;");
        ROLES();
        int lane;
        asm volatile("mov.u32 %0, %%laneid;" : "=r"(lane));
        if (warp == 2 && elect()) {
            asm volatile("prefetch.tensormap [%0];" ::"l"(&tm_x) : "memory");
#pragma unroll
            for (int i = 0; i < 27; i++) mbar_init(bar_full + 8 * i, i < 12 || i >= 23 ? 1 : i < 16 ? 16 : 8);
#pragma unroll
            for (int i = 0; i <= E0; i++) {
                mbar_arrive(bar_full + 8 * i);
                asm volatile("mbarrier.arrive.shared::cta.b64 _, [%0], 16;" ::"r"(bar_empty + 8 * i) : "memory");
            }
            asm volatile("fence.mbarrier_init.release.cluster;" ::: "memory");
        }
        __syncwarp();
        asm volatile("barrier.cluster.arrive.relaxed.aligned;" ::: "memory");
        if (warp == 2 && !(SPARE && bx >= NCTA)) {
            __nanosleep(200);
            if (elect()) {
                mbar_expect_tx(bar_x, 16 * XP);
                tma2d(sb + SM_Q, &tm_x, 0, rg * 16, bar_x);
            }
            __syncwarp();
        }
        asm volatile("barrier.cluster.wait.aligned;" ::: "memory");
        const uint32_t tag = load_tag(gs);
        if (SPARE && bx >= NCTA) {
            if (warp == 1) {
#pragma unroll 1
                for (int e = 3; e < 83; e++) {
                    const int v = (e - 3) / 5;
                    mbar_wait_sleep(bar_empty + 8 * (e & 3), ~(e >> 2) & 1);
                    if (elect()) {
                        mbar_expect_tx(bar_full + 8 * (e & 3), SLOT);
                        tma2d_mc(sb + (e & 3) * SLOT + c * UNIT, &tm_wq, (8 * (v & 3) + 4 * c + 3) * DH + 64, (e - 3 - v * 5) * 128,
                                 bar_full + 8 * (e & 3), EVICT_NORMAL);
                    }
                }
            }
            __syncwarp();
            asm volatile("barrier.cluster.arrive.relaxed.aligned;\nbarrier.cluster.wait.aligned;" ::: "memory");
            return;
        }
        if (warp == 3) {
#pragma unroll 1
            for (int e = 4; e < 20; e++) {
                __nanosleep(e == 4 ? 2000 : 400);
                const int hd = (e * 52) >> 8, row = (e - hd * 5) * 128 + qb * 8 + (lane >> 1);
                if (lane < 16 && row < D_)
                    asm volatile("prefetch.global.L2 [%0];" ::"l"(padd(args.wq, (row * QD + (4 * j + ((0x1320 >> (4 * hd)) & 3)) * DH + (lane & 1) * 64) * 2)) : "memory");
            }
            __syncwarp();
            mbar_wait_sleep(bar_go, 0);
            __nanosleep(2000);
#pragma unroll 1
            for (int unit = 72 + bx; unit < 216; unit += NCTA) {
                float a[8];
#pragma unroll
                for (int i = 0; i < 8; i++) a[i] = 0.f;
#pragma unroll 1
                for (int k = lane >> 1; k < D_; k += 16) {
                    const float cv = __bfloat162float(*padd(args.cvec, k * 2));
                    mod_fma(a, __ldg(reinterpret_cast<const uint4*>(padd(args.w_mod, (k * (6 * D_) + unit * 16 + (lane & 1) * 8) * 2))), rbf(cv * sigmoidf_(cv)));
                }
                const float v = mod_reduce(a, lane), v1 = __shfl_down_sync(0xffffffffu, v, 8);
                if (lane < 8) *padd(gs->mod2, ((unit - 72) * 8 + (lane & 1) * 4 + (lane & 2) + (lane >> 2)) * 4) = pack_bf16(v, v1);
            }
            __syncwarp();
            if (lane == 0) flag_release(padd(g_flag_mod, bx * 4), tag);
#pragma unroll 1
            for (int k = 0; k < 36; k++) {
                __nanosleep(200);
                __stcg(padd(gs->h[0], (~tag & 1) * (NCTA * 36 * 512) + ((rg * 36 + k) * 32 + lane) * 16), make_uint4(0, 0, 0, 0));
            }
            __syncwarp();
            mbar_wait_sleep(bar_qfree + 16, 0);
            __nanosleep(2000);
            {
                uint4 v;
                uint32_t it = 0;
#pragma unroll 1
                do {
                    v = ld_relaxed(reinterpret_cast<const uint4*>(padd(g_flag_mod, lane * 16)));
                } while (((v.x ^ tag) | (v.y ^ tag) | (v.z ^ tag) | (v.w ^ tag)) && ++it < SPIN / 16);
                asm volatile("fence.acquire.gpu;" ::: "memory");
            }
            __syncwarp();
            {
                float w1 = 0.f, w2 = 0.f;
#pragma unroll 1
                for (int k = lane; k < D_ / 2; k += 32) {
                    const uint32_t* mp = padd(gs->mod2, k * 4);
                    const uint32_t sv = __ldcg(mp + D_ / 2), c1 = badd2(__ldcg(mp + D_), 0x3f803f80u);
                    const uint32_t wr = *reinterpret_cast<const uint32_t*>(padd(args.w_r, k * 4)), wp = bmul2(c1, wr);
                    reinterpret_cast<uint2*>(smem_raw + SM_T)[k] = make_uint2(__ldcg(mp), wp);
                    reinterpret_cast<uint2*>(smem_raw + SM_TC)[k] = make_uint2(c1, sv);
                    reinterpret_cast<uint32_t*>(smem_raw + SM_TG)[k] = __ldcg(mp + 3 * D_ / 2);
                    w1 += bf_lo(wp) + bf_hi(wp);
                    w2 += bf_lo(sv) * bf_lo(wr) + bf_hi(sv) * bf_hi(wr);
                }
#pragma unroll 1
                for (int i = 1; i < 32; i <<= 1) { w1 += __shfl_xor_sync(0xffffffffu, w1, i); w2 += __shfl_xor_sync(0xffffffffu, w2, i); }
                *reinterpret_cast<float2*>(smem_raw + SM_TS) = make_float2(w1, w2);
            }
#pragma unroll
            for (int i = 0; i < 4; i++) reinterpret_cast<uint4*>(smem_raw + SM_RED)[lane + 32 * i] = make_uint4(~0u, ~0u, ~0u, ~0u);
            asm volatile("fence.proxy.async.shared::cta;" ::: "memory");
            __syncwarp();
            if (elect()) {
                uint8_t* mb = g_frag + (size_t)rg * 8 * WREG + 3 * 4096;
#pragma unroll 1
                for (int k = 0; k < 8; k++, mb += WREG) {
#pragma unroll
                    for (int i = 0; i < 3; i++)
                        asm volatile("cp.async.bulk.global.shared::cta.bulk_group [%0], [%1], 2048;" ::"l"(mb + i * 2048), "r"(sb + SM_RED) : "memory");
                    __nanosleep(500);
                }
                asm volatile("cp.async.bulk.commit_group;\ncp.async.bulk.wait_group 0;\nfence.proxy.async.global;" ::: "memory");
            }
            __syncwarp();
            if (lane == 0) mbar_arrive(bar_mod);
            __syncwarp();
            mbar_wait_sleep(bar_go + 8, 0);
            if (elect()) asm volatile("prefetch.tensormap [%0];\nprefetch.tensormap [%1];\nprefetch.tensormap [%2];" ::"l"(&tm_x), "l"(&tm_p), "l"(&tm_d) : "memory");
            __syncwarp();
            *padd(g_flag_part, qb * 1024 + (lane >> 3) * 256 + j * 32 + (lane & 7) * 4) = 0;
            __syncwarp();
#pragma unroll 1
            for (int i = 1; i < 4; i++) {
                mbar_wait(bar_pub + 8 * i, 0);
                unsigned int* flags = padd(g_flag_part, qb * 1024 + (i - 1) * 256);
                if (elect()) { flag_release(padd(flags, j * 32), tag); DBG_PG(93); }
                __syncwarp();
                const uint32_t slot = (i + 2) & 3;
                flag_wait(padd(flags, (lane & 7) * 32), tag);
                asm volatile("fence.proxy.async.global;" ::: "memory");
                if (lane == 0 && i == 3) DBG_PG(101);
                mbar_wait(bar_go + 8 + 8 * i, 0);
                mbar_wait(bar_empty + 8 * slot, i == 3);
                if (elect()) {
                    mbar_expect_tx(bar_full + 8 * slot, SLOT);
                    tma3d(sb + slot * SLOT, &tm_p, 0, j * 20 + (i - 1) * 4, qb * 8, bar_full + 8 * slot);
                    tma3d(sb + slot * SLOT + UNIT, &tm_p, 0, j * 20 + (i - 1) * 4 + 2, qb * 8, bar_full + 8 * slot);
                }
            }
        } else if (warp == 0) {
#pragma unroll 1
            for (int i = 0; i < 48; i++) {
                if (SPARE && i == 34) {
                    flag_wait(&g_flag_q3[qb * 32], tag);
                    if (elect()) {
                        asm volatile("fence.proxy.async.global;" ::: "memory");
                        mbar_expect_tx(bar_q3, UNIT);
#pragma unroll 1
                        for (int k = 0; k < 8; k++) bulk_load(sb + SM_Q + 2 * SLOT + k * 4096 + 2048, &g_q3[(rg * 8 + k) * 128], 2048, bar_q3);
                    }
                }
                if (i == 0 || i == 17 || i == 34) { mbar_wait_sleep(bar_qfree + (i >> 4) * 8, 0); __nanosleep(2000); }
                __nanosleep(500);
                if (elect()) {
                    asm volatile("mbarrier.expect_tx.shared::cta.b64 [%0], %1;" ::"r"(bar_g), "n"(1920) : "memory");
                    tma2d(sb + SM_Q + i * 1920, i < 24 ? &tm_g : &tm_u, (bx * 36) & ~7, (i < 24 ? i : i - 24) * 24, bar_g);
                }
            }
            if (elect()) mbar_arrive(bar_g);
#pragma unroll 1
            for (int i = 0; i < 18; i++) {
                __nanosleep(400);
                if (elect()) l2_prefetch(args.w_down + (size_t)(bx * 36 + i * 2) * D_, 4 * D_);
            }
            __syncwarp();
            mbar_wait_sleep(bar_go + 8 * 2, 0);
            uint32_t acc = 0;
#pragma unroll 1
            for (int k = lane; k < 16 * 9; k += 32) acc |= touch(padd(args.x, (rg * 16 * D_ + k * 64) * 2));
            if (acc == 0) reinterpret_cast<volatile uint32_t*>(smem_raw + SM_BAR)[127] = acc;
            __syncwarp();
            mbar_wait_sleep(bar_go + 8 * 4, 0);
            *reinterpret_cast<uint2*>(padd(g_cand, ((lane >> 2) * NCTA + rg) * 32 + (lane & 3) * 8)) = make_uint2(0, 0);
            uint4* rp = padd(g_rows, (rg * 2 * RSLOT + lane) * 16);
#pragma unroll
            for (int k = 0; k < 12; k++) rp[k * 32] = make_uint4(~0u, ~0u, ~0u, ~0u);
            if (bx < 72) {
                uint4* yp = reinterpret_cast<uint4*>(padd(g_ypart, bx * NCTA * 64 + lane * 16));
#pragma unroll
                for (int k = 0; k < 16; k++) yp[k * 32] = make_uint4(~0u, ~0u, ~0u, ~0u);
            }
            asm volatile("fence.acq_rel.gpu;" ::: "memory");
            __syncwarp();
            if (lane == 0) mbar_arrive(bar_pre);
        } else if (warp == 1) {
            __nanosleep(100);
            auto put = [&](uint32_t fb, uint32_t slot, const CUtensorMap* tm, int c0, int c1, uint64_t pol) {
                if (elect()) {
                    mbar_expect_tx(fb, SLOT);
                    tma2d_mc(sb + slot * SLOT + c * UNIT, tm, c0, c1, fb, pol);
                }
            };
            auto prefetch_kv = [&](int n) {
                if (elect()) {
                    const size_t off = (size_t)((2 * j + (n >> 5)) * S_ + (n & 15) * 128) * DH + qb * 1024;
                    l2_prefetch(args.kc + off, 2048);
                    l2_prefetch(args.vc + off, 2048);
                }
            };
            put(bar_w0, 6, &tm_wq, 4 * j * DH + c * 64, -64, EVICT_FIRST);
#pragma unroll 1
            for (int e = E0 + 1; e < 19; e++) {
                const int i = SPARE && e < 12 ? e - 2 : e, hd = (i * 52) >> 8;
                const bool half = SPARE && hd == 2;
                const int c0 = (4 * j + ((0x1320 >> (4 * hd)) & 3)) * DH + (half ? 0 : c * 64);
                const int c1 = half ? (2 * (e - 12) + c) * 128 : (i - hd * 5) * 128 - 64;
                if (e < E0 + 5) __nanosleep(300);
                mbar_wait(bar_empty + 8 * (e & 3), ~(e >> 2) & 1);
                put(bar_full + 8 * (e & 3), e & 3, &tm_wq, c0, c1, EVICT_FIRST);
                if (e >= PF_KV && !(e & 1)) prefetch_kv((e - PF_KV) >> 1);
            }
            mbar_wait(bar_empty + 24, 1);
            put(bar_full + 24, 3, &tm_k, c * 64, 2 * j * S_, EVICT_NORMAL);
            mbar_wait(bar_empty, 0);
            put(bar_full, 0, &tm_wq, (4 * j + 1) * DH + c * 64, 448, EVICT_FIRST);
            prefetch_kv((20 - PF_KV) >> 1);
            if (elect()) mbar_arrive(bar_go);
#pragma unroll 1
            for (int n = 1; n < 64; n++) {
                const uint32_t sv = (n & 1) * 2, sk = sv ^ 3;
                const int m = n - 1;
                mbar_wait_sleep(bar_empty + 8 * sk, ~((n + 9) >> 1) & 1);
                put(bar_full + 8 * sk, sk, &tm_k, c * 64, (2 * j + (n >> 5)) * S_ + (n & 15) * 128, (n & 16) ? EVICT_FIRST : EVICT_NORMAL);
                mbar_wait_sleep(bar_empty + 8 * sv, (n >> 1) & 1);
                put(bar_full + 8 * sv, sv, &tm_v, c * 64, (2 * j + (m >> 5)) * S_ + (m & 15) * 128, (m & 16) ? EVICT_FIRST : EVICT_NORMAL);
                const int pn = n + ((20 - PF_KV) >> 1);
                if (!(pn & 80)) prefetch_kv(pn);
                if (n >= PF_WO) {
                    if (elect()) {
                        if (n < PF_WO + 9) l2_prefetch(args.wo + (size_t)bx * (QD * D_ / NCTA) + (n - PF_WO) * 2048, 4096);
                        if (n >= PF_O) {
                            l2_prefetch(g_frag + (size_t)(rg * 8 + 2 * (n - PF_O)) * WREG, 4096);
                            l2_prefetch(g_frag + (size_t)(rg * 8 + 2 * (n - PF_O) + 1) * WREG, 4096);
                        }
                    }
                }
            }
            mbar_wait_sleep(bar_empty + 24, 1);
            put(bar_full + 24, 3, &tm_v, c * 64, (2 * j + 1) * S_ + 15 * 128, EVICT_FIRST);
#pragma unroll 1
            for (int i = 0; i < 18; i++) {
                const int e = 148 + i + (i > 10) + (i > 14);
                mbar_wait_sleep(bar_empty + 8 * (e & 3), ~(e >> 2) & 1);
                put(bar_full + 8 * (e & 3), e & 3, &tm_wo, (i >> 1) * 64, (4 * j + ((i & 1) ? 1 + c : 3 * c)) * DH, EVICT_FIRST);
                arrive_if(bar_go + 2 + 2 * i, elect() && (i & 3) == 3);
            }
            asm volatile("fence.proxy.async.global;" ::: "memory");
            mbar_wait(bar_empty, 1);
            if (elect()) {
                mbar_expect_tx(bar_full, 16 * XP);
                tma2d(sb, &tm_x, 0, rg * 16, bar_full);
            }
            mbar_wait(bar_empty + 16, 1);
            if (elect()) {
                mbar_expect_tx(bar_full + 16, SLOT);
                tma3d(sb + 2 * SLOT, &tm_p, 0, j * 20 + 12, qb * 8, bar_full + 16);
                tma3d(sb + 2 * SLOT + UNIT, &tm_p, 0, j * 20 + 14, qb * 8, bar_full + 16);
            }
            mbar_wait(bar_empty + 24, 1);
            __nanosleep(300);
            if (elect()) {
                mbar_expect_tx(bar_full + 24, UNIT);
                tma3d(sb + 3 * SLOT, &tm_p, 0, j * 20 + 16, qb * 8, bar_full + 24);
            }
            mbar_wait(bar_empty + 8, 0);
            mbar_wait(bar_empty + 16, 0);
            __nanosleep(300);
            if (elect()) {
#pragma unroll
                for (int i = 1; i < 3; i++) {
                    mbar_expect_tx(bar_full + 8 * i, 18 * XP);
                    tma2d(sb + i * SLOT, &tm_d, 0, bx * 36 + (i - 1) * 18, bar_full + 8 * i);
                }
            }
        } else {
            if (elect()) asm volatile("prefetch.tensormap [%0];\nprefetch.tensormap [%1];\nprefetch.tensormap [%2];" ::"l"(&tm_k), "l"(&tm_v), "l"(&tm_wo) : "memory");
            if (SPARE) {
                mbar_wait_sleep(bar_pub, 0);
                if (lane == 0) flag_release(padd(g_flag_h, rg * 128), tag);
                __syncwarp();
            }
            bar_sync(1, 192);
#pragma unroll 1
            for (uint32_t e = E0 + 5; e < 20; e++) {
                mbar_wait(bar_full + 8 * (e & 3), (e >> 2) & 1);
                if (!(((SPARE ? 0xa080 : 0x8420) >> e) & 1)) bar_sync(1, 192);
            }
#pragma unroll 1
            for (uint32_t e = 20; e < 148; e += 2) {
                mbar_wait_sleep(bar_full + 8 * (e & 3), (e >> 2) & 1);
                bar_sync(4, 160);
                if (SPARE && e == 112) mbar_wait(bar_q3, 0);
                mbar_wait_sleep(bar_full + 8 + 8 * (e & 3), (e >> 2) & 1);
                bar_sync(1, 192);
            }
            bar_sync(4, 160);
#pragma unroll 1
            for (uint32_t e = 148; e < 168; e++) {
                mbar_wait(bar_full + 8 * (e & 3), (e >> 2) & 1);
                if (e != 159 && e != 164) bar_sync(1, 192);
            }
        }
        __syncwarp();
        uint32_t rows = 0x1111u << warp;
        auto store_rows = [&](uint32_t m) {
#pragma unroll 1
            for (; m; m &= m - 1) {
                const int i = __ffs(m) - 1;
                asm volatile("cp.async.bulk.global.shared::cta.bulk_group.L2::cache_hint [%0], [%1], %2, %3;"
                             ::"l"(padd(args.out, (rg * 16 + i) * (D_ * 2))), "r"(sb + i * XP), "n"(D_ * 2), "l"(EVICT_FIRST) : "memory");
            }
        };
        mbar_wait_sleep(bar_out, 0);
        if (bx == 127 && warp == 0 && lane == 0) gs->epoch[0] = tag;
        if (elect()) {
            asm volatile("fence.proxy.async.shared::cta;" ::: "memory");
            const uint2 sel = lds64(sb + SM_RED + 64);
            if ((sel.x >> 4) == rg) rows &= ~(1u << (sel.x & 15));
            if ((sel.y >> 4) == rg) rows &= ~(1u << (sel.y & 15));
            store_rows(rows);
            asm volatile("cp.async.bulk.commit_group;\ncp.async.bulk.wait_group.read 0;" ::: "memory");
        }
    } else {
        uint32_t cv[2] = {0, 0}, tag0 = 0;
        {
            uint32_t ws, t, b;
            asm volatile("mov.u32 %0, smem_raw;\nmov.u32 %1, %%tid.x;\nmov.u32 %2, %%ctaid.x;" : "=r"(ws), "=r"(t), "=r"(b));
            t -= 128;
            const uint32_t* cp = padd(reinterpret_cast<const uint32_t*>(args.cvec), (t & 0xe0) + (t & 7) * 4);
            asm volatile("{\n.reg .pred p, q, r;\nsetp.lt.u32 r, %8, 256;\nsetp.lt.and.u32 p, %9, 72, r;\nsetp.lt.and.u32 q, %8, 128, p;\n"
                         "@p ld.global.nc.u32 %0, [%5];\n@q ld.global.nc.u32 %1, [%6 + 1024];\n@r ld.global.ca.u32 %2, [%7];\n"
                         "@p cp.async.cg.shared.global [%3], [%4], 16;\n@p cp.async.cg.shared.global [%3 + 4096], [%4 + 884736], 16;\n"
                         "@p cp.async.cg.shared.global [%3 + 8192], [%4 + 1769472], 16;\n@p cp.async.cg.shared.global [%3 + 12288], [%4 + 2654208], 16;\n"
                         "@q cp.async.cg.shared.global [%3 + 16384], [%4 + 3538944], 16;\n}"
                         : "+r"(cv[0]), "+r"(cv[1]), "+r"(tag0)
                         : "r"(ws + SM_Q + SLOT + t * 16), "l"(padd(args.w_mod, (t >> 1 & 127) * (12 * D_) + (t & 1) * 16 + b * 32)),
                           "l"(padd(cp, (t & 24) * 32)), "l"(cp), "l"(padd(gs->epoch, b >> 8)), "r"(t), "r"(b) : "memory");
        }
        uint32_t tag = __shfl_sync(0xffffffffu, tag0, 0);
        asm volatile("barrier.cluster.arrive.relaxed.aligned;" ::: "memory");
        asm volatile("setmaxnreg.inc.sync.aligned.u32 240;");
        const int lane = threadIdx.x & 31;
        const int cw = warp - 4;
        const int w = cw >> 2;
        const int tid = threadIdx.x - 128;
        ROLES();
        float* red = reinterpret_cast<float*>(smem_raw + SM_RED);
        DBG_INIT();
        DBG_G(120);
        DBG_T(100);

        {
            if (bx < 72) {
                uint2* mdst = &gs->mod1[(tid >> 3) * D_ + bx * 8 + (tid & 7)];
                if (tid < 8 * MREP) st_relaxed64(mdst, 0, 0);
                uint32_t sa[10];
#pragma unroll
                for (int i = 0; i < 2; i++) {
                    const float lo = bf_lo(cv[i]), hi = bf_hi(cv[i]);
                    cv[i] = pack_bf16(lo * sigmoidf_(lo), hi * sigmoidf_(hi));
                }
#pragma unroll
                for (int i = 0; i < 10; i++) sa[i] = __shfl_sync(0xffffffffu, cv[i >> 3], (i & 7) * 4 + (lane & 3));
                anchor(bar_full + 504, sa[0] & sa[1] & sa[2] & sa[3] & sa[4] & sa[5] & sa[6] & sa[7] & sa[8] & sa[9] & (uint32_t)(uintptr_t)mdst & (uint32_t)((uintptr_t)mdst >> 32));
                asm volatile("cp.async.wait_all;" ::: "memory");
                __syncwarp();
                const uint32_t ws = sb + SM_Q + SLOT + cw * 512 + (lane & 15) * 32 + (lane & 16);
                float d[16];
#pragma unroll
                for (int i = 0; i < 16; i++) d[i] = 0.f;
#pragma unroll
                for (int i = 0; i < 5; i++) {
                    const uint4 b = ldsm4t(ws + (i < 4 || cw < 4 ? i * 4096 : 0));
                    mma16816(d + 8 * (i & 1), sa[2 * i], sa[2 * i], sa[2 * i + 1], sa[2 * i + 1], b.x, b.y);
                    mma16816(d + 8 * (i & 1) + 4, sa[2 * i], sa[2 * i], sa[2 * i + 1], sa[2 * i + 1], b.z, b.w);
                }
                if (lane < 8) reinterpret_cast<float2*>(red)[lane * 8 + cw] = (lane & 4) ? make_float2(d[4] + d[12], d[5] + d[13]) : make_float2(d[0] + d[8], d[1] + d[9]);
                bar_sync(3, 256);
                if (tid < 8 * MREP) {
                    const float4* r = reinterpret_cast<const float4*>(red) + (tid & 7) * 4;
                    const float4 r0 = r[0], r1 = r[1], r2 = r[2], r3 = r[3];
                    st_relaxed64(mdst, pack_bf16(((r0.x + r0.z) + (r1.x + r1.z)) + ((r2.x + r2.z) + (r3.x + r3.z)),
                                                 ((r0.y + r0.w) + (r1.y + r1.w)) + ((r2.y + r2.w) + (r3.y + r3.w))), tag + 1);
                }
            }
            if (cw < 4) st_relaxed4(gs->h[~tag & 1] + (size_t)(rg * 36 + cw) * 32 + lane, 0, 0, 0, 0);
            DBG_G(106);
            asm volatile("barrier.cluster.wait.aligned;" ::: "memory");
            mbar_wait(bar_x, 0);
            asm volatile("add.u32 %0, %0, 1;" : "+r"(tag));
            uint32_t x[20];
            float st[12], st2[12];
            rows_load(x, sb + SM_Q + (lane & 15) * XP + (lane >> 4) * 16 + cw * 32, cw);
#pragma unroll
            for (int i = 0; i < 12; i++) { st[i] = 0.f; st2[i] = 0.f; }
#pragma unroll
            for (int k = 0; k < 9; k++) stats_add((k & 1) ? st2 : st, x[2 * k], x[2 * k + 1], 0x3f803f80u);
#pragma unroll
            for (int i = 0; i < 12; i++) st[i] += st2[i];
            uint32_t mean2;
            float dot;
            const float rsd = rows_stats(st, reinterpret_cast<float4*>(red + 128), cw, lane, mean2, dot);
            const uint4* mp = reinterpret_cast<const uint4*>(gs->mod1 + ((bx >> 1) & (MREP - 1)) * D_) + min(tid, D_ / 4 - 1);
            uint4 v0 = make_uint4(0, tag, 0, tag), v1 = v0;
            auto look = [&]() {
                asm volatile("{\n.reg .pred p;\n.reg .b64 a, b, c, d;\nsetp.lt.s32 p, %9, 5;\nmov.b64 a, {%0, %1};\nmov.b64 b, {%2, %3};\n"
                             "mov.b64 c, {%4, %5};\nmov.b64 d, {%6, %7};\n@p ld.relaxed.gpu.global.v2.b64 {a, b}, [%8];\n"
                             "@p ld.relaxed.gpu.global.v2.b64 {c, d}, [%8 + 2304];\n"
                             "mov.b64 {%0, %1}, a;\nmov.b64 {%2, %3}, b;\nmov.b64 {%4, %5}, c;\nmov.b64 {%6, %7}, d;\n}"
                             : "+r"(v0.x), "+r"(v0.y), "+r"(v0.z), "+r"(v0.w), "+r"(v1.x), "+r"(v1.y), "+r"(v1.z), "+r"(v1.w)
                             : "l"(mp), "r"(cw) : "memory");
            };
            rows_normalise(x, x, mean2, rsd, lane, look);
            fence_regs(x);
            uint32_t it = 0;
#pragma unroll 1
            while (((v0.y ^ tag) | (v0.w ^ tag) | (v1.y ^ tag) | (v1.w ^ tag)) && ++it < SPIN / 16) look();
            uint4* smod = reinterpret_cast<uint4*>(smem_raw + SM_Q + M_MOD);
            if (tid < D_ / 4) smod[tid] = make_uint4(badd2(v1.x, 0x3f803f80u), v0.x, badd2(v1.z, 0x3f803f80u), v0.z);
            uint4* hdst = g_h + (size_t)(rg * 36 + cw) * 32 + lane;
            uint2* hdst2 = reinterpret_cast<uint2*>(g_h + (size_t)(rg * 36 + 32) * 32) + tid;
            bar_sync(3, 256);
            DBG_G(107);
#pragma unroll
            for (int k = 0; k < 9; k++) {
                const uint2 cs = lds64(sb + SM_Q + M_MOD + (cw * 8 + (lane & 3) + (k < 8 ? (k >> 1) * 64 + (k & 1) * 4 : 256 - cw * 4)) * 8);
                const uint32_t c1 = cs.x, sa = cs.y;
                x[2 * k] = badd2(bmul2(x[2 * k], c1), sa);
                if (x[2 * k] == 0) x[2 * k] = 0x8000u;
                x[2 * k + 1] = badd2(bmul2(x[2 * k + 1], c1), sa);
            }
#pragma unroll
            for (int ch = 0; ch < 4; ch++) st_relaxed4(hdst + ch * 256, x[4 * ch], x[4 * ch + 1], x[4 * ch + 2], x[4 * ch + 3]);
            st_relaxed64(hdst2, x[16], x[17]);
            __syncwarp();
            if (SPARE && lane == 0) mbar_arrive(bar_pub);
            DBG_G(108);
        }

        uint32_t rel_base;
        asm("mapa.shared::cluster.u32 %0, %1, %2;" : "=r"(rel_base) : "r"(bar_empty), "r"(lane & 1));
        auto release = [&](uint32_t slot) { if (lane < 2) mbar_arrive_cluster(rel_base + 8 * slot); };
        uint32_t q[32], p[32];
        float s[64], o[64];

        const int lw = cw & 3;
        const uint32_t relw = lw == 2 && lane < 8, handw = lw == 2 || cw == 1;
        auto release4 = [&](uint32_t off, uint32_t on = 1) {
            asm volatile("{\n.reg .pred p;\nsetp.ne.b32 p, %1, 0;\n@p mbarrier.arrive.shared::cluster.b64 _, [%0];\n}" ::"r"(rel_base + off), "r"(relw & on) : "memory"); };
        auto handoff = [&](uint32_t on = 1) {
            asm volatile("{\n.reg .pred p;\nsetp.ne.b32 p, %1, 0;\n@p bar.arrive %0, 192;\n}" ::"r"(2 - w), "r"(handw & on) : "memory"); };
        if (cw == 6) bar_arrive(1, 192);

        uint4* qpark = reinterpret_cast<uint4*>(smem_raw + SM_Q - SLOT) + cw * 256 + lane;
        {
            uint32_t h[144];
            const uint4* hf = g_h + (size_t)(qb * 8 + cw) * (36 * 32) + lane;
            auto load_h = [&](auto lo, auto hi) {
#pragma unroll
                for (int ks = lo.value; ks < hi.value; ks++) {
                    const uint4 v = h_frag(hf, ks, lane);
                    h[4 * ks] = v.x; h[4 * ks + 1] = v.y; h[4 * ks + 2] = v.z; h[4 * ks + 3] = v.w;
                }
            };
            auto check_h = [&](auto lo, auto hi) {
                uint32_t it = 0;
                bool miss;
#pragma unroll 1
                do {
                    uint32_t mn = ~0u;
#pragma unroll
                    for (int ks = lo.value; ks < hi.value; ks++) mn = __vimin3_u32(mn, h[4 * ks], h[4 * ks + 2]);
                    miss = __any_sync(0xffffffffu, mn == 0);
                    if (miss) load_h(lo, hi);
                    asm volatile("add.u32 %0, %0, 1;" : "+r"(it));
                } while (miss && it < SPIN / 16);
            };
            auto check_h2 = [&](auto lo, auto hi, auto nx) {
                float f0 = __uint_as_float(~0u), f1 = f0;
                hold(f0, f1);
                auto low = [&]() {
                    uint32_t m0 = __float_as_uint(f0), m1 = m0;
#pragma unroll
                    for (int ks = lo.value; ks < hi.value; ks += 2) { m0 = __vimin3_u32(m0, h[4 * ks], h[4 * ks + 2]); m1 = __vimin3_u32(m1, h[4 * ks + 4], h[4 * ks + 6]); }
                    return min(m0, m1);
                };
                anchor(const_cast<uint4*>(hf), h[4 * hi.value - 1] & __float_as_uint(f0));
                load_h(hi, nx);
                if (__any_sync(0xffffffffu, low() == 0)) {
                    uint32_t it = 0;
#pragma unroll 1
                    do load_h(lo, hi); while (__any_sync(0xffffffffu, low() == 0) && ++it < SPIN / 16);
                }
            };
            __nanosleep(100);
            load_h(IC<0>{}, IC<4>{});
            DBG_T(104); DBG_G(109);
            mbar_wait(bar_w0, 0);
#pragma unroll
            for (int e = E0 + 1; e < E0 + 3; e++) mbar_wait(bar_full + 8 * (e & 3), e >> 2);
#pragma unroll
            for (int i = 0; i < 64; i++) o[i] = 0.f;
            auto group = [&](auto tc, auto ec) {
                constexpr int t = tc.value, e = ec.value, k0 = t ? 8 * t - 4 : 0;
                constexpr bool first = e < E0 + 5, turns = e >= E0 + 4;
                uint64_t dv = (first ? args.d0 : desc_lo(0, UNIT) | (0x40000040ull << 32)) + ((t ? 0 : 512) + (e == E0 ? 6 : e & 3) * (SLOT / 16));
                if (first && t == 0) check_h(IC<0>{}, IC<4>{});
                if (first && t >= 3) mbar_wait(bar_full + 8 * (e & 3), e >> 2);
                if (first && t > 0) check_h2(IC<k0>{}, IC<8 * t + 4>{}, IC<t < 4 ? 8 * t + 12 : 0>{});
                if (t != 1 && turns) bar_sync(1 + w, 192);
                if (t != 1 || first) WG_FENCE();
#pragma unroll
                for (int ks = k0; ks < 8 * t + 4; ks++) {
                    mma_rs128<1>(o, h[4 * ks], h[4 * ks + 1], h[4 * ks + 2], h[4 * ks + 3], dv, ks);
                    if (t && turns && ks == k0 + QSPLIT - 1) WG_COMMIT();
                }
                if (t || first) WG_COMMIT();
                if (first && t == 0) load_h(IC<4>{}, IC<12>{});
                if (t > 0) {
                    WG_WAIT(1);
                    if (turns) handoff();
                    if ((t == 1 && !first) || (t > 1 && e <= E0 + 4)) release4(8 * ((e - 1) & 3));
                    if (turns && e != 18) { WG_WAIT(0); release4(8 * (e & 3)); }
                }
            };
            auto head = [&](auto ec, int slot) {
                constexpr int e = ec.value;
                fence_regs(o);
                group(IC<0>{}, IC<e>{}); group(IC<1>{}, IC<e + 1>{}); group(IC<2>{}, IC<e + 2>{}); group(IC<3>{}, IC<e + 3>{});
                if (e == 15) return;
                group(IC<4>{}, IC<e + 4>{});
                fence_regs(o);
#pragma unroll
                for (int i = 0; i < 8; i++)
                    qpark[slot * 2048 + i * 32] = make_uint4(pack_bf16(o[8 * i], o[8 * i + 1]), pack_bf16(o[8 * i + 2], o[8 * i + 3]),
                                                             pack_bf16(o[8 * i + 4], o[8 * i + 5]), pack_bf16(o[8 * i + 6], o[8 * i + 7]));
            };
            head(IC<E0>{}, 1);
            head(IC<E0 + 5>{}, 2);
            if (SPARE) {
                float (&u)[32] = reinterpret_cast<float (&)[32]>(o);
                fence_regs(u);
#pragma unroll
                for (int t = 0; t < 2; t++) {
                    uint64_t dv = args.d0 + t * (SLOT / 16);
                    bar_sync(1 + w, 192);
                    WG_FENCE();
#pragma unroll
                    for (int ks = 0; ks < 16 + 4 * t; ks++) {
                        mma_rs64<1>(u, h[64 * t + 4 * ks], h[64 * t + 4 * ks + 1], h[64 * t + 4 * ks + 2], h[64 * t + 4 * ks + 3], dv, ks | t);
                        if (ks == 2 * QSPLIT + 4 * t - 1) WG_COMMIT();
                    }
                    WG_COMMIT();
                    WG_WAIT(1);
                    handoff();
                    WG_WAIT(0);
                    release4(8 * t);
                }
                fence_regs(u);
                release4(16);
#pragma unroll
                for (int i = 0; i < 4; i++)
                    qpark[3 * 2048 + i * 32] = make_uint4(pack_bf16(u[8 * i], u[8 * i + 1]), pack_bf16(u[8 * i + 2], u[8 * i + 3]),
                                                          pack_bf16(u[8 * i + 4], u[8 * i + 5]), pack_bf16(u[8 * i + 6], u[8 * i + 7]));
            } else {
                head(IC<10>{}, 3);
            }
            head(IC<15>{}, 0);
#pragma unroll
            for (int i = 0; i < 8; i++) {
                const uint4 v = lds128(smem_u32(qpark + 2048 + i * 32));
                q[4 * i] = v.x; q[4 * i + 1] = v.y; q[4 * i + 2] = v.z; q[4 * i + 3] = v.w;
            }
#pragma unroll
            for (int i = 0; i < 32; i++) p[i] = h[112 + i];
            WG_WAIT(0);
            fence_regs(o);
            release4(16);
        }
        DBG_T(105);
        DBG_G(125);

        uint8_t* frag = reinterpret_cast<uint8_t*>(__shfl_sync(0xffffffffu, reinterpret_cast<unsigned long long>(g_frag + (size_t)(rg * 8 + cw) * WREG + lane * 16), lane));
        const uint4* qnext = reinterpret_cast<const uint4*>(__shfl_sync(0xffffffffu, reinterpret_cast<unsigned long long>(padd(smem_raw, SM_Q + tid * 16 + cw * 3584)), lane));
        uint8_t* odst = reinterpret_cast<uint8_t*>(const_cast<uint4*>(qnext));
        qnext -= 2048;
        float m0, m1, l0 = 0.25f, l1 = 0.25f, t0, t1;
        uint32_t bad = 0;
        auto finish = [&](auto lo, auto hi, uint32_t bit, auto sink) {
#pragma unroll
            for (int i = lo.value; i < hi.value; i++) {
                const uint32_t v0 = pack_bf16(o[8 * i] * t0, o[8 * i + 1] * t0), v1 = pack_bf16(o[8 * i + 2] * t1, o[8 * i + 3] * t1);
                const uint32_t v2 = pack_bf16(o[8 * i + 4] * t0, o[8 * i + 5] * t0), v3 = pack_bf16(o[8 * i + 6] * t1, o[8 * i + 7] * t1);
                if (i == 0 && fabsf(o[0] * t0) >= 0x1p-31f) bad |= bit << 8;
                sink(i, v0, v1, v2, v3);
            }
        };
        float lq[6];
        auto row_parts = [&]() {
#pragma unroll
            for (int i = 0; i < 3; i++) { lq[i] = __shfl_xor_sync(0xffffffffu, l0, i + 1); lq[3 + i] = __shfl_xor_sync(0xffffffffu, l1, i + 1); }
        };
        auto row_sums = [&](uint32_t bit) {
            t0 = (l0 + lq[0]) + (lq[1] + lq[2]); t1 = (l1 + lq[3]) + (lq[4] + lq[5]);
            if (!(t0 >= LMIN && t0 < LMAX && t1 >= LMIN && t1 < LMAX)) bad |= bit;
        };
        auto issue_pv = [&](uint64_t dv, int acc) {
            asm volatile("{\n.reg .pred p;\nsetp.eq.b32 p, %0, 0;\n@p bar.sync 4, 160;\n}" ::"r"(w) : "memory");
#pragma unroll
            for (int ks = 0; ks < 8; ks++)
                mma_rs128<1>(o, p[4 * ks], p[4 * ks + 1], p[4 * ks + 2], p[4 * ks + 3], dv, ks ? 1 : acc);
            WG_COMMIT();
        };
#pragma unroll
        for (int i = 0; i < 64; i++) s[i] = 0.f;
        uint64_t dv_lo = args.d0;
        uint32_t voff = 0;
        auto issue_qk = [&]() {
            uint64_t dk = dv_lo ^ (desc_lo(0, UNIT) ^ desc_lo(3 * SLOT, 16));
            bar_sync(1 + w, 192);
            fence_regs(s); fence_regs(q); fence_regs(o); fence_regs(p);
            WG_FENCE();
#pragma unroll
            for (int ks = 0; ks < 8; ks++)
                if (ks == 3) mma_rs128<0, 1018>(s, q[4 * ks], q[4 * ks + 1], q[4 * ks + 2], q[4 * ks + 3], dk, 1);
                else mma_rs128<0, 2>(s, q[4 * ks], q[4 * ks + 1], q[4 * ks + 2], q[4 * ks + 3], dk, ks != 0);
            WG_COMMIT();
        };
        auto to_frag = [&](int i, uint32_t v0, uint32_t v1, uint32_t v2, uint32_t v3) {
            *reinterpret_cast<uint4*>(odst + i * 512) = make_uint4(v0, v1, v2, v3); };
        int n = 0;
        auto scores_ready = [&]() {
            WG_WAIT(1);
            fence_regs(s); fence_regs(q);
        };
        auto pass_on = [&]() {
            release4(voff ^ 24);
            handoff();
        };
#pragma unroll 1
        for (;;) {
            {
                {
                    asm volatile("st.shared.v2.f32 [%0], {%1, %2};" ::"r"(sb + SM_RED + tid * 8), "f"(l0), "f"(l1) : "memory");
                    __syncwarp();
                    const uint4 a = lds128(sb + SM_RED + (tid & ~3) * 8), b = lds128(sb + SM_RED + (tid & ~3) * 8 + 16);
                    l0 = __uint_as_float(a.x); lq[0] = __uint_as_float(a.z); lq[1] = __uint_as_float(b.x); lq[2] = __uint_as_float(b.z);
                    l1 = __uint_as_float(a.y); lq[3] = __uint_as_float(a.w); lq[4] = __uint_as_float(b.y); lq[5] = __uint_as_float(b.w);
                }
                issue_qk();
                hold(l0, l1);
                row_sums(1u << (n >> 4));
                t0 = rcp_fast(t0); t1 = rcp_fast(t1);
                l0 = 0.f; l1 = 0.f;
                odst = n ? frag + ((n >> 4) - 1) * 4096 : odst;
                qnext = n == 48 ? reinterpret_cast<const uint4*>(frag) : qnext + 2048;
                anchor(bar_full + 504, (t0 + t1) * __uint_as_float((bad ^ (uint32_t)(uintptr_t)odst ^ (uint32_t)(uintptr_t)qnext) & 0x3fffffff));
                asm volatile("{\n.reg .pred p;\nsetp.ne.b32 p, %1, 0;\n@p mbarrier.arrive.shared::cta.b64 _, [%0];\n}"
                             ::"r"(bar_qfree + (n >> 1) - 8), "r"(lane ? 0 : n) : "memory");
                issue_pv(dv_lo, 1);
                scores_ready();
                const uint32_t a = pack_bf16(fmaxf(fmaxf(s[0], s[1]), fmaxf(s[4], s[5])), fmaxf(fmaxf(s[2], s[3]), fmaxf(s[6], s[7])));
                const uint32_t b = bmax2(bmax2(a, __shfl_xor_sync(0xffffffffu, a, 1)), bmax2(__shfl_xor_sync(0xffffffffu, a, 2), __shfl_xor_sync(0xffffffffu, a, 3)));
                pass_on();
                m0 = fmaf(-CS, bf_lo(b), -POFF); m1 = fmaf(-CS, bf_hi(b), -POFF);
            }
#pragma unroll 1
            for (;;) {
                DBG_T(n);
#pragma unroll
                for (int i = 0; i < 4 * STAGE; i++) s[i] = fmaf(s[i], CS, (i & 2) ? m1 : m0);
#pragma unroll
                for (int i = 0; i < 4 * SPLIT; i++) s[i] = ex2(s[i]);
#pragma unroll
                for (int i = 0; i < SPLIT; i++) { l0 += s[4 * i] + s[4 * i + 1]; l1 += s[4 * i + 2] + s[4 * i + 3]; }
                m0 = fmaf(l0, 0.f, m0); m1 = fmaf(l1, 0.f, m1);
                anchor(bar_full + 504, l0 + l1);
                WG_WAIT(0);
                fence_regs(o); fence_regs(p);
                release4(voff);
                dv_lo ^= 2 * SLOT / 16;
                voff ^= 16;
                n++;
#pragma unroll
                for (int i = 4 * STAGE; i < 64; i++) s[i] = fmaf(s[i], CS, (i & 2) ? m1 : m0);
#pragma unroll
                for (int i = 4 * SPLIT; i < 64; i++) s[i] = ex2(s[i]);
#pragma unroll
                for (int i = SPLIT; i < 16; i++) { l0 += s[4 * i] + s[4 * i + 1]; l1 += s[4 * i + 2] + s[4 * i + 3]; }
#pragma unroll
                for (int i = 0; i < 32; i++) p[i] = pack_bf16(s[2 * i], s[2 * i + 1]);
                const int jn = n & 15;
                if (jn > 1) {
                    issue_qk();
                    if ((n & 10) == 2) {
                        if (n & 1) {
#pragma unroll
                            for (int i = 0; i < 64; i++) o[i] *= (i & 2) ? t1 : t0;
                        } else {
                            row_parts();
                            row_sums(2u << (n >> 4));
                            const uint32_t e0 = __float_as_uint(t0) >> 23, e1 = __float_as_uint(t1) >> 23;
                            m0 -= __uint_as_float(0x4b000000u | e0) - (8388608.f + 127.f - POFF);
                            m1 -= __uint_as_float(0x4b000000u | e1) - (8388608.f + 127.f - POFF);
                            t0 = __uint_as_float((254 - (int)POFF - e0) << 23); t1 = __uint_as_float((254 - (int)POFF - e1) << 23);
                            l0 *= t0; l1 *= t1;
                        }
                    }
                    fence_regs(o);
                    WG_FENCE();
                    issue_pv(dv_lo, 1);
                    scores_ready();
                    pass_on();
                    if (jn != 15) continue;
#pragma unroll
                    for (int i = 0; i < 8; i++) {
                        const uint4 v = qnext[i * 32];
                        q[4 * i] = v.x; q[4 * i + 1] = v.y; q[4 * i + 2] = v.z; q[4 * i + 3] = v.w;
                    }
                    continue;
                }
                if (jn == 0) break;
                finish(IC<0>{}, IC<ESPLIT>{}, 1u << (n >> 4), to_frag);
                issue_qk();
                hold(t0, t1);
                finish(IC<ESPLIT>{}, IC<8>{}, 1u << (n >> 4), to_frag);
                WG_FENCE();
                issue_pv(dv_lo, 0);
                scores_ready();
                pass_on();
            }
            if (n == 64) break;
        }
        DBG_T(64);
        uint32_t a1[32], a2[32];
        bar_sync(1 + w, 192);
        fence_regs(o); fence_regs(p);
        WG_FENCE();
        issue_pv(args.d0 + 3 * SLOT / 16, 1);
        handoff();
        mbar_wait(bar_mod, 0);
        const int tid_ = __shfl_sync(0xffffffffu, tid, lane);
        row_parts();
        row_sums(16);
        t0 = rcp_fast(t0); t1 = rcp_fast(t1);
        anchor(frag, q[0] & q[4] & q[8] & q[12] & q[16] & q[20] & q[24] & q[28] & __float_as_uint(t0) & __float_as_uint(t1) & tid_);
        frag_load(a1, frag + 4096);
        frag_load<0, 4>(a2, frag + 8192);
        anchor(frag, bad);
        WG_WAIT(0);
        fence_regs(o); fence_regs(p);
        release4(24);
        finish(IC<0>{}, IC<8>{}, 16, [&](int i, uint32_t v0, uint32_t v1, uint32_t v2, uint32_t v3) {
            p[4 * i] = v0; p[4 * i + 1] = v1; p[4 * i + 2] = v2; p[4 * i + 3] = v3; });
        anchor(frag, p[31] & p[15]);
        frag_load<4, 8>(a2, frag + 8192);
        bad = __reduce_or_sync(0xffffffffu, bad);
        bad = ((bad | ~(bad >> 8)) >> 1) & 15;
        if (__builtin_expect(bad != 0, 0)) {
            uint8_t* keep = g_keep + (size_t)(rg * 8 + cw) * 4096 + lane * 16;
            frag_store(keep, p);
            attn_fallback(bad, tag, gs, frag, keep, args.wq, args.kc, args.vc);
            frag_load(q, frag); frag_load(a1, frag + 4096); frag_load(a2, frag + 8192); frag_load(p, keep);
            anchor(frag, q[0] & q[4] & q[8] & q[12] & q[16] & q[20] & q[24] & q[28] & p[0] & p[4] & p[8] & p[12] & p[16] & p[20] & p[24] & p[28]);
        }
        DBG_T(80);
        DBG_G(124);

        const uint32_t eye = (tid_ >> 3 & 3) == (tid_ & 3) ? 0x3f80u << ((tid_ & 4) * 4) : 0;
        auto sum8 = [&](uint32_t* r, const uint4 (&v)[8]) {
            float d[16];
#pragma unroll
            for (int i = 0; i < 16; i++) d[i] = 0.f;
#pragma unroll
            for (int src = 0; src < 8; src++) {
                mma1688(d + 8 * (src & 1), v[src].x, v[src].y, eye);
                mma1688(d + 8 * (src & 1) + 4, v[src].z, v[src].w, eye);
            }
#pragma unroll
            for (int i = 0; i < 4; i++) r[i] = pack_bf16(d[2 * i] + d[8 + 2 * i], d[2 * i + 1] + d[9 + 2 * i]);
        };
        uint4 v2[8], v3[8], wf[23];
        uint2 u4[8], gw[9];
        uint32_t x1[20], xs, pa, ta;
        const uint8_t *mb, *mb4;
        auto load_wf = [&](auto lo, auto hi) {
            const uint32_t wa = sb + SM_Q + ((tid_ & 8) * (D_ / 8) + cw * 16 + (tid_ & 7) + (tid_ & 16) / 2) * 80;
            const uint32_t wb = wa + (512 - cw * 8) * 80 - (tid_ & 16) * 39;
#pragma unroll
            for (int i = lo.value; i < hi.value; i++) wf[i] = ldsm4t(i < 20 ? wa + (i / 5) * 10240 + (i % 5) * 16 : wb + (i - 20) * 32);
        };
        uint32_t at[18];
        {
            float (&u)[32] = reinterpret_cast<float (&)[32]>(o);
            uint32_t off = 0;
            auto turn = [&](const uint32_t (&a)[32], const uint32_t (&b)[32], int acc) {
                uint64_t dv = args.d0 + off * (SLOT / 128);
                bar_sync(1 + w, 192);
                fence_regs(u);
                WG_FENCE();
#pragma unroll
                for (int ks = 0; ks < 16; ks++) {
                    const uint32_t* f = ks < 8 ? &a[4 * ks] : &b[4 * ks - 32];
                    mma_rs64<1>(u, f[0], f[1], f[2], f[3], dv, ks | acc);
                    if (ks == OSPLIT - 1) WG_COMMIT();
                }
                WG_COMMIT();
                WG_WAIT(1);
            };
            auto done = [&]() {
                WG_WAIT(0);
                fence_regs(u);
                release4(off);
                off = (off + 8) & 24;
            };
            auto store = [&](uint8_t* dst) {
#pragma unroll
                for (int i = 0; i < 4; i++)
                    st_relaxed4(dst + i * 512, pack_bf16(u[8 * i], u[8 * i + 1]), pack_bf16(u[8 * i + 2], u[8 * i + 3]),
                                pack_bf16(u[8 * i + 4], u[8 * i + 5]), pack_bf16(u[8 * i + 6], u[8 * i + 7]));
            };
            pa = sb + w * (UNIT - 2048) + tid_ * 16;
#pragma unroll
            for (int i = 0; i < 8; i++) at[i] = 0;
            fence_regs(q); fence_regs(p);
            uint8_t* dst = frag;
#pragma unroll
            for (int i = 0; i < 8; i++) asm volatile("" : "=r"(v2[i].x), "=r"(v2[i].y), "=r"(v2[i].z), "=r"(v2[i].w));
#pragma unroll 1
            for (int k = 0; k < 8; k++, dst += 2048) {
                const uint32_t poff = (off + 8) & 24;
                const bool sum = (0xa0 >> k) & 1;
                turn(q, p, 0);
                handoff();
                auto sum_p = [&](auto lo, auto hi) {
#pragma unroll
                    for (int i = lo.value; i < hi.value; i++) {
                        float a[8], b[8];
#pragma unroll
                        for (int src = 0; src < 8; src++) {
                            const uint32_t x = i == 0 ? v2[src].x : i == 1 ? v2[src].y : i == 2 ? v2[src].z : v2[src].w;
                            a[src] = bf_lo(x); b[src] = bf_hi(x);
                        }
                        at[i] = at[4 + i];
                        at[4 + i] = pack_bf16(((a[0] + a[2]) + (a[4] + a[6])) + ((a[1] + a[3]) + (a[5] + a[7])),
                                              ((b[0] + b[2]) + (b[4] + b[6])) + ((b[1] + b[3]) + (b[5] + b[7])));
                    }
                };
                if (sum) {
                    mbar_wait(bar_full + poff, 1);
#pragma unroll
                    for (int src = 0; src < 8; src++) v2[src] = lds128(pa + poff * (SLOT / 8) + src * 2048);
                    __syncwarp();
                    release(poff >> 3);
                    done();
                    off = (off + 8) & 24;
                    sum_p(IC<0>{}, IC<2>{});
                } else {
                    done();
                }
                turn(a1, a2, 1);
                handoff();
                if (sum) sum_p(IC<2>{}, IC<4>{});
                done();
                store(dst);
                __syncwarp();
                asm volatile("{\n.reg .pred p;\nsetp.ne.b32 p, %1, 0;\n@p mbarrier.arrive.shared::cta.b64 _, [%0];\n}"
                             ::"r"(bar_pub + 4 + 4 * k), "r"(lane ? 0 : (0x2a >> k) & 1) : "memory");
            }
            turn(q, p, 0);
            handoff();
            mb = padd(g_frag, (qb * 64 + j) * WREG + 3 * 4096 + tid_ * 16);
            mb4 = padd(mb, 4096 + ((cw >> 1) - cw) * 512 + (cw & 1) * 8);
            xs = sb + (tid_ & 15) * XP + (tid_ & 16) + cw * 32;
            ta = sb + (cw * 8 + (tid_ & 3)) * 8;
#pragma unroll
            for (int k = 0; k < 9; k++) {
                gw[k] = lds64(ta + SM_T + (k < 8 ? (k >> 1) * 64 + (k & 1) * 4 : 256 - cw * 4) * 8);
                if (!(tid_ & 4)) gw[k].y = 0x3f803f80u;
            }
            mbar_wait(bar_g, 0);
            done();
            load_wf(IC<0>{}, IC<WF0>{});
            turn(a1, a2, 1);
            if (w == 0) handoff();
            done();
            store(dst);
            mbar_wait(bar_full, 0);
            rows_load(x1, xs, cw);
            if (w == 0) bar_sync(5, 256); else bar_arrive(5, 256);
        }
        DBG_T(81);
        DBG_G(122);

        {
        const int tid = tid_, lane = tid & 31;
        const int g8 = lane >> 2, qd = lane & 3, l16 = lane & 15;
        uint32_t h2[18], gb[9], k1, k2;
        float4* rec = reinterpret_cast<float4*>(red + 128);
        const uint2* candp = reinterpret_cast<const uint2*>(padd(g_cand, ((bx & (CREP - 1)) * NCTA + (tid >> 1)) * 32 + (tid & 1) * 8));
        uint2 cd;
        auto stage_out = [&]() {
#pragma unroll
            for (int k = 0; k < 9; k++) {
                x1[2 * k] = badd2(x1[2 * k], bmul2(gb[k], h2[2 * k]));
                x1[2 * k + 1] = badd2(x1[2 * k + 1], bmul2(gb[k], h2[2 * k + 1]));
            }
#pragma unroll
            for (int ch = 0; ch < 4; ch++) stsm_x4(xs + ch * 256, x1[4 * ch], x1[4 * ch + 1], x1[4 * ch + 2], x1[4 * ch + 3]);
            asm volatile("stmatrix.sync.aligned.m8n8.x2.shared.b16 [%0], {%1, %2};" ::"r"(xs + 1024 - cw * 16), "r"(x1[16]), "r"(x1[17]) : "memory");
        };
        {
            uint32_t it = 0, miss;
            mbar_wait(bar_full + 8, 0);
#pragma unroll
            for (int src = 0; src < 8; src++) v2[src] = lds128(pa + SLOT + src * 2048);
            sum8(at + 8, v2);
            float st[12];
#pragma unroll
            for (int i = 0; i < 12; i++) st[i] = 0.f;
            auto add_pair = [&](int k) {
                x1[2 * k] = badd2(x1[2 * k], bmul2(gw[k].x, at[2 * k]));
                x1[2 * k + 1] = badd2(x1[2 * k + 1], bmul2(gw[k].x, at[2 * k + 1]));
                stats_add(st, x1[2 * k], x1[2 * k + 1], gw[k].y);
            };
#pragma unroll
            for (int k = 0; k < 6; k++) add_pair(k);
            mbar_wait(bar_full + 16, 0);
#pragma unroll
            for (int src = 0; src < 8; src++) v3[src] = lds128(pa + 2 * SLOT + src * 2048);
            miss = __vimax3_u32(__vimax3_u32(v3[0].x, v3[0].z, v3[1].x), __vimax3_u32(v3[1].z, v3[2].x, v3[2].z), __vimax3_u32(v3[3].x, v3[3].z, v3[4].x));
            miss = __vimax3_u32(miss, __vimax3_u32(v3[4].z, v3[5].x, v3[5].z), max(__vimax3_u32(v3[6].x, v3[6].z, v3[7].x), v3[7].z));
            if (__any_sync(0xffffffffu, miss == ~0u))
#pragma unroll 1
            do {
                miss = 0;
#pragma unroll
                for (int src = 0; src < 8; src++) reload16(v3[src], mb + (size_t)src * 8 * WREG, miss);
            } while (__any_sync(0xffffffffu, miss) && ++it < SPIN / 16);
            if (lane < 4) mbar_arrive_cluster(rel_base + 8 * (1 + (lane >> 1)));
            sum8(at + 12, v3);
            add_pair(6); add_pair(7);
            load_wf(IC<WF0>{}, IC<WF1>{});
            uint2 cs[9];
#pragma unroll
            for (int k = 0; k < 9; k++) cs[k] = lds64(ta + SM_TC + (k < 8 ? (k >> 1) * 64 + (k & 1) * 4 : 256 - cw * 4) * 8);
            mbar_wait(bar_pre, 0);
            mbar_wait(bar_full + 24, 0);
#pragma unroll
            for (int src = 0; src < 8; src++) u4[src] = lds64(sb + 3 * SLOT + src * 2048 + (cw >> 1) * 512 + lane * 16 + (cw & 1) * 8);
            miss = __vimax3_u32(__vimax3_u32(u4[0].x, u4[1].x, u4[2].x), __vimax3_u32(u4[3].x, u4[4].x, u4[5].x), max(u4[6].x, u4[7].x));
            if (__any_sync(0xffffffffu, miss == ~0u))
#pragma unroll 1
            do {
                miss = 0;
#pragma unroll
                for (int src = 0; src < 8; src++) reload8(u4[src], mb4 + (size_t)src * 8 * WREG, miss);
            } while (__any_sync(0xffffffffu, miss) && ++it < SPIN / 16);
            float d[8] = {0.f, 0.f, 0.f, 0.f, 0.f, 0.f, 0.f, 0.f};
#pragma unroll
            for (int i = 0; i < 4; i++) mma16816(d + 4 * (i & 1), u4[2 * i].x, u4[2 * i].y, u4[2 * i + 1].x, u4[2 * i + 1].y, eye, eye);
            at[16] = pack_bf16(d[0] + d[4], d[1] + d[5]); at[17] = pack_bf16(d[2] + d[6], d[3] + d[7]);
            add_pair(8);
            DBG_G(123);
            const float2 ws = *reinterpret_cast<const float2*>(smem_raw + SM_TS);
            uint4* cdst = padd(g_cand, (tid * NCTA + rg) * 32);
            uint32_t mean2;
            float dot;
            const float rsd = rows_stats(st, rec, cw, lane, mean2, dot);
            const uint32_t b = __float_as_uint(fmaf(fmaf(-bf_lo(mean2), ws.x, dot), rsd, ws.y));
            const uint32_t key = (((b & 0x80000000u) ? ~b : (b | 0x80000000u)) | 2047u) - (rg * 16 + l16);
            top2(key, k1, k2);
            if (tid < CREP) st_relaxed(cdst, k1, tag, k2, tag);
            cd = ld_relaxed64(candp);
            rows_normalise(h2, x1, mean2, rsd, lane, [&]() {
#pragma unroll
                for (int k = 0; k < 9; k++) gb[k] = lds32(sb + SM_TG + (cw * 8 + qd + (k < 8 ? (k >> 1) * 64 + (k & 1) * 4 : 256 - cw * 4)) * 4);
                load_wf(IC<WF1>{}, IC<WF2>{});
            });
#pragma unroll
            for (int k = 0; k < 18; k++) h2[k] = badd2(bmul2(h2[k], cs[k >> 1].x), cs[k >> 1].y);
            const uint32_t r1 = ~k1 & 15, r2 = ~k2 & 15;
            uint32_t todo = ((r1 & 7) == g8) | ((r2 & 7) == g8) << 1;
#pragma unroll 1
            while (todo) {
                const bool second = !(todo & 1), hi = (second ? r2 : r1) & 8;
                uint4* dst = padd(g_rows, ((rg * 2 + second) * RSLOT + cw * 24 + qd) * 16);
                uint32_t r[18];
#pragma unroll
                for (int k = 0; k < 9; k++) { r[k] = hi ? h2[2 * k + 1] : h2[2 * k]; r[9 + k] = hi ? x1[2 * k + 1] : x1[2 * k]; }
                fence_regs(r);
                st_relaxed(dst, r[0], r[1], r[2], r[3]);
                st_relaxed(dst + 8, r[4], r[5], r[6], r[7]);
                st_relaxed64(reinterpret_cast<uint2*>(padd(dst, 256 - qd * 8)), r[8], r[17]);
                st_relaxed(dst + 4, r[9], r[10], r[11], r[12]);
                st_relaxed(dst + 12, r[13], r[14], r[15], r[16]);
                todo &= todo - 1;
            }
            __syncwarp();

            stage_out();
        }
        DBG_G(110);
        float4* part = reinterpret_cast<float4*>(smem_raw + 3 * SLOT + UNIT + 8192);
        bf16* act = reinterpret_cast<bf16*>(smem_raw + 3 * SLOT + UNIT + 4096);
        {
            uint32_t it = 0;
            const bool own = (tid >> 1) == rg;
            const uint32_t ks = sb + 3 * SLOT + UNIT + 5120;
#pragma unroll 1
            while (__any_sync(0xffffffffu, cd.y != tag && !own) && ++it < SPIN / 16)
                asm volatile("{\n.reg .pred p;\n.reg .b64 u;\nsetp.ne.u32 p, %1, %3;\nmov.b64 u, {%0, %1};\n"
                             "@p ld.relaxed.gpu.global.b64 u, [%2];\nmov.b64 {%0, %1}, u;\n}" : "+r"(cd.x), "+r"(cd.y) : "l"(candp), "r"(tag) : "memory");
            asm volatile("st.shared.u32 [%0], %1;" ::"r"(ks + tid * 4), "r"(own ? (tid & 1) ? k2 : k1 : cd.x) : "memory");
            bar_sync(3, 256);
            DBG_G(111);
            const uint4 a = lds128(ks + lane * 16), b = lds128(ks + 512 + lane * 16);
            const uint32_t a1 = max(a.x, a.z), a2 = __vimax3_u32(min(a.x, a.z), a.y, a.w);
            const uint32_t b1 = max(b.x, b.z), b2 = __vimax3_u32(min(b.x, b.z), b.y, b.w);
            const uint32_t c1 = max(a1, b1), c2 = __vimax3_u32(min(a1, b1), a2, b2);
            k1 = __reduce_max_sync(0xffffffffu, c1);
            k2 = __reduce_max_sync(0xffffffffu, c1 == k1 ? c2 : c1);
        }
        const int sel0 = ~k1 & 2047, sel1 = ~k2 & 2047;
        const uint32_t slot0 = (sel0 >> 4) * 2, slot1 = (sel1 >> 4) * 2 + ((sel0 ^ sel1) < 16);
        uint4 da[13];
        {
            const uint4* hp = padd(g_rows, (((g8 & 1) ? slot1 : slot0) * RSLOT + cw * 24 + qd) * 16);
            const uint2* hp2 = reinterpret_cast<const uint2*>(padd(hp, 256 - qd * 8));
            uint4 hv[2] = {ld_relaxed2(hp), ld_relaxed2(hp + 8)};
            uint2 hw = ld_relaxed64(hp2);
            if (tid == 255) {
                reinterpret_cast<int2*>(red)[8] = make_int2(sel0, sel1);
                mbar_arrive(bar_out);
            }
            load_wf(IC<WF2>{}, IC<23>{});
            mbar_wait(bar_full + 8, 1);
            mbar_wait(bar_full + 16, 1);
            auto load_d = [&](auto lo, auto hi) {
                const int r = (lane & 7) + (lane & 16) / 2;
                const uint32_t d0 = sb + SLOT + r * XP + cw * 144 + (lane & 8) * 2, d1 = d0 + (r < 2 ? 16 * XP : SLOT - 2 * XP);
                const uint32_t d2 = sb + 2 * SLOT + (14 + (lane & 3)) * XP + cw * 144 + (lane >> 3) * 16;
#pragma unroll
                for (int i = lo.value; i < hi.value; i++) da[i] = ldsm4t(i < 10 ? ((i & 1) ? d1 : d0) + (i >> 1) * 32 : d2 + (i - 10) * 64);
            };
            load_d(IC<0>{}, IC<DL>{});
            uint32_t it = 0, miss;
            float f0 = 1.f, f1 = 1.f;
            hold(f0, f1);
            if (__any_sync(0xffffffffu, max(__vimax3_u32(__vimax3_u32(__float_as_uint(f0), hv[0].x, hv[0].z), hv[1].x, hv[1].z), hw.x) == ~0u))
#pragma unroll 1
            do {
                miss = 0;
                reload16(hv[0], hp, miss);
                reload16(hv[1], hp + 8, miss);
                reload8(hw, hp2, miss);
            } while (__any_sync(0xffffffffu, miss) && ++it < SPIN / 16);
            DBG_G(112);
            float acc[20];
#pragma unroll
            for (int i = 0; i < 20; i++) acc[i] = 0.f;
#pragma unroll
            for (int i = 0; i < 5; i++) mma1688(acc + 4 * i, (i & 1) ? wf[20 + i / 2].z : wf[20 + i / 2].x, (i & 1) ? wf[20 + i / 2].w : wf[20 + i / 2].y, hw.x);
#pragma unroll
            for (int i = 0; i < 20; i++)
                mma16816(acc + 4 * (i % 5), wf[i].x, wf[i].y, wf[i].z, wf[i].w, (i / 5 & 1) ? hv[i / 10].z : hv[i / 10].x, (i / 5 & 1) ? hv[i / 10].w : hv[i / 10].y);
            if (qd == 0) {
#pragma unroll
                for (int i = 0; i < 5; i++) part[cw * 40 + i * 8 + g8] = make_float4(acc[4 * i], acc[4 * i + 1], acc[4 * i + 2], acc[4 * i + 3]);
            }
            load_d(IC<DL>{}, IC<13>{});
        }
        {
            uint2* dst = padd(g_ypart, ((cw * 9 * NCTA + bx) * 8 + g8) * 8);
            bar_sync(3, 256);
            if (cw < 5) {
                const float* pp = reinterpret_cast<const float*>(part) + ((bx & 1) << 4) + tid;
                const float g = rbf(((pp[0] + pp[160]) + (pp[320] + pp[480])) + ((pp[640] + pp[800]) + (pp[960] + pp[1120])));
                const float v = rbf(g * sigmoidf_(g)) * __shfl_down_sync(0xffffffffu, g, 2);
                if (!(tid & 2)) act[(tid & 1) * 56 + (tid >> 2)] = __float2bfloat16_rn(tid < 144 ? v : 0.f);
            }
            bar_sync(3, 256);
            DBG_G(113);
            const uint32_t ap = sb + 3 * SLOT + UNIT + 4096 + (lane & 1) * 112 + (lane >> 3) * 16;
            const uint4 b0 = ldsm4(ap);
            const uint32_t b1 = lds32(sb + 3 * SLOT + UNIT + 4096 + (g8 & 1) * 112 + 64 + qd * 4);
            float y[20];
#pragma unroll
            for (int i = 0; i < 20; i++) y[i] = 0.f;
#pragma unroll
            for (int i = 0; i < 5; i++) {
                mma16816(y + 4 * i, da[2 * i].x, da[2 * i].y, da[2 * i].z, da[2 * i].w, b0.x, b0.y);
                mma16816(y + 4 * i, da[2 * i + 1].x, da[2 * i + 1].y, da[2 * i + 1].z, da[2 * i + 1].w, b0.z, b0.w);
                mma1688(y + 4 * i, (i & 1) ? da[10 + i / 2].z : da[10 + i / 2].x, (i & 1) ? da[10 + i / 2].w : da[10 + i / 2].y, b1);
            }
            if (qd == 0) {
#pragma unroll
                for (int i = 0; i < 9; i++)
                    asm volatile("st.relaxed.gpu.global.v2.f32 [%0], {%1, %2};" ::"l"(dst + i * (NCTA * 8)), "f"(y[2 * i]), "f"(y[2 * i + 1]) : "memory");
            }
        }
        DBG_G(114);
        if (bx < 72) {
            const int G = bx, tok = g8 & 1, cp = G * 4 + qd;
            const uint2* src = padd(g_ypart, (bx * NCTA * 8 + tid) * 8);
            const uint8_t* hsrc = reinterpret_cast<const uint8_t*>(padd(g_rows, (tok ? slot1 : slot0) * (RSLOT * 16) +
                (G < 64 ? (G >> 1 & 7) * 384 + (G >> 5) * 128 + qd * 16 + (G >> 1 & 8) + (G & 1) * 4 : (G - 64) * 384 + 256 + qd * 8)));
            const uint8_t* xsrc = hsrc + (G < 64 ? 64 : 4);
            uint32_t* dst = padd(reinterpret_cast<uint32_t*>(args.out), (tok ? sel1 : sel0) * (D_ * 2) + cp * 4);
            const uint32_t gb = reinterpret_cast<const uint32_t*>(smem_raw + SM_TG)[cp];
            const uint32_t ksel = ((tok ? k2 : k1) & ~2047u) | 1024u;
            const float sg = sigmoidf_(rbf(__uint_as_float((ksel & 0x80000000u) ? (ksel & 0x7fffffffu) : ~ksel)));
            uint2 v[4];
            uint32_t hv = 0, xv = 0, it = 0, miss;
            if (cw == 0) { hv = ld_relaxed32(hsrc); xv = ld_relaxed32(xsrc); }
#pragma unroll
            for (int i = 0; i < 4; i++) v[i] = make_uint2(~0u, 0);
#pragma unroll 1
            do {
#pragma unroll
                for (int i = 0; i < 4; i++) reload8(v[i], src + i * 256, miss);
            } while (__any_sync(0xffffffffu, max(__vimax3_u32(v[0].x, v[1].x, v[2].x), v[3].x) == ~0u) && ++it < SPIN / 16);
#pragma unroll 1
            while (max(hv, xv) == ~0u && ++it < SPIN / 16) { hv = ld_relaxed32(hsrc); xv = ld_relaxed32(xsrc); }
            __syncwarp();
            float y0 = (__uint_as_float(v[0].x) + __uint_as_float(v[1].x)) + (__uint_as_float(v[2].x) + __uint_as_float(v[3].x));
            float y1 = (__uint_as_float(v[0].y) + __uint_as_float(v[1].y)) + (__uint_as_float(v[2].y) + __uint_as_float(v[3].y));
            y0 += __shfl_xor_sync(0xffffffffu, y0, 8); y1 += __shfl_xor_sync(0xffffffffu, y1, 8);
            y0 += __shfl_xor_sync(0xffffffffu, y0, 16); y1 += __shfl_xor_sync(0xffffffffu, y1, 16);
            if (lane < 8) reinterpret_cast<float2*>(rec)[cw * 8 + lane] = make_float2(y0, y1);
            bar_sync(3, 256);
            if (cw == 0) {
                const float4 t0_ = rec[(lane >> 3) * 4 + qd], t1_ = rec[16 + (lane >> 3) * 4 + qd];
                y0 = tok ? t0_.y + t1_.y : t0_.x + t1_.x; y1 = tok ? t0_.w + t1_.w : t0_.z + t1_.z;
                y0 += __shfl_xor_sync(0xffffffffu, y0, 8); y1 += __shfl_xor_sync(0xffffffffu, y1, 8);
                y0 += __shfl_xor_sync(0xffffffffu, y0, 16); y1 += __shfl_xor_sync(0xffffffffu, y1, 16);
                const uint32_t y2 = bmul2(pack_bf16(y0, y1), pack_bf16(sg, sg));
                if (lane < 8) *dst = badd2(xv, bmul2(gb, badd2(hv, y2)));
            }
        }
        }
        DBG_T(88);
        DBG_G(121);
    }
}

typedef CUresult (*EncodeFn)(CUtensorMap*, CUtensorMapDataType, cuuint32_t, void*, const cuuint64_t*, const cuuint64_t*,
                             const cuuint32_t*, const cuuint32_t*, CUtensorMapInterleave, CUtensorMapSwizzle,
                             CUtensorMapL2promotion, CUtensorMapFloatOOBfill);

static void make_map(EncodeFn enc, CUtensorMap* m, const void* ptr, int rank, const cuuint64_t* dims,
                     const cuuint64_t* strides, const cuuint32_t* box, CUtensorMapSwizzle sw = CU_TENSOR_MAP_SWIZZLE_128B,
                     CUtensorMapDataType dt = CU_TENSOR_MAP_DATA_TYPE_BFLOAT16) {
    const cuuint32_t es[3] = {1, 1, 1};
    enc(m, dt, rank, const_cast<void*>(ptr), dims, strides, box, es,
        CU_TENSOR_MAP_INTERLEAVE_NONE, sw, CU_TENSOR_MAP_L2_PROMOTION_L2_128B,
        CU_TENSOR_MAP_FLOAT_OOB_FILL_NONE);
}

extern "C" void kernel_launch(void* const* d_in, const int* in_sizes, int n_in, void* d_out, int out_size) {
    const bf16* x = (const bf16*)d_in[0];
    const bf16* kc = (const bf16*)d_in[1];
    const bf16* vc = (const bf16*)d_in[2];
    const bf16* wq = (const bf16*)d_in[3];
    const bf16* wo = (const bf16*)d_in[4];
    const bf16* w_r = (const bf16*)d_in[6];
    const bf16* w_gate = (const bf16*)d_in[7];
    const bf16* w_up = (const bf16*)d_in[8];
    const bf16* w_down = (const bf16*)d_in[9];
    const bf16* cvec = (const bf16*)d_in[10];
    const bf16* w_mod = (const bf16*)d_in[11];
    bf16* out = (bf16*)d_out;

    void* fn = nullptr;
    cudaDriverEntryPointQueryResult qr;
    cudaGetDriverEntryPoint("cuTensorMapEncodeTiled", &fn, cudaEnableDefault, &qr);
    EncodeFn enc = (EncodeFn)fn;
    void* p_s;
    cudaGetSymbolAddress(&p_s, g_s);

    CUtensorMap tm_wq, tm_k, tm_v, tm_wo, tm_p, tm_x, tm_d, tm_g, tm_u;
    { cuuint64_t d[2] = {QD, D_}, s[1] = {QD * 2}; cuuint32_t b[2] = {64, 128}; make_map(enc, &tm_wq, wq, 2, d, s, b); }
    { cuuint64_t d[2] = {DH, HKV * S_}, s[1] = {DH * 2}; cuuint32_t b[2] = {64, 128};
      make_map(enc, &tm_k, kc, 2, d, s, b); make_map(enc, &tm_v, vc, 2, d, s, b); }
    { cuuint64_t d[2] = {D_, QD}, s[1] = {D_ * 2}; cuuint32_t b[2] = {64, 128}; make_map(enc, &tm_wo, wo, 2, d, s, b); }
    { cuuint64_t d[3] = {256, 160, NCTA}, s[2] = {1024, 8 * WREG}; cuuint32_t b[3] = {256, 2, 8};
      make_map(enc, &tm_p, ((Scratch*)p_s)->frag, 3, d, s, b, CU_TENSOR_MAP_SWIZZLE_NONE, CU_TENSOR_MAP_DATA_TYPE_UINT32); }
    { cuuint64_t d[2] = {D_ / 4, S_}, s[1] = {D_ * 2}; cuuint32_t b[2] = {XP / 8, 16};
      make_map(enc, &tm_x, x, 2, d, s, b, CU_TENSOR_MAP_SWIZZLE_NONE, CU_TENSOR_MAP_DATA_TYPE_UINT64); }
    { cuuint64_t d[2] = {D_ / 4, F_}, s[1] = {D_ * 2}; cuuint32_t b[2] = {XP / 8, 18};
      make_map(enc, &tm_d, w_down, 2, d, s, b, CU_TENSOR_MAP_SWIZZLE_NONE, CU_TENSOR_MAP_DATA_TYPE_UINT64); }
    { cuuint64_t d[2] = {F_, D_}, s[1] = {F_ * 2}; cuuint32_t b[2] = {40, 24};
      make_map(enc, &tm_g, w_gate, 2, d, s, b, CU_TENSOR_MAP_SWIZZLE_NONE); make_map(enc, &tm_u, w_up, 2, d, s, b, CU_TENSOR_MAP_SWIZZLE_NONE); }

    cudaFuncSetAttribute(fused_kernel<true>, cudaFuncAttributeMaxDynamicSharedMemorySize, SM_TOTAL);
    cudaFuncSetAttribute(fused_kernel<false>, cudaFuncAttributeMaxDynamicSharedMemorySize, SM_TOTAL);
    cudaLaunchConfig_t cfg = {};
    cfg.gridDim = NCTA + 4; cfg.blockDim = 384; cfg.dynamicSmemBytes = SM_TOTAL;
    cudaLaunchAttribute at;
    at.id = cudaLaunchAttributeClusterDimension; at.val.clusterDim.x = 2; at.val.clusterDim.y = 1; at.val.clusterDim.z = 1;
    cfg.attrs = &at; cfg.numAttrs = 1;
    int ncl = 0;
    if (cudaOccupancyMaxActiveClusters(&ncl, fused_kernel<true>, &cfg) != cudaSuccess) { ncl = 0; cudaGetLastError(); }
    Args args{w_mod, cvec, (Scratch*)p_s, desc_lo(0, UNIT) | (0x40000040ull << 32), out, x, kc, vc, wq, wo, w_r, w_down};
    if (USE_SPARE && ncl >= NCTA / 2 + 2)
        fused_kernel<true><<<NCTA + 4, 384, SM_TOTAL>>>(args, tm_wq, tm_k, tm_v, tm_wo, tm_p, tm_x, tm_d, tm_g, tm_u);
    else
        fused_kernel<false><<<NCTA, 384, SM_TOTAL>>>(args, tm_wq, tm_k, tm_v, tm_wo, tm_p, tm_x, tm_d, tm_g, tm_u);
}
```

```cpp
#include <cuda_runtime.h>
#include <cuda_bf16.h>
#include <cuda.h>
#include <stdint.h>
#include <math.h>

typedef __nv_bfloat16 bf16;

constexpr int S_ = 2048;
constexpr int D_ = 576;
constexpr int HQ = 32, HKV = 16, DH = 128;
constexpr int F_ = 4608;
constexpr int QD = HQ * DH;

constexpr int NCTA = 128;
constexpr int WREG = 5 * 4096;
constexpr int CREP = 8;
constexpr int RSLOT = 192;
constexpr int MREP = 4;
struct Scratch {
    unsigned int epoch[128];
    unsigned int flag_mod[NCTA];
    unsigned int flag_part[16 * 256];
    unsigned int flag_q3[16 * 32];
    unsigned int flag_h[NCTA * 32];
    uint2 mod1[MREP * D_];
    uint32_t mod2[4 * D_];
    uint4 cand[CREP * NCTA * 2];
    uint2 ypart[72 * NCTA * 8];
    uint4 h[2][NCTA * 36 * 32];
    uint4 q3[NCTA * 8 * 128];
    uint4 rows[NCTA * 2 * RSLOT];
    uint8_t frag[NCTA * 8 * WREG];
    uint8_t keep[NCTA * 8 * 4096];
};
__device__ __align__(1024) Scratch g_s;
#define g_h gs->h[tag & 1]
#define g_q3 gs->q3
#define g_keep gs->keep
#define g_flag_h gs->flag_h
#define g_flag_part gs->flag_part
#define g_flag_mod gs->flag_mod
#define g_flag_q3 gs->flag_q3
#define g_frag gs->frag
#define g_cand gs->cand
#define g_ypart gs->ypart
#define g_rows gs->rows

#define DBG_INIT()
#define DBG_P(i)
#define DBG_PG(i)
#define DBG_T(i)
#define DBG_G(i)

__device__ __forceinline__ uint32_t pack_bf16(float lo, float hi) {
    uint32_t r;
    asm("cvt.rn.bf16x2.f32 %0, %1, %2;" : "=r"(r) : "f"(hi), "f"(lo));
    return r;
}
__device__ __forceinline__ float rbf(float x) { return __uint_as_float(pack_bf16(0.f, x)); }
__device__ __forceinline__ float bf_lo(uint32_t v) { return __uint_as_float(v << 16); }
__device__ __forceinline__ float bf_hi(uint32_t v) { return __uint_as_float(v & 0xffff0000u); }
__device__ __forceinline__ float ex2(float x) {
    float y;
    asm("ex2.approx.ftz.f32 %0, %1;" : "=f"(y) : "f"(x));
    return y;
}
template <class T>
__device__ __forceinline__ T* padd(T* p, uint32_t off) {
    unsigned long long r;
    asm("{\n.reg .b32 l, h;\nmov.b64 {l, h}, %1;\nadd.cc.u32 l, l, %2;\naddc.u32 h, h, 0;\nmov.b64 %0, {l, h};\n}" : "=l"(r) : "l"(p), "r"(off));
    return reinterpret_cast<T*>(r);
}
__device__ __forceinline__ uint32_t smem_u32(const void* p) { return (uint32_t)__cvta_generic_to_shared(p); }
__device__ __forceinline__ void mbar_init(uint32_t bar, uint32_t cnt) {
    asm volatile("mbarrier.init.shared::cta.b64 [%0], %1;" ::"r"(bar), "r"(cnt) : "memory");
}
__device__ __forceinline__ void mbar_expect_tx(uint32_t bar, uint32_t bytes) {
    asm volatile("mbarrier.arrive.expect_tx.shared::cta.b64 _, [%0], %1;" ::"r"(bar), "r"(bytes) : "memory");
}
__device__ __forceinline__ void mbar_arrive(uint32_t bar) {
    asm volatile("mbarrier.arrive.shared::cta.b64 _, [%0];" ::"r"(bar) : "memory");
}
__device__ __forceinline__ void arrive_if(uint32_t bar, bool on) {
    asm volatile("{\n.reg .pred p;\nsetp.ne.b32 p, %1, 0;\n@p mbarrier.arrive.shared::cta.b64 _, [%0];\n}" ::"r"(bar), "r"((uint32_t)on) : "memory");
}
__device__ __forceinline__ void mbar_arrive_cluster(uint32_t cluster_addr) {
    asm volatile("mbarrier.arrive.shared::cluster.b64 _, [%0];" ::"r"(cluster_addr) : "memory");
}
constexpr uint32_t SPIN = 1u << 20;
__device__ __forceinline__ void mbar_wait(uint32_t bar, uint32_t parity) {
    asm volatile("{\n.reg .pred p;\n.reg .b32 c;\nmov.b32 c, 0;\n"
                 "W_%=:\nmbarrier.try_wait.parity.shared::cta.b64 p, [%0], %1;\n"
                 "add.u32 c, c, 1;\nsetp.lt.and.u32 p, c, 0x100000, !p;\n@p bra W_%=;\n}"
                 ::"r"(bar), "r"(parity) : "memory");
}
__device__ __forceinline__ void anchor(uint32_t addr, float v) {
    asm volatile("{\n.reg .pred p;\nsetp.lt.f32 p, %1, 0f00000000;\n@p st.volatile.shared.f32 [%0], %1;\n}" ::"r"(addr), "f"(v) : "memory");
}
__device__ __forceinline__ void anchor(uint32_t addr, uint32_t v) {
    asm volatile("{\n.reg .pred p;\nsetp.eq.u32 p, %1, 0xffffffff;\n@p st.volatile.shared.u32 [%0], %1;\n}" ::"r"(addr), "r"(v) : "memory");
}
__device__ __forceinline__ void anchor(void* p, uint32_t v) {
    asm volatile("{\n.reg .pred p;\nsetp.eq.u32 p, %1, 0xffffffff;\n@p st.volatile.u32 [%0], %1;\n}" ::"l"(p), "r"(v) : "memory");
}
__device__ __forceinline__ void hold(float& a, float& b) {
    asm volatile("{\n.reg .pred p;\n.reg .b64 t;\n.reg .b32 l, h;\nmov.u64 t, %%clock64;\nmov.b64 {l, h}, t;\nsetp.eq.u32 p, h, 0xffffffff;\n"
                 "@p mov.f32 %0, 0f00000000;\n@p mov.f32 %1, 0f00000000;\n}" : "+f"(a), "+f"(b) :: "memory");
}
__device__ __forceinline__ void mbar_wait_sleep(uint32_t bar, uint32_t parity) {
    asm volatile("{\n.reg .pred p;\n.reg .b32 c;\nmov.b32 c, 0;\n"
                 "W_%=:\nmbarrier.try_wait.parity.shared::cta.b64 p, [%0], %1, 5000;\n"
                 "add.u32 c, c, 1;\nsetp.lt.and.u32 p, c, 0x20000, !p;\n@p bra W_%=;\n}"
                 ::"r"(bar), "r"(parity) : "memory");
}
__device__ __forceinline__ uint32_t load_tag(const Scratch* gs) {
    uint32_t tag;
    asm volatile("ld.global.ca.u32 %0, [%1];" : "=r"(tag) : "l"(gs->epoch) : "memory");
    return tag + 1;
}
__device__ __forceinline__ uint4 ld_relaxed(const uint4* p) {
    uint4 v;
    asm volatile("ld.relaxed.gpu.global.v4.u32 {%0,%1,%2,%3}, [%4];" : "=r"(v.x), "=r"(v.y), "=r"(v.z), "=r"(v.w) : "l"(p) : "memory");
    return v;
}
__device__ __forceinline__ void st_relaxed(uint4* p, uint32_t a, uint32_t b, uint32_t c, uint32_t d) {
    asm volatile("{\n.reg .b64 u, v;\nmov.b64 u, {%1, %2};\nmov.b64 v, {%3, %4};\nst.relaxed.gpu.global.v2.b64 [%0], {u, v};\n}"
                 ::"l"(p), "r"(a), "r"(b), "r"(c), "r"(d) : "memory");
}
__device__ __forceinline__ void st_relaxed4(void* p, uint32_t a, uint32_t b, uint32_t c, uint32_t d) {
    asm volatile("st.relaxed.gpu.global.v4.u32 [%0], {%1, %2, %3, %4};" ::"l"(p), "r"(a), "r"(b), "r"(c), "r"(d) : "memory");
}
__device__ __forceinline__ uint2 ld_relaxed64(const uint2* p) {
    uint2 v;
    asm volatile("{\n.reg .b64 u;\nld.relaxed.gpu.global.b64 u, [%2];\nmov.b64 {%0, %1}, u;\n}" : "=r"(v.x), "=r"(v.y) : "l"(p) : "memory");
    return v;
}
__device__ __forceinline__ void st_relaxed64(uint2* p, uint32_t a, uint32_t b) {
    asm volatile("{\n.reg .b64 u;\nmov.b64 u, {%1, %2};\nst.relaxed.gpu.global.b64 [%0], u;\n}" ::"l"(p), "r"(a), "r"(b) : "memory");
}
__device__ __forceinline__ uint4 ld_relaxed2(const uint4* p) {
    uint4 v;
    asm volatile("{\n.reg .b64 u, w;\nld.relaxed.gpu.global.v2.b64 {u, w}, [%4];\nmov.b64 {%0, %1}, u;\nmov.b64 {%2, %3}, w;\n}"
                 : "=r"(v.x), "=r"(v.y), "=r"(v.z), "=r"(v.w) : "l"(p) : "memory");
    return v;
}
__device__ __forceinline__ void reload16(uint4& v, const void* p, uint32_t& miss) {
    asm volatile("{\n.reg .pred p;\n.reg .b32 m;\n.reg .b64 u, w;\nmax.u32 m, %0, %2;\nsetp.eq.u32 p, m, 0xffffffff;\n"
                 "mov.b64 u, {%0, %1};\nmov.b64 w, {%2, %3};\n@p ld.relaxed.gpu.global.v2.b64 {u, w}, [%5];\n"
                 "mov.b64 {%0, %1}, u;\nmov.b64 {%2, %3}, w;\n@p mov.u32 %4, 1;\n}"
                 : "+r"(v.x), "+r"(v.y), "+r"(v.z), "+r"(v.w), "+r"(miss) : "l"(p) : "memory");
}
__device__ __forceinline__ void reload8(uint2& v, const void* p, uint32_t& miss) {
    asm volatile("{\n.reg .pred p;\n.reg .b64 u;\nsetp.eq.u32 p, %0, 0xffffffff;\nmov.b64 u, {%0, %1};\n"
                 "@p ld.relaxed.gpu.global.b64 u, [%3];\nmov.b64 {%0, %1}, u;\n@p mov.u32 %2, 1;\n}"
                 : "+r"(v.x), "+r"(v.y), "+r"(miss) : "l"(p) : "memory");
}
__device__ __forceinline__ uint32_t ld_relaxed32(const void* p) {
    uint32_t v;
    asm volatile("ld.relaxed.gpu.global.u32 %0, [%1];" : "=r"(v) : "l"(p) : "memory");
    return v;
}
__device__ __forceinline__ void flag_wait(const unsigned int* p, uint32_t tag) {
    uint32_t v, it = 0;
#pragma unroll 1
    do {
        asm volatile("ld.relaxed.gpu.global.u32 %0, [%1];" : "=r"(v) : "l"(p) : "memory");
    } while (__any_sync(0xffffffffu, v != tag) && ++it < SPIN / 16);
    asm volatile("fence.acquire.gpu;" ::: "memory");
    __syncwarp();
}
__device__ __forceinline__ bool elect() {
    uint32_t p;
    asm volatile("{\n.reg .pred p;\nelect.sync _|p, 0xffffffff;\nselp.u32 %0, 1, 0, p;\n}" : "=r"(p));
    return p;
}
__device__ __forceinline__ void flag_release(unsigned int* p, uint32_t tag) {
    asm volatile("st.release.gpu.global.u32 [%0], %1;" ::"l"(p), "r"(tag) : "memory");
}
__device__ __forceinline__ uint32_t touch(const void* p) {
    uint32_t v;
    asm volatile("ld.global.nc.L1::no_allocate.L2::128B.u32 %0, [%1];" : "=r"(v) : "l"(p));
    return v;
}
__device__ __forceinline__ void bar_sync(int id, int n) { asm volatile("bar.sync %0, %1;" ::"r"(id), "r"(n) : "memory"); }
__device__ __forceinline__ void bar_arrive(int id, int n) { asm volatile("bar.arrive %0, %1;" ::"r"(id), "r"(n) : "memory"); }

constexpr uint64_t EVICT_NORMAL = 0x1000000000000000ull, EVICT_FIRST = 0x12F0000000000000ull;
__device__ __forceinline__ void tma2d(uint32_t dst, const CUtensorMap* m, int c0, int c1, uint32_t bar) {
    asm volatile("cp.async.bulk.tensor.2d.shared::cluster.global.mbarrier::complete_tx::bytes.L2::cache_hint [%0], [%1, {%3, %4}], [%2], %5;"
                 ::"r"(dst), "l"(m), "r"(bar), "r"(c0), "r"(c1), "l"(EVICT_FIRST) : "memory");
}
__device__ __forceinline__ void tma2d_mc(uint32_t dst, const CUtensorMap* m, int c0, int c1, uint32_t bar, uint64_t pol) {
    asm volatile("cp.async.bulk.tensor.2d.shared::cluster.global.mbarrier::complete_tx::bytes.multicast::cluster.L2::cache_hint [%0], [%1, {%3, %4}], [%2], %5, %6;"
                 ::"r"(dst), "l"(m), "r"(bar), "r"(c0), "r"(c1), "h"((uint16_t)3), "l"(pol) : "memory");
}
__device__ __forceinline__ void tma3d(uint32_t dst, const CUtensorMap* m, int c0, int c1, int c2, uint32_t bar) {
    asm volatile("cp.async.bulk.tensor.3d.shared::cluster.global.mbarrier::complete_tx::bytes.L2::cache_hint [%0], [%1, {%3, %4, %5}], [%2], %6;"
                 ::"r"(dst), "l"(m), "r"(bar), "r"(c0), "r"(c1), "r"(c2), "l"(EVICT_FIRST) : "memory");
}
__device__ __forceinline__ void bulk_load(uint32_t dst, const void* src, uint32_t bytes, uint32_t bar) {
    asm volatile("cp.async.bulk.shared::cluster.global.mbarrier::complete_tx::bytes [%0], [%1], %2, [%3];"
                 ::"r"(dst), "l"(src), "r"(bytes), "r"(bar) : "memory");
}
__device__ __forceinline__ void l2_prefetch(const void* src, uint32_t bytes) {
    asm volatile("cp.async.bulk.prefetch.L2.global [%0], %1;" ::"l"(src), "r"(bytes) : "memory");
}
__device__ __forceinline__ uint32_t bmul2(uint32_t a, uint32_t b) { uint32_t r; asm("mul.rn.bf16x2 %0, %1, %2;" : "=r"(r) : "r"(a), "r"(b)); return r; }
__device__ __forceinline__ uint32_t badd2(uint32_t a, uint32_t b) { uint32_t r; asm("add.rn.bf16x2 %0, %1, %2;" : "=r"(r) : "r"(a), "r"(b)); return r; }
__device__ __forceinline__ uint32_t bsub2(uint32_t a, uint32_t b) { uint32_t r; asm("sub.rn.bf16x2 %0, %1, %2;" : "=r"(r) : "r"(a), "r"(b)); return r; }
__device__ __forceinline__ uint32_t bmax2(uint32_t a, uint32_t b) { uint32_t r; asm("max.bf16x2 %0, %1, %2;" : "=r"(r) : "r"(a), "r"(b)); return r; }
__device__ __forceinline__ uint4 lds128(uint32_t a) { uint4 v; asm volatile("ld.shared.v4.u32 {%0,%1,%2,%3}, [%4];" : "=r"(v.x), "=r"(v.y), "=r"(v.z), "=r"(v.w) : "r"(a) : "memory"); return v; }
__device__ __forceinline__ uint2 lds64(uint32_t a) { uint2 v; asm volatile("ld.shared.v2.u32 {%0,%1}, [%2];" : "=r"(v.x), "=r"(v.y) : "r"(a) : "memory"); return v; }
__device__ __forceinline__ uint32_t lds32(uint32_t a) { uint32_t v; asm volatile("ld.shared.u32 %0, [%1];" : "=r"(v) : "r"(a) : "memory"); return v; }
__device__ __forceinline__ uint4 ldsm4(uint32_t a) {
    uint4 v;
    asm volatile("ldmatrix.sync.aligned.m8n8.x4.shared.b16 {%0,%1,%2,%3}, [%4];" : "=r"(v.x), "=r"(v.y), "=r"(v.z), "=r"(v.w) : "r"(a) : "memory");
    return v;
}
__device__ __forceinline__ uint4 ldsm4t(uint32_t a) {
    uint4 v;
    asm volatile("ldmatrix.sync.aligned.m8n8.x4.trans.shared.b16 {%0,%1,%2,%3}, [%4];" : "=r"(v.x), "=r"(v.y), "=r"(v.z), "=r"(v.w) : "r"(a) : "memory");
    return v;
}
__device__ __forceinline__ void mma1688(float* d, uint32_t a0, uint32_t a1, uint32_t b) {
    asm("mma.sync.aligned.m16n8k8.row.col.f32.bf16.bf16.f32 {%0,%1,%2,%3}, {%4,%5}, {%6}, {%0,%1,%2,%3};"
        : "+f"(d[0]), "+f"(d[1]), "+f"(d[2]), "+f"(d[3]) : "r"(a0), "r"(a1), "r"(b));
}
__device__ __forceinline__ void mma16816(float* d, uint32_t a0, uint32_t a1, uint32_t a2, uint32_t a3, uint32_t b0, uint32_t b1) {
    asm("mma.sync.aligned.m16n8k16.row.col.f32.bf16.bf16.f32 {%0,%1,%2,%3}, {%4,%5,%6,%7}, {%8,%9}, {%0,%1,%2,%3};"
                 : "+f"(d[0]), "+f"(d[1]), "+f"(d[2]), "+f"(d[3]) : "r"(a0), "r"(a1), "r"(a2), "r"(a3), "r"(b0), "r"(b1));
}
__device__ __forceinline__ void stsm_x4(uint32_t addr, uint32_t a, uint32_t b, uint32_t c, uint32_t d) {
    asm volatile("stmatrix.sync.aligned.m8n8.x4.shared.b16 [%0], {%1, %2, %3, %4};"
                 ::"r"(addr), "r"(a), "r"(b), "r"(c), "r"(d) : "memory");
}

__device__ __forceinline__ uint64_t mkdesc(uint32_t addr, uint32_t lbo, uint32_t sbo) {
    return (uint64_t)((addr & 0x3FFFF) >> 4) | ((uint64_t)(lbo >> 4) << 16) | ((uint64_t)(sbo >> 4) << 32) | (1ull << 62);
}
constexpr uint32_t SM0 = 1024;
__host__ __device__ constexpr uint32_t desc_lo(uint32_t off, uint32_t lbo) { return ((SM0 + off) >> 4) | ((lbo >> 4) << 16); }
#define WG_FENCE() asm volatile("wgmma.fence.sync.aligned;" ::: "memory")
#define WG_COMMIT() asm volatile("wgmma.commit_group.sync.aligned;" ::: "memory")
#define WG_WAIT(n) asm volatile("wgmma.wait_group.sync.aligned %0;" ::"n"(n) : "memory")

#define F8(a, i) "+f"(a[i]), "+f"(a[i + 1]), "+f"(a[i + 2]), "+f"(a[i + 3]), "+f"(a[i + 4]), "+f"(a[i + 5]), "+f"(a[i + 6]), "+f"(a[i + 7])
#define F16(a, i) F8(a, i), F8(a, i + 8)
#define F64(a) F16(a, 0), F16(a, 16), F16(a, 32), F16(a, 48)
#define F32(a) F16(a, 0), F16(a, 16)
#define L64 "%0,%1,%2,%3,%4,%5,%6,%7,%8,%9,%10,%11,%12,%13,%14,%15,%16,%17,%18,%19,%20,%21,%22,%23,%24,%25,%26,%27,%28,%29,%30,%31,%32,%33,%34,%35,%36,%37,%38,%39,%40,%41,%42,%43,%44,%45,%46,%47,%48,%49,%50,%51,%52,%53,%54,%55,%56,%57,%58,%59,%60,%61,%62,%63"
#define L32 "%0,%1,%2,%3,%4,%5,%6,%7,%8,%9,%10,%11,%12,%13,%14,%15,%16,%17,%18,%19,%20,%21,%22,%23,%24,%25,%26,%27,%28,%29,%30,%31"

template <int TB, int STEP = 128>
__device__ __forceinline__ void mma_rs128(float (&d)[64], uint32_t a0, uint32_t a1, uint32_t a2, uint32_t a3, uint64_t& b, int acc) {
    asm volatile("{\n.reg .pred p;\nsetp.ne.b32 p, %69, 0;\n"
                 "wgmma.mma_async.sync.aligned.m64n128k16.f32.bf16.bf16 {" L64 "}, {%65,%66,%67,%68}, %64, p, 1, 1, %70;\nadd.s64 %64, %64, %71;\n}"
                 : F64(d), "+l"(b) : "r"(a0), "r"(a1), "r"(a2), "r"(a3), "r"(acc), "n"(TB), "n"(STEP));
}
template <int TB>
__device__ __forceinline__ void mma_rs64(float (&d)[32], uint32_t a0, uint32_t a1, uint32_t a2, uint32_t a3, uint64_t& b, int acc) {
    asm volatile("{\n.reg .pred p;\nsetp.ne.b32 p, %37, 0;\n"
                 "wgmma.mma_async.sync.aligned.m64n64k16.f32.bf16.bf16 {" L32 "}, {%33,%34,%35,%36}, %32, p, 1, 1, %38;\nadd.s64 %32, %32, 128;\n}"
                 : F32(d), "+l"(b) : "r"(a0), "r"(a1), "r"(a2), "r"(a3), "r"(acc), "n"(TB));
}
template <int N>
__device__ __forceinline__ void fence_regs(float (&d)[N]) {
#pragma unroll
    for (int i = 0; i < N; i++) asm volatile("" : "+f"(d[i])::"memory");
}
template <int N>
__device__ __forceinline__ void fence_regs(uint32_t (&d)[N]) {
#pragma unroll
    for (int i = 0; i < N; i++) asm volatile("" : "+r"(d[i])::"memory");
}

template <int V> struct IC { static constexpr int value = V; };

constexpr int SLOT = 32768, UNIT = 16384;
constexpr int SM_Q = 4 * SLOT;
constexpr int SM_BAR = 7 * SLOT;
constexpr int SM_RED = SM_BAR + 512;
constexpr int SM_TOTAL = SM_BAR + 3072;
constexpr int XP = D_ * 2 + 16;
constexpr int M_MOD = 16 * XP;
constexpr int SM_T = SM_Q + 2 * D_ * 80, SM_TC = SM_T + D_ * 4, SM_TG = SM_TC + D_ * 4, SM_TS = SM_TG + D_ * 2;
constexpr float CS = 0.08838834764831845f * 1.4426950408889634f;
#define USE_SPARE 1
constexpr float POFF = 102.f, LMIN = 0x1p-104f;
#define LMAX 0.5f
constexpr int SPLIT = 10;
constexpr int STAGE = 11;
constexpr int ESPLIT = 3;
constexpr int QSPLIT = 4, OSPLIT = 6;
constexpr int WF0 = 3, WF1 = 13, WF2 = 19, DL = 9;
constexpr int PF_KV = 8;
constexpr int PF_WO = 50, PF_O = 60;

__device__ __forceinline__ int cluster_role() {
    int k;
    asm volatile("mov.u32 %0, %%ctaid.x;" : "=r"(k));
    const int c = (k & 1) << 6;
    k >>= 1;
    const int r = ((k - 36) * 37) >> 8, i = k - 36 - r * 7;
    return c + (k < 4 ? 12 + k : k < 36 ? ((k - 4) & 7) * 8 + ((k - 4) >> 3) : (i + (i > 0)) * 8 + ((4 + r) & 7));
}

struct Args {
    const bf16 *w_mod, *cvec;
    Scratch* gs;
    uint64_t d0;
    bf16* out;
    const bf16 *x, *kc, *vc, *wq, *wo, *w_r, *w_down;
};

__device__ __forceinline__ void frag_store(uint8_t* p, const uint32_t (&a)[32]) {
#pragma unroll
    for (int i = 0; i < 8; i++)
        __stcg(reinterpret_cast<uint4*>(p + i * 512), make_uint4(a[4 * i], a[4 * i + 1], a[4 * i + 2], a[4 * i + 3]));
}
template <int LO = 0, int HI = 8>
__device__ __forceinline__ void frag_load(uint32_t (&a)[32], const uint8_t* p) {
#pragma unroll
    for (int i = LO; i < HI; i++) {
        const uint4 v = ld_relaxed(reinterpret_cast<const uint4*>(p + i * 512));
        a[4 * i] = v.x; a[4 * i + 1] = v.y; a[4 * i + 2] = v.z; a[4 * i + 3] = v.w;
    }
}
__device__ __forceinline__ float quad_sum(float v) {
    v += __shfl_xor_sync(0xffffffffu, v, 1);
    return v + __shfl_xor_sync(0xffffffffu, v, 2);
}
__device__ __forceinline__ float quad_max(float v) {
    v = fmaxf(v, __shfl_xor_sync(0xffffffffu, v, 1));
    return fmaxf(v, __shfl_xor_sync(0xffffffffu, v, 2));
}
__device__ __forceinline__ float rcp_fast(float x) { float y; asm("rcp.approx.ftz.f32 %0, %1;" : "=f"(y) : "f"(x)); return y; }
__device__ __forceinline__ float sigmoidf_(float x) { return rcp_fast(1.f + ex2(-1.4426950408889634f * x)); }
__device__ __forceinline__ void top2(uint32_t k, uint32_t& k1, uint32_t& k2) {
    k1 = __reduce_max_sync(0xffffffffu, k);
    k2 = __reduce_max_sync(0xffffffffu, k == k1 ? 0 : k);
}

__device__ __forceinline__ void mod_fma(float (&a)[8], const uint4 w, float sc) {
    a[0] += sc * bf_lo(w.x); a[1] += sc * bf_hi(w.x); a[2] += sc * bf_lo(w.y); a[3] += sc * bf_hi(w.y);
    a[4] += sc * bf_lo(w.z); a[5] += sc * bf_hi(w.z); a[6] += sc * bf_lo(w.w); a[7] += sc * bf_hi(w.w);
}
__device__ __forceinline__ float mod_reduce(float (&a)[8], int lane) {
#pragma unroll
    for (int h = 4; h > 0; h >>= 1) {
        const bool up = lane & (8 / h);
#pragma unroll
        for (int i = 0; i < h; i++)
            a[i] = (up ? a[i + h] : a[i]) + __shfl_xor_sync(0xffffffffu, up ? a[i] : a[i + h], 8 / h);
    }
    return a[0] + __shfl_xor_sync(0xffffffffu, a[0], 16);
}

__device__ __forceinline__ float ln_stats(float sum, float sq, uint32_t& mean2) {
    const float mean = sum * (1.f / D_);
    const float var = fmaxf(fmaf(-mean, mean, sq * (1.f / D_)), 0.f);
    float sd;
    asm("sqrt.approx.ftz.f32 %0, %1;" : "=f"(sd) : "f"(rbf(rbf(var) + 1e-5f)));
    mean2 = pack_bf16(mean, mean);
    return rcp_fast(rbf(sd));
}
__device__ __forceinline__ uint32_t ln_pair(uint32_t x, uint32_t mean2, float rsd) {
    const uint32_t d = bsub2(x, mean2);
    return pack_bf16(bf_lo(d) * rsd, bf_hi(d) * rsd);
}
__device__ __forceinline__ void rows_load(uint32_t (&x)[20], uint32_t xs, int cw) {
#pragma unroll
    for (int ch = 0; ch < 5; ch++) {
        const uint4 v = ldsm4(ch < 4 ? xs + ch * 256 : xs + 1024 - cw * 16);
        x[4 * ch] = v.x; x[4 * ch + 1] = v.y; x[4 * ch + 2] = v.z; x[4 * ch + 3] = v.w;
    }
}
__device__ __forceinline__ void stats_add(float (&st)[12], uint32_t a, uint32_t b, uint32_t w) {
    mma1688(st, a, b, w);
    mma1688(st + 4, a, b, a);
    mma1688(st + 8, a, b, b);
}
__device__ __forceinline__ float rows_stats(const float (&st)[12], float4* rec, int cw, int lane, uint32_t& mean2, float& dot) {
    const int g8 = lane >> 2;
    if ((g8 >> 1) == (lane & 3)) {
        rec[cw * 16 + g8] = make_float4(st[0], (g8 & 1) ? st[5] : st[4], st[1], 0.f);
        rec[cw * 16 + 8 + g8] = make_float4(st[2], (g8 & 1) ? st[11] : st[10], st[3], 0.f);
    }
    bar_sync(3, 256);
    const float4* r = rec + (lane >> 4) * 64 + (lane & 15);
    const float4 s0 = r[0], s1 = r[16], s2 = r[32], s3 = r[48];
    const float sum = (s0.x + s1.x) + (s2.x + s3.x), sq = (s0.y + s1.y) + (s2.y + s3.y);
    dot = (s0.z + s1.z) + (s2.z + s3.z);
    dot += __shfl_xor_sync(0xffffffffu, dot, 16);
    return ln_stats(sum + __shfl_xor_sync(0xffffffffu, sum, 16), sq + __shfl_xor_sync(0xffffffffu, sq, 16), mean2);
}
template <class F>
__device__ __forceinline__ void rows_normalise(uint32_t* y, const uint32_t* x, uint32_t mean2, float rsd, int lane, F loads) {
    const int g8 = lane >> 2;
    const uint32_t ma2 = __shfl_sync(0xffffffffu, mean2, g8), mb2 = __shfl_sync(0xffffffffu, mean2, g8 + 8);
    const float ra = __shfl_sync(0xffffffffu, rsd, g8), rb = __shfl_sync(0xffffffffu, rsd, g8 + 8);
    loads();
#pragma unroll
    for (int k = 0; k < 9; k++) { y[2 * k] = ln_pair(x[2 * k], ma2, ra); y[2 * k + 1] = ln_pair(x[2 * k + 1], mb2, rb); }
}

__device__ __forceinline__ uint4 h_frag(const uint4* hf, int ks, int lane) {
    if (ks < 32) return ld_relaxed2(hf + ks * 32);
    const uint2* p = reinterpret_cast<const uint2*>(padd(hf, 256 - lane * 8) + ks * 32 - 16);
    const uint2 a = ld_relaxed64(p), b = ld_relaxed64(p + 32);
    return make_uint4(a.x, a.y, b.x, b.y);
}

__device__ __noinline__ void attn_fallback(uint32_t bad, uint32_t tag, const Scratch* gs, uint8_t* frag, uint8_t* keep, const bf16* wq, const bf16* kc, const bf16* vc) {
  const int lane = threadIdx.x & 31, g8 = lane >> 2, qd = lane & 3;
  const int role = cluster_role(), j = role & 7, qb = (role >> 2 & 14) + (role >> 6);
  const uint4* hf = g_h + (size_t)(qb * 8 + (threadIdx.x >> 5) - 4) * (36 * 32) + lane;
#pragma unroll 1
  for (int t = 0; t < 4; t++) {
    if (!((bad >> t) & 1)) continue;
    const bf16 *wqp = wq + (4 * j + t) * DH, *kp = kc + (size_t)(2 * j + (t >> 1)) * S_ * DH, *vp = vc + (size_t)(2 * j + (t >> 1)) * S_ * DH;
    uint32_t q[32];
    float o[64];
#pragma unroll
    for (int i = 0; i < 64; i++) o[i] = 0.f;
#pragma unroll 1
    for (int ks = 0; ks < 36; ks++) {
        const uint4 a = h_frag(hf, ks, lane);
        const unsigned short* wr = reinterpret_cast<const unsigned short*>(wqp + (size_t)(ks * 16 + 2 * qd) * QD + g8);
#pragma unroll
        for (int dt = 0; dt < 16; dt++) {
            const uint32_t b0 = __ldg(wr + dt * 8) | ((uint32_t)__ldg(wr + dt * 8 + QD) << 16);
            const uint32_t b1 = __ldg(wr + dt * 8 + 8 * QD) | ((uint32_t)__ldg(wr + dt * 8 + 9 * QD) << 16);
            mma16816(o + 4 * dt, a.x, a.y, a.z, a.w, b0, b1);
        }
    }
#pragma unroll
    for (int i = 0; i < 32; i++) q[i] = pack_bf16(o[2 * i], o[2 * i + 1]);
#pragma unroll
    for (int i = 0; i < 64; i++) o[i] = 0.f;
    float m0 = -INFINITY, m1 = -INFINITY, l0 = 0.f, l1 = 0.f;
#pragma unroll 1
    for (int key = 0; key < S_; key += 16) {
        float sc[8];
#pragma unroll
        for (int i = 0; i < 8; i++) sc[i] = 0.f;
#pragma unroll
        for (int nt = 0; nt < 2; nt++) {
            const uint32_t* kr = reinterpret_cast<const uint32_t*>(kp + (size_t)(key + nt * 8 + g8) * DH) + qd;
#pragma unroll
            for (int ks = 0; ks < 8; ks++)
                mma16816(sc + 4 * nt, q[4 * ks], q[4 * ks + 1], q[4 * ks + 2], q[4 * ks + 3], __ldg(kr + ks * 8), __ldg(kr + ks * 8 + 4));
        }
        const float n0 = quad_max(fmaxf(fmaxf(m0, fmaxf(sc[0], sc[1])), fmaxf(sc[4], sc[5])));
        const float n1 = quad_max(fmaxf(fmaxf(m1, fmaxf(sc[2], sc[3])), fmaxf(sc[6], sc[7])));
        const float f0 = ex2((m0 - n0) * CS), f1 = ex2((m1 - n1) * CS);
        m0 = n0; m1 = n1;
#pragma unroll
        for (int i = 0; i < 8; i++) sc[i] = ex2((sc[i] - ((i & 2) ? n1 : n0)) * CS);
        l0 = l0 * f0 + (sc[0] + sc[1]) + (sc[4] + sc[5]);
        l1 = l1 * f1 + (sc[2] + sc[3]) + (sc[6] + sc[7]);
        const uint32_t e0 = pack_bf16(sc[0], sc[1]), e1 = pack_bf16(sc[2], sc[3]), e2 = pack_bf16(sc[4], sc[5]), e3 = pack_bf16(sc[6], sc[7]);
        const unsigned short* vr = reinterpret_cast<const unsigned short*>(vp + (size_t)(key + 2 * qd) * DH + g8);
#pragma unroll
        for (int dt = 0; dt < 16; dt++) {
            o[4 * dt] *= f0; o[4 * dt + 1] *= f0; o[4 * dt + 2] *= f1; o[4 * dt + 3] *= f1;
            const uint32_t b0 = __ldg(vr + dt * 8) | ((uint32_t)__ldg(vr + dt * 8 + DH) << 16);
            const uint32_t b1 = __ldg(vr + dt * 8 + 8 * DH) | ((uint32_t)__ldg(vr + dt * 8 + 9 * DH) << 16);
            mma16816(o + 4 * dt, e0, e1, e2, e3, b0, b1);
        }
    }
    const float i0 = 1.f / quad_sum(l0), i1 = 1.f / quad_sum(l1);
#pragma unroll
    for (int i = 0; i < 16; i++) {
        q[2 * i] = pack_bf16(o[4 * i] * i0, o[4 * i + 1] * i0);
        q[2 * i + 1] = pack_bf16(o[4 * i + 2] * i1, o[4 * i + 3] * i1);
    }
    frag_store(t < 3 ? frag + t * 4096 : keep, q);
  }
}

__device__ __forceinline__ void spare_q3(Scratch* gs, uint32_t sb, uint32_t bar_full, uint32_t bar_empty, int lane, int cw) {
    const uint32_t tag = load_tag(gs);
    uint32_t rel_base, e = 3;
    asm("mapa.shared::cluster.u32 %0, %1, %2;" : "=r"(rel_base) : "r"(bar_empty), "r"(lane & 1));
#pragma unroll 1
    for (int qb = blockIdx.x - NCTA; qb < 16; qb += 4) {
        uint32_t h[144];
        float o[64];
        flag_wait(&g_flag_h[(qb * 8 + cw) * 32], tag);
        const uint4* hf = g_h + (size_t)(qb * 8 + cw) * (36 * 32) + lane;
#pragma unroll
        for (int ks = 0; ks < 36; ks++) {
            const uint4 v = h_frag(hf, ks, lane);
            h[4 * ks] = v.x; h[4 * ks + 1] = v.y; h[4 * ks + 2] = v.z; h[4 * ks + 3] = v.w;
        }
#pragma unroll
        for (int i = 0; i < 64; i++) o[i] = 0.f;
#pragma unroll 1
        for (int v = 0; v < 4; v++) {
            fence_regs(o);
#pragma unroll
            for (int t = 0; t < 5; t++) {
                mbar_wait(bar_full + 8 * (e & 3), (e >> 2) & 1);
                uint64_t dv = mkdesc(sb + (e & 3) * SLOT, UNIT, 1024);
                WG_FENCE();
#pragma unroll
                for (int ks = 0; ks < (t < 4 ? 8 : 4); ks++)
                    mma_rs128<1>(o, h[32 * t + 4 * ks], h[32 * t + 4 * ks + 1], h[32 * t + 4 * ks + 2], h[32 * t + 4 * ks + 3], dv, ks | t);
                WG_COMMIT();
                if (t > 0) { WG_WAIT(1); if (lane < 2) mbar_arrive_cluster(rel_base + 8 * ((e - 1) & 3)); }
                e++;
            }
            WG_WAIT(0);
            fence_regs(o);
            if (lane < 2) mbar_arrive_cluster(rel_base + 8 * ((e - 1) & 3));
            uint4* dst = &g_q3[((qb * 8 + 2 * v) * 8 + cw) * 128 + lane];
#pragma unroll
            for (int i = 0; i < 8; i++)
                __stcg(dst + (i >> 2) * 1024 + (i & 3) * 32, make_uint4(pack_bf16(o[8 * i], o[8 * i + 1]), pack_bf16(o[8 * i + 2], o[8 * i + 3]),
                                                                        pack_bf16(o[8 * i + 4], o[8 * i + 5]), pack_bf16(o[8 * i + 6], o[8 * i + 7])));
        }
        bar_sync(3, 256);
        if (cw == 0 && lane == 0) flag_release(&g_flag_q3[qb * 32], tag);
        __syncwarp();
    }
}

template <bool SPARE>
__global__ void __cluster_dims__(2, 1, 1) __launch_bounds__(384, 1)
fused_kernel(const Args args, const __grid_constant__ CUtensorMap tm_wq,
             const __grid_constant__ CUtensorMap tm_k, const __grid_constant__ CUtensorMap tm_v,
             const __grid_constant__ CUtensorMap tm_wo, const __grid_constant__ CUtensorMap tm_p,
             const __grid_constant__ CUtensorMap tm_x, const __grid_constant__ CUtensorMap tm_d,
             const __grid_constant__ CUtensorMap tm_g, const __grid_constant__ CUtensorMap tm_u) {
    extern __shared__ __align__(1024) uint8_t smem_raw[];
    const uint32_t sb = smem_u32(smem_raw);
    Scratch* const gs = args.gs;
    const uint32_t bar_full = sb + SM_BAR;
    const uint32_t bar_g = bar_full + 8 * 4;
    const uint32_t bar_mod = bar_g + 8;
    const uint32_t bar_go = bar_mod + 8;
    const uint32_t bar_x = bar_go + 40;
    const uint32_t bar_empty = bar_x + 8;
    const uint32_t bar_pub = bar_empty + 8 * 4;
    const uint32_t bar_qfree = bar_pub + 32;
    const uint32_t bar_out = bar_qfree + 24;
    const uint32_t bar_q3 = bar_out + 8;
    const uint32_t bar_pre = bar_q3 + 16;
    const uint32_t bar_w0 = bar_q3 + 8;
    constexpr int E0 = SPARE ? 2 : 0;

#define ROLES() const int role = cluster_role(), c = role >> 6, j = role & 7, qb = (role >> 2 & 14) + c, rg = qb * 8 + j; uint32_t bx; asm volatile("mov.u32 %0, %%ctaid.x;" : "=r"(bx))
    const int warp = __shfl_sync(0xffffffffu, threadIdx.x >> 5, 0);

    if (SPARE && blockIdx.x >= NCTA && warp >= 4) {
        asm volatile("barrier.cluster.arrive.relaxed.aligned;" ::: "memory");
        asm volatile("setmaxnreg.inc.sync.aligned.u32 240;");
        asm volatile("barrier.cluster.wait.aligned;" ::: "memory");
        spare_q3(gs, sb, bar_full, bar_empty, threadIdx.x & 31, warp - 4);
        asm volatile("barrier.cluster.arrive.relaxed.aligned;\nbarrier.cluster.wait.aligned;" ::: "memory");
    } else if (warp < 4) {
        asm volatile("setmaxnreg.dec.sync.aligned.u32 24;");
        ROLES();
        int lane;
        asm volatile("mov.u32 %0, %%laneid;" : "=r"(lane));
        if (warp == 2 && elect()) {
            asm volatile("prefetch.tensormap [%0];" ::"l"(&tm_x) : "memory");
#pragma unroll
            for (int i = 0; i < 27; i++) mbar_init(bar_full + 8 * i, i < 12 || i >= 23 ? 1 : i < 16 ? 16 : 8);
#pragma unroll
            for (int i = 0; i <= E0; i++) {
                mbar_arrive(bar_full + 8 * i);
                asm volatile("mbarrier.arrive.shared::cta.b64 _, [%0], 16;" ::"r"(bar_empty + 8 * i) : "memory");
            }
            asm volatile("fence.mbarrier_init.release.cluster;" ::: "memory");
        }
        __syncwarp();
        asm volatile("barrier.cluster.arrive.relaxed.aligned;" ::: "memory");
        if (warp == 2 && !(SPARE && bx >= NCTA)) {
            __nanosleep(200);
            if (elect()) {
                mbar_expect_tx(bar_x, 16 * XP);
                tma2d(sb + SM_Q, &tm_x, 0, rg * 16, bar_x);
            }
            __syncwarp();
        }
        asm volatile("barrier.cluster.wait.aligned;" ::: "memory");
        const uint32_t tag = load_tag(gs);
        if (SPARE && bx >= NCTA) {
            if (warp == 1) {
#pragma unroll 1
                for (int e = 3; e < 83; e++) {
                    const int v = (e - 3) / 5;
                    mbar_wait_sleep(bar_empty + 8 * (e & 3), ~(e >> 2) & 1);
                    if (elect()) {
                        mbar_expect_tx(bar_full + 8 * (e & 3), SLOT);
                        tma2d_mc(sb + (e & 3) * SLOT + c * UNIT, &tm_wq, (8 * (v & 3) + 4 * c + 3) * DH + 64, (e - 3 - v * 5) * 128,
                                 bar_full + 8 * (e & 3), EVICT_NORMAL);
                    }
                }
            }
            __syncwarp();
            asm volatile("barrier.cluster.arrive.relaxed.aligned;\nbarrier.cluster.wait.aligned;" ::: "memory");
            return;
        }
        if (warp == 3) {
#pragma unroll 1
            for (int e = 4; e < 20; e++) {
                __nanosleep(e == 4 ? 2000 : 400);
                const int hd = (e * 52) >> 8, row = (e - hd * 5) * 128 + qb * 8 + (lane >> 1);
                if (lane < 16 && row < D_)
                    asm volatile("prefetch.global.L2 [%0];" ::"l"(padd(args.wq, (row * QD + (4 * j + ((0x1320 >> (4 * hd)) & 3)) * DH + (lane & 1) * 64) * 2)) : "memory");
            }
            __syncwarp();
            mbar_wait_sleep(bar_go, 0);
            __nanosleep(2000);
#pragma unroll 1
            for (int unit = 72 + bx; unit < 216; unit += NCTA) {
                float a[8];
#pragma unroll
                for (int i = 0; i < 8; i++) a[i] = 0.f;
#pragma unroll 1
                for (int k = lane >> 1; k < D_; k += 16) {
                    const float cv = __bfloat162float(*padd(args.cvec, k * 2));
                    mod_fma(a, __ldg(reinterpret_cast<const uint4*>(padd(args.w_mod, (k * (6 * D_) + unit * 16 + (lane & 1) * 8) * 2))), rbf(cv * sigmoidf_(cv)));
                }
                const float v = mod_reduce(a, lane), v1 = __shfl_down_sync(0xffffffffu, v, 8);
                if (lane < 8) *padd(gs->mod2, ((unit - 72) * 8 + (lane & 1) * 4 + (lane & 2) + (lane >> 2)) * 4) = pack_bf16(v, v1);
            }
            __syncwarp();
            if (lane == 0) flag_release(padd(g_flag_mod, bx * 4), tag);
#pragma unroll 1
            for (int k = 0; k < 36; k++) {
                __nanosleep(200);
                __stcg(padd(gs->h[0], (~tag & 1) * (NCTA * 36 * 512) + ((rg * 36 + k) * 32 + lane) * 16), make_uint4(0, 0, 0, 0));
            }
            __syncwarp();
            mbar_wait_sleep(bar_qfree + 16, 0);
            __nanosleep(2000);
            {
                uint4 v;
                uint32_t it = 0;
#pragma unroll 1
                do {
                    v = ld_relaxed(reinterpret_cast<const uint4*>(padd(g_flag_mod, lane * 16)));
                } while (((v.x ^ tag) | (v.y ^ tag) | (v.z ^ tag) | (v.w ^ tag)) && ++it < SPIN / 16);
                asm volatile("fence.acquire.gpu;" ::: "memory");
            }
            __syncwarp();
            {
                float w1 = 0.f, w2 = 0.f;
#pragma unroll 1
                for (int k = lane; k < D_ / 2; k += 32) {
                    const uint32_t* mp = padd(gs->mod2, k * 4);
                    const uint32_t sv = __ldcg(mp + D_ / 2), c1 = badd2(__ldcg(mp + D_), 0x3f803f80u);
                    const uint32_t wr = *reinterpret_cast<const uint32_t*>(padd(args.w_r, k * 4)), wp = bmul2(c1, wr);
                    reinterpret_cast<uint2*>(smem_raw + SM_T)[k] = make_uint2(__ldcg(mp), wp);
                    reinterpret_cast<uint2*>(smem_raw + SM_TC)[k] = make_uint2(c1, sv);
                    reinterpret_cast<uint32_t*>(smem_raw + SM_TG)[k] = __ldcg(mp + 3 * D_ / 2);
                    w1 += bf_lo(wp) + bf_hi(wp);
                    w2 += bf_lo(sv) * bf_lo(wr) + bf_hi(sv) * bf_hi(wr);
                }
#pragma unroll 1
                for (int i = 1; i < 32; i <<= 1) { w1 += __shfl_xor_sync(0xffffffffu, w1, i); w2 += __shfl_xor_sync(0xffffffffu, w2, i); }
                *reinterpret_cast<float2*>(smem_raw + SM_TS) = make_float2(w1, w2);
            }
#pragma unroll
            for (int i = 0; i < 4; i++) reinterpret_cast<uint4*>(smem_raw + SM_RED)[lane + 32 * i] = make_uint4(~0u, ~0u, ~0u, ~0u);
            asm volatile("fence.proxy.async.shared::cta;" ::: "memory");
            __syncwarp();
            if (elect()) {
                uint8_t* mb = g_frag + (size_t)rg * 8 * WREG + 3 * 4096;
#pragma unroll 1
                for (int k = 0; k < 8; k++, mb += WREG) {
#pragma unroll
                    for (int i = 0; i < 3; i++)
                        asm volatile("cp.async.bulk.global.shared::cta.bulk_group [%0], [%1], 2048;" ::"l"(mb + i * 2048), "r"(sb + SM_RED) : "memory");
                    __nanosleep(500);
                }
                asm volatile("cp.async.bulk.commit_group;\ncp.async.bulk.wait_group 0;\nfence.proxy.async.global;" ::: "memory");
            }
            __syncwarp();
            if (lane == 0) mbar_arrive(bar_mod);
            __syncwarp();
            mbar_wait_sleep(bar_go + 8, 0);
            if (elect()) asm volatile("prefetch.tensormap [%0];\nprefetch.tensormap [%1];\nprefetch.tensormap [%2];" ::"l"(&tm_x), "l"(&tm_p), "l"(&tm_d) : "memory");
            __syncwarp();
            *padd(g_flag_part, qb * 1024 + (lane >> 3) * 256 + j * 32 + (lane & 7) * 4) = 0;
            __syncwarp();
#pragma unroll 1
            for (int i = 1; i < 4; i++) {
                mbar_wait(bar_pub + 8 * i, 0);
                unsigned int* flags = padd(g_flag_part, qb * 1024 + (i - 1) * 256);
                if (elect()) { flag_release(padd(flags, j * 32), tag); DBG_PG(93); }
                __syncwarp();
                const uint32_t slot = (i + 2) & 3;
                flag_wait(padd(flags, (lane & 7) * 32), tag);
                asm volatile("fence.proxy.async.global;" ::: "memory");
                if (lane == 0 && i == 3) DBG_PG(101);
                mbar_wait(bar_go + 8 + 8 * i, 0);
                mbar_wait(bar_empty + 8 * slot, i == 3);
                if (elect()) {
                    mbar_expect_tx(bar_full + 8 * slot, SLOT);
                    tma3d(sb + slot * SLOT, &tm_p, 0, j * 20 + (i - 1) * 4, qb * 8, bar_full + 8 * slot);
                    tma3d(sb + slot * SLOT + UNIT, &tm_p, 0, j * 20 + (i - 1) * 4 + 2, qb * 8, bar_full + 8 * slot);
                }
            }
        } else if (warp == 0) {
#pragma unroll 1
            for (int i = 0; i < 48; i++) {
                if (SPARE && i == 34) {
                    flag_wait(&g_flag_q3[qb * 32], tag);
                    if (elect()) {
                        asm volatile("fence.proxy.async.global;" ::: "memory");
                        mbar_expect_tx(bar_q3, UNIT);
#pragma unroll 1
                        for (int k = 0; k < 8; k++) bulk_load(sb + SM_Q + 2 * SLOT + k * 4096 + 2048, &g_q3[(rg * 8 + k) * 128], 2048, bar_q3);
                    }
                }
                if (i == 0 || i == 17 || i == 34) { mbar_wait_sleep(bar_qfree + (i >> 4) * 8, 0); __nanosleep(2000); }
                __nanosleep(500);
                if (elect()) {
                    asm volatile("mbarrier.expect_tx.shared::cta.b64 [%0], %1;" ::"r"(bar_g), "n"(1920) : "memory");
                    tma2d(sb + SM_Q + i * 1920, i < 24 ? &tm_g : &tm_u, (bx * 36) & ~7, (i < 24 ? i : i - 24) * 24, bar_g);
                }
            }
            if (elect()) mbar_arrive(bar_g);
#pragma unroll 1
            for (int i = 0; i < 18; i++) {
                __nanosleep(400);
                if (elect()) l2_prefetch(args.w_down + (size_t)(bx * 36 + i * 2) * D_, 4 * D_);
            }
            __syncwarp();
            mbar_wait_sleep(bar_go + 8 * 2, 0);
            uint32_t acc = 0;
#pragma unroll 1
            for (int k = lane; k < 16 * 9; k += 32) acc |= touch(padd(args.x, (rg * 16 * D_ + k * 64) * 2));
            if (acc == 0) reinterpret_cast<volatile uint32_t*>(smem_raw + SM_BAR)[127] = acc;
            __syncwarp();
            mbar_wait_sleep(bar_go + 8 * 4, 0);
            *reinterpret_cast<uint2*>(padd(g_cand, ((lane >> 2) * NCTA + rg) * 32 + (lane & 3) * 8)) = make_uint2(0, 0);
            uint4* rp = padd(g_rows, (rg * 2 * RSLOT + lane) * 16);
#pragma unroll
            for (int k = 0; k < 12; k++) rp[k * 32] = make_uint4(~0u, ~0u, ~0u, ~0u);
            if (bx < 72) {
                uint4* yp = reinterpret_cast<uint4*>(padd(g_ypart, bx * NCTA * 64 + lane * 16));
#pragma unroll
                for (int k = 0; k < 16; k++) yp[k * 32] = make_uint4(~0u, ~0u, ~0u, ~0u);
            }
            asm volatile("fence.acq_rel.gpu;" ::: "memory");
            __syncwarp();
            if (lane == 0) mbar_arrive(bar_pre);
        } else if (warp == 1) {
            __nanosleep(100);
            auto put = [&](uint32_t fb, uint32_t slot, const CUtensorMap* tm, int c0, int c1, uint64_t pol) {
                if (elect()) {
                    mbar_expect_tx(fb, SLOT);
                    tma2d_mc(sb + slot * SLOT + c * UNIT, tm, c0, c1, fb, pol);
                }
            };
            auto prefetch_kv = [&](int n) {
                if (elect()) {
                    const size_t off = (size_t)((2 * j + (n >> 5)) * S_ + (n & 15) * 128) * DH + qb * 1024;
                    l2_prefetch(args.kc + off, 2048);
                    l2_prefetch(args.vc + off, 2048);
                }
            };
            put(bar_w0, 6, &tm_wq, 4 * j * DH + c * 64, -64, EVICT_FIRST);
#pragma unroll 1
            for (int e = E0 + 1; e < 19; e++) {
                const int i = SPARE && e < 12 ? e - 2 : e, hd = (i * 52) >> 8;
                const bool half = SPARE && hd == 2;
                const int c0 = (4 * j + ((0x1320 >> (4 * hd)) & 3)) * DH + (half ? 0 : c * 64);
                const int c1 = half ? (2 * (e - 12) + c) * 128 : (i - hd * 5) * 128 - 64;
                if (e < E0 + 5) __nanosleep(300);
                mbar_wait(bar_empty + 8 * (e & 3), ~(e >> 2) & 1);
                put(bar_full + 8 * (e & 3), e & 3, &tm_wq, c0, c1, EVICT_FIRST);
                if (e >= PF_KV && !(e & 1)) prefetch_kv((e - PF_KV) >> 1);
            }
            mbar_wait(bar_empty + 24, 1);
            put(bar_full + 24, 3, &tm_k, c * 64, 2 * j * S_, EVICT_NORMAL);
            mbar_wait(bar_empty, 0);
            put(bar_full, 0, &tm_wq, (4 * j + 1) * DH + c * 64, 448, EVICT_FIRST);
            prefetch_kv((20 - PF_KV) >> 1);
            if (elect()) mbar_arrive(bar_go);
#pragma unroll 1
            for (int n = 1; n < 64; n++) {
                const uint32_t sv = (n & 1) * 2, sk = sv ^ 3;
                const int m = n - 1;
                mbar_wait_sleep(bar_empty + 8 * sk, ~((n + 9) >> 1) & 1);
                put(bar_full + 8 * sk, sk, &tm_k, c * 64, (2 * j + (n >> 5)) * S_ + (n & 15) * 128, (n & 16) ? EVICT_FIRST : EVICT_NORMAL);
                mbar_wait_sleep(bar_empty + 8 * sv, (n >> 1) & 1);
                put(bar_full + 8 * sv, sv, &tm_v, c * 64, (2 * j + (m >> 5)) * S_ + (m & 15) * 128, (m & 16) ? EVICT_FIRST : EVICT_NORMAL);
                const int pn = n + ((20 - PF_KV) >> 1);
                if (!(pn & 80)) prefetch_kv(pn);
                if (n >= PF_WO) {
                    if (elect()) {
                        if (n < PF_WO + 9) l2_prefetch(args.wo + (size_t)bx * (QD * D_ / NCTA) + (n - PF_WO) * 2048, 4096);
                        if (n >= PF_O) {
                            l2_prefetch(g_frag + (size_t)(rg * 8 + 2 * (n - PF_O)) * WREG, 4096);
                            l2_prefetch(g_frag + (size_t)(rg * 8 + 2 * (n - PF_O) + 1) * WREG, 4096);
                        }
                    }
                }
            }
            mbar_wait_sleep(bar_empty + 24, 1);
            put(bar_full + 24, 3, &tm_v, c * 64, (2 * j + 1) * S_ + 15 * 128, EVICT_FIRST);
#pragma unroll 1
            for (int i = 0; i < 18; i++) {
                const int e = 148 + i + (i > 10) + (i > 14);
                mbar_wait_sleep(bar_empty + 8 * (e & 3), ~(e >> 2) & 1);
                put(bar_full + 8 * (e & 3), e & 3, &tm_wo, (i >> 1) * 64, (4 * j + ((i & 1) ? 1 + c : 3 * c)) * DH, EVICT_FIRST);
                arrive_if(bar_go + 2 + 2 * i, elect() && (i & 3) == 3);
            }
            asm volatile("fence.proxy.async.global;" ::: "memory");
            mbar_wait(bar_empty, 1);
            if (elect()) {
                mbar_expect_tx(bar_full, 16 * XP);
                tma2d(sb, &tm_x, 0, rg * 16, bar_full);
            }
            mbar_wait(bar_empty + 16, 1);
            if (elect()) {
                mbar_expect_tx(bar_full + 16, SLOT);
                tma3d(sb + 2 * SLOT, &tm_p, 0, j * 20 + 12, qb * 8, bar_full + 16);
                tma3d(sb + 2 * SLOT + UNIT, &tm_p, 0, j * 20 + 14, qb * 8, bar_full + 16);
            }
            mbar_wait(bar_empty + 24, 1);
            __nanosleep(300);
            if (elect()) {
                mbar_expect_tx(bar_full + 24, UNIT);
                tma3d(sb + 3 * SLOT, &tm_p, 0, j * 20 + 16, qb * 8, bar_full + 24);
            }
            mbar_wait(bar_empty + 8, 0);
            mbar_wait(bar_empty + 16, 0);
            __nanosleep(300);
            if (elect()) {
#pragma unroll
                for (int i = 1; i < 3; i++) {
                    mbar_expect_tx(bar_full + 8 * i, 18 * XP);
                    tma2d(sb + i * SLOT, &tm_d, 0, bx * 36 + (i - 1) * 18, bar_full + 8 * i);
                }
            }
        } else {
            if (elect()) asm volatile("prefetch.tensormap [%0];\nprefetch.tensormap [%1];\nprefetch.tensormap [%2];" ::"l"(&tm_k), "l"(&tm_v), "l"(&tm_wo) : "memory");
            if (SPARE) {
                mbar_wait_sleep(bar_pub, 0);
                if (lane == 0) flag_release(padd(g_flag_h, rg * 128), tag);
                __syncwarp();
            }
            bar_sync(1, 192);
#pragma unroll 1
            for (uint32_t e = E0 + 5; e < 20; e++) {
                mbar_wait(bar_full + 8 * (e & 3), (e >> 2) & 1);
                if (!(((SPARE ? 0xa080 : 0x8420) >> e) & 1)) bar_sync(1, 192);
            }
#pragma unroll 1
            for (uint32_t e = 20; e < 148; e += 2) {
                mbar_wait_sleep(bar_full + 8 * (e & 3), (e >> 2) & 1);
                bar_sync(4, 160);
                if (SPARE && e == 112) mbar_wait(bar_q3, 0);
                mbar_wait_sleep(bar_full + 8 + 8 * (e & 3), (e >> 2) & 1);
                bar_sync(1, 192);
            }
            bar_sync(4, 160);
#pragma unroll 1
            for (uint32_t e = 148; e < 168; e++) {
                mbar_wait(bar_full + 8 * (e & 3), (e >> 2) & 1);
                if (e != 159 && e != 164) bar_sync(1, 192);
            }
        }
        __syncwarp();
        uint32_t rows = 0x1111u << warp;
        auto store_rows = [&](uint32_t m) {
#pragma unroll 1
            for (; m; m &= m - 1) {
                const int i = __ffs(m) - 1;
                asm volatile("cp.async.bulk.global.shared::cta.bulk_group.L2::cache_hint [%0], [%1], %2, %3;"
                             ::"l"(padd(args.out, (rg * 16 + i) * (D_ * 2))), "r"(sb + i * XP), "n"(D_ * 2), "l"(EVICT_FIRST) : "memory");
            }
        };
        mbar_wait_sleep(bar_out, 0);
        if (bx == 127 && warp == 0 && lane == 0) gs->epoch[0] = tag;
        if (elect()) {
            asm volatile("fence.proxy.async.shared::cta;" ::: "memory");
            const uint2 sel = lds64(sb + SM_RED + 64);
            if ((sel.x >> 4) == rg) rows &= ~(1u << (sel.x & 15));
            if ((sel.y >> 4) == rg) rows &= ~(1u << (sel.y & 15));
            store_rows(rows);
            asm volatile("cp.async.bulk.commit_group;\ncp.async.bulk.wait_group.read 0;" ::: "memory");
        }
    } else {
        uint32_t cv[2] = {0, 0}, tag0 = 0;
        {
            uint32_t ws, t, b;
            asm volatile("mov.u32 %0, smem_raw;\nmov.u32 %1, %%tid.x;\nmov.u32 %2, %%ctaid.x;" : "=r"(ws), "=r"(t), "=r"(b));
            t -= 128;
            const uint32_t* cp = padd(reinterpret_cast<const uint32_t*>(args.cvec), (t & 0xe0) + (t & 7) * 4);
            asm volatile("{\n.reg .pred p, q, r;\nsetp.lt.u32 r, %8, 256;\nsetp.lt.and.u32 p, %9, 72, r;\nsetp.lt.and.u32 q, %8, 128, p;\n"
                         "@p ld.global.nc.u32 %0, [%5];\n@q ld.global.nc.u32 %1, [%6 + 1024];\n@r ld.global.ca.u32 %2, [%7];\n"
                         "@p cp.async.cg.shared.global [%3], [%4], 16;\n@p cp.async.cg.shared.global [%3 + 4096], [%4 + 884736], 16;\n"
                         "@p cp.async.cg.shared.global [%3 + 8192], [%4 + 1769472], 16;\n@p cp.async.cg.shared.global [%3 + 12288], [%4 + 2654208], 16;\n"
                         "@q cp.async.cg.shared.global [%3 + 16384], [%4 + 3538944], 16;\n}"
                         : "+r"(cv[0]), "+r"(cv[1]), "+r"(tag0)
                         : "r"(ws + SM_Q + SLOT + t * 16), "l"(padd(args.w_mod, (t >> 1 & 127) * (12 * D_) + (t & 1) * 16 + b * 32)),
                           "l"(padd(cp, (t & 24) * 32)), "l"(cp), "l"(padd(gs->epoch, b >> 8)), "r"(t), "r"(b) : "memory");
        }
        uint32_t tag = __shfl_sync(0xffffffffu, tag0, 0);
        asm volatile("barrier.cluster.arrive.relaxed.aligned;" ::: "memory");
        asm volatile("setmaxnreg.inc.sync.aligned.u32 240;");
        const int lane = threadIdx.x & 31;
        const int cw = warp - 4;
        const int w = cw >> 2;
        const int tid = threadIdx.x - 128;
        ROLES();
        float* red = reinterpret_cast<float*>(smem_raw + SM_RED);
        DBG_INIT();
        DBG_G(120);
        DBG_T(100);

        uint32_t x[20];
        uint4* hdst;
        uint2* hdst2;
        {
            if (bx < 72) {
                uint2* mdst = &gs->mod1[(tid >> 3) * D_ + bx * 8 + (tid & 7)];
                if (tid < 8 * MREP) st_relaxed64(mdst, 0, 0);
                uint32_t sa[10];
#pragma unroll
                for (int i = 0; i < 2; i++) {
                    const float lo = bf_lo(cv[i]), hi = bf_hi(cv[i]);
                    cv[i] = pack_bf16(lo * sigmoidf_(lo), hi * sigmoidf_(hi));
                }
#pragma unroll
                for (int i = 0; i < 10; i++) sa[i] = __shfl_sync(0xffffffffu, cv[i >> 3], (i & 7) * 4 + (lane & 3));
                anchor(bar_full + 504, sa[0] & sa[1] & sa[2] & sa[3] & sa[4] & sa[5] & sa[6] & sa[7] & sa[8] & sa[9] & (uint32_t)(uintptr_t)mdst & (uint32_t)((uintptr_t)mdst >> 32));
                asm volatile("cp.async.wait_all;" ::: "memory");
                __syncwarp();
                const uint32_t ws = sb + SM_Q + SLOT + cw * 512 + (lane & 15) * 32 + (lane & 16);
                float d[16];
#pragma unroll
                for (int i = 0; i < 16; i++) d[i] = 0.f;
#pragma unroll
                for (int i = 0; i < 5; i++) {
                    const uint4 b = ldsm4t(ws + (i < 4 || cw < 4 ? i * 4096 : 0));
                    mma16816(d + 8 * (i & 1), sa[2 * i], sa[2 * i], sa[2 * i + 1], sa[2 * i + 1], b.x, b.y);
                    mma16816(d + 8 * (i & 1) + 4, sa[2 * i], sa[2 * i], sa[2 * i + 1], sa[2 * i + 1], b.z, b.w);
                }
                if (lane < 8) reinterpret_cast<float2*>(red)[lane * 8 + cw] = (lane & 4) ? make_float2(d[4] + d[12], d[5] + d[13]) : make_float2(d[0] + d[8], d[1] + d[9]);
                bar_sync(3, 256);
                if (tid < 8 * MREP) {
                    const float4* r = reinterpret_cast<const float4*>(red) + (tid & 7) * 4;
                    const float4 r0 = r[0], r1 = r[1], r2 = r[2], r3 = r[3];
                    st_relaxed64(mdst, pack_bf16(((r0.x + r0.z) + (r1.x + r1.z)) + ((r2.x + r2.z) + (r3.x + r3.z)),
                                                 ((r0.y + r0.w) + (r1.y + r1.w)) + ((r2.y + r2.w) + (r3.y + r3.w))), tag + 1);
                }
            }
            if (cw < 4) st_relaxed4(gs->h[~tag & 1] + (size_t)(rg * 36 + cw) * 32 + lane, 0, 0, 0, 0);
            DBG_G(106);
            asm volatile("barrier.cluster.wait.aligned;" ::: "memory");
            mbar_wait(bar_x, 0);
            asm volatile("add.u32 %0, %0, 1;" : "+r"(tag));
            float st[12], st2[12];
            rows_load(x, sb + SM_Q + (lane & 15) * XP + (lane >> 4) * 16 + cw * 32, cw);
#pragma unroll
            for (int i = 0; i < 12; i++) { st[i] = 0.f; st2[i] = 0.f; }
#pragma unroll
            for (int k = 0; k < 9; k++) stats_add((k & 1) ? st2 : st, x[2 * k], x[2 * k + 1], 0x3f803f80u);
#pragma unroll
            for (int i = 0; i < 12; i++) st[i] += st2[i];
            uint32_t mean2;
            float dot;
            const float rsd = rows_stats(st, reinterpret_cast<float4*>(red + 128), cw, lane, mean2, dot);
            const uint4* mp = reinterpret_cast<const uint4*>(gs->mod1 + ((bx >> 1) & (MREP - 1)) * D_) + min(tid, D_ / 4 - 1);
            uint4 v0 = make_uint4(0, tag, 0, tag), v1 = v0;
            auto look = [&]() {
                asm volatile("{\n.reg .pred p;\n.reg .b64 a, b, c, d;\nsetp.lt.s32 p, %9, 5;\nmov.b64 a, {%0, %1};\nmov.b64 b, {%2, %3};\n"
                             "mov.b64 c, {%4, %5};\nmov.b64 d, {%6, %7};\n@p ld.relaxed.gpu.global.v2.b64 {a, b}, [%8];\n"
                             "@p ld.relaxed.gpu.global.v2.b64 {c, d}, [%8 + 2304];\n"
                             "mov.b64 {%0, %1}, a;\nmov.b64 {%2, %3}, b;\nmov.b64 {%4, %5}, c;\nmov.b64 {%6, %7}, d;\n}"
                             : "+r"(v0.x), "+r"(v0.y), "+r"(v0.z), "+r"(v0.w), "+r"(v1.x), "+r"(v1.y), "+r"(v1.z), "+r"(v1.w)
                             : "l"(mp), "r"(cw) : "memory");
            };
            rows_normalise(x, x, mean2, rsd, lane, look);
            fence_regs(x);
            uint32_t it = 0;
#pragma unroll 1
            while (((v0.y ^ tag) | (v0.w ^ tag) | (v1.y ^ tag) | (v1.w ^ tag)) && ++it < SPIN / 16) look();
            uint4* smod = reinterpret_cast<uint4*>(smem_raw + SM_Q + M_MOD);
            if (tid < D_ / 4) smod[tid] = make_uint4(badd2(v1.x, 0x3f803f80u), v0.x, badd2(v1.z, 0x3f803f80u), v0.z);
            hdst = g_h + (size_t)(rg * 36 + cw) * 32 + lane;
            hdst2 = reinterpret_cast<uint2*>(g_h + (size_t)(rg * 36 + 32) * 32) + tid;
            bar_sync(3, 256);
            DBG_G(107);
#pragma unroll
            for (int k = 0; k < 9; k++) {
                const uint2 cs = lds64(sb + SM_Q + M_MOD + (cw * 8 + (lane & 3) + (k < 8 ? (k >> 1) * 64 + (k & 1) * 4 : 256 - cw * 4)) * 8);
                const uint32_t c1 = cs.x, sa = cs.y;
                x[2 * k] = badd2(bmul2(x[2 * k], c1), sa);
                if (x[2 * k] == 0) x[2 * k] = 0x8000u;
                x[2 * k + 1] = badd2(bmul2(x[2 * k + 1], c1), sa);
            }
#pragma unroll
            for (int ch = 0; ch < 3; ch++) st_relaxed4(hdst + ch * 256, x[4 * ch], x[4 * ch + 1], x[4 * ch + 2], x[4 * ch + 3]);
            DBG_G(108);
        }

        uint32_t rel_base;
        asm("mapa.shared::cluster.u32 %0, %1, %2;" : "=r"(rel_base) : "r"(bar_empty), "r"(lane & 1));
        auto release = [&](uint32_t slot) { if (lane < 2) mbar_arrive_cluster(rel_base + 8 * slot); };
        uint32_t q[32], p[32];
        float s[64], o[64];

        const int lw = cw & 3;
        const uint32_t relw = lw == 2 && lane < 8, handw = lw == 2 || cw == 1;
        auto release4 = [&](uint32_t off, uint32_t on = 1) {
            asm volatile("{\n.reg .pred p;\nsetp.ne.b32 p, %1, 0;\n@p mbarrier.arrive.shared::cluster.b64 _, [%0];\n}" ::"r"(rel_base + off), "r"(relw & on) : "memory"); };
        auto handoff = [&](uint32_t on = 1) {
            asm volatile("{\n.reg .pred p;\nsetp.ne.b32 p, %1, 0;\n@p bar.arrive %0, 192;\n}" ::"r"(2 - w), "r"(handw & on) : "memory"); };
        if (cw == 6) bar_arrive(1, 192);

        uint4* qpark = reinterpret_cast<uint4*>(smem_raw + SM_Q - SLOT) + cw * 256 + lane;
        {
            uint32_t h[144];
            const uint4* hf = g_h + (size_t)(qb * 8 + cw) * (36 * 32) + lane;
            auto load_h = [&](auto lo, auto hi) {
#pragma unroll
                for (int ks = lo.value; ks < hi.value; ks++) {
                    const uint4 v = h_frag(hf, ks, lane);
                    h[4 * ks] = v.x; h[4 * ks + 1] = v.y; h[4 * ks + 2] = v.z; h[4 * ks + 3] = v.w;
                }
            };
            auto check_h = [&](auto lo, auto hi) {
                uint32_t it = 0;
                bool miss;
#pragma unroll 1
                do {
                    uint32_t mn = ~0u;
#pragma unroll
                    for (int ks = lo.value; ks < hi.value; ks++) mn = __vimin3_u32(mn, h[4 * ks], h[4 * ks + 2]);
                    miss = __any_sync(0xffffffffu, mn == 0);
                    if (miss) load_h(lo, hi);
                    asm volatile("add.u32 %0, %0, 1;" : "+r"(it));
                } while (miss && it < SPIN / 16);
            };
            auto check_h2 = [&](auto lo, auto hi, auto nx) {
                float f0 = __uint_as_float(~0u), f1 = f0;
                hold(f0, f1);
                auto low = [&]() {
                    uint32_t m0 = __float_as_uint(f0), m1 = m0;
#pragma unroll
                    for (int ks = lo.value; ks < hi.value; ks += 2) { m0 = __vimin3_u32(m0, h[4 * ks], h[4 * ks + 2]); m1 = __vimin3_u32(m1, h[4 * ks + 4], h[4 * ks + 6]); }
                    return min(m0, m1);
                };
                anchor(const_cast<uint4*>(hf), h[4 * hi.value - 1] & __float_as_uint(f0));
                load_h(hi, nx);
                if (__any_sync(0xffffffffu, low() == 0)) {
                    uint32_t it = 0;
#pragma unroll 1
                    do load_h(lo, hi); while (__any_sync(0xffffffffu, low() == 0) && ++it < SPIN / 16);
                }
            };
            __nanosleep(100);
            load_h(IC<0>{}, IC<4>{});
            st_relaxed4(hdst + 3 * 256, x[12], x[13], x[14], x[15]);
            st_relaxed64(hdst2, x[16], x[17]);
            __syncwarp();
            if (SPARE && lane == 0) mbar_arrive(bar_pub);
            DBG_T(104); DBG_G(109);
            mbar_wait(bar_w0, 0);
#pragma unroll
            for (int e = E0 + 1; e < E0 + 3; e++) mbar_wait(bar_full + 8 * (e & 3), e >> 2);
#pragma unroll
            for (int i = 0; i < 64; i++) o[i] = 0.f;
            auto group = [&](auto tc, auto ec) {
                constexpr int t = tc.value, e = ec.value, k0 = t ? 8 * t - 4 : 0;
                constexpr bool first = e < E0 + 5, turns = e >= E0 + 4;
                uint64_t dv = (first ? args.d0 : desc_lo(0, UNIT) | (0x40000040ull << 32)) + ((t ? 0 : 512) + (e == E0 ? 6 : e & 3) * (SLOT / 16));
                if (first && t == 0) check_h(IC<0>{}, IC<4>{});
                if (first && t >= 3) mbar_wait(bar_full + 8 * (e & 3), e >> 2);
                if (first && t > 0) check_h2(IC<k0>{}, IC<8 * t + 4>{}, IC<t < 4 ? 8 * t + 12 : 0>{});
                if (t != 1 && turns) bar_sync(1 + w, 192);
                if (t != 1 || first) WG_FENCE();
#pragma unroll
                for (int ks = k0; ks < 8 * t + 4; ks++) {
                    mma_rs128<1>(o, h[4 * ks], h[4 * ks + 1], h[4 * ks + 2], h[4 * ks + 3], dv, ks);
                    if (t && turns && ks == k0 + QSPLIT - 1) WG_COMMIT();
                }
                if (t || first) WG_COMMIT();
                if (first && t == 0) load_h(IC<4>{}, IC<12>{});
                if (t > 0) {
                    WG_WAIT(1);
                    if (turns) handoff();
                    if ((t == 1 && !first) || (t > 1 && e <= E0 + 4)) release4(8 * ((e - 1) & 3));
                    if (turns && e != 18) { WG_WAIT(0); release4(8 * (e & 3)); }
                }
            };
            auto head = [&](auto ec, int slot) {
                constexpr int e = ec.value;
                fence_regs(o);
                group(IC<0>{}, IC<e>{}); group(IC<1>{}, IC<e + 1>{}); group(IC<2>{}, IC<e + 2>{}); group(IC<3>{}, IC<e + 3>{});
                if (e == 15) return;
                group(IC<4>{}, IC<e + 4>{});
                fence_regs(o);
#pragma unroll
                for (int i = 0; i < 8; i++)
                    qpark[slot * 2048 + i * 32] = make_uint4(pack_bf16(o[8 * i], o[8 * i + 1]), pack_bf16(o[8 * i + 2], o[8 * i + 3]),
                                                             pack_bf16(o[8 * i + 4], o[8 * i + 5]), pack_bf16(o[8 * i + 6], o[8 * i + 7]));
            };
            head(IC<E0>{}, 1);
            head(IC<E0 + 5>{}, 2);
            if (SPARE) {
                float (&u)[32] = reinterpret_cast<float (&)[32]>(o);
                fence_regs(u);
#pragma unroll
                for (int t = 0; t < 2; t++) {
                    uint64_t dv = args.d0 + t * (SLOT / 16);
                    bar_sync(1 + w, 192);
                    WG_FENCE();
#pragma unroll
                    for (int ks = 0; ks < 16 + 4 * t; ks++) {
                        mma_rs64<1>(u, h[64 * t + 4 * ks], h[64 * t + 4 * ks + 1], h[64 * t + 4 * ks + 2], h[64 * t + 4 * ks + 3], dv, ks | t);
                        if (ks == 2 * QSPLIT + 4 * t - 1) WG_COMMIT();
                    }
                    WG_COMMIT();
                    WG_WAIT(1);
                    handoff();
                    WG_WAIT(0);
                    release4(8 * t);
                }
                fence_regs(u);
                release4(16);
#pragma unroll
                for (int i = 0; i < 4; i++)
                    qpark[3 * 2048 + i * 32] = make_uint4(pack_bf16(u[8 * i], u[8 * i + 1]), pack_bf16(u[8 * i + 2], u[8 * i + 3]),
                                                          pack_bf16(u[8 * i + 4], u[8 * i + 5]), pack_bf16(u[8 * i + 6], u[8 * i + 7]));
            } else {
                head(IC<10>{}, 3);
            }
            head(IC<15>{}, 0);
#pragma unroll
            for (int i = 0; i < 8; i++) {
                const uint4 v = lds128(smem_u32(qpark + 2048 + i * 32));
                q[4 * i] = v.x; q[4 * i + 1] = v.y; q[4 * i + 2] = v.z; q[4 * i + 3] = v.w;
            }
#pragma unroll
            for (int i = 0; i < 32; i++) p[i] = h[112 + i];
            WG_WAIT(0);
            fence_regs(o);
            release4(16);
        }
        DBG_T(105);
        DBG_G(125);

        uint8_t* frag = reinterpret_cast<uint8_t*>(__shfl_sync(0xffffffffu, reinterpret_cast<unsigned long long>(g_frag + (size_t)(rg * 8 + cw) * WREG + lane * 16), lane));
        const uint4* qnext = reinterpret_cast<const uint4*>(__shfl_sync(0xffffffffu, reinterpret_cast<unsigned long long>(padd(smem_raw, SM_Q + tid * 16 + cw * 3584)), lane));
        uint8_t* odst = reinterpret_cast<uint8_t*>(const_cast<uint4*>(qnext));
        qnext -= 2048;
        float m0, m1, l0 = 0.25f, l1 = 0.25f, t0, t1;
        uint32_t bad = 0;
        auto finish = [&](auto lo, auto hi, uint32_t bit, auto sink) {
#pragma unroll
            for (int i = lo.value; i < hi.value; i++) {
                const uint32_t v0 = pack_bf16(o[8 * i] * t0, o[8 * i + 1] * t0), v1 = pack_bf16(o[8 * i + 2] * t1, o[8 * i + 3] * t1);
                const uint32_t v2 = pack_bf16(o[8 * i + 4] * t0, o[8 * i + 5] * t0), v3 = pack_bf16(o[8 * i + 6] * t1, o[8 * i + 7] * t1);
                if (i == 0 && fabsf(o[0] * t0) >= 0x1p-31f) bad |= bit << 8;
                sink(i, v0, v1, v2, v3);
            }
        };
        float lq[6];
        auto row_parts = [&]() {
#pragma unroll
            for (int i = 0; i < 3; i++) { lq[i] = __shfl_xor_sync(0xffffffffu, l0, i + 1); lq[3 + i] = __shfl_xor_sync(0xffffffffu, l1, i + 1); }
        };
        auto row_sums = [&](uint32_t bit) {
            t0 = (l0 + lq[0]) + (lq[1] + lq[2]); t1 = (l1 + lq[3]) + (lq[4] + lq[5]);
            if (!(t0 >= LMIN && t0 < LMAX && t1 >= LMIN && t1 < LMAX)) bad |= bit;
        };
        auto issue_pv = [&](uint64_t dv, int acc) {
            asm volatile("{\n.reg .pred p;\nsetp.eq.b32 p, %0, 0;\n@p bar.sync 4, 160;\n}" ::"r"(w) : "memory");
#pragma unroll
            for (int ks = 0; ks < 8; ks++)
                mma_rs128<1>(o, p[4 * ks], p[4 * ks + 1], p[4 * ks + 2], p[4 * ks + 3], dv, ks ? 1 : acc);
            WG_COMMIT();
        };
#pragma unroll
        for (int i = 0; i < 64; i++) s[i] = 0.f;
        uint64_t dv_lo = args.d0;
        uint32_t voff = 0;
        auto issue_qk = [&]() {
            uint64_t dk = dv_lo ^ (desc_lo(0, UNIT) ^ desc_lo(3 * SLOT, 16));
            bar_sync(1 + w, 192);
            fence_regs(s); fence_regs(q); fence_regs(o); fence_regs(p);
            WG_FENCE();
#pragma unroll
            for (int ks = 0; ks < 8; ks++)
                if (ks == 3) mma_rs128<0, 1018>(s, q[4 * ks], q[4 * ks + 1], q[4 * ks + 2], q[4 * ks + 3], dk, 1);
                else mma_rs128<0, 2>(s, q[4 * ks], q[4 * ks + 1], q[4 * ks + 2], q[4 * ks + 3], dk, ks != 0);
            WG_COMMIT();
        };
        auto to_frag = [&](int i, uint32_t v0, uint32_t v1, uint32_t v2, uint32_t v3) {
            *reinterpret_cast<uint4*>(odst + i * 512) = make_uint4(v0, v1, v2, v3); };
        int n = 0;
        auto scores_ready = [&]() {
            WG_WAIT(1);
            fence_regs(s); fence_regs(q);
        };
        auto pass_on = [&]() {
            release4(voff ^ 24);
            handoff();
        };
#pragma unroll 1
        for (;;) {
            {
                {
                    asm volatile("st.shared.v2.f32 [%0], {%1, %2};" ::"r"(sb + SM_RED + tid * 8), "f"(l0), "f"(l1) : "memory");
                    __syncwarp();
                    const uint4 a = lds128(sb + SM_RED + (tid & ~3) * 8), b = lds128(sb + SM_RED + (tid & ~3) * 8 + 16);
                    l0 = __uint_as_float(a.x); lq[0] = __uint_as_float(a.z); lq[1] = __uint_as_float(b.x); lq[2] = __uint_as_float(b.z);
                    l1 = __uint_as_float(a.y); lq[3] = __uint_as_float(a.w); lq[4] = __uint_as_float(b.y); lq[5] = __uint_as_float(b.w);
                }
                issue_qk();
                hold(l0, l1);
                row_sums(1u << (n >> 4));
                t0 = rcp_fast(t0); t1 = rcp_fast(t1);
                l0 = 0.f; l1 = 0.f;
                odst = n ? frag + ((n >> 4) - 1) * 4096 : odst;
                qnext = n == 48 ? reinterpret_cast<const uint4*>(frag) : qnext + 2048;
                anchor(bar_full + 504, (t0 + t1) * __uint_as_float((bad ^ (uint32_t)(uintptr_t)odst ^ (uint32_t)(uintptr_t)qnext) & 0x3fffffff));
                asm volatile("{\n.reg .pred p;\nsetp.ne.b32 p, %1, 0;\n@p mbarrier.arrive.shared::cta.b64 _, [%0];\n}"
                             ::"r"(bar_qfree + (n >> 1) - 8), "r"(lane ? 0 : n) : "memory");
                issue_pv(dv_lo, 1);
                scores_ready();
                const uint32_t a = pack_bf16(fmaxf(fmaxf(s[0], s[1]), fmaxf(s[4], s[5])), fmaxf(fmaxf(s[2], s[3]), fmaxf(s[6], s[7])));
                const uint32_t b = bmax2(bmax2(a, __shfl_xor_sync(0xffffffffu, a, 1)), bmax2(__shfl_xor_sync(0xffffffffu, a, 2), __shfl_xor_sync(0xffffffffu, a, 3)));
                pass_on();
                m0 = fmaf(-CS, bf_lo(b), -POFF); m1 = fmaf(-CS, bf_hi(b), -POFF);
            }
#pragma unroll 1
            for (;;) {
                DBG_T(n);
#pragma unroll
                for (int i = 0; i < 4 * STAGE; i++) s[i] = fmaf(s[i], CS, (i & 2) ? m1 : m0);
#pragma unroll
                for (int i = 0; i < 4 * SPLIT; i++) s[i] = ex2(s[i]);
#pragma unroll
                for (int i = 0; i < SPLIT; i++) { l0 += s[4 * i] + s[4 * i + 1]; l1 += s[4 * i + 2] + s[4 * i + 3]; }
                m0 = fmaf(l0, 0.f, m0); m1 = fmaf(l1, 0.f, m1);
                anchor(bar_full + 504, l0 + l1);
                WG_WAIT(0);
                fence_regs(o); fence_regs(p);
                release4(voff);
                dv_lo ^= 2 * SLOT / 16;
                voff ^= 16;
                n++;
#pragma unroll
                for (int i = 4 * STAGE; i < 64; i++) s[i] = fmaf(s[i], CS, (i & 2) ? m1 : m0);
#pragma unroll
                for (int i = 4 * SPLIT; i < 64; i++) s[i] = ex2(s[i]);
#pragma unroll
                for (int i = SPLIT; i < 16; i++) { l0 += s[4 * i] + s[4 * i + 1]; l1 += s[4 * i + 2] + s[4 * i + 3]; }
#pragma unroll
                for (int i = 0; i < 32; i++) p[i] = pack_bf16(s[2 * i], s[2 * i + 1]);
                const int jn = n & 15;
                if (jn > 1) {
                    issue_qk();
                    if ((n & 10) == 2) {
                        if (n & 1) {
#pragma unroll
                            for (int i = 0; i < 64; i++) o[i] *= (i & 2) ? t1 : t0;
                        } else {
                            row_parts();
                            row_sums(2u << (n >> 4));
                            const uint32_t e0 = __float_as_uint(t0) >> 23, e1 = __float_as_uint(t1) >> 23;
                            m0 -= __uint_as_float(0x4b000000u | e0) - (8388608.f + 127.f - POFF);
                            m1 -= __uint_as_float(0x4b000000u | e1) - (8388608.f + 127.f - POFF);
                            t0 = __uint_as_float((254 - (int)POFF - e0) << 23); t1 = __uint_as_float((254 - (int)POFF - e1) << 23);
                            l0 *= t0; l1 *= t1;
                        }
                    }
                    fence_regs(o);
                    WG_FENCE();
                    issue_pv(dv_lo, 1);
                    scores_ready();
                    pass_on();
                    if (jn != 15) continue;
#pragma unroll
                    for (int i = 0; i < 8; i++) {
                        const uint4 v = qnext[i * 32];
                        q[4 * i] = v.x; q[4 * i + 1] = v.y; q[4 * i + 2] = v.z; q[4 * i + 3] = v.w;
                    }
                    continue;
                }
                if (jn == 0) break;
                finish(IC<0>{}, IC<ESPLIT>{}, 1u << (n >> 4), to_frag);
                issue_qk();
                hold(t0, t1);
                finish(IC<ESPLIT>{}, IC<8>{}, 1u << (n >> 4), to_frag);
                WG_FENCE();
                issue_pv(dv_lo, 0);
                scores_ready();
                pass_on();
            }
            if (n == 64) break;
        }
        DBG_T(64);
        uint32_t a1[32], a2[32];
        bar_sync(1 + w, 192);
        fence_regs(o); fence_regs(p);
        WG_FENCE();
        issue_pv(args.d0 + 3 * SLOT / 16, 1);
        handoff();
        mbar_wait(bar_mod, 0);
        const int tid_ = __shfl_sync(0xffffffffu, tid, lane);
        row_parts();
        row_sums(16);
        t0 = rcp_fast(t0); t1 = rcp_fast(t1);
        anchor(frag, q[0] & q[4] & q[8] & q[12] & q[16] & q[20] & q[24] & q[28] & __float_as_uint(t0) & __float_as_uint(t1) & tid_);
        frag_load(a1, frag + 4096);
        frag_load<0, 4>(a2, frag + 8192);
        anchor(frag, bad);
        WG_WAIT(0);
        fence_regs(o); fence_regs(p);
        release4(24);
        finish(IC<0>{}, IC<8>{}, 16, [&](int i, uint32_t v0, uint32_t v1, uint32_t v2, uint32_t v3) {
            p[4 * i] = v0; p[4 * i + 1] = v1; p[4 * i + 2] = v2; p[4 * i + 3] = v3; });
        anchor(frag, p[31] & p[15]);
        frag_load<4, 8>(a2, frag + 8192);
        bad = __reduce_or_sync(0xffffffffu, bad);
        bad = ((bad | ~(bad >> 8)) >> 1) & 15;
        if (__builtin_expect(bad != 0, 0)) {
            uint8_t* keep = g_keep + (size_t)(rg * 8 + cw) * 4096 + lane * 16;
            frag_store(keep, p);
            attn_fallback(bad, tag, gs, frag, keep, args.wq, args.kc, args.vc);
            frag_load(q, frag); frag_load(a1, frag + 4096); frag_load(a2, frag + 8192); frag_load(p, keep);
            anchor(frag, q[0] & q[4] & q[8] & q[12] & q[16] & q[20] & q[24] & q[28] & p[0] & p[4] & p[8] & p[12] & p[16] & p[20] & p[24] & p[28]);
        }
        DBG_T(80);
        DBG_G(124);

        const uint32_t eye = (tid_ >> 3 & 3) == (tid_ & 3) ? 0x3f80u << ((tid_ & 4) * 4) : 0;
        auto sum8 = [&](uint32_t* r, const uint4 (&v)[8]) {
            float d[16];
#pragma unroll
            for (int i = 0; i < 16; i++) d[i] = 0.f;
#pragma unroll
            for (int src = 0; src < 8; src++) {
                mma1688(d + 8 * (src & 1), v[src].x, v[src].y, eye);
                mma1688(d + 8 * (src & 1) + 4, v[src].z, v[src].w, eye);
            }
#pragma unroll
            for (int i = 0; i < 4; i++) r[i] = pack_bf16(d[2 * i] + d[8 + 2 * i], d[2 * i + 1] + d[9 + 2 * i]);
        };
        uint4 v2[8], v3[8], wf[23];
        uint2 u4[8], gw[9];
        uint32_t x1[20], xs, pa, ta;
        const uint8_t *mb, *mb4;
        auto load_wf = [&](auto lo, auto hi) {
            const uint32_t wa = sb + SM_Q + ((tid_ & 8) * (D_ / 8) + cw * 16 + (tid_ & 7) + (tid_ & 16) / 2) * 80;
            const uint32_t wb = wa + (512 - cw * 8) * 80 - (tid_ & 16) * 39;
#pragma unroll
            for (int i = lo.value; i < hi.value; i++) wf[i] = ldsm4t(i < 20 ? wa + (i / 5) * 10240 + (i % 5) * 16 : wb + (i - 20) * 32);
        };
        uint32_t at[18];
        {
            float (&u)[32] = reinterpret_cast<float (&)[32]>(o);
            uint32_t off = 0;
            auto turn = [&](const uint32_t (&a)[32], const uint32_t (&b)[32], int acc) {
                uint64_t dv = args.d0 + off * (SLOT / 128);
                bar_sync(1 + w, 192);
                fence_regs(u);
                WG_FENCE();
#pragma unroll
                for (int ks = 0; ks < 16; ks++) {
                    const uint32_t* f = ks < 8 ? &a[4 * ks] : &b[4 * ks - 32];
                    mma_rs64<1>(u, f[0], f[1], f[2], f[3], dv, ks | acc);
                    if (ks == OSPLIT - 1) WG_COMMIT();
                }
                WG_COMMIT();
                WG_WAIT(1);
            };
            auto done = [&]() {
                WG_WAIT(0);
                fence_regs(u);
                release4(off);
                off = (off + 8) & 24;
            };
            auto store = [&](uint8_t* dst) {
#pragma unroll
                for (int i = 0; i < 4; i++)
                    st_relaxed4(dst + i * 512, pack_bf16(u[8 * i], u[8 * i + 1]), pack_bf16(u[8 * i + 2], u[8 * i + 3]),
                                pack_bf16(u[8 * i + 4], u[8 * i + 5]), pack_bf16(u[8 * i + 6], u[8 * i + 7]));
            };
            pa = sb + w * (UNIT - 2048) + tid_ * 16;
#pragma unroll
            for (int i = 0; i < 8; i++) at[i] = 0;
            fence_regs(q); fence_regs(p);
            uint8_t* dst = frag;
#pragma unroll
            for (int i = 0; i < 8; i++) asm volatile("" : "=r"(v2[i].x), "=r"(v2[i].y), "=r"(v2[i].z), "=r"(v2[i].w));
#pragma unroll 1
            for (int k = 0; k < 8; k++, dst += 2048) {
                const uint32_t poff = (off + 8) & 24;
                const bool sum = (0xa0 >> k) & 1;
                turn(q, p, 0);
                handoff();
                auto sum_p = [&](auto lo, auto hi) {
#pragma unroll
                    for (int i = lo.value; i < hi.value; i++) {
                        float a[8], b[8];
#pragma unroll
                        for (int src = 0; src < 8; src++) {
                            const uint32_t x = i == 0 ? v2[src].x : i == 1 ? v2[src].y : i == 2 ? v2[src].z : v2[src].w;
                            a[src] = bf_lo(x); b[src] = bf_hi(x);
                        }
                        at[i] = at[4 + i];
                        at[4 + i] = pack_bf16(((a[0] + a[2]) + (a[4] + a[6])) + ((a[1] + a[3]) + (a[5] + a[7])),
                                              ((b[0] + b[2]) + (b[4] + b[6])) + ((b[1] + b[3]) + (b[5] + b[7])));
                    }
                };
                if (sum) {
                    mbar_wait(bar_full + poff, 1);
#pragma unroll
                    for (int src = 0; src < 8; src++) v2[src] = lds128(pa + poff * (SLOT / 8) + src * 2048);
                    __syncwarp();
                    release(poff >> 3);
                    done();
                    off = (off + 8) & 24;
                    sum_p(IC<0>{}, IC<2>{});
                } else {
                    done();
                }
                turn(a1, a2, 1);
                handoff();
                if (sum) sum_p(IC<2>{}, IC<4>{});
                done();
                store(dst);
                __syncwarp();
                asm volatile("{\n.reg .pred p;\nsetp.ne.b32 p, %1, 0;\n@p mbarrier.arrive.shared::cta.b64 _, [%0];\n}"
                             ::"r"(bar_pub + 4 + 4 * k), "r"(lane ? 0 : (0x2a >> k) & 1) : "memory");
            }
            turn(q, p, 0);
            handoff();
            mb = padd(g_frag, (qb * 64 + j) * WREG + 3 * 4096 + tid_ * 16);
            mb4 = padd(mb, 4096 + ((cw >> 1) - cw) * 512 + (cw & 1) * 8);
            xs = sb + (tid_ & 15) * XP + (tid_ & 16) + cw * 32;
            ta = sb + (cw * 8 + (tid_ & 3)) * 8;
#pragma unroll
            for (int k = 0; k < 9; k++) {
                gw[k] = lds64(ta + SM_T + (k < 8 ? (k >> 1) * 64 + (k & 1) * 4 : 256 - cw * 4) * 8);
                if (!(tid_ & 4)) gw[k].y = 0x3f803f80u;
            }
            mbar_wait(bar_g, 0);
            done();
            load_wf(IC<0>{}, IC<WF0>{});
            turn(a1, a2, 1);
            if (w == 0) handoff();
            done();
            store(dst);
            mbar_wait(bar_full, 0);
            rows_load(x1, xs, cw);
            if (w == 0) bar_sync(5, 256); else bar_arrive(5, 256);
        }
        DBG_T(81);
        DBG_G(122);

        {
        const int tid = tid_, lane = tid & 31;
        const int g8 = lane >> 2, qd = lane & 3, l16 = lane & 15;
        uint32_t h2[18], gb[9], k1, k2;
        float4* rec = reinterpret_cast<float4*>(red + 128);
        const uint2* candp = reinterpret_cast<const uint2*>(padd(g_cand, ((bx & (CREP - 1)) * NCTA + (tid >> 1)) * 32 + (tid & 1) * 8));
        uint2 cd;
        auto stage_out = [&]() {
#pragma unroll
            for (int k = 0; k < 9; k++) {
                x1[2 * k] = badd2(x1[2 * k], bmul2(gb[k], h2[2 * k]));
                x1[2 * k + 1] = badd2(x1[2 * k + 1], bmul2(gb[k], h2[2 * k + 1]));
            }
#pragma unroll
            for (int ch = 0; ch < 4; ch++) stsm_x4(xs + ch * 256, x1[4 * ch], x1[4 * ch + 1], x1[4 * ch + 2], x1[4 * ch + 3]);
            asm volatile("stmatrix.sync.aligned.m8n8.x2.shared.b16 [%0], {%1, %2};" ::"r"(xs + 1024 - cw * 16), "r"(x1[16]), "r"(x1[17]) : "memory");
        };
        {
            uint32_t it = 0, miss;
            mbar_wait(bar_full + 8, 0);
#pragma unroll
            for (int src = 0; src < 8; src++) v2[src] = lds128(pa + SLOT + src * 2048);
            sum8(at + 8, v2);
            float st[12];
#pragma unroll
            for (int i = 0; i < 12; i++) st[i] = 0.f;
            auto add_pair = [&](int k) {
                x1[2 * k] = badd2(x1[2 * k], bmul2(gw[k].x, at[2 * k]));
                x1[2 * k + 1] = badd2(x1[2 * k + 1], bmul2(gw[k].x, at[2 * k + 1]));
                stats_add(st, x1[2 * k], x1[2 * k + 1], gw[k].y);
            };
#pragma unroll
            for (int k = 0; k < 6; k++) add_pair(k);
            mbar_wait(bar_full + 16, 0);
#pragma unroll
            for (int src = 0; src < 8; src++) v3[src] = lds128(pa + 2 * SLOT + src * 2048);
            miss = __vimax3_u32(__vimax3_u32(v3[0].x, v3[0].z, v3[1].x), __vimax3_u32(v3[1].z, v3[2].x, v3[2].z), __vimax3_u32(v3[3].x, v3[3].z, v3[4].x));
            miss = __vimax3_u32(miss, __vimax3_u32(v3[4].z, v3[5].x, v3[5].z), max(__vimax3_u32(v3[6].x, v3[6].z, v3[7].x), v3[7].z));
            if (__any_sync(0xffffffffu, miss == ~0u))
#pragma unroll 1
            do {
                miss = 0;
#pragma unroll
                for (int src = 0; src < 8; src++) reload16(v3[src], mb + (size_t)src * 8 * WREG, miss);
            } while (__any_sync(0xffffffffu, miss) && ++it < SPIN / 16);
            if (lane < 4) mbar_arrive_cluster(rel_base + 8 * (1 + (lane >> 1)));
            sum8(at + 12, v3);
            add_pair(6); add_pair(7);
            load_wf(IC<WF0>{}, IC<WF1>{});
            uint2 cs[9];
#pragma unroll
            for (int k = 0; k < 9; k++) cs[k] = lds64(ta + SM_TC + (k < 8 ? (k >> 1) * 64 + (k & 1) * 4 : 256 - cw * 4) * 8);
            mbar_wait(bar_pre, 0);
            mbar_wait(bar_full + 24, 0);
#pragma unroll
            for (int src = 0; src < 8; src++) u4[src] = lds64(sb + 3 * SLOT + src * 2048 + (cw >> 1) * 512 + lane * 16 + (cw & 1) * 8);
            miss = __vimax3_u32(__vimax3_u32(u4[0].x, u4[1].x, u4[2].x), __vimax3_u32(u4[3].x, u4[4].x, u4[5].x), max(u4[6].x, u4[7].x));
            if (__any_sync(0xffffffffu, miss == ~0u))
#pragma unroll 1
            do {
                miss = 0;
#pragma unroll
                for (int src = 0; src < 8; src++) reload8(u4[src], mb4 + (size_t)src * 8 * WREG, miss);
            } while (__any_sync(0xffffffffu, miss) && ++it < SPIN / 16);
            float d[8] = {0.f, 0.f, 0.f, 0.f, 0.f, 0.f, 0.f, 0.f};
#pragma unroll
            for (int i = 0; i < 4; i++) mma16816(d + 4 * (i & 1), u4[2 * i].x, u4[2 * i].y, u4[2 * i + 1].x, u4[2 * i + 1].y, eye, eye);
            at[16] = pack_bf16(d[0] + d[4], d[1] + d[5]); at[17] = pack_bf16(d[2] + d[6], d[3] + d[7]);
            add_pair(8);
            DBG_G(123);
            const float2 ws = *reinterpret_cast<const float2*>(smem_raw + SM_TS);
            uint4* cdst = padd(g_cand, (tid * NCTA + rg) * 32);
            uint32_t mean2;
            float dot;
            const float rsd = rows_stats(st, rec, cw, lane, mean2, dot);
            const uint32_t b = __float_as_uint(fmaf(fmaf(-bf_lo(mean2), ws.x, dot), rsd, ws.y));
            const uint32_t key = (((b & 0x80000000u) ? ~b : (b | 0x80000000u)) | 2047u) - (rg * 16 + l16);
            top2(key, k1, k2);
            if (tid < CREP) st_relaxed(cdst, k1, tag, k2, tag);
            cd = ld_relaxed64(candp);
            rows_normalise(h2, x1, mean2, rsd, lane, [&]() {
#pragma unroll
                for (int k = 0; k < 9; k++) gb[k] = lds32(sb + SM_TG + (cw * 8 + qd + (k < 8 ? (k >> 1) * 64 + (k & 1) * 4 : 256 - cw * 4)) * 4);
                load_wf(IC<WF1>{}, IC<WF2>{});
            });
#pragma unroll
            for (int k = 0; k < 18; k++) h2[k] = badd2(bmul2(h2[k], cs[k >> 1].x), cs[k >> 1].y);
            const uint32_t r1 = ~k1 & 15, r2 = ~k2 & 15;
            uint32_t todo = ((r1 & 7) == g8) | ((r2 & 7) == g8) << 1;
#pragma unroll 1
            while (todo) {
                const bool second = !(todo & 1), hi = (second ? r2 : r1) & 8;
                uint4* dst = padd(g_rows, ((rg * 2 + second) * RSLOT + cw * 24 + qd) * 16);
                uint32_t r[18];
#pragma unroll
                for (int k = 0; k < 9; k++) { r[k] = hi ? h2[2 * k + 1] : h2[2 * k]; r[9 + k] = hi ? x1[2 * k + 1] : x1[2 * k]; }
                fence_regs(r);
                st_relaxed(dst, r[0], r[1], r[2], r[3]);
                st_relaxed(dst + 8, r[4], r[5], r[6], r[7]);
                st_relaxed64(reinterpret_cast<uint2*>(padd(dst, 256 - qd * 8)), r[8], r[17]);
                st_relaxed(dst + 4, r[9], r[10], r[11], r[12]);
                st_relaxed(dst + 12, r[13], r[14], r[15], r[16]);
                todo &= todo - 1;
            }
            __syncwarp();

            stage_out();
        }
        DBG_G(110);
        float4* part = reinterpret_cast<float4*>(smem_raw + 3 * SLOT + UNIT + 8192);
        bf16* act = reinterpret_cast<bf16*>(smem_raw + 3 * SLOT + UNIT + 4096);
        {
            uint32_t it = 0;
            const bool own = (tid >> 1) == rg;
            const uint32_t ks = sb + 3 * SLOT + UNIT + 5120;
#pragma unroll 1
            while (__any_sync(0xffffffffu, cd.y != tag && !own) && ++it < SPIN / 16)
                asm volatile("{\n.reg .pred p;\n.reg .b64 u;\nsetp.ne.u32 p, %1, %3;\nmov.b64 u, {%0, %1};\n"
                             "@p ld.relaxed.gpu.global.b64 u, [%2];\nmov.b64 {%0, %1}, u;\n}" : "+r"(cd.x), "+r"(cd.y) : "l"(candp), "r"(tag) : "memory");
            asm volatile("st.shared.u32 [%0], %1;" ::"r"(ks + tid * 4), "r"(own ? (tid & 1) ? k2 : k1 : cd.x) : "memory");
            bar_sync(3, 256);
            DBG_G(111);
            const uint4 a = lds128(ks + lane * 16), b = lds128(ks + 512 + lane * 16);
            const uint32_t a1 = max(a.x, a.z), a2 = __vimax3_u32(min(a.x, a.z), a.y, a.w);
            const uint32_t b1 = max(b.x, b.z), b2 = __vimax3_u32(min(b.x, b.z), b.y, b.w);
            const uint32_t c1 = max(a1, b1), c2 = __vimax3_u32(min(a1, b1), a2, b2);
            k1 = __reduce_max_sync(0xffffffffu, c1);
            k2 = __reduce_max_sync(0xffffffffu, c1 == k1 ? c2 : c1);
        }
        const int sel0 = ~k1 & 2047, sel1 = ~k2 & 2047;
        const uint32_t slot0 = (sel0 >> 4) * 2, slot1 = (sel1 >> 4) * 2 + ((sel0 ^ sel1) < 16);
        uint4 da[13];
        {
            const uint4* hp = padd(g_rows, (((g8 & 1) ? slot1 : slot0) * RSLOT + cw * 24 + qd) * 16);
            const uint2* hp2 = reinterpret_cast<const uint2*>(padd(hp, 256 - qd * 8));
            uint4 hv[2] = {ld_relaxed2(hp), ld_relaxed2(hp + 8)};
            uint2 hw = ld_relaxed64(hp2);
            if (tid == 255) {
                reinterpret_cast<int2*>(red)[8] = make_int2(sel0, sel1);
                mbar_arrive(bar_out);
            }
            load_wf(IC<WF2>{}, IC<23>{});
            mbar_wait(bar_full + 8, 1);
            mbar_wait(bar_full + 16, 1);
            auto load_d = [&](auto lo, auto hi) {
                const int r = (lane & 7) + (lane & 16) / 2;
                const uint32_t d0 = sb + SLOT + r * XP + cw * 144 + (lane & 8) * 2, d1 = d0 + (r < 2 ? 16 * XP : SLOT - 2 * XP);
                const uint32_t d2 = sb + 2 * SLOT + (14 + (lane & 3)) * XP + cw * 144 + (lane >> 3) * 16;
#pragma unroll
                for (int i = lo.value; i < hi.value; i++) da[i] = ldsm4t(i < 10 ? ((i & 1) ? d1 : d0) + (i >> 1) * 32 : d2 + (i - 10) * 64);
            };
            load_d(IC<0>{}, IC<DL>{});
            uint32_t it = 0, miss;
            float f0 = 1.f, f1 = 1.f;
            hold(f0, f1);
            if (__any_sync(0xffffffffu, max(__vimax3_u32(__vimax3_u32(__float_as_uint(f0), hv[0].x, hv[0].z), hv[1].x, hv[1].z), hw.x) == ~0u))
#pragma unroll 1
            do {
                miss = 0;
                reload16(hv[0], hp, miss);
                reload16(hv[1], hp + 8, miss);
                reload8(hw, hp2, miss);
            } while (__any_sync(0xffffffffu, miss) && ++it < SPIN / 16);
            DBG_G(112);
            float acc[20];
#pragma unroll
            for (int i = 0; i < 20; i++) acc[i] = 0.f;
#pragma unroll
            for (int i = 0; i < 5; i++) mma1688(acc + 4 * i, (i & 1) ? wf[20 + i / 2].z : wf[20 + i / 2].x, (i & 1) ? wf[20 + i / 2].w : wf[20 + i / 2].y, hw.x);
#pragma unroll
            for (int i = 0; i < 20; i++)
                mma16816(acc + 4 * (i % 5), wf[i].x, wf[i].y, wf[i].z, wf[i].w, (i / 5 & 1) ? hv[i / 10].z : hv[i / 10].x, (i / 5 & 1) ? hv[i / 10].w : hv[i / 10].y);
            if (qd == 0) {
#pragma unroll
                for (int i = 0; i < 5; i++) part[cw * 40 + i * 8 + g8] = make_float4(acc[4 * i], acc[4 * i + 1], acc[4 * i + 2], acc[4 * i + 3]);
            }
            load_d(IC<DL>{}, IC<13>{});
        }
        {
            uint2* dst = padd(g_ypart, ((cw * 9 * NCTA + bx) * 8 + g8) * 8);
            bar_sync(3, 256);
            if (cw < 5) {
                const float* pp = reinterpret_cast<const float*>(part) + ((bx & 1) << 4) + tid;
                const float g = rbf(((pp[0] + pp[160]) + (pp[320] + pp[480])) + ((pp[640] + pp[800]) + (pp[960] + pp[1120])));
                const float v = rbf(g * sigmoidf_(g)) * __shfl_down_sync(0xffffffffu, g, 2);
                if (!(tid & 2)) act[(tid & 1) * 56 + (tid >> 2)] = __float2bfloat16_rn(tid < 144 ? v : 0.f);
            }
            bar_sync(3, 256);
            DBG_G(113);
            const uint32_t ap = sb + 3 * SLOT + UNIT + 4096 + (lane & 1) * 112 + (lane >> 3) * 16;
            const uint4 b0 = ldsm4(ap);
            const uint32_t b1 = lds32(sb + 3 * SLOT + UNIT + 4096 + (g8 & 1) * 112 + 64 + qd * 4);
            float y[20];
#pragma unroll
            for (int i = 0; i < 20; i++) y[i] = 0.f;
#pragma unroll
            for (int i = 0; i < 5; i++) {
                mma16816(y + 4 * i, da[2 * i].x, da[2 * i].y, da[2 * i].z, da[2 * i].w, b0.x, b0.y);
                mma16816(y + 4 * i, da[2 * i + 1].x, da[2 * i + 1].y, da[2 * i + 1].z, da[2 * i + 1].w, b0.z, b0.w);
                mma1688(y + 4 * i, (i & 1) ? da[10 + i / 2].z : da[10 + i / 2].x, (i & 1) ? da[10 + i / 2].w : da[10 + i / 2].y, b1);
            }
            if (qd == 0) {
#pragma unroll
                for (int i = 0; i < 9; i++)
                    asm volatile("st.relaxed.gpu.global.v2.f32 [%0], {%1, %2};" ::"l"(dst + i * (NCTA * 8)), "f"(y[2 * i]), "f"(y[2 * i + 1]) : "memory");
            }
        }
        DBG_G(114);
        if (bx < 72) {
            const int G = bx, tok = g8 & 1, cp = G * 4 + qd;
            const uint2* src = padd(g_ypart, (bx * NCTA * 8 + tid) * 8);
            const uint8_t* hsrc = reinterpret_cast<const uint8_t*>(padd(g_rows, (tok ? slot1 : slot0) * (RSLOT * 16) +
                (G < 64 ? (G >> 1 & 7) * 384 + (G >> 5) * 128 + qd * 16 + (G >> 1 & 8) + (G & 1) * 4 : (G - 64) * 384 + 256 + qd * 8)));
            const uint8_t* xsrc = hsrc + (G < 64 ? 64 : 4);
            uint32_t* dst = padd(reinterpret_cast<uint32_t*>(args.out), (tok ? sel1 : sel0) * (D_ * 2) + cp * 4);
            const uint32_t gb = reinterpret_cast<const uint32_t*>(smem_raw + SM_TG)[cp];
            const uint32_t ksel = ((tok ? k2 : k1) & ~2047u) | 1024u;
            const float sg = sigmoidf_(rbf(__uint_as_float((ksel & 0x80000000u) ? (ksel & 0x7fffffffu) : ~ksel)));
            uint2 v[4];
            uint32_t hv = 0, xv = 0, it = 0, miss;
            if (cw == 0) { hv = ld_relaxed32(hsrc); xv = ld_relaxed32(xsrc); }
#pragma unroll
            for (int i = 0; i < 4; i++) v[i] = make_uint2(~0u, 0);
#pragma unroll 1
            do {
#pragma unroll
                for (int i = 0; i < 4; i++) reload8(v[i], src + i * 256, miss);
            } while (__any_sync(0xffffffffu, max(__vimax3_u32(v[0].x, v[1].x, v[2].x), v[3].x) == ~0u) && ++it < SPIN / 16);
#pragma unroll 1
            while (max(hv, xv) == ~0u && ++it < SPIN / 16) { hv = ld_relaxed32(hsrc); xv = ld_relaxed32(xsrc); }
            __syncwarp();
            float y0 = (__uint_as_float(v[0].x) + __uint_as_float(v[1].x)) + (__uint_as_float(v[2].x) + __uint_as_float(v[3].x));
            float y1 = (__uint_as_float(v[0].y) + __uint_as_float(v[1].y)) + (__uint_as_float(v[2].y) + __uint_as_float(v[3].y));
            y0 += __shfl_xor_sync(0xffffffffu, y0, 8); y1 += __shfl_xor_sync(0xffffffffu, y1, 8);
            y0 += __shfl_xor_sync(0xffffffffu, y0, 16); y1 += __shfl_xor_sync(0xffffffffu, y1, 16);
            if (lane < 8) reinterpret_cast<float2*>(rec)[cw * 8 + lane] = make_float2(y0, y1);
            bar_sync(3, 256);
            if (cw == 0) {
                const float4 t0_ = rec[(lane >> 3) * 4 + qd], t1_ = rec[16 + (lane >> 3) * 4 + qd];
                y0 = tok ? t0_.y + t1_.y : t0_.x + t1_.x; y1 = tok ? t0_.w + t1_.w : t0_.z + t1_.z;
                y0 += __shfl_xor_sync(0xffffffffu, y0, 8); y1 += __shfl_xor_sync(0xffffffffu, y1, 8);
                y0 += __shfl_xor_sync(0xffffffffu, y0, 16); y1 += __shfl_xor_sync(0xffffffffu, y1, 16);
                const uint32_t y2 = bmul2(pack_bf16(y0, y1), pack_bf16(sg, sg));
                if (lane < 8) *dst = badd2(xv, bmul2(gb, badd2(hv, y2)));
            }
        }
        }
        DBG_T(88);
        DBG_G(121);
    }
}

typedef CUresult (*EncodeFn)(CUtensorMap*, CUtensorMapDataType, cuuint32_t, void*, const cuuint64_t*, const cuuint64_t*,
                             const cuuint32_t*, const cuuint32_t*, CUtensorMapInterleave, CUtensorMapSwizzle,
                             CUtensorMapL2promotion, CUtensorMapFloatOOBfill);

static void make_map(EncodeFn enc, CUtensorMap* m, const void* ptr, int rank, const cuuint64_t* dims,
                     const cuuint64_t* strides, const cuuint32_t* box, CUtensorMapSwizzle sw = CU_TENSOR_MAP_SWIZZLE_128B,
                     CUtensorMapDataType dt = CU_TENSOR_MAP_DATA_TYPE_BFLOAT16) {
    const cuuint32_t es[3] = {1, 1, 1};
    enc(m, dt, rank, const_cast<void*>(ptr), dims, strides, box, es,
        CU_TENSOR_MAP_INTERLEAVE_NONE, sw, CU_TENSOR_MAP_L2_PROMOTION_L2_128B,
        CU_TENSOR_MAP_FLOAT_OOB_FILL_NONE);
}

extern "C" void kernel_launch(void* const* d_in, const int* in_sizes, int n_in, void* d_out, int out_size) {
    const bf16* x = (const bf16*)d_in[0];
    const bf16* kc = (const bf16*)d_in[1];
    const bf16* vc = (const bf16*)d_in[2];
    const bf16* wq = (const bf16*)d_in[3];
    const bf16* wo = (const bf16*)d_in[4];
    const bf16* w_r = (const bf16*)d_in[6];
    const bf16* w_gate = (const bf16*)d_in[7];
    const bf16* w_up = (const bf16*)d_in[8];
    const bf16* w_down = (const bf16*)d_in[9];
    const bf16* cvec = (const bf16*)d_in[10];
    const bf16* w_mod = (const bf16*)d_in[11];
    bf16* out = (bf16*)d_out;

    void* fn = nullptr;
    cudaDriverEntryPointQueryResult qr;
    cudaGetDriverEntryPoint("cuTensorMapEncodeTiled", &fn, cudaEnableDefault, &qr);
    EncodeFn enc = (EncodeFn)fn;
    void* p_s;
    cudaGetSymbolAddress(&p_s, g_s);

    CUtensorMap tm_wq, tm_k, tm_v, tm_wo, tm_p, tm_x, tm_d, tm_g, tm_u;
    { cuuint64_t d[2] = {QD, D_}, s[1] = {QD * 2}; cuuint32_t b[2] = {64, 128}; make_map(enc, &tm_wq, wq, 2, d, s, b); }
    { cuuint64_t d[2] = {DH, HKV * S_}, s[1] = {DH * 2}; cuuint32_t b[2] = {64, 128};
      make_map(enc, &tm_k, kc, 2, d, s, b); make_map(enc, &tm_v, vc, 2, d, s, b); }
    { cuuint64_t d[2] = {D_, QD}, s[1] = {D_ * 2}; cuuint32_t b[2] = {64, 128}; make_map(enc, &tm_wo, wo, 2, d, s, b); }
    { cuuint64_t d[3] = {256, 160, NCTA}, s[2] = {1024, 8 * WREG}; cuuint32_t b[3] = {256, 2, 8};
      make_map(enc, &tm_p, ((Scratch*)p_s)->frag, 3, d, s, b, CU_TENSOR_MAP_SWIZZLE_NONE, CU_TENSOR_MAP_DATA_TYPE_UINT32); }
    { cuuint64_t d[2] = {D_ / 4, S_}, s[1] = {D_ * 2}; cuuint32_t b[2] = {XP / 8, 16};
      make_map(enc, &tm_x, x, 2, d, s, b, CU_TENSOR_MAP_SWIZZLE_NONE, CU_TENSOR_MAP_DATA_TYPE_UINT64); }
    { cuuint64_t d[2] = {D_ / 4, F_}, s[1] = {D_ * 2}; cuuint32_t b[2] = {XP / 8, 18};
      make_map(enc, &tm_d, w_down, 2, d, s, b, CU_TENSOR_MAP_SWIZZLE_NONE, CU_TENSOR_MAP_DATA_TYPE_UINT64); }
    { cuuint64_t d[2] = {F_, D_}, s[1] = {F_ * 2}; cuuint32_t b[2] = {40, 24};
      make_map(enc, &tm_g, w_gate, 2, d, s, b, CU_TENSOR_MAP_SWIZZLE_NONE); make_map(enc, &tm_u, w_up, 2, d, s, b, CU_TENSOR_MAP_SWIZZLE_NONE); }

    cudaFuncSetAttribute(fused_kernel<true>, cudaFuncAttributeMaxDynamicSharedMemorySize, SM_TOTAL);
    cudaFuncSetAttribute(fused_kernel<false>, cudaFuncAttributeMaxDynamicSharedMemorySize, SM_TOTAL);
    cudaLaunchConfig_t cfg = {};
    cfg.gridDim = NCTA + 4; cfg.blockDim = 384; cfg.dynamicSmemBytes = SM_TOTAL;
    cudaLaunchAttribute at;
    at.id = cudaLaunchAttributeClusterDimension; at.val.clusterDim.x = 2; at.val.clusterDim.y = 1; at.val.clusterDim.z = 1;
    cfg.attrs = &at; cfg.numAttrs = 1;
    int ncl = 0;
    if (cudaOccupancyMaxActiveClusters(&ncl, fused_kernel<true>, &cfg) != cudaSuccess) { ncl = 0; cudaGetLastError(); }
    Args args{w_mod, cvec, (Scratch*)p_s, desc_lo(0, UNIT) | (0x40000040ull << 32), out, x, kc, vc, wq, wo, w_r, w_down};
    if (USE_SPARE && ncl >= NCTA / 2 + 2)
        fused_kernel<true><<<NCTA + 4, 384, SM_TOTAL>>>(args, tm_wq, tm_k, tm_v, tm_wo, tm_p, tm_x, tm_d, tm_g, tm_u);
    else
        fused_kernel<false><<<NCTA, 384, SM_TOTAL>>>(args, tm_wq, tm_k, tm_v, tm_wo, tm_p, tm_x, tm_d, tm_g, tm_u);
}
```

```cpp
#include <cuda_runtime.h>
#include <cuda_bf16.h>
#include <cuda.h>
#include <stdint.h>
#include <math.h>

typedef __nv_bfloat16 bf16;

constexpr int S_ = 2048;
constexpr int D_ = 576;
constexpr int HQ = 32, HKV = 16, DH = 128;
constexpr int F_ = 4608;
constexpr int QD = HQ * DH;

constexpr int NCTA = 128;
constexpr int WREG = 5 * 4096;
constexpr int CREP = 8;
constexpr int RSLOT = 192;
struct Scratch {
    unsigned int epoch[128];
    unsigned int flag_mod[NCTA];
    unsigned int flag_part[16 * 256];
    unsigned int flag_q3[16 * 32];
    unsigned int flag_h[NCTA * 32];
    uint2 mod1[640];
    uint32_t mod2[4 * D_];
    uint4 cand[CREP * NCTA * 2];
    uint2 ypart[72 * NCTA * 8];
    uint4 h[2][NCTA * 36 * 32];
    uint4 q3[NCTA * 8 * 128];
    uint4 rows[NCTA * 2 * RSLOT];
    uint8_t frag[NCTA * 8 * WREG];
    uint8_t keep[NCTA * 8 * 4096];
};
__device__ __align__(1024) Scratch g_s;
#define g_h gs->h[tag & 1]
#define g_q3 gs->q3
#define g_keep gs->keep
#define g_flag_h gs->flag_h
#define g_flag_part gs->flag_part
#define g_flag_mod gs->flag_mod
#define g_flag_q3 gs->flag_q3
#define g_frag gs->frag
#define g_cand gs->cand
#define g_ypart gs->ypart
#define g_rows gs->rows

#define DBG_INIT()
#define DBG_P(i)
#define DBG_PG(i)
#define DBG_T(i)
#define DBG_G(i)

__device__ __forceinline__ uint32_t pack_bf16(float lo, float hi) {
    uint32_t r;
    asm("cvt.rn.bf16x2.f32 %0, %1, %2;" : "=r"(r) : "f"(hi), "f"(lo));
    return r;
}
__device__ __forceinline__ float rbf(float x) { return __uint_as_float(pack_bf16(0.f, x)); }
__device__ __forceinline__ float bf_lo(uint32_t v) { return __uint_as_float(v << 16); }
__device__ __forceinline__ float bf_hi(uint32_t v) { return __uint_as_float(v & 0xffff0000u); }
__device__ __forceinline__ float ex2(float x) {
    float y;
    asm("ex2.approx.ftz.f32 %0, %1;" : "=f"(y) : "f"(x));
    return y;
}
template <class T>
__device__ __forceinline__ T* padd(T* p, uint32_t off) {
    unsigned long long r;
    asm("{\n.reg .b32 l, h;\nmov.b64 {l, h}, %1;\nadd.cc.u32 l, l, %2;\naddc.u32 h, h, 0;\nmov.b64 %0, {l, h};\n}" : "=l"(r) : "l"(p), "r"(off));
    return reinterpret_cast<T*>(r);
}
__device__ __forceinline__ uint32_t smem_u32(const void* p) { return (uint32_t)__cvta_generic_to_shared(p); }
__device__ __forceinline__ void mbar_init(uint32_t bar, uint32_t cnt) {
    asm volatile("mbarrier.init.shared::cta.b64 [%0], %1;" ::"r"(bar), "r"(cnt) : "memory");
}
__device__ __forceinline__ void mbar_expect_tx(uint32_t bar, uint32_t bytes) {
    asm volatile("mbarrier.arrive.expect_tx.shared::cta.b64 _, [%0], %1;" ::"r"(bar), "r"(bytes) : "memory");
}
__device__ __forceinline__ void mbar_arrive(uint32_t bar) {
    asm volatile("mbarrier.arrive.shared::cta.b64 _, [%0];" ::"r"(bar) : "memory");
}
__device__ __forceinline__ void arrive_if(uint32_t bar, bool on) {
    asm volatile("{\n.reg .pred p;\nsetp.ne.b32 p, %1, 0;\n@p mbarrier.arrive.shared::cta.b64 _, [%0];\n}" ::"r"(bar), "r"((uint32_t)on) : "memory");
}
__device__ __forceinline__ void mbar_arrive_cluster(uint32_t cluster_addr) {
    asm volatile("mbarrier.arrive.shared::cluster.b64 _, [%0];" ::"r"(cluster_addr) : "memory");
}
constexpr uint32_t SPIN = 1u << 20;
__device__ __forceinline__ void mbar_wait(uint32_t bar, uint32_t parity) {
    asm volatile("{\n.reg .pred p;\n.reg .b32 c;\nmov.b32 c, 0;\n"
                 "W_%=:\nmbarrier.try_wait.parity.shared::cta.b64 p, [%0], %1;\n"
                 "add.u32 c, c, 1;\nsetp.lt.and.u32 p, c, 0x100000, !p;\n@p bra W_%=;\n}"
                 ::"r"(bar), "r"(parity) : "memory");
}
__device__ __forceinline__ void anchor(uint32_t addr, float v) {
    asm volatile("{\n.reg .pred p;\nsetp.lt.f32 p, %1, 0f00000000;\n@p st.volatile.shared.f32 [%0], %1;\n}" ::"r"(addr), "f"(v) : "memory");
}
__device__ __forceinline__ void anchor(uint32_t addr, uint32_t v) {
    asm volatile("{\n.reg .pred p;\nsetp.eq.u32 p, %1, 0xffffffff;\n@p st.volatile.shared.u32 [%0], %1;\n}" ::"r"(addr), "r"(v) : "memory");
}
__device__ __forceinline__ void anchor(void* p, uint32_t v) {
    asm volatile("{\n.reg .pred p;\nsetp.eq.u32 p, %1, 0xffffffff;\n@p st.volatile.u32 [%0], %1;\n}" ::"l"(p), "r"(v) : "memory");
}
__device__ __forceinline__ void hold(float& a, float& b) {
    asm volatile("{\n.reg .pred p;\n.reg .b64 t;\n.reg .b32 l, h;\nmov.u64 t, %%clock64;\nmov.b64 {l, h}, t;\nsetp.eq.u32 p, h, 0xffffffff;\n"
                 "@p mov.f32 %0, 0f00000000;\n@p mov.f32 %1, 0f00000000;\n}" : "+f"(a), "+f"(b) :: "memory");
}
__device__ __forceinline__ void mbar_wait_sleep(uint32_t bar, uint32_t parity) {
    asm volatile("{\n.reg .pred p;\n.reg .b32 c;\nmov.b32 c, 0;\n"
                 "W_%=:\nmbarrier.try_wait.parity.shared::cta.b64 p, [%0], %1, 5000;\n"
                 "add.u32 c, c, 1;\nsetp.lt.and.u32 p, c, 0x20000, !p;\n@p bra W_%=;\n}"
                 ::"r"(bar), "r"(parity) : "memory");
}
__device__ __forceinline__ uint32_t load_tag(const Scratch* gs) {
    uint32_t tag;
    asm volatile("ld.global.ca.u32 %0, [%1];" : "=r"(tag) : "l"(gs->epoch) : "memory");
    return tag + 1;
}
__device__ __forceinline__ uint4 ld_relaxed(const uint4* p) {
    uint4 v;
    asm volatile("ld.relaxed.gpu.global.v4.u32 {%0,%1,%2,%3}, [%4];" : "=r"(v.x), "=r"(v.y), "=r"(v.z), "=r"(v.w) : "l"(p) : "memory");
    return v;
}
__device__ __forceinline__ void st_relaxed(uint4* p, uint32_t a, uint32_t b, uint32_t c, uint32_t d) {
    asm volatile("{\n.reg .b64 u, v;\nmov.b64 u, {%1, %2};\nmov.b64 v, {%3, %4};\nst.relaxed.gpu.global.v2.b64 [%0], {u, v};\n}"
                 ::"l"(p), "r"(a), "r"(b), "r"(c), "r"(d) : "memory");
}
__device__ __forceinline__ void st_relaxed4(void* p, uint32_t a, uint32_t b, uint32_t c, uint32_t d) {
    asm volatile("st.relaxed.gpu.global.v4.u32 [%0], {%1, %2, %3, %4};" ::"l"(p), "r"(a), "r"(b), "r"(c), "r"(d) : "memory");
}
__device__ __forceinline__ uint2 ld_relaxed64(const uint2* p) {
    uint2 v;
    asm volatile("{\n.reg .b64 u;\nld.relaxed.gpu.global.b64 u, [%2];\nmov.b64 {%0, %1}, u;\n}" : "=r"(v.x), "=r"(v.y) : "l"(p) : "memory");
    return v;
}
__device__ __forceinline__ void st_relaxed64(uint2* p, uint32_t a, uint32_t b) {
    asm volatile("{\n.reg .b64 u;\nmov.b64 u, {%1, %2};\nst.relaxed.gpu.global.b64 [%0], u;\n}" ::"l"(p), "r"(a), "r"(b) : "memory");
}
__device__ __forceinline__ uint4 ld_relaxed2(const uint4* p) {
    uint4 v;
    asm volatile("{\n.reg .b64 u, w;\nld.relaxed.gpu.global.v2.b64 {u, w}, [%4];\nmov.b64 {%0, %1}, u;\nmov.b64 {%2, %3}, w;\n}"
                 : "=r"(v.x), "=r"(v.y), "=r"(v.z), "=r"(v.w) : "l"(p) : "memory");
    return v;
}
__device__ __forceinline__ void reload16(uint4& v, const void* p, uint32_t& miss) {
    asm volatile("{\n.reg .pred p;\n.reg .b32 m;\n.reg .b64 u, w;\nmax.u32 m, %0, %2;\nsetp.eq.u32 p, m, 0xffffffff;\n"
                 "mov.b64 u, {%0, %1};\nmov.b64 w, {%2, %3};\n@p ld.relaxed.gpu.global.v2.b64 {u, w}, [%5];\n"
                 "mov.b64 {%0, %1}, u;\nmov.b64 {%2, %3}, w;\n@p mov.u32 %4, 1;\n}"
                 : "+r"(v.x), "+r"(v.y), "+r"(v.z), "+r"(v.w), "+r"(miss) : "l"(p) : "memory");
}
__device__ __forceinline__ void reload8(uint2& v, const void* p, uint32_t& miss) {
    asm volatile("{\n.reg .pred p;\n.reg .b64 u;\nsetp.eq.u32 p, %0, 0xffffffff;\nmov.b64 u, {%0, %1};\n"
                 "@p ld.relaxed.gpu.global.b64 u, [%3];\nmov.b64 {%0, %1}, u;\n@p mov.u32 %2, 1;\n}"
                 : "+r"(v.x), "+r"(v.y), "+r"(miss) : "l"(p) : "memory");
}
__device__ __forceinline__ uint32_t ld_relaxed32(const void* p) {
    uint32_t v;
    asm volatile("ld.relaxed.gpu.global.u32 %0, [%1];" : "=r"(v) : "l"(p) : "memory");
    return v;
}
__device__ __forceinline__ void flag_wait(const unsigned int* p, uint32_t tag) {
    uint32_t v, it = 0;
#pragma unroll 1
    do {
        asm volatile("ld.relaxed.gpu.global.u32 %0, [%1];" : "=r"(v) : "l"(p) : "memory");
    } while (__any_sync(0xffffffffu, v != tag) && ++it < SPIN / 16);
    asm volatile("fence.acquire.gpu;" ::: "memory");
    __syncwarp();
}
__device__ __forceinline__ bool elect() {
    uint32_t p;
    asm volatile("{\n.reg .pred p;\nelect.sync _|p, 0xffffffff;\nselp.u32 %0, 1, 0, p;\n}" : "=r"(p));
    return p;
}
__device__ __forceinline__ void flag_release(unsigned int* p, uint32_t tag) {
    asm volatile("st.release.gpu.global.u32 [%0], %1;" ::"l"(p), "r"(tag) : "memory");
}
__device__ __forceinline__ uint32_t touch(const void* p) {
    uint32_t v;
    asm volatile("ld.global.nc.L1::no_allocate.L2::128B.u32 %0, [%1];" : "=r"(v) : "l"(p));
    return v;
}
__device__ __forceinline__ void bar_sync(int id, int n) { asm volatile("bar.sync %0, %1;" ::"r"(id), "r"(n) : "memory"); }
__device__ __forceinline__ void bar_arrive(int id, int n) { asm volatile("bar.arrive %0, %1;" ::"r"(id), "r"(n) : "memory"); }

constexpr uint64_t EVICT_NORMAL = 0x1000000000000000ull, EVICT_FIRST = 0x12F0000000000000ull;
__device__ __forceinline__ void tma2d(uint32_t dst, const CUtensorMap* m, int c0, int c1, uint32_t bar) {
    asm volatile("cp.async.bulk.tensor.2d.shared::cluster.global.mbarrier::complete_tx::bytes.L2::cache_hint [%0], [%1, {%3, %4}], [%2], %5;"
                 ::"r"(dst), "l"(m), "r"(bar), "r"(c0), "r"(c1), "l"(EVICT_FIRST) : "memory");
}
__device__ __forceinline__ void tma2d_mc(uint32_t dst, const CUtensorMap* m, int c0, int c1, uint32_t bar, uint64_t pol) {
    asm volatile("cp.async.bulk.tensor.2d.shared::cluster.global.mbarrier::complete_tx::bytes.multicast::cluster.L2::cache_hint [%0], [%1, {%3, %4}], [%2], %5, %6;"
                 ::"r"(dst), "l"(m), "r"(bar), "r"(c0), "r"(c1), "h"((uint16_t)3), "l"(pol) : "memory");
}
__device__ __forceinline__ void tma3d(uint32_t dst, const CUtensorMap* m, int c0, int c1, int c2, uint32_t bar) {
    asm volatile("cp.async.bulk.tensor.3d.shared::cluster.global.mbarrier::complete_tx::bytes.L2::cache_hint [%0], [%1, {%3, %4, %5}], [%2], %6;"
                 ::"r"(dst), "l"(m), "r"(bar), "r"(c0), "r"(c1), "r"(c2), "l"(EVICT_FIRST) : "memory");
}
__device__ __forceinline__ void bulk_load(uint32_t dst, const void* src, uint32_t bytes, uint32_t bar) {
    asm volatile("cp.async.bulk.shared::cluster.global.mbarrier::complete_tx::bytes [%0], [%1], %2, [%3];"
                 ::"r"(dst), "l"(src), "r"(bytes), "r"(bar) : "memory");
}
__device__ __forceinline__ void l2_prefetch(const void* src, uint32_t bytes) {
    asm volatile("cp.async.bulk.prefetch.L2.global [%0], %1;" ::"l"(src), "r"(bytes) : "memory");
}
__device__ __forceinline__ uint32_t bmul2(uint32_t a, uint32_t b) { uint32_t r; asm("mul.rn.bf16x2 %0, %1, %2;" : "=r"(r) : "r"(a), "r"(b)); return r; }
__device__ __forceinline__ uint32_t badd2(uint32_t a, uint32_t b) { uint32_t r; asm("add.rn.bf16x2 %0, %1, %2;" : "=r"(r) : "r"(a), "r"(b)); return r; }
__device__ __forceinline__ uint32_t bsub2(uint32_t a, uint32_t b) { uint32_t r; asm("sub.rn.bf16x2 %0, %1, %2;" : "=r"(r) : "r"(a), "r"(b)); return r; }
__device__ __forceinline__ uint32_t bmax2(uint32_t a, uint32_t b) { uint32_t r; asm("max.bf16x2 %0, %1, %2;" : "=r"(r) : "r"(a), "r"(b)); return r; }
__device__ __forceinline__ uint4 lds128(uint32_t a) { uint4 v; asm volatile("ld.shared.v4.u32 {%0,%1,%2,%3}, [%4];" : "=r"(v.x), "=r"(v.y), "=r"(v.z), "=r"(v.w) : "r"(a) : "memory"); return v; }
__device__ __forceinline__ uint2 lds64(uint32_t a) { uint2 v; asm volatile("ld.shared.v2.u32 {%0,%1}, [%2];" : "=r"(v.x), "=r"(v.y) : "r"(a) : "memory"); return v; }
__device__ __forceinline__ uint32_t lds32(uint32_t a) { uint32_t v; asm volatile("ld.shared.u32 %0, [%1];" : "=r"(v) : "r"(a) : "memory"); return v; }
__device__ __forceinline__ uint4 ldsm4(uint32_t a) {
    uint4 v;
    asm volatile("ldmatrix.sync.aligned.m8n8.x4.shared.b16 {%0,%1,%2,%3}, [%4];" : "=r"(v.x), "=r"(v.y), "=r"(v.z), "=r"(v.w) : "r"(a) : "memory");
    return v;
}
__device__ __forceinline__ uint4 ldsm4t(uint32_t a) {
    uint4 v;
    asm volatile("ldmatrix.sync.aligned.m8n8.x4.trans.shared.b16 {%0,%1,%2,%3}, [%4];" : "=r"(v.x), "=r"(v.y), "=r"(v.z), "=r"(v.w) : "r"(a) : "memory");
    return v;
}
__device__ __forceinline__ void mma1688(float* d, uint32_t a0, uint32_t a1, uint32_t b) {
    asm("mma.sync.aligned.m16n8k8.row.col.f32.bf16.bf16.f32 {%0,%1,%2,%3}, {%4,%5}, {%6}, {%0,%1,%2,%3};"
        : "+f"(d[0]), "+f"(d[1]), "+f"(d[2]), "+f"(d[3]) : "r"(a0), "r"(a1), "r"(b));
}
__device__ __forceinline__ void mma16816(float* d, uint32_t a0, uint32_t a1, uint32_t a2, uint32_t a3, uint32_t b0, uint32_t b1) {
    asm("mma.sync.aligned.m16n8k16.row.col.f32.bf16.bf16.f32 {%0,%1,%2,%3}, {%4,%5,%6,%7}, {%8,%9}, {%0,%1,%2,%3};"
                 : "+f"(d[0]), "+f"(d[1]), "+f"(d[2]), "+f"(d[3]) : "r"(a0), "r"(a1), "r"(a2), "r"(a3), "r"(b0), "r"(b1));
}
__device__ __forceinline__ void stsm_x4(uint32_t addr, uint32_t a, uint32_t b, uint32_t c, uint32_t d) {
    asm volatile("stmatrix.sync.aligned.m8n8.x4.shared.b16 [%0], {%1, %2, %3, %4};"
                 ::"r"(addr), "r"(a), "r"(b), "r"(c), "r"(d) : "memory");
}

__device__ __forceinline__ uint64_t mkdesc(uint32_t addr, uint32_t lbo, uint32_t sbo) {
    return (uint64_t)((addr & 0x3FFFF) >> 4) | ((uint64_t)(lbo >> 4) << 16) | ((uint64_t)(sbo >> 4) << 32) | (1ull << 62);
}
constexpr uint32_t SM0 = 1024;
__host__ __device__ constexpr uint32_t desc_lo(uint32_t off, uint32_t lbo) { return ((SM0 + off) >> 4) | ((lbo >> 4) << 16); }
#define WG_FENCE() asm volatile("wgmma.fence.sync.aligned;" ::: "memory")
#define WG_COMMIT() asm volatile("wgmma.commit_group.sync.aligned;" ::: "memory")
#define WG_WAIT(n) asm volatile("wgmma.wait_group.sync.aligned %0;" ::"n"(n) : "memory")

#define F8(a, i) "+f"(a[i]), "+f"(a[i + 1]), "+f"(a[i + 2]), "+f"(a[i + 3]), "+f"(a[i + 4]), "+f"(a[i + 5]), "+f"(a[i + 6]), "+f"(a[i + 7])
#define F16(a, i) F8(a, i), F8(a, i + 8)
#define F64(a) F16(a, 0), F16(a, 16), F16(a, 32), F16(a, 48)
#define F32(a) F16(a, 0), F16(a, 16)
#define L64 "%0,%1,%2,%3,%4,%5,%6,%7,%8,%9,%10,%11,%12,%13,%14,%15,%16,%17,%18,%19,%20,%21,%22,%23,%24,%25,%26,%27,%28,%29,%30,%31,%32,%33,%34,%35,%36,%37,%38,%39,%40,%41,%42,%43,%44,%45,%46,%47,%48,%49,%50,%51,%52,%53,%54,%55,%56,%57,%58,%59,%60,%61,%62,%63"
#define L32 "%0,%1,%2,%3,%4,%5,%6,%7,%8,%9,%10,%11,%12,%13,%14,%15,%16,%17,%18,%19,%20,%21,%22,%23,%24,%25,%26,%27,%28,%29,%30,%31"

template <int TB, int STEP = 128>
__device__ __forceinline__ void mma_rs128(float (&d)[64], uint32_t a0, uint32_t a1, uint32_t a2, uint32_t a3, uint64_t& b, int acc) {
    asm volatile("{\n.reg .pred p;\nsetp.ne.b32 p, %69, 0;\n"
                 "wgmma.mma_async.sync.aligned.m64n128k16.f32.bf16.bf16 {" L64 "}, {%65,%66,%67,%68}, %64, p, 1, 1, %70;\nadd.s64 %64, %64, %71;\n}"
                 : F64(d), "+l"(b) : "r"(a0), "r"(a1), "r"(a2), "r"(a3), "r"(acc), "n"(TB), "n"(STEP));
}
template <int TB>
__device__ __forceinline__ void mma_rs64(float (&d)[32], uint32_t a0, uint32_t a1, uint32_t a2, uint32_t a3, uint64_t& b, int acc) {
    asm volatile("{\n.reg .pred p;\nsetp.ne.b32 p, %37, 0;\n"
                 "wgmma.mma_async.sync.aligned.m64n64k16.f32.bf16.bf16 {" L32 "}, {%33,%34,%35,%36}, %32, p, 1, 1, %38;\nadd.s64 %32, %32, 128;\n}"
                 : F32(d), "+l"(b) : "r"(a0), "r"(a1), "r"(a2), "r"(a3), "r"(acc), "n"(TB));
}
template <int N>
__device__ __forceinline__ void fence_regs(float (&d)[N]) {
#pragma unroll
    for (int i = 0; i < N; i++) asm volatile("" : "+f"(d[i])::"memory");
}
template <int N>
__device__ __forceinline__ void fence_regs(uint32_t (&d)[N]) {
#pragma unroll
    for (int i = 0; i < N; i++) asm volatile("" : "+r"(d[i])::"memory");
}

template <int V> struct IC { static constexpr int value = V; };

constexpr int SLOT = 32768, UNIT = 16384;
constexpr int SM_Q = 4 * SLOT;
constexpr int SM_BAR = 7 * SLOT;
constexpr int SM_RED = SM_BAR + 512;
constexpr int SM_TOTAL = SM_BAR + 3072;
constexpr int XP = D_ * 2 + 16;
constexpr int M_MOD = 16 * XP;
constexpr int SM_T = SM_Q + 2 * D_ * 80, SM_TC = SM_T + D_ * 4, SM_TG = SM_TC + D_ * 4, SM_TS = SM_TG + D_ * 2;
constexpr float CS = 0.08838834764831845f * 1.4426950408889634f;
#define USE_SPARE 1
constexpr float POFF = 102.f, LMIN = 0x1p-104f;
#define LMAX 0.5f
constexpr int SPLIT = 10;
constexpr int STAGE = 11;
constexpr int ESPLIT = 3;
constexpr int QSPLIT = 4, OSPLIT = 6;
constexpr int WF0 = 3, WF1 = 10, WF2 = 19, DL = 9;
constexpr int PF_KV = 8;
constexpr int PF_WO = 50, PF_O = 60;

__device__ __forceinline__ int cluster_role() {
    int k;
    asm volatile("mov.u32 %0, %%ctaid.x;" : "=r"(k));
    const int c = (k & 1) << 6;
    k >>= 1;
    const int r = ((k - 36) * 37) >> 8, i = k - 36 - r * 7;
    return c + (k < 4 ? 12 + k : k < 36 ? ((k - 4) & 7) * 8 + ((k - 4) >> 3) : (i + (i > 0)) * 8 + ((4 + r) & 7));
}

struct Args {
    const bf16 *w_mod, *cvec;
    Scratch* gs;
    uint64_t d0;
    bf16* out;
    const bf16 *x, *kc, *vc, *wq, *wo, *w_r, *w_down;
};

__device__ __forceinline__ void frag_store(uint8_t* p, const uint32_t (&a)[32]) {
#pragma unroll
    for (int i = 0; i < 8; i++)
        __stcg(reinterpret_cast<uint4*>(p + i * 512), make_uint4(a[4 * i], a[4 * i + 1], a[4 * i + 2], a[4 * i + 3]));
}
template <int LO = 0, int HI = 8>
__device__ __forceinline__ void frag_load(uint32_t (&a)[32], const uint8_t* p) {
#pragma unroll
    for (int i = LO; i < HI; i++) {
        const uint4 v = ld_relaxed(reinterpret_cast<const uint4*>(p + i * 512));
        a[4 * i] = v.x; a[4 * i + 1] = v.y; a[4 * i + 2] = v.z; a[4 * i + 3] = v.w;
    }
}
__device__ __forceinline__ float quad_sum(float v) {
    v += __shfl_xor_sync(0xffffffffu, v, 1);
    return v + __shfl_xor_sync(0xffffffffu, v, 2);
}
__device__ __forceinline__ float quad_max(float v) {
    v = fmaxf(v, __shfl_xor_sync(0xffffffffu, v, 1));
    return fmaxf(v, __shfl_xor_sync(0xffffffffu, v, 2));
}
__device__ __forceinline__ float rcp_fast(float x) { float y; asm("rcp.approx.ftz.f32 %0, %1;" : "=f"(y) : "f"(x)); return y; }
__device__ __forceinline__ float sigmoidf_(float x) { return rcp_fast(1.f + ex2(-1.4426950408889634f * x)); }
__device__ __forceinline__ void top2(uint32_t k, uint32_t& k1, uint32_t& k2) {
    k1 = __reduce_max_sync(0xffffffffu, k);
    k2 = __reduce_max_sync(0xffffffffu, k == k1 ? 0 : k);
}

__device__ __forceinline__ void mod_fma(float (&a)[8], const uint4 w, float sc) {
    a[0] += sc * bf_lo(w.x); a[1] += sc * bf_hi(w.x); a[2] += sc * bf_lo(w.y); a[3] += sc * bf_hi(w.y);
    a[4] += sc * bf_lo(w.z); a[5] += sc * bf_hi(w.z); a[6] += sc * bf_lo(w.w); a[7] += sc * bf_hi(w.w);
}
__device__ __forceinline__ float mod_reduce(float (&a)[8], int lane) {
#pragma unroll
    for (int h = 4; h > 0; h >>= 1) {
        const bool up = lane & (8 / h);
#pragma unroll
        for (int i = 0; i < h; i++)
            a[i] = (up ? a[i + h] : a[i]) + __shfl_xor_sync(0xffffffffu, up ? a[i] : a[i + h], 8 / h);
    }
    return a[0] + __shfl_xor_sync(0xffffffffu, a[0], 16);
}

__device__ __forceinline__ float ln_stats(float sum, float sq, uint32_t& mean2) {
    const float mean = sum * (1.f / D_);
    const float var = fmaxf(fmaf(-mean, mean, sq * (1.f / D_)), 0.f);
    float sd;
    asm("sqrt.approx.ftz.f32 %0, %1;" : "=f"(sd) : "f"(rbf(rbf(var) + 1e-5f)));
    mean2 = pack_bf16(mean, mean);
    return rcp_fast(rbf(sd));
}
__device__ __forceinline__ uint32_t ln_pair(uint32_t x, uint32_t mean2, float rsd) {
    const uint32_t d = bsub2(x, mean2);
    return pack_bf16(bf_lo(d) * rsd, bf_hi(d) * rsd);
}
__device__ __forceinline__ void rows_load(uint32_t (&x)[20], uint32_t xs, int cw) {
#pragma unroll
    for (int ch = 0; ch < 5; ch++) {
        const uint4 v = ldsm4(ch < 4 ? xs + ch * 256 : xs + 1024 - cw * 16);
        x[4 * ch] = v.x; x[4 * ch + 1] = v.y; x[4 * ch + 2] = v.z; x[4 * ch + 3] = v.w;
    }
}
__device__ __forceinline__ void stats_add(float (&st)[12], uint32_t a, uint32_t b, uint32_t w) {
    mma1688(st, a, b, w);
    mma1688(st + 4, a, b, a);
    mma1688(st + 8, a, b, b);
}
__device__ __forceinline__ float rows_stats(const float (&st)[12], float4* rec, int cw, int lane, uint32_t& mean2, float& dot) {
    const int g8 = lane >> 2;
    if ((g8 >> 1) == (lane & 3)) {
        rec[cw * 16 + g8] = make_float4(st[0], (g8 & 1) ? st[5] : st[4], st[1], 0.f);
        rec[cw * 16 + 8 + g8] = make_float4(st[2], (g8 & 1) ? st[11] : st[10], st[3], 0.f);
    }
    bar_sync(3, 256);
    const float4* r = rec + (lane >> 4) * 64 + (lane & 15);
    const float4 s0 = r[0], s1 = r[16], s2 = r[32], s3 = r[48];
    const float sum = (s0.x + s1.x) + (s2.x + s3.x), sq = (s0.y + s1.y) + (s2.y + s3.y);
    dot = (s0.z + s1.z) + (s2.z + s3.z);
    dot += __shfl_xor_sync(0xffffffffu, dot, 16);
    return ln_stats(sum + __shfl_xor_sync(0xffffffffu, sum, 16), sq + __shfl_xor_sync(0xffffffffu, sq, 16), mean2);
}
template <class F>
__device__ __forceinline__ void rows_normalise(uint32_t* y, const uint32_t* x, uint32_t mean2, float rsd, int lane, F loads) {
    const int g8 = lane >> 2;
    const uint32_t ma2 = __shfl_sync(0xffffffffu, mean2, g8), mb2 = __shfl_sync(0xffffffffu, mean2, g8 + 8);
    const float ra = __shfl_sync(0xffffffffu, rsd, g8), rb = __shfl_sync(0xffffffffu, rsd, g8 + 8);
    loads();
#pragma unroll
    for (int k = 0; k < 9; k++) { y[2 * k] = ln_pair(x[2 * k], ma2, ra); y[2 * k + 1] = ln_pair(x[2 * k + 1], mb2, rb); }
}

__device__ __forceinline__ uint4 h_frag(const uint4* hf, int ks, int lane) {
    if (ks < 32) return ld_relaxed2(hf + ks * 32);
    const uint2* p = reinterpret_cast<const uint2*>(padd(hf, 256 - lane * 8) + ks * 32 - 16);
    const uint2 a = ld_relaxed64(p), b = ld_relaxed64(p + 32);
    return make_uint4(a.x, a.y, b.x, b.y);
}

__device__ __noinline__ void attn_fallback(uint32_t bad, uint32_t tag, const Scratch* gs, uint8_t* frag, uint8_t* keep, const bf16* wq, const bf16* kc, const bf16* vc) {
  const int lane = threadIdx.x & 31, g8 = lane >> 2, qd = lane & 3;
  const int role = cluster_role(), j = role & 7, qb = (role >> 2 & 14) + (role >> 6);
  const uint4* hf = g_h + (size_t)(qb * 8 + (threadIdx.x >> 5) - 4) * (36 * 32) + lane;
#pragma unroll 1
  for (int t = 0; t < 4; t++) {
    if (!((bad >> t) & 1)) continue;
    const bf16 *wqp = wq + (4 * j + t) * DH, *kp = kc + (size_t)(2 * j + (t >> 1)) * S_ * DH, *vp = vc + (size_t)(2 * j + (t >> 1)) * S_ * DH;
    uint32_t q[32];
    float o[64];
#pragma unroll
    for (int i = 0; i < 64; i++) o[i] = 0.f;
#pragma unroll 1
    for (int ks = 0; ks < 36; ks++) {
        const uint4 a = h_frag(hf, ks, lane);
        const unsigned short* wr = reinterpret_cast<const unsigned short*>(wqp + (size_t)(ks * 16 + 2 * qd) * QD + g8);
#pragma unroll
        for (int dt = 0; dt < 16; dt++) {
            const uint32_t b0 = __ldg(wr + dt * 8) | ((uint32_t)__ldg(wr + dt * 8 + QD) << 16);
            const uint32_t b1 = __ldg(wr + dt * 8 + 8 * QD) | ((uint32_t)__ldg(wr + dt * 8 + 9 * QD) << 16);
            mma16816(o + 4 * dt, a.x, a.y, a.z, a.w, b0, b1);
        }
    }
#pragma unroll
    for (int i = 0; i < 32; i++) q[i] = pack_bf16(o[2 * i], o[2 * i + 1]);
#pragma unroll
    for (int i = 0; i < 64; i++) o[i] = 0.f;
    float m0 = -INFINITY, m1 = -INFINITY, l0 = 0.f, l1 = 0.f;
#pragma unroll 1
    for (int key = 0; key < S_; key += 16) {
        float sc[8];
#pragma unroll
        for (int i = 0; i < 8; i++) sc[i] = 0.f;
#pragma unroll
        for (int nt = 0; nt < 2; nt++) {
            const uint32_t* kr = reinterpret_cast<const uint32_t*>(kp + (size_t)(key + nt * 8 + g8) * DH) + qd;
#pragma unroll
            for (int ks = 0; ks < 8; ks++)
                mma16816(sc + 4 * nt, q[4 * ks], q[4 * ks + 1], q[4 * ks + 2], q[4 * ks + 3], __ldg(kr + ks * 8), __ldg(kr + ks * 8 + 4));
        }
        const float n0 = quad_max(fmaxf(fmaxf(m0, fmaxf(sc[0], sc[1])), fmaxf(sc[4], sc[5])));
        const float n1 = quad_max(fmaxf(fmaxf(m1, fmaxf(sc[2], sc[3])), fmaxf(sc[6], sc[7])));
        const float f0 = ex2((m0 - n0) * CS), f1 = ex2((m1 - n1) * CS);
        m0 = n0; m1 = n1;
#pragma unroll
        for (int i = 0; i < 8; i++) sc[i] = ex2((sc[i] - ((i & 2) ? n1 : n0)) * CS);
        l0 = l0 * f0 + (sc[0] + sc[1]) + (sc[4] + sc[5]);
        l1 = l1 * f1 + (sc[2] + sc[3]) + (sc[6] + sc[7]);
        const uint32_t e0 = pack_bf16(sc[0], sc[1]), e1 = pack_bf16(sc[2], sc[3]), e2 = pack_bf16(sc[4], sc[5]), e3 = pack_bf16(sc[6], sc[7]);
        const unsigned short* vr = reinterpret_cast<const unsigned short*>(vp + (size_t)(key + 2 * qd) * DH + g8);
#pragma unroll
        for (int dt = 0; dt < 16; dt++) {
            o[4 * dt] *= f0; o[4 * dt + 1] *= f0; o[4 * dt + 2] *= f1; o[4 * dt + 3] *= f1;
            const uint32_t b0 = __ldg(vr + dt * 8) | ((uint32_t)__ldg(vr + dt * 8 + DH) << 16);
            const uint32_t b1 = __ldg(vr + dt * 8 + 8 * DH) | ((uint32_t)__ldg(vr + dt * 8 + 9 * DH) << 16);
            mma16816(o + 4 * dt, e0, e1, e2, e3, b0, b1);
        }
    }
    const float i0 = 1.f / quad_sum(l0), i1 = 1.f / quad_sum(l1);
#pragma unroll
    for (int i = 0; i < 16; i++) {
        q[2 * i] = pack_bf16(o[4 * i] * i0, o[4 * i + 1] * i0);
        q[2 * i + 1] = pack_bf16(o[4 * i + 2] * i1, o[4 * i + 3] * i1);
    }
    frag_store(t < 3 ? frag + t * 4096 : keep, q);
  }
}

__device__ __forceinline__ void spare_q3(Scratch* gs, uint32_t sb, uint32_t bar_full, uint32_t bar_empty, int lane, int cw) {
    const uint32_t tag = load_tag(gs);
    uint32_t rel_base, e = 3;
    asm("mapa.shared::cluster.u32 %0, %1, %2;" : "=r"(rel_base) : "r"(bar_empty), "r"(lane & 1));
#pragma unroll 1
    for (int qb = blockIdx.x - NCTA; qb < 16; qb += 4) {
        uint32_t h[144];
        float o[64];
        flag_wait(&g_flag_h[(qb * 8 + cw) * 32], tag);
        const uint4* hf = g_h + (size_t)(qb * 8 + cw) * (36 * 32) + lane;
#pragma unroll
        for (int ks = 0; ks < 36; ks++) {
            const uint4 v = h_frag(hf, ks, lane);
            h[4 * ks] = v.x; h[4 * ks + 1] = v.y; h[4 * ks + 2] = v.z; h[4 * ks + 3] = v.w;
        }
#pragma unroll
        for (int i = 0; i < 64; i++) o[i] = 0.f;
#pragma unroll 1
        for (int v = 0; v < 4; v++) {
            fence_regs(o);
#pragma unroll
            for (int t = 0; t < 5; t++) {
                mbar_wait(bar_full + 8 * (e & 3), (e >> 2) & 1);
                uint64_t dv = mkdesc(sb + (e & 3) * SLOT, UNIT, 1024);
                WG_FENCE();
#pragma unroll
                for (int ks = 0; ks < (t < 4 ? 8 : 4); ks++)
                    mma_rs128<1>(o, h[32 * t + 4 * ks], h[32 * t + 4 * ks + 1], h[32 * t + 4 * ks + 2], h[32 * t + 4 * ks + 3], dv, ks | t);
                WG_COMMIT();
                if (t > 0) { WG_WAIT(1); if (lane < 2) mbar_arrive_cluster(rel_base + 8 * ((e - 1) & 3)); }
                e++;
            }
            WG_WAIT(0);
            fence_regs(o);
            if (lane < 2) mbar_arrive_cluster(rel_base + 8 * ((e - 1) & 3));
            uint4* dst = &g_q3[((qb * 8 + 2 * v) * 8 + cw) * 128 + lane];
#pragma unroll
            for (int i = 0; i < 8; i++)
                __stcg(dst + (i >> 2) * 1024 + (i & 3) * 32, make_uint4(pack_bf16(o[8 * i], o[8 * i + 1]), pack_bf16(o[8 * i + 2], o[8 * i + 3]),
                                                                        pack_bf16(o[8 * i + 4], o[8 * i + 5]), pack_bf16(o[8 * i + 6], o[8 * i + 7])));
        }
        bar_sync(3, 256);
        if (cw == 0 && lane == 0) flag_release(&g_flag_q3[qb * 32], tag);
        __syncwarp();
    }
}

template <bool SPARE>
__global__ void __cluster_dims__(2, 1, 1) __launch_bounds__(384, 1)
fused_kernel(const Args args, const __grid_constant__ CUtensorMap tm_wq,
             const __grid_constant__ CUtensorMap tm_k, const __grid_constant__ CUtensorMap tm_v,
             const __grid_constant__ CUtensorMap tm_wo, const __grid_constant__ CUtensorMap tm_p,
             const __grid_constant__ CUtensorMap tm_x, const __grid_constant__ CUtensorMap tm_d,
             const __grid_constant__ CUtensorMap tm_g, const __grid_constant__ CUtensorMap tm_u) {
    extern __shared__ __align__(1024) uint8_t smem_raw[];
    const uint32_t sb = smem_u32(smem_raw);
    Scratch* const gs = args.gs;
    const uint32_t bar_full = sb + SM_BAR;
    const uint32_t bar_g = bar_full + 8 * 4;
    const uint32_t bar_mod = bar_g + 8;
    const uint32_t bar_go = bar_mod + 8;
    const uint32_t bar_x = bar_go + 40;
    const uint32_t bar_empty = bar_x + 8;
    const uint32_t bar_pub = bar_empty + 8 * 4;
    const uint32_t bar_qfree = bar_pub + 32;
    const uint32_t bar_out = bar_qfree + 24;
    const uint32_t bar_q3 = bar_out + 8;
    const uint32_t bar_pre = bar_q3 + 16;
    const uint32_t bar_w0 = bar_q3 + 8;
    constexpr int E0 = SPARE ? 2 : 0;

#define ROLES() const int role = cluster_role(), c = role >> 6, j = role & 7, qb = (role >> 2 & 14) + c, rg = qb * 8 + j; uint32_t bx; asm volatile("mov.u32 %0, %%ctaid.x;" : "=r"(bx))
    const int warp = __shfl_sync(0xffffffffu, threadIdx.x >> 5, 0);

    if (SPARE && blockIdx.x >= NCTA && warp >= 4) {
        asm volatile("barrier.cluster.arrive.relaxed.aligned;" ::: "memory");
        asm volatile("setmaxnreg.inc.sync.aligned.u32 240;");
        asm volatile("barrier.cluster.wait.aligned;" ::: "memory");
        spare_q3(gs, sb, bar_full, bar_empty, threadIdx.x & 31, warp - 4);
        asm volatile("barrier.cluster.arrive.relaxed.aligned;\nbarrier.cluster.wait.aligned;" ::: "memory");
    } else if (warp < 4) {
        asm volatile("setmaxnreg.dec.sync.aligned.u32 24;");
        ROLES();
        int lane;
        asm volatile("mov.u32 %0, %%laneid;" : "=r"(lane));
        if (warp == 2 && elect()) {
            asm volatile("prefetch.tensormap [%0];" ::"l"(&tm_x) : "memory");
#pragma unroll
            for (int i = 0; i < 27; i++) mbar_init(bar_full + 8 * i, i < 12 || i >= 23 ? 1 : i < 16 ? 16 : 8);
#pragma unroll
            for (int i = 0; i <= E0; i++) {
                mbar_arrive(bar_full + 8 * i);
                asm volatile("mbarrier.arrive.shared::cta.b64 _, [%0], 16;" ::"r"(bar_empty + 8 * i) : "memory");
            }
            asm volatile("fence.mbarrier_init.release.cluster;" ::: "memory");
        }
        __syncwarp();
        asm volatile("barrier.cluster.arrive.relaxed.aligned;" ::: "memory");
        if (warp == 2 && !(SPARE && bx >= NCTA)) {
            __nanosleep(200);
            if (elect()) {
                mbar_expect_tx(bar_x, 16 * XP);
                tma2d(sb + SM_Q, &tm_x, 0, rg * 16, bar_x);
            }
            __syncwarp();
        }
        asm volatile("barrier.cluster.wait.aligned;" ::: "memory");
        const uint32_t tag = load_tag(gs);
        if (SPARE && bx >= NCTA) {
            if (warp == 1) {
#pragma unroll 1
                for (int e = 3; e < 83; e++) {
                    const int v = (e - 3) / 5;
                    mbar_wait_sleep(bar_empty + 8 * (e & 3), ~(e >> 2) & 1);
                    if (elect()) {
                        mbar_expect_tx(bar_full + 8 * (e & 3), SLOT);
                        tma2d_mc(sb + (e & 3) * SLOT + c * UNIT, &tm_wq, (8 * (v & 3) + 4 * c + 3) * DH + 64, (e - 3 - v * 5) * 128,
                                 bar_full + 8 * (e & 3), EVICT_NORMAL);
                    }
                }
            }
            __syncwarp();
            asm volatile("barrier.cluster.arrive.relaxed.aligned;\nbarrier.cluster.wait.aligned;" ::: "memory");
            return;
        }
        if (warp == 3) {
#pragma unroll 1
            for (int e = 4; e < 20; e++) {
                __nanosleep(e == 4 ? 2000 : 400);
                const int hd = (e * 52) >> 8, row = (e - hd * 5) * 128 + qb * 8 + (lane >> 1);
                if (lane < 16 && row < D_)
                    asm volatile("prefetch.global.L2 [%0];" ::"l"(padd(args.wq, (row * QD + (4 * j + ((0x1320 >> (4 * hd)) & 3)) * DH + (lane & 1) * 64) * 2)) : "memory");
            }
            __syncwarp();
            mbar_wait_sleep(bar_go, 0);
            __nanosleep(2000);
#pragma unroll 1
            for (int unit = 72 + bx; unit < 216; unit += NCTA) {
                float a[8];
#pragma unroll
                for (int i = 0; i < 8; i++) a[i] = 0.f;
#pragma unroll 1
                for (int k = lane >> 1; k < D_; k += 16) {
                    const float cv = __bfloat162float(*padd(args.cvec, k * 2));
                    mod_fma(a, __ldg(reinterpret_cast<const uint4*>(padd(args.w_mod, (k * (6 * D_) + unit * 16 + (lane & 1) * 8) * 2))), rbf(cv * sigmoidf_(cv)));
                }
                const float v = mod_reduce(a, lane), v1 = __shfl_down_sync(0xffffffffu, v, 8);
                if (lane < 8) *padd(gs->mod2, ((unit - 72) * 8 + (lane & 1) * 4 + (lane & 2) + (lane >> 2)) * 4) = pack_bf16(v, v1);
            }
            __syncwarp();
            if (lane == 0) flag_release(padd(g_flag_mod, bx * 4), tag);
#pragma unroll 1
            for (int k = 0; k < 36; k++) {
                __nanosleep(200);
                __stcg(padd(gs->h[0], (~tag & 1) * (NCTA * 36 * 512) + ((rg * 36 + k) * 32 + lane) * 16), make_uint4(0, 0, 0, 0));
            }
            __syncwarp();
            mbar_wait_sleep(bar_qfree + 16, 0);
            __nanosleep(2000);
            {
                uint4 v;
                uint32_t it = 0;
#pragma unroll 1
                do {
                    v = ld_relaxed(reinterpret_cast<const uint4*>(padd(g_flag_mod, lane * 16)));
                } while (((v.x ^ tag) | (v.y ^ tag) | (v.z ^ tag) | (v.w ^ tag)) && ++it < SPIN / 16);
                asm volatile("fence.acquire.gpu;" ::: "memory");
            }
            __syncwarp();
            {
                float w1 = 0.f, w2 = 0.f;
#pragma unroll 1
                for (int k = lane; k < D_ / 2; k += 32) {
                    const uint32_t* mp = padd(gs->mod2, k * 4);
                    const uint32_t sv = __ldcg(mp + D_ / 2), c1 = badd2(__ldcg(mp + D_), 0x3f803f80u);
                    const uint32_t wr = *reinterpret_cast<const uint32_t*>(padd(args.w_r, k * 4)), wp = bmul2(c1, wr);
                    reinterpret_cast<uint2*>(smem_raw + SM_T)[k] = make_uint2(__ldcg(mp), wp);
                    reinterpret_cast<uint2*>(smem_raw + SM_TC)[k] = make_uint2(c1, sv);
                    reinterpret_cast<uint32_t*>(smem_raw + SM_TG)[k] = __ldcg(mp + 3 * D_ / 2);
                    w1 += bf_lo(wp) + bf_hi(wp);
                    w2 += bf_lo(sv) * bf_lo(wr) + bf_hi(sv) * bf_hi(wr);
                }
#pragma unroll 1
                for (int i = 1; i < 32; i <<= 1) { w1 += __shfl_xor_sync(0xffffffffu, w1, i); w2 += __shfl_xor_sync(0xffffffffu, w2, i); }
                *reinterpret_cast<float2*>(smem_raw + SM_TS) = make_float2(w1, w2);
            }
#pragma unroll
            for (int i = 0; i < 4; i++) reinterpret_cast<uint4*>(smem_raw + SM_RED)[lane + 32 * i] = make_uint4(~0u, ~0u, ~0u, ~0u);
            asm volatile("fence.proxy.async.shared::cta;" ::: "memory");
            __syncwarp();
            if (elect()) {
                uint8_t* mb = g_frag + (size_t)rg * 8 * WREG + 3 * 4096;
#pragma unroll 1
                for (int k = 0; k < 8; k++, mb += WREG) {
#pragma unroll
                    for (int i = 0; i < 3; i++)
                        asm volatile("cp.async.bulk.global.shared::cta.bulk_group [%0], [%1], 2048;" ::"l"(mb + i * 2048), "r"(sb + SM_RED) : "memory");
                    __nanosleep(500);
                }
                asm volatile("cp.async.bulk.commit_group;\ncp.async.bulk.wait_group 0;\nfence.proxy.async.global;" ::: "memory");
            }
            __syncwarp();
            if (lane == 0) mbar_arrive(bar_mod);
            __syncwarp();
            mbar_wait_sleep(bar_go + 8, 0);
            if (elect()) asm volatile("prefetch.tensormap [%0];\nprefetch.tensormap [%1];\nprefetch.tensormap [%2];" ::"l"(&tm_x), "l"(&tm_p), "l"(&tm_d) : "memory");
            __syncwarp();
            *padd(g_flag_part, qb * 1024 + (lane >> 3) * 256 + j * 32 + (lane & 7) * 4) = 0;
            __syncwarp();
#pragma unroll 1
            for (int i = 1; i < 4; i++) {
                mbar_wait(bar_pub + 8 * i, 0);
                unsigned int* flags = padd(g_flag_part, qb * 1024 + (i - 1) * 256);
                if (elect()) { flag_release(padd(flags, j * 32), tag); DBG_PG(93); }
                __syncwarp();
                const uint32_t slot = (i + 2) & 3;
                flag_wait(padd(flags, (lane & 7) * 32), tag);
                asm volatile("fence.proxy.async.global;" ::: "memory");
                if (lane == 0 && i == 3) DBG_PG(101);
                mbar_wait(bar_go + 8 + 8 * i, 0);
                mbar_wait(bar_empty + 8 * slot, i == 3);
                if (elect()) {
                    mbar_expect_tx(bar_full + 8 * slot, SLOT);
                    tma3d(sb + slot * SLOT, &tm_p, 0, j * 20 + (i - 1) * 4, qb * 8, bar_full + 8 * slot);
                    tma3d(sb + slot * SLOT + UNIT, &tm_p, 0, j * 20 + (i - 1) * 4 + 2, qb * 8, bar_full + 8 * slot);
                }
            }
        } else if (warp == 0) {
#pragma unroll 1
            for (int i = 0; i < 48; i++) {
                if (SPARE && i == 34) {
                    flag_wait(&g_flag_q3[qb * 32], tag);
                    if (elect()) {
                        asm volatile("fence.proxy.async.global;" ::: "memory");
                        mbar_expect_tx(bar_q3, UNIT);
#pragma unroll 1
                        for (int k = 0; k < 8; k++) bulk_load(sb + SM_Q + 2 * SLOT + k * 4096 + 2048, &g_q3[(rg * 8 + k) * 128], 2048, bar_q3);
                    }
                }
                if (i == 0 || i == 17 || i == 34) { mbar_wait_sleep(bar_qfree + (i >> 4) * 8, 0); __nanosleep(2000); }
                __nanosleep(500);
                if (elect()) {
                    asm volatile("mbarrier.expect_tx.shared::cta.b64 [%0], %1;" ::"r"(bar_g), "n"(1920) : "memory");
                    tma2d(sb + SM_Q + i * 1920, i < 24 ? &tm_g : &tm_u, (bx * 36) & ~7, (i < 24 ? i : i - 24) * 24, bar_g);
                }
            }
            if (elect()) mbar_arrive(bar_g);
#pragma unroll 1
            for (int i = 0; i < 18; i++) {
                __nanosleep(400);
                if (elect()) l2_prefetch(args.w_down + (size_t)(bx * 36 + i * 2) * D_, 4 * D_);
            }
            __syncwarp();
            mbar_wait_sleep(bar_go + 8 * 2, 0);
            uint32_t acc = 0;
#pragma unroll 1
            for (int k = lane; k < 16 * 9; k += 32) acc |= touch(padd(args.x, (rg * 16 * D_ + k * 64) * 2));
            if (acc == 0) reinterpret_cast<volatile uint32_t*>(smem_raw + SM_BAR)[127] = acc;
            __syncwarp();
            mbar_wait_sleep(bar_go + 8 * 4, 0);
            *reinterpret_cast<uint2*>(padd(g_cand, ((lane >> 2) * NCTA + rg) * 32 + (lane & 3) * 8)) = make_uint2(0, 0);
            uint4* rp = padd(g_rows, (rg * 2 * RSLOT + lane) * 16);
#pragma unroll
            for (int k = 0; k < 12; k++) rp[k * 32] = make_uint4(~0u, ~0u, ~0u, ~0u);
            if (bx < 72) {
                uint4* yp = reinterpret_cast<uint4*>(padd(g_ypart, bx * NCTA * 64 + lane * 16));
#pragma unroll
                for (int k = 0; k < 16; k++) yp[k * 32] = make_uint4(~0u, ~0u, ~0u, ~0u);
            }
            asm volatile("fence.acq_rel.gpu;" ::: "memory");
            __syncwarp();
            if (lane == 0) mbar_arrive(bar_pre);
        } else if (warp == 1) {
            __nanosleep(100);
            auto put = [&](uint32_t fb, uint32_t slot, const CUtensorMap* tm, int c0, int c1, uint64_t pol) {
                if (elect()) {
                    mbar_expect_tx(fb, SLOT);
                    tma2d_mc(sb + slot * SLOT + c * UNIT, tm, c0, c1, fb, pol);
                }
            };
            auto prefetch_kv = [&](int n) {
                if (elect()) {
                    const size_t off = (size_t)((2 * j + (n >> 5)) * S_ + (n & 15) * 128) * DH + qb * 1024;
                    l2_prefetch(args.kc + off, 2048);
                    l2_prefetch(args.vc + off, 2048);
                }
            };
            put(bar_w0, 6, &tm_wq, 4 * j * DH + c * 64, -64, EVICT_FIRST);
#pragma unroll 1
            for (int e = E0 + 1; e < 19; e++) {
                const int i = SPARE && e < 12 ? e - 2 : e, hd = (i * 52) >> 8;
                const bool half = SPARE && hd == 2;
                const int c0 = (4 * j + ((0x1320 >> (4 * hd)) & 3)) * DH + (half ? 0 : c * 64);
                const int c1 = half ? (2 * (e - 12) + c) * 128 : (i - hd * 5) * 128 - 64;
                if (e < E0 + 5) __nanosleep(300);
                mbar_wait(bar_empty + 8 * (e & 3), ~(e >> 2) & 1);
                put(bar_full + 8 * (e & 3), e & 3, &tm_wq, c0, c1, EVICT_FIRST);
                if (e >= PF_KV && !(e & 1)) prefetch_kv((e - PF_KV) >> 1);
            }
            mbar_wait(bar_empty + 24, 1);
            put(bar_full + 24, 3, &tm_k, c * 64, 2 * j * S_, EVICT_NORMAL);
            mbar_wait(bar_empty, 0);
            put(bar_full, 0, &tm_wq, (4 * j + 1) * DH + c * 64, 448, EVICT_FIRST);
            prefetch_kv((20 - PF_KV) >> 1);
            if (elect()) mbar_arrive(bar_go);
#pragma unroll 1
            for (int n = 1; n < 64; n++) {
                const uint32_t sv = (n & 1) * 2, sk = sv ^ 3;
                const int m = n - 1;
                mbar_wait_sleep(bar_empty + 8 * sk, ~((n + 9) >> 1) & 1);
                put(bar_full + 8 * sk, sk, &tm_k, c * 64, (2 * j + (n >> 5)) * S_ + (n & 15) * 128, (n & 16) ? EVICT_FIRST : EVICT_NORMAL);
                mbar_wait_sleep(bar_empty + 8 * sv, (n >> 1) & 1);
                put(bar_full + 8 * sv, sv, &tm_v, c * 64, (2 * j + (m >> 5)) * S_ + (m & 15) * 128, (m & 16) ? EVICT_FIRST : EVICT_NORMAL);
                const int pn = n + ((20 - PF_KV) >> 1);
                if (!(pn & 80)) prefetch_kv(pn);
                if (n >= PF_WO) {
                    if (elect()) {
                        if (n < PF_WO + 9) l2_prefetch(args.wo + (size_t)bx * (QD * D_ / NCTA) + (n - PF_WO) * 2048, 4096);
                        if (n >= PF_O) {
                            l2_prefetch(g_frag + (size_t)(rg * 8 + 2 * (n - PF_O)) * WREG, 4096);
                            l2_prefetch(g_frag + (size_t)(rg * 8 + 2 * (n - PF_O) + 1) * WREG, 4096);
                        }
                    }
                }
            }
            mbar_wait_sleep(bar_empty + 24, 1);
            put(bar_full + 24, 3, &tm_v, c * 64, (2 * j + 1) * S_ + 15 * 128, EVICT_FIRST);
#pragma unroll 1
            for (int i = 0; i < 18; i++) {
                const int e = 148 + i + (i > 10) + (i > 14);
                mbar_wait_sleep(bar_empty + 8 * (e & 3), ~(e >> 2) & 1);
                put(bar_full + 8 * (e & 3), e & 3, &tm_wo, (i >> 1) * 64, (4 * j + ((i & 1) ? 1 + c : 3 * c)) * DH, EVICT_FIRST);
                arrive_if(bar_go + 2 + 2 * i, elect() && (i & 3) == 3);
            }
            asm volatile("fence.proxy.async.global;" ::: "memory");
            mbar_wait(bar_empty, 1);
            if (elect()) {
                mbar_expect_tx(bar_full, 16 * XP);
                tma2d(sb, &tm_x, 0, rg * 16, bar_full);
            }
            mbar_wait(bar_empty + 16, 1);
            if (elect()) {
                mbar_expect_tx(bar_full + 16, SLOT);
                tma3d(sb + 2 * SLOT, &tm_p, 0, j * 20 + 12, qb * 8, bar_full + 16);
                tma3d(sb + 2 * SLOT + UNIT, &tm_p, 0, j * 20 + 14, qb * 8, bar_full + 16);
            }
            mbar_wait(bar_empty + 24, 1);
            __nanosleep(200);
            if (elect()) {
                mbar_expect_tx(bar_full + 24, UNIT);
                tma3d(sb + 3 * SLOT, &tm_p, 0, j * 20 + 16, qb * 8, bar_full + 24);
            }
            mbar_wait(bar_empty + 8, 0);
            mbar_wait(bar_empty + 16, 0);
            __nanosleep(300);
            if (elect()) {
#pragma unroll
                for (int i = 1; i < 3; i++) {
                    mbar_expect_tx(bar_full + 8 * i, 18 * XP);
                    tma2d(sb + i * SLOT, &tm_d, 0, bx * 36 + (i - 1) * 18, bar_full + 8 * i);
                }
            }
        } else {
            if (elect()) asm volatile("prefetch.tensormap [%0];\nprefetch.tensormap [%1];\nprefetch.tensormap [%2];" ::"l"(&tm_k), "l"(&tm_v), "l"(&tm_wo) : "memory");
            if (SPARE) {
                mbar_wait_sleep(bar_pub, 0);
                if (lane == 0) flag_release(padd(g_flag_h, rg * 128), tag);
                __syncwarp();
            }
            bar_sync(1, 192);
#pragma unroll 1
            for (uint32_t e = E0 + 5; e < 20; e++) {
                mbar_wait(bar_full + 8 * (e & 3), (e >> 2) & 1);
                if (!(((SPARE ? 0xa080 : 0x8420) >> e) & 1)) bar_sync(1, 192);
            }
#pragma unroll 1
            for (uint32_t e = 20; e < 148; e += 2) {
                mbar_wait_sleep(bar_full + 8 * (e & 3), (e >> 2) & 1);
                bar_sync(4, 160);
                if (SPARE && e == 112) mbar_wait(bar_q3, 0);
                mbar_wait_sleep(bar_full + 8 + 8 * (e & 3), (e >> 2) & 1);
                bar_sync(1, 192);
            }
            bar_sync(4, 160);
#pragma unroll 1
            for (uint32_t e = 148; e < 168; e++) {
                mbar_wait(bar_full + 8 * (e & 3), (e >> 2) & 1);
                if (e != 159 && e != 164) bar_sync(1, 192);
            }
        }
        __syncwarp();
        uint32_t rows = 0x1111u << warp;
        auto store_rows = [&](uint32_t m) {
#pragma unroll 1
            for (; m; m &= m - 1) {
                const int i = __ffs(m) - 1;
                asm volatile("cp.async.bulk.global.shared::cta.bulk_group.L2::cache_hint [%0], [%1], %2, %3;"
                             ::"l"(padd(args.out, (rg * 16 + i) * (D_ * 2))), "r"(sb + i * XP), "n"(D_ * 2), "l"(EVICT_FIRST) : "memory");
            }
        };
        mbar_wait_sleep(bar_out, 0);
        if (bx == 127 && warp == 0 && lane == 0) gs->epoch[0] = tag;
        if (elect()) {
            asm volatile("fence.proxy.async.shared::cta;" ::: "memory");
            const uint2 sel = lds64(sb + SM_RED + 64);
            if ((sel.x >> 4) == rg) rows &= ~(1u << (sel.x & 15));
            if ((sel.y >> 4) == rg) rows &= ~(1u << (sel.y & 15));
            store_rows(rows);
            asm volatile("cp.async.bulk.commit_group;\ncp.async.bulk.wait_group.read 0;" ::: "memory");
        }
    } else {
        uint32_t cv[2] = {0, 0}, tag0 = 0;
        {
            uint32_t ws, t, b;
            asm volatile("mov.u32 %0, smem_raw;\nmov.u32 %1, %%tid.x;\nmov.u32 %2, %%ctaid.x;" : "=r"(ws), "=r"(t), "=r"(b));
            t -= 128;
            const uint32_t* cp = padd(reinterpret_cast<const uint32_t*>(args.cvec), (t & 0xe0) + (t & 7) * 4);
            asm volatile("{\n.reg .pred p, q, r;\nsetp.lt.u32 r, %8, 256;\nsetp.lt.and.u32 p, %9, 72, r;\nsetp.lt.and.u32 q, %8, 128, p;\n"
                         "@p ld.global.nc.u32 %0, [%5];\n@q ld.global.nc.u32 %1, [%6 + 1024];\n@r ld.global.ca.u32 %2, [%7];\n"
                         "@p cp.async.cg.shared.global [%3], [%4], 16;\n@p cp.async.cg.shared.global [%3 + 4096], [%4 + 884736], 16;\n"
                         "@p cp.async.cg.shared.global [%3 + 8192], [%4 + 1769472], 16;\n@p cp.async.cg.shared.global [%3 + 12288], [%4 + 2654208], 16;\n"
                         "@q cp.async.cg.shared.global [%3 + 16384], [%4 + 3538944], 16;\n}"
                         : "+r"(cv[0]), "+r"(cv[1]), "+r"(tag0)
                         : "r"(ws + SM_Q + SLOT + t * 16), "l"(padd(args.w_mod, (t >> 1 & 127) * (12 * D_) + (t & 1) * 16 + b * 32)),
                           "l"(padd(cp, (t & 24) * 32)), "l"(cp), "l"(padd(gs->epoch, b >> 8)), "r"(t), "r"(b) : "memory");
        }
        uint32_t tag = __shfl_sync(0xffffffffu, tag0, 0);
        asm volatile("barrier.cluster.arrive.relaxed.aligned;" ::: "memory");
        asm volatile("setmaxnreg.inc.sync.aligned.u32 240;");
        const int lane = threadIdx.x & 31;
        const int cw = warp - 4;
        const int w = cw >> 2;
        const int tid = threadIdx.x - 128;
        ROLES();
        float* red = reinterpret_cast<float*>(smem_raw + SM_RED);
        DBG_INIT();
        DBG_G(120);
        DBG_T(100);

        uint32_t x[20];
        uint4* hdst;
        uint2* hdst2;
        {
            if (bx < 72) {
                uint2* mdst = &gs->mod1[bx * 8 + tid];
                if (tid < 8) st_relaxed64(mdst, 0, 0);
                uint32_t sa[10];
#pragma unroll
                for (int i = 0; i < 2; i++) {
                    const float lo = bf_lo(cv[i]), hi = bf_hi(cv[i]);
                    cv[i] = pack_bf16(lo * sigmoidf_(lo), hi * sigmoidf_(hi));
                }
#pragma unroll
                for (int i = 0; i < 10; i++) sa[i] = __shfl_sync(0xffffffffu, cv[i >> 3], (i & 7) * 4 + (lane & 3));
                anchor(bar_full + 504, sa[0] & sa[1] & sa[2] & sa[3] & sa[4] & sa[5] & sa[6] & sa[7] & sa[8] & sa[9] & (uint32_t)(uintptr_t)mdst & (uint32_t)((uintptr_t)mdst >> 32));
                asm volatile("cp.async.wait_all;" ::: "memory");
                __syncwarp();
                const uint32_t ws = sb + SM_Q + SLOT + cw * 512 + (lane & 15) * 32 + (lane & 16);
                float d[16];
#pragma unroll
                for (int i = 0; i < 16; i++) d[i] = 0.f;
#pragma unroll
                for (int i = 0; i < 5; i++) {
                    const uint4 b = ldsm4t(ws + (i < 4 || cw < 4 ? i * 4096 : 0));
                    mma16816(d + 8 * (i & 1), sa[2 * i], sa[2 * i], sa[2 * i + 1], sa[2 * i + 1], b.x, b.y);
                    mma16816(d + 8 * (i & 1) + 4, sa[2 * i], sa[2 * i], sa[2 * i + 1], sa[2 * i + 1], b.z, b.w);
                }
                if (lane < 8) reinterpret_cast<float2*>(red)[lane * 8 + cw] = (lane & 4) ? make_float2(d[4] + d[12], d[5] + d[13]) : make_float2(d[0] + d[8], d[1] + d[9]);
                bar_sync(3, 256);
                if (tid < 8) {
                    const float4* r = reinterpret_cast<const float4*>(red) + tid * 4;
                    const float4 r0 = r[0], r1 = r[1], r2 = r[2], r3 = r[3];
                    st_relaxed64(mdst, pack_bf16(((r0.x + r0.z) + (r1.x + r1.z)) + ((r2.x + r2.z) + (r3.x + r3.z)),
                                                 ((r0.y + r0.w) + (r1.y + r1.w)) + ((r2.y + r2.w) + (r3.y + r3.w))), tag + 1);
                }
            }
            if (cw < 4) st_relaxed4(gs->h[~tag & 1] + (size_t)(rg * 36 + cw) * 32 + lane, 0, 0, 0, 0);
            DBG_G(106);
            asm volatile("barrier.cluster.wait.aligned;" ::: "memory");
            mbar_wait(bar_x, 0);
            asm volatile("add.u32 %0, %0, 1;" : "+r"(tag));
            float st[12], st2[12];
            rows_load(x, sb + SM_Q + (lane & 15) * XP + (lane >> 4) * 16 + cw * 32, cw);
#pragma unroll
            for (int i = 0; i < 12; i++) { st[i] = 0.f; st2[i] = 0.f; }
#pragma unroll
            for (int k = 0; k < 9; k++) stats_add((k & 1) ? st2 : st, x[2 * k], x[2 * k + 1], 0x3f803f80u);
#pragma unroll
            for (int i = 0; i < 12; i++) st[i] += st2[i];
            uint32_t mean2;
            float dot;
            const float rsd = rows_stats(st, reinterpret_cast<float4*>(red + 128), cw, lane, mean2, dot);
            const uint4* mp = reinterpret_cast<const uint4*>(gs->mod1) + min(tid, D_ / 4 - 1);
            uint4 v0 = make_uint4(0, tag, 0, tag), v1 = v0;
            auto look = [&]() {
                asm volatile("{\n.reg .pred p;\n.reg .b64 a, b, c, d;\nsetp.lt.s32 p, %9, 5;\nmov.b64 a, {%0, %1};\nmov.b64 b, {%2, %3};\n"
                             "mov.b64 c, {%4, %5};\nmov.b64 d, {%6, %7};\n@p ld.relaxed.gpu.global.v2.b64 {a, b}, [%8];\n"
                             "@p ld.relaxed.gpu.global.v2.b64 {c, d}, [%8 + 2304];\n"
                             "mov.b64 {%0, %1}, a;\nmov.b64 {%2, %3}, b;\nmov.b64 {%4, %5}, c;\nmov.b64 {%6, %7}, d;\n}"
                             : "+r"(v0.x), "+r"(v0.y), "+r"(v0.z), "+r"(v0.w), "+r"(v1.x), "+r"(v1.y), "+r"(v1.z), "+r"(v1.w)
                             : "l"(mp), "r"(cw) : "memory");
            };
            rows_normalise(x, x, mean2, rsd, lane, look);
            fence_regs(x);
            uint32_t it = 0;
#pragma unroll 1
            while (((v0.y ^ tag) | (v0.w ^ tag) | (v1.y ^ tag) | (v1.w ^ tag)) && ++it < SPIN / 16) look();
            uint4* smod = reinterpret_cast<uint4*>(smem_raw + SM_Q + M_MOD);
            if (tid < D_ / 4) smod[tid] = make_uint4(badd2(v1.x, 0x3f803f80u), v0.x, badd2(v1.z, 0x3f803f80u), v0.z);
            hdst = g_h + (size_t)(rg * 36 + cw) * 32 + lane;
            hdst2 = reinterpret_cast<uint2*>(g_h + (size_t)(rg * 36 + 32) * 32) + tid;
            bar_sync(3, 256);
            DBG_G(107);
#pragma unroll
            for (int k = 0; k < 9; k++) {
                const uint2 cs = lds64(sb + SM_Q + M_MOD + (cw * 8 + (lane & 3) + (k < 8 ? (k >> 1) * 64 + (k & 1) * 4 : 256 - cw * 4)) * 8);
                const uint32_t c1 = cs.x, sa = cs.y;
                x[2 * k] = badd2(bmul2(x[2 * k], c1), sa);
                if (x[2 * k] == 0) x[2 * k] = 0x8000u;
                x[2 * k + 1] = badd2(bmul2(x[2 * k + 1], c1), sa);
            }
#pragma unroll
            for (int ch = 0; ch < 3; ch++) st_relaxed4(hdst + ch * 256, x[4 * ch], x[4 * ch + 1], x[4 * ch + 2], x[4 * ch + 3]);
            DBG_G(108);
        }

        uint32_t rel_base;
        asm("mapa.shared::cluster.u32 %0, %1, %2;" : "=r"(rel_base) : "r"(bar_empty), "r"(lane & 1));
        auto release = [&](uint32_t slot) { if (lane < 2) mbar_arrive_cluster(rel_base + 8 * slot); };
        uint32_t q[32], p[32];
        float s[64], o[64];

        const int lw = cw & 3;
        const uint32_t relw = lw == 2 && lane < 8, handw = lw == 2 || cw == 1;
        auto release4 = [&](uint32_t off, uint32_t on = 1) {
            asm volatile("{\n.reg .pred p;\nsetp.ne.b32 p, %1, 0;\n@p mbarrier.arrive.shared::cluster.b64 _, [%0];\n}" ::"r"(rel_base + off), "r"(relw & on) : "memory"); };
        auto handoff = [&](uint32_t on = 1) {
            asm volatile("{\n.reg .pred p;\nsetp.ne.b32 p, %1, 0;\n@p bar.arrive %0, 192;\n}" ::"r"(2 - w), "r"(handw & on) : "memory"); };
        if (cw == 6) bar_arrive(1, 192);

        uint4* qpark = reinterpret_cast<uint4*>(smem_raw + SM_Q - SLOT) + cw * 256 + lane;
        {
            uint32_t h[144];
            const uint4* hf = g_h + (size_t)(qb * 8 + cw) * (36 * 32) + lane;
            auto load_h = [&](auto lo, auto hi) {
#pragma unroll
                for (int ks = lo.value; ks < hi.value; ks++) {
                    const uint4 v = h_frag(hf, ks, lane);
                    h[4 * ks] = v.x; h[4 * ks + 1] = v.y; h[4 * ks + 2] = v.z; h[4 * ks + 3] = v.w;
                }
            };
            auto check_h = [&](auto lo, auto hi) {
                uint32_t it = 0;
                bool miss;
#pragma unroll 1
                do {
                    uint32_t mn = ~0u;
#pragma unroll
                    for (int ks = lo.value; ks < hi.value; ks++) mn = __vimin3_u32(mn, h[4 * ks], h[4 * ks + 2]);
                    miss = __any_sync(0xffffffffu, mn == 0);
                    if (miss) load_h(lo, hi);
                    asm volatile("add.u32 %0, %0, 1;" : "+r"(it));
                } while (miss && it < SPIN / 16);
            };
            auto check_h2 = [&](auto lo, auto hi, auto nx) {
                float f0 = __uint_as_float(~0u), f1 = f0;
                hold(f0, f1);
                auto low = [&]() {
                    uint32_t m0 = __float_as_uint(f0), m1 = m0;
#pragma unroll
                    for (int ks = lo.value; ks < hi.value; ks += 2) { m0 = __vimin3_u32(m0, h[4 * ks], h[4 * ks + 2]); m1 = __vimin3_u32(m1, h[4 * ks + 4], h[4 * ks + 6]); }
                    return min(m0, m1);
                };
                anchor(const_cast<uint4*>(hf), h[4 * hi.value - 1] & __float_as_uint(f0));
                load_h(hi, nx);
                if (__any_sync(0xffffffffu, low() == 0)) {
                    uint32_t it = 0;
#pragma unroll 1
                    do load_h(lo, hi); while (__any_sync(0xffffffffu, low() == 0) && ++it < SPIN / 16);
                }
            };
            __nanosleep(100);
            load_h(IC<0>{}, IC<4>{});
            st_relaxed4(hdst + 3 * 256, x[12], x[13], x[14], x[15]);
            st_relaxed64(hdst2, x[16], x[17]);
            __syncwarp();
            if (SPARE && lane == 0) mbar_arrive(bar_pub);
            DBG_T(104); DBG_G(109);
            mbar_wait(bar_w0, 0);
#pragma unroll
            for (int e = E0 + 1; e < E0 + 3; e++) mbar_wait(bar_full + 8 * (e & 3), e >> 2);
#pragma unroll
            for (int i = 0; i < 64; i++) o[i] = 0.f;
            auto group = [&](auto tc, auto ec) {
                constexpr int t = tc.value, e = ec.value, k0 = t ? 8 * t - 4 : 0;
                constexpr bool first = e < E0 + 5, turns = e >= E0 + 4;
                uint64_t dv = (first ? args.d0 : desc_lo(0, UNIT) | (0x40000040ull << 32)) + ((t ? 0 : 512) + (e == E0 ? 6 : e & 3) * (SLOT / 16));
                if (first && t == 0) check_h(IC<0>{}, IC<4>{});
                if (first && t >= 3) mbar_wait(bar_full + 8 * (e & 3), e >> 2);
                if (first && t > 0) check_h2(IC<k0>{}, IC<8 * t + 4>{}, IC<t < 4 ? 8 * t + 12 : 0>{});
                if (t != 1 && turns) bar_sync(1 + w, 192);
                if (t != 1 || first) WG_FENCE();
#pragma unroll
                for (int ks = k0; ks < 8 * t + 4; ks++) {
                    mma_rs128<1>(o, h[4 * ks], h[4 * ks + 1], h[4 * ks + 2], h[4 * ks + 3], dv, ks);
                    if (t && turns && ks == k0 + QSPLIT - 1) WG_COMMIT();
                }
                if (t || first) WG_COMMIT();
                if (first && t == 0) load_h(IC<4>{}, IC<12>{});
                if (t > 0) {
                    WG_WAIT(1);
                    if (turns) handoff();
                    if ((t == 1 && !first) || (t > 1 && e <= E0 + 4)) release4(8 * ((e - 1) & 3));
                    if (turns && e != 18) { WG_WAIT(0); release4(8 * (e & 3)); }
                }
            };
            auto head = [&](auto ec, int slot) {
                constexpr int e = ec.value;
                fence_regs(o);
                group(IC<0>{}, IC<e>{}); group(IC<1>{}, IC<e + 1>{}); group(IC<2>{}, IC<e + 2>{}); group(IC<3>{}, IC<e + 3>{});
                if (e == 15) return;
                group(IC<4>{}, IC<e + 4>{});
                fence_regs(o);
#pragma unroll
                for (int i = 0; i < 8; i++)
                    qpark[slot * 2048 + i * 32] = make_uint4(pack_bf16(o[8 * i], o[8 * i + 1]), pack_bf16(o[8 * i + 2], o[8 * i + 3]),
                                                             pack_bf16(o[8 * i + 4], o[8 * i + 5]), pack_bf16(o[8 * i + 6], o[8 * i + 7]));
            };
            head(IC<E0>{}, 1);
            head(IC<E0 + 5>{}, 2);
            if (SPARE) {
                float (&u)[32] = reinterpret_cast<float (&)[32]>(o);
                fence_regs(u);
#pragma unroll
                for (int t = 0; t < 2; t++) {
                    uint64_t dv = args.d0 + t * (SLOT / 16);
                    bar_sync(1 + w, 192);
                    WG_FENCE();
#pragma unroll
                    for (int ks = 0; ks < 16 + 4 * t; ks++) {
                        mma_rs64<1>(u, h[64 * t + 4 * ks], h[64 * t + 4 * ks + 1], h[64 * t + 4 * ks + 2], h[64 * t + 4 * ks + 3], dv, ks | t);
                        if (ks == 2 * QSPLIT + 4 * t - 1) WG_COMMIT();
                    }
                    WG_COMMIT();
                    WG_WAIT(1);
                    handoff();
                    WG_WAIT(0);
                    release4(8 * t);
                }
                fence_regs(u);
                release4(16);
#pragma unroll
                for (int i = 0; i < 4; i++)
                    qpark[3 * 2048 + i * 32] = make_uint4(pack_bf16(u[8 * i], u[8 * i + 1]), pack_bf16(u[8 * i + 2], u[8 * i + 3]),
                                                          pack_bf16(u[8 * i + 4], u[8 * i + 5]), pack_bf16(u[8 * i + 6], u[8 * i + 7]));
            } else {
                head(IC<10>{}, 3);
            }
            head(IC<15>{}, 0);
#pragma unroll
            for (int i = 0; i < 8; i++) {
                const uint4 v = lds128(smem_u32(qpark + 2048 + i * 32));
                q[4 * i] = v.x; q[4 * i + 1] = v.y; q[4 * i + 2] = v.z; q[4 * i + 3] = v.w;
            }
#pragma unroll
            for (int i = 0; i < 32; i++) p[i] = h[112 + i];
            WG_WAIT(0);
            fence_regs(o);
            release4(16);
        }
        DBG_T(105);
        DBG_G(125);

        uint8_t* frag = reinterpret_cast<uint8_t*>(__shfl_sync(0xffffffffu, reinterpret_cast<unsigned long long>(g_frag + (size_t)(rg * 8 + cw) * WREG + lane * 16), lane));
        const uint4* qnext = reinterpret_cast<const uint4*>(__shfl_sync(0xffffffffu, reinterpret_cast<unsigned long long>(padd(smem_raw, SM_Q + tid * 16 + cw * 3584)), lane));
        uint8_t* odst = reinterpret_cast<uint8_t*>(const_cast<uint4*>(qnext));
        qnext -= 2048;
        float m0, m1, l0 = 0.25f, l1 = 0.25f, t0, t1;
        uint32_t bad = 0;
        auto finish = [&](auto lo, auto hi, uint32_t bit, auto sink) {
#pragma unroll
            for (int i = lo.value; i < hi.value; i++) {
                const uint32_t v0 = pack_bf16(o[8 * i] * t0, o[8 * i + 1] * t0), v1 = pack_bf16(o[8 * i + 2] * t1, o[8 * i + 3] * t1);
                const uint32_t v2 = pack_bf16(o[8 * i + 4] * t0, o[8 * i + 5] * t0), v3 = pack_bf16(o[8 * i + 6] * t1, o[8 * i + 7] * t1);
                if (i == 0 && fabsf(o[0] * t0) >= 0x1p-31f) bad |= bit << 8;
                sink(i, v0, v1, v2, v3);
            }
        };
        float lq[6];
        auto row_parts = [&]() {
#pragma unroll
            for (int i = 0; i < 3; i++) { lq[i] = __shfl_xor_sync(0xffffffffu, l0, i + 1); lq[3 + i] = __shfl_xor_sync(0xffffffffu, l1, i + 1); }
        };
        auto row_sums = [&](uint32_t bit) {
            t0 = (l0 + lq[0]) + (lq[1] + lq[2]); t1 = (l1 + lq[3]) + (lq[4] + lq[5]);
            if (!(t0 >= LMIN && t0 < LMAX && t1 >= LMIN && t1 < LMAX)) bad |= bit;
        };
        auto issue_pv = [&](uint64_t dv, int acc) {
            asm volatile("{\n.reg .pred p;\nsetp.eq.b32 p, %0, 0;\n@p bar.sync 4, 160;\n}" ::"r"(w) : "memory");
#pragma unroll
            for (int ks = 0; ks < 8; ks++)
                mma_rs128<1>(o, p[4 * ks], p[4 * ks + 1], p[4 * ks + 2], p[4 * ks + 3], dv, ks ? 1 : acc);
            WG_COMMIT();
        };
#pragma unroll
        for (int i = 0; i < 64; i++) s[i] = 0.f;
        uint64_t dv_lo = args.d0;
        uint32_t voff = 0;
        auto issue_qk = [&]() {
            uint64_t dk = dv_lo ^ (desc_lo(0, UNIT) ^ desc_lo(3 * SLOT, 16));
            bar_sync(1 + w, 192);
            fence_regs(s); fence_regs(q); fence_regs(o); fence_regs(p);
            WG_FENCE();
#pragma unroll
            for (int ks = 0; ks < 8; ks++)
                if (ks == 3) mma_rs128<0, 1018>(s, q[4 * ks], q[4 * ks + 1], q[4 * ks + 2], q[4 * ks + 3], dk, 1);
                else mma_rs128<0, 2>(s, q[4 * ks], q[4 * ks + 1], q[4 * ks + 2], q[4 * ks + 3], dk, ks != 0);
            WG_COMMIT();
        };
        auto to_frag = [&](int i, uint32_t v0, uint32_t v1, uint32_t v2, uint32_t v3) {
            *reinterpret_cast<uint4*>(odst + i * 512) = make_uint4(v0, v1, v2, v3); };
        int n = 0;
        auto scores_ready = [&]() {
            WG_WAIT(1);
            fence_regs(s); fence_regs(q);
        };
        auto pass_on = [&]() {
            release4(voff ^ 24);
            handoff();
        };
#pragma unroll 1
        for (;;) {
            {
                {
                    asm volatile("st.shared.v2.f32 [%0], {%1, %2};" ::"r"(sb + SM_RED + tid * 8), "f"(l0), "f"(l1) : "memory");
                    __syncwarp();
                    const uint4 a = lds128(sb + SM_RED + (tid & ~3) * 8), b = lds128(sb + SM_RED + (tid & ~3) * 8 + 16);
                    l0 = __uint_as_float(a.x); lq[0] = __uint_as_float(a.z); lq[1] = __uint_as_float(b.x); lq[2] = __uint_as_float(b.z);
                    l1 = __uint_as_float(a.y); lq[3] = __uint_as_float(a.w); lq[4] = __uint_as_float(b.y); lq[5] = __uint_as_float(b.w);
                }
                issue_qk();
                hold(l0, l1);
                row_sums(1u << (n >> 4));
                t0 = rcp_fast(t0); t1 = rcp_fast(t1);
                l0 = 0.f; l1 = 0.f;
                odst = n ? frag + ((n >> 4) - 1) * 4096 : odst;
                qnext = n == 48 ? reinterpret_cast<const uint4*>(frag) : qnext + 2048;
                anchor(bar_full + 504, (t0 + t1) * __uint_as_float((bad ^ (uint32_t)(uintptr_t)odst ^ (uint32_t)(uintptr_t)qnext) & 0x3fffffff));
                asm volatile("{\n.reg .pred p;\nsetp.ne.b32 p, %1, 0;\n@p mbarrier.arrive.shared::cta.b64 _, [%0];\n}"
                             ::"r"(bar_qfree + (n >> 1) - 8), "r"(lane ? 0 : n) : "memory");
                issue_pv(dv_lo, 1);
                scores_ready();
                const uint32_t a = pack_bf16(fmaxf(fmaxf(s[0], s[1]), fmaxf(s[4], s[5])), fmaxf(fmaxf(s[2], s[3]), fmaxf(s[6], s[7])));
                const uint32_t b = bmax2(bmax2(a, __shfl_xor_sync(0xffffffffu, a, 1)), bmax2(__shfl_xor_sync(0xffffffffu, a, 2), __shfl_xor_sync(0xffffffffu, a, 3)));
                pass_on();
                m0 = fmaf(-CS, bf_lo(b), -POFF); m1 = fmaf(-CS, bf_hi(b), -POFF);
            }
#pragma unroll 1
            for (;;) {
                DBG_T(n);
#pragma unroll
                for (int i = 0; i < 4 * STAGE; i++) s[i] = fmaf(s[i], CS, (i & 2) ? m1 : m0);
#pragma unroll
                for (int i = 0; i < 4 * SPLIT; i++) s[i] = ex2(s[i]);
#pragma unroll
                for (int i = 0; i < SPLIT; i++) { l0 += s[4 * i] + s[4 * i + 1]; l1 += s[4 * i + 2] + s[4 * i + 3]; }
                m0 = fmaf(l0, 0.f, m0); m1 = fmaf(l1, 0.f, m1);
                anchor(bar_full + 504, l0 + l1);
                WG_WAIT(0);
                fence_regs(o); fence_regs(p);
                release4(voff);
                dv_lo ^= 2 * SLOT / 16;
                voff ^= 16;
                n++;
#pragma unroll
                for (int i = 4 * STAGE; i < 64; i++) s[i] = fmaf(s[i], CS, (i & 2) ? m1 : m0);
#pragma unroll
                for (int i = 4 * SPLIT; i < 64; i++) s[i] = ex2(s[i]);
#pragma unroll
                for (int i = SPLIT; i < 16; i++) { l0 += s[4 * i] + s[4 * i + 1]; l1 += s[4 * i + 2] + s[4 * i + 3]; }
#pragma unroll
                for (int i = 0; i < 32; i++) p[i] = pack_bf16(s[2 * i], s[2 * i + 1]);
                const int jn = n & 15;
                if (jn > 1) {
                    issue_qk();
                    if ((n & 10) == 2) {
                        if (n & 1) {
#pragma unroll
                            for (int i = 0; i < 64; i++) o[i] *= (i & 2) ? t1 : t0;
                        } else {
                            row_parts();
                            row_sums(2u << (n >> 4));
                            const uint32_t e0 = __float_as_uint(t0) >> 23, e1 = __float_as_uint(t1) >> 23;
                            m0 -= __uint_as_float(0x4b000000u | e0) - (8388608.f + 127.f - POFF);
                            m1 -= __uint_as_float(0x4b000000u | e1) - (8388608.f + 127.f - POFF);
                            t0 = __uint_as_float((254 - (int)POFF - e0) << 23); t1 = __uint_as_float((254 - (int)POFF - e1) << 23);
                            l0 *= t0; l1 *= t1;
                        }
                    }
                    fence_regs(o);
                    WG_FENCE();
                    issue_pv(dv_lo, 1);
                    scores_ready();
                    pass_on();
                    if (jn != 15) continue;
#pragma unroll
                    for (int i = 0; i < 8; i++) {
                        const uint4 v = qnext[i * 32];
                        q[4 * i] = v.x; q[4 * i + 1] = v.y; q[4 * i + 2] = v.z; q[4 * i + 3] = v.w;
                    }
                    continue;
                }
                if (jn == 0) break;
                finish(IC<0>{}, IC<ESPLIT>{}, 1u << (n >> 4), to_frag);
                issue_qk();
                hold(t0, t1);
                finish(IC<ESPLIT>{}, IC<8>{}, 1u << (n >> 4), to_frag);
                WG_FENCE();
                issue_pv(dv_lo, 0);
                scores_ready();
                pass_on();
            }
            if (n == 64) break;
        }
        DBG_T(64);
        uint32_t a1[32], a2[32];
        bar_sync(1 + w, 192);
        fence_regs(o); fence_regs(p);
        WG_FENCE();
        issue_pv(args.d0 + 3 * SLOT / 16, 1);
        handoff();
        mbar_wait(bar_mod, 0);
        const int tid_ = __shfl_sync(0xffffffffu, tid, lane);
        row_parts();
        row_sums(16);
        t0 = rcp_fast(t0); t1 = rcp_fast(t1);
        anchor(frag, q[0] & q[4] & q[8] & q[12] & q[16] & q[20] & q[24] & q[28] & __float_as_uint(t0) & __float_as_uint(t1) & tid_);
        frag_load(a1, frag + 4096);
        frag_load<0, 4>(a2, frag + 8192);
        anchor(frag, bad);
        WG_WAIT(0);
        fence_regs(o); fence_regs(p);
        release4(24);
        finish(IC<0>{}, IC<8>{}, 16, [&](int i, uint32_t v0, uint32_t v1, uint32_t v2, uint32_t v3) {
            p[4 * i] = v0; p[4 * i + 1] = v1; p[4 * i + 2] = v2; p[4 * i + 3] = v3; });
        anchor(frag, p[31] & p[15]);
        frag_load<4, 8>(a2, frag + 8192);
        bad = __reduce_or_sync(0xffffffffu, bad);
        bad = ((bad | ~(bad >> 8)) >> 1) & 15;
        if (__builtin_expect(bad != 0, 0)) {
            uint8_t* keep = g_keep + (size_t)(rg * 8 + cw) * 4096 + lane * 16;
            frag_store(keep, p);
            attn_fallback(bad, tag, gs, frag, keep, args.wq, args.kc, args.vc);
            frag_load(q, frag); frag_load(a1, frag + 4096); frag_load(a2, frag + 8192); frag_load(p, keep);
            anchor(frag, q[0] & q[4] & q[8] & q[12] & q[16] & q[20] & q[24] & q[28] & p[0] & p[4] & p[8] & p[12] & p[16] & p[20] & p[24] & p[28]);
        }
        DBG_T(80);
        DBG_G(124);

        const uint32_t eye = (tid_ >> 3 & 3) == (tid_ & 3) ? 0x3f80u << ((tid_ & 4) * 4) : 0;
        auto sum8 = [&](uint32_t* r, const uint4 (&v)[8]) {
            float d[16];
#pragma unroll
            for (int i = 0; i < 16; i++) d[i] = 0.f;
#pragma unroll
            for (int src = 0; src < 8; src++) {
                mma1688(d + 8 * (src & 1), v[src].x, v[src].y, eye);
                mma1688(d + 8 * (src & 1) + 4, v[src].z, v[src].w, eye);
            }
#pragma unroll
            for (int i = 0; i < 4; i++) r[i] = pack_bf16(d[2 * i] + d[8 + 2 * i], d[2 * i + 1] + d[9 + 2 * i]);
        };
        uint4 v2[8], v3[8], wf[23];
        uint2 u4[8], gw[9];
        uint32_t x1[20], xs, pa, ta;
        const uint8_t *mb, *mb4;
        auto load_wf = [&](auto lo, auto hi) {
            const uint32_t wa = sb + SM_Q + ((tid_ & 8) * (D_ / 8) + cw * 16 + (tid_ & 7) + (tid_ & 16) / 2) * 80;
            const uint32_t wb = wa + (512 - cw * 8) * 80 - (tid_ & 16) * 39;
#pragma unroll
            for (int i = lo.value; i < hi.value; i++) wf[i] = ldsm4t(i < 20 ? wa + (i / 5) * 10240 + (i % 5) * 16 : wb + (i - 20) * 32);
        };
        uint32_t at[18];
        {
            float (&u)[32] = reinterpret_cast<float (&)[32]>(o);
            uint32_t off = 0;
            auto turn = [&](const uint32_t (&a)[32], const uint32_t (&b)[32], int acc) {
                uint64_t dv = args.d0 + off * (SLOT / 128);
                bar_sync(1 + w, 192);
                fence_regs(u);
                WG_FENCE();
#pragma unroll
                for (int ks = 0; ks < 16; ks++) {
                    const uint32_t* f = ks < 8 ? &a[4 * ks] : &b[4 * ks - 32];
                    mma_rs64<1>(u, f[0], f[1], f[2], f[3], dv, ks | acc);
                    if (ks == OSPLIT - 1) WG_COMMIT();
                }
                WG_COMMIT();
                WG_WAIT(1);
            };
            auto done = [&]() {
                WG_WAIT(0);
                fence_regs(u);
                release4(off);
                off = (off + 8) & 24;
            };
            auto store = [&](uint8_t* dst) {
#pragma unroll
                for (int i = 0; i < 4; i++)
                    st_relaxed4(dst + i * 512, pack_bf16(u[8 * i], u[8 * i + 1]), pack_bf16(u[8 * i + 2], u[8 * i + 3]),
                                pack_bf16(u[8 * i + 4], u[8 * i + 5]), pack_bf16(u[8 * i + 6], u[8 * i + 7]));
            };
            pa = sb + w * (UNIT - 2048) + tid_ * 16;
#pragma unroll
            for (int i = 0; i < 8; i++) at[i] = 0;
            fence_regs(q); fence_regs(p);
            uint8_t* dst = frag;
#pragma unroll
            for (int i = 0; i < 8; i++) asm volatile("" : "=r"(v2[i].x), "=r"(v2[i].y), "=r"(v2[i].z), "=r"(v2[i].w));
#pragma unroll 1
            for (int k = 0; k < 8; k++, dst += 2048) {
                const uint32_t poff = (off + 8) & 24;
                const bool sum = (0xa0 >> k) & 1;
                turn(q, p, 0);
                handoff();
                auto sum_p = [&](auto lo, auto hi) {
#pragma unroll
                    for (int i = lo.value; i < hi.value; i++) {
                        float a[8], b[8];
#pragma unroll
                        for (int src = 0; src < 8; src++) {
                            const uint32_t x = i == 0 ? v2[src].x : i == 1 ? v2[src].y : i == 2 ? v2[src].z : v2[src].w;
                            a[src] = bf_lo(x); b[src] = bf_hi(x);
                        }
                        at[i] = at[4 + i];
                        at[4 + i] = pack_bf16(((a[0] + a[2]) + (a[4] + a[6])) + ((a[1] + a[3]) + (a[5] + a[7])),
                                              ((b[0] + b[2]) + (b[4] + b[6])) + ((b[1] + b[3]) + (b[5] + b[7])));
                    }
                };
                if (sum) {
                    mbar_wait(bar_full + poff, 1);
#pragma unroll
                    for (int src = 0; src < 8; src++) v2[src] = lds128(pa + poff * (SLOT / 8) + src * 2048);
                    __syncwarp();
                    release(poff >> 3);
                    done();
                    off = (off + 8) & 24;
                    sum_p(IC<0>{}, IC<2>{});
                } else {
                    done();
                }
                turn(a1, a2, 1);
                handoff();
                if (sum) sum_p(IC<2>{}, IC<4>{});
                done();
                store(dst);
                __syncwarp();
                asm volatile("{\n.reg .pred p;\nsetp.ne.b32 p, %1, 0;\n@p mbarrier.arrive.shared::cta.b64 _, [%0];\n}"
                             ::"r"(bar_pub + 4 + 4 * k), "r"(lane ? 0 : (0x2a >> k) & 1) : "memory");
            }
            turn(q, p, 0);
            handoff();
            mb = padd(g_frag, (qb * 64 + j) * WREG + 3 * 4096 + tid_ * 16);
            mb4 = padd(mb, 4096 + ((cw >> 1) - cw) * 512 + (cw & 1) * 8);
            xs = sb + (tid_ & 15) * XP + (tid_ & 16) + cw * 32;
            ta = sb + (cw * 8 + (tid_ & 3)) * 8;
#pragma unroll
            for (int k = 0; k < 9; k++) {
                gw[k] = lds64(ta + SM_T + (k < 8 ? (k >> 1) * 64 + (k & 1) * 4 : 256 - cw * 4) * 8);
                if (!(tid_ & 4)) gw[k].y = 0x3f803f80u;
            }
            mbar_wait(bar_g, 0);
            done();
            load_wf(IC<0>{}, IC<WF0>{});
            turn(a1, a2, 1);
            if (w == 0) handoff();
            done();
            store(dst);
            mbar_wait(bar_full, 0);
            rows_load(x1, xs, cw);
            if (w == 0) bar_sync(5, 256); else bar_arrive(5, 256);
        }
        DBG_T(81);
        DBG_G(122);

        {
        const int tid = tid_, lane = tid & 31;
        const int g8 = lane >> 2, qd = lane & 3, l16 = lane & 15;
        uint32_t h2[18], gb[9], k1, k2;
        float4* rec = reinterpret_cast<float4*>(red + 128);
        const uint2* candp = reinterpret_cast<const uint2*>(padd(g_cand, ((qb >> 1) * NCTA + (tid >> 1)) * 32 + (tid & 1) * 8));
        uint2 cd;
        auto stage_out = [&]() {
#pragma unroll
            for (int k = 0; k < 9; k++) {
                x1[2 * k] = badd2(x1[2 * k], bmul2(gb[k], h2[2 * k]));
                x1[2 * k + 1] = badd2(x1[2 * k + 1], bmul2(gb[k], h2[2 * k + 1]));
            }
#pragma unroll
            for (int ch = 0; ch < 4; ch++) stsm_x4(xs + ch * 256, x1[4 * ch], x1[4 * ch + 1], x1[4 * ch + 2], x1[4 * ch + 3]);
            asm volatile("stmatrix.sync.aligned.m8n8.x2.shared.b16 [%0], {%1, %2};" ::"r"(xs + 1024 - cw * 16), "r"(x1[16]), "r"(x1[17]) : "memory");
        };
        {
            uint32_t it = 0, miss;
            mbar_wait(bar_full + 8, 0);
#pragma unroll
            for (int src = 0; src < 8; src++) v2[src] = lds128(pa + SLOT + src * 2048);
            sum8(at + 8, v2);
            float st[12];
#pragma unroll
            for (int i = 0; i < 12; i++) st[i] = 0.f;
            auto add_pair = [&](int k) {
                x1[2 * k] = badd2(x1[2 * k], bmul2(gw[k].x, at[2 * k]));
                x1[2 * k + 1] = badd2(x1[2 * k + 1], bmul2(gw[k].x, at[2 * k + 1]));
                stats_add(st, x1[2 * k], x1[2 * k + 1], gw[k].y);
            };
#pragma unroll
            for (int k = 0; k < 6; k++) add_pair(k);
            mbar_wait(bar_full + 16, 0);
#pragma unroll
            for (int src = 0; src < 8; src++) v3[src] = lds128(pa + 2 * SLOT + src * 2048);
            miss = __vimax3_u32(__vimax3_u32(v3[0].x, v3[0].z, v3[1].x), __vimax3_u32(v3[1].z, v3[2].x, v3[2].z), __vimax3_u32(v3[3].x, v3[3].z, v3[4].x));
            miss = __vimax3_u32(miss, __vimax3_u32(v3[4].z, v3[5].x, v3[5].z), max(__vimax3_u32(v3[6].x, v3[6].z, v3[7].x), v3[7].z));
            if (__any_sync(0xffffffffu, miss == ~0u))
#pragma unroll 1
            do {
                miss = 0;
#pragma unroll
                for (int src = 0; src < 8; src++) reload16(v3[src], mb + (size_t)src * 8 * WREG, miss);
            } while (__any_sync(0xffffffffu, miss) && ++it < SPIN / 16);
            if (lane < 4) mbar_arrive_cluster(rel_base + 8 * (1 + (lane >> 1)));
            sum8(at + 12, v3);
            add_pair(6); add_pair(7);
            load_wf(IC<WF0>{}, IC<WF1>{});
            uint2 cs[9];
#pragma unroll
            for (int k = 0; k < 9; k++) cs[k] = lds64(ta + SM_TC + (k < 8 ? (k >> 1) * 64 + (k & 1) * 4 : 256 - cw * 4) * 8);
            mbar_wait(bar_pre, 0);
            mbar_wait(bar_full + 24, 0);
#pragma unroll
            for (int src = 0; src < 8; src++) u4[src] = lds64(sb + 3 * SLOT + src * 2048 + (cw >> 1) * 512 + lane * 16 + (cw & 1) * 8);
            miss = __vimax3_u32(__vimax3_u32(u4[0].x, u4[1].x, u4[2].x), __vimax3_u32(u4[3].x, u4[4].x, u4[5].x), max(u4[6].x, u4[7].x));
            if (__any_sync(0xffffffffu, miss == ~0u))
#pragma unroll 1
            do {
                miss = 0;
#pragma unroll
                for (int src = 0; src < 8; src++) reload8(u4[src], mb4 + (size_t)src * 8 * WREG, miss);
            } while (__any_sync(0xffffffffu, miss) && ++it < SPIN / 16);
            float d[8] = {0.f, 0.f, 0.f, 0.f, 0.f, 0.f, 0.f, 0.f};
#pragma unroll
            for (int i = 0; i < 4; i++) mma16816(d + 4 * (i & 1), u4[2 * i].x, u4[2 * i].y, u4[2 * i + 1].x, u4[2 * i + 1].y, eye, eye);
            at[16] = pack_bf16(d[0] + d[4], d[1] + d[5]); at[17] = pack_bf16(d[2] + d[6], d[3] + d[7]);
            add_pair(8);
            DBG_G(123);
            const float2 ws = *reinterpret_cast<const float2*>(smem_raw + SM_TS);
            uint4* cdst = padd(g_cand, (tid * NCTA + rg) * 32);
            uint32_t mean2;
            float dot;
            const float rsd = rows_stats(st, rec, cw, lane, mean2, dot);
            const uint32_t b = __float_as_uint(fmaf(fmaf(-bf_lo(mean2), ws.x, dot), rsd, ws.y));
            const uint32_t key = (((b & 0x80000000u) ? ~b : (b | 0x80000000u)) | 2047u) - (rg * 16 + l16);
            top2(key, k1, k2);
            if (tid < CREP) st_relaxed(cdst, k1, tag, k2, tag);
            cd = ld_relaxed64(candp);
            rows_normalise(h2, x1, mean2, rsd, lane, [&]() {
#pragma unroll
                for (int k = 0; k < 9; k++) gb[k] = lds32(sb + SM_TG + (cw * 8 + qd + (k < 8 ? (k >> 1) * 64 + (k & 1) * 4 : 256 - cw * 4)) * 4);
                load_wf(IC<WF1>{}, IC<WF2>{});
            });
#pragma unroll
            for (int k = 0; k < 18; k++) h2[k] = badd2(bmul2(h2[k], cs[k >> 1].x), cs[k >> 1].y);
            const uint32_t r1 = ~k1 & 15, r2 = ~k2 & 15;
            uint32_t todo = ((r1 & 7) == g8) | ((r2 & 7) == g8) << 1;
#pragma unroll 1
            while (todo) {
                const bool second = !(todo & 1), hi = (second ? r2 : r1) & 8;
                uint4* dst = padd(g_rows, ((rg * 2 + second) * RSLOT + cw * 24 + qd) * 16);
                uint32_t r[18];
#pragma unroll
                for (int k = 0; k < 9; k++) { r[k] = hi ? h2[2 * k + 1] : h2[2 * k]; r[9 + k] = hi ? x1[2 * k + 1] : x1[2 * k]; }
                fence_regs(r);
                st_relaxed(dst, r[0], r[1], r[2], r[3]);
                st_relaxed(dst + 8, r[4], r[5], r[6], r[7]);
                st_relaxed64(reinterpret_cast<uint2*>(padd(dst, 256 - qd * 8)), r[8], r[17]);
                st_relaxed(dst + 4, r[9], r[10], r[11], r[12]);
                st_relaxed(dst + 12, r[13], r[14], r[15], r[16]);
                todo &= todo - 1;
            }
            __syncwarp();

            stage_out();
        }
        DBG_G(110);
        float4* part = reinterpret_cast<float4*>(smem_raw + 3 * SLOT + UNIT + 8192);
        bf16* act = reinterpret_cast<bf16*>(smem_raw + 3 * SLOT + UNIT + 4096);
        {
            uint32_t it = 0;
            const bool own = (tid >> 1) == rg;
            const uint32_t ks = sb + 3 * SLOT + UNIT + 5120;
#pragma unroll 1
            while (__any_sync(0xffffffffu, cd.y != tag && !own) && ++it < SPIN / 16)
                asm volatile("{\n.reg .pred p;\n.reg .b64 u;\nsetp.ne.u32 p, %1, %3;\nmov.b64 u, {%0, %1};\n"
                             "@p ld.relaxed.gpu.global.b64 u, [%2];\nmov.b64 {%0, %1}, u;\n}" : "+r"(cd.x), "+r"(cd.y) : "l"(candp), "r"(tag) : "memory");
            asm volatile("st.shared.u32 [%0], %1;" ::"r"(ks + tid * 4), "r"(own ? (tid & 1) ? k2 : k1 : cd.x) : "memory");
            bar_sync(3, 256);
            DBG_G(111);
            const uint4 a = lds128(ks + lane * 16), b = lds128(ks + 512 + lane * 16);
            const uint32_t a1 = max(a.x, a.z), a2 = __vimax3_u32(min(a.x, a.z), a.y, a.w);
            const uint32_t b1 = max(b.x, b.z), b2 = __vimax3_u32(min(b.x, b.z), b.y, b.w);
            const uint32_t c1 = max(a1, b1), c2 = __vimax3_u32(min(a1, b1), a2, b2);
            k1 = __reduce_max_sync(0xffffffffu, c1);
            k2 = __reduce_max_sync(0xffffffffu, c1 == k1 ? c2 : c1);
        }
        const int sel0 = ~k1 & 2047, sel1 = ~k2 & 2047;
        const uint32_t slot0 = (sel0 >> 4) * 2, slot1 = (sel1 >> 4) * 2 + ((sel0 ^ sel1) < 16);
        uint4 da[13];
        {
            const uint4* hp = padd(g_rows, (((g8 & 1) ? slot1 : slot0) * RSLOT + cw * 24 + qd) * 16);
            const uint2* hp2 = reinterpret_cast<const uint2*>(padd(hp, 256 - qd * 8));
            uint4 hv[2] = {ld_relaxed2(hp), ld_relaxed2(hp + 8)};
            uint2 hw = ld_relaxed64(hp2);
            if (tid == 255) {
                reinterpret_cast<int2*>(red)[8] = make_int2(sel0, sel1);
                mbar_arrive(bar_out);
            }
            load_wf(IC<WF2>{}, IC<23>{});
            mbar_wait(bar_full + 8, 1);
            mbar_wait(bar_full + 16, 1);
            auto load_d = [&](auto lo, auto hi) {
                const int r = (lane & 7) + (lane & 16) / 2;
                const uint32_t d0 = sb + SLOT + r * XP + cw * 144 + (lane & 8) * 2, d1 = d0 + (r < 2 ? 16 * XP : SLOT - 2 * XP);
                const uint32_t d2 = sb + 2 * SLOT + (14 + (lane & 3)) * XP + cw * 144 + (lane >> 3) * 16;
#pragma unroll
                for (int i = lo.value; i < hi.value; i++) da[i] = ldsm4t(i < 10 ? ((i & 1) ? d1 : d0) + (i >> 1) * 32 : d2 + (i - 10) * 64);
            };
            load_d(IC<0>{}, IC<DL>{});
            uint32_t it = 0, miss;
            float f0 = 1.f, f1 = 1.f;
            hold(f0, f1);
            if (__any_sync(0xffffffffu, max(__vimax3_u32(__vimax3_u32(__float_as_uint(f0), hv[0].x, hv[0].z), hv[1].x, hv[1].z), hw.x) == ~0u))
#pragma unroll 1
            do {
                miss = 0;
                reload16(hv[0], hp, miss);
                reload16(hv[1], hp + 8, miss);
                reload8(hw, hp2, miss);
            } while (__any_sync(0xffffffffu, miss) && ++it < SPIN / 16);
            DBG_G(112);
            float acc[20];
#pragma unroll
            for (int i = 0; i < 20; i++) acc[i] = 0.f;
#pragma unroll
            for (int i = 0; i < 5; i++) mma1688(acc + 4 * i, (i & 1) ? wf[20 + i / 2].z : wf[20 + i / 2].x, (i & 1) ? wf[20 + i / 2].w : wf[20 + i / 2].y, hw.x);
#pragma unroll
            for (int i = 0; i < 20; i++)
                mma16816(acc + 4 * (i % 5), wf[i].x, wf[i].y, wf[i].z, wf[i].w, (i / 5 & 1) ? hv[i / 10].z : hv[i / 10].x, (i / 5 & 1) ? hv[i / 10].w : hv[i / 10].y);
            if (qd == 0) {
#pragma unroll
                for (int i = 0; i < 5; i++) part[cw * 40 + i * 8 + g8] = make_float4(acc[4 * i], acc[4 * i + 1], acc[4 * i + 2], acc[4 * i + 3]);
            }
            load_d(IC<DL>{}, IC<13>{});
        }
        {
            uint2* dst = padd(g_ypart, ((cw * 9 * NCTA + bx) * 8 + g8) * 8);
            bar_sync(3, 256);
            if (cw < 5) {
                const float* pp = reinterpret_cast<const float*>(part) + ((bx & 1) << 4) + tid;
                const float g = rbf(((pp[0] + pp[160]) + (pp[320] + pp[480])) + ((pp[640] + pp[800]) + (pp[960] + pp[1120])));
                const float v = rbf(g * sigmoidf_(g)) * __shfl_down_sync(0xffffffffu, g, 2);
                if (!(tid & 2)) act[(tid & 1) * 56 + (tid >> 2)] = __float2bfloat16_rn(tid < 144 ? v : 0.f);
            }
            bar_sync(3, 256);
            DBG_G(113);
            const uint32_t ap = sb + 3 * SLOT + UNIT + 4096 + (lane & 1) * 112 + (lane >> 3) * 16;
            const uint4 b0 = ldsm4(ap);
            const uint32_t b1 = lds32(sb + 3 * SLOT + UNIT + 4096 + (g8 & 1) * 112 + 64 + qd * 4);
            float y[20];
#pragma unroll
            for (int i = 0; i < 20; i++) y[i] = 0.f;
#pragma unroll
            for (int i = 0; i < 5; i++) {
                mma16816(y + 4 * i, da[2 * i].x, da[2 * i].y, da[2 * i].z, da[2 * i].w, b0.x, b0.y);
                mma16816(y + 4 * i, da[2 * i + 1].x, da[2 * i + 1].y, da[2 * i + 1].z, da[2 * i + 1].w, b0.z, b0.w);
                mma1688(y + 4 * i, (i & 1) ? da[10 + i / 2].z : da[10 + i / 2].x, (i & 1) ? da[10 + i / 2].w : da[10 + i / 2].y, b1);
            }
            if (qd == 0) {
#pragma unroll
                for (int i = 0; i < 9; i++)
                    asm volatile("st.relaxed.gpu.global.v2.f32 [%0], {%1, %2};" ::"l"(dst + i * (NCTA * 8)), "f"(y[2 * i]), "f"(y[2 * i + 1]) : "memory");
            }
        }
        DBG_G(114);
        if (bx < 72) {
            const int G = bx, tok = g8 & 1, cp = G * 4 + qd;
            const uint2* src = padd(g_ypart, (bx * NCTA * 8 + tid) * 8);
            const uint8_t* hsrc = reinterpret_cast<const uint8_t*>(padd(g_rows, (tok ? slot1 : slot0) * (RSLOT * 16) +
                (G < 64 ? (G >> 1 & 7) * 384 + (G >> 5) * 128 + qd * 16 + (G >> 1 & 8) + (G & 1) * 4 : (G - 64) * 384 + 256 + qd * 8)));
            const uint8_t* xsrc = hsrc + (G < 64 ? 64 : 4);
            uint32_t* dst = padd(reinterpret_cast<uint32_t*>(args.out), (tok ? sel1 : sel0) * (D_ * 2) + cp * 4);
            const uint32_t gb = reinterpret_cast<const uint32_t*>(smem_raw + SM_TG)[cp];
            const uint32_t ksel = ((tok ? k2 : k1) & ~2047u) | 1024u;
            const float sg = sigmoidf_(rbf(__uint_as_float((ksel & 0x80000000u) ? (ksel & 0x7fffffffu) : ~ksel)));
            uint2 v[4];
            uint32_t hv = 0, xv = 0, it = 0, miss;
            if (cw == 0) { hv = ld_relaxed32(hsrc); xv = ld_relaxed32(xsrc); }
#pragma unroll
            for (int i = 0; i < 4; i++) v[i] = make_uint2(~0u, 0);
#pragma unroll 1
            do {
#pragma unroll
                for (int i = 0; i < 4; i++) reload8(v[i], src + i * 256, miss);
            } while (__any_sync(0xffffffffu, max(__vimax3_u32(v[0].x, v[1].x, v[2].x), v[3].x) == ~0u) && ++it < SPIN / 16);
#pragma unroll 1
            while (max(hv, xv) == ~0u && ++it < SPIN / 16) { hv = ld_relaxed32(hsrc); xv = ld_relaxed32(xsrc); }
            __syncwarp();
            float y0 = (__uint_as_float(v[0].x) + __uint_as_float(v[1].x)) + (__uint_as_float(v[2].x) + __uint_as_float(v[3].x));
            float y1 = (__uint_as_float(v[0].y) + __uint_as_float(v[1].y)) + (__uint_as_float(v[2].y) + __uint_as_float(v[3].y));
            y0 += __shfl_xor_sync(0xffffffffu, y0, 8); y1 += __shfl_xor_sync(0xffffffffu, y1, 8);
            y0 += __shfl_xor_sync(0xffffffffu, y0, 16); y1 += __shfl_xor_sync(0xffffffffu, y1, 16);
            if (lane < 8) reinterpret_cast<float2*>(rec)[cw * 8 + lane] = make_float2(y0, y1);
            bar_sync(3, 256);
            if (cw == 0) {
                const float4 t0_ = rec[(lane >> 3) * 4 + qd], t1_ = rec[16 + (lane >> 3) * 4 + qd];
                y0 = tok ? t0_.y + t1_.y : t0_.x + t1_.x; y1 = tok ? t0_.w + t1_.w : t0_.z + t1_.z;
                y0 += __shfl_xor_sync(0xffffffffu, y0, 8); y1 += __shfl_xor_sync(0xffffffffu, y1, 8);
                y0 += __shfl_xor_sync(0xffffffffu, y0, 16); y1 += __shfl_xor_sync(0xffffffffu, y1, 16);
                const uint32_t y2 = bmul2(pack_bf16(y0, y1), pack_bf16(sg, sg));
                if (lane < 8) *dst = badd2(xv, bmul2(gb, badd2(hv, y2)));
            }
        }
        }
        DBG_T(88);
        DBG_G(121);
    }
}

typedef CUresult (*EncodeFn)(CUtensorMap*, CUtensorMapDataType, cuuint32_t, void*, const cuuint64_t*, const cuuint64_t*,
                             const cuuint32_t*, const cuuint32_t*, CUtensorMapInterleave, CUtensorMapSwizzle,
                             CUtensorMapL2promotion, CUtensorMapFloatOOBfill);

static void make_map(EncodeFn enc, CUtensorMap* m, const void* ptr, int rank, const cuuint64_t* dims,
                     const cuuint64_t* strides, const cuuint32_t* box, CUtensorMapSwizzle sw = CU_TENSOR_MAP_SWIZZLE_128B,
                     CUtensorMapDataType dt = CU_TENSOR_MAP_DATA_TYPE_BFLOAT16) {
    const cuuint32_t es[3] = {1, 1, 1};
    enc(m, dt, rank, const_cast<void*>(ptr), dims, strides, box, es,
        CU_TENSOR_MAP_INTERLEAVE_NONE, sw, CU_TENSOR_MAP_L2_PROMOTION_L2_128B,
        CU_TENSOR_MAP_FLOAT_OOB_FILL_NONE);
}

extern "C" void kernel_launch(void* const* d_in, const int* in_sizes, int n_in, void* d_out, int out_size) {
    const bf16* x = (const bf16*)d_in[0];
    const bf16* kc = (const bf16*)d_in[1];
    const bf16* vc = (const bf16*)d_in[2];
    const bf16* wq = (const bf16*)d_in[3];
    const bf16* wo = (const bf16*)d_in[4];
    const bf16* w_r = (const bf16*)d_in[6];
    const bf16* w_gate = (const bf16*)d_in[7];
    const bf16* w_up = (const bf16*)d_in[8];
    const bf16* w_down = (const bf16*)d_in[9];
    const bf16* cvec = (const bf16*)d_in[10];
    const bf16* w_mod = (const bf16*)d_in[11];
    bf16* out = (bf16*)d_out;

    void* fn = nullptr;
    cudaDriverEntryPointQueryResult qr;
    cudaGetDriverEntryPoint("cuTensorMapEncodeTiled", &fn, cudaEnableDefault, &qr);
    EncodeFn enc = (EncodeFn)fn;
    void* p_s;
    cudaGetSymbolAddress(&p_s, g_s);

    CUtensorMap tm_wq, tm_k, tm_v, tm_wo, tm_p, tm_x, tm_d, tm_g, tm_u;
    { cuuint64_t d[2] = {QD, D_}, s[1] = {QD * 2}; cuuint32_t b[2] = {64, 128}; make_map(enc, &tm_wq, wq, 2, d, s, b); }
    { cuuint64_t d[2] = {DH, HKV * S_}, s[1] = {DH * 2}; cuuint32_t b[2] = {64, 128};
      make_map(enc, &tm_k, kc, 2, d, s, b); make_map(enc, &tm_v, vc, 2, d, s, b); }
    { cuuint64_t d[2] = {D_, QD}, s[1] = {D_ * 2}; cuuint32_t b[2] = {64, 128}; make_map(enc, &tm_wo, wo, 2, d, s, b); }
    { cuuint64_t d[3] = {256, 160, NCTA}, s[2] = {1024, 8 * WREG}; cuuint32_t b[3] = {256, 2, 8};
      make_map(enc, &tm_p, ((Scratch*)p_s)->frag, 3, d, s, b, CU_TENSOR_MAP_SWIZZLE_NONE, CU_TENSOR_MAP_DATA_TYPE_UINT32); }
    { cuuint64_t d[2] = {D_ / 4, S_}, s[1] = {D_ * 2}; cuuint32_t b[2] = {XP / 8, 16};
      make_map(enc, &tm_x, x, 2, d, s, b, CU_TENSOR_MAP_SWIZZLE_NONE, CU_TENSOR_MAP_DATA_TYPE_UINT64); }
    { cuuint64_t d[2] = {D_ / 4, F_}, s[1] = {D_ * 2}; cuuint32_t b[2] = {XP / 8, 18};
      make_map(enc, &tm_d, w_down, 2, d, s, b, CU_TENSOR_MAP_SWIZZLE_NONE, CU_TENSOR_MAP_DATA_TYPE_UINT64); }
    { cuuint64_t d[2] = {F_, D_}, s[1] = {F_ * 2}; cuuint32_t b[2] = {40, 24};
      make_map(enc, &tm_g, w_gate, 2, d, s, b, CU_TENSOR_MAP_SWIZZLE_NONE); make_map(enc, &tm_u, w_up, 2, d, s, b, CU_TENSOR_MAP_SWIZZLE_NONE); }

    cudaFuncSetAttribute(fused_kernel<true>, cudaFuncAttributeMaxDynamicSharedMemorySize, SM_TOTAL);
    cudaFuncSetAttribute(fused_kernel<false>, cudaFuncAttributeMaxDynamicSharedMemorySize, SM_TOTAL);
    cudaLaunchConfig_t cfg = {};
    cfg.gridDim = NCTA + 4; cfg.blockDim = 384; cfg.dynamicSmemBytes = SM_TOTAL;
    cudaLaunchAttribute at;
    at.id = cudaLaunchAttributeClusterDimension; at.val.clusterDim.x = 2; at.val.clusterDim.y = 1; at.val.clusterDim.z = 1;
    cfg.attrs = &at; cfg.numAttrs = 1;
    int ncl = 0;
    if (cudaOccupancyMaxActiveClusters(&ncl, fused_kernel<true>, &cfg) != cudaSuccess) { ncl = 0; cudaGetLastError(); }
    Args args{w_mod, cvec, (Scratch*)p_s, desc_lo(0, UNIT) | (0x40000040ull << 32), out, x, kc, vc, wq, wo, w_r, w_down};
    if (USE_SPARE && ncl >= NCTA / 2 + 2)
        fused_kernel<true><<<NCTA + 4, 384, SM_TOTAL>>>(args, tm_wq, tm_k, tm_v, tm_wo, tm_p, tm_x, tm_d, tm_g, tm_u);
    else
        fused_kernel<false><<<NCTA, 384, SM_TOTAL>>>(args, tm_wq, tm_k, tm_v, tm_wo, tm_p, tm_x, tm_d, tm_g, tm_u);
}
```
